```python
import torch

def _softmax(x, axis=-1):
    return torch.softmax(x, dim=axis)
def _gelu(x):
    return torch.nn.functional.gelu(x, approximate="tanh")
def _silu(x):
    return torch.nn.functional.silu(x)
def _sigmoid(x):
    return torch.sigmoid(x)
def _layernorm(x, axis=-1, eps=1e-5):
    m = x.mean(dim=axis, keepdim=True)
    v = x.var(dim=axis, keepdim=True, unbiased=False)
    return (x - m) / torch.sqrt(v + eps)
def _scatter_add(tgt, idx, src, axis=0):
    return tgt.clone().index_add_(axis, idx, src)
def _segment_sum(src, seg, n):
    out = torch.zeros((n,) + src.shape[1:], dtype=src.dtype)
    return out.index_add_(0, seg, src)
def _pad(x, pw):
    flat = tuple(v for pair in reversed(pw) for v in pair)
    return torch.nn.functional.pad(x, flat)

kernel_name = 'sequential_preLN__linear_kernel_hedgehog__glu_gated_bilinear__prompt'

def setup_inputs():

    _w = (lambda a: (lambda t: t.to(torch.bfloat16) if t.is_floating_point() else t)(torch.as_tensor(a)))
    def _A_setup():
        B, S, D, H = 1, 2048, 512, 32
        Dh = D // H
        return {
            "x": _w((lambda *s: torch.randn(*s, dtype=torch.bfloat16) * 0.05)(B, S, D)),
            "wqkv": _w((lambda *s: torch.randn(*s, dtype=torch.bfloat16) * 0.2)(D, 3 * D)),
            "w_phi": _w((lambda *s: torch.randn(*s, dtype=torch.bfloat16) * 0.2)(H, Dh, Dh) * (Dh ** -0.5)),
            "wo": _w((lambda *s: torch.randn(*s, dtype=torch.bfloat16) * 0.05)(D, D)),
        }
    _A_in = _A_setup()

    def _B_setup():
        B, S, D, F = 1, 2048, 512, 1376
        return {
            "x": _w((lambda *s: torch.randn(*s, dtype=torch.bfloat16) * 0.05)(B, S, D)),
            "w_gate": _w((lambda *s: torch.randn(*s, dtype=torch.bfloat16) * 0.4)(D, F) * (D ** -0.5)),
            "w_up": _w((lambda *s: torch.randn(*s, dtype=torch.bfloat16) * 0.4)(D, F) * (D ** -0.5)),
            "w_down": _w((lambda *s: torch.randn(*s, dtype=torch.bfloat16) * 0.4)(F, D) * (F ** -0.5)),
        }
    _B_in = _B_setup()

    return {
        "A_x": _A_in["x"],
        "A_wqkv": _A_in["wqkv"],
        "A_w_phi": _A_in["w_phi"],
        "A_wo": _A_in["wo"],
        "B_x": _B_in["x"],
        "B_w_gate": _B_in["w_gate"],
        "B_w_up": _B_in["w_up"],
        "B_w_down": _B_in["w_down"],
    }

def reference(A_x, A_wqkv, A_w_phi, A_wo, B_x, B_w_gate, B_w_up, B_w_down):
    def _A_ref(x, wqkv, w_phi, wo):
        B, S, D = x.shape
        H = 32; Dh = D // H
        qkv = (lambda x, *d: x.permute(*d))((x @ wqkv).reshape(B, S, 3, H, Dh), 2, 0, 3, 1, 4)
        q, k, v = qkv[0], qkv[1], qkv[2]
        pq = torch.einsum("bhsd,hdf->bhsf", q, w_phi)
        pk = torch.einsum("bhsd,hdf->bhsf", k, w_phi)
        phi_q = torch.concatenate([_softmax(pq, axis=-1), _softmax(-pq, axis=-1)], axis=-1)
        phi_k = torch.concatenate([_softmax(pk, axis=-1), _softmax(-pk, axis=-1)], axis=-1)
        kv = torch.einsum("bhsf,bhsd->bhfd", phi_k, v)
        z  = torch.einsum("bhsf->bhf", phi_k)
        num = torch.einsum("bhqf,bhfd->bhqd", phi_q, kv)
        den = torch.einsum("bhqf,bhf->bhq", phi_q, z)[..., None] + 1e-6
        o = num / den
        return (lambda x, *d: x.permute(*d))(o, 0, 2, 1, 3).reshape(B, S, D) @ wo

    def _B_ref(x, w_gate, w_up, w_down):
        g = torch.einsum("bsd,df->bsf", x, w_gate)
        u = torch.einsum("bsd,df->bsf", x, w_up)
        h = g * u
        return torch.einsum("bsf,fd->bsd", h, w_down)

    x = A_x
    h = x + _A_ref(_layernorm(x, axis=-1), A_wqkv, A_w_phi, A_wo)
    h2 = h + _B_ref(_layernorm(h, axis=-1), B_w_gate, B_w_up, B_w_down)
    return h2
```

```cpp
#include <cuda_runtime.h>
#include <cuda_bf16.h>
#include <cuda.h>
#include <stdint.h>

namespace hk {

constexpr int SEQ = 2048, DM = 512, FF = 1376, FFP = 1408;
constexpr int NCTA = 128;
constexpr int NTHREADS = 384;
constexpr uint32_t SLOT = 16384;
constexpr uint32_t OFF_A = 0, OFF_B = 8 * SLOT, OFF_MISC = 14 * SLOT;
constexpr uint32_t BAR_FULLA = OFF_MISC + 0, BAR_EMPTYA = OFF_MISC + 64, BAR_FULLB = OFF_MISC + 128,
                   BAR_EMPTYB = OFF_MISC + 176, BAR_CS1 = OFF_MISC + 224, BAR_CS3 = OFF_MISC + 232,
                   BAR_PUB = OFF_MISC + 240;
constexpr uint32_t OFF_CS1 = OFF_MISC + 384, OFF_CS3 = OFF_CS1 + 768;
constexpr uint32_t SMEM_BYTES = OFF_CS3 + 1536;
constexpr int NB = 6;

constexpr int ACC_KV = 0, ACC_Z = 2048, ACC_CS1 = 2176, ACC_CS3 = 2368, ACC_SIZE = 2752;

__device__ __align__(1024) __nv_bfloat16 g_o[SEQ * DM];
__device__ __align__(1024) __nv_bfloat16 g_h[SEQ * DM];
__device__ __align__(1024) __nv_bfloat16 g_hh[SEQ * FFP];
__device__ __align__(128) float g_hstat[SEQ * 16];
__device__ __align__(128) float g_acc[8 * ACC_SIZE];
__device__ __align__(128) unsigned g_cnt[8 * 4 * 32];
__device__ __align__(128) unsigned g_flag[16 * 5 * 32];
__device__ unsigned g_epoch;

#define TL(i) do {} while (0)

struct Params {
    CUtensorMap tx, to, th, thh, twkv, twq, two, twg, twu, twd;
    const __nv_bfloat16 *wqkv, *wphi, *wo, *wg, *wu, *wd;
    __nv_bfloat16* out;
};

__device__ __forceinline__ uint32_t smem_u32(const void* p) { return (uint32_t)__cvta_generic_to_shared(p); }
__device__ __forceinline__ void mbar_init(uint32_t bar, uint32_t cnt) {
    asm volatile("mbarrier.init.shared::cta.b64 [%0], %1;" ::"r"(bar), "r"(cnt) : "memory");
}
__device__ __forceinline__ void mbar_expect_tx(uint32_t bar, uint32_t bytes) {
    asm volatile("mbarrier.arrive.expect_tx.shared::cta.b64 _, [%0], %1;" ::"r"(bar), "r"(bytes) : "memory");
}
__device__ __forceinline__ void mbar_arrive(uint32_t bar) {
    asm volatile("mbarrier.arrive.shared::cta.b64 _, [%0];" ::"r"(bar) : "memory");
}
__device__ __forceinline__ void mbar_arrive_if(uint32_t bar, bool pred) {
    asm volatile("{.reg .pred p; setp.ne.u32 p, %1, 0; @p mbarrier.arrive.shared::cta.b64 _, [%0];}" ::"r"(bar), "r"((uint32_t)pred) : "memory");
}
__device__ __forceinline__ bool mbar_try(uint32_t bar, uint32_t parity) {
    uint32_t ok;
    asm volatile("{.reg .pred p; mbarrier.try_wait.parity.shared::cta.b64 p, [%1], %2; selp.u32 %0,1,0,p;}"
                 : "=r"(ok) : "r"(bar), "r"(parity) : "memory");
    return ok;
}
__device__ __forceinline__ bool mbar_test(uint32_t bar, uint32_t parity) {
    uint32_t ok;
    asm volatile("{.reg .pred p; mbarrier.test_wait.parity.shared::cta.b64 p, [%1], %2; selp.u32 %0,1,0,p;}"
                 : "=r"(ok) : "r"(bar), "r"(parity) : "memory");
    return ok;
}
__device__ __forceinline__ void trap_if_gt(uint32_t v, uint32_t lim) {
    asm volatile("{.reg .pred p; setp.gt.u32 p, %0, %1; @p trap;}" ::"r"(v), "r"(lim));
}
__device__ __forceinline__ void mbar_wait(uint32_t bar, uint32_t parity) {
    asm volatile("{\n"
                 ".reg .pred P1, P2;\n"
                 ".reg .u32 c;\n"
                 "mov.u32 c, 0;\n"
                 "LAB_WAIT:\n"
                 "mbarrier.try_wait.parity.shared::cta.b64 P1, [%0], %1;\n"
                 "@P1 bra LAB_DONE;\n"
                 "add.u32 c, c, 1;\n"
                 "setp.gt.u32 P2, c, 4194304;\n"
                 "@P2 trap;\n"
                 "bra LAB_WAIT;\n"
                 "LAB_DONE:\n"
                 "}" ::"r"(bar), "r"(parity) : "memory");
}
__device__ __forceinline__ void tma2d(uint32_t dst, const CUtensorMap* tm, uint32_t bar, int c0, int c1) {
    asm volatile("cp.async.bulk.tensor.2d.shared::cluster.global.mbarrier::complete_tx::bytes [%0], [%1, {%3, %4}], [%2];"
                 ::"r"(dst), "l"(tm), "r"(bar), "r"(c0), "r"(c1) : "memory");
}
__device__ __forceinline__ void tma3d(uint32_t dst, const CUtensorMap* tm, uint32_t bar, int c0, int c1, int c2) {
    asm volatile("cp.async.bulk.tensor.3d.shared::cluster.global.mbarrier::complete_tx::bytes [%0], [%1, {%3, %4, %5}], [%2];"
                 ::"r"(dst), "l"(tm), "r"(bar), "r"(c0), "r"(c1), "r"(c2) : "memory");
}
__device__ __forceinline__ void prefetch_tmap(const CUtensorMap* tm) {
    asm volatile("prefetch.tensormap [%0];" ::"l"(tm) : "memory");
}
__device__ __forceinline__ void prefetch_l2(const void* p, uint32_t bytes) {
    asm volatile("cp.async.bulk.prefetch.L2.global [%0], %1;" ::"l"(p), "r"(bytes) : "memory");
}
__device__ __forceinline__ unsigned ld_acquire(const unsigned* p) {
    unsigned v; asm volatile("ld.acquire.gpu.global.u32 %0, [%1];" : "=r"(v) : "l"(p) : "memory"); return v;
}
__device__ __forceinline__ uint2 ld_acquire2(const unsigned* p) {
    unsigned long long v; asm volatile("ld.acquire.gpu.global.u64 %0, [%1];" : "=l"(v) : "l"(p) : "memory");
    return make_uint2((unsigned)v, (unsigned)(v >> 32));
}
__device__ __forceinline__ void st_relaxed(unsigned* p, unsigned v) {
    asm volatile("st.relaxed.gpu.global.u32 [%0], %1;" ::"l"(p), "r"(v) : "memory");
}
__device__ __forceinline__ void red_relaxed(unsigned* p, unsigned v) {
    asm volatile("red.relaxed.gpu.global.add.u32 [%0], %1;" ::"l"(p), "r"(v) : "memory");
}
__device__ __forceinline__ void fence_gpu() { asm volatile("fence.acq_rel.gpu;" ::: "memory"); }
__device__ __forceinline__ void fence_async_smem() { asm volatile("fence.proxy.async.shared::cta;" ::: "memory"); }
__device__ __forceinline__ void fence_async_global() { asm volatile("fence.proxy.async.global;" ::: "memory"); }
__device__ __forceinline__ void wait_count(const unsigned* p, unsigned target) {
    uint32_t it = 0;
    while ((int)(ld_acquire(p) - target) < 0) trap_if_gt(++it, 1u << 22);
}
__device__ __forceinline__ void red_f32(float* p, float a) {
    asm volatile("red.relaxed.gpu.global.add.f32 [%0], %1;" ::"l"(p), "f"(a) : "memory");
}
__device__ __forceinline__ void red_f32x2(float* p, float a, float b) {
    asm volatile("red.relaxed.gpu.global.add.v2.f32 [%0], {%1, %2};" ::"l"(p), "f"(a), "f"(b) : "memory");
}
__device__ __forceinline__ void red_f32x4(float* p, float a, float b, float c, float d) {
    asm volatile("red.relaxed.gpu.global.add.v4.f32 [%0], {%1, %2, %3, %4};" ::"l"(p), "f"(a), "f"(b), "f"(c), "f"(d) : "memory");
}
__device__ __forceinline__ float4 ld_l2_f4(const float* p) {
    float4 v;
    asm volatile("ld.relaxed.gpu.global.v4.f32 {%0,%1,%2,%3}, [%4];" : "=f"(v.x), "=f"(v.y), "=f"(v.z), "=f"(v.w) : "l"(p) : "memory");
    return v;
}
__device__ __forceinline__ float2 ld_l2_f2(const float* p) {
    float2 v;
    asm volatile("ld.relaxed.gpu.global.v2.f32 {%0,%1}, [%2];" : "=f"(v.x), "=f"(v.y) : "l"(p) : "memory");
    return v;
}
__device__ __forceinline__ float ld_l2_f(const float* p) {
    float v;
    asm volatile("ld.relaxed.gpu.global.f32 %0, [%1];" : "=f"(v) : "l"(p) : "memory");
    return v;
}
__device__ __forceinline__ uint4 ldg_nc(const void* p) {
    uint4 v;
    asm volatile("ld.global.nc.L1::no_allocate.v4.u32 {%0,%1,%2,%3}, [%4];" : "=r"(v.x), "=r"(v.y), "=r"(v.z), "=r"(v.w) : "l"(p));
    return v;
}
__device__ __forceinline__ void stg128(void* p, uint32_t a, uint32_t b, uint32_t c, uint32_t d) {
    asm volatile("st.global.v4.u32 [%0], {%1,%2,%3,%4};" ::"l"(p), "r"(a), "r"(b), "r"(c), "r"(d) : "memory");
}
__device__ __forceinline__ uint4 lds128(uint32_t a) {
    uint4 v;
    asm volatile("ld.shared.v4.u32 {%0,%1,%2,%3}, [%4];" : "=r"(v.x), "=r"(v.y), "=r"(v.z), "=r"(v.w) : "r"(a) : "memory");
    return v;
}
__device__ __forceinline__ float2 lds_f2(uint32_t a) {
    float2 v;
    asm volatile("ld.shared.v2.f32 {%0,%1}, [%2];" : "=f"(v.x), "=f"(v.y) : "r"(a) : "memory");
    return v;
}
__device__ __forceinline__ void sts_f2(uint32_t a, float x, float y) {
    asm volatile("st.shared.v2.f32 [%0], {%1,%2};" ::"r"(a), "f"(x), "f"(y) : "memory");
}
__device__ __forceinline__ void sts64(uint32_t a, uint32_t x, uint32_t y) {
    asm volatile("st.shared.v2.u32 [%0], {%1,%2};" ::"r"(a), "r"(x), "r"(y) : "memory");
}
__device__ __forceinline__ void sts128(uint32_t a, uint32_t x, uint32_t y, uint32_t z, uint32_t w) {
    asm volatile("st.shared.v4.u32 [%0], {%1,%2,%3,%4};" ::"r"(a), "r"(x), "r"(y), "r"(z), "r"(w) : "memory");
}
__device__ __forceinline__ void stsm4(uint32_t a, uint32_t r0, uint32_t r1, uint32_t r2, uint32_t r3) {
    asm volatile("stmatrix.sync.aligned.m8n8.x4.shared.b16 [%0], {%1,%2,%3,%4};" ::"r"(a), "r"(r0), "r"(r1), "r"(r2), "r"(r3) : "memory");
}
__device__ __forceinline__ void ldsm4(uint32_t a, uint32_t& r0, uint32_t& r1, uint32_t& r2, uint32_t& r3) {
    asm volatile("ldmatrix.sync.aligned.m8n8.x4.shared.b16 {%0,%1,%2,%3}, [%4];" : "=r"(r0), "=r"(r1), "=r"(r2), "=r"(r3) : "r"(a) : "memory");
}
__device__ __forceinline__ void ldsm4t(uint32_t a, uint32_t& r0, uint32_t& r1, uint32_t& r2, uint32_t& r3) {
    asm volatile("ldmatrix.sync.aligned.m8n8.x4.trans.shared.b16 {%0,%1,%2,%3}, [%4];" : "=r"(r0), "=r"(r1), "=r"(r2), "=r"(r3) : "r"(a) : "memory");
}
__device__ __forceinline__ void mma16816(float* c, const uint32_t* a, uint32_t b0, uint32_t b1) {
    asm volatile("mma.sync.aligned.m16n8k16.row.col.f32.bf16.bf16.f32 {%0,%1,%2,%3}, {%4,%5,%6,%7}, {%8,%9}, {%0,%1,%2,%3};"
                 : "+f"(c[0]), "+f"(c[1]), "+f"(c[2]), "+f"(c[3])
                 : "r"(a[0]), "r"(a[1]), "r"(a[2]), "r"(a[3]), "r"(b0), "r"(b1));
}
__device__ __forceinline__ uint32_t pack_bf16(float lo, float hi) {
    uint32_t r; asm("cvt.rn.bf16x2.f32 %0, %1, %2;" : "=r"(r) : "f"(hi), "f"(lo)); return r;
}
__device__ __forceinline__ float bf_lo(uint32_t w) { return __uint_as_float(w << 16); }
__device__ __forceinline__ float bf_hi(uint32_t w) { return __uint_as_float(w & 0xffff0000u); }
__device__ __forceinline__ float ex2(float x) { float r; asm("ex2.approx.ftz.f32 %0, %1;" : "=f"(r) : "f"(x)); return r; }
__device__ __forceinline__ float rcp(float x) { float r; asm("rcp.approx.ftz.f32 %0, %1;" : "=f"(r) : "f"(x)); return r; }
__device__ __forceinline__ void bar_sync(int id, int n) { asm volatile("bar.sync %0, %1;" ::"r"(id), "r"(n) : "memory"); }

__device__ __forceinline__ uint32_t desc_lo(uint32_t addr) { return ((addr & 0x3FFFF) >> 4) | (512u << 16); }
#define DESC_HI "0x40000040"
__device__ __forceinline__ void wg_fence() { asm volatile("wgmma.fence.sync.aligned;" ::: "memory"); }
__device__ __forceinline__ void wg_commit() { asm volatile("wgmma.commit_group.sync.aligned;" ::: "memory"); }
template <int N> __device__ __forceinline__ void wg_wait() { asm volatile("wgmma.wait_group.sync.aligned %0;" ::"n"(N) : "memory"); }
template <int N> __device__ __forceinline__ void fence_acc(float* d) {
#pragma unroll
    for (int i = 0; i < N; i++) asm volatile("" : "+f"(d[i])::"memory");
}
#define R4(o) "+f"(d[o + 0]), "+f"(d[o + 1]), "+f"(d[o + 2]), "+f"(d[o + 3])
#define R8(o) R4(o), R4(o + 4)
__device__ __forceinline__ void wgmma_n128(float* d, uint32_t da, uint32_t db, int sc) {
    asm volatile("{.reg .pred p; .reg .b64 da, db; setp.ne.b32 p, %66, 0; mov.b64 da, {%64, " DESC_HI "}; mov.b64 db, {%65, " DESC_HI "};\n"
                 "wgmma.mma_async.sync.aligned.m64n128k16.f32.bf16.bf16 {%0,%1,%2,%3,%4,%5,%6,%7,%8,%9,%10,%11,%12,%13,%14,%15,%16,%17,%18,%19,%20,%21,%22,%23,%24,%25,%26,%27,%28,%29,%30,%31,"
                 "%32,%33,%34,%35,%36,%37,%38,%39,%40,%41,%42,%43,%44,%45,%46,%47,%48,%49,%50,%51,%52,%53,%54,%55,%56,%57,%58,%59,%60,%61,%62,%63}, da, db, p, 1, 1, 0, 1;}"
                 : R8(0), R8(8), R8(16), R8(24), R8(32), R8(40), R8(48), R8(56)
                 : "r"(da), "r"(db), "r"(sc));
}
__device__ __forceinline__ void wgmma_n64(float* d, uint32_t da, uint32_t db, int sc) {
    asm volatile("{.reg .pred p; .reg .b64 da, db; setp.ne.b32 p, %34, 0; mov.b64 da, {%32, " DESC_HI "}; mov.b64 db, {%33, " DESC_HI "};\n"
                 "wgmma.mma_async.sync.aligned.m64n64k16.f32.bf16.bf16 {%0,%1,%2,%3,%4,%5,%6,%7,%8,%9,%10,%11,%12,%13,%14,%15,%16,%17,%18,%19,%20,%21,%22,%23,%24,%25,%26,%27,%28,%29,%30,%31}, da, db, p, 1, 1, 0, 1;}"
                 : R8(0), R8(8), R8(16), R8(24)
                 : "r"(da), "r"(db), "r"(sc));
}
__device__ __forceinline__ void wgmma_n48(float* d, uint32_t da, uint32_t db, int sc) {
    asm volatile("{.reg .pred p; .reg .b64 da, db; setp.ne.b32 p, %26, 0; mov.b64 da, {%24, " DESC_HI "}; mov.b64 db, {%25, " DESC_HI "};\n"
                 "wgmma.mma_async.sync.aligned.m64n48k16.f32.bf16.bf16 {%0,%1,%2,%3,%4,%5,%6,%7,%8,%9,%10,%11,%12,%13,%14,%15,%16,%17,%18,%19,%20,%21,%22,%23}, da, db, p, 1, 1, 0, 1;}"
                 : R8(0), R8(8), R8(16)
                 : "r"(da), "r"(db), "r"(sc));
}
__device__ __forceinline__ void wgmma_n40_tt(float* d, uint32_t da, uint32_t db, int sc) {
    asm volatile("{.reg .pred p; .reg .b64 da, db; setp.ne.b32 p, %22, 0; mov.b64 da, {%20, " DESC_HI "}; mov.b64 db, {%21, " DESC_HI "};\n"
                 "wgmma.mma_async.sync.aligned.m64n40k16.f32.bf16.bf16 {%0,%1,%2,%3,%4,%5,%6,%7,%8,%9,%10,%11,%12,%13,%14,%15,%16,%17,%18,%19}, da, db, p, 1, 1, 1, 1;}"
                 : R8(0), R8(8), R4(16)
                 : "r"(da), "r"(db), "r"(sc));
}

__device__ __forceinline__ void quad_transpose(uint32_t r0, uint32_t r1, uint32_t r2, uint32_t r3, uint32_t* o, int q) {
    const bool odd = q & 1, hi = q & 2;
    uint32_t a = odd ? r0 : r1, b = odd ? r2 : r3;
    a = __shfl_xor_sync(0xffffffffu, a, 1);
    b = __shfl_xor_sync(0xffffffffu, b, 1);
    uint32_t s0 = odd ? a : r0, s1 = odd ? r1 : a, s2 = odd ? b : r2, s3 = odd ? r3 : b;
    uint32_t c = hi ? s0 : s2, d = hi ? s1 : s3;
    c = __shfl_xor_sync(0xffffffffu, c, 2);
    d = __shfl_xor_sync(0xffffffffu, d, 2);
    o[0] = hi ? c : s0; o[1] = hi ? d : s1; o[2] = hi ? s2 : c; o[3] = hi ? s3 : d;
}
__device__ __forceinline__ void store_rows64(__nv_bfloat16* p_row_g, int pitch, const uint32_t* lo, const uint32_t* hi, int q) {
    uint32_t o[4];
#pragma unroll
    for (int grp = 0; grp < 2; grp++) {
        quad_transpose(lo[4 * grp], lo[4 * grp + 1], lo[4 * grp + 2], lo[4 * grp + 3], o, q);
        stg128(p_row_g + grp * 32 + q * 8, o[0], o[1], o[2], o[3]);
        quad_transpose(hi[4 * grp], hi[4 * grp + 1], hi[4 * grp + 2], hi[4 * grp + 3], o, q);
        stg128(p_row_g + 8 * pitch + grp * 32 + q * 8, o[0], o[1], o[2], o[3]);
    }
}

__device__ __forceinline__ void feature_map(const uint32_t* a, const uint32_t* wb, uint32_t* plus, uint32_t* minus) {
    constexpr float L2E = 1.4426950408889634f;
    float p[8];
#pragma unroll
    for (int i = 0; i < 8; i++) p[i] = 0.f;
    mma16816(p, a, wb[0], wb[1]);
    mma16816(p + 4, a, wb[2], wb[3]);
    float mx0 = fmaxf(fmaxf(p[0], p[1]), fmaxf(p[4], p[5])), mn0 = fminf(fminf(p[0], p[1]), fminf(p[4], p[5]));
    float mx1 = fmaxf(fmaxf(p[2], p[3]), fmaxf(p[6], p[7])), mn1 = fminf(fminf(p[2], p[3]), fminf(p[6], p[7]));
#pragma unroll
    for (int s = 1; s <= 2; s <<= 1) {
        mx0 = fmaxf(mx0, __shfl_xor_sync(0xffffffffu, mx0, s));
        mn0 = fminf(mn0, __shfl_xor_sync(0xffffffffu, mn0, s));
        mx1 = fmaxf(mx1, __shfl_xor_sync(0xffffffffu, mx1, s));
        mn1 = fminf(mn1, __shfl_xor_sync(0xffffffffu, mn1, s));
    }
    float ep[8], em[8];
#pragma unroll
    for (int i = 0; i < 8; i++) {
        const bool r1 = (i & 2);
        ep[i] = ex2((p[i] - (r1 ? mx1 : mx0)) * L2E);
        em[i] = ex2(((r1 ? mn1 : mn0) - p[i]) * L2E);
    }
    float sp0 = (ep[0] + ep[1]) + (ep[4] + ep[5]), sp1 = (ep[2] + ep[3]) + (ep[6] + ep[7]);
    float sm0 = (em[0] + em[1]) + (em[4] + em[5]), sm1 = (em[2] + em[3]) + (em[6] + em[7]);
#pragma unroll
    for (int s = 1; s <= 2; s <<= 1) {
        sp0 += __shfl_xor_sync(0xffffffffu, sp0, s);
        sp1 += __shfl_xor_sync(0xffffffffu, sp1, s);
        sm0 += __shfl_xor_sync(0xffffffffu, sm0, s);
        sm1 += __shfl_xor_sync(0xffffffffu, sm1, s);
    }
    sp0 = rcp(sp0); sp1 = rcp(sp1); sm0 = rcp(sm0); sm1 = rcp(sm1);
    plus[0] = pack_bf16(ep[0] * sp0, ep[1] * sp0);
    plus[1] = pack_bf16(ep[2] * sp1, ep[3] * sp1);
    plus[2] = pack_bf16(ep[4] * sp0, ep[5] * sp0);
    plus[3] = pack_bf16(ep[6] * sp1, ep[7] * sp1);
    minus[0] = pack_bf16(em[0] * sm0, em[1] * sm0);
    minus[1] = pack_bf16(em[2] * sm1, em[3] * sm1);
    minus[2] = pack_bf16(em[4] * sm0, em[5] * sm0);
    minus[3] = pack_bf16(em[6] * sm1, em[7] * sm1);
}

__device__ __forceinline__ void ln_frag(const float* acc, uint32_t cs_addr, float rs0, float nm0, float rs1, float nm1, uint32_t* a) {
    const float2 c0 = lds_f2(cs_addr), c1 = lds_f2(cs_addr + 32);
    a[0] = pack_bf16(fmaf(acc[0], rs0, nm0 * c0.x), fmaf(acc[1], rs0, nm0 * c0.y));
    a[1] = pack_bf16(fmaf(acc[2], rs1, nm1 * c0.x), fmaf(acc[3], rs1, nm1 * c0.y));
    a[2] = pack_bf16(fmaf(acc[4], rs0, nm0 * c1.x), fmaf(acc[5], rs0, nm0 * c1.y));
    a[3] = pack_bf16(fmaf(acc[6], rs1, nm1 * c1.x), fmaf(acc[7], rs1, nm1 * c1.y));
}

__device__ __forceinline__ uint32_t hh_pair(const float* ag, const float* au, int t, int hf, uint32_t cs3q, float mean, float r2) {
    const float2 cg = lds_f2(cs3q + t * 32), cu = lds_f2(cs3q + 768 + t * 32);
    const float g0 = fmaf(-mean, cg.x, ag[4 * t + 2 * hf]), g1 = fmaf(-mean, cg.y, ag[4 * t + 2 * hf + 1]);
    const float u0 = fmaf(-mean, cu.x, au[4 * t + 2 * hf]), u1 = fmaf(-mean, cu.y, au[4 * t + 2 * hf + 1]);
    return pack_bf16(g0 * r2 * u0, g1 * r2 * u1);
}

struct Ring {
    int slot; uint32_t phase;
    __device__ __forceinline__ void adv() { if (++slot == NB) { slot = 0; phase ^= 1; } }
};

__global__ void __launch_bounds__(NTHREADS, 1) fused_kernel(const __grid_constant__ Params P) {
    extern __shared__ __align__(1024) uint8_t smem_raw[];
    const uint32_t sb = smem_u32(smem_raw);
    const int tid = threadIdx.x, lane = tid & 31;
    const int warp = __shfl_sync(0xffffffffu, tid >> 5, 0);
    const int m = blockIdx.x >> 3, j = blockIdx.x & 7;

    if (tid == 0) {
        trap_if_gt(sb & 1023, 0);
        TL(0);
        for (int i = 0; i < 8; i++) { mbar_init(sb + BAR_FULLA + 8 * i, 1); mbar_init(sb + BAR_EMPTYA + 8 * i, 8); }
        for (int i = 0; i < NB; i++) { mbar_init(sb + BAR_FULLB + 8 * i, 1); mbar_init(sb + BAR_EMPTYB + 8 * i, 8); }
        mbar_init(sb + BAR_CS1, 32); mbar_init(sb + BAR_CS3, 32);
        for (int i = 0; i < 12; i++) mbar_init(sb + BAR_PUB + 8 * i, 4);
        asm volatile("fence.mbarrier_init.release.cluster;" ::: "memory");
    }
    __syncthreads();

    float* const acc_j = g_acc + j * ACC_SIZE;
    unsigned* const cnt_j = g_cnt + j * 128;

    if (warp >= 8) {
        asm volatile("setmaxnreg.dec.sync.aligned.u32 72;");
        if (warp == 8) {
            if (lane == 0) {
                Ring r{0, 0};
#pragma unroll 1
                for (int i = 0; i < 52; i++) {
                    const uint32_t full = sb + BAR_FULLB + 8 * r.slot, dst = sb + OFF_B + r.slot * SLOT;
                    mbar_wait(sb + BAR_EMPTYB + 8 * r.slot, r.phase ^ 1);
                    mbar_expect_tx(full, SLOT);
                    if (i < 8) {
                        tma3d(dst, &P.twkv, full, 64 * j, 64 * i, 1);
                    } else if (i < 12) {
                        tma2d(dst, &P.twq, full, 64 * j, 128 * (i - 8));
                    } else if (i < 16) {
                        tma2d(dst, &P.two, full, 64 * j, 128 * (i - 12));
                    } else if (i < 40) {
                        const int c = (i - 16) >> 3, kt = (i - 16) & 7;
                        tma2d(dst, &P.twg, full, 176 * j + 64 * c, 64 * kt);
                        tma2d(dst + 8192, &P.twu, full, 176 * j + 64 * c, 64 * kt);
                    } else {
                        const int c = (i - 40) >> 2, jj = ((i - 40) & 3) * 2;
                        tma2d(dst, &P.twd, full, 64 * j, 176 * jj + 64 * c);
                        tma2d(dst + 8192, &P.twd, full, 64 * j, 176 * (jj + 1) + 64 * c);
                    }
                    r.adv();
                }
            }
        } else if (warp == 9) {
            if (lane < 8) {
                mbar_expect_tx(sb + BAR_FULLA + 8 * lane, SLOT);
                tma2d(sb + OFF_A + lane * SLOT, &P.tx, sb + BAR_FULLA + 8 * lane, 64 * lane, 128 * m);
            }
            __syncwarp();
            const unsigned epoch = ld_acquire(&g_epoch) + 1;
            {
                const int col = 176 * j + 8 * lane;
                const bool act = lane < 22 && col < FF;
#pragma unroll 1
                for (int mat = 0; mat < 2; mat++) {
                    float s[8];
#pragma unroll
                    for (int i = 0; i < 8; i++) s[i] = 0.f;
                    const __nv_bfloat16* src = (mat ? P.wu : P.wg) + (size_t)(32 * m) * FF + col;
                    if (act) {
#pragma unroll 1
                        for (int b = 0; b < 4; b++) {
                            uint4 v[8];
#pragma unroll
                            for (int i = 0; i < 8; i++) v[i] = ldg_nc(src + (size_t)(8 * b + i) * FF);
#pragma unroll
                            for (int i = 0; i < 8; i++) {
                                s[0] += bf_lo(v[i].x); s[1] += bf_hi(v[i].x); s[2] += bf_lo(v[i].y); s[3] += bf_hi(v[i].y);
                                s[4] += bf_lo(v[i].z); s[5] += bf_hi(v[i].z); s[6] += bf_lo(v[i].w); s[7] += bf_hi(v[i].w);
                            }
                        }
                    }
                    if (mat == 0) { if (lane == 0) wait_count(cnt_j + 0, epoch); __syncwarp(); }
                    if (act) {
                        float* dst = acc_j + ACC_CS3 + mat * 192 + 8 * lane;
                        red_f32x4(dst, s[0], s[1], s[2], s[3]);
                        red_f32x4(dst + 4, s[4], s[5], s[6], s[7]);
                    }
                }
                __syncwarp();
                if (lane == 0) { fence_gpu(); red_relaxed(cnt_j + 64, 1); }
                __syncwarp();
            }
            int r = (lane < 8) ? 1 : 6;
            uint32_t it = 0;
            while (__any_sync(0xffffffffu, r < 6)) {
                if (r < 6 && mbar_test(sb + BAR_EMPTYA + 8 * lane, (r - 1) & 1)) {
                    const uint2 f = ld_acquire2(g_flag + (m * 5 + (r - 1)) * 32 + 2 * lane);
                    if (f.x == epoch && f.y == epoch) {
                        fence_async_global();
                        const uint32_t full = sb + BAR_FULLA + 8 * lane;
                        mbar_expect_tx(full, SLOT);
                        const CUtensorMap* tm = r == 1 ? &P.to : (r == 2 ? &P.th : &P.thh);
                        const int c0 = r < 3 ? 64 * lane : 176 * lane + 64 * (r - 3);
                        tma2d(sb + OFF_A + lane * SLOT, tm, full, c0, 128 * m);
                        r++;
                    }
                }
                trap_if_gt(++it, 1u << 24);
            }
        } else {
            const int a = warp - 10;
            uint4 v[12];
            {
                const int c8 = lane & 7, r4 = lane >> 3;
                const __nv_bfloat16* src = P.wqkv + (size_t)(32 * m + 16 * a + r4) * (3 * DM) + 64 * j + 8 * c8;
#pragma unroll
                for (int i = 0; i < 4; i++)
#pragma unroll
                    for (int s = 0; s < 3; s++) v[i * 3 + s] = ldg_nc(src + (size_t)(4 * i) * (3 * DM) + s * DM);
            }
            const unsigned epoch = ld_acquire(&g_epoch) + 1;
            if (m == 0 && a == 0) {
                for (int i = lane; i < ACC_SIZE / 4; i += 32) stg128(acc_j + 4 * i, 0, 0, 0, 0);
                __syncwarp();
                if (lane == 0) { fence_gpu(); st_relaxed(cnt_j + 0, epoch); }
                __syncwarp();
            }
            if (a == 1 && lane == 0) {
                prefetch_l2(P.wo + (size_t)blockIdx.x * 2048, 4096);
                prefetch_l2(P.wd + (size_t)blockIdx.x * 5504, 11008);
            }
            {
                float s[24];
#pragma unroll
                for (int sct = 0; sct < 3; sct++) {
#pragma unroll
                    for (int e = 0; e < 8; e++) s[sct * 8 + e] = 0.f;
#pragma unroll
                    for (int i = 0; i < 4; i++) {
                        const uint4 w = v[i * 3 + sct];
                        s[sct * 8 + 0] += bf_lo(w.x); s[sct * 8 + 1] += bf_hi(w.x); s[sct * 8 + 2] += bf_lo(w.y); s[sct * 8 + 3] += bf_hi(w.y);
                        s[sct * 8 + 4] += bf_lo(w.z); s[sct * 8 + 5] += bf_hi(w.z); s[sct * 8 + 6] += bf_lo(w.w); s[sct * 8 + 7] += bf_hi(w.w);
                    }
                }
                const bool b4 = lane & 16, b3 = lane & 8;
                float t[12], u[6];
#pragma unroll
                for (int sct = 0; sct < 3; sct++)
#pragma unroll
                    for (int e = 0; e < 4; e++) {
                        const float send = b4 ? s[sct * 8 + e] : s[sct * 8 + 4 + e];
                        const float keep = b4 ? s[sct * 8 + 4 + e] : s[sct * 8 + e];
                        t[sct * 4 + e] = keep + __shfl_xor_sync(0xffffffffu, send, 16);
                    }
#pragma unroll
                for (int sct = 0; sct < 3; sct++)
#pragma unroll
                    for (int e = 0; e < 2; e++) {
                        const float send = b3 ? t[sct * 4 + e] : t[sct * 4 + 2 + e];
                        const float keep = b3 ? t[sct * 4 + 2 + e] : t[sct * 4 + e];
                        u[sct * 2 + e] = keep + __shfl_xor_sync(0xffffffffu, send, 8);
                    }
                if (lane == 0) wait_count(cnt_j + 0, epoch);
                __syncwarp();
                const int col = 8 * (lane & 7) + (b4 ? 4 : 0) + (b3 ? 2 : 0);
#pragma unroll
                for (int sct = 0; sct < 3; sct++) red_f32x2(acc_j + ACC_CS1 + sct * 64 + col, u[sct * 2], u[sct * 2 + 1]);
                __syncwarp();
                if (lane == 0) { fence_gpu(); red_relaxed(cnt_j + 32, 1); }
                __syncwarp();
            }
            if (a == 0) {
                if (lane == 0) wait_count(cnt_j + 32, epoch * 32);
                __syncwarp();
#pragma unroll
                for (int i = 0; i < 3; i++) {
                    const float2 c = ld_l2_f2(acc_j + ACC_CS1 + 64 * i + 2 * lane);
                    sts_f2(sb + OFF_CS1 + (64 * i + 2 * lane) * 4, c.x, c.y);
                }
                mbar_arrive(sb + BAR_CS1);
            }
#pragma unroll 1
            for (int ev = 0; ev < 6; ev++) {
                if (lane == 0) {
                    mbar_wait(sb + BAR_PUB + 8 * (a * 6 + ev), 0);
                    fence_gpu();
                    if (ev == 0) red_relaxed(cnt_j + 96, 1);
                    else st_relaxed(g_flag + (m * 5 + (ev - 1)) * 32 + 2 * j + a, epoch);
                }
                __syncwarp();
                if (ev == 2 && a == 0) {
                    if (lane == 0) wait_count(cnt_j + 64, epoch * 16);
                    __syncwarp();
#pragma unroll
                    for (int i = 0; i < 6; i++) {
                        const float2 c = ld_l2_f2(acc_j + ACC_CS3 + 64 * i + 2 * lane);
                        sts_f2(sb + OFF_CS3 + (64 * i + 2 * lane) * 4, c.x, c.y);
                    }
                    mbar_arrive(sb + BAR_CS3);
                }
            }
        }
    } else {
        asm volatile("setmaxnreg.inc.sync.aligned.u32 216;");
        const int w = warp >> 2, wv = warp & 3, g = lane >> 2, q = lane & 3;
        const int row_cta = 64 * w + 16 * wv;
        const size_t grow = (size_t)128 * m + row_cta + g;
        const uint32_t sa = sb + OFF_A + w * 8192;
        const uint32_t dA = desc_lo(sa), dB = desc_lo(sb + OFF_B);
        const uint32_t pub = sb + BAR_PUB + 48 * w;
        const bool l0 = lane == 0;
        Ring rg{0, 0};
        int prev = 0;

        uint32_t wb[16];
        {
            const unsigned short* wp = reinterpret_cast<const unsigned short*>(P.wphi) + (size_t)(4 * j) * 256;
#pragma unroll
            for (int hh = 0; hh < 4; hh++)
#pragma unroll
                for (int nt = 0; nt < 2; nt++)
#pragma unroll
                    for (int kh = 0; kh < 2; kh++) {
                        const unsigned short* p = wp + hh * 256 + (2 * q + 8 * kh) * 16 + 8 * nt + g;
                        wb[hh * 4 + nt * 2 + kh] = (uint32_t)__ldg(p) | ((uint32_t)__ldg(p + 16) << 16);
                    }
        }
        unsigned epoch = 0;
        if (tid == 0) epoch = ld_acquire(&g_epoch) + 1;

        float accKV[64], accQ[32];
        float st_sh = 0.f, st_s0 = 0.f, st_s1 = 0.f, st_q0 = 0.f, st_q1 = 0.f;
        {
            const int srow = 16 * wv + (lane >> 1);
            const uint32_t srow_addr = sa + srow * 128;
#pragma unroll 1
            for (int kt = 0; kt < 8; kt++) {
                mbar_wait(sb + BAR_FULLA + 8 * kt, 0);
                mbar_wait(sb + BAR_FULLB + 8 * rg.slot, rg.phase);
                if (kt == 0 && tid == 0) TL(1);
                wg_fence();
#pragma unroll
                for (int k = 0; k < 4; k++)
                    wgmma_n128(accKV, dA + ((kt * SLOT + k * 32) >> 4),
                               dB + ((rg.slot * SLOT + k * 2048) >> 4), (kt | k) != 0);
                wg_commit();
                if (kt == 0) st_sh = bf_lo(lds128(srow_addr + ((srow & 7) << 4)).x);
#pragma unroll
                for (int i = 0; i < 4; i++) {
                    const uint4 v = lds128(srow_addr + kt * SLOT + ((((lane & 1) * 4 + i) ^ (srow & 7)) << 4));
                    const uint32_t ww[4] = {v.x, v.y, v.z, v.w};
#pragma unroll
                    for (int e = 0; e < 4; e++) {
                        const float d0 = bf_lo(ww[e]) - st_sh, d1 = bf_hi(ww[e]) - st_sh;
                        st_s0 += d0; st_q0 = fmaf(d0, d0, st_q0);
                        st_s1 += d1; st_q1 = fmaf(d1, d1, st_q1);
                    }
                }
                wg_wait<1>();
                mbar_arrive_if(sb + BAR_EMPTYB + 8 * prev, l0 && kt > 0);
                prev = rg.slot; rg.adv();
            }
        }
        int qs0, qs1;
        {
            mbar_wait(sb + BAR_FULLB + 8 * rg.slot, rg.phase);
            qs0 = rg.slot; rg.adv();
            mbar_wait(sb + BAR_FULLB + 8 * rg.slot, rg.phase);
            qs1 = rg.slot; rg.adv();
            wg_fence();
#pragma unroll
            for (int k = 0; k < 16; k++)
                wgmma_n64(accQ, dA + (((k >> 2) * SLOT + (k & 3) * 32) >> 4),
                          dB + (((k < 8 ? qs0 : qs1) * SLOT + (k & 7) * 2048) >> 4), k != 0);
            wg_commit();
        }
        float rs0, nm0, rs1, nm1;
        {
            float s = st_s0 + st_s1, sq = st_q0 + st_q1;
            s += __shfl_xor_sync(0xffffffffu, s, 1);
            sq += __shfl_xor_sync(0xffffffffu, sq, 1);
            const float md = s * (1.f / DM);
            const float var = fmaxf(sq * (1.f / DM) - md * md, 0.f);
            const float rs = rsqrtf(var + 1e-5f);
            const float nm = -(st_sh + md) * rs;
            rs0 = __shfl_sync(0xffffffffu, rs, 2 * g); nm0 = __shfl_sync(0xffffffffu, nm, 2 * g);
            rs1 = __shfl_sync(0xffffffffu, rs, 2 * g + 16); nm1 = __shfl_sync(0xffffffffu, nm, 2 * g + 16);
        }
        uint32_t res_lo[8], res_hi[8];
        const int lrow = 16 * wv + ((lane >> 3) & 1) * 8 + (lane & 7);
        const uint32_t lrow_off = lrow * 128;
        wg_wait<1>();
        fence_acc<64>(accKV);
        if (lane == 0) mbar_arrive(sb + BAR_EMPTYB + 8 * prev);
        if (tid == 0) TL(2);
        mbar_wait(sb + BAR_CS1, 0);
        {
            uint32_t fp[16], fm[16], vf[16];
#pragma unroll
            for (int hh = 0; hh < 4; hh++) {
                uint32_t a[4];
                ln_frag(accKV + 8 * hh, sb + OFF_CS1 + (64 + 16 * hh + 2 * q) * 4, rs0, nm0, rs1, nm1, a);
                feature_map(a, wb + 4 * hh, fp + 4 * hh, fm + 4 * hh);
                ln_frag(accKV + 32 + 8 * hh, sb + OFF_CS1 + (128 + 16 * hh + 2 * q) * 4, rs0, nm0, rs1, nm1, vf + 4 * hh);
            }
#pragma unroll
            for (int b = 0; b < 4; b++)
                ldsm4(sa + j * SLOT + lrow_off + (((2 * b + (lane >> 4)) ^ (lrow & 7)) << 4),
                      res_lo[2 * b], res_hi[2 * b], res_lo[2 * b + 1], res_hi[2 * b + 1]);
            wg_wait<0>();
            if (lane == 0) { mbar_arrive(sb + BAR_EMPTYB + 8 * qs0); mbar_arrive(sb + BAR_EMPTYB + 8 * qs1); }
            const int ch = lane >> 4, sw = lrow & 7;
#pragma unroll
            for (int hh = 0; hh < 4; hh++) {
                const uint32_t pk = sa + (hh >> 1) * SLOT + lrow_off, vt = sa + (2 + (hh >> 1)) * SLOT + lrow_off;
                stsm4(pk + (((4 * (hh & 1) + ch) ^ sw) << 4), fp[4 * hh], fp[4 * hh + 1], fp[4 * hh + 2], fp[4 * hh + 3]);
                stsm4(pk + (((4 * (hh & 1) + 2 + ch) ^ sw) << 4), fm[4 * hh], fm[4 * hh + 1], fm[4 * hh + 2], fm[4 * hh + 3]);
                stsm4(vt + (((2 * (hh & 1) + ch) ^ sw) << 4), vf[4 * hh], vf[4 * hh + 1], vf[4 * hh + 2], vf[4 * hh + 3]);
            }
            stsm4(sa + (2 + ch) * SLOT + lrow_off + ((4 ^ sw) << 4), 0x3f803f80u, 0x3f803f80u, 0x3f803f80u, 0x3f803f80u);
            fence_async_smem();
            bar_sync(1, 256);
            float kvd[20];
            wg_fence();
#pragma unroll
            for (int k = 0; k < 8; k++)
                wgmma_n40_tt(kvd, desc_lo(sb + OFF_A) + ((w * SLOT + k * 2048) >> 4),
                             desc_lo(sb + OFF_A) + (((2 + w) * SLOT + k * 2048) >> 4), k != 0);
            wg_commit();
            mbar_wait(sb + BAR_FULLB + 8 * rg.slot, rg.phase);
            qs0 = rg.slot; rg.adv();
            mbar_wait(sb + BAR_FULLB + 8 * rg.slot, rg.phase);
            qs1 = rg.slot; rg.adv();
            wg_fence();
#pragma unroll
            for (int k = 0; k < 16; k++)
                wgmma_n64(accQ, dA + (((4 + (k >> 2)) * SLOT + (k & 3) * 32) >> 4),
                          dB + (((k < 8 ? qs0 : qs1) * SLOT + (k & 7) * 2048) >> 4), 1);
            wg_commit();
            wg_wait<1>();
            fence_acc<20>(kvd);
            const bool h1 = wv >= 2;
            const int head = 2 * w + (wv >> 1), f = 16 * (wv & 1) + g;
            float* kvp = acc_j + ACC_KV + head * 512 + f * 16 + 2 * q;
            red_f32x2(kvp, h1 ? kvd[8] : kvd[0], h1 ? kvd[9] : kvd[1]);
            red_f32x2(kvp + 128, h1 ? kvd[10] : kvd[2], h1 ? kvd[11] : kvd[3]);
            red_f32x2(kvp + 8, h1 ? kvd[12] : kvd[4], h1 ? kvd[13] : kvd[5]);
            red_f32x2(kvp + 136, h1 ? kvd[14] : kvd[6], h1 ? kvd[15] : kvd[7]);
            if (q == 0) {
                red_f32(acc_j + ACC_Z + head * 32 + f, kvd[16]);
                red_f32(acc_j + ACC_Z + head * 32 + f + 8, kvd[18]);
            }
            __syncwarp();
            if (lane == 0) mbar_arrive(pub + 0);
            if (tid == 0) TL(3);
        }
        {
            wg_wait<0>();
            fence_acc<32>(accQ);
            if (lane == 0) {
                mbar_arrive(sb + BAR_EMPTYB + 8 * qs0); mbar_arrive(sb + BAR_EMPTYB + 8 * qs1);
            }
            if (lane < 8 && lane != j) mbar_arrive(sb + BAR_EMPTYA + 8 * lane);
            uint32_t fp[16], fm[16];
#pragma unroll
            for (int hh = 0; hh < 4; hh++) {
                uint32_t a[4];
                ln_frag(accQ + 8 * hh, sb + OFF_CS1 + (16 * hh + 2 * q) * 4, rs0, nm0, rs1, nm1, a);
                feature_map(a, wb + 4 * hh, fp + 4 * hh, fm + 4 * hh);
            }
            if (tid == 0) { TL(4); wait_count(cnt_j + 96, epoch * 32); TL(5); }
            bar_sync(1, 256);
            const uint32_t kvs = sb + OFF_A + j * SLOT;
            {
                const float4 a0 = ld_l2_f4(acc_j + ACC_KV + 4 * tid), a1 = ld_l2_f4(acc_j + ACC_KV + 4 * (tid + 256));
                float zz = 0.f;
                if (tid < 128) zz = ld_l2_f(acc_j + ACC_Z + tid);
                sts64(kvs + (tid >> 2) * 48 + (tid & 3) * 8, pack_bf16(a0.x, a0.y), pack_bf16(a0.z, a0.w));
                sts64(kvs + ((tid >> 2) + 64) * 48 + (tid & 3) * 8, pack_bf16(a1.x, a1.y), pack_bf16(a1.z, a1.w));
                if (tid < 128) { const uint32_t z2 = pack_bf16(zz, zz); sts128(kvs + tid * 48 + 32, z2, z2, z2, z2); }
            }
            bar_sync(1, 256);
            uint32_t o_lo[8], o_hi[8];
#pragma unroll
            for (int hh = 0; hh < 4; hh++) {
                uint32_t b[8], zb[4];
                const uint32_t base = kvs + hh * 32 * 48;
                ldsm4t(base + (lane & 15) * 48 + (lane >> 4) * 16, b[0], b[1], b[2], b[3]);
                ldsm4t(base + (16 + (lane & 15)) * 48 + (lane >> 4) * 16, b[4], b[5], b[6], b[7]);
                ldsm4t(base + lane * 48 + 32, zb[0], zb[1], zb[2], zb[3]);
                float n0[4] = {0.f, 0.f, 0.f, 0.f}, n1[4] = {0.f, 0.f, 0.f, 0.f}, dn[4] = {0.f, 0.f, 0.f, 0.f};
                mma16816(n0, fp + 4 * hh, b[0], b[1]); mma16816(n1, fp + 4 * hh, b[2], b[3]); mma16816(dn, fp + 4 * hh, zb[0], zb[1]);
                mma16816(n0, fm + 4 * hh, b[4], b[5]); mma16816(n1, fm + 4 * hh, b[6], b[7]); mma16816(dn, fm + 4 * hh, zb[2], zb[3]);
                const float r0 = __fdividef(1.f, dn[0] + 1e-6f), r1 = __fdividef(1.f, dn[2] + 1e-6f);
                o_lo[2 * hh] = pack_bf16(n0[0] * r0, n0[1] * r0); o_hi[2 * hh] = pack_bf16(n0[2] * r1, n0[3] * r1);
                o_lo[2 * hh + 1] = pack_bf16(n1[0] * r0, n1[1] * r0); o_hi[2 * hh + 1] = pack_bf16(n1[2] * r1, n1[3] * r1);
            }
            store_rows64(g_o + grow * DM + 64 * j, DM, o_lo, o_hi, q);
            fence_async_smem();
            __syncwarp();
            if (lane == 0) { mbar_arrive(pub + 8); mbar_arrive(sb + BAR_EMPTYA + 8 * j); }
            if (tid == 0) TL(6);
        }
        {
            float acc2[32];
#pragma unroll
            for (int t = 0; t < 8; t++) {
                acc2[4 * t] = bf_lo(res_lo[t]); acc2[4 * t + 1] = bf_hi(res_lo[t]);
                acc2[4 * t + 2] = bf_lo(res_hi[t]); acc2[4 * t + 3] = bf_hi(res_hi[t]);
            }
            fence_acc<32>(acc2);
#pragma unroll 1
            for (int kp = 0; kp < 4; kp++) {
                mbar_wait(sb + BAR_FULLB + 8 * rg.slot, rg.phase);
#pragma unroll
                for (int hf = 0; hf < 2; hf++) {
                    const int kt = 2 * kp + hf;
                    mbar_wait(sb + BAR_FULLA + 8 * kt, 1);
                    wg_fence();
#pragma unroll
                    for (int k = 0; k < 4; k++)
                        wgmma_n64(acc2, dA + ((kt * SLOT + k * 32) >> 4),
                                  dB + ((rg.slot * SLOT + (hf * 4 + k) * 2048) >> 4), 1);
                    wg_commit();
                    wg_wait<1>();
                    mbar_arrive_if(sb + BAR_EMPTYA + 8 * ((kt + 7) & 7), l0 && kt > 0);
                    if (hf == 0) mbar_arrive_if(sb + BAR_EMPTYB + 8 * prev, l0 && kt > 0);
                }
                prev = rg.slot; rg.adv();
            }
            wg_wait<0>();
            fence_acc<32>(acc2);
            if (lane == 0) { mbar_arrive(sb + BAR_EMPTYA + 8 * 7); mbar_arrive(sb + BAR_EMPTYB + 8 * prev); }
            if (tid == 0) TL(8);
            float s0 = 0.f, s1 = 0.f;
#pragma unroll
            for (int t = 0; t < 8; t++) {
                res_lo[t] = pack_bf16(acc2[4 * t], acc2[4 * t + 1]);
                res_hi[t] = pack_bf16(acc2[4 * t + 2], acc2[4 * t + 3]);
                s0 += bf_lo(res_lo[t]) + bf_hi(res_lo[t]);
                s1 += bf_lo(res_hi[t]) + bf_hi(res_hi[t]);
            }
            store_rows64(g_h + grow * DM + 64 * j, DM, res_lo, res_hi, q);
            s0 += __shfl_xor_sync(0xffffffffu, s0, 1); s1 += __shfl_xor_sync(0xffffffffu, s1, 1);
            s0 += __shfl_xor_sync(0xffffffffu, s0, 2); s1 += __shfl_xor_sync(0xffffffffu, s1, 2);
            const float mu0 = s0 * (1.f / 64), mu1 = s1 * (1.f / 64);
            float q0 = 0.f, q1 = 0.f;
#pragma unroll
            for (int t = 0; t < 8; t++) {
                float d;
                d = bf_lo(res_lo[t]) - mu0; q0 = fmaf(d, d, q0);
                d = bf_hi(res_lo[t]) - mu0; q0 = fmaf(d, d, q0);
                d = bf_lo(res_hi[t]) - mu1; q1 = fmaf(d, d, q1);
                d = bf_hi(res_hi[t]) - mu1; q1 = fmaf(d, d, q1);
            }
            q0 += __shfl_xor_sync(0xffffffffu, q0, 1); q1 += __shfl_xor_sync(0xffffffffu, q1, 1);
            q0 += __shfl_xor_sync(0xffffffffu, q0, 2); q1 += __shfl_xor_sync(0xffffffffu, q1, 2);
            if (q < 2) {
                float2* sp = reinterpret_cast<float2*>(g_hstat + (grow + 8 * q) * 16 + 2 * j);
                *sp = q ? make_float2(mu1, q1) : make_float2(mu0, q0);
            }
            __syncwarp();
            if (lane == 0) mbar_arrive(pub + 16);
            if (tid == 0) TL(9);
        }
        float accA[64], accB[64], accG[24], accU[24];
        float hm0, hm1, hr0, hr1;
        __nv_bfloat16* const hhp = g_hh + grow * FFP + 176 * j;
        const uint32_t cs3q = sb + OFF_CS3 + 8 * q;
#define KT_N128(ACC, KT, FIRST)                                                                             \
    do {                                                                                                    \
        mbar_wait(sb + BAR_FULLB + 8 * rg.slot, rg.phase);                                                  \
        wg_fence();                                                                                         \
        _Pragma("unroll") for (int k = 0; k < 4; k++)                                                       \
            wgmma_n128(ACC, dA + (((KT) * SLOT + k * 32) >> 4),                                   \
                       dB + ((rg.slot * SLOT + k * 2048) >> 4), !((FIRST) && k == 0));         \
        wg_commit();                                                                                        \
    } while (0)
#define REL_PREV_B()                                                                                        \
    do {                                                                                                    \
        wg_wait<1>();                                                                                       \
        mbar_arrive_if(sb + BAR_EMPTYB + 8 * prev, l0);                                                     \
        prev = rg.slot; rg.adv();                                                                           \
    } while (0)
#define HH_PIECE(AG, AU, C, U)                                                                              \
    do {                                                                                                    \
        const int hf_ = (U) & 1, t0_ = ((U) >> 1) * 4;                                                      \
        const float mean_ = hf_ ? hm1 : hm0, r2_ = hf_ ? hr1 : hr0;                                         \
        uint32_t o_[4];                                                                                     \
        quad_transpose(hh_pair(AG, AU, t0_, hf_, cs3q + (C) * 256, mean_, r2_), hh_pair(AG, AU, t0_ + 1, hf_, cs3q + (C) * 256, mean_, r2_), \
                       hh_pair(AG, AU, t0_ + 2, hf_, cs3q + (C) * 256, mean_, r2_), hh_pair(AG, AU, t0_ + 3, hf_, cs3q + (C) * 256, mean_, r2_), o_, q); \
        stg128(hhp + hf_ * 8 * FFP + (C) * 64 + t0_ * 8 + q * 8, o_[0], o_[1], o_[2], o_[3]);               \
    } while (0)
        {
#pragma unroll 1
            for (int kt = 0; kt < 8; kt++) {
                mbar_wait(sb + BAR_FULLA + 8 * kt, 0);
                if (kt == 0 && tid == 0) TL(10);
                KT_N128(accA, kt, kt == 0);
                wg_wait<1>();
                mbar_arrive_if(sb + BAR_EMPTYB + 8 * prev, l0 && kt > 0);
                prev = rg.slot; rg.adv();
            }
            const float4 sa0 = ld_l2_f4(g_hstat + grow * 16 + 4 * q), sa1 = ld_l2_f4(g_hstat + (grow + 8) * 16 + 4 * q);
            KT_N128(accB, 0, true);
            {
                float m0 = sa0.x + sa0.z, m1 = sa1.x + sa1.z;
                m0 += __shfl_xor_sync(0xffffffffu, m0, 1); m1 += __shfl_xor_sync(0xffffffffu, m1, 1);
                m0 += __shfl_xor_sync(0xffffffffu, m0, 2); m1 += __shfl_xor_sync(0xffffffffu, m1, 2);
                hm0 = m0 * 0.125f; hm1 = m1 * 0.125f;
                float v0 = sa0.y + sa0.w + 64.f * ((sa0.x - hm0) * (sa0.x - hm0) + (sa0.z - hm0) * (sa0.z - hm0));
                float v1 = sa1.y + sa1.w + 64.f * ((sa1.x - hm1) * (sa1.x - hm1) + (sa1.z - hm1) * (sa1.z - hm1));
                v0 += __shfl_xor_sync(0xffffffffu, v0, 1); v1 += __shfl_xor_sync(0xffffffffu, v1, 1);
                v0 += __shfl_xor_sync(0xffffffffu, v0, 2); v1 += __shfl_xor_sync(0xffffffffu, v1, 2);
                hr0 = __fdividef(1.f, v0 * (1.f / DM) + 1e-5f); hr1 = __fdividef(1.f, v1 * (1.f / DM) + 1e-5f);
            }
            mbar_wait(sb + BAR_CS3, 0);
            REL_PREV_B();
            fence_acc<64>(accA);
            if (tid == 0) TL(11);
#pragma unroll
            for (int u = 0; u < 4; u++) {
                HH_PIECE(accA, accA + 32, 0, u);
                if (u == 3) { __syncwarp(); if (lane == 0) mbar_arrive(pub + 24); }
                KT_N128(accB, u + 1, false);
                REL_PREV_B();
            }
#pragma unroll 1
            for (int kt = 5; kt < 8; kt++) {
                KT_N128(accB, kt, false);
                REL_PREV_B();
            }
#define KT_N48(KT, FIRST)                                                                                   \
    do {                                                                                                    \
        mbar_wait(sb + BAR_FULLB + 8 * rg.slot, rg.phase);                                                  \
        wg_fence();                                                                                         \
        _Pragma("unroll") for (int k = 0; k < 4; k++) {                                                     \
            const uint32_t da_ = dA + (((KT) * SLOT + k * 32) >> 4);                              \
            wgmma_n48(accG, da_, dB + ((rg.slot * SLOT + k * 2048) >> 4), !((FIRST) && k == 0)); \
            wgmma_n48(accU, da_, dB + ((rg.slot * SLOT + 8192 + k * 2048) >> 4), !((FIRST) && k == 0)); \
        }                                                                                                   \
        wg_commit();                                                                                        \
    } while (0)
            KT_N48(0, true);
            REL_PREV_B();
            fence_acc<64>(accB);
            if (tid == 0) TL(12);
#pragma unroll
            for (int u = 0; u < 4; u++) {
                HH_PIECE(accB, accB + 32, 1, u);
                if (u == 3) { __syncwarp(); if (lane == 0) mbar_arrive(pub + 32); }
                KT_N48(u + 1, false);
                REL_PREV_B();
                mbar_arrive_if(sb + BAR_EMPTYA + 8 * u, l0);
            }
#pragma unroll 1
            for (int kt = 5; kt < 8; kt++) {
                KT_N48(kt, false);
                REL_PREV_B();
                mbar_arrive_if(sb + BAR_EMPTYA + 8 * (kt - 1), l0);
            }
        }
        {
            float acc4[32];
#pragma unroll
            for (int t = 0; t < 8; t++) {
                acc4[4 * t] = bf_lo(res_lo[t]); acc4[4 * t + 1] = bf_hi(res_lo[t]);
                acc4[4 * t + 2] = bf_lo(res_hi[t]); acc4[4 * t + 3] = bf_hi(res_hi[t]);
            }
            fence_acc<32>(acc4);
#define KT_P4(T, HF, NK)                                                                                    \
    do {                                                                                                    \
        const int s_ = (T) & 7;                                                                             \
        if (!(HF)) mbar_wait(sb + BAR_FULLB + 8 * rg.slot, rg.phase);                                       \
        mbar_wait(sb + BAR_FULLA + 8 * s_, (((T) >> 3) + 1) & 1);                                           \
        wg_fence();                                                                                         \
        _Pragma("unroll") for (int k = 0; k < (NK); k++)                                                    \
            wgmma_n64(acc4, dA + ((s_ * SLOT + k * 32) >> 4),                                     \
                      dB + ((rg.slot * SLOT + (HF) * 8192 + k * 2048) >> 4), 1);               \
        wg_commit();                                                                                        \
        wg_wait<1>();                                                                                       \
        mbar_arrive_if(sb + BAR_EMPTYA + 8 * (((T) + 7) & 7), l0);                                          \
        if (!(HF)) mbar_arrive_if(sb + BAR_EMPTYB + 8 * prev, l0);                                          \
        if (HF) { prev = rg.slot; rg.adv(); }                                                               \
    } while (0)
            KT_P4(0, 0, 4);
            fence_acc<24>(accG); fence_acc<24>(accU);
            if (tid == 0) TL(13);
            HH_PIECE(accG, accU, 2, 0);
            KT_P4(1, 1, 4);
            HH_PIECE(accG, accU, 2, 1);
            KT_P4(2, 0, 4);
            {
                uint32_t o_[4];
                quad_transpose(hh_pair(accG, accU, 4, 0, cs3q + 512, hm0, hr0), hh_pair(accG, accU, 5, 0, cs3q + 512, hm0, hr0),
                               hh_pair(accG, accU, 4, 1, cs3q + 512, hm1, hr1), hh_pair(accG, accU, 5, 1, cs3q + 512, hm1, hr1), o_, q);
                stg128(hhp + (q >> 1) * 8 * FFP + 128 + 32 + (q & 1) * 8, o_[0], o_[1], o_[2], o_[3]);
                __syncwarp();
                if (lane == 0) mbar_arrive(pub + 40);
            }
            KT_P4(3, 1, 4);
#pragma unroll 1
            for (int t = 4; t < 16; t += 2) { KT_P4(t, 0, 4); KT_P4(t + 1, 1, 4); }
            if (tid == 0) TL(14);
#pragma unroll 1
            for (int t = 16; t < 24; t += 2) { KT_P4(t, 0, 3); KT_P4(t + 1, 1, 3); }
            wg_wait<0>();
            fence_acc<32>(acc4);
            if (tid == 0) TL(15);
#pragma unroll
            for (int t = 0; t < 8; t++) {
                res_lo[t] = pack_bf16(acc4[4 * t], acc4[4 * t + 1]);
                res_hi[t] = pack_bf16(acc4[4 * t + 2], acc4[4 * t + 3]);
            }
            store_rows64(P.out + grow * DM + 64 * j, DM, res_lo, res_hi, q);
            if (tid == 0) {
                if (blockIdx.x == 0) g_epoch = epoch;
                TL(16);
            }
        }
    }
}

typedef CUresult (*EncodeFn)(CUtensorMap*, CUtensorMapDataType, cuuint32_t, void*, const cuuint64_t*, const cuuint64_t*,
                             const cuuint32_t*, const cuuint32_t*, CUtensorMapInterleave, CUtensorMapSwizzle,
                             CUtensorMapL2promotion, CUtensorMapFloatOOBfill);

static void make_map2d(EncodeFn enc, CUtensorMap* tm, const void* base, uint64_t cols, uint64_t rows, uint64_t pitch_elems,
                       uint32_t box_rows) {
    cuuint64_t gd[2] = {cols, rows};
    cuuint64_t gs[1] = {pitch_elems * 2};
    cuuint32_t bd[2] = {64, box_rows};
    cuuint32_t es[2] = {1, 1};
    enc(tm, CU_TENSOR_MAP_DATA_TYPE_BFLOAT16, 2, const_cast<void*>(base), gd, gs, bd, es, CU_TENSOR_MAP_INTERLEAVE_NONE,
        CU_TENSOR_MAP_SWIZZLE_128B, CU_TENSOR_MAP_L2_PROMOTION_L2_256B, CU_TENSOR_MAP_FLOAT_OOB_FILL_NONE);
}

}

extern "C" void kernel_launch(void* const* d_in, const int* in_sizes, int n_in, void* d_out, int out_size) {
    using namespace hk;
    (void)in_sizes; (void)n_in; (void)out_size;
    static EncodeFn enc = nullptr;
    static void *po = nullptr, *ph = nullptr, *phh = nullptr;
    if (!enc) {
        void* fn = nullptr;
        cudaDriverEntryPointQueryResult qr;
        cudaGetDriverEntryPoint("cuTensorMapEncodeTiled", &fn, cudaEnableDefault, &qr);
        enc = (EncodeFn)fn;
        cudaGetSymbolAddress(&po, g_o);
        cudaGetSymbolAddress(&ph, g_h);
        cudaGetSymbolAddress(&phh, g_hh);
        cudaFuncSetAttribute(fused_kernel, cudaFuncAttributeMaxDynamicSharedMemorySize, SMEM_BYTES);
    }
    Params P;
    const __nv_bfloat16* x = (const __nv_bfloat16*)d_in[0];
    P.wqkv = (const __nv_bfloat16*)d_in[1];
    P.wphi = (const __nv_bfloat16*)d_in[2];
    P.wo = (const __nv_bfloat16*)d_in[3];
    P.wg = (const __nv_bfloat16*)d_in[5];
    P.wu = (const __nv_bfloat16*)d_in[6];
    P.wd = (const __nv_bfloat16*)d_in[7];
    P.out = (__nv_bfloat16*)d_out;
    make_map2d(enc, &P.tx, x, DM, SEQ, DM, 128);
    make_map2d(enc, &P.to, po, DM, SEQ, DM, 128);
    make_map2d(enc, &P.th, ph, DM, SEQ, DM, 128);
    make_map2d(enc, &P.thh, phh, FFP, SEQ, FFP, 128);
    make_map2d(enc, &P.twq, P.wqkv, 3 * DM, DM, 3 * DM, 128);
    make_map2d(enc, &P.two, P.wo, DM, DM, DM, 128);
    make_map2d(enc, &P.twg, P.wg, FF, DM, FF, 64);
    make_map2d(enc, &P.twu, P.wu, FF, DM, FF, 64);
    make_map2d(enc, &P.twd, P.wd, DM, FF, DM, 64);
    {
        cuuint64_t gd[3] = {(cuuint64_t)DM, (cuuint64_t)DM, 3};
        cuuint64_t gs[2] = {(cuuint64_t)3 * DM * 2, (cuuint64_t)DM * 2};
        cuuint32_t bd[3] = {64, 64, 2};
        cuuint32_t es[3] = {1, 1, 1};
        enc(&P.twkv, CU_TENSOR_MAP_DATA_TYPE_BFLOAT16, 3, const_cast<__nv_bfloat16*>(P.wqkv), gd, gs, bd, es,
            CU_TENSOR_MAP_INTERLEAVE_NONE, CU_TENSOR_MAP_SWIZZLE_128B, CU_TENSOR_MAP_L2_PROMOTION_L2_256B,
            CU_TENSOR_MAP_FLOAT_OOB_FILL_NONE);
    }
    fused_kernel<<<NCTA, NTHREADS, SMEM_BYTES>>>(P);
}
```

```cpp
#include <cuda_runtime.h>
#include <cuda_bf16.h>
#include <cuda.h>
#include <stdint.h>

namespace hk {

constexpr int SEQ = 2048, DM = 512, FF = 1376, FFP = 1408;
constexpr int NCTA = 128;
constexpr int NTHREADS = 384;
constexpr uint32_t SLOT = 16384;
constexpr uint32_t OFF_A = 0, OFF_B = 8 * SLOT, OFF_MISC = 14 * SLOT;
constexpr uint32_t BAR_FULLA = OFF_MISC + 0, BAR_EMPTYA = OFF_MISC + 64, BAR_FULLB = OFF_MISC + 128,
                   BAR_EMPTYB = OFF_MISC + 176, BAR_CS1 = OFF_MISC + 224, BAR_CS3 = OFF_MISC + 232,
                   BAR_PUB = OFF_MISC + 240;
constexpr uint32_t OFF_CS1 = OFF_MISC + 384;
constexpr uint32_t OFF_CS3 = OFF_CS1 + 1024;
constexpr uint32_t SMEM_BYTES = OFF_CS3 + 1536;
constexpr int NB = 6;

constexpr int ACC_KV = 0, ACC_Z = 2048, ACC_CS1 = 2176, ACC_CS3 = 2368, ACC_SIZE = 2752;

__device__ __align__(1024) __nv_bfloat16 g_o[SEQ * DM];
__device__ __align__(1024) __nv_bfloat16 g_h[SEQ * DM];
__device__ __align__(1024) __nv_bfloat16 g_hh[SEQ * FFP];
__device__ __align__(128) float g_hstat[SEQ * 16];
__device__ __align__(128) unsigned long long g_xstat[SEQ * 2];
__device__ __align__(128) float g_acc[8 * ACC_SIZE];
__device__ __align__(128) unsigned g_cnt[8 * 4 * 32];
__device__ __align__(128) unsigned g_flag[16 * 5 * 32];
__device__ unsigned g_epoch;

#define TL(i, pred) do {} while (0)
#define TLG(i, pred) do {} while (0)

struct Params {
    CUtensorMap tx, to, th, thh, twkv, twq, two, twg, twu, twd;
    const __nv_bfloat16 *x, *wqkv, *wphi, *wo, *wg, *wu, *wd;
    __nv_bfloat16* out;
};

__device__ __forceinline__ uint32_t smem_u32(const void* p) { return (uint32_t)__cvta_generic_to_shared(p); }
__device__ __forceinline__ void mbar_init(uint32_t bar, uint32_t cnt) {
    asm volatile("mbarrier.init.shared::cta.b64 [%0], %1;" ::"r"(bar), "r"(cnt) : "memory");
}
__device__ __forceinline__ void mbar_expect_tx(uint32_t bar, uint32_t bytes) {
    asm volatile("mbarrier.arrive.expect_tx.shared::cta.b64 _, [%0], %1;" ::"r"(bar), "r"(bytes) : "memory");
}
__device__ __forceinline__ void mbar_arrive(uint32_t bar) {
    asm volatile("mbarrier.arrive.shared::cta.b64 _, [%0];" ::"r"(bar) : "memory");
}
__device__ __forceinline__ void mbar_arrive_if(uint32_t bar, bool pred) {
    asm volatile("{.reg .pred p; setp.ne.u32 p, %1, 0; @p mbarrier.arrive.shared::cta.b64 _, [%0];}" ::"r"(bar), "r"((uint32_t)pred) : "memory");
}
__device__ __forceinline__ bool mbar_try(uint32_t bar, uint32_t parity) {
    uint32_t ok;
    asm volatile("{.reg .pred p; mbarrier.try_wait.parity.shared::cta.b64 p, [%1], %2; selp.u32 %0,1,0,p;}"
                 : "=r"(ok) : "r"(bar), "r"(parity) : "memory");
    return ok;
}
__device__ __forceinline__ bool mbar_test(uint32_t bar, uint32_t parity) {
    uint32_t ok;
    asm volatile("{.reg .pred p; mbarrier.test_wait.parity.shared::cta.b64 p, [%1], %2; selp.u32 %0,1,0,p;}"
                 : "=r"(ok) : "r"(bar), "r"(parity) : "memory");
    return ok;
}
__device__ __forceinline__ void trap_if_gt(uint32_t v, uint32_t lim) {
    asm volatile("{.reg .pred p; setp.gt.u32 p, %0, %1; @p trap;}" ::"r"(v), "r"(lim));
}
__device__ __forceinline__ void mbar_wait(uint32_t bar, uint32_t parity) {
    asm volatile("{\n"
                 ".reg .pred P1, P2;\n"
                 ".reg .u32 c;\n"
                 "mov.u32 c, 0;\n"
                 "LAB_WAIT:\n"
                 "mbarrier.try_wait.parity.shared::cta.b64 P1, [%0], %1;\n"
                 "@P1 bra LAB_DONE;\n"
                 "add.u32 c, c, 1;\n"
                 "setp.gt.u32 P2, c, 4194304;\n"
                 "@P2 trap;\n"
                 "bra LAB_WAIT;\n"
                 "LAB_DONE:\n"
                 "}" ::"r"(bar), "r"(parity) : "memory");
}
__device__ __forceinline__ void mbar_waitc(uint32_t bar, uint32_t parity) {
    asm volatile("{\n"
                 ".reg .pred P1;\n"
                 "LAB_WAIT:\n"
                 "mbarrier.try_wait.parity.shared::cta.b64 P1, [%0], %1;\n"
                 "@!P1 bra LAB_WAIT;\n"
                 "}" ::"r"(bar), "r"(parity) : "memory");
}
__device__ __forceinline__ void tma2d(uint32_t dst, const CUtensorMap* tm, uint32_t bar, int c0, int c1) {
    asm volatile("cp.async.bulk.tensor.2d.shared::cluster.global.mbarrier::complete_tx::bytes [%0], [%1, {%3, %4}], [%2];"
                 ::"r"(dst), "l"(tm), "r"(bar), "r"(c0), "r"(c1) : "memory");
}
__device__ __forceinline__ void tma3d(uint32_t dst, const CUtensorMap* tm, uint32_t bar, int c0, int c1, int c2) {
    asm volatile("cp.async.bulk.tensor.3d.shared::cluster.global.mbarrier::complete_tx::bytes [%0], [%1, {%3, %4, %5}], [%2];"
                 ::"r"(dst), "l"(tm), "r"(bar), "r"(c0), "r"(c1), "r"(c2) : "memory");
}
__device__ __forceinline__ void prefetch_tmap(const CUtensorMap* tm) {
    asm volatile("prefetch.tensormap [%0];" ::"l"(tm) : "memory");
}
__device__ __forceinline__ void prefetch_l2(const void* p, uint32_t bytes) {
    asm volatile("cp.async.bulk.prefetch.L2.global [%0], %1;" ::"l"(p), "r"(bytes) : "memory");
}
__device__ __forceinline__ unsigned ld_acquire(const unsigned* p) {
    unsigned v; asm volatile("ld.acquire.gpu.global.u32 %0, [%1];" : "=r"(v) : "l"(p) : "memory"); return v;
}
__device__ __forceinline__ uint2 ld_acquire2(const unsigned* p) {
    unsigned long long v; asm volatile("ld.acquire.gpu.global.u64 %0, [%1];" : "=l"(v) : "l"(p) : "memory");
    return make_uint2((unsigned)v, (unsigned)(v >> 32));
}
__device__ __forceinline__ void st_relaxed(unsigned* p, unsigned v) {
    asm volatile("st.relaxed.gpu.global.u32 [%0], %1;" ::"l"(p), "r"(v) : "memory");
}
__device__ __forceinline__ void red_relaxed(unsigned* p, unsigned v) {
    asm volatile("red.relaxed.gpu.global.add.u32 [%0], %1;" ::"l"(p), "r"(v) : "memory");
}
__device__ __forceinline__ void fence_gpu() { asm volatile("fence.acq_rel.gpu;" ::: "memory"); }
__device__ __forceinline__ void fence_async_smem() { asm volatile("fence.proxy.async.shared::cta;" ::: "memory"); }
__device__ __forceinline__ void fence_async_global() { asm volatile("fence.proxy.async.global;" ::: "memory"); }
__device__ __forceinline__ void wait_count(const unsigned* p, unsigned target) {
    uint32_t it = 0;
    while ((int)(ld_acquire(p) - target) < 0) trap_if_gt(++it, 1u << 22);
}
__device__ __forceinline__ void wait_count_warp(const unsigned* p, unsigned target) {
    uint32_t it = 0;
    while (__any_sync(0xffffffffu, (int)(ld_acquire(p) - target) < 0)) trap_if_gt(++it, 1u << 22);
}
__device__ __forceinline__ void red_f32(float* p, float a) {
    asm volatile("red.relaxed.gpu.global.add.f32 [%0], %1;" ::"l"(p), "f"(a) : "memory");
}
__device__ __forceinline__ void red_f32x2(float* p, float a, float b) {
    asm volatile("red.relaxed.gpu.global.add.v2.f32 [%0], {%1, %2};" ::"l"(p), "f"(a), "f"(b) : "memory");
}
__device__ __forceinline__ void red_f32x4(float* p, float a, float b, float c, float d) {
    asm volatile("red.relaxed.gpu.global.add.v4.f32 [%0], {%1, %2, %3, %4};" ::"l"(p), "f"(a), "f"(b), "f"(c), "f"(d) : "memory");
}
__device__ __forceinline__ float4 ld_l2_f4(const float* p) {
    float4 v;
    asm volatile("ld.relaxed.gpu.global.v4.f32 {%0,%1,%2,%3}, [%4];" : "=f"(v.x), "=f"(v.y), "=f"(v.z), "=f"(v.w) : "l"(p) : "memory");
    return v;
}
__device__ __forceinline__ float2 ld_l2_f2(const float* p) {
    float2 v;
    asm volatile("ld.relaxed.gpu.global.v2.f32 {%0,%1}, [%2];" : "=f"(v.x), "=f"(v.y) : "l"(p) : "memory");
    return v;
}
__device__ __forceinline__ float ld_l2_f(const float* p) {
    float v;
    asm volatile("ld.relaxed.gpu.global.f32 %0, [%1];" : "=f"(v) : "l"(p) : "memory");
    return v;
}
__device__ __forceinline__ uint4 ldg_nc(const void* p) {
    uint4 v;
    asm volatile("ld.global.nc.L1::no_allocate.v4.u32 {%0,%1,%2,%3}, [%4];" : "=r"(v.x), "=r"(v.y), "=r"(v.z), "=r"(v.w) : "l"(p));
    return v;
}
__device__ __forceinline__ void stg128(void* p, uint32_t a, uint32_t b, uint32_t c, uint32_t d) {
    asm volatile("st.global.v4.u32 [%0], {%1,%2,%3,%4};" ::"l"(p), "r"(a), "r"(b), "r"(c), "r"(d) : "memory");
}
__device__ __forceinline__ uint4 lds128(uint32_t a) {
    uint4 v;
    asm volatile("ld.shared.v4.u32 {%0,%1,%2,%3}, [%4];" : "=r"(v.x), "=r"(v.y), "=r"(v.z), "=r"(v.w) : "r"(a) : "memory");
    return v;
}
__device__ __forceinline__ float2 lds_f2(uint32_t a) {
    float2 v;
    asm volatile("ld.shared.v2.f32 {%0,%1}, [%2];" : "=f"(v.x), "=f"(v.y) : "r"(a) : "memory");
    return v;
}
__device__ __forceinline__ void sts_f2(uint32_t a, float x, float y) {
    asm volatile("st.shared.v2.f32 [%0], {%1,%2};" ::"r"(a), "f"(x), "f"(y) : "memory");
}
__device__ __forceinline__ void sts64(uint32_t a, uint32_t x, uint32_t y) {
    asm volatile("st.shared.v2.u32 [%0], {%1,%2};" ::"r"(a), "r"(x), "r"(y) : "memory");
}
__device__ __forceinline__ void sts128(uint32_t a, uint32_t x, uint32_t y, uint32_t z, uint32_t w) {
    asm volatile("st.shared.v4.u32 [%0], {%1,%2,%3,%4};" ::"r"(a), "r"(x), "r"(y), "r"(z), "r"(w) : "memory");
}
__device__ __forceinline__ void stsm4(uint32_t a, uint32_t r0, uint32_t r1, uint32_t r2, uint32_t r3) {
    asm volatile("stmatrix.sync.aligned.m8n8.x4.shared.b16 [%0], {%1,%2,%3,%4};" ::"r"(a), "r"(r0), "r"(r1), "r"(r2), "r"(r3) : "memory");
}
__device__ __forceinline__ void ldsm4(uint32_t a, uint32_t& r0, uint32_t& r1, uint32_t& r2, uint32_t& r3) {
    asm volatile("ldmatrix.sync.aligned.m8n8.x4.shared.b16 {%0,%1,%2,%3}, [%4];" : "=r"(r0), "=r"(r1), "=r"(r2), "=r"(r3) : "r"(a) : "memory");
}
__device__ __forceinline__ void ldsm4t(uint32_t a, uint32_t& r0, uint32_t& r1, uint32_t& r2, uint32_t& r3) {
    asm volatile("ldmatrix.sync.aligned.m8n8.x4.trans.shared.b16 {%0,%1,%2,%3}, [%4];" : "=r"(r0), "=r"(r1), "=r"(r2), "=r"(r3) : "r"(a) : "memory");
}
__device__ __forceinline__ void mma16816(float* c, const uint32_t* a, uint32_t b0, uint32_t b1) {
    asm("mma.sync.aligned.m16n8k16.row.col.f32.bf16.bf16.f32 {%0,%1,%2,%3}, {%4,%5,%6,%7}, {%8,%9}, {%0,%1,%2,%3};"
                 : "+f"(c[0]), "+f"(c[1]), "+f"(c[2]), "+f"(c[3])
                 : "r"(a[0]), "r"(a[1]), "r"(a[2]), "r"(a[3]), "r"(b0), "r"(b1));
}
__device__ __forceinline__ uint32_t pack_bf16(float lo, float hi) {
    uint32_t r; asm("cvt.rn.bf16x2.f32 %0, %1, %2;" : "=r"(r) : "f"(hi), "f"(lo)); return r;
}
__device__ __forceinline__ float bf_lo(uint32_t w) { return __uint_as_float(w << 16); }
__device__ __forceinline__ float bf_hi(uint32_t w) { return __uint_as_float(w & 0xffff0000u); }
__device__ __forceinline__ float ex2(float x) { float r; asm("ex2.approx.ftz.f32 %0, %1;" : "=f"(r) : "f"(x)); return r; }
__device__ __forceinline__ float rcp(float x) { float r; asm("rcp.approx.ftz.f32 %0, %1;" : "=f"(r) : "f"(x)); return r; }
__device__ __forceinline__ void bar_sync(int id, int n) { asm volatile("bar.sync %0, %1;" ::"r"(id), "r"(n) : "memory"); }

__device__ __forceinline__ uint32_t desc_lo(uint32_t addr) { return ((addr & 0x3FFFF) >> 4) | (512u << 16); }
#define DESC_HI "0x40000040"
__device__ __forceinline__ void wg_fence() { asm volatile("wgmma.fence.sync.aligned;" ::: "memory"); }
__device__ __forceinline__ void wg_commit() { asm volatile("wgmma.commit_group.sync.aligned;" ::: "memory"); }
template <int N> __device__ __forceinline__ void wg_wait() { asm volatile("wgmma.wait_group.sync.aligned %0;" ::"n"(N) : "memory"); }
template <int N> __device__ __forceinline__ void fence_acc(float* d) {
#pragma unroll
    for (int i = 0; i < N; i++) asm volatile("" : "+f"(d[i])::"memory");
}
#define R4(o) "+f"(d[o + 0]), "+f"(d[o + 1]), "+f"(d[o + 2]), "+f"(d[o + 3])
#define R8(o) R4(o), R4(o + 4)
__device__ __forceinline__ void wgmma_n128(float* d, uint32_t da, uint32_t db, int sc) {
    asm volatile("{.reg .pred p; .reg .b64 da, db; setp.ne.b32 p, %66, 0; mov.b64 da, {%64, " DESC_HI "}; mov.b64 db, {%65, " DESC_HI "};\n"
                 "wgmma.mma_async.sync.aligned.m64n128k16.f32.bf16.bf16 {%0,%1,%2,%3,%4,%5,%6,%7,%8,%9,%10,%11,%12,%13,%14,%15,%16,%17,%18,%19,%20,%21,%22,%23,%24,%25,%26,%27,%28,%29,%30,%31,"
                 "%32,%33,%34,%35,%36,%37,%38,%39,%40,%41,%42,%43,%44,%45,%46,%47,%48,%49,%50,%51,%52,%53,%54,%55,%56,%57,%58,%59,%60,%61,%62,%63}, da, db, p, 1, 1, 0, 1;}"
                 : R8(0), R8(8), R8(16), R8(24), R8(32), R8(40), R8(48), R8(56)
                 : "r"(da), "r"(db), "r"(sc));
}
__device__ __forceinline__ void wgmma_n64(float* d, uint32_t da, uint32_t db, int sc) {
    asm volatile("{.reg .pred p; .reg .b64 da, db; setp.ne.b32 p, %34, 0; mov.b64 da, {%32, " DESC_HI "}; mov.b64 db, {%33, " DESC_HI "};\n"
                 "wgmma.mma_async.sync.aligned.m64n64k16.f32.bf16.bf16 {%0,%1,%2,%3,%4,%5,%6,%7,%8,%9,%10,%11,%12,%13,%14,%15,%16,%17,%18,%19,%20,%21,%22,%23,%24,%25,%26,%27,%28,%29,%30,%31}, da, db, p, 1, 1, 0, 1;}"
                 : R8(0), R8(8), R8(16), R8(24)
                 : "r"(da), "r"(db), "r"(sc));
}
__device__ __forceinline__ void wgmma_n48(float* d, uint32_t da, uint32_t db, int sc) {
    asm volatile("{.reg .pred p; .reg .b64 da, db; setp.ne.b32 p, %26, 0; mov.b64 da, {%24, " DESC_HI "}; mov.b64 db, {%25, " DESC_HI "};\n"
                 "wgmma.mma_async.sync.aligned.m64n48k16.f32.bf16.bf16 {%0,%1,%2,%3,%4,%5,%6,%7,%8,%9,%10,%11,%12,%13,%14,%15,%16,%17,%18,%19,%20,%21,%22,%23}, da, db, p, 1, 1, 0, 1;}"
                 : R8(0), R8(8), R8(16)
                 : "r"(da), "r"(db), "r"(sc));
}
__device__ __forceinline__ void wgmma_n40_tt(float* d, uint32_t da, uint32_t db, int sc) {
    asm volatile("{.reg .pred p; .reg .b64 da, db; setp.ne.b32 p, %22, 0; mov.b64 da, {%20, " DESC_HI "}; mov.b64 db, {%21, " DESC_HI "};\n"
                 "wgmma.mma_async.sync.aligned.m64n40k16.f32.bf16.bf16 {%0,%1,%2,%3,%4,%5,%6,%7,%8,%9,%10,%11,%12,%13,%14,%15,%16,%17,%18,%19}, da, db, p, 1, 1, 1, 1;}"
                 : R8(0), R8(8), R4(16)
                 : "r"(da), "r"(db), "r"(sc));
}

__device__ __forceinline__ void quad_transpose(uint32_t r0, uint32_t r1, uint32_t r2, uint32_t r3, uint32_t* o, int q) {
    const bool odd = q & 1, hi = q & 2;
    uint32_t a = odd ? r0 : r1, b = odd ? r2 : r3;
    a = __shfl_xor_sync(0xffffffffu, a, 1);
    b = __shfl_xor_sync(0xffffffffu, b, 1);
    uint32_t s0 = odd ? a : r0, s1 = odd ? r1 : a, s2 = odd ? b : r2, s3 = odd ? r3 : b;
    uint32_t c = hi ? s0 : s2, d = hi ? s1 : s3;
    c = __shfl_xor_sync(0xffffffffu, c, 2);
    d = __shfl_xor_sync(0xffffffffu, d, 2);
    o[0] = hi ? c : s0; o[1] = hi ? d : s1; o[2] = hi ? s2 : c; o[3] = hi ? s3 : d;
}
__device__ __forceinline__ void red_f32_if(float* p, float a, bool pred) {
    asm volatile("{.reg .pred p; setp.ne.u32 p, %2, 0; @p red.relaxed.gpu.global.add.f32 [%0], %1;}" ::"l"(p), "f"(a), "r"((uint32_t)pred) : "memory");
}
__device__ __forceinline__ void stg_f2_if(float* p, float a, float b, bool pred) {
    asm volatile("{.reg .pred p; setp.ne.u32 p, %3, 0; @p st.global.v2.f32 [%0], {%1,%2};}" ::"l"(p), "f"(a), "f"(b), "r"((uint32_t)pred) : "memory");
}
__device__ __forceinline__ void stg64(void* p, uint32_t a, uint32_t b) {
    asm volatile("st.global.v2.u32 [%0], {%1,%2};" ::"l"(p), "r"(a), "r"(b) : "memory");
}
__device__ __forceinline__ void store_pair(__nv_bfloat16* p, uint32_t r0, uint32_t r1, bool odd) {
    const uint32_t x = __shfl_xor_sync(0xffffffffu, odd ? r0 : r1, 1);
    stg64(p, odd ? x : r0, odd ? r1 : x);
}
__device__ __forceinline__ void mma16816_z(float* c, const uint32_t* a, uint32_t b0, uint32_t b1) {
    asm("mma.sync.aligned.m16n8k16.row.col.f32.bf16.bf16.f32 {%0,%1,%2,%3}, {%4,%5,%6,%7}, {%8,%9}, {%10,%10,%10,%10};"
                 : "=f"(c[0]), "=f"(c[1]), "=f"(c[2]), "=f"(c[3])
                 : "r"(a[0]), "r"(a[1]), "r"(a[2]), "r"(a[3]), "r"(b0), "r"(b1), "f"(0.f));
}
__device__ __forceinline__ uint32_t max2(uint32_t a, uint32_t b) { uint32_t r; asm("max.bf16x2 %0, %1, %2;" : "=r"(r) : "r"(a), "r"(b)); return r; }
__device__ __forceinline__ uint32_t min2(uint32_t a, uint32_t b) { uint32_t r; asm("min.bf16x2 %0, %1, %2;" : "=r"(r) : "r"(a), "r"(b)); return r; }
__device__ __forceinline__ void bar_arrive(int id, int n) { asm volatile("bar.arrive %0, %1;" ::"r"(id), "r"(n) : "memory"); }
__device__ __forceinline__ void mbar_arrive_n_if(uint32_t bar, uint32_t n, bool pred) {
    asm volatile("{.reg .pred p; setp.ne.u32 p, %1, 0; @p mbarrier.arrive.shared::cta.b64 _, [%0], %2;}" ::"r"(bar), "r"((uint32_t)pred), "r"(n) : "memory");
}
__device__ __forceinline__ float4 lds_f4(uint32_t a) {
    float4 v;
    asm volatile("ld.shared.v4.f32 {%0,%1,%2,%3}, [%4];" : "=f"(v.x), "=f"(v.y), "=f"(v.z), "=f"(v.w) : "r"(a) : "memory");
    return v;
}
__device__ __forceinline__ uint4 ld_tagged(const unsigned long long* p) {
    unsigned long long a, b;
    asm volatile("ld.relaxed.gpu.global.v2.b64 {%0,%1}, [%2];" : "=l"(a), "=l"(b) : "l"(p) : "memory");
    return make_uint4((unsigned)a, (unsigned)(a >> 32), (unsigned)b, (unsigned)(b >> 32));
}
__device__ __forceinline__ void st_tagged_if(unsigned long long* p, float a, float b, unsigned tag, bool pred) {
    const unsigned long long t = (unsigned long long)tag << 32;
    asm volatile("{.reg .pred p; setp.ne.u32 p, %3, 0; @p st.relaxed.gpu.global.v2.b64 [%0], {%1,%2};}"
                 ::"l"(p), "l"(t | __float_as_uint(a)), "l"(t | __float_as_uint(b)), "r"((uint32_t)pred) : "memory");
}

__device__ __forceinline__ void store_tile(uint32_t tile_rows, __nv_bfloat16* gdst, const uint32_t* lo, const uint32_t* hi, int lane) {
    const int r = lane & 15;
#pragma unroll
    for (int b = 0; b < 4; b++)
        stsm4(tile_rows + r * 128 + (((2 * b + (lane >> 4)) ^ (r & 7)) << 4), lo[2 * b], hi[2 * b], lo[2 * b + 1], hi[2 * b + 1]);
    __syncwarp();
#pragma unroll
    for (int i = 0; i < 4; i++) {
        const int rr = 4 * i + (lane >> 3);
        const uint4 v = lds128(tile_rows + rr * 128 + (((lane & 7) ^ (rr & 7)) << 4));
        stg128(gdst + rr * DM + (lane & 7) * 8, v.x, v.y, v.z, v.w);
    }
}

template <bool NORM>
__device__ __forceinline__ void feature_map(const uint32_t* a, const uint32_t* wb, float c0, float c1, uint32_t* plus, uint32_t* minus, float* rs) {
    float p[8];
    mma16816_z(p, a, wb[0], wb[1]);
    mma16816_z(p + 4, a, wb[2], wb[3]);
    const uint32_t P0 = pack_bf16(p[0], p[2]), P1 = pack_bf16(p[1], p[3]), P2 = pack_bf16(p[4], p[6]), P3 = pack_bf16(p[5], p[7]);
    uint32_t mx = max2(max2(P0, P1), max2(P2, P3)), mn = min2(min2(P0, P1), min2(P2, P3));
#pragma unroll
    for (int s = 1; s <= 2; s <<= 1) {
        mx = max2(mx, __shfl_xor_sync(0xffffffffu, mx, s));
        mn = min2(mn, __shfl_xor_sync(0xffffffffu, mn, s));
    }
    const float mx0 = bf_lo(mx) * c0, mx1 = bf_hi(mx) * c1, mn0 = bf_lo(mn) * c0, mn1 = bf_hi(mn) * c1;
    p[0] = bf_lo(P0); p[2] = bf_hi(P0); p[1] = bf_lo(P1); p[3] = bf_hi(P1);
    p[4] = bf_lo(P2); p[6] = bf_hi(P2); p[5] = bf_lo(P3); p[7] = bf_hi(P3);
    float ep[8], em[8];
#pragma unroll
    for (int i = 0; i < 8; i++) {
        const bool r1 = (i & 2);
        ep[i] = ex2(fmaf(p[i], r1 ? c1 : c0, r1 ? -mx1 : -mx0));
        em[i] = ex2(fmaf(p[i], r1 ? -c1 : -c0, r1 ? mn1 : mn0));
    }
    float sp[4], sm[4];
#pragma unroll
    for (int i = 0; i < 4; i++) { plus[i] = pack_bf16(ep[2 * i], ep[2 * i + 1]); minus[i] = pack_bf16(em[2 * i], em[2 * i + 1]); }
    mma16816_z(sp, plus, 0x3f803f80u, 0x3f803f80u);
    mma16816_z(sm, minus, 0x3f803f80u, 0x3f803f80u);
    rs[0] = rcp(sp[0]); rs[1] = rcp(sp[2]); rs[2] = rcp(sm[0]); rs[3] = rcp(sm[2]);
    if (NORM) {
#pragma unroll
        for (int i = 0; i < 4; i++) {
            plus[i] = pack_bf16(ep[2 * i] * rs[i & 1], ep[2 * i + 1] * rs[i & 1]);
            minus[i] = pack_bf16(em[2 * i] * rs[2 + (i & 1)], em[2 * i + 1] * rs[2 + (i & 1)]);
        }
    }
}

template <bool SCALE>
__device__ __forceinline__ void ln_frag(const float* acc, uint32_t cs_addr, float rs0, float nm0, float rs1, float nm1, uint32_t* a) {
    const float2 c0 = lds_f2(cs_addr), c1 = lds_f2(cs_addr + 32);
    const float s0 = SCALE ? rs0 : 1.f, s1 = SCALE ? rs1 : 1.f;
    a[0] = pack_bf16(fmaf(nm0, c0.x, acc[0]) * s0, fmaf(nm0, c0.y, acc[1]) * s0);
    a[1] = pack_bf16(fmaf(nm1, c0.x, acc[2]) * s1, fmaf(nm1, c0.y, acc[3]) * s1);
    a[2] = pack_bf16(fmaf(nm0, c1.x, acc[4]) * s0, fmaf(nm0, c1.y, acc[5]) * s0);
    a[3] = pack_bf16(fmaf(nm1, c1.x, acc[6]) * s1, fmaf(nm1, c1.y, acc[7]) * s1);
}

__device__ __forceinline__ uint32_t hh_pair(const float* ag, float4 cs, float nmean) {
    const float g0 = fmaf(nmean, cs.x, ag[0]), g1 = fmaf(nmean, cs.y, ag[1]);
    const float u0 = fmaf(nmean, cs.z, ag[32]), u1 = fmaf(nmean, cs.w, ag[33]);
    return pack_bf16(g0 * u0, g1 * u1);
}

struct Ring {
    int slot; uint32_t phase;
    __device__ __forceinline__ void adv() { if (++slot == NB) { slot = 0; phase ^= 1; } }
};

__global__ void __launch_bounds__(NTHREADS, 1) fused_kernel(const __grid_constant__ Params P) {
    extern __shared__ __align__(1024) uint8_t smem_raw[];
    const uint32_t sb = smem_u32(smem_raw);
    const int tid = threadIdx.x, lane = tid & 31;
    const int warp = __shfl_sync(0xffffffffu, tid >> 5, 0);
    const int m = blockIdx.x >> 3, j = blockIdx.x & 7;

    if (warp == 8) {
        if (lane < NB) {
            const uint32_t full = sb + BAR_FULLB + 8 * lane;
            mbar_init(full, 1); mbar_init(sb + BAR_EMPTYB + 8 * lane, 8);
            asm volatile("fence.mbarrier_init.release.cluster;" ::: "memory");
            mbar_expect_tx(full, SLOT);
            tma3d(sb + OFF_B + lane * SLOT, &P.twkv, full, 64 * j, 64 * lane, 1);
        }
    } else if (warp == 9) {
        if (lane < 8) {
            const uint32_t full = sb + BAR_FULLA + 8 * lane;
            mbar_init(full, 1); mbar_init(sb + BAR_EMPTYA + 8 * lane, 8);
            asm volatile("fence.mbarrier_init.release.cluster;" ::: "memory");
            mbar_expect_tx(full, SLOT);
            tma2d(sb + OFF_A + lane * SLOT, &P.tx, full, 64 * lane, 128 * m);
        }
    } else if (warp == 10) {
        if (lane < 14) mbar_init(sb + BAR_CS1 + 8 * lane, lane == 0 ? 32 : (lane == 1 ? 160 : 4));
        trap_if_gt(sb & 1023, 0);
    }
    TL(0, tid == 0); TLG(0, tid == 0);
    __syncthreads();

    float* const acc_j = g_acc + j * ACC_SIZE;
    unsigned* const cnt_j = g_cnt + j * 128;

    if (warp >= 8) {
        asm volatile("setmaxnreg.dec.sync.aligned.u32 72;");
        if (warp == 8) {
            if (lane == 0) {
                Ring r{0, 1};
#pragma unroll 1
                for (int i = 6; i < 56; i++) {
                    const uint32_t full = sb + BAR_FULLB + 8 * r.slot, dst = sb + OFF_B + r.slot * SLOT;
                    mbar_wait(sb + BAR_EMPTYB + 8 * r.slot, r.phase ^ 1);
                    if (i >= 8 && i < 12) {
                        mbar_arrive(full);
                    } else {
                        mbar_expect_tx(full, SLOT);
                        if (i < 8) {
                            tma3d(dst, &P.twkv, full, 64 * j, 64 * i, 1);
                        } else if (i < 20) {
                            tma2d(dst, i < 16 ? &P.twq : &P.two, full, 64 * j, 128 * (i & 3));
                        } else if (i < 44) {
                            const int c = (i - 20) >> 3, kt = (i - 20) & 7;
                            tma2d(dst, &P.twg, full, 176 * j + 64 * c, 64 * kt);
                            tma2d(dst + 8192, &P.twu, full, 176 * j + 64 * c, 64 * kt);
                        } else {
                            const int c = (i - 44) >> 2, jj = (i & 3) * 2;
                            tma2d(dst, &P.twd, full, 64 * j, 176 * jj + 64 * c);
                            tma2d(dst + 8192, &P.twd, full, 64 * j, 176 * (jj + 1) + 64 * c);
                        }
                    }
                    r.adv();
                }
            }
        } else {
            const unsigned epoch = ld_acquire(&g_epoch) + 1;
            if (m == 0 && warp == 10) {
                for (int i = lane; i < ACC_SIZE / 4; i += 32) stg128(acc_j + 4 * i, 0, 0, 0, 0);
                __syncwarp();
                if (lane == 0) { fence_gpu(); st_relaxed(cnt_j + 0, epoch); }
                __syncwarp();
            }
#pragma unroll 1
            for (int job = 0; job < (warp == 9 ? 2 : 1); job++) {
                const bool ffn = warp == 9;
                const int col = ffn ? 176 * j + 8 * lane : (lane >> 3) * DM + 64 * j + 8 * (lane & 7);
                const bool act = ffn ? (lane < 22 && col < FF) : lane < 24;
                const int pitch = ffn ? FF : 3 * DM;
                const __nv_bfloat16* src = (ffn ? (job ? P.wu : P.wg) : P.wqkv) + (size_t)(32 * m + (warp == 11 ? 16 : 0)) * pitch + col;
                float s[8];
#pragma unroll
                for (int i = 0; i < 8; i++) s[i] = 0.f;
                if (act) {
#pragma unroll 1
                    for (int b = 0; b < (ffn ? 4 : 2); b++) {
                        uint4 v[8];
#pragma unroll
                        for (int i = 0; i < 8; i++) v[i] = ldg_nc(src + (8 * b + i) * pitch);
#pragma unroll
                        for (int i = 0; i < 8; i++) {
                            s[0] += bf_lo(v[i].x); s[1] += bf_hi(v[i].x); s[2] += bf_lo(v[i].y); s[3] += bf_hi(v[i].y);
                            s[4] += bf_lo(v[i].z); s[5] += bf_hi(v[i].z); s[6] += bf_lo(v[i].w); s[7] += bf_hi(v[i].w);
                        }
                    }
                }
                wait_count_warp(cnt_j + 0, epoch);
                if (act) {
                    float* dst = acc_j + (ffn ? ACC_CS3 + job * 192 : ACC_CS1) + 8 * lane;
                    red_f32x4(dst, s[0], s[1], s[2], s[3]);
                    red_f32x4(dst + 4, s[4], s[5], s[6], s[7]);
                }
                __syncwarp();
                if (lane == 0) { fence_gpu(); red_relaxed(cnt_j + (ffn ? 64 : 32), 1); }
                __syncwarp();
            }
            if (warp == 9) {
                int r = (lane < 8) ? 1 : 6;
                uint32_t it = 0;
                while (__any_sync(0xffffffffu, r < 6)) {
                    if (r < 6 && mbar_test(sb + BAR_EMPTYA + 8 * lane, (r - 1) & 1)) {
                        const uint32_t full = sb + BAR_FULLA + 8 * lane;
                        if (r < 3 && lane == j) {
                            mbar_arrive(full);
                            r++;
                        } else {
                            const uint2 f = ld_acquire2(g_flag + (m * 5 + (r - 1)) * 32 + 2 * lane);
                            if (f.x == epoch && f.y == epoch) {
                                fence_async_global();
                                mbar_expect_tx(full, SLOT);
                                const CUtensorMap* tm = r == 1 ? &P.to : (r == 2 ? &P.th : &P.thh);
                                const int c0 = r < 3 ? 64 * lane : 176 * lane + 64 * (r - 3);
                                tma2d(sb + OFF_A + lane * SLOT, tm, full, c0, 128 * m);
                                r++;
                            }
                        }
                    }
                    trap_if_gt(++it, 1u << 24);
                }
            } else {
                const int a = warp - 10;
                if (a == 0) {
                    wait_count_warp(cnt_j + 32, epoch * 32);
#pragma unroll
                    for (int i = 0; i < 3; i++) {
                        const float2 c = ld_l2_f2(acc_j + ACC_CS1 + 64 * i + 2 * lane);
                        sts_f2(sb + OFF_CS1 + (64 * i + 2 * lane) * 4, c.x, c.y);
                    }
                    mbar_arrive(sb + BAR_CS1);
                } else if (lane == 0) {
                    prefetch_l2(P.wo + (size_t)blockIdx.x * 2048, 4096);
                    prefetch_l2(P.wd + (size_t)blockIdx.x * 5504, 11008);
                }
#pragma unroll 1
                for (int ev = 0; ev < 6; ev += (ev >= 2 + a) ? 2 - (ev == 2) : 1 + (ev == 2)) {
                    if (lane == 0) {
                        mbar_wait(sb + BAR_PUB + 8 * (a * 6 + ev), 0);
                        fence_gpu();
                        unsigned* fl = g_flag + (m * 5 + (ev - 1)) * 32 + 2 * j;
                        if (ev == 0) red_relaxed(cnt_j + 96, 1);
                        else {
                            st_relaxed(fl + a, epoch);
                            if (ev >= 3) st_relaxed(fl + (a ^ 1), epoch);
                        }
                    }
                    __syncwarp();
                    if (ev == 2 && a == 0) {
                        wait_count_warp(cnt_j + 64, epoch * 32);
#pragma unroll
                        for (int i = 0; i < 3; i++) {
                            const float2 cg = ld_l2_f2(acc_j + ACC_CS3 + 64 * i + 2 * lane);
                            const float2 cu = ld_l2_f2(acc_j + ACC_CS3 + 192 + 64 * i + 2 * lane);
                            sts128(sb + OFF_CS3 + (32 * i + lane) * 16, __float_as_uint(cg.x), __float_as_uint(cg.y),
                                   __float_as_uint(cu.x), __float_as_uint(cu.y));
                        }
                        mbar_arrive(sb + BAR_CS3);
                    }
                }
            }
        }
    } else {
        asm volatile("setmaxnreg.inc.sync.aligned.u32 216;");
        const int w = warp >> 2, wv = warp & 3, g = lane >> 2, q = lane & 3;
        const int row_w = 128 * m + 16 * warp;
        const uint32_t sa = sb + OFF_A + w * 8192;
        const uint32_t dA = desc_lo(sa), dB = desc_lo(sb + OFF_B);
        const uint32_t pub = sb + BAR_PUB + 48 * w;
        const bool l0 = lane == 0;
        Ring rg{0, 0};
        int prev = 0;
        const unsigned epoch = ld_acquire(&g_epoch) + 1;

        {
            const int row = 128 * m + 16 * j + 2 * warp + (lane >> 4);
            uint4 v[4];
#pragma unroll
            for (int i = 0; i < 4; i++) v[i] = ldg_nc(P.x + (size_t)row * DM + ((lane & 15) + 16 * i) * 8);
            float f[32];
#pragma unroll
            for (int i = 0; i < 4; i++) {
                f[8 * i] = bf_lo(v[i].x); f[8 * i + 1] = bf_hi(v[i].x); f[8 * i + 2] = bf_lo(v[i].y); f[8 * i + 3] = bf_hi(v[i].y);
                f[8 * i + 4] = bf_lo(v[i].z); f[8 * i + 5] = bf_hi(v[i].z); f[8 * i + 6] = bf_lo(v[i].w); f[8 * i + 7] = bf_hi(v[i].w);
            }
            float s0 = 0.f, s1 = 0.f;
#pragma unroll
            for (int i = 0; i < 16; i++) { s0 += f[2 * i]; s1 += f[2 * i + 1]; }
            s0 += s1;
#pragma unroll
            for (int o = 8; o; o >>= 1) s0 += __shfl_xor_sync(0xffffffffu, s0, o);
            const float mean = s0 * (1.f / DM);
            s0 = 0.f; s1 = 0.f;
#pragma unroll
            for (int i = 0; i < 16; i++) {
                const float d0 = f[2 * i] - mean, d1 = f[2 * i + 1] - mean;
                s0 = fmaf(d0, d0, s0); s1 = fmaf(d1, d1, s1);
            }
            s0 += s1;
#pragma unroll
            for (int o = 8; o; o >>= 1) s0 += __shfl_xor_sync(0xffffffffu, s0, o);
            const float rs = rsqrtf(s0 * (1.f / DM) + 1e-5f);
            st_tagged_if(g_xstat + 2 * row, rs, -mean, epoch, (lane & 15) == 0);
        }
        uint32_t wb[16];
        {
            const unsigned short* wp = reinterpret_cast<const unsigned short*>(P.wphi) + (4 * j) * 256 + 2 * q * 16 + g;
#pragma unroll
            for (int i = 0; i < 16; i++) {
                const unsigned short* p = wp + (i >> 2) * 256 + (i & 1) * 128 + ((i >> 1) & 1) * 8;
                wb[i] = (uint32_t)__ldg(p) | ((uint32_t)__ldg(p + 16) << 16);
            }
        }
        constexpr float L2E = 1.4426950408889634f;
        uint32_t fp[16], fm[16];
        float fr[16];
        float rs0, nm0, rs1, nm1;
        {
            float acc[64];
#pragma unroll 1
            for (int kt = 0; kt < 8; kt++) {
                mbar_waitc(sb + BAR_FULLA + 8 * kt, 0);
                mbar_waitc(sb + BAR_FULLB + 8 * rg.slot, rg.phase);
                TL(20 + kt, tid == 0);
                wg_fence();
#pragma unroll
                for (int k = 0; k < 4; k++)
                    wgmma_n128(acc, dA + ((kt * SLOT + k * 32) >> 4), dB + ((rg.slot * SLOT + k * 2048) >> 4), (kt | k) != 0);
                wg_commit();
                wg_wait<1>();
                mbar_arrive_if(sb + BAR_EMPTYB + 8 * prev, l0 && kt > 0);
                prev = rg.slot; rg.adv();
            }
            {
                uint4 a, b;
                uint32_t it = 0;
                do {
                    a = ld_tagged(g_xstat + 2 * (row_w + g));
                    b = ld_tagged(g_xstat + 2 * (row_w + g + 8));
                    trap_if_gt(++it, 1u << 22);
                } while (__any_sync(0xffffffffu, a.y != epoch || a.w != epoch || b.y != epoch || b.w != epoch));
                rs0 = __uint_as_float(a.x); nm0 = __uint_as_float(a.z); rs1 = __uint_as_float(b.x); nm1 = __uint_as_float(b.z);
            }
            mbar_waitc(sb + BAR_CS1, 0);
            wg_wait<0>();
            fence_acc<64>(acc);
            mbar_arrive_if(sb + BAR_EMPTYB + 8 * prev, l0);
            TL(2, tid == 0);
#pragma unroll
            for (int i = 2; i < 6; i++) mbar_waitc(sb + BAR_FULLB + 8 * i, 1);
            const int lrow = 16 * warp + (lane & 15), ch = lane >> 4, sw = lane & 7;
            const uint32_t st = sb + OFF_B + 2 * SLOT + lrow * 128;
            uint32_t ka[16];
#pragma unroll
            for (int hh = 0; hh < 4; hh++)
                ln_frag<false>(acc + 8 * hh, sb + OFF_CS1 + (64 + 16 * hh + 2 * q) * 4, rs0, nm0, rs1, nm1, ka + 4 * hh);
#pragma unroll
            for (int hh = 0; hh < 4; hh++) {
                uint32_t a[4];
                ln_frag<true>(acc + 32 + 8 * hh, sb + OFF_CS1 + (128 + 16 * hh + 2 * q) * 4, rs0, nm0, rs1, nm1, a);
                stsm4(st + (2 + (hh >> 1)) * SLOT + (((2 * (hh & 1) + ch) ^ sw) << 4), a[0], a[1], a[2], a[3]);
            }
#pragma unroll
            for (int hh = 0; hh < 4; hh++) feature_map<true>(ka + 4 * hh, wb + 4 * hh, rs0 * L2E, rs1 * L2E, fp + 4 * hh, fm + 4 * hh, fr);
#pragma unroll
            for (int hh = 0; hh < 4; hh++) {
                stsm4(st + (hh >> 1) * SLOT + (((4 * (hh & 1) + ch) ^ sw) << 4), fp[4 * hh], fp[4 * hh + 1], fp[4 * hh + 2], fp[4 * hh + 3]);
                stsm4(st + (hh >> 1) * SLOT + (((4 * (hh & 1) + 2 + ch) ^ sw) << 4), fm[4 * hh], fm[4 * hh + 1], fm[4 * hh + 2], fm[4 * hh + 3]);
            }
            stsm4(st + (2 + ch) * SLOT + ((4 ^ sw) << 4), 0x3f803f80u, 0x3f803f80u, 0x3f803f80u, 0x3f803f80u);
            fence_async_smem();
            bar_sync(1, 256);
            float kvd[20];
            wg_fence();
#pragma unroll
            for (int k = 0; k < 8; k++)
                wgmma_n40_tt(kvd, dB + (((2 + w) * SLOT + k * 2048) >> 4), dB + (((4 + w) * SLOT + k * 2048) >> 4), k != 0);
            wg_commit();
            wg_wait<0>();
            fence_acc<20>(kvd);
            const bool h1 = wv >= 2;
            const int f = 16 * warp + g;
            float* kvp = acc_j + ACC_KV + f * 16 + 2 * q;
            red_f32x2(kvp, h1 ? kvd[8] : kvd[0], h1 ? kvd[9] : kvd[1]);
            red_f32x2(kvp + 128, h1 ? kvd[10] : kvd[2], h1 ? kvd[11] : kvd[3]);
            red_f32x2(kvp + 8, h1 ? kvd[12] : kvd[4], h1 ? kvd[13] : kvd[5]);
            red_f32x2(kvp + 136, h1 ? kvd[14] : kvd[6], h1 ? kvd[15] : kvd[7]);
            red_f32_if(acc_j + ACC_Z + f + 8 * (q & 1), q ? kvd[18] : kvd[16], q < 2);
            __syncwarp();
            mbar_arrive_if(pub, l0);
            mbar_arrive_if(sb + BAR_EMPTYB + 8 * (2 + (lane & 3)), lane < 4);
            TL(3, tid == 0);
        }
        uint32_t res_lo[8], res_hi[8];
        const uint32_t own_rows = sb + OFF_A + j * SLOT + warp * 2048;
        {
            float acc[32];
            rg.slot = 0; rg.phase = 0;
#pragma unroll 1
            for (int b = 0; b < 4; b++) {
                mbar_waitc(sb + BAR_FULLB + 8 * rg.slot, rg.phase);
                wg_fence();
#pragma unroll
                for (int k = 0; k < 8; k++)
                    wgmma_n64(acc, dA + (((2 * b + (k >> 2)) * SLOT + (k & 3) * 32) >> 4), dB + ((rg.slot * SLOT + k * 2048) >> 4), (b | k) != 0);
                wg_commit();
                wg_wait<1>();
                mbar_arrive_if(sb + BAR_EMPTYB + 8 * prev, l0 && b > 0);
                prev = rg.slot; rg.adv();
            }
            wg_wait<0>();
            fence_acc<32>(acc);
            mbar_arrive_if(sb + BAR_EMPTYB + 8 * prev, l0);
            mbar_arrive_if(sb + BAR_EMPTYA + 8 * (lane & 7), lane < 8 && (lane | 1) != (j | 1));
            TL(4, tid == 0);
            uint32_t qa[16];
#pragma unroll
            for (int hh = 0; hh < 4; hh++)
                ln_frag<false>(acc + 8 * hh, sb + OFF_CS1 + (16 * hh + 2 * q) * 4, rs0, nm0, rs1, nm1, qa + 4 * hh);
#pragma unroll
            for (int hh = 0; hh < 4; hh++) feature_map<false>(qa + 4 * hh, wb + 4 * hh, rs0 * L2E, rs1 * L2E, fp + 4 * hh, fm + 4 * hh, fr + 4 * hh);
#pragma unroll
            for (int b = 0; b < 4; b++)
                ldsm4(own_rows + (lane & 15) * 128 + (((2 * b + (lane >> 4)) ^ (lane & 7)) << 4),
                      res_lo[2 * b], res_hi[2 * b], res_lo[2 * b + 1], res_hi[2 * b + 1]);
            TL(5, tid == 0);
            if (warp == 0) wait_count_warp(cnt_j + 96, epoch * 32);
            TL(6, tid == 0);
            bar_sync(1, 256);
            const uint32_t kvs = sb + OFF_A + (j ^ 1) * SLOT;
            {
                const float4 a0 = ld_l2_f4(acc_j + ACC_KV + 4 * tid), a1 = ld_l2_f4(acc_j + ACC_KV + 4 * (tid + 256));
                const float zz = ld_l2_f(acc_j + ACC_Z + (tid & 127));
                sts64(kvs + (tid >> 2) * 48 + (tid & 3) * 8, pack_bf16(a0.x, a0.y), pack_bf16(a0.z, a0.w));
                sts64(kvs + ((tid >> 2) + 64) * 48 + (tid & 3) * 8, pack_bf16(a1.x, a1.y), pack_bf16(a1.z, a1.w));
                const uint32_t z2 = pack_bf16(zz, zz);
                sts64(kvs + (tid & 127) * 48 + 32 + w * 8, z2, z2);
            }
            bar_sync(1, 256);
            uint32_t o_lo[8], o_hi[8];
#pragma unroll
            for (int hh = 0; hh < 4; hh++) {
                uint32_t b[8], zb[4];
                const uint32_t base = kvs + hh * 32 * 48;
                ldsm4t(base + (lane & 15) * 48 + (lane >> 4) * 16, b[0], b[1], b[2], b[3]);
                ldsm4t(base + (16 + (lane & 15)) * 48 + (lane >> 4) * 16, b[4], b[5], b[6], b[7]);
                ldsm4t(base + lane * 48 + 32, zb[0], zb[1], zb[2], zb[3]);
                float n0[4], n1[4], dn[4], m0[4], m1[4], dm[4];
                mma16816_z(n0, fp + 4 * hh, b[0], b[1]); mma16816_z(n1, fp + 4 * hh, b[2], b[3]); mma16816_z(dn, fp + 4 * hh, zb[0], zb[1]);
                mma16816_z(m0, fm + 4 * hh, b[4], b[5]); mma16816_z(m1, fm + 4 * hh, b[6], b[7]); mma16816_z(dm, fm + 4 * hh, zb[2], zb[3]);
                const float* r = fr + 4 * hh;
                const float i0 = rcp(fmaf(dn[0], r[0], fmaf(dm[0], r[2], 1e-6f))), i1 = rcp(fmaf(dn[2], r[1], fmaf(dm[2], r[3], 1e-6f)));
                const float p0 = r[0] * i0, q0 = r[2] * i0, p1 = r[1] * i1, q1 = r[3] * i1;
                o_lo[2 * hh] = pack_bf16(fmaf(n0[0], p0, m0[0] * q0), fmaf(n0[1], p0, m0[1] * q0));
                o_hi[2 * hh] = pack_bf16(fmaf(n0[2], p1, m0[2] * q1), fmaf(n0[3], p1, m0[3] * q1));
                o_lo[2 * hh + 1] = pack_bf16(fmaf(n1[0], p0, m1[0] * q0), fmaf(n1[1], p0, m1[1] * q0));
                o_hi[2 * hh + 1] = pack_bf16(fmaf(n1[2], p1, m1[2] * q1), fmaf(n1[3], p1, m1[3] * q1));
            }
            store_tile(own_rows, g_o + (size_t)row_w * DM + 64 * j, o_lo, o_hi, lane);
            fence_async_smem();
            __syncwarp();
            mbar_arrive_if(pub + 8, l0);
            mbar_arrive_if(sb + BAR_EMPTYA + 8 * (j ^ (lane & 1)), lane < 2);
            TL(7, tid == 0);
        }
        {
            float acc[32];
#pragma unroll
            for (int t = 0; t < 8; t++) {
                acc[4 * t] = bf_lo(res_lo[t]); acc[4 * t + 1] = bf_hi(res_lo[t]);
                acc[4 * t + 2] = bf_lo(res_hi[t]); acc[4 * t + 3] = bf_hi(res_hi[t]);
            }
            fence_acc<32>(acc);
#pragma unroll 1
            for (int kp = 0; kp < 4; kp++) {
                mbar_waitc(sb + BAR_FULLB + 8 * rg.slot, rg.phase);
#pragma unroll
                for (int hf = 0; hf < 2; hf++) {
                    const int kt = 2 * kp + hf;
                    mbar_waitc(sb + BAR_FULLA + 8 * kt, 1);
                    TL(8, kt == 0 && tid == 0);
                    wg_fence();
#pragma unroll
                    for (int k = 0; k < 4; k++)
                        wgmma_n64(acc, dA + ((kt * SLOT + k * 32) >> 4), dB + ((rg.slot * SLOT + (hf * 4 + k) * 2048) >> 4), 1);
                    wg_commit();
                    wg_wait<1>();
                    mbar_arrive_if(sb + BAR_EMPTYA + 8 * ((kt + 7) & 7), l0 && kt > 0 && kt - 1 != j);
                    if (hf == 0) mbar_arrive_if(sb + BAR_EMPTYB + 8 * prev, l0 && kt > 0);
                }
                prev = rg.slot; rg.adv();
            }
            wg_wait<0>();
            fence_acc<32>(acc);
            mbar_arrive_if(sb + BAR_EMPTYA + 8 * 7, l0 && j != 7);
            mbar_arrive_if(sb + BAR_EMPTYB + 8 * prev, l0);
            TL(9, tid == 0);
            float s0 = 0.f, s1 = 0.f;
#pragma unroll
            for (int t = 0; t < 8; t++) {
                res_lo[t] = pack_bf16(acc[4 * t], acc[4 * t + 1]);
                res_hi[t] = pack_bf16(acc[4 * t + 2], acc[4 * t + 3]);
                s0 += acc[4 * t] + acc[4 * t + 1];
                s1 += acc[4 * t + 2] + acc[4 * t + 3];
            }
            store_tile(own_rows, g_h + (size_t)row_w * DM + 64 * j, res_lo, res_hi, lane);
            s0 += __shfl_xor_sync(0xffffffffu, s0, 1); s1 += __shfl_xor_sync(0xffffffffu, s1, 1);
            s0 += __shfl_xor_sync(0xffffffffu, s0, 2); s1 += __shfl_xor_sync(0xffffffffu, s1, 2);
            const float mu0 = s0 * (1.f / 64), mu1 = s1 * (1.f / 64);
            float q0 = 0.f, q1 = 0.f;
#pragma unroll
            for (int t = 0; t < 8; t++) {
                float d;
                d = acc[4 * t] - mu0; q0 = fmaf(d, d, q0);
                d = acc[4 * t + 1] - mu0; q0 = fmaf(d, d, q0);
                d = acc[4 * t + 2] - mu1; q1 = fmaf(d, d, q1);
                d = acc[4 * t + 3] - mu1; q1 = fmaf(d, d, q1);
            }
            q0 += __shfl_xor_sync(0xffffffffu, q0, 1); q1 += __shfl_xor_sync(0xffffffffu, q1, 1);
            q0 += __shfl_xor_sync(0xffffffffu, q0, 2); q1 += __shfl_xor_sync(0xffffffffu, q1, 2);
            stg_f2_if(g_hstat + (row_w + g + 8 * (q & 1)) * 16 + 2 * j, q ? mu1 : mu0, q ? q1 : q0, q < 2);
            fence_async_smem();
            __syncwarp();
            mbar_arrive_if(pub + 16, l0);
            mbar_arrive_if(sb + BAR_EMPTYA + 8 * j, l0);
            TL(10, tid == 0);
        }
        if (w == 1) {
#pragma unroll 1
            for (int kt = 0; kt < 8; kt++) mbar_waitc(sb + BAR_FULLA + 8 * kt, 0);
            const float* sp = g_hstat + (128 * m + (tid & 127)) * 16;
            float4 v[4];
#pragma unroll
            for (int i = 0; i < 4; i++) v[i] = ld_l2_f4(sp + 4 * i);
            float mean = 0.f;
#pragma unroll
            for (int i = 0; i < 4; i++) mean += v[i].x + v[i].z;
            mean *= 0.125f;
            float m2 = 0.f, dv = 0.f;
#pragma unroll
            for (int i = 0; i < 4; i++) {
                m2 += v[i].y + v[i].w;
                dv = fmaf(v[i].x - mean, v[i].x - mean, dv); dv = fmaf(v[i].z - mean, v[i].z - mean, dv);
            }
            sts_f2(sb + OFF_CS1 + (tid & 127) * 8, -mean, __fdividef(1.f, fmaf(dv, 64.f, m2) * (1.f / DM) + 1e-5f));
            mbar_arrive(sb + BAR_CS3);
        }
        {
            float acc0[64], acc1[64];
            const uint32_t dA0 = desc_lo(sb + OFF_A);
#pragma unroll 1
            for (int c = w; c < 3; c += 2) {
                if (c > 0) bar_sync(1 + c, 256);
                rg.slot = (c == 2) ? 0 : 2 + 2 * c; rg.phase = (c == 0);
#pragma unroll 1
                for (int kt = 0; kt < 8; kt++) {
                    mbar_waitc(sb + BAR_FULLA + 8 * kt, 0);
                    mbar_waitc(sb + BAR_FULLB + 8 * rg.slot, rg.phase);
                    TL(30 + 8 * c + kt, (tid & 127) == 0);
                    wg_fence();
#pragma unroll
                    for (int k = 0; k < 4; k++) {
                        const uint32_t db = dB + ((rg.slot * SLOT + k * 2048) >> 4);
                        wgmma_n128(acc0, dA0 + ((kt * SLOT + k * 32) >> 4), db, (kt | k) != 0);
                        wgmma_n128(acc1, dA0 + ((kt * SLOT + 8192 + k * 32) >> 4), db, (kt | k) != 0);
                    }
                    wg_commit();
                    wg_wait<1>();
                    mbar_arrive_n_if(sb + BAR_EMPTYB + 8 * prev, 2, l0 && kt > 0);
                    mbar_arrive_if(sb + BAR_EMPTYA + 8 * ((kt + 7) & 7), l0 && kt > 0 && c > 0);
                    prev = rg.slot; rg.adv();
                }
                bar_arrive(2 + c, 256);
                mbar_waitc(sb + BAR_CS3, 0);
                float nm[4];
#pragma unroll
                for (int i = 0; i < 4; i++) nm[i] = lds_f2(sb + OFF_CS1 + (64 * (i >> 1) + 16 * wv + g + 8 * (i & 1)) * 8).x;
                wg_wait<0>();
                fence_acc<64>(acc0); fence_acc<64>(acc1);
                mbar_arrive_n_if(sb + BAR_EMPTYB + 8 * prev, 2, l0);
                mbar_arrive_if(sb + BAR_EMPTYA + 8 * 7, l0 && c > 0);
                TL(11 + c, (tid & 127) == 0);
                __nv_bfloat16* hp = g_hh + (size_t)(128 * m + 16 * wv + g) * FFP + 176 * j + 64 * c + (q & 1) * 8 + (q >> 1) * 4;
#pragma unroll
                for (int tp = 0; tp < 4; tp++) {
                    if (tp < 3 || c < 2) {
                        const uint32_t ca = sb + OFF_CS3 + (32 * c + 8 * tp + q) * 16;
                        const float4 c0 = lds_f4(ca), c1 = lds_f4(ca + 64);
                        store_pair(hp + 16 * tp, hh_pair(acc0 + 8 * tp, c0, nm[0]), hh_pair(acc0 + 8 * tp + 4, c1, nm[0]), q & 1);
                        store_pair(hp + 8 * FFP + 16 * tp, hh_pair(acc0 + 8 * tp + 2, c0, nm[1]), hh_pair(acc0 + 8 * tp + 6, c1, nm[1]), q & 1);
                        store_pair(hp + 64 * FFP + 16 * tp, hh_pair(acc1 + 8 * tp, c0, nm[2]), hh_pair(acc1 + 8 * tp + 4, c1, nm[2]), q & 1);
                        store_pair(hp + 72 * FFP + 16 * tp, hh_pair(acc1 + 8 * tp + 2, c0, nm[3]), hh_pair(acc1 + 8 * tp + 6, c1, nm[3]), q & 1);
                    }
                }
                __syncwarp();
                mbar_arrive_if(pub + 24 + 8 * c, l0);
                TL(54 + c, (tid & 127) == 0);
            }
            if (w == 1) bar_sync(4, 256);
        }
        {
            float acc[32];
            rg.slot = 2; rg.phase = 1;
#define KT_P4(T, HF, NK)                                                                                    \
    do {                                                                                                    \
        const int s_ = (T) & 7;                                                                             \
        if (!(HF)) mbar_waitc(sb + BAR_FULLB + 8 * rg.slot, rg.phase);                                       \
        mbar_waitc(sb + BAR_FULLA + 8 * s_, (((T) >> 3) + 1) & 1);                                           \
        wg_fence();                                                                                         \
        _Pragma("unroll") for (int k = 0; k < (NK); k++)                                                    \
            wgmma_n64(acc, dA + ((s_ * SLOT + k * 32) >> 4), dB + ((rg.slot * SLOT + (HF) * 8192 + k * 2048) >> 4), ((T) | k) != 0); \
        wg_commit();                                                                                        \
        wg_wait<1>();                                                                                       \
        mbar_arrive_if(sb + BAR_EMPTYA + 8 * (((T) + 7) & 7), l0 && (T) > 0);                               \
        if (!(HF)) mbar_arrive_if(sb + BAR_EMPTYB + 8 * prev, l0 && (T) > 0);                               \
        if (HF) { prev = rg.slot; rg.adv(); }                                                               \
    } while (0)
#pragma unroll 1
            for (int t = 0; t < 16; t += 2) { KT_P4(t, 0, 4); KT_P4(t + 1, 1, 4); }
            TL(14, tid == 0);
#pragma unroll 1
            for (int t = 16; t < 24; t += 2) { KT_P4(t, 0, 3); KT_P4(t + 1, 1, 3); }
            wg_wait<0>();
            fence_acc<32>(acc);
            TL(15, tid == 0);
            const float r0 = lds_f2(sb + OFF_CS1 + (16 * warp + g) * 8).y, r1 = lds_f2(sb + OFF_CS1 + (16 * warp + g + 8) * 8).y;
#pragma unroll
            for (int t = 0; t < 8; t++) {
                res_lo[t] = pack_bf16(fmaf(acc[4 * t], r0, bf_lo(res_lo[t])), fmaf(acc[4 * t + 1], r0, bf_hi(res_lo[t])));
                res_hi[t] = pack_bf16(fmaf(acc[4 * t + 2], r1, bf_lo(res_hi[t])), fmaf(acc[4 * t + 3], r1, bf_hi(res_hi[t])));
            }
            store_tile(own_rows, P.out + (size_t)row_w * DM + 64 * j, res_lo, res_hi, lane);
            if (tid == 0 && blockIdx.x == 0) g_epoch = epoch;
            TL(16, tid == 0); TLG(1, tid == 0);
        }
    }
}

typedef CUresult (*EncodeFn)(CUtensorMap*, CUtensorMapDataType, cuuint32_t, void*, const cuuint64_t*, const cuuint64_t*,
                             const cuuint32_t*, const cuuint32_t*, CUtensorMapInterleave, CUtensorMapSwizzle,
                             CUtensorMapL2promotion, CUtensorMapFloatOOBfill);

static void make_map2d(EncodeFn enc, CUtensorMap* tm, const void* base, uint64_t cols, uint64_t rows, uint64_t pitch_elems,
                       uint32_t box_rows) {
    cuuint64_t gd[2] = {cols, rows};
    cuuint64_t gs[1] = {pitch_elems * 2};
    cuuint32_t bd[2] = {64, box_rows};
    cuuint32_t es[2] = {1, 1};
    enc(tm, CU_TENSOR_MAP_DATA_TYPE_BFLOAT16, 2, const_cast<void*>(base), gd, gs, bd, es, CU_TENSOR_MAP_INTERLEAVE_NONE,
        CU_TENSOR_MAP_SWIZZLE_128B, CU_TENSOR_MAP_L2_PROMOTION_L2_256B, CU_TENSOR_MAP_FLOAT_OOB_FILL_NONE);
}

}

extern "C" void kernel_launch(void* const* d_in, const int* in_sizes, int n_in, void* d_out, int out_size) {
    using namespace hk;
    (void)in_sizes; (void)n_in; (void)out_size;
    static EncodeFn enc = nullptr;
    static void *po = nullptr, *ph = nullptr, *phh = nullptr;
    if (!enc) {
        void* fn = nullptr;
        cudaDriverEntryPointQueryResult qr;
        cudaGetDriverEntryPoint("cuTensorMapEncodeTiled", &fn, cudaEnableDefault, &qr);
        enc = (EncodeFn)fn;
        cudaGetSymbolAddress(&po, g_o);
        cudaGetSymbolAddress(&ph, g_h);
        cudaGetSymbolAddress(&phh, g_hh);
        cudaFuncSetAttribute(fused_kernel, cudaFuncAttributeMaxDynamicSharedMemorySize, SMEM_BYTES);
    }
    Params P;
    const __nv_bfloat16* x = (const __nv_bfloat16*)d_in[0];
    P.x = x;
    P.wqkv = (const __nv_bfloat16*)d_in[1];
    P.wphi = (const __nv_bfloat16*)d_in[2];
    P.wo = (const __nv_bfloat16*)d_in[3];
    P.wg = (const __nv_bfloat16*)d_in[5];
    P.wu = (const __nv_bfloat16*)d_in[6];
    P.wd = (const __nv_bfloat16*)d_in[7];
    P.out = (__nv_bfloat16*)d_out;
    make_map2d(enc, &P.tx, x, DM, SEQ, DM, 128);
    make_map2d(enc, &P.to, po, DM, SEQ, DM, 128);
    make_map2d(enc, &P.th, ph, DM, SEQ, DM, 128);
    make_map2d(enc, &P.thh, phh, FFP, SEQ, FFP, 128);
    make_map2d(enc, &P.twq, P.wqkv, 3 * DM, DM, 3 * DM, 128);
    make_map2d(enc, &P.two, P.wo, DM, DM, DM, 128);
    make_map2d(enc, &P.twg, P.wg, FF, DM, FF, 64);
    make_map2d(enc, &P.twu, P.wu, FF, DM, FF, 64);
    make_map2d(enc, &P.twd, P.wd, DM, FF, DM, 64);
    {
        cuuint64_t gd[3] = {(cuuint64_t)DM, (cuuint64_t)DM, 3};
        cuuint64_t gs[2] = {(cuuint64_t)3 * DM * 2, (cuuint64_t)DM * 2};
        cuuint32_t bd[3] = {64, 64, 2};
        cuuint32_t es[3] = {1, 1, 1};
        enc(&P.twkv, CU_TENSOR_MAP_DATA_TYPE_BFLOAT16, 3, const_cast<__nv_bfloat16*>(P.wqkv), gd, gs, bd, es,
            CU_TENSOR_MAP_INTERLEAVE_NONE, CU_TENSOR_MAP_SWIZZLE_128B, CU_TENSOR_MAP_L2_PROMOTION_L2_256B,
            CU_TENSOR_MAP_FLOAT_OOB_FILL_NONE);
    }
    fused_kernel<<<NCTA, NTHREADS, SMEM_BYTES>>>(P);
}
```

```cpp
#include <cuda_runtime.h>
#include <cuda_bf16.h>
#include <cuda.h>
#include <stdint.h>

namespace hk {

constexpr int SEQ = 2048, DM = 512, FF = 1376, FFP = 1408;
constexpr int NCTA = 128;
constexpr int NTHREADS = 384;
constexpr uint32_t SLOT = 16384;
constexpr uint32_t OFF_A = 0, OFF_B = 8 * SLOT, OFF_MISC = 14 * SLOT;
constexpr uint32_t BAR_FULLA = OFF_MISC + 0, BAR_EMPTYA = OFF_MISC + 64, BAR_FULLB = OFF_MISC + 128,
                   BAR_EMPTYB = OFF_MISC + 176, BAR_CS1 = OFF_MISC + 224, BAR_CS3 = OFF_MISC + 232,
                   BAR_PUB = OFF_MISC + 240;
constexpr uint32_t OFF_CS1 = OFF_MISC + 384;
constexpr uint32_t OFF_CS3 = OFF_CS1 + 1024;
constexpr uint32_t SMEM_BYTES = OFF_CS3 + 1536;
constexpr int NB = 6;

constexpr int ACC_KV = 0, ACC_Z = 2048, ACC_CS1 = 2176, ACC_CS3 = 2368, ACC_SIZE = 2752;

__device__ __align__(1024) __nv_bfloat16 g_o[SEQ * DM];
__device__ __align__(1024) __nv_bfloat16 g_h[SEQ * DM];
__device__ __align__(1024) __nv_bfloat16 g_hh[SEQ * FFP];
__device__ __align__(128) float g_hstat[SEQ * 16];
__device__ __align__(128) unsigned long long g_xstat[SEQ * 2];
__device__ __align__(128) float g_acc[8 * ACC_SIZE];
__device__ __align__(128) unsigned g_cnt[8 * 4 * 32];
__device__ __align__(128) unsigned g_flag[16 * 8 * 8];
__device__ unsigned g_epoch;

#define TL(i, pred) do {} while (0)
#define TLG(i, pred) do {} while (0)

struct Params {
    CUtensorMap tx, to, th, thh, twkv, twq, two, twg, twu, twd;
    const __nv_bfloat16 *x, *wqkv, *wphi, *wo, *wg, *wu, *wd;
    __nv_bfloat16* out;
};

__device__ __forceinline__ uint32_t smem_u32(const void* p) { return (uint32_t)__cvta_generic_to_shared(p); }
__device__ __forceinline__ void mbar_init(uint32_t bar, uint32_t cnt) {
    asm volatile("mbarrier.init.shared::cta.b64 [%0], %1;" ::"r"(bar), "r"(cnt) : "memory");
}
__device__ __forceinline__ void mbar_expect_tx(uint32_t bar, uint32_t bytes) {
    asm volatile("mbarrier.arrive.expect_tx.shared::cta.b64 _, [%0], %1;" ::"r"(bar), "r"(bytes) : "memory");
}
__device__ __forceinline__ void mbar_arrive(uint32_t bar) {
    asm volatile("mbarrier.arrive.shared::cta.b64 _, [%0];" ::"r"(bar) : "memory");
}
__device__ __forceinline__ void mbar_arrive_if(uint32_t bar, bool pred) {
    asm volatile("{.reg .pred p; setp.ne.u32 p, %1, 0; @p mbarrier.arrive.shared::cta.b64 _, [%0];}" ::"r"(bar), "r"((uint32_t)pred) : "memory");
}
__device__ __forceinline__ bool mbar_try(uint32_t bar, uint32_t parity) {
    uint32_t ok;
    asm volatile("{.reg .pred p; mbarrier.try_wait.parity.shared::cta.b64 p, [%1], %2; selp.u32 %0,1,0,p;}"
                 : "=r"(ok) : "r"(bar), "r"(parity) : "memory");
    return ok;
}
__device__ __forceinline__ bool mbar_test(uint32_t bar, uint32_t parity) {
    uint32_t ok;
    asm volatile("{.reg .pred p; mbarrier.test_wait.parity.shared::cta.b64 p, [%1], %2; selp.u32 %0,1,0,p;}"
                 : "=r"(ok) : "r"(bar), "r"(parity) : "memory");
    return ok;
}
__device__ __forceinline__ void trap_if_gt(uint32_t v, uint32_t lim) {
    asm volatile("{.reg .pred p; setp.gt.u32 p, %0, %1; @p trap;}" ::"r"(v), "r"(lim));
}
__device__ __forceinline__ void mbar_wait(uint32_t bar, uint32_t parity) {
    asm volatile("{\n"
                 ".reg .pred P1, P2;\n"
                 ".reg .u32 c;\n"
                 "mov.u32 c, 0;\n"
                 "LAB_WAIT:\n"
                 "mbarrier.try_wait.parity.shared::cta.b64 P1, [%0], %1;\n"
                 "@P1 bra LAB_DONE;\n"
                 "add.u32 c, c, 1;\n"
                 "setp.gt.u32 P2, c, 4194304;\n"
                 "@P2 trap;\n"
                 "bra LAB_WAIT;\n"
                 "LAB_DONE:\n"
                 "}" ::"r"(bar), "r"(parity) : "memory");
}
__device__ __forceinline__ void mbar_waitc(uint32_t bar, uint32_t parity) {
    asm volatile("{\n"
                 ".reg .pred P1;\n"
                 "LAB_WAIT:\n"
                 "mbarrier.try_wait.parity.shared::cta.b64 P1, [%0], %1;\n"
                 "@!P1 bra LAB_WAIT;\n"
                 "}" ::"r"(bar), "r"(parity) : "memory");
}
__device__ __forceinline__ void tma2d(uint32_t dst, const CUtensorMap* tm, uint32_t bar, int c0, int c1) {
    asm volatile("cp.async.bulk.tensor.2d.shared::cluster.global.mbarrier::complete_tx::bytes [%0], [%1, {%3, %4}], [%2];"
                 ::"r"(dst), "l"(tm), "r"(bar), "r"(c0), "r"(c1) : "memory");
}
__device__ __forceinline__ void tma3d(uint32_t dst, const CUtensorMap* tm, uint32_t bar, int c0, int c1, int c2) {
    asm volatile("cp.async.bulk.tensor.3d.shared::cluster.global.mbarrier::complete_tx::bytes [%0], [%1, {%3, %4, %5}], [%2];"
                 ::"r"(dst), "l"(tm), "r"(bar), "r"(c0), "r"(c1), "r"(c2) : "memory");
}
__device__ __forceinline__ void prefetch_tmap(const CUtensorMap* tm) {
    asm volatile("prefetch.tensormap [%0];" ::"l"(tm) : "memory");
}
__device__ __forceinline__ void prefetch_l2(const void* p, uint32_t bytes) {
    asm volatile("cp.async.bulk.prefetch.L2.global [%0], %1;" ::"l"(p), "r"(bytes) : "memory");
}
__device__ __forceinline__ unsigned ld_acquire(const unsigned* p) {
    unsigned v; asm volatile("ld.acquire.gpu.global.u32 %0, [%1];" : "=r"(v) : "l"(p) : "memory"); return v;
}
__device__ __forceinline__ uint4 ld_acquire4(const unsigned* p) {
    uint4 v;
    asm volatile("ld.acquire.gpu.global.v4.u32 {%0,%1,%2,%3}, [%4];" : "=r"(v.x), "=r"(v.y), "=r"(v.z), "=r"(v.w) : "l"(p) : "memory");
    return v;
}
__device__ __forceinline__ unsigned ld_relaxed(const unsigned* p) {
    unsigned v; asm volatile("ld.relaxed.gpu.global.u32 %0, [%1];" : "=r"(v) : "l"(p)); return v;
}
__device__ __forceinline__ void st_relaxed(unsigned* p, unsigned v) {
    asm volatile("st.relaxed.gpu.global.u32 [%0], %1;" ::"l"(p), "r"(v) : "memory");
}
__device__ __forceinline__ void red_relaxed(unsigned* p, unsigned v) {
    asm volatile("red.relaxed.gpu.global.add.u32 [%0], %1;" ::"l"(p), "r"(v) : "memory");
}
__device__ __forceinline__ void fence_gpu() { asm volatile("fence.acq_rel.gpu;" ::: "memory"); }
__device__ __forceinline__ void fence_async_smem() { asm volatile("fence.proxy.async.shared::cta;" ::: "memory"); }
__device__ __forceinline__ void fence_async_global() { asm volatile("fence.proxy.async.global;" ::: "memory"); }
__device__ __forceinline__ void wait_count(const unsigned* p, unsigned target) {
    uint32_t it = 0;
    while ((int)(ld_acquire(p) - target) < 0) trap_if_gt(++it, 1u << 22);
}
__device__ __forceinline__ void wait_count_warp(const unsigned* p, unsigned target) {
    uint32_t it = 0;
    while (__any_sync(0xffffffffu, (int)(ld_acquire(p) - target) < 0)) trap_if_gt(++it, 1u << 22);
}
__device__ __forceinline__ void red_f32(float* p, float a) {
    asm volatile("red.relaxed.gpu.global.add.f32 [%0], %1;" ::"l"(p), "f"(a) : "memory");
}
__device__ __forceinline__ void red_f32x2(float* p, float a, float b) {
    asm volatile("red.relaxed.gpu.global.add.v2.f32 [%0], {%1, %2};" ::"l"(p), "f"(a), "f"(b) : "memory");
}
__device__ __forceinline__ void red_f32x4(float* p, float a, float b, float c, float d) {
    asm volatile("red.relaxed.gpu.global.add.v4.f32 [%0], {%1, %2, %3, %4};" ::"l"(p), "f"(a), "f"(b), "f"(c), "f"(d) : "memory");
}
__device__ __forceinline__ float4 ld_l2_f4(const float* p) {
    float4 v;
    asm volatile("ld.relaxed.gpu.global.v4.f32 {%0,%1,%2,%3}, [%4];" : "=f"(v.x), "=f"(v.y), "=f"(v.z), "=f"(v.w) : "l"(p) : "memory");
    return v;
}
__device__ __forceinline__ float2 ld_l2_f2(const float* p) {
    float2 v;
    asm volatile("ld.relaxed.gpu.global.v2.f32 {%0,%1}, [%2];" : "=f"(v.x), "=f"(v.y) : "l"(p) : "memory");
    return v;
}
__device__ __forceinline__ float ld_l2_f(const float* p) {
    float v;
    asm volatile("ld.relaxed.gpu.global.f32 %0, [%1];" : "=f"(v) : "l"(p) : "memory");
    return v;
}
__device__ __forceinline__ uint4 ldg_nc(const void* p) {
    uint4 v;
    asm volatile("ld.global.nc.L1::no_allocate.v4.u32 {%0,%1,%2,%3}, [%4];" : "=r"(v.x), "=r"(v.y), "=r"(v.z), "=r"(v.w) : "l"(p));
    return v;
}
__device__ __forceinline__ void stg128(void* p, uint32_t a, uint32_t b, uint32_t c, uint32_t d) {
    asm volatile("st.global.v4.u32 [%0], {%1,%2,%3,%4};" ::"l"(p), "r"(a), "r"(b), "r"(c), "r"(d) : "memory");
}
__device__ __forceinline__ uint4 lds128(uint32_t a) {
    uint4 v;
    asm volatile("ld.shared.v4.u32 {%0,%1,%2,%3}, [%4];" : "=r"(v.x), "=r"(v.y), "=r"(v.z), "=r"(v.w) : "r"(a) : "memory");
    return v;
}
__device__ __forceinline__ float2 lds_f2(uint32_t a) {
    float2 v;
    asm volatile("ld.shared.v2.f32 {%0,%1}, [%2];" : "=f"(v.x), "=f"(v.y) : "r"(a) : "memory");
    return v;
}
__device__ __forceinline__ void sts_f2(uint32_t a, float x, float y) {
    asm volatile("st.shared.v2.f32 [%0], {%1,%2};" ::"r"(a), "f"(x), "f"(y) : "memory");
}
__device__ __forceinline__ void sts64(uint32_t a, uint32_t x, uint32_t y) {
    asm volatile("st.shared.v2.u32 [%0], {%1,%2};" ::"r"(a), "r"(x), "r"(y) : "memory");
}
__device__ __forceinline__ void sts128(uint32_t a, uint32_t x, uint32_t y, uint32_t z, uint32_t w) {
    asm volatile("st.shared.v4.u32 [%0], {%1,%2,%3,%4};" ::"r"(a), "r"(x), "r"(y), "r"(z), "r"(w) : "memory");
}
__device__ __forceinline__ void stsm4(uint32_t a, uint32_t r0, uint32_t r1, uint32_t r2, uint32_t r3) {
    asm volatile("stmatrix.sync.aligned.m8n8.x4.shared.b16 [%0], {%1,%2,%3,%4};" ::"r"(a), "r"(r0), "r"(r1), "r"(r2), "r"(r3) : "memory");
}
__device__ __forceinline__ void ldsm4(uint32_t a, uint32_t& r0, uint32_t& r1, uint32_t& r2, uint32_t& r3) {
    asm volatile("ldmatrix.sync.aligned.m8n8.x4.shared.b16 {%0,%1,%2,%3}, [%4];" : "=r"(r0), "=r"(r1), "=r"(r2), "=r"(r3) : "r"(a) : "memory");
}
__device__ __forceinline__ void ldsm4t(uint32_t a, uint32_t& r0, uint32_t& r1, uint32_t& r2, uint32_t& r3) {
    asm volatile("ldmatrix.sync.aligned.m8n8.x4.trans.shared.b16 {%0,%1,%2,%3}, [%4];" : "=r"(r0), "=r"(r1), "=r"(r2), "=r"(r3) : "r"(a) : "memory");
}
__device__ __forceinline__ void mma16816(float* c, const uint32_t* a, uint32_t b0, uint32_t b1) {
    asm("mma.sync.aligned.m16n8k16.row.col.f32.bf16.bf16.f32 {%0,%1,%2,%3}, {%4,%5,%6,%7}, {%8,%9}, {%0,%1,%2,%3};"
                 : "+f"(c[0]), "+f"(c[1]), "+f"(c[2]), "+f"(c[3])
                 : "r"(a[0]), "r"(a[1]), "r"(a[2]), "r"(a[3]), "r"(b0), "r"(b1));
}
__device__ __forceinline__ uint32_t pack_bf16(float lo, float hi) {
    uint32_t r; asm("cvt.rn.bf16x2.f32 %0, %1, %2;" : "=r"(r) : "f"(hi), "f"(lo)); return r;
}
__device__ __forceinline__ float bf_lo(uint32_t w) { return __uint_as_float(w << 16); }
__device__ __forceinline__ float bf_hi(uint32_t w) { return __uint_as_float(w & 0xffff0000u); }
__device__ __forceinline__ float ex2(float x) { float r; asm("ex2.approx.ftz.f32 %0, %1;" : "=f"(r) : "f"(x)); return r; }
__device__ __forceinline__ float rcp(float x) { float r; asm("rcp.approx.ftz.f32 %0, %1;" : "=f"(r) : "f"(x)); return r; }
__device__ __forceinline__ void bar_sync(int id, int n) { asm volatile("bar.sync %0, %1;" ::"r"(id), "r"(n) : "memory"); }

__device__ __forceinline__ uint32_t desc_lo(uint32_t addr) { return ((addr & 0x3FFFF) >> 4) | (512u << 16); }
#define DESC_HI "0x40000040"
__device__ __forceinline__ void wg_fence() { asm volatile("wgmma.fence.sync.aligned;" ::: "memory"); }
__device__ __forceinline__ void wg_commit() { asm volatile("wgmma.commit_group.sync.aligned;" ::: "memory"); }
template <int N> __device__ __forceinline__ void wg_wait() { asm volatile("wgmma.wait_group.sync.aligned %0;" ::"n"(N) : "memory"); }
template <int N> __device__ __forceinline__ void fence_acc(float* d) {
#pragma unroll
    for (int i = 0; i < N; i++) asm volatile("" : "+f"(d[i])::"memory");
}
#define R4(o) "+f"(d[o + 0]), "+f"(d[o + 1]), "+f"(d[o + 2]), "+f"(d[o + 3])
#define R8(o) R4(o), R4(o + 4)
__device__ __forceinline__ void wgmma_n128(float* d, uint32_t da, uint32_t db, int sc) {
    asm volatile("{.reg .pred p; .reg .b64 da, db; setp.ne.b32 p, %66, 0; mov.b64 da, {%64, " DESC_HI "}; mov.b64 db, {%65, " DESC_HI "};\n"
                 "wgmma.mma_async.sync.aligned.m64n128k16.f32.bf16.bf16 {%0,%1,%2,%3,%4,%5,%6,%7,%8,%9,%10,%11,%12,%13,%14,%15,%16,%17,%18,%19,%20,%21,%22,%23,%24,%25,%26,%27,%28,%29,%30,%31,"
                 "%32,%33,%34,%35,%36,%37,%38,%39,%40,%41,%42,%43,%44,%45,%46,%47,%48,%49,%50,%51,%52,%53,%54,%55,%56,%57,%58,%59,%60,%61,%62,%63}, da, db, p, 1, 1, 0, 1;}"
                 : R8(0), R8(8), R8(16), R8(24), R8(32), R8(40), R8(48), R8(56)
                 : "r"(da), "r"(db), "r"(sc));
}
__device__ __forceinline__ void wgmma_n64(float* d, uint32_t da, uint32_t db, int sc) {
    asm volatile("{.reg .pred p; .reg .b64 da, db; setp.ne.b32 p, %34, 0; mov.b64 da, {%32, " DESC_HI "}; mov.b64 db, {%33, " DESC_HI "};\n"
                 "wgmma.mma_async.sync.aligned.m64n64k16.f32.bf16.bf16 {%0,%1,%2,%3,%4,%5,%6,%7,%8,%9,%10,%11,%12,%13,%14,%15,%16,%17,%18,%19,%20,%21,%22,%23,%24,%25,%26,%27,%28,%29,%30,%31}, da, db, p, 1, 1, 0, 1;}"
                 : R8(0), R8(8), R8(16), R8(24)
                 : "r"(da), "r"(db), "r"(sc));
}
__device__ __forceinline__ void wgmma_n48(float* d, uint32_t da, uint32_t db, int sc) {
    asm volatile("{.reg .pred p; .reg .b64 da, db; setp.ne.b32 p, %26, 0; mov.b64 da, {%24, " DESC_HI "}; mov.b64 db, {%25, " DESC_HI "};\n"
                 "wgmma.mma_async.sync.aligned.m64n48k16.f32.bf16.bf16 {%0,%1,%2,%3,%4,%5,%6,%7,%8,%9,%10,%11,%12,%13,%14,%15,%16,%17,%18,%19,%20,%21,%22,%23}, da, db, p, 1, 1, 0, 1;}"
                 : R8(0), R8(8), R8(16)
                 : "r"(da), "r"(db), "r"(sc));
}
__device__ __forceinline__ void wgmma_n40_tt(float* d, uint32_t da, uint32_t db, int sc) {
    asm volatile("{.reg .pred p; .reg .b64 da, db; setp.ne.b32 p, %22, 0; mov.b64 da, {%20, " DESC_HI "}; mov.b64 db, {%21, " DESC_HI "};\n"
                 "wgmma.mma_async.sync.aligned.m64n40k16.f32.bf16.bf16 {%0,%1,%2,%3,%4,%5,%6,%7,%8,%9,%10,%11,%12,%13,%14,%15,%16,%17,%18,%19}, da, db, p, 1, 1, 1, 1;}"
                 : R8(0), R8(8), R4(16)
                 : "r"(da), "r"(db), "r"(sc));
}

__device__ __forceinline__ void quad_transpose(uint32_t r0, uint32_t r1, uint32_t r2, uint32_t r3, uint32_t* o, int q) {
    const bool odd = q & 1, hi = q & 2;
    uint32_t a = odd ? r0 : r1, b = odd ? r2 : r3;
    a = __shfl_xor_sync(0xffffffffu, a, 1);
    b = __shfl_xor_sync(0xffffffffu, b, 1);
    uint32_t s0 = odd ? a : r0, s1 = odd ? r1 : a, s2 = odd ? b : r2, s3 = odd ? r3 : b;
    uint32_t c = hi ? s0 : s2, d = hi ? s1 : s3;
    c = __shfl_xor_sync(0xffffffffu, c, 2);
    d = __shfl_xor_sync(0xffffffffu, d, 2);
    o[0] = hi ? c : s0; o[1] = hi ? d : s1; o[2] = hi ? s2 : c; o[3] = hi ? s3 : d;
}
__device__ __forceinline__ void red_f32_if(float* p, float a, bool pred) {
    asm volatile("{.reg .pred p; setp.ne.u32 p, %2, 0; @p red.relaxed.gpu.global.add.f32 [%0], %1;}" ::"l"(p), "f"(a), "r"((uint32_t)pred) : "memory");
}
__device__ __forceinline__ void stg_f2_if(float* p, float a, float b, bool pred) {
    asm volatile("{.reg .pred p; setp.ne.u32 p, %3, 0; @p st.global.v2.f32 [%0], {%1,%2};}" ::"l"(p), "f"(a), "f"(b), "r"((uint32_t)pred) : "memory");
}
__device__ __forceinline__ void stg64(void* p, uint32_t a, uint32_t b) {
    asm volatile("st.global.v2.u32 [%0], {%1,%2};" ::"l"(p), "r"(a), "r"(b) : "memory");
}
__device__ __forceinline__ void store_pair(__nv_bfloat16* p, uint32_t r0, uint32_t r1, bool odd) {
    const uint32_t x = __shfl_xor_sync(0xffffffffu, odd ? r0 : r1, 1);
    stg64(p, odd ? x : r0, odd ? r1 : x);
}
__device__ __forceinline__ void mma16816_z(float* c, const uint32_t* a, uint32_t b0, uint32_t b1) {
    asm("mma.sync.aligned.m16n8k16.row.col.f32.bf16.bf16.f32 {%0,%1,%2,%3}, {%4,%5,%6,%7}, {%8,%9}, {%10,%10,%10,%10};"
                 : "=f"(c[0]), "=f"(c[1]), "=f"(c[2]), "=f"(c[3])
                 : "r"(a[0]), "r"(a[1]), "r"(a[2]), "r"(a[3]), "r"(b0), "r"(b1), "f"(0.f));
}
__device__ __forceinline__ uint32_t max2(uint32_t a, uint32_t b) { uint32_t r; asm("max.bf16x2 %0, %1, %2;" : "=r"(r) : "r"(a), "r"(b)); return r; }
__device__ __forceinline__ uint32_t min2(uint32_t a, uint32_t b) { uint32_t r; asm("min.bf16x2 %0, %1, %2;" : "=r"(r) : "r"(a), "r"(b)); return r; }
__device__ __forceinline__ void bar_arrive(int id, int n) { asm volatile("bar.arrive %0, %1;" ::"r"(id), "r"(n) : "memory"); }
__device__ __forceinline__ void mbar_arrive_n_if(uint32_t bar, uint32_t n, bool pred) {
    asm volatile("{.reg .pred p; setp.ne.u32 p, %1, 0; @p mbarrier.arrive.shared::cta.b64 _, [%0], %2;}" ::"r"(bar), "r"((uint32_t)pred), "r"(n) : "memory");
}
__device__ __forceinline__ float4 lds_f4(uint32_t a) {
    float4 v;
    asm volatile("ld.shared.v4.f32 {%0,%1,%2,%3}, [%4];" : "=f"(v.x), "=f"(v.y), "=f"(v.z), "=f"(v.w) : "r"(a) : "memory");
    return v;
}
__device__ __forceinline__ uint4 ld_tagged(const unsigned long long* p) {
    unsigned long long a, b;
    asm volatile("ld.relaxed.gpu.global.v2.b64 {%0,%1}, [%2];" : "=l"(a), "=l"(b) : "l"(p) : "memory");
    return make_uint4((unsigned)a, (unsigned)(a >> 32), (unsigned)b, (unsigned)(b >> 32));
}
__device__ __forceinline__ void st_tagged_if(unsigned long long* p, float a, float b, unsigned tag, bool pred) {
    const unsigned long long t = (unsigned long long)tag << 32;
    asm volatile("{.reg .pred p; setp.ne.u32 p, %3, 0; @p st.relaxed.gpu.global.v2.b64 [%0], {%1,%2};}"
                 ::"l"(p), "l"(t | __float_as_uint(a)), "l"(t | __float_as_uint(b)), "r"((uint32_t)pred) : "memory");
}

__device__ __forceinline__ void store_tile(uint32_t tile_rows, __nv_bfloat16* gdst, const uint32_t* lo, const uint32_t* hi, int lane) {
    const int r = lane & 15;
#pragma unroll
    for (int b = 0; b < 4; b++)
        stsm4(tile_rows + r * 128 + (((2 * b + (lane >> 4)) ^ (r & 7)) << 4), lo[2 * b], hi[2 * b], lo[2 * b + 1], hi[2 * b + 1]);
    __syncwarp();
#pragma unroll
    for (int i = 0; i < 4; i++) {
        const int rr = 4 * i + (lane >> 3);
        const uint4 v = lds128(tile_rows + rr * 128 + (((lane & 7) ^ (rr & 7)) << 4));
        stg128(gdst + rr * DM + (lane & 7) * 8, v.x, v.y, v.z, v.w);
    }
}

template <bool NORM>
__device__ __forceinline__ void feature_map(const uint32_t* a, const uint32_t* wb, float c0, float c1, uint32_t* plus, uint32_t* minus, float* rs) {
    float p[8];
    mma16816_z(p, a, wb[0], wb[1]);
    mma16816_z(p + 4, a, wb[2], wb[3]);
    const uint32_t P0 = pack_bf16(p[0], p[2]), P1 = pack_bf16(p[1], p[3]), P2 = pack_bf16(p[4], p[6]), P3 = pack_bf16(p[5], p[7]);
    uint32_t mx = max2(max2(P0, P1), max2(P2, P3)), mn = min2(min2(P0, P1), min2(P2, P3));
#pragma unroll
    for (int s = 1; s <= 2; s <<= 1) {
        mx = max2(mx, __shfl_xor_sync(0xffffffffu, mx, s));
        mn = min2(mn, __shfl_xor_sync(0xffffffffu, mn, s));
    }
    const float mx0 = bf_lo(mx) * c0, mx1 = bf_hi(mx) * c1, mn0 = bf_lo(mn) * c0, mn1 = bf_hi(mn) * c1;
    p[0] = bf_lo(P0); p[2] = bf_hi(P0); p[1] = bf_lo(P1); p[3] = bf_hi(P1);
    p[4] = bf_lo(P2); p[6] = bf_hi(P2); p[5] = bf_lo(P3); p[7] = bf_hi(P3);
    float ep[8], em[8];
#pragma unroll
    for (int i = 0; i < 8; i++) {
        const bool r1 = (i & 2);
        ep[i] = ex2(fmaf(p[i], r1 ? c1 : c0, r1 ? -mx1 : -mx0));
        em[i] = ex2(fmaf(p[i], r1 ? -c1 : -c0, r1 ? mn1 : mn0));
    }
    float sp[4], sm[4];
#pragma unroll
    for (int i = 0; i < 4; i++) { plus[i] = pack_bf16(ep[2 * i], ep[2 * i + 1]); minus[i] = pack_bf16(em[2 * i], em[2 * i + 1]); }
    mma16816_z(sp, plus, 0x3f803f80u, 0x3f803f80u);
    mma16816_z(sm, minus, 0x3f803f80u, 0x3f803f80u);
    rs[0] = rcp(sp[0]); rs[1] = rcp(sp[2]); rs[2] = rcp(sm[0]); rs[3] = rcp(sm[2]);
    if (NORM) {
#pragma unroll
        for (int i = 0; i < 4; i++) {
            plus[i] = pack_bf16(ep[2 * i] * rs[i & 1], ep[2 * i + 1] * rs[i & 1]);
            minus[i] = pack_bf16(em[2 * i] * rs[2 + (i & 1)], em[2 * i + 1] * rs[2 + (i & 1)]);
        }
    }
}

template <bool SCALE>
__device__ __forceinline__ void ln_frag(const float* acc, uint32_t cs_addr, float rs0, float nm0, float rs1, float nm1, uint32_t* a) {
    const float2 c0 = lds_f2(cs_addr), c1 = lds_f2(cs_addr + 32);
    const float s0 = SCALE ? rs0 : 1.f, s1 = SCALE ? rs1 : 1.f;
    a[0] = pack_bf16(fmaf(nm0, c0.x, acc[0]) * s0, fmaf(nm0, c0.y, acc[1]) * s0);
    a[1] = pack_bf16(fmaf(nm1, c0.x, acc[2]) * s1, fmaf(nm1, c0.y, acc[3]) * s1);
    a[2] = pack_bf16(fmaf(nm0, c1.x, acc[4]) * s0, fmaf(nm0, c1.y, acc[5]) * s0);
    a[3] = pack_bf16(fmaf(nm1, c1.x, acc[6]) * s1, fmaf(nm1, c1.y, acc[7]) * s1);
}

__device__ __forceinline__ uint32_t hh_pair(const float* ag, float4 cs, float nmean) {
    const float g0 = fmaf(nmean, cs.x, ag[0]), g1 = fmaf(nmean, cs.y, ag[1]);
    const float u0 = fmaf(nmean, cs.z, ag[32]), u1 = fmaf(nmean, cs.w, ag[33]);
    return pack_bf16(g0 * u0, g1 * u1);
}

struct Ring {
    int slot; uint32_t phase;
    __device__ __forceinline__ void adv() { if (++slot == NB) { slot = 0; phase ^= 1; } }
};

__global__ void __launch_bounds__(NTHREADS, 1) fused_kernel(const __grid_constant__ Params P) {
    extern __shared__ __align__(1024) uint8_t smem_raw[];
    const uint32_t sb = smem_u32(smem_raw);
    const int tid = threadIdx.x, lane = tid & 31;
    const int warp = __shfl_sync(0xffffffffu, tid >> 5, 0);
    const int m = blockIdx.x >> 3, j = blockIdx.x & 7;

    const unsigned epoch = ld_relaxed(&g_epoch) + 1;
    uint4 xv[4];
    unsigned short wraw[32];
    if (warp < 8) {
        const __nv_bfloat16* xp = P.x + (size_t)(128 * m + 16 * j + 2 * warp + (lane >> 4)) * DM + (lane & 15) * 8;
#pragma unroll
        for (int i = 0; i < 4; i++) xv[i] = ldg_nc(xp + 128 * i);
        const unsigned short* wp = reinterpret_cast<const unsigned short*>(P.wphi) + (4 * j) * 256 + 2 * (lane & 3) * 16 + (lane >> 2);
#pragma unroll
        for (int i = 0; i < 32; i++)
            asm volatile("ld.global.nc.u16 %0, [%1];" : "=h"(wraw[i]) : "l"(wp + (i >> 3) * 256 + ((i >> 1) & 1) * 128 + ((i >> 2) & 1) * 8 + (i & 1) * 16));
    } else if (warp == 8) {
        if (lane < NB) {
            const uint32_t full = sb + BAR_FULLB + 8 * lane;
            mbar_init(full, 1); mbar_init(sb + BAR_EMPTYB + 8 * lane, 8);
            asm volatile("fence.mbarrier_init.release.cluster;" ::: "memory");
            mbar_expect_tx(full, SLOT);
            tma3d(sb + OFF_B + lane * SLOT, &P.twkv, full, 64 * j, 64 * lane, 1);
        }
    } else if (warp == 9) {
        if (lane < 8) {
            const uint32_t full = sb + BAR_FULLA + 8 * lane;
            mbar_init(full, 1); mbar_init(sb + BAR_EMPTYA + 8 * lane, 8);
            asm volatile("fence.mbarrier_init.release.cluster;" ::: "memory");
            mbar_expect_tx(full, SLOT);
            tma2d(sb + OFF_A + lane * SLOT, &P.tx, full, 64 * lane, 128 * m);
        }
    } else if (warp == 10) {
        if (lane < 14) mbar_init(sb + BAR_CS1 + 8 * lane, lane == 0 ? 32 : (lane == 1 ? 160 : 4));
        trap_if_gt(sb & 1023, 0);
    }
    TL(0, tid == 0); TLG(0, tid == 0);
    __syncthreads();

    float* const acc_j = g_acc + j * ACC_SIZE;
    unsigned* const cnt_j = g_cnt + j * 128;

    if (warp >= 8) {
        asm volatile("setmaxnreg.dec.sync.aligned.u32 72;");
        if (warp == 8) {
            if (lane == 0) {
                Ring r{0, 1};
#pragma unroll 1
                for (int i = 6; i < 56; i++) {
                    const uint32_t full = sb + BAR_FULLB + 8 * r.slot, dst = sb + OFF_B + r.slot * SLOT;
                    mbar_wait(sb + BAR_EMPTYB + 8 * r.slot, r.phase ^ 1);
                    if (i >= 8 && i < 12) {
                        mbar_arrive(full);
                    } else {
                        mbar_expect_tx(full, SLOT);
                        if (i < 8) {
                            tma3d(dst, &P.twkv, full, 64 * j, 64 * i, 1);
                        } else if (i < 20) {
                            tma2d(dst, i < 16 ? &P.twq : &P.two, full, 64 * j, 128 * (i & 3));
                        } else if (i < 44) {
                            const int c = (i - 20) >> 3, kt = (i - 20) & 7;
                            tma2d(dst, &P.twg, full, 176 * j + 64 * c, 64 * kt);
                            tma2d(dst + 8192, &P.twu, full, 176 * j + 64 * c, 64 * kt);
                        } else {
                            const int c = (i - 44) >> 2, jj = (i & 3) * 2;
                            tma2d(dst, &P.twd, full, 64 * j, 176 * jj + 64 * c);
                            tma2d(dst + 8192, &P.twd, full, 64 * j, 176 * (jj + 1) + 64 * c);
                        }
                    }
                    r.adv();
                }
            }
        } else {
            if (m == 0 && warp == 10) {
                for (int i = lane; i < ACC_SIZE / 4; i += 32) stg128(acc_j + 4 * i, 0, 0, 0, 0);
                __syncwarp();
                if (lane == 0) { fence_gpu(); st_relaxed(cnt_j + 0, epoch); }
                __syncwarp();
            }
#pragma unroll 1
            for (int job = 0; job < (warp == 9 ? 2 : 1); job++) {
                const bool ffn = warp == 9;
                const int col = ffn ? 176 * j + 8 * lane : (lane >> 3) * DM + 64 * j + 8 * (lane & 7);
                const bool act = ffn ? (lane < 22 && col < FF) : lane < 24;
                const int pitch = ffn ? FF : 3 * DM;
                const __nv_bfloat16* src = (ffn ? (job ? P.wu : P.wg) : P.wqkv) + (size_t)(32 * m + (warp == 11 ? 16 : 0)) * pitch + col;
                float s[8];
#pragma unroll
                for (int i = 0; i < 8; i++) s[i] = 0.f;
                if (act) {
#pragma unroll 1
                    for (int b = 0; b < (ffn ? 4 : 2); b++) {
                        uint4 v[8];
#pragma unroll
                        for (int i = 0; i < 8; i++) v[i] = ldg_nc(src + (8 * b + i) * pitch);
#pragma unroll
                        for (int i = 0; i < 8; i++) {
                            s[0] += bf_lo(v[i].x); s[1] += bf_hi(v[i].x); s[2] += bf_lo(v[i].y); s[3] += bf_hi(v[i].y);
                            s[4] += bf_lo(v[i].z); s[5] += bf_hi(v[i].z); s[6] += bf_lo(v[i].w); s[7] += bf_hi(v[i].w);
                        }
                    }
                }
                wait_count_warp(cnt_j + 0, epoch);
                if (act) {
                    float* dst = acc_j + (ffn ? ACC_CS3 + job * 192 : ACC_CS1) + 8 * lane;
                    red_f32x4(dst, s[0], s[1], s[2], s[3]);
                    red_f32x4(dst + 4, s[4], s[5], s[6], s[7]);
                }
                __syncwarp();
                if (lane == 0) { fence_gpu(); red_relaxed(cnt_j + (ffn ? 64 : 32), 1); }
                __syncwarp();
            }
            if (warp == 9) {
                int r = (lane < 8) ? 1 : 6;
                int ready = (lane == j) ? 2 : 0;
                uint32_t it = 0;
                while (__any_sync(0xffffffffu, r < 6)) {
                    const bool e = r < 6 && mbar_test(sb + BAR_EMPTYA + 8 * (lane & 7), (r - 1) & 1);
                    const bool pending = __any_sync(0xffffffffu, r < 6 && ready >= r);
                    if (r < 6 && ready < r && (e || !pending)) {
                        const uint4 f = ld_acquire4(g_flag + (m * 8 + lane) * 8 + (r < 3 ? 0 : 4));
                        if (r < 3) ready = (f.x == epoch && f.y == epoch) ? ((f.z == epoch && f.w == epoch) ? 2 : 1) : 0;
                        else ready = f.x == epoch ? (f.y == epoch ? (f.z == epoch ? 5 : 4) : 3) : 2;
                    }
                    if (e && ready >= r) {
                        const uint32_t full = sb + BAR_FULLA + 8 * lane;
                        if (r < 3 && lane == j) {
                            mbar_arrive(full);
                        } else {
                            fence_async_global();
                            mbar_expect_tx(full, SLOT);
                            const CUtensorMap* tm = r == 1 ? &P.to : (r == 2 ? &P.th : &P.thh);
                            const int c0 = r < 3 ? 64 * lane : 176 * lane + 64 * (r - 3);
                            tma2d(sb + OFF_A + lane * SLOT, tm, full, c0, 128 * m);
                        }
                        r++;
                    }
                    trap_if_gt(++it, 1u << 24);
                }
            } else {
                const int a = warp - 10;
                if (a == 0) {
                    wait_count_warp(cnt_j + 32, epoch * 32);
#pragma unroll
                    for (int i = 0; i < 3; i++) {
                        const float2 c = ld_l2_f2(acc_j + ACC_CS1 + 64 * i + 2 * lane);
                        sts_f2(sb + OFF_CS1 + (64 * i + 2 * lane) * 4, c.x, c.y);
                    }
                    mbar_arrive(sb + BAR_CS1);
                } else if (lane == 0) {
                    prefetch_l2(P.wo + (size_t)blockIdx.x * 2048, 4096);
                    prefetch_l2(P.wd + (size_t)blockIdx.x * 5504, 11008);
                }
#pragma unroll 1
                for (int ev = 0; ev < 6; ev += (ev >= 2 + a) ? 2 - (ev == 2) : 1 + (ev == 2)) {
                    if (lane == 0) {
                        mbar_wait(sb + BAR_PUB + 8 * (a * 6 + ev), 0);
                        fence_gpu();
                        if (ev == 0) red_relaxed(cnt_j + 96, 1);
                        else st_relaxed(g_flag + blockIdx.x * 8 + (ev < 3 ? 2 * ev - 2 + a : ev + 1), epoch);
                    }
                    __syncwarp();
                    if (ev == 2 && a == 0) {
                        wait_count_warp(cnt_j + 64, epoch * 32);
#pragma unroll
                        for (int i = 0; i < 3; i++) {
                            const float2 cg = ld_l2_f2(acc_j + ACC_CS3 + 64 * i + 2 * lane);
                            const float2 cu = ld_l2_f2(acc_j + ACC_CS3 + 192 + 64 * i + 2 * lane);
                            sts128(sb + OFF_CS3 + (32 * i + lane) * 16, __float_as_uint(cg.x), __float_as_uint(cg.y),
                                   __float_as_uint(cu.x), __float_as_uint(cu.y));
                        }
                        mbar_arrive(sb + BAR_CS3);
                    }
                }
            }
        }
    } else {
        asm volatile("setmaxnreg.inc.sync.aligned.u32 216;");
        const int w = warp >> 2, wv = warp & 3, g = lane >> 2, q = lane & 3;
        const int row_w = 128 * m + 16 * warp;
        const uint32_t sa = sb + OFF_A + w * 8192;
        const uint32_t dA = desc_lo(sa), dB = desc_lo(sb + OFF_B);
        const uint32_t pub = sb + BAR_PUB + 48 * w;
        const bool l0 = lane == 0;
        Ring rg{0, 0};
        int prev = 0;

        uint32_t wb[16];
        {
            const int row = 128 * m + 16 * j + 2 * warp + (lane >> 4);
            const uint4* v = xv;
            float f[32];
#pragma unroll
            for (int i = 0; i < 4; i++) {
                f[8 * i] = bf_lo(v[i].x); f[8 * i + 1] = bf_hi(v[i].x); f[8 * i + 2] = bf_lo(v[i].y); f[8 * i + 3] = bf_hi(v[i].y);
                f[8 * i + 4] = bf_lo(v[i].z); f[8 * i + 5] = bf_hi(v[i].z); f[8 * i + 6] = bf_lo(v[i].w); f[8 * i + 7] = bf_hi(v[i].w);
            }
            float s0 = 0.f, s1 = 0.f;
#pragma unroll
            for (int i = 0; i < 16; i++) { s0 += f[2 * i]; s1 += f[2 * i + 1]; }
            s0 += s1;
#pragma unroll
            for (int o = 8; o; o >>= 1) s0 += __shfl_xor_sync(0xffffffffu, s0, o);
            const float mean = s0 * (1.f / DM);
            s0 = 0.f; s1 = 0.f;
#pragma unroll
            for (int i = 0; i < 16; i++) {
                const float d0 = f[2 * i] - mean, d1 = f[2 * i + 1] - mean;
                s0 = fmaf(d0, d0, s0); s1 = fmaf(d1, d1, s1);
            }
            s0 += s1;
#pragma unroll
            for (int o = 8; o; o >>= 1) s0 += __shfl_xor_sync(0xffffffffu, s0, o);
            const float rs = rsqrtf(s0 * (1.f / DM) + 1e-5f);
            st_tagged_if(g_xstat + 2 * row, rs, -mean, epoch, (lane & 15) == 0);
#pragma unroll
            for (int i = 0; i < 16; i++) wb[i] = (uint32_t)wraw[2 * i] | ((uint32_t)wraw[2 * i + 1] << 16);
        }
        constexpr float L2E = 1.4426950408889634f;
        uint32_t fp[16], fm[16];
        float fr[16];
        float rs0, nm0, rs1, nm1;
        {
            float acc[64];
#pragma unroll 1
            for (int kt = 0; kt < 8; kt++) {
                mbar_waitc(sb + BAR_FULLA + 8 * kt, 0);
                mbar_waitc(sb + BAR_FULLB + 8 * rg.slot, rg.phase);
                TL(20 + kt, tid == 0);
                wg_fence();
#pragma unroll
                for (int k = 0; k < 4; k++)
                    wgmma_n128(acc, dA + ((kt * SLOT + k * 32) >> 4), dB + ((rg.slot * SLOT + k * 2048) >> 4), (kt | k) != 0);
                wg_commit();
                wg_wait<1>();
                mbar_arrive_if(sb + BAR_EMPTYB + 8 * prev, l0 && kt > 0);
                prev = rg.slot; rg.adv();
            }
            {
                uint4 a, b;
                uint32_t it = 0;
                do {
                    a = ld_tagged(g_xstat + 2 * (row_w + g));
                    b = ld_tagged(g_xstat + 2 * (row_w + g + 8));
                    trap_if_gt(++it, 1u << 22);
                } while (__any_sync(0xffffffffu, a.y != epoch || a.w != epoch || b.y != epoch || b.w != epoch));
                rs0 = __uint_as_float(a.x); nm0 = __uint_as_float(a.z); rs1 = __uint_as_float(b.x); nm1 = __uint_as_float(b.z);
            }
            TL(17, tid == 0);
            mbar_waitc(sb + BAR_CS1, 0);
            TL(18, tid == 0);
            wg_wait<0>();
            fence_acc<64>(acc);
            mbar_arrive_if(sb + BAR_EMPTYB + 8 * prev, l0);
            TL(2, tid == 0);
#pragma unroll
            for (int i = 2; i < 6; i++) mbar_waitc(sb + BAR_FULLB + 8 * i, 1);
            const int lrow = 16 * warp + (lane & 15), ch = lane >> 4, sw = lane & 7;
            const uint32_t st = sb + OFF_B + 2 * SLOT + lrow * 128;
            uint32_t ka[16];
#pragma unroll
            for (int hh = 0; hh < 4; hh++)
                ln_frag<false>(acc + 8 * hh, sb + OFF_CS1 + (64 + 16 * hh + 2 * q) * 4, rs0, nm0, rs1, nm1, ka + 4 * hh);
#pragma unroll
            for (int hh = 0; hh < 4; hh++) {
                uint32_t a[4];
                ln_frag<true>(acc + 32 + 8 * hh, sb + OFF_CS1 + (128 + 16 * hh + 2 * q) * 4, rs0, nm0, rs1, nm1, a);
                stsm4(st + (2 + (hh >> 1)) * SLOT + (((2 * (hh & 1) + ch) ^ sw) << 4), a[0], a[1], a[2], a[3]);
            }
#pragma unroll
            for (int hh = 0; hh < 4; hh++) feature_map<true>(ka + 4 * hh, wb + 4 * hh, rs0 * L2E, rs1 * L2E, fp + 4 * hh, fm + 4 * hh, fr);
#pragma unroll
            for (int hh = 0; hh < 4; hh++) {
                stsm4(st + (hh >> 1) * SLOT + (((4 * (hh & 1) + ch) ^ sw) << 4), fp[4 * hh], fp[4 * hh + 1], fp[4 * hh + 2], fp[4 * hh + 3]);
                stsm4(st + (hh >> 1) * SLOT + (((4 * (hh & 1) + 2 + ch) ^ sw) << 4), fm[4 * hh], fm[4 * hh + 1], fm[4 * hh + 2], fm[4 * hh + 3]);
            }
            stsm4(st + (2 + ch) * SLOT + ((4 ^ sw) << 4), 0x3f803f80u, 0x3f803f80u, 0x3f803f80u, 0x3f803f80u);
            fence_async_smem();
            TL(19, tid == 0);
            bar_sync(1, 256);
            float kvd[20];
            wg_fence();
#pragma unroll
            for (int k = 0; k < 8; k++)
                wgmma_n40_tt(kvd, dB + (((2 + w) * SLOT + k * 2048) >> 4), dB + (((4 + w) * SLOT + k * 2048) >> 4), k != 0);
            wg_commit();
            wg_wait<0>();
            fence_acc<20>(kvd);
            const bool h1 = wv >= 2;
            const int f = 16 * warp + g;
            float* kvp = acc_j + ACC_KV + f * 16 + 2 * q;
            red_f32x2(kvp, h1 ? kvd[8] : kvd[0], h1 ? kvd[9] : kvd[1]);
            red_f32x2(kvp + 128, h1 ? kvd[10] : kvd[2], h1 ? kvd[11] : kvd[3]);
            red_f32x2(kvp + 8, h1 ? kvd[12] : kvd[4], h1 ? kvd[13] : kvd[5]);
            red_f32x2(kvp + 136, h1 ? kvd[14] : kvd[6], h1 ? kvd[15] : kvd[7]);
            red_f32_if(acc_j + ACC_Z + f + 8 * (q & 1), q ? kvd[18] : kvd[16], q < 2);
            __syncwarp();
            mbar_arrive_if(pub, l0);
            mbar_arrive_if(sb + BAR_EMPTYB + 8 * (2 + (lane & 3)), lane < 4);
            TL(3, tid == 0);
        }
        uint32_t res_lo[8], res_hi[8];
        const uint32_t own_rows = sb + OFF_A + j * SLOT + warp * 2048;
        {
            float acc[32];
            rg.slot = 0; rg.phase = 0;
#pragma unroll 1
            for (int b = 0; b < 4; b++) {
                mbar_waitc(sb + BAR_FULLB + 8 * rg.slot, rg.phase);
                wg_fence();
#pragma unroll
                for (int k = 0; k < 8; k++)
                    wgmma_n64(acc, dA + (((2 * b + (k >> 2)) * SLOT + (k & 3) * 32) >> 4), dB + ((rg.slot * SLOT + k * 2048) >> 4), (b | k) != 0);
                wg_commit();
                wg_wait<1>();
                mbar_arrive_if(sb + BAR_EMPTYB + 8 * prev, l0 && b > 0);
                prev = rg.slot; rg.adv();
            }
            wg_wait<0>();
            fence_acc<32>(acc);
            mbar_arrive_if(sb + BAR_EMPTYB + 8 * prev, l0);
            mbar_arrive_if(sb + BAR_EMPTYA + 8 * (lane & 7), lane < 8 && (lane | 1) != (j | 1));
            TL(4, tid == 0);
            uint32_t qa[16];
#pragma unroll
            for (int hh = 0; hh < 4; hh++)
                ln_frag<false>(acc + 8 * hh, sb + OFF_CS1 + (16 * hh + 2 * q) * 4, rs0, nm0, rs1, nm1, qa + 4 * hh);
#pragma unroll
            for (int hh = 0; hh < 4; hh++) feature_map<false>(qa + 4 * hh, wb + 4 * hh, rs0 * L2E, rs1 * L2E, fp + 4 * hh, fm + 4 * hh, fr + 4 * hh);
#pragma unroll
            for (int b = 0; b < 4; b++)
                ldsm4(own_rows + (lane & 15) * 128 + (((2 * b + (lane >> 4)) ^ (lane & 7)) << 4),
                      res_lo[2 * b], res_hi[2 * b], res_lo[2 * b + 1], res_hi[2 * b + 1]);
            TL(5, tid == 0);
            if (warp == 0) wait_count_warp(cnt_j + 96, epoch * 32);
            TL(6, tid == 0);
            bar_sync(1, 256);
            const uint32_t kvs = sb + OFF_A + (j ^ 1) * SLOT;
            {
                const float4 a0 = ld_l2_f4(acc_j + ACC_KV + 4 * tid), a1 = ld_l2_f4(acc_j + ACC_KV + 4 * (tid + 256));
                const float zz = ld_l2_f(acc_j + ACC_Z + (tid & 127));
                sts64(kvs + (tid >> 2) * 48 + (tid & 3) * 8, pack_bf16(a0.x, a0.y), pack_bf16(a0.z, a0.w));
                sts64(kvs + ((tid >> 2) + 64) * 48 + (tid & 3) * 8, pack_bf16(a1.x, a1.y), pack_bf16(a1.z, a1.w));
                const uint32_t z2 = pack_bf16(zz, zz);
                sts64(kvs + (tid & 127) * 48 + 32 + w * 8, z2, z2);
            }
            bar_sync(1, 256);
            uint32_t o_lo[8], o_hi[8];
#pragma unroll
            for (int hh = 0; hh < 4; hh++) {
                uint32_t b[8], zb[4];
                const uint32_t base = kvs + hh * 32 * 48;
                ldsm4t(base + (lane & 15) * 48 + (lane >> 4) * 16, b[0], b[1], b[2], b[3]);
                ldsm4t(base + (16 + (lane & 15)) * 48 + (lane >> 4) * 16, b[4], b[5], b[6], b[7]);
                ldsm4t(base + lane * 48 + 32, zb[0], zb[1], zb[2], zb[3]);
                float n0[4], n1[4], dn[4], m0[4], m1[4], dm[4];
                mma16816_z(n0, fp + 4 * hh, b[0], b[1]); mma16816_z(n1, fp + 4 * hh, b[2], b[3]); mma16816_z(dn, fp + 4 * hh, zb[0], zb[1]);
                mma16816_z(m0, fm + 4 * hh, b[4], b[5]); mma16816_z(m1, fm + 4 * hh, b[6], b[7]); mma16816_z(dm, fm + 4 * hh, zb[2], zb[3]);
                const float* r = fr + 4 * hh;
                const float i0 = rcp(fmaf(dn[0], r[0], fmaf(dm[0], r[2], 1e-6f))), i1 = rcp(fmaf(dn[2], r[1], fmaf(dm[2], r[3], 1e-6f)));
                const float p0 = r[0] * i0, q0 = r[2] * i0, p1 = r[1] * i1, q1 = r[3] * i1;
                o_lo[2 * hh] = pack_bf16(fmaf(n0[0], p0, m0[0] * q0), fmaf(n0[1], p0, m0[1] * q0));
                o_hi[2 * hh] = pack_bf16(fmaf(n0[2], p1, m0[2] * q1), fmaf(n0[3], p1, m0[3] * q1));
                o_lo[2 * hh + 1] = pack_bf16(fmaf(n1[0], p0, m1[0] * q0), fmaf(n1[1], p0, m1[1] * q0));
                o_hi[2 * hh + 1] = pack_bf16(fmaf(n1[2], p1, m1[2] * q1), fmaf(n1[3], p1, m1[3] * q1));
            }
            store_tile(own_rows, g_o + (size_t)row_w * DM + 64 * j, o_lo, o_hi, lane);
            fence_async_smem();
            __syncwarp();
            mbar_arrive_if(pub + 8, l0);
            mbar_arrive_if(sb + BAR_EMPTYA + 8 * (j ^ (lane & 1)), lane < 2);
            TL(7, tid == 0);
        }
        {
            float acc[32];
#pragma unroll
            for (int t = 0; t < 8; t++) {
                acc[4 * t] = bf_lo(res_lo[t]); acc[4 * t + 1] = bf_hi(res_lo[t]);
                acc[4 * t + 2] = bf_lo(res_hi[t]); acc[4 * t + 3] = bf_hi(res_hi[t]);
            }
            fence_acc<32>(acc);
#pragma unroll 1
            for (int kp = 0; kp < 4; kp++) {
                mbar_waitc(sb + BAR_FULLB + 8 * rg.slot, rg.phase);
#pragma unroll
                for (int hf = 0; hf < 2; hf++) {
                    const int kt = 2 * kp + hf;
                    mbar_waitc(sb + BAR_FULLA + 8 * kt, 1);
                    TL(8, kt == 0 && tid == 0);
                    wg_fence();
#pragma unroll
                    for (int k = 0; k < 4; k++)
                        wgmma_n64(acc, dA + ((kt * SLOT + k * 32) >> 4), dB + ((rg.slot * SLOT + (hf * 4 + k) * 2048) >> 4), 1);
                    wg_commit();
                    wg_wait<1>();
                    mbar_arrive_if(sb + BAR_EMPTYA + 8 * ((kt + 7) & 7), l0 && kt > 0 && kt - 1 != j);
                    if (hf == 0) mbar_arrive_if(sb + BAR_EMPTYB + 8 * prev, l0 && kt > 0);
                }
                prev = rg.slot; rg.adv();
            }
            wg_wait<0>();
            fence_acc<32>(acc);
            mbar_arrive_if(sb + BAR_EMPTYA + 8 * 7, l0 && j != 7);
            mbar_arrive_if(sb + BAR_EMPTYB + 8 * prev, l0);
            TL(9, tid == 0);
            float s0 = 0.f, s1 = 0.f;
#pragma unroll
            for (int t = 0; t < 8; t++) {
                res_lo[t] = pack_bf16(acc[4 * t], acc[4 * t + 1]);
                res_hi[t] = pack_bf16(acc[4 * t + 2], acc[4 * t + 3]);
                s0 += acc[4 * t] + acc[4 * t + 1];
                s1 += acc[4 * t + 2] + acc[4 * t + 3];
            }
            store_tile(own_rows, g_h + (size_t)row_w * DM + 64 * j, res_lo, res_hi, lane);
            s0 += __shfl_xor_sync(0xffffffffu, s0, 1); s1 += __shfl_xor_sync(0xffffffffu, s1, 1);
            s0 += __shfl_xor_sync(0xffffffffu, s0, 2); s1 += __shfl_xor_sync(0xffffffffu, s1, 2);
            const float mu0 = s0 * (1.f / 64), mu1 = s1 * (1.f / 64);
            float q0 = 0.f, q1 = 0.f;
#pragma unroll
            for (int t = 0; t < 8; t++) {
                float d;
                d = acc[4 * t] - mu0; q0 = fmaf(d, d, q0);
                d = acc[4 * t + 1] - mu0; q0 = fmaf(d, d, q0);
                d = acc[4 * t + 2] - mu1; q1 = fmaf(d, d, q1);
                d = acc[4 * t + 3] - mu1; q1 = fmaf(d, d, q1);
            }
            q0 += __shfl_xor_sync(0xffffffffu, q0, 1); q1 += __shfl_xor_sync(0xffffffffu, q1, 1);
            q0 += __shfl_xor_sync(0xffffffffu, q0, 2); q1 += __shfl_xor_sync(0xffffffffu, q1, 2);
            stg_f2_if(g_hstat + (row_w + g + 8 * (q & 1)) * 16 + 2 * j, q ? mu1 : mu0, q ? q1 : q0, q < 2);
            fence_async_smem();
            __syncwarp();
            mbar_arrive_if(pub + 16, l0);
            mbar_arrive_if(sb + BAR_EMPTYA + 8 * j, l0);
            TL(10, tid == 0);
        }
        if (w == 1) {
#pragma unroll 1
            for (int kt = 0; kt < 8; kt++) mbar_waitc(sb + BAR_FULLA + 8 * kt, 0);
            const float* sp = g_hstat + (128 * m + (tid & 127)) * 16;
            float4 v[4];
#pragma unroll
            for (int i = 0; i < 4; i++) v[i] = ld_l2_f4(sp + 4 * i);
            float mean = 0.f;
#pragma unroll
            for (int i = 0; i < 4; i++) mean += v[i].x + v[i].z;
            mean *= 0.125f;
            float m2 = 0.f, dv = 0.f;
#pragma unroll
            for (int i = 0; i < 4; i++) {
                m2 += v[i].y + v[i].w;
                dv = fmaf(v[i].x - mean, v[i].x - mean, dv); dv = fmaf(v[i].z - mean, v[i].z - mean, dv);
            }
            sts_f2(sb + OFF_CS1 + (tid & 127) * 8, -mean, __fdividef(1.f, fmaf(dv, 64.f, m2) * (1.f / DM) + 1e-5f));
            mbar_arrive(sb + BAR_CS3);
        }
        {
            float acc0[64], acc1[64];
            const uint32_t dA0 = desc_lo(sb + OFF_A);
#pragma unroll 1
            for (int c = w; c < 3; c += 2) {
                if (c > 0) bar_sync(1 + c, 256);
                rg.slot = (c == 2) ? 0 : 2 + 2 * c; rg.phase = (c == 0);
#pragma unroll 1
                for (int kt = 0; kt < 8; kt++) {
                    mbar_waitc(sb + BAR_FULLA + 8 * kt, 0);
                    mbar_waitc(sb + BAR_FULLB + 8 * rg.slot, rg.phase);
                    TL(44 + c * 2 + (kt == 1), (tid & 127) == 0 && kt < 2);
                    wg_fence();
#pragma unroll
                    for (int k = 0; k < 4; k++) {
                        const uint32_t db = dB + ((rg.slot * SLOT + k * 2048) >> 4);
                        wgmma_n128(acc0, dA0 + ((kt * SLOT + k * 32) >> 4), db, (kt | k) != 0);
                        wgmma_n128(acc1, dA0 + ((kt * SLOT + 8192 + k * 32) >> 4), db, (kt | k) != 0);
                    }
                    wg_commit();
                    wg_wait<1>();
                    mbar_arrive_n_if(sb + BAR_EMPTYB + 8 * prev, 2, l0 && kt > 0);
                    mbar_arrive_if(sb + BAR_EMPTYA + 8 * ((kt + 7) & 7), l0 && kt > 0 && c > 0);
                    prev = rg.slot; rg.adv();
                }
                bar_arrive(2 + c, 256);
                mbar_waitc(sb + BAR_CS3, 0);
                float nm[4];
#pragma unroll
                for (int i = 0; i < 4; i++) nm[i] = lds_f2(sb + OFF_CS1 + (64 * (i >> 1) + 16 * wv + g + 8 * (i & 1)) * 8).x;
                wg_wait<0>();
                fence_acc<64>(acc0); fence_acc<64>(acc1);
                mbar_arrive_n_if(sb + BAR_EMPTYB + 8 * prev, 2, l0);
                mbar_arrive_if(sb + BAR_EMPTYA + 8 * 7, l0 && c > 0);
                TL(11 + c, (tid & 127) == 0);
                __nv_bfloat16* hp = g_hh + (size_t)(128 * m + 16 * wv + g) * FFP + 176 * j + 64 * c + (q & 1) * 8 + (q >> 1) * 4;
#pragma unroll
                for (int tp = 0; tp < 4; tp++) {
                    if (tp < 3 || c < 2) {
                        const uint32_t ca = sb + OFF_CS3 + (32 * c + 8 * tp + q) * 16;
                        const float4 c0 = lds_f4(ca), c1 = lds_f4(ca + 64);
                        store_pair(hp + 16 * tp, hh_pair(acc0 + 8 * tp, c0, nm[0]), hh_pair(acc0 + 8 * tp + 4, c1, nm[0]), q & 1);
                        store_pair(hp + 8 * FFP + 16 * tp, hh_pair(acc0 + 8 * tp + 2, c0, nm[1]), hh_pair(acc0 + 8 * tp + 6, c1, nm[1]), q & 1);
                        store_pair(hp + 64 * FFP + 16 * tp, hh_pair(acc1 + 8 * tp, c0, nm[2]), hh_pair(acc1 + 8 * tp + 4, c1, nm[2]), q & 1);
                        store_pair(hp + 72 * FFP + 16 * tp, hh_pair(acc1 + 8 * tp + 2, c0, nm[3]), hh_pair(acc1 + 8 * tp + 6, c1, nm[3]), q & 1);
                    }
                }
                __syncwarp();
                mbar_arrive_if(pub + 24 + 8 * c, l0);
                TL(54 + c, (tid & 127) == 0);
            }
            if (w == 1) bar_sync(4, 256);
        }
        {
            float acc[32];
            rg.slot = 2; rg.phase = 1;
#define KT_P4(T, HF, NK)                                                                                    \
    do {                                                                                                    \
        const int s_ = (T) & 7;                                                                             \
        if (!(HF)) mbar_waitc(sb + BAR_FULLB + 8 * rg.slot, rg.phase);                                       \
        mbar_waitc(sb + BAR_FULLA + 8 * s_, (((T) >> 3) + 1) & 1);                                           \
        if (!(HF)) TL(30 + (T) / 2, tid == 0);                                                              \
        wg_fence();                                                                                         \
        _Pragma("unroll") for (int k = 0; k < (NK); k++)                                                    \
            wgmma_n64(acc, dA + ((s_ * SLOT + k * 32) >> 4), dB + ((rg.slot * SLOT + (HF) * 8192 + k * 2048) >> 4), ((T) | k) != 0); \
        wg_commit();                                                                                        \
        wg_wait<1>();                                                                                       \
        mbar_arrive_if(sb + BAR_EMPTYA + 8 * (((T) + 7) & 7), l0 && (T) > 0);                               \
        if (!(HF)) mbar_arrive_if(sb + BAR_EMPTYB + 8 * prev, l0 && (T) > 0);                               \
        if (HF) { prev = rg.slot; rg.adv(); }                                                               \
    } while (0)
#pragma unroll 1
            for (int t = 0; t < 16; t += 2) { KT_P4(t, 0, 4); KT_P4(t + 1, 1, 4); }
            TL(14, tid == 0);
#pragma unroll 1
            for (int t = 16; t < 24; t += 2) { KT_P4(t, 0, 3); KT_P4(t + 1, 1, 3); }
            wg_wait<0>();
            fence_acc<32>(acc);
            TL(15, tid == 0);
            const float r0 = lds_f2(sb + OFF_CS1 + (16 * warp + g) * 8).y, r1 = lds_f2(sb + OFF_CS1 + (16 * warp + g + 8) * 8).y;
#pragma unroll
            for (int t = 0; t < 8; t++) {
                res_lo[t] = pack_bf16(fmaf(acc[4 * t], r0, bf_lo(res_lo[t])), fmaf(acc[4 * t + 1], r0, bf_hi(res_lo[t])));
                res_hi[t] = pack_bf16(fmaf(acc[4 * t + 2], r1, bf_lo(res_hi[t])), fmaf(acc[4 * t + 3], r1, bf_hi(res_hi[t])));
            }
            store_tile(own_rows, P.out + (size_t)row_w * DM + 64 * j, res_lo, res_hi, lane);
            if (tid == 0 && blockIdx.x == 0) g_epoch = epoch;
            TL(16, tid == 0); TLG(1, tid == 0);
        }
    }
}

typedef CUresult (*EncodeFn)(CUtensorMap*, CUtensorMapDataType, cuuint32_t, void*, const cuuint64_t*, const cuuint64_t*,
                             const cuuint32_t*, const cuuint32_t*, CUtensorMapInterleave, CUtensorMapSwizzle,
                             CUtensorMapL2promotion, CUtensorMapFloatOOBfill);

static void make_map2d(EncodeFn enc, CUtensorMap* tm, const void* base, uint64_t cols, uint64_t rows, uint64_t pitch_elems,
                       uint32_t box_rows) {
    cuuint64_t gd[2] = {cols, rows};
    cuuint64_t gs[1] = {pitch_elems * 2};
    cuuint32_t bd[2] = {64, box_rows};
    cuuint32_t es[2] = {1, 1};
    enc(tm, CU_TENSOR_MAP_DATA_TYPE_BFLOAT16, 2, const_cast<void*>(base), gd, gs, bd, es, CU_TENSOR_MAP_INTERLEAVE_NONE,
        CU_TENSOR_MAP_SWIZZLE_128B, CU_TENSOR_MAP_L2_PROMOTION_L2_256B, CU_TENSOR_MAP_FLOAT_OOB_FILL_NONE);
}

}

extern "C" void kernel_launch(void* const* d_in, const int* in_sizes, int n_in, void* d_out, int out_size) {
    using namespace hk;
    (void)in_sizes; (void)n_in; (void)out_size;
    static EncodeFn enc = nullptr;
    static void *po = nullptr, *ph = nullptr, *phh = nullptr;
    if (!enc) {
        void* fn = nullptr;
        cudaDriverEntryPointQueryResult qr;
        cudaGetDriverEntryPoint("cuTensorMapEncodeTiled", &fn, cudaEnableDefault, &qr);
        enc = (EncodeFn)fn;
        cudaGetSymbolAddress(&po, g_o);
        cudaGetSymbolAddress(&ph, g_h);
        cudaGetSymbolAddress(&phh, g_hh);
        cudaFuncSetAttribute(fused_kernel, cudaFuncAttributeMaxDynamicSharedMemorySize, SMEM_BYTES);
    }
    Params P;
    const __nv_bfloat16* x = (const __nv_bfloat16*)d_in[0];
    P.x = x;
    P.wqkv = (const __nv_bfloat16*)d_in[1];
    P.wphi = (const __nv_bfloat16*)d_in[2];
    P.wo = (const __nv_bfloat16*)d_in[3];
    P.wg = (const __nv_bfloat16*)d_in[5];
    P.wu = (const __nv_bfloat16*)d_in[6];
    P.wd = (const __nv_bfloat16*)d_in[7];
    P.out = (__nv_bfloat16*)d_out;
    make_map2d(enc, &P.tx, x, DM, SEQ, DM, 128);
    make_map2d(enc, &P.to, po, DM, SEQ, DM, 128);
    make_map2d(enc, &P.th, ph, DM, SEQ, DM, 128);
    make_map2d(enc, &P.thh, phh, FFP, SEQ, FFP, 128);
    make_map2d(enc, &P.twq, P.wqkv, 3 * DM, DM, 3 * DM, 128);
    make_map2d(enc, &P.two, P.wo, DM, DM, DM, 128);
    make_map2d(enc, &P.twg, P.wg, FF, DM, FF, 64);
    make_map2d(enc, &P.twu, P.wu, FF, DM, FF, 64);
    make_map2d(enc, &P.twd, P.wd, DM, FF, DM, 64);
    {
        cuuint64_t gd[3] = {(cuuint64_t)DM, (cuuint64_t)DM, 3};
        cuuint64_t gs[2] = {(cuuint64_t)3 * DM * 2, (cuuint64_t)DM * 2};
        cuuint32_t bd[3] = {64, 64, 2};
        cuuint32_t es[3] = {1, 1, 1};
        enc(&P.twkv, CU_TENSOR_MAP_DATA_TYPE_BFLOAT16, 3, const_cast<__nv_bfloat16*>(P.wqkv), gd, gs, bd, es,
            CU_TENSOR_MAP_INTERLEAVE_NONE, CU_TENSOR_MAP_SWIZZLE_128B, CU_TENSOR_MAP_L2_PROMOTION_L2_256B,
            CU_TENSOR_MAP_FLOAT_OOB_FILL_NONE);
    }
    fused_kernel<<<NCTA, NTHREADS, SMEM_BYTES>>>(P);
}
```

```cpp
#include <cuda_runtime.h>
#include <cuda_bf16.h>
#include <cuda.h>
#include <stdint.h>

namespace hk {

constexpr int SEQ = 2048, DM = 512, FF = 1376, FFP = 1536;
constexpr int NCTA = 132;
constexpr int NTHREADS = 384;
constexpr uint32_t SLOT = 16384;
constexpr uint32_t OFF_A = 0, OFF_B = 8 * SLOT, OFF_MISC = 14 * SLOT;
constexpr uint32_t BAR_FULLA = OFF_MISC + 0, BAR_EMPTYA = OFF_MISC + 64, BAR_FULLB = OFF_MISC + 128,
                   BAR_EMPTYB = OFF_MISC + 176, BAR_CS1 = OFF_MISC + 224, BAR_CS3 = OFF_MISC + 232,
                   BAR_PUB = OFF_MISC + 240;
constexpr uint32_t OFF_CS1 = OFF_MISC + 384;
constexpr uint32_t OFF_CS3 = OFF_CS1 + 1024;
constexpr uint32_t SMEM_BYTES = OFF_CS3 + 1536;
constexpr int NB = 6;

constexpr int ACC_KV = 0, ACC_Z = 2048, ACC_SIZE = 2176;

__device__ __align__(1024) __nv_bfloat16 g_o[SEQ * DM];
__device__ __align__(1024) __nv_bfloat16 g_h[SEQ * DM];
__device__ __align__(1024) __nv_bfloat16 g_hh[SEQ * FFP];
__device__ __align__(128) float g_hstat[SEQ * 16];
__device__ __align__(128) unsigned long long g_xstat[SEQ * 2];
__device__ __align__(128) float g_acc[8 * ACC_SIZE];
__device__ __align__(128) unsigned g_cnt[8 * 32];
__device__ __align__(128) unsigned long long g_cs[8 * 5 * 128];
__device__ __align__(128) unsigned g_flag[16 * 8 * 8];
__device__ unsigned g_epoch;

#define TL(i, pred) do {} while (0)
#define TLG(i, pred) do {} while (0)

struct Params {
    CUtensorMap tx, to, th, thh, twkv, twq, two, twg, twu, twd;
    const __nv_bfloat16 *x, *wqkv, *wphi, *wo, *wg, *wu, *wd;
    __nv_bfloat16* out;
    int use_smid;
    unsigned char role[NCTA];
};

__device__ __forceinline__ uint32_t smem_u32(const void* p) { return (uint32_t)__cvta_generic_to_shared(p); }
__device__ __forceinline__ void mbar_init(uint32_t bar, uint32_t cnt) {
    asm volatile("mbarrier.init.shared::cta.b64 [%0], %1;" ::"r"(bar), "r"(cnt) : "memory");
}
__device__ __forceinline__ void mbar_expect_tx(uint32_t bar, uint32_t bytes) {
    asm volatile("mbarrier.arrive.expect_tx.shared::cta.b64 _, [%0], %1;" ::"r"(bar), "r"(bytes) : "memory");
}
__device__ __forceinline__ void mbar_arrive(uint32_t bar) {
    asm volatile("mbarrier.arrive.shared::cta.b64 _, [%0];" ::"r"(bar) : "memory");
}
__device__ __forceinline__ void mbar_arrive_if(uint32_t bar, bool pred) {
    asm volatile("{.reg .pred p; setp.ne.u32 p, %1, 0; @p mbarrier.arrive.shared::cta.b64 _, [%0];}" ::"r"(bar), "r"((uint32_t)pred) : "memory");
}
__device__ __forceinline__ bool mbar_try(uint32_t bar, uint32_t parity) {
    uint32_t ok;
    asm volatile("{.reg .pred p; mbarrier.try_wait.parity.shared::cta.b64 p, [%1], %2; selp.u32 %0,1,0,p;}"
                 : "=r"(ok) : "r"(bar), "r"(parity) : "memory");
    return ok;
}
__device__ __forceinline__ bool mbar_test(uint32_t bar, uint32_t parity) {
    uint32_t ok;
    asm volatile("{.reg .pred p; mbarrier.test_wait.parity.shared::cta.b64 p, [%1], %2; selp.u32 %0,1,0,p;}"
                 : "=r"(ok) : "r"(bar), "r"(parity) : "memory");
    return ok;
}
__device__ __forceinline__ void trap_if_gt(uint32_t v, uint32_t lim) {
    asm volatile("{.reg .pred p; setp.gt.u32 p, %0, %1; @p trap;}" ::"r"(v), "r"(lim));
}
__device__ __forceinline__ void mbar_wait(uint32_t bar, uint32_t parity) {
    asm volatile("{\n"
                 ".reg .pred P1, P2;\n"
                 ".reg .u32 c;\n"
                 "mov.u32 c, 0;\n"
                 "LAB_WAIT:\n"
                 "mbarrier.try_wait.parity.shared::cta.b64 P1, [%0], %1;\n"
                 "@P1 bra LAB_DONE;\n"
                 "add.u32 c, c, 1;\n"
                 "setp.gt.u32 P2, c, 4194304;\n"
                 "@P2 trap;\n"
                 "bra LAB_WAIT;\n"
                 "LAB_DONE:\n"
                 "}" ::"r"(bar), "r"(parity) : "memory");
}
__device__ __forceinline__ void mbar_waitc(uint32_t bar, uint32_t parity) {
    asm volatile("{\n"
                 ".reg .pred P1;\n"
                 "LAB_WAIT:\n"
                 "mbarrier.try_wait.parity.shared::cta.b64 P1, [%0], %1;\n"
                 "@!P1 bra LAB_WAIT;\n"
                 "}" ::"r"(bar), "r"(parity) : "memory");
}
__device__ __forceinline__ void tma2d(uint32_t dst, const CUtensorMap* tm, uint32_t bar, int c0, int c1) {
    asm volatile("cp.async.bulk.tensor.2d.shared::cluster.global.mbarrier::complete_tx::bytes [%0], [%1, {%3, %4}], [%2];"
                 ::"r"(dst), "l"(tm), "r"(bar), "r"(c0), "r"(c1) : "memory");
}
__device__ __forceinline__ void tma3d(uint32_t dst, const CUtensorMap* tm, uint32_t bar, int c0, int c1, int c2) {
    asm volatile("cp.async.bulk.tensor.3d.shared::cluster.global.mbarrier::complete_tx::bytes [%0], [%1, {%3, %4, %5}], [%2];"
                 ::"r"(dst), "l"(tm), "r"(bar), "r"(c0), "r"(c1), "r"(c2) : "memory");
}
__device__ __forceinline__ void prefetch_tmap(const CUtensorMap* tm) {
    asm volatile("prefetch.tensormap [%0];" ::"l"(tm) : "memory");
}
__device__ __forceinline__ void prefetch_l2(const void* p, uint32_t bytes) {
    asm volatile("cp.async.bulk.prefetch.L2.global [%0], %1;" ::"l"(p), "r"(bytes) : "memory");
}
__device__ __forceinline__ unsigned ld_acquire(const unsigned* p) {
    unsigned v; asm volatile("ld.acquire.gpu.global.u32 %0, [%1];" : "=r"(v) : "l"(p) : "memory"); return v;
}
__device__ __forceinline__ uint4 ld_acquire4(const unsigned* p) {
    uint4 v;
    asm volatile("ld.acquire.gpu.global.v4.u32 {%0,%1,%2,%3}, [%4];" : "=r"(v.x), "=r"(v.y), "=r"(v.z), "=r"(v.w) : "l"(p) : "memory");
    return v;
}
__device__ __forceinline__ unsigned ld_relaxed(const unsigned* p) {
    unsigned v; asm volatile("ld.relaxed.gpu.global.u32 %0, [%1];" : "=r"(v) : "l"(p)); return v;
}
__device__ __forceinline__ void st_relaxed(unsigned* p, unsigned v) {
    asm volatile("st.relaxed.gpu.global.u32 [%0], %1;" ::"l"(p), "r"(v) : "memory");
}
__device__ __forceinline__ void red_relaxed(unsigned* p, unsigned v) {
    asm volatile("red.relaxed.gpu.global.add.u32 [%0], %1;" ::"l"(p), "r"(v) : "memory");
}
__device__ __forceinline__ void fence_gpu() { asm volatile("fence.acq_rel.gpu;" ::: "memory"); }
__device__ __forceinline__ void fence_async_smem() { asm volatile("fence.proxy.async.shared::cta;" ::: "memory"); }
__device__ __forceinline__ void fence_async_global() { asm volatile("fence.proxy.async.global;" ::: "memory"); }
__device__ __forceinline__ void wait_count(const unsigned* p, unsigned target) {
    uint32_t it = 0;
    while ((int)(ld_acquire(p) - target) < 0) trap_if_gt(++it, 1u << 22);
}
__device__ __forceinline__ void wait_count_warp(const unsigned* p, unsigned target) {
    uint32_t it = 0;
    while (__any_sync(0xffffffffu, (int)(ld_acquire(p) - target) < 0)) trap_if_gt(++it, 1u << 22);
}
__device__ __forceinline__ void red_f32(float* p, float a) {
    asm volatile("red.relaxed.gpu.global.add.f32 [%0], %1;" ::"l"(p), "f"(a) : "memory");
}
__device__ __forceinline__ void red_f32x2(float* p, float a, float b) {
    asm volatile("red.relaxed.gpu.global.add.v2.f32 [%0], {%1, %2};" ::"l"(p), "f"(a), "f"(b) : "memory");
}
__device__ __forceinline__ void red_f32x4(float* p, float a, float b, float c, float d) {
    asm volatile("red.relaxed.gpu.global.add.v4.f32 [%0], {%1, %2, %3, %4};" ::"l"(p), "f"(a), "f"(b), "f"(c), "f"(d) : "memory");
}
__device__ __forceinline__ float4 ld_l2_f4(const float* p) {
    float4 v;
    asm volatile("ld.relaxed.gpu.global.v4.f32 {%0,%1,%2,%3}, [%4];" : "=f"(v.x), "=f"(v.y), "=f"(v.z), "=f"(v.w) : "l"(p) : "memory");
    return v;
}
__device__ __forceinline__ float2 ld_l2_f2(const float* p) {
    float2 v;
    asm volatile("ld.relaxed.gpu.global.v2.f32 {%0,%1}, [%2];" : "=f"(v.x), "=f"(v.y) : "l"(p) : "memory");
    return v;
}
__device__ __forceinline__ float ld_l2_f(const float* p) {
    float v;
    asm volatile("ld.relaxed.gpu.global.f32 %0, [%1];" : "=f"(v) : "l"(p) : "memory");
    return v;
}
__device__ __forceinline__ uint4 ldg_nc(const void* p) {
    uint4 v;
    asm volatile("ld.global.nc.L1::no_allocate.v4.u32 {%0,%1,%2,%3}, [%4];" : "=r"(v.x), "=r"(v.y), "=r"(v.z), "=r"(v.w) : "l"(p));
    return v;
}
__device__ __forceinline__ void stg128(void* p, uint32_t a, uint32_t b, uint32_t c, uint32_t d) {
    asm volatile("st.global.v4.u32 [%0], {%1,%2,%3,%4};" ::"l"(p), "r"(a), "r"(b), "r"(c), "r"(d) : "memory");
}
__device__ __forceinline__ uint4 lds128(uint32_t a) {
    uint4 v;
    asm volatile("ld.shared.v4.u32 {%0,%1,%2,%3}, [%4];" : "=r"(v.x), "=r"(v.y), "=r"(v.z), "=r"(v.w) : "r"(a) : "memory");
    return v;
}
__device__ __forceinline__ float2 lds_f2(uint32_t a) {
    float2 v;
    asm volatile("ld.shared.v2.f32 {%0,%1}, [%2];" : "=f"(v.x), "=f"(v.y) : "r"(a) : "memory");
    return v;
}
__device__ __forceinline__ void sts_f2(uint32_t a, float x, float y) {
    asm volatile("st.shared.v2.f32 [%0], {%1,%2};" ::"r"(a), "f"(x), "f"(y) : "memory");
}
__device__ __forceinline__ void sts64(uint32_t a, uint32_t x, uint32_t y) {
    asm volatile("st.shared.v2.u32 [%0], {%1,%2};" ::"r"(a), "r"(x), "r"(y) : "memory");
}
__device__ __forceinline__ void sts128(uint32_t a, uint32_t x, uint32_t y, uint32_t z, uint32_t w) {
    asm volatile("st.shared.v4.u32 [%0], {%1,%2,%3,%4};" ::"r"(a), "r"(x), "r"(y), "r"(z), "r"(w) : "memory");
}
__device__ __forceinline__ void stsm4(uint32_t a, uint32_t r0, uint32_t r1, uint32_t r2, uint32_t r3) {
    asm volatile("stmatrix.sync.aligned.m8n8.x4.shared.b16 [%0], {%1,%2,%3,%4};" ::"r"(a), "r"(r0), "r"(r1), "r"(r2), "r"(r3) : "memory");
}
__device__ __forceinline__ void ldsm4(uint32_t a, uint32_t& r0, uint32_t& r1, uint32_t& r2, uint32_t& r3) {
    asm volatile("ldmatrix.sync.aligned.m8n8.x4.shared.b16 {%0,%1,%2,%3}, [%4];" : "=r"(r0), "=r"(r1), "=r"(r2), "=r"(r3) : "r"(a) : "memory");
}
__device__ __forceinline__ void ldsm4t(uint32_t a, uint32_t& r0, uint32_t& r1, uint32_t& r2, uint32_t& r3) {
    asm volatile("ldmatrix.sync.aligned.m8n8.x4.trans.shared.b16 {%0,%1,%2,%3}, [%4];" : "=r"(r0), "=r"(r1), "=r"(r2), "=r"(r3) : "r"(a) : "memory");
}
__device__ __forceinline__ void mma16816(float* c, const uint32_t* a, uint32_t b0, uint32_t b1) {
    asm("mma.sync.aligned.m16n8k16.row.col.f32.bf16.bf16.f32 {%0,%1,%2,%3}, {%4,%5,%6,%7}, {%8,%9}, {%0,%1,%2,%3};"
                 : "+f"(c[0]), "+f"(c[1]), "+f"(c[2]), "+f"(c[3])
                 : "r"(a[0]), "r"(a[1]), "r"(a[2]), "r"(a[3]), "r"(b0), "r"(b1));
}
__device__ __forceinline__ uint32_t pack_bf16(float lo, float hi) {
    uint32_t r; asm("cvt.rn.bf16x2.f32 %0, %1, %2;" : "=r"(r) : "f"(hi), "f"(lo)); return r;
}
__device__ __forceinline__ float bf_lo(uint32_t w) { return __uint_as_float(w << 16); }
__device__ __forceinline__ float bf_hi(uint32_t w) { return __uint_as_float(w & 0xffff0000u); }
__device__ __forceinline__ float ex2(float x) { float r; asm("ex2.approx.ftz.f32 %0, %1;" : "=f"(r) : "f"(x)); return r; }
__device__ __forceinline__ float rcp(float x) { float r; asm("rcp.approx.ftz.f32 %0, %1;" : "=f"(r) : "f"(x)); return r; }
__device__ __forceinline__ void bar_sync(int id, int n) { asm volatile("bar.sync %0, %1;" ::"r"(id), "r"(n) : "memory"); }

__device__ __forceinline__ uint32_t desc_lo(uint32_t addr) { return ((addr & 0x3FFFF) >> 4) | (512u << 16); }
#define DESC_HI "0x40000040"
__device__ __forceinline__ void wg_fence() { asm volatile("wgmma.fence.sync.aligned;" ::: "memory"); }
__device__ __forceinline__ void wg_commit() { asm volatile("wgmma.commit_group.sync.aligned;" ::: "memory"); }
template <int N> __device__ __forceinline__ void wg_wait() { asm volatile("wgmma.wait_group.sync.aligned %0;" ::"n"(N) : "memory"); }
template <int N> __device__ __forceinline__ void fence_acc(float* d) {
#pragma unroll
    for (int i = 0; i < N; i++) asm volatile("" : "+f"(d[i])::"memory");
}
#define R4(o) "+f"(d[o + 0]), "+f"(d[o + 1]), "+f"(d[o + 2]), "+f"(d[o + 3])
#define R8(o) R4(o), R4(o + 4)
__device__ __forceinline__ void wgmma_n128(float* d, uint32_t da, uint32_t db, int sc) {
    asm volatile("{.reg .pred p; .reg .b64 da, db; setp.ne.b32 p, %66, 0; mov.b64 da, {%64, " DESC_HI "}; mov.b64 db, {%65, " DESC_HI "};\n"
                 "wgmma.mma_async.sync.aligned.m64n128k16.f32.bf16.bf16 {%0,%1,%2,%3,%4,%5,%6,%7,%8,%9,%10,%11,%12,%13,%14,%15,%16,%17,%18,%19,%20,%21,%22,%23,%24,%25,%26,%27,%28,%29,%30,%31,"
                 "%32,%33,%34,%35,%36,%37,%38,%39,%40,%41,%42,%43,%44,%45,%46,%47,%48,%49,%50,%51,%52,%53,%54,%55,%56,%57,%58,%59,%60,%61,%62,%63}, da, db, p, 1, 1, 0, 1;}"
                 : R8(0), R8(8), R8(16), R8(24), R8(32), R8(40), R8(48), R8(56)
                 : "r"(da), "r"(db), "r"(sc));
}
__device__ __forceinline__ void wgmma_n64(float* d, uint32_t da, uint32_t db, int sc) {
    asm volatile("{.reg .pred p; .reg .b64 da, db; setp.ne.b32 p, %34, 0; mov.b64 da, {%32, " DESC_HI "}; mov.b64 db, {%33, " DESC_HI "};\n"
                 "wgmma.mma_async.sync.aligned.m64n64k16.f32.bf16.bf16 {%0,%1,%2,%3,%4,%5,%6,%7,%8,%9,%10,%11,%12,%13,%14,%15,%16,%17,%18,%19,%20,%21,%22,%23,%24,%25,%26,%27,%28,%29,%30,%31}, da, db, p, 1, 1, 0, 1;}"
                 : R8(0), R8(8), R8(16), R8(24)
                 : "r"(da), "r"(db), "r"(sc));
}
__device__ __forceinline__ void wgmma_n48(float* d, uint32_t da, uint32_t db, int sc) {
    asm volatile("{.reg .pred p; .reg .b64 da, db; setp.ne.b32 p, %26, 0; mov.b64 da, {%24, " DESC_HI "}; mov.b64 db, {%25, " DESC_HI "};\n"
                 "wgmma.mma_async.sync.aligned.m64n48k16.f32.bf16.bf16 {%0,%1,%2,%3,%4,%5,%6,%7,%8,%9,%10,%11,%12,%13,%14,%15,%16,%17,%18,%19,%20,%21,%22,%23}, da, db, p, 1, 1, 0, 1;}"
                 : R8(0), R8(8), R8(16)
                 : "r"(da), "r"(db), "r"(sc));
}
__device__ __forceinline__ void wgmma_n40_tt(float* d, uint32_t da, uint32_t db, int sc) {
    asm volatile("{.reg .pred p; .reg .b64 da, db; setp.ne.b32 p, %22, 0; mov.b64 da, {%20, " DESC_HI "}; mov.b64 db, {%21, " DESC_HI "};\n"
                 "wgmma.mma_async.sync.aligned.m64n40k16.f32.bf16.bf16 {%0,%1,%2,%3,%4,%5,%6,%7,%8,%9,%10,%11,%12,%13,%14,%15,%16,%17,%18,%19}, da, db, p, 1, 1, 1, 1;}"
                 : R8(0), R8(8), R4(16)
                 : "r"(da), "r"(db), "r"(sc));
}

__device__ __forceinline__ void quad_transpose(uint32_t r0, uint32_t r1, uint32_t r2, uint32_t r3, uint32_t* o, int q) {
    const bool odd = q & 1, hi = q & 2;
    uint32_t a = odd ? r0 : r1, b = odd ? r2 : r3;
    a = __shfl_xor_sync(0xffffffffu, a, 1);
    b = __shfl_xor_sync(0xffffffffu, b, 1);
    uint32_t s0 = odd ? a : r0, s1 = odd ? r1 : a, s2 = odd ? b : r2, s3 = odd ? r3 : b;
    uint32_t c = hi ? s0 : s2, d = hi ? s1 : s3;
    c = __shfl_xor_sync(0xffffffffu, c, 2);
    d = __shfl_xor_sync(0xffffffffu, d, 2);
    o[0] = hi ? c : s0; o[1] = hi ? d : s1; o[2] = hi ? s2 : c; o[3] = hi ? s3 : d;
}
__device__ __forceinline__ void red_f32_if(float* p, float a, bool pred) {
    asm volatile("{.reg .pred p; setp.ne.u32 p, %2, 0; @p red.relaxed.gpu.global.add.f32 [%0], %1;}" ::"l"(p), "f"(a), "r"((uint32_t)pred) : "memory");
}
__device__ __forceinline__ void stg_f2_if(float* p, float a, float b, bool pred) {
    asm volatile("{.reg .pred p; setp.ne.u32 p, %3, 0; @p st.global.v2.f32 [%0], {%1,%2};}" ::"l"(p), "f"(a), "f"(b), "r"((uint32_t)pred) : "memory");
}
__device__ __forceinline__ void stg64(void* p, uint32_t a, uint32_t b) {
    asm volatile("st.global.v2.u32 [%0], {%1,%2};" ::"l"(p), "r"(a), "r"(b) : "memory");
}
__device__ __forceinline__ void store_pair(__nv_bfloat16* p, uint32_t r0, uint32_t r1, bool odd) {
    const uint32_t x = __shfl_xor_sync(0xffffffffu, odd ? r0 : r1, 1);
    stg64(p, odd ? x : r0, odd ? r1 : x);
}
__device__ __forceinline__ void mma16816_z(float* c, const uint32_t* a, uint32_t b0, uint32_t b1) {
    asm("mma.sync.aligned.m16n8k16.row.col.f32.bf16.bf16.f32 {%0,%1,%2,%3}, {%4,%5,%6,%7}, {%8,%9}, {%10,%10,%10,%10};"
                 : "=f"(c[0]), "=f"(c[1]), "=f"(c[2]), "=f"(c[3])
                 : "r"(a[0]), "r"(a[1]), "r"(a[2]), "r"(a[3]), "r"(b0), "r"(b1), "f"(0.f));
}
__device__ __forceinline__ uint32_t max2(uint32_t a, uint32_t b) { uint32_t r; asm("max.bf16x2 %0, %1, %2;" : "=r"(r) : "r"(a), "r"(b)); return r; }
__device__ __forceinline__ uint32_t min2(uint32_t a, uint32_t b) { uint32_t r; asm("min.bf16x2 %0, %1, %2;" : "=r"(r) : "r"(a), "r"(b)); return r; }
__device__ __forceinline__ void bar_arrive(int id, int n) { asm volatile("bar.arrive %0, %1;" ::"r"(id), "r"(n) : "memory"); }
__device__ __forceinline__ void mbar_arrive_n_if(uint32_t bar, uint32_t n, bool pred) {
    asm volatile("{.reg .pred p; setp.ne.u32 p, %1, 0; @p mbarrier.arrive.shared::cta.b64 _, [%0], %2;}" ::"r"(bar), "r"((uint32_t)pred), "r"(n) : "memory");
}
__device__ __forceinline__ float4 lds_f4(uint32_t a) {
    float4 v;
    asm volatile("ld.shared.v4.f32 {%0,%1,%2,%3}, [%4];" : "=f"(v.x), "=f"(v.y), "=f"(v.z), "=f"(v.w) : "r"(a) : "memory");
    return v;
}
__device__ __forceinline__ uint4 ld_tagged(const unsigned long long* p) {
    unsigned long long a, b;
    asm volatile("ld.acquire.gpu.global.v2.b64 {%0,%1}, [%2];" : "=l"(a), "=l"(b) : "l"(p) : "memory");
    return make_uint4((unsigned)a, (unsigned)(a >> 32), (unsigned)b, (unsigned)(b >> 32));
}
__device__ __forceinline__ void st_tagged_if(unsigned long long* p, float a, float b, unsigned tag, bool pred) {
    const unsigned long long t = (unsigned long long)tag << 32;
    asm volatile("{.reg .pred p; setp.ne.u32 p, %3, 0; @p st.relaxed.gpu.global.v2.b64 [%0], {%1,%2};}"
                 ::"l"(p), "l"(t | __float_as_uint(a)), "l"(t | __float_as_uint(b)), "r"((uint32_t)pred) : "memory");
}

__device__ __forceinline__ void store_tile(uint32_t tile_rows, __nv_bfloat16* gdst, const uint32_t* lo, const uint32_t* hi, int lane) {
    const int r = lane & 15;
#pragma unroll
    for (int b = 0; b < 4; b++)
        stsm4(tile_rows + r * 128 + (((2 * b + (lane >> 4)) ^ (r & 7)) << 4), lo[2 * b], hi[2 * b], lo[2 * b + 1], hi[2 * b + 1]);
    __syncwarp();
#pragma unroll
    for (int i = 0; i < 4; i++) {
        const int rr = 4 * i + (lane >> 3);
        const uint4 v = lds128(tile_rows + rr * 128 + (((lane & 7) ^ (rr & 7)) << 4));
        stg128(gdst + rr * DM + (lane & 7) * 8, v.x, v.y, v.z, v.w);
    }
}

template <bool NORM>
__device__ __forceinline__ void feature_map(const uint32_t* a, const uint32_t* wb, float c0, float c1, uint32_t* plus, uint32_t* minus, float* rs) {
    float p[8];
    mma16816_z(p, a, wb[0], wb[1]);
    mma16816_z(p + 4, a, wb[2], wb[3]);
    const uint32_t P0 = pack_bf16(p[0], p[2]), P1 = pack_bf16(p[1], p[3]), P2 = pack_bf16(p[4], p[6]), P3 = pack_bf16(p[5], p[7]);
    uint32_t mx = max2(max2(P0, P1), max2(P2, P3)), mn = min2(min2(P0, P1), min2(P2, P3));
#pragma unroll
    for (int s = 1; s <= 2; s <<= 1) {
        mx = max2(mx, __shfl_xor_sync(0xffffffffu, mx, s));
        mn = min2(mn, __shfl_xor_sync(0xffffffffu, mn, s));
    }
    const float mx0 = bf_lo(mx) * c0, mx1 = bf_hi(mx) * c1, mn0 = bf_lo(mn) * c0, mn1 = bf_hi(mn) * c1;
    p[0] = bf_lo(P0); p[2] = bf_hi(P0); p[1] = bf_lo(P1); p[3] = bf_hi(P1);
    p[4] = bf_lo(P2); p[6] = bf_hi(P2); p[5] = bf_lo(P3); p[7] = bf_hi(P3);
    float ep[8], em[8];
#pragma unroll
    for (int i = 0; i < 8; i++) {
        const bool r1 = (i & 2);
        ep[i] = ex2(fmaf(p[i], r1 ? c1 : c0, r1 ? -mx1 : -mx0));
        em[i] = ex2(fmaf(p[i], r1 ? -c1 : -c0, r1 ? mn1 : mn0));
    }
    float sp[4], sm[4];
#pragma unroll
    for (int i = 0; i < 4; i++) { plus[i] = pack_bf16(ep[2 * i], ep[2 * i + 1]); minus[i] = pack_bf16(em[2 * i], em[2 * i + 1]); }
    mma16816_z(sp, plus, 0x3f803f80u, 0x3f803f80u);
    mma16816_z(sm, minus, 0x3f803f80u, 0x3f803f80u);
    rs[0] = rcp(sp[0]); rs[1] = rcp(sp[2]); rs[2] = rcp(sm[0]); rs[3] = rcp(sm[2]);
    if (NORM) {
#pragma unroll
        for (int i = 0; i < 4; i++) {
            plus[i] = pack_bf16(ep[2 * i] * rs[i & 1], ep[2 * i + 1] * rs[i & 1]);
            minus[i] = pack_bf16(em[2 * i] * rs[2 + (i & 1)], em[2 * i + 1] * rs[2 + (i & 1)]);
        }
    }
}

template <bool SCALE>
__device__ __forceinline__ void ln_frag(const float* acc, uint32_t cs_addr, float rs0, float nm0, float rs1, float nm1, uint32_t* a) {
    const float2 c0 = lds_f2(cs_addr), c1 = lds_f2(cs_addr + 32);
    const float s0 = SCALE ? rs0 : 1.f, s1 = SCALE ? rs1 : 1.f;
    a[0] = pack_bf16(fmaf(nm0, c0.x, acc[0]) * s0, fmaf(nm0, c0.y, acc[1]) * s0);
    a[1] = pack_bf16(fmaf(nm1, c0.x, acc[2]) * s1, fmaf(nm1, c0.y, acc[3]) * s1);
    a[2] = pack_bf16(fmaf(nm0, c1.x, acc[4]) * s0, fmaf(nm0, c1.y, acc[5]) * s0);
    a[3] = pack_bf16(fmaf(nm1, c1.x, acc[6]) * s1, fmaf(nm1, c1.y, acc[7]) * s1);
}

__device__ __forceinline__ uint32_t hh_pair(const float* ag, float4 cs, float nmean) {
    const float g0 = fmaf(nmean, cs.x, ag[0]), g1 = fmaf(nmean, cs.y, ag[1]);
    const float u0 = fmaf(nmean, cs.z, ag[32]), u1 = fmaf(nmean, cs.w, ag[33]);
    return pack_bf16(g0 * u0, g1 * u1);
}

struct Ring {
    int slot; uint32_t phase;
    __device__ __forceinline__ void adv() { if (++slot == NB) { slot = 0; phase ^= 1; } }
};

__global__ void __launch_bounds__(NTHREADS, 1) fused_kernel(const __grid_constant__ Params P) {
    extern __shared__ __align__(1024) uint8_t smem_raw[];
    const uint32_t sb = smem_u32(smem_raw);
    const int tid = threadIdx.x, lane = tid & 31;
    const int warp = __shfl_sync(0xffffffffu, tid >> 5, 0);
    unsigned role = blockIdx.x;
    if (P.use_smid) asm volatile("mov.u32 %0, %%smid;" : "=r"(role));
    role = P.role[role];
    const int m = role >> 3, j = role & 7;
    const bool helper = role >= 128;

    const unsigned epoch = ld_relaxed(&g_epoch) + 1;
    uint4 xv[4];
    uint32_t wraw[16];
    if (warp < 8) {
        if (!helper) {
            const __nv_bfloat16* xp = P.x + (size_t)(128 * m + 16 * j + 2 * warp + (lane >> 4)) * DM + (lane & 15) * 8;
#pragma unroll
            for (int i = 0; i < 4; i++) xv[i] = ldg_nc(xp + 128 * i);
            const uint32_t* wp = reinterpret_cast<const uint32_t*>(P.wphi) + (4 * j) * 128 + (lane & 3) * 16 + (lane >> 2);
#pragma unroll
            for (int i = 0; i < 16; i++)
                asm volatile("ld.global.nc.u32 %0, [%1];" : "=r"(wraw[i]) : "l"(wp + (i >> 2) * 128 + ((i >> 1) & 1) * 64 + (i & 1) * 8));
        }
    } else if (warp == 8) {
        if (lane < NB) {
            const uint32_t full = sb + BAR_FULLB + 8 * lane;
            mbar_init(full, 1); mbar_init(sb + BAR_EMPTYB + 8 * lane, 8);
            asm volatile("fence.mbarrier_init.release.cluster;" ::: "memory");
            if (!helper) {
                mbar_expect_tx(full, SLOT);
                tma3d(sb + OFF_B + lane * SLOT, &P.twkv, full, 64 * j, 64 * lane, 1);
            }
        }
    } else if (warp == 9) {
        if (lane < 8) {
            const uint32_t full = sb + BAR_FULLA + 8 * lane;
            mbar_init(full, 1); mbar_init(sb + BAR_EMPTYA + 8 * lane, 8);
            asm volatile("fence.mbarrier_init.release.cluster;" ::: "memory");
            if (!helper) {
                mbar_expect_tx(full, SLOT);
                tma2d(sb + OFF_A + lane * SLOT, &P.tx, full, 64 * lane, 128 * m);
            }
        }
    } else if (warp == 10) {
        if (lane < 14) mbar_init(sb + BAR_CS1 + 8 * lane, lane == 0 ? 32 : (lane == 1 ? 160 : 4));
        trap_if_gt(sb & 1023, 0);
    }
    TL(0, tid == 0); TLG(0, tid == 0);
    __syncthreads();

    if (helper) {
        if (warp == 8) {
            if (lane == 0) {
#pragma unroll 1
                for (int i = 0; i < 72; i++) {
                    const uint32_t full = sb + BAR_FULLA + 8 * (i & 7), dst = sb + OFF_A + (i & 7) * SLOT;
                    mbar_wait(sb + BAR_EMPTYA + 8 * (i & 7), ((i >> 3) & 1) ^ 1);
                    mbar_expect_tx(full, SLOT);
                    if (i < 16) {
                        tma3d(dst, &P.twkv, full, 64 * (2 * j + (i >> 3)), 64 * (i & 7), 1);
                    } else if (i < 24) {
                        tma2d(dst, &P.twq, full, 64 * (2 * j + ((i >> 2) & 1)), 128 * (i & 3));
                    } else {
                        const int u = (i >> 3) - 3, c0 = 176 * (2 * j + (u & 1)) + 64 * (u >> 1);
                        tma2d(dst, &P.twg, full, c0, 64 * (i & 7));
                        tma2d(dst + 8192, &P.twu, full, c0, 64 * (i & 7));
                    }
                }
                prefetch_l2(P.wd + (size_t)j * 176128, 352256);
            }
        } else if (warp == 9) {
            if (lane == 0) prefetch_l2(P.wo + (size_t)j * 65536, 131072);
            wait_count_warp(g_cnt + (lane & 7) * 32, epoch * 32);
        } else if (warp < 4) {
            for (int i = tid; i < 2 * ACC_SIZE / 4; i += 128) stg128(g_acc + 2 * j * ACC_SIZE + 4 * i, 0, 0, 0, 0);
            for (int i = tid; i < 512; i += 128) sts128(sb + OFF_B + 16 * i, 0x3f803f80u, 0x3f803f80u, 0x3f803f80u, 0x3f803f80u);
            fence_async_smem();
            fence_gpu();
            bar_sync(1, 128);
            float acc[64];
            int i = 0;
#pragma unroll 1
            for (int job = 0; job < 10; job++) {
                const int n = (job >> 1) == 1 ? 4 : 8;
#pragma unroll 1
                for (int t = 0; t < n; t++, i++) {
                    mbar_wait(sb + BAR_FULLA + 8 * (i & 7), (i >> 3) & 1);
                    wg_fence();
#pragma unroll
                    for (int k = 0; k < 4; k++)
                        wgmma_n128(acc, desc_lo(sb + OFF_B), desc_lo(sb + OFF_A) + (((i & 7) * SLOT + k * 2048) >> 4), (t | k) != 0);
                    wg_commit();
                    wg_wait<0>();
                    mbar_arrive_n_if(sb + BAR_EMPTYA + 8 * (i & 7), 2, lane == 0);
                }
                fence_acc<64>(acc);
                unsigned long long* dst = g_cs + ((2 * j + (job & 1)) * 5 + (job >> 1)) * 128 + 2 * (lane & 3);
#pragma unroll
                for (int t = 0; t < 16; t++) st_tagged_if(dst + 8 * t, acc[4 * t], acc[4 * t + 1], epoch, (tid >> 2) == t);
            }
        }
        return;
    }

    float* const acc_j = g_acc + j * ACC_SIZE;
    unsigned* const cnt_j = g_cnt + j * 32;

    if (warp >= 8) {
        asm volatile("setmaxnreg.dec.sync.aligned.u32 72;");
        if (warp == 8) {
            if (lane == 0) {
                Ring r{0, 1};
#pragma unroll 1
                for (int i = 6; i < 56; i++) {
                    const uint32_t full = sb + BAR_FULLB + 8 * r.slot, dst = sb + OFF_B + r.slot * SLOT;
                    mbar_wait(sb + BAR_EMPTYB + 8 * r.slot, r.phase ^ 1);
                    if (i >= 8 && i < 12) {
                        mbar_arrive(full);
                    } else {
                        mbar_expect_tx(full, SLOT);
                        if (i < 8) {
                            tma3d(dst, &P.twkv, full, 64 * j, 64 * i, 1);
                        } else if (i < 20) {
                            tma2d(dst, i < 16 ? &P.twq : &P.two, full, 64 * j, 128 * (i & 3));
                        } else if (i < 44) {
                            const int c = (i - 20) >> 3, kt = (i - 20) & 7;
                            tma2d(dst, &P.twg, full, 176 * j + 64 * c, 64 * kt);
                            tma2d(dst + 8192, &P.twu, full, 176 * j + 64 * c, 64 * kt);
                        } else {
                            const int c = (i - 44) >> 2, jj = (i & 3) * 2;
                            tma2d(dst, &P.twd, full, 64 * j, 176 * jj + 64 * c);
                            tma2d(dst + 8192, &P.twd, full, 64 * j, 176 * (jj + 1) + 64 * c);
                        }
                    }
                    r.adv();
                }
            }
        } else if (warp == 9) {
            int r = (lane < 8) ? 1 : 6;
            int ready = (lane == j) ? 2 : 0;
            uint32_t it = 0;
            while (__any_sync(0xffffffffu, r < 6)) {
                const bool e = r < 6 && mbar_test(sb + BAR_EMPTYA + 8 * (lane & 7), (r - 1) & 1);
                const bool pending = __any_sync(0xffffffffu, r < 6 && ready >= r);
                if (r < 6 && ready < r && (e || !pending)) {
                    const uint4 f = ld_acquire4(g_flag + (m * 8 + lane) * 8 + (r < 3 ? 0 : 4));
                    if (r < 3) ready = (f.x == epoch && f.y == epoch) ? ((f.z == epoch && f.w == epoch) ? 2 : 1) : 0;
                    else ready = f.x == epoch ? (f.y == epoch ? (f.z == epoch ? 5 : 4) : 3) : 2;
                }
                if (e && ready >= r) {
                    const uint32_t full = sb + BAR_FULLA + 8 * lane;
                    if (r < 3 && lane == j) {
                        mbar_arrive(full);
                    } else {
                        fence_async_global();
                        mbar_expect_tx(full, SLOT);
                        const CUtensorMap* tm = r == 1 ? &P.to : (r == 2 ? &P.th : &P.thh);
                        const int c0 = r < 3 ? 64 * lane : 192 * lane + 64 * (r - 3);
                        tma2d(sb + OFF_A + lane * SLOT, tm, full, c0, 128 * m);
                    }
                    r++;
                }
                trap_if_gt(++it, 1u << 24);
            }
        } else {
            const int a = warp - 10;
            const unsigned long long* cs = g_cs + j * 640 + 2 * lane;
            if (a == 0) {
                uint4 v[4];
                uint32_t it = 0;
                bool bad;
                do {
                    bad = false;
#pragma unroll
                    for (int i = 0; i < 4; i++) { v[i] = ld_tagged(cs + 64 * i); bad |= v[i].y != epoch || v[i].w != epoch; }
                    trap_if_gt(++it, 1u << 22);
                } while (__any_sync(0xffffffffu, bad));
                sts64(sb + OFF_CS1 + 256 + 8 * lane, v[0].x, v[0].z);
                sts64(sb + OFF_CS1 + 512 + 8 * lane, v[1].x, v[1].z);
                sts_f2(sb + OFF_CS1 + 8 * lane, __uint_as_float(v[2].x) + __uint_as_float(v[3].x), __uint_as_float(v[2].z) + __uint_as_float(v[3].z));
                mbar_arrive(sb + BAR_CS1);
            }
#pragma unroll 1
            for (int ev = 0; ev < 6; ev += (ev >= 2 + a) ? 2 - (ev == 2) : 1 + (ev == 2)) {
                if (lane == 0) {
                    mbar_wait(sb + BAR_PUB + 8 * (a * 6 + ev), 0);
                    fence_gpu();
                    if (ev == 0) red_relaxed(cnt_j, 1);
                    else st_relaxed(g_flag + role * 8 + (ev < 3 ? 2 * ev - 2 + a : ev + 1), epoch);
                }
                __syncwarp();
                if (ev == 2 && a == 0) {
#pragma unroll 1
                    for (int c = 0; c < 3; c++) {
                        uint4 vg, vu;
                        uint32_t it = 0;
                        do {
                            vg = ld_tagged(cs + 256 + 128 * c); vu = ld_tagged(cs + 320 + 128 * c);
                            trap_if_gt(++it, 1u << 22);
                        } while (__any_sync(0xffffffffu, vg.y != epoch || vg.w != epoch || vu.y != epoch || vu.w != epoch));
                        sts128(sb + OFF_CS3 + (32 * c + lane) * 16, vg.x, vg.z, vu.x, vu.z);
                    }
                    mbar_arrive(sb + BAR_CS3);
                }
            }
        }
    } else {
        asm volatile("setmaxnreg.inc.sync.aligned.u32 216;");
        const int w = warp >> 2, wv = warp & 3, g = lane >> 2, q = lane & 3;
        const int row_w = 128 * m + 16 * warp;
        const uint32_t sa = sb + OFF_A + w * 8192;
        const uint32_t dA = desc_lo(sa), dB = desc_lo(sb + OFF_B);
        const uint32_t pub = sb + BAR_PUB + 48 * w;
        const bool l0 = lane == 0;
        Ring rg{0, 0};
        int prev = 0;

        uint32_t wb[16];
        {
            const int row = 128 * m + 16 * j + 2 * warp + (lane >> 4);
            const uint4* v = xv;
            float f[32];
#pragma unroll
            for (int i = 0; i < 4; i++) {
                f[8 * i] = bf_lo(v[i].x); f[8 * i + 1] = bf_hi(v[i].x); f[8 * i + 2] = bf_lo(v[i].y); f[8 * i + 3] = bf_hi(v[i].y);
                f[8 * i + 4] = bf_lo(v[i].z); f[8 * i + 5] = bf_hi(v[i].z); f[8 * i + 6] = bf_lo(v[i].w); f[8 * i + 7] = bf_hi(v[i].w);
            }
            float s0 = 0.f, s1 = 0.f;
#pragma unroll
            for (int i = 0; i < 16; i++) { s0 += f[2 * i]; s1 += f[2 * i + 1]; }
            s0 += s1;
#pragma unroll
            for (int o = 8; o; o >>= 1) s0 += __shfl_xor_sync(0xffffffffu, s0, o);
            const float mean = s0 * (1.f / DM);
            s0 = 0.f; s1 = 0.f;
#pragma unroll
            for (int i = 0; i < 16; i++) {
                const float d0 = f[2 * i] - mean, d1 = f[2 * i + 1] - mean;
                s0 = fmaf(d0, d0, s0); s1 = fmaf(d1, d1, s1);
            }
            s0 += s1;
#pragma unroll
            for (int o = 8; o; o >>= 1) s0 += __shfl_xor_sync(0xffffffffu, s0, o);
            const float rs = rsqrtf(s0 * (1.f / DM) + 1e-5f);
            st_tagged_if(g_xstat + 2 * row, rs, -mean, epoch, (lane & 15) == 0);
        }
        constexpr float L2E = 1.4426950408889634f;
        uint32_t fp[16], fm[16];
        float fr[16];
        float rs0, nm0, rs1, nm1;
        {
            float acc[64];
#pragma unroll 1
            for (int kt = 0; kt < 8; kt++) {
                mbar_waitc(sb + BAR_FULLA + 8 * kt, 0);
                mbar_waitc(sb + BAR_FULLB + 8 * rg.slot, rg.phase);
                TL(20 + kt, tid == 0);
                wg_fence();
#pragma unroll
                for (int k = 0; k < 4; k++)
                    wgmma_n128(acc, dA + ((kt * SLOT + k * 32) >> 4), dB + ((rg.slot * SLOT + k * 2048) >> 4), (kt | k) != 0);
                wg_commit();
                wg_wait<1>();
                mbar_arrive_if(sb + BAR_EMPTYB + 8 * prev, l0 && kt > 0);
                prev = rg.slot; rg.adv();
            }
            {
                uint4 a, b;
                uint32_t it = 0;
                do {
                    a = ld_tagged(g_xstat + 2 * (row_w + g));
                    b = ld_tagged(g_xstat + 2 * (row_w + g + 8));
                    trap_if_gt(++it, 1u << 22);
                } while (__any_sync(0xffffffffu, a.y != epoch || a.w != epoch || b.y != epoch || b.w != epoch));
                rs0 = __uint_as_float(a.x); nm0 = __uint_as_float(a.z); rs1 = __uint_as_float(b.x); nm1 = __uint_as_float(b.z);
            }
#pragma unroll
            for (int i = 0; i < 8; i++) {
                wb[(i >> 1) * 4 + (i & 1)] = __byte_perm(wraw[2 * i], wraw[2 * i + 1], 0x5410);
                wb[(i >> 1) * 4 + 2 + (i & 1)] = __byte_perm(wraw[2 * i], wraw[2 * i + 1], 0x7632);
            }
            TL(17, tid == 0);
            mbar_waitc(sb + BAR_CS1, 0);
            TL(18, tid == 0);
            wg_wait<0>();
            fence_acc<64>(acc);
            mbar_arrive_if(sb + BAR_EMPTYB + 8 * prev, l0);
            TL(2, tid == 0);
#pragma unroll
            for (int i = 2; i < 6; i++) mbar_waitc(sb + BAR_FULLB + 8 * i, 1);
            const int lrow = 16 * warp + (lane & 15), ch = lane >> 4, sw = lane & 7;
            const uint32_t st = sb + OFF_B + 2 * SLOT + lrow * 128;
            uint32_t ka[16];
#pragma unroll
            for (int hh = 0; hh < 4; hh++)
                ln_frag<false>(acc + 8 * hh, sb + OFF_CS1 + (64 + 16 * hh + 2 * q) * 4, rs0, nm0, rs1, nm1, ka + 4 * hh);
#pragma unroll
            for (int hh = 0; hh < 4; hh++) {
                uint32_t a[4];
                ln_frag<true>(acc + 32 + 8 * hh, sb + OFF_CS1 + (128 + 16 * hh + 2 * q) * 4, rs0, nm0, rs1, nm1, a);
                stsm4(st + (2 + (hh >> 1)) * SLOT + (((2 * (hh & 1) + ch) ^ sw) << 4), a[0], a[1], a[2], a[3]);
            }
#pragma unroll
            for (int hh = 0; hh < 4; hh++) feature_map<true>(ka + 4 * hh, wb + 4 * hh, rs0 * L2E, rs1 * L2E, fp + 4 * hh, fm + 4 * hh, fr);
#pragma unroll
            for (int hh = 0; hh < 4; hh++) {
                stsm4(st + (hh >> 1) * SLOT + (((4 * (hh & 1) + ch) ^ sw) << 4), fp[4 * hh], fp[4 * hh + 1], fp[4 * hh + 2], fp[4 * hh + 3]);
                stsm4(st + (hh >> 1) * SLOT + (((4 * (hh & 1) + 2 + ch) ^ sw) << 4), fm[4 * hh], fm[4 * hh + 1], fm[4 * hh + 2], fm[4 * hh + 3]);
            }
            stsm4(st + (2 + ch) * SLOT + ((4 ^ sw) << 4), 0x3f803f80u, 0x3f803f80u, 0x3f803f80u, 0x3f803f80u);
            fence_async_smem();
            TL(19, tid == 0);
            bar_sync(1, 256);
            float kvd[20];
            wg_fence();
#pragma unroll
            for (int k = 0; k < 8; k++)
                wgmma_n40_tt(kvd, dB + (((2 + w) * SLOT + k * 2048) >> 4), dB + (((4 + w) * SLOT + k * 2048) >> 4), k != 0);
            wg_commit();
            wg_wait<0>();
            fence_acc<20>(kvd);
            const bool h1 = wv >= 2;
            const int f = 16 * warp + g;
            float* kvp = acc_j + ACC_KV + f * 16 + 2 * q;
            red_f32x2(kvp, h1 ? kvd[8] : kvd[0], h1 ? kvd[9] : kvd[1]);
            red_f32x2(kvp + 128, h1 ? kvd[10] : kvd[2], h1 ? kvd[11] : kvd[3]);
            red_f32x2(kvp + 8, h1 ? kvd[12] : kvd[4], h1 ? kvd[13] : kvd[5]);
            red_f32x2(kvp + 136, h1 ? kvd[14] : kvd[6], h1 ? kvd[15] : kvd[7]);
            red_f32_if(acc_j + ACC_Z + f + 8 * (q & 1), q ? kvd[18] : kvd[16], q < 2);
            __syncwarp();
            mbar_arrive_if(pub, l0);
            mbar_arrive_if(sb + BAR_EMPTYB + 8 * (2 + (lane & 3)), lane < 4);
            TL(3, tid == 0);
        }
        uint32_t res_lo[8], res_hi[8];
        const uint32_t own_rows = sb + OFF_A + j * SLOT + warp * 2048;
        {
            float acc[32];
            rg.slot = 0; rg.phase = 0;
#pragma unroll 1
            for (int b = 0; b < 4; b++) {
                mbar_waitc(sb + BAR_FULLB + 8 * rg.slot, rg.phase);
                wg_fence();
#pragma unroll
                for (int k = 0; k < 8; k++)
                    wgmma_n64(acc, dA + (((2 * b + (k >> 2)) * SLOT + (k & 3) * 32) >> 4), dB + ((rg.slot * SLOT + k * 2048) >> 4), (b | k) != 0);
                wg_commit();
                wg_wait<1>();
                mbar_arrive_if(sb + BAR_EMPTYB + 8 * prev, l0 && b > 0);
                prev = rg.slot; rg.adv();
            }
            wg_wait<0>();
            fence_acc<32>(acc);
            mbar_arrive_if(sb + BAR_EMPTYB + 8 * prev, l0);
            mbar_arrive_if(sb + BAR_EMPTYA + 8 * (lane & 7), lane < 8 && (lane | 1) != (j | 1));
            TL(4, tid == 0);
            uint32_t qa[16];
#pragma unroll
            for (int hh = 0; hh < 4; hh++)
                ln_frag<false>(acc + 8 * hh, sb + OFF_CS1 + (16 * hh + 2 * q) * 4, rs0, nm0, rs1, nm1, qa + 4 * hh);
#pragma unroll
            for (int hh = 0; hh < 4; hh++) feature_map<false>(qa + 4 * hh, wb + 4 * hh, rs0 * L2E, rs1 * L2E, fp + 4 * hh, fm + 4 * hh, fr + 4 * hh);
#pragma unroll
            for (int b = 0; b < 4; b++)
                ldsm4(own_rows + (lane & 15) * 128 + (((2 * b + (lane >> 4)) ^ (lane & 7)) << 4),
                      res_lo[2 * b], res_hi[2 * b], res_lo[2 * b + 1], res_hi[2 * b + 1]);
            TL(5, tid == 0);
            if (warp == 0) wait_count_warp(cnt_j, epoch * 32);
            TL(6, tid == 0);
            bar_sync(1, 256);
            const uint32_t kvs = sb + OFF_A + (j ^ 1) * SLOT;
            {
                const float4 a0 = ld_l2_f4(acc_j + ACC_KV + 4 * tid), a1 = ld_l2_f4(acc_j + ACC_KV + 4 * (tid + 256));
                const float zz = ld_l2_f(acc_j + ACC_Z + (tid & 127));
                sts64(kvs + (tid >> 2) * 48 + (tid & 3) * 8, pack_bf16(a0.x, a0.y), pack_bf16(a0.z, a0.w));
                sts64(kvs + ((tid >> 2) + 64) * 48 + (tid & 3) * 8, pack_bf16(a1.x, a1.y), pack_bf16(a1.z, a1.w));
                const uint32_t z2 = pack_bf16(zz, zz);
                sts64(kvs + (tid & 127) * 48 + 32 + w * 8, z2, z2);
            }
            bar_sync(1, 256);
            uint32_t o_lo[8], o_hi[8];
#pragma unroll
            for (int hh = 0; hh < 4; hh++) {
                uint32_t b[8], zb[4];
                const uint32_t base = kvs + hh * 32 * 48;
                ldsm4t(base + (lane & 15) * 48 + (lane >> 4) * 16, b[0], b[1], b[2], b[3]);
                ldsm4t(base + (16 + (lane & 15)) * 48 + (lane >> 4) * 16, b[4], b[5], b[6], b[7]);
                ldsm4t(base + lane * 48 + 32, zb[0], zb[1], zb[2], zb[3]);
                float n0[4], n1[4], dn[4], m0[4], m1[4], dm[4];
                mma16816_z(n0, fp + 4 * hh, b[0], b[1]); mma16816_z(n1, fp + 4 * hh, b[2], b[3]); mma16816_z(dn, fp + 4 * hh, zb[0], zb[1]);
                mma16816_z(m0, fm + 4 * hh, b[4], b[5]); mma16816_z(m1, fm + 4 * hh, b[6], b[7]); mma16816_z(dm, fm + 4 * hh, zb[2], zb[3]);
                const float* r = fr + 4 * hh;
                const float i0 = rcp(fmaf(dn[0], r[0], fmaf(dm[0], r[2], 1e-6f))), i1 = rcp(fmaf(dn[2], r[1], fmaf(dm[2], r[3], 1e-6f)));
                const float p0 = r[0] * i0, q0 = r[2] * i0, p1 = r[1] * i1, q1 = r[3] * i1;
                o_lo[2 * hh] = pack_bf16(fmaf(n0[0], p0, m0[0] * q0), fmaf(n0[1], p0, m0[1] * q0));
                o_hi[2 * hh] = pack_bf16(fmaf(n0[2], p1, m0[2] * q1), fmaf(n0[3], p1, m0[3] * q1));
                o_lo[2 * hh + 1] = pack_bf16(fmaf(n1[0], p0, m1[0] * q0), fmaf(n1[1], p0, m1[1] * q0));
                o_hi[2 * hh + 1] = pack_bf16(fmaf(n1[2], p1, m1[2] * q1), fmaf(n1[3], p1, m1[3] * q1));
            }
            store_tile(own_rows, g_o + (size_t)row_w * DM + 64 * j, o_lo, o_hi, lane);
            fence_async_smem();
            __syncwarp();
            mbar_arrive_if(pub + 8, l0);
            mbar_arrive_if(sb + BAR_EMPTYA + 8 * (j ^ (lane & 1)), lane < 2);
            TL(7, tid == 0);
        }
        {
            float acc[32];
#pragma unroll
            for (int t = 0; t < 8; t++) {
                acc[4 * t] = bf_lo(res_lo[t]); acc[4 * t + 1] = bf_hi(res_lo[t]);
                acc[4 * t + 2] = bf_lo(res_hi[t]); acc[4 * t + 3] = bf_hi(res_hi[t]);
            }
            fence_acc<32>(acc);
#pragma unroll 1
            for (int kp = 0; kp < 4; kp++) {
                mbar_waitc(sb + BAR_FULLB + 8 * rg.slot, rg.phase);
#pragma unroll
                for (int hf = 0; hf < 2; hf++) {
                    const int kt = 2 * kp + hf;
                    mbar_waitc(sb + BAR_FULLA + 8 * kt, 1);
                    TL(8, kt == 0 && tid == 0);
                    wg_fence();
#pragma unroll
                    for (int k = 0; k < 4; k++)
                        wgmma_n64(acc, dA + ((kt * SLOT + k * 32) >> 4), dB + ((rg.slot * SLOT + (hf * 4 + k) * 2048) >> 4), 1);
                    wg_commit();
                    wg_wait<1>();
                    mbar_arrive_if(sb + BAR_EMPTYA + 8 * ((kt + 7) & 7), l0 && kt > 0 && kt - 1 != j);
                    if (hf == 0) mbar_arrive_if(sb + BAR_EMPTYB + 8 * prev, l0 && kt > 0);
                }
                prev = rg.slot; rg.adv();
            }
            wg_wait<0>();
            fence_acc<32>(acc);
            mbar_arrive_if(sb + BAR_EMPTYA + 8 * 7, l0 && j != 7);
            mbar_arrive_if(sb + BAR_EMPTYB + 8 * prev, l0);
            TL(9, tid == 0);
            float s0 = 0.f, s1 = 0.f;
#pragma unroll
            for (int t = 0; t < 8; t++) {
                res_lo[t] = pack_bf16(acc[4 * t], acc[4 * t + 1]);
                res_hi[t] = pack_bf16(acc[4 * t + 2], acc[4 * t + 3]);
                s0 += acc[4 * t] + acc[4 * t + 1];
                s1 += acc[4 * t + 2] + acc[4 * t + 3];
            }
            store_tile(own_rows, g_h + (size_t)row_w * DM + 64 * j, res_lo, res_hi, lane);
            s0 += __shfl_xor_sync(0xffffffffu, s0, 1); s1 += __shfl_xor_sync(0xffffffffu, s1, 1);
            s0 += __shfl_xor_sync(0xffffffffu, s0, 2); s1 += __shfl_xor_sync(0xffffffffu, s1, 2);
            const float mu0 = s0 * (1.f / 64), mu1 = s1 * (1.f / 64);
            float q0 = 0.f, q1 = 0.f;
#pragma unroll
            for (int t = 0; t < 8; t++) {
                float d;
                d = acc[4 * t] - mu0; q0 = fmaf(d, d, q0);
                d = acc[4 * t + 1] - mu0; q0 = fmaf(d, d, q0);
                d = acc[4 * t + 2] - mu1; q1 = fmaf(d, d, q1);
                d = acc[4 * t + 3] - mu1; q1 = fmaf(d, d, q1);
            }
            q0 += __shfl_xor_sync(0xffffffffu, q0, 1); q1 += __shfl_xor_sync(0xffffffffu, q1, 1);
            q0 += __shfl_xor_sync(0xffffffffu, q0, 2); q1 += __shfl_xor_sync(0xffffffffu, q1, 2);
            stg_f2_if(g_hstat + (row_w + g + 8 * (q & 1)) * 16 + 2 * j, q ? mu1 : mu0, q ? q1 : q0, q < 2);
            fence_async_smem();
            __syncwarp();
            mbar_arrive_if(pub + 16, l0);
            mbar_arrive_if(sb + BAR_EMPTYA + 8 * j, l0);
            TL(10, tid == 0);
        }
        if (w == 1) {
#pragma unroll 1
            for (int kt = 0; kt < 8; kt++) mbar_waitc(sb + BAR_FULLA + 8 * kt, 0);
            const float* sp = g_hstat + (128 * m + (tid & 127)) * 16;
            float4 v[4];
#pragma unroll
            for (int i = 0; i < 4; i++) v[i] = ld_l2_f4(sp + 4 * i);
            float mean = 0.f;
#pragma unroll
            for (int i = 0; i < 4; i++) mean += v[i].x + v[i].z;
            mean *= 0.125f;
            float m2 = 0.f, dv = 0.f;
#pragma unroll
            for (int i = 0; i < 4; i++) {
                m2 += v[i].y + v[i].w;
                dv = fmaf(v[i].x - mean, v[i].x - mean, dv); dv = fmaf(v[i].z - mean, v[i].z - mean, dv);
            }
            sts_f2(sb + OFF_CS1 + (tid & 127) * 8, -mean, __fdividef(1.f, fmaf(dv, 64.f, m2) * (1.f / DM) + 1e-5f));
            mbar_arrive(sb + BAR_CS3);
        }
        {
            float acc0[64], acc1[64];
            const uint32_t dA0 = desc_lo(sb + OFF_A);
#pragma unroll 1
            for (int c = w; c < 3; c += 2) {
                if (c > 0) bar_sync(1 + c, 256);
                rg.slot = (c == 2) ? 0 : 2 + 2 * c; rg.phase = (c == 0);
#pragma unroll 1
                for (int kt = 0; kt < 8; kt++) {
                    mbar_waitc(sb + BAR_FULLA + 8 * kt, 0);
                    mbar_waitc(sb + BAR_FULLB + 8 * rg.slot, rg.phase);
                    TL(44 + c * 2 + (kt == 1), (tid & 127) == 0 && kt < 2);
                    wg_fence();
#pragma unroll
                    for (int k = 0; k < 4; k++) {
                        const uint32_t db = dB + ((rg.slot * SLOT + k * 2048) >> 4);
                        wgmma_n128(acc0, dA0 + ((kt * SLOT + k * 32) >> 4), db, (kt | k) != 0);
                        wgmma_n128(acc1, dA0 + ((kt * SLOT + 8192 + k * 32) >> 4), db, (kt | k) != 0);
                    }
                    wg_commit();
                    wg_wait<1>();
                    mbar_arrive_n_if(sb + BAR_EMPTYB + 8 * prev, 2, l0 && kt > 0);
                    mbar_arrive_if(sb + BAR_EMPTYA + 8 * ((kt + 7) & 7), l0 && kt > 0 && c > 0);
                    prev = rg.slot; rg.adv();
                }
                bar_arrive(2 + c, 256);
                mbar_waitc(sb + BAR_CS3, 0);
                float nm[4];
#pragma unroll
                for (int i = 0; i < 4; i++) nm[i] = lds_f2(sb + OFF_CS1 + (64 * (i >> 1) + 16 * wv + g + 8 * (i & 1)) * 8).x;
                wg_wait<0>();
                fence_acc<64>(acc0); fence_acc<64>(acc1);
                mbar_arrive_n_if(sb + BAR_EMPTYB + 8 * prev, 2, l0);
                mbar_arrive_if(sb + BAR_EMPTYA + 8 * 7, l0 && c > 0);
                TL(11 + c, (tid & 127) == 0);
                __nv_bfloat16* hp = g_hh + (size_t)(128 * m + 16 * wv + g) * FFP + 192 * j + 64 * c + (q & 1) * 8 + (q >> 1) * 4;
#pragma unroll
                for (int tp = 0; tp < 4; tp++) {
                    if (tp < 3 || c < 2) {
                        const uint32_t ca = sb + OFF_CS3 + (32 * c + 8 * tp + q) * 16;
                        const float4 c0 = lds_f4(ca), c1 = lds_f4(ca + 64);
                        store_pair(hp + 16 * tp, hh_pair(acc0 + 8 * tp, c0, nm[0]), hh_pair(acc0 + 8 * tp + 4, c1, nm[0]), q & 1);
                        store_pair(hp + 8 * FFP + 16 * tp, hh_pair(acc0 + 8 * tp + 2, c0, nm[1]), hh_pair(acc0 + 8 * tp + 6, c1, nm[1]), q & 1);
                        store_pair(hp + 64 * FFP + 16 * tp, hh_pair(acc1 + 8 * tp, c0, nm[2]), hh_pair(acc1 + 8 * tp + 4, c1, nm[2]), q & 1);
                        store_pair(hp + 72 * FFP + 16 * tp, hh_pair(acc1 + 8 * tp + 2, c0, nm[3]), hh_pair(acc1 + 8 * tp + 6, c1, nm[3]), q & 1);
                    }
                }
                __syncwarp();
                mbar_arrive_if(pub + 24 + 8 * c, l0);
                TL(54 + c, (tid & 127) == 0);
            }
            if (w == 1) bar_sync(4, 256);
        }
        {
            float acc[32];
            rg.slot = 2; rg.phase = 1;
#define KT_P4(T, HF, NK)                                                                                    \
    do {                                                                                                    \
        const int s_ = (T) & 7;                                                                             \
        if (!(HF)) mbar_waitc(sb + BAR_FULLB + 8 * rg.slot, rg.phase);                                       \
        mbar_waitc(sb + BAR_FULLA + 8 * s_, (((T) >> 3) + 1) & 1);                                           \
        if (!(HF)) TL(30 + (T) / 2, tid == 0);                                                              \
        wg_fence();                                                                                         \
        _Pragma("unroll") for (int k = 0; k < (NK); k++)                                                    \
            wgmma_n64(acc, dA + ((s_ * SLOT + k * 32) >> 4), dB + ((rg.slot * SLOT + (HF) * 8192 + k * 2048) >> 4), ((T) | k) != 0); \
        wg_commit();                                                                                        \
        wg_wait<1>();                                                                                       \
        mbar_arrive_if(sb + BAR_EMPTYA + 8 * (((T) + 7) & 7), l0 && (T) > 0);                               \
        if (!(HF)) mbar_arrive_if(sb + BAR_EMPTYB + 8 * prev, l0 && (T) > 0);                               \
        if (HF) { prev = rg.slot; rg.adv(); }                                                               \
    } while (0)
#pragma unroll 1
            for (int t = 0; t < 16; t += 2) { KT_P4(t, 0, 4); KT_P4(t + 1, 1, 4); }
            TL(14, tid == 0);
#pragma unroll 1
            for (int t = 16; t < 24; t += 2) { KT_P4(t, 0, 3); KT_P4(t + 1, 1, 3); }
            wg_wait<0>();
            fence_acc<32>(acc);
            TL(15, tid == 0);
            const float r0 = lds_f2(sb + OFF_CS1 + (16 * warp + g) * 8).y, r1 = lds_f2(sb + OFF_CS1 + (16 * warp + g + 8) * 8).y;
#pragma unroll
            for (int t = 0; t < 8; t++) {
                res_lo[t] = pack_bf16(fmaf(acc[4 * t], r0, bf_lo(res_lo[t])), fmaf(acc[4 * t + 1], r0, bf_hi(res_lo[t])));
                res_hi[t] = pack_bf16(fmaf(acc[4 * t + 2], r1, bf_lo(res_hi[t])), fmaf(acc[4 * t + 3], r1, bf_hi(res_hi[t])));
            }
            store_tile(own_rows, P.out + (size_t)row_w * DM + 64 * j, res_lo, res_hi, lane);
            if (tid == 0 && role == 0) g_epoch = epoch;
            TL(16, tid == 0); TLG(1, tid == 0);
        }
    }
}

typedef CUresult (*EncodeFn)(CUtensorMap*, CUtensorMapDataType, cuuint32_t, void*, const cuuint64_t*, const cuuint64_t*,
                             const cuuint32_t*, const cuuint32_t*, CUtensorMapInterleave, CUtensorMapSwizzle,
                             CUtensorMapL2promotion, CUtensorMapFloatOOBfill);

static void make_map2d(EncodeFn enc, CUtensorMap* tm, const void* base, uint64_t cols, uint64_t rows, uint64_t pitch_elems,
                       uint32_t box_rows) {
    cuuint64_t gd[2] = {cols, rows};
    cuuint64_t gs[1] = {pitch_elems * 2};
    cuuint32_t bd[2] = {64, box_rows};
    cuuint32_t es[2] = {1, 1};
    enc(tm, CU_TENSOR_MAP_DATA_TYPE_BFLOAT16, 2, const_cast<void*>(base), gd, gs, bd, es, CU_TENSOR_MAP_INTERLEAVE_NONE,
        CU_TENSOR_MAP_SWIZZLE_128B, CU_TENSOR_MAP_L2_PROMOTION_L2_256B, CU_TENSOR_MAP_FLOAT_OOB_FILL_NONE);
}

}

extern "C" void kernel_launch(void* const* d_in, const int* in_sizes, int n_in, void* d_out, int out_size) {
    using namespace hk;
    (void)in_sizes; (void)n_in; (void)out_size;
    static EncodeFn enc = nullptr;
    static void *po = nullptr, *ph = nullptr, *phh = nullptr;
    static int std_layout = 0;
    if (!enc) {
        void* fn = nullptr;
        cudaDriverEntryPointQueryResult qr;
        cudaGetDriverEntryPoint("cuTensorMapEncodeTiled", &fn, cudaEnableDefault, &qr);
        enc = (EncodeFn)fn;
        cudaGetSymbolAddress(&po, g_o);
        cudaGetSymbolAddress(&ph, g_h);
        cudaGetSymbolAddress(&phh, g_hh);
        cudaFuncSetAttribute(fused_kernel, cudaFuncAttributeMaxDynamicSharedMemorySize, SMEM_BYTES);
        int dev = 0, sms = 0;
        cudaGetDevice(&dev);
        cudaDeviceGetAttribute(&sms, cudaDevAttrMultiProcessorCount, dev);
        cudaFuncSetAttribute(fused_kernel, cudaFuncAttributeNonPortableClusterSizeAllowed, 1);
        const int sizes[3] = {8, 9, 16}, want[3] = {15, 9, 7};
        bool ok = sms == NCTA;
        for (int i = 0; i < 3 && ok; i++) {
            cudaLaunchConfig_t cfg = {};
            cfg.gridDim = dim3(sizes[i] * 8); cfg.blockDim = dim3(NTHREADS); cfg.dynamicSmemBytes = SMEM_BYTES;
            cudaLaunchAttribute at;
            at.id = cudaLaunchAttributeClusterDimension;
            at.val.clusterDim.x = sizes[i]; at.val.clusterDim.y = 1; at.val.clusterDim.z = 1;
            cfg.attrs = &at; cfg.numAttrs = 1;
            int n = 0;
            ok = cudaOccupancyMaxActiveClusters(&n, fused_kernel, &cfg) == cudaSuccess && n == want[i];
        }
        (void)cudaGetLastError();
        std_layout = ok ? 1 : 0;
    }
    Params P;
    const __nv_bfloat16* x = (const __nv_bfloat16*)d_in[0];
    P.x = x;
    P.wqkv = (const __nv_bfloat16*)d_in[1];
    P.wphi = (const __nv_bfloat16*)d_in[2];
    P.wo = (const __nv_bfloat16*)d_in[3];
    P.wg = (const __nv_bfloat16*)d_in[5];
    P.wu = (const __nv_bfloat16*)d_in[6];
    P.wd = (const __nv_bfloat16*)d_in[7];
    P.out = (__nv_bfloat16*)d_out;
    P.use_smid = std_layout;
    for (int i = 0; i < NCTA; i++) {
        int role = i < 4 ? 128 + i : i - 4;
        if (std_layout) {
            const int tpc = i >> 1, odd = i & 1;
            if (tpc < 32) role = (tpc & 7) * 8 + (tpc >> 3) * 2 + odd;
            else if (tpc < 60) role = (8 + (tpc - 32) % 7) * 8 + ((tpc - 32) / 7) * 2 + odd;
            else if (tpc < 62) role = 128 + (tpc - 60) * 2 + odd;
            else role = 15 * 8 + (tpc - 62) * 2 + odd;
        }
        P.role[i] = (unsigned char)role;
    }
    make_map2d(enc, &P.tx, x, DM, SEQ, DM, 128);
    make_map2d(enc, &P.to, po, DM, SEQ, DM, 128);
    make_map2d(enc, &P.th, ph, DM, SEQ, DM, 128);
    make_map2d(enc, &P.thh, phh, FFP, SEQ, FFP, 128);
    make_map2d(enc, &P.twq, P.wqkv, 3 * DM, DM, 3 * DM, 128);
    make_map2d(enc, &P.two, P.wo, DM, DM, DM, 128);
    make_map2d(enc, &P.twg, P.wg, FF, DM, FF, 64);
    make_map2d(enc, &P.twu, P.wu, FF, DM, FF, 64);
    make_map2d(enc, &P.twd, P.wd, DM, FF, DM, 64);
    {
        cuuint64_t gd[3] = {(cuuint64_t)DM, (cuuint64_t)DM, 3};
        cuuint64_t gs[2] = {(cuuint64_t)3 * DM * 2, (cuuint64_t)DM * 2};
        cuuint32_t bd[3] = {64, 64, 2};
        cuuint32_t es[3] = {1, 1, 1};
        enc(&P.twkv, CU_TENSOR_MAP_DATA_TYPE_BFLOAT16, 3, const_cast<__nv_bfloat16*>(P.wqkv), gd, gs, bd, es,
            CU_TENSOR_MAP_INTERLEAVE_NONE, CU_TENSOR_MAP_SWIZZLE_128B, CU_TENSOR_MAP_L2_PROMOTION_L2_256B,
            CU_TENSOR_MAP_FLOAT_OOB_FILL_NONE);
    }
    fused_kernel<<<NCTA, NTHREADS, SMEM_BYTES>>>(P);
}
```

```cpp
#include <cuda_runtime.h>
#include <cuda_bf16.h>
#include <cuda.h>
#include <stdint.h>

namespace hk {

constexpr int SEQ = 2048, DM = 512, FF = 1376, FFP = 1536;
constexpr int NCTA = 132;
constexpr int NTHREADS = 384;
constexpr uint32_t SLOT = 16384;
constexpr uint32_t OFF_A = 0, OFF_B = 8 * SLOT, OFF_MISC = 14 * SLOT;
constexpr uint32_t BAR_FULLA = OFF_MISC + 0, BAR_EMPTYA = OFF_MISC + 64, BAR_FULLB = OFF_MISC + 128,
                   BAR_EMPTYB = OFF_MISC + 176, BAR_CS1 = OFF_MISC + 224, BAR_CS3 = OFF_MISC + 232,
                   BAR_PUB = OFF_MISC + 240,
                   BAR_CSQ = OFF_MISC + 336;
constexpr uint32_t OFF_CS1 = OFF_MISC + 384;
constexpr uint32_t OFF_CS3 = OFF_CS1 + 1024;
constexpr uint32_t SMEM_BYTES = OFF_CS3 + 1536;
constexpr int NB = 6;

constexpr int ACC_KV = 0, ACC_Z = 2048, ACC_SIZE = 2176;

__device__ __align__(1024) __nv_bfloat16 g_o[SEQ * DM];
__device__ __align__(1024) __nv_bfloat16 g_h[SEQ * DM];
__device__ __align__(1024) __nv_bfloat16 g_hh[SEQ * FFP];
__device__ __align__(128) float g_hstat[SEQ * 16];
__device__ __align__(128) unsigned long long g_xstat[SEQ * 2];
__device__ __align__(128) float g_acc[8 * ACC_SIZE];
__device__ __align__(128) unsigned g_cnt[8 * 32];
__device__ __align__(128) unsigned long long g_cs[8 * 5 * 128];
__device__ __align__(128) unsigned g_flag[16 * 8 * 8];
__device__ unsigned g_epoch;

#define TL(i, pred) do {} while (0)
#define TLG(i, pred) do {} while (0)

struct Params {
    CUtensorMap tx, to, th, thh, twkv, twq, two, twg, twu, twd;
    const __nv_bfloat16 *x, *wqkv, *wphi, *wo, *wg, *wu, *wd;
    __nv_bfloat16* out;
    int use_smid;
    unsigned char role[NCTA];
};

__device__ __forceinline__ uint32_t smem_u32(const void* p) { return (uint32_t)__cvta_generic_to_shared(p); }
__device__ __forceinline__ void mbar_init(uint32_t bar, uint32_t cnt) {
    asm volatile("mbarrier.init.shared::cta.b64 [%0], %1;" ::"r"(bar), "r"(cnt) : "memory");
}
__device__ __forceinline__ void mbar_expect_tx(uint32_t bar, uint32_t bytes) {
    asm volatile("mbarrier.arrive.expect_tx.shared::cta.b64 _, [%0], %1;" ::"r"(bar), "r"(bytes) : "memory");
}
__device__ __forceinline__ void mbar_arrive(uint32_t bar) {
    asm volatile("mbarrier.arrive.shared::cta.b64 _, [%0];" ::"r"(bar) : "memory");
}
__device__ __forceinline__ void mbar_arrive_if(uint32_t bar, bool pred) {
    asm volatile("{.reg .pred p; setp.ne.u32 p, %1, 0; @p mbarrier.arrive.shared::cta.b64 _, [%0];}" ::"r"(bar), "r"((uint32_t)pred) : "memory");
}
__device__ __forceinline__ bool mbar_try(uint32_t bar, uint32_t parity) {
    uint32_t ok;
    asm volatile("{.reg .pred p; mbarrier.try_wait.parity.shared::cta.b64 p, [%1], %2; selp.u32 %0,1,0,p;}"
                 : "=r"(ok) : "r"(bar), "r"(parity) : "memory");
    return ok;
}
__device__ __forceinline__ bool mbar_test(uint32_t bar, uint32_t parity) {
    uint32_t ok;
    asm volatile("{.reg .pred p; mbarrier.test_wait.parity.shared::cta.b64 p, [%1], %2; selp.u32 %0,1,0,p;}"
                 : "=r"(ok) : "r"(bar), "r"(parity) : "memory");
    return ok;
}
__device__ __forceinline__ void trap_if_gt(uint32_t v, uint32_t lim) {
    asm volatile("{.reg .pred p; setp.gt.u32 p, %0, %1; @p trap;}" ::"r"(v), "r"(lim));
}
__device__ __forceinline__ void mbar_wait(uint32_t bar, uint32_t parity) {
    asm volatile("{\n"
                 ".reg .pred P1, P2;\n"
                 ".reg .u32 c;\n"
                 "mov.u32 c, 0;\n"
                 "LAB_WAIT:\n"
                 "mbarrier.try_wait.parity.shared::cta.b64 P1, [%0], %1;\n"
                 "@P1 bra LAB_DONE;\n"
                 "add.u32 c, c, 1;\n"
                 "setp.gt.u32 P2, c, 4194304;\n"
                 "@P2 trap;\n"
                 "bra LAB_WAIT;\n"
                 "LAB_DONE:\n"
                 "}" ::"r"(bar), "r"(parity) : "memory");
}
__device__ __forceinline__ void mbar_waitc(uint32_t bar, uint32_t parity) {
    asm volatile("{\n"
                 ".reg .pred P1;\n"
                 "LAB_WAIT:\n"
                 "mbarrier.try_wait.parity.shared::cta.b64 P1, [%0], %1;\n"
                 "@!P1 bra LAB_WAIT;\n"
                 "}" ::"r"(bar), "r"(parity) : "memory");
}
__device__ __forceinline__ void tma2d(uint32_t dst, const CUtensorMap* tm, uint32_t bar, int c0, int c1) {
    asm volatile("cp.async.bulk.tensor.2d.shared::cluster.global.mbarrier::complete_tx::bytes [%0], [%1, {%3, %4}], [%2];"
                 ::"r"(dst), "l"(tm), "r"(bar), "r"(c0), "r"(c1) : "memory");
}
__device__ __forceinline__ void tma3d(uint32_t dst, const CUtensorMap* tm, uint32_t bar, int c0, int c1, int c2) {
    asm volatile("cp.async.bulk.tensor.3d.shared::cluster.global.mbarrier::complete_tx::bytes [%0], [%1, {%3, %4, %5}], [%2];"
                 ::"r"(dst), "l"(tm), "r"(bar), "r"(c0), "r"(c1), "r"(c2) : "memory");
}
__device__ __forceinline__ void prefetch_tmap(const CUtensorMap* tm) {
    asm volatile("prefetch.tensormap [%0];" ::"l"(tm) : "memory");
}
__device__ __forceinline__ void prefetch_l2(const void* p, uint32_t bytes) {
    asm volatile("cp.async.bulk.prefetch.L2.global [%0], %1;" ::"l"(p), "r"(bytes) : "memory");
}
__device__ __forceinline__ unsigned ld_acquire(const unsigned* p) {
    unsigned v; asm volatile("ld.acquire.gpu.global.u32 %0, [%1];" : "=r"(v) : "l"(p) : "memory"); return v;
}
__device__ __forceinline__ uint4 ld_acquire4(const unsigned* p) {
    uint4 v;
    asm volatile("ld.acquire.gpu.global.v4.u32 {%0,%1,%2,%3}, [%4];" : "=r"(v.x), "=r"(v.y), "=r"(v.z), "=r"(v.w) : "l"(p) : "memory");
    return v;
}
__device__ __forceinline__ unsigned ld_relaxed(const unsigned* p) {
    unsigned v; asm volatile("ld.relaxed.gpu.global.u32 %0, [%1];" : "=r"(v) : "l"(p)); return v;
}
__device__ __forceinline__ void st_relaxed(unsigned* p, unsigned v) {
    asm volatile("st.relaxed.gpu.global.u32 [%0], %1;" ::"l"(p), "r"(v) : "memory");
}
__device__ __forceinline__ void red_relaxed(unsigned* p, unsigned v) {
    asm volatile("red.relaxed.gpu.global.add.u32 [%0], %1;" ::"l"(p), "r"(v) : "memory");
}
__device__ __forceinline__ void fence_gpu() { asm volatile("fence.acq_rel.gpu;" ::: "memory"); }
__device__ __forceinline__ void fence_async_smem() { asm volatile("fence.proxy.async.shared::cta;" ::: "memory"); }
__device__ __forceinline__ void fence_async_global() { asm volatile("fence.proxy.async.global;" ::: "memory"); }
__device__ __forceinline__ void wait_count(const unsigned* p, unsigned target) {
    uint32_t it = 0;
    while ((int)(ld_acquire(p) - target) < 0) trap_if_gt(++it, 1u << 22);
}
__device__ __forceinline__ void wait_count_warp(const unsigned* p, unsigned target) {
    uint32_t it = 0;
    while (__any_sync(0xffffffffu, (int)(ld_acquire(p) - target) < 0)) trap_if_gt(++it, 1u << 22);
}
__device__ __forceinline__ void red_f32(float* p, float a) {
    asm volatile("red.relaxed.gpu.global.add.f32 [%0], %1;" ::"l"(p), "f"(a) : "memory");
}
__device__ __forceinline__ void red_f32x2(float* p, float a, float b) {
    asm volatile("red.relaxed.gpu.global.add.v2.f32 [%0], {%1, %2};" ::"l"(p), "f"(a), "f"(b) : "memory");
}
__device__ __forceinline__ void red_f32x4(float* p, float a, float b, float c, float d) {
    asm volatile("red.relaxed.gpu.global.add.v4.f32 [%0], {%1, %2, %3, %4};" ::"l"(p), "f"(a), "f"(b), "f"(c), "f"(d) : "memory");
}
__device__ __forceinline__ float4 ld_l2_f4(const float* p) {
    float4 v;
    asm volatile("ld.relaxed.gpu.global.v4.f32 {%0,%1,%2,%3}, [%4];" : "=f"(v.x), "=f"(v.y), "=f"(v.z), "=f"(v.w) : "l"(p) : "memory");
    return v;
}
__device__ __forceinline__ float2 ld_l2_f2(const float* p) {
    float2 v;
    asm volatile("ld.relaxed.gpu.global.v2.f32 {%0,%1}, [%2];" : "=f"(v.x), "=f"(v.y) : "l"(p) : "memory");
    return v;
}
__device__ __forceinline__ float ld_l2_f(const float* p) {
    float v;
    asm volatile("ld.relaxed.gpu.global.f32 %0, [%1];" : "=f"(v) : "l"(p) : "memory");
    return v;
}
__device__ __forceinline__ uint4 ldg_nc(const void* p) {
    uint4 v;
    asm volatile("ld.global.nc.L1::no_allocate.v4.u32 {%0,%1,%2,%3}, [%4];" : "=r"(v.x), "=r"(v.y), "=r"(v.z), "=r"(v.w) : "l"(p));
    return v;
}
__device__ __forceinline__ void stg128(void* p, uint32_t a, uint32_t b, uint32_t c, uint32_t d) {
    asm volatile("st.global.v4.u32 [%0], {%1,%2,%3,%4};" ::"l"(p), "r"(a), "r"(b), "r"(c), "r"(d) : "memory");
}
__device__ __forceinline__ uint4 lds128(uint32_t a) {
    uint4 v;
    asm volatile("ld.shared.v4.u32 {%0,%1,%2,%3}, [%4];" : "=r"(v.x), "=r"(v.y), "=r"(v.z), "=r"(v.w) : "r"(a) : "memory");
    return v;
}
__device__ __forceinline__ float2 lds_f2(uint32_t a) {
    float2 v;
    asm volatile("ld.shared.v2.f32 {%0,%1}, [%2];" : "=f"(v.x), "=f"(v.y) : "r"(a) : "memory");
    return v;
}
__device__ __forceinline__ void sts_f2(uint32_t a, float x, float y) {
    asm volatile("st.shared.v2.f32 [%0], {%1,%2};" ::"r"(a), "f"(x), "f"(y) : "memory");
}
__device__ __forceinline__ void sts64(uint32_t a, uint32_t x, uint32_t y) {
    asm volatile("st.shared.v2.u32 [%0], {%1,%2};" ::"r"(a), "r"(x), "r"(y) : "memory");
}
__device__ __forceinline__ void sts128(uint32_t a, uint32_t x, uint32_t y, uint32_t z, uint32_t w) {
    asm volatile("st.shared.v4.u32 [%0], {%1,%2,%3,%4};" ::"r"(a), "r"(x), "r"(y), "r"(z), "r"(w) : "memory");
}
__device__ __forceinline__ void stsm4(uint32_t a, uint32_t r0, uint32_t r1, uint32_t r2, uint32_t r3) {
    asm volatile("stmatrix.sync.aligned.m8n8.x4.shared.b16 [%0], {%1,%2,%3,%4};" ::"r"(a), "r"(r0), "r"(r1), "r"(r2), "r"(r3) : "memory");
}
__device__ __forceinline__ void ldsm4(uint32_t a, uint32_t& r0, uint32_t& r1, uint32_t& r2, uint32_t& r3) {
    asm volatile("ldmatrix.sync.aligned.m8n8.x4.shared.b16 {%0,%1,%2,%3}, [%4];" : "=r"(r0), "=r"(r1), "=r"(r2), "=r"(r3) : "r"(a) : "memory");
}
__device__ __forceinline__ void ldsm4t(uint32_t a, uint32_t& r0, uint32_t& r1, uint32_t& r2, uint32_t& r3) {
    asm volatile("ldmatrix.sync.aligned.m8n8.x4.trans.shared.b16 {%0,%1,%2,%3}, [%4];" : "=r"(r0), "=r"(r1), "=r"(r2), "=r"(r3) : "r"(a) : "memory");
}
__device__ __forceinline__ void mma16816(float* c, const uint32_t* a, uint32_t b0, uint32_t b1) {
    asm("mma.sync.aligned.m16n8k16.row.col.f32.bf16.bf16.f32 {%0,%1,%2,%3}, {%4,%5,%6,%7}, {%8,%9}, {%0,%1,%2,%3};"
                 : "+f"(c[0]), "+f"(c[1]), "+f"(c[2]), "+f"(c[3])
                 : "r"(a[0]), "r"(a[1]), "r"(a[2]), "r"(a[3]), "r"(b0), "r"(b1));
}
__device__ __forceinline__ uint32_t pack_bf16(float lo, float hi) {
    uint32_t r; asm("cvt.rn.bf16x2.f32 %0, %1, %2;" : "=r"(r) : "f"(hi), "f"(lo)); return r;
}
__device__ __forceinline__ float bf_lo(uint32_t w) { return __uint_as_float(w << 16); }
__device__ __forceinline__ float bf_hi(uint32_t w) { return __uint_as_float(w & 0xffff0000u); }
__device__ __forceinline__ float ex2(float x) { float r; asm("ex2.approx.ftz.f32 %0, %1;" : "=f"(r) : "f"(x)); return r; }
__device__ __forceinline__ float rcp(float x) { float r; asm("rcp.approx.ftz.f32 %0, %1;" : "=f"(r) : "f"(x)); return r; }
__device__ __forceinline__ void bar_sync(int id, int n) { asm volatile("bar.sync %0, %1;" ::"r"(id), "r"(n) : "memory"); }

__device__ __forceinline__ uint32_t desc_lo(uint32_t addr) { return ((addr & 0x3FFFF) >> 4) | (512u << 16); }
#define DESC_HI "0x40000040"
__device__ __forceinline__ void wg_fence() { asm volatile("wgmma.fence.sync.aligned;" ::: "memory"); }
__device__ __forceinline__ void wg_commit() { asm volatile("wgmma.commit_group.sync.aligned;" ::: "memory"); }
template <int N> __device__ __forceinline__ void wg_wait() { asm volatile("wgmma.wait_group.sync.aligned %0;" ::"n"(N) : "memory"); }
template <int N> __device__ __forceinline__ void fence_acc(float* d) {
#pragma unroll
    for (int i = 0; i < N; i++) asm volatile("" : "+f"(d[i])::"memory");
}
#define R4(o) "+f"(d[o + 0]), "+f"(d[o + 1]), "+f"(d[o + 2]), "+f"(d[o + 3])
#define R8(o) R4(o), R4(o + 4)
__device__ __forceinline__ void wgmma_n128(float* d, uint32_t da, uint32_t db, int sc) {
    asm volatile("{.reg .pred p; .reg .b64 da, db; setp.ne.b32 p, %66, 0; mov.b64 da, {%64, " DESC_HI "}; mov.b64 db, {%65, " DESC_HI "};\n"
                 "wgmma.mma_async.sync.aligned.m64n128k16.f32.bf16.bf16 {%0,%1,%2,%3,%4,%5,%6,%7,%8,%9,%10,%11,%12,%13,%14,%15,%16,%17,%18,%19,%20,%21,%22,%23,%24,%25,%26,%27,%28,%29,%30,%31,"
                 "%32,%33,%34,%35,%36,%37,%38,%39,%40,%41,%42,%43,%44,%45,%46,%47,%48,%49,%50,%51,%52,%53,%54,%55,%56,%57,%58,%59,%60,%61,%62,%63}, da, db, p, 1, 1, 0, 1;}"
                 : R8(0), R8(8), R8(16), R8(24), R8(32), R8(40), R8(48), R8(56)
                 : "r"(da), "r"(db), "r"(sc));
}
__device__ __forceinline__ void wgmma_n64(float* d, uint32_t da, uint32_t db, int sc) {
    asm volatile("{.reg .pred p; .reg .b64 da, db; setp.ne.b32 p, %34, 0; mov.b64 da, {%32, " DESC_HI "}; mov.b64 db, {%33, " DESC_HI "};\n"
                 "wgmma.mma_async.sync.aligned.m64n64k16.f32.bf16.bf16 {%0,%1,%2,%3,%4,%5,%6,%7,%8,%9,%10,%11,%12,%13,%14,%15,%16,%17,%18,%19,%20,%21,%22,%23,%24,%25,%26,%27,%28,%29,%30,%31}, da, db, p, 1, 1, 0, 1;}"
                 : R8(0), R8(8), R8(16), R8(24)
                 : "r"(da), "r"(db), "r"(sc));
}
__device__ __forceinline__ void wgmma_n40_tt(float* d, uint32_t da, uint32_t db, int sc) {
    asm volatile("{.reg .pred p; .reg .b64 da, db; setp.ne.b32 p, %22, 0; mov.b64 da, {%20, " DESC_HI "}; mov.b64 db, {%21, " DESC_HI "};\n"
                 "wgmma.mma_async.sync.aligned.m64n40k16.f32.bf16.bf16 {%0,%1,%2,%3,%4,%5,%6,%7,%8,%9,%10,%11,%12,%13,%14,%15,%16,%17,%18,%19}, da, db, p, 1, 1, 1, 1;}"
                 : R8(0), R8(8), R4(16)
                 : "r"(da), "r"(db), "r"(sc));
}

__device__ __forceinline__ void wgmma_n8_tt(float* d, uint32_t da, uint32_t db, int sc) {
    asm volatile("{.reg .pred p; .reg .b64 da, db; setp.ne.b32 p, %6, 0; mov.b64 da, {%4, " DESC_HI "}; mov.b64 db, {%5, " DESC_HI "};\n"
                 "wgmma.mma_async.sync.aligned.m64n8k16.f32.bf16.bf16 {%0,%1,%2,%3}, da, db, p, 1, 1, 1, 1;}"
                 : R4(0)
                 : "r"(da), "r"(db), "r"(sc));
}

__device__ __forceinline__ void red_f32_if(float* p, float a, bool pred) {
    asm volatile("{.reg .pred p; setp.ne.u32 p, %2, 0; @p red.relaxed.gpu.global.add.f32 [%0], %1;}" ::"l"(p), "f"(a), "r"((uint32_t)pred) : "memory");
}
__device__ __forceinline__ void stg_f2_if(float* p, float a, float b, bool pred) {
    asm volatile("{.reg .pred p; setp.ne.u32 p, %3, 0; @p st.global.v2.f32 [%0], {%1,%2};}" ::"l"(p), "f"(a), "f"(b), "r"((uint32_t)pred) : "memory");
}
__device__ __forceinline__ void stg64(void* p, uint32_t a, uint32_t b) {
    asm volatile("st.global.v2.u32 [%0], {%1,%2};" ::"l"(p), "r"(a), "r"(b) : "memory");
}
__device__ __forceinline__ void store_pair(__nv_bfloat16* p, uint32_t r0, uint32_t r1, bool odd) {
    const uint32_t x = __shfl_xor_sync(0xffffffffu, odd ? r0 : r1, 1);
    stg64(p, odd ? x : r0, odd ? r1 : x);
}
__device__ __forceinline__ void mma16816_z(float* c, const uint32_t* a, uint32_t b0, uint32_t b1) {
    asm("mma.sync.aligned.m16n8k16.row.col.f32.bf16.bf16.f32 {%0,%1,%2,%3}, {%4,%5,%6,%7}, {%8,%9}, {%10,%10,%10,%10};"
                 : "=f"(c[0]), "=f"(c[1]), "=f"(c[2]), "=f"(c[3])
                 : "r"(a[0]), "r"(a[1]), "r"(a[2]), "r"(a[3]), "r"(b0), "r"(b1), "f"(0.f));
}
__device__ __forceinline__ uint32_t max2(uint32_t a, uint32_t b) { uint32_t r; asm("max.bf16x2 %0, %1, %2;" : "=r"(r) : "r"(a), "r"(b)); return r; }
__device__ __forceinline__ uint32_t min2(uint32_t a, uint32_t b) { uint32_t r; asm("min.bf16x2 %0, %1, %2;" : "=r"(r) : "r"(a), "r"(b)); return r; }
__device__ __forceinline__ void bar_arrive(int id, int n) { asm volatile("bar.arrive %0, %1;" ::"r"(id), "r"(n) : "memory"); }
__device__ __forceinline__ void mbar_arrive_n_if(uint32_t bar, uint32_t n, bool pred) {
    asm volatile("{.reg .pred p; setp.ne.u32 p, %1, 0; @p mbarrier.arrive.shared::cta.b64 _, [%0], %2;}" ::"r"(bar), "r"((uint32_t)pred), "r"(n) : "memory");
}
__device__ __forceinline__ float4 lds_f4(uint32_t a) {
    float4 v;
    asm volatile("ld.shared.v4.f32 {%0,%1,%2,%3}, [%4];" : "=f"(v.x), "=f"(v.y), "=f"(v.z), "=f"(v.w) : "r"(a) : "memory");
    return v;
}
__device__ __forceinline__ uint4 ld_tagged(const unsigned long long* p) {
    unsigned long long a, b;
    asm volatile("ld.acquire.gpu.global.v2.b64 {%0,%1}, [%2];" : "=l"(a), "=l"(b) : "l"(p) : "memory");
    return make_uint4((unsigned)a, (unsigned)(a >> 32), (unsigned)b, (unsigned)(b >> 32));
}
__device__ __forceinline__ uint4 ld_tagged_rlx(const unsigned long long* p) {
    unsigned long long a, b;
    asm volatile("ld.relaxed.gpu.global.v2.b64 {%0,%1}, [%2];" : "=l"(a), "=l"(b) : "l"(p) : "memory");
    return make_uint4((unsigned)a, (unsigned)(a >> 32), (unsigned)b, (unsigned)(b >> 32));
}
__device__ __forceinline__ void st_tagged_if(unsigned long long* p, float a, float b, unsigned tag, bool pred) {
    const unsigned long long t = (unsigned long long)tag << 32;
    asm volatile("{.reg .pred p; setp.ne.u32 p, %3, 0; @p st.relaxed.gpu.global.v2.b64 [%0], {%1,%2};}"
                 ::"l"(p), "l"(t | __float_as_uint(a)), "l"(t | __float_as_uint(b)), "r"((uint32_t)pred) : "memory");
}

__device__ __forceinline__ void store_tile(uint32_t tile_rows, __nv_bfloat16* gdst, const uint32_t* lo, const uint32_t* hi, int lane) {
    const int r = lane & 15;
#pragma unroll
    for (int b = 0; b < 4; b++)
        stsm4(tile_rows + r * 128 + (((2 * b + (lane >> 4)) ^ (r & 7)) << 4), lo[2 * b], hi[2 * b], lo[2 * b + 1], hi[2 * b + 1]);
    __syncwarp();
#pragma unroll
    for (int i = 0; i < 4; i++) {
        const int rr = 4 * i + (lane >> 3);
        const uint4 v = lds128(tile_rows + rr * 128 + (((lane & 7) ^ (rr & 7)) << 4));
        stg128(gdst + rr * DM + (lane & 7) * 8, v.x, v.y, v.z, v.w);
    }
}

template <bool NORM>
__device__ __forceinline__ void feature_map(const uint32_t* a, const uint32_t* wb, float c0, float c1, uint32_t* plus, uint32_t* minus, float* rs) {
    float p[8];
    mma16816_z(p, a, wb[0], wb[1]);
    mma16816_z(p + 4, a, wb[2], wb[3]);
    const uint32_t P0 = pack_bf16(p[0], p[2]), P1 = pack_bf16(p[1], p[3]), P2 = pack_bf16(p[4], p[6]), P3 = pack_bf16(p[5], p[7]);
    uint32_t mx = max2(max2(P0, P1), max2(P2, P3)), mn = min2(min2(P0, P1), min2(P2, P3));
#pragma unroll
    for (int s = 1; s <= 2; s <<= 1) {
        mx = max2(mx, __shfl_xor_sync(0xffffffffu, mx, s));
        mn = min2(mn, __shfl_xor_sync(0xffffffffu, mn, s));
    }
    const float mx0 = bf_lo(mx) * c0, mx1 = bf_hi(mx) * c1, mn0 = bf_lo(mn) * c0, mn1 = bf_hi(mn) * c1;
    p[0] = bf_lo(P0); p[2] = bf_hi(P0); p[1] = bf_lo(P1); p[3] = bf_hi(P1);
    p[4] = bf_lo(P2); p[6] = bf_hi(P2); p[5] = bf_lo(P3); p[7] = bf_hi(P3);
    float ep[8], em[8];
#pragma unroll
    for (int i = 0; i < 8; i++) {
        const bool r1 = (i & 2);
        ep[i] = ex2(fmaf(p[i], r1 ? c1 : c0, r1 ? -mx1 : -mx0));
        em[i] = ex2(fmaf(p[i], r1 ? -c1 : -c0, r1 ? mn1 : mn0));
    }
    float sp[4], sm[4];
#pragma unroll
    for (int i = 0; i < 4; i++) { plus[i] = pack_bf16(ep[2 * i], ep[2 * i + 1]); minus[i] = pack_bf16(em[2 * i], em[2 * i + 1]); }
    mma16816_z(sp, plus, 0x3f803f80u, 0x3f803f80u);
    mma16816_z(sm, minus, 0x3f803f80u, 0x3f803f80u);
    rs[0] = rcp(sp[0]); rs[1] = rcp(sp[2]); rs[2] = rcp(sm[0]); rs[3] = rcp(sm[2]);
    if (NORM) {
#pragma unroll
        for (int i = 0; i < 4; i++) {
            plus[i] = pack_bf16(ep[2 * i] * rs[i & 1], ep[2 * i + 1] * rs[i & 1]);
            minus[i] = pack_bf16(em[2 * i] * rs[2 + (i & 1)], em[2 * i + 1] * rs[2 + (i & 1)]);
        }
    }
}

template <bool SCALE>
__device__ __forceinline__ void ln_frag(const float* acc, uint32_t cs_addr, float rs0, float nm0, float rs1, float nm1, uint32_t* a) {
    const float2 c0 = lds_f2(cs_addr), c1 = lds_f2(cs_addr + 32);
    const float s0 = SCALE ? rs0 : 1.f, s1 = SCALE ? rs1 : 1.f;
    a[0] = pack_bf16(fmaf(nm0, c0.x, acc[0]) * s0, fmaf(nm0, c0.y, acc[1]) * s0);
    a[1] = pack_bf16(fmaf(nm1, c0.x, acc[2]) * s1, fmaf(nm1, c0.y, acc[3]) * s1);
    a[2] = pack_bf16(fmaf(nm0, c1.x, acc[4]) * s0, fmaf(nm0, c1.y, acc[5]) * s0);
    a[3] = pack_bf16(fmaf(nm1, c1.x, acc[6]) * s1, fmaf(nm1, c1.y, acc[7]) * s1);
}

__device__ __forceinline__ uint32_t hh_pair(const float* ag, float4 cs, float nmean) {
    const float g0 = fmaf(nmean, cs.x, ag[0]), g1 = fmaf(nmean, cs.y, ag[1]);
    const float u0 = fmaf(nmean, cs.z, ag[32]), u1 = fmaf(nmean, cs.w, ag[33]);
    return pack_bf16(g0 * u0, g1 * u1);
}

struct Ring {
    int slot; uint32_t phase;
    __device__ __forceinline__ void adv() { if (++slot == NB) { slot = 0; phase ^= 1; } }
};

__global__ void __launch_bounds__(NTHREADS, 1) fused_kernel(const __grid_constant__ Params P) {
    extern __shared__ __align__(1024) uint8_t smem_raw[];
    const uint32_t sb = smem_u32(smem_raw);
    const int tid = threadIdx.x, lane = tid & 31;
    const int warp = __shfl_sync(0xffffffffu, tid >> 5, 0);
    unsigned role = blockIdx.x;
    if (P.use_smid) asm volatile("mov.u32 %0, %%smid;" : "=r"(role));
    role = P.role[role];
    const int m = role >> 3, j = role & 7;
    const bool helper = role >= 128;

    const unsigned epoch = ld_relaxed(&g_epoch) + 1;
    uint4 xv[4];
    uint32_t wraw[16];
    if (warp < 8) {
        if (!helper) {
            const __nv_bfloat16* xp = P.x + (size_t)(128 * m + 16 * j + 2 * warp + (lane >> 4)) * DM + (lane & 15) * 8;
#pragma unroll
            for (int i = 0; i < 4; i++) xv[i] = ldg_nc(xp + 128 * i);
            const uint32_t* wp = reinterpret_cast<const uint32_t*>(P.wphi) + (4 * j) * 128 + (lane & 3) * 16 + (lane >> 2);
#pragma unroll
            for (int i = 0; i < 16; i++)
                asm volatile("ld.global.nc.u32 %0, [%1];" : "=r"(wraw[i]) : "l"(wp + (i >> 2) * 128 + ((i >> 1) & 1) * 64 + (i & 1) * 8));
        }
    } else if (warp == 8) {
        if (lane < NB) {
            const uint32_t full = sb + BAR_FULLB + 8 * lane;
            mbar_init(full, 1); mbar_init(sb + BAR_EMPTYB + 8 * lane, 8);
            asm volatile("fence.mbarrier_init.release.cluster;" ::: "memory");
            if (!helper) {
                mbar_expect_tx(full, SLOT);
                tma3d(sb + OFF_B + lane * SLOT, &P.twkv, full, 64 * j, 64 * lane, 1);
            }
        }
    } else if (warp == 9) {
        if (lane < 8) {
            const uint32_t full = sb + BAR_FULLA + 8 * lane;
            mbar_init(full, 1); mbar_init(sb + BAR_EMPTYA + 8 * lane, 8);
            asm volatile("fence.mbarrier_init.release.cluster;" ::: "memory");
            mbar_expect_tx(full, SLOT);
            if (!helper) tma2d(sb + OFF_A + lane * SLOT, &P.tx, full, 64 * lane, 128 * m);
            else tma3d(sb + OFF_A + lane * SLOT, &P.twkv, full, 128 * j, 64 * lane, 1);
        }
    } else if (warp == 10) {
        if (lane < 15) mbar_init(sb + BAR_CS1 + 8 * lane, lane == 1 ? 160 : ((lane == 0 || lane == 14) ? 32 : 4));
        trap_if_gt(sb & 1023, 0);
    }
    TL(0, tid == 0); TLG(0, tid == 0);
    __syncthreads();

    if (helper) {
        if (warp == 8) {
            if (lane == 0) {
#pragma unroll 1
                for (int i = 8; i < 72; i++) {
                    const uint32_t full = sb + BAR_FULLA + 8 * (i & 7), dst = sb + OFF_A + (i & 7) * SLOT;
                    mbar_wait(sb + BAR_EMPTYA + 8 * (i & 7), ((i >> 3) & 1) ^ 1);
                    mbar_expect_tx(full, SLOT);
                    if (i < 16) {
                        tma3d(dst, &P.twkv, full, 128 * j + 64, 64 * (i & 7), 1);
                    } else if (i < 24) {
                        tma2d(dst, &P.twq, full, 64 * (2 * j + ((i >> 2) & 1)), 128 * (i & 3));
                    } else {
                        const int u = (i >> 3) - 3, c0 = 176 * (2 * j + (u & 1)) + 64 * (u >> 1);
                        tma2d(dst, &P.twg, full, c0, 64 * (i & 7));
                        tma2d(dst + 8192, &P.twu, full, c0, 64 * (i & 7));
                    }
                }
                prefetch_l2(P.wd + (size_t)j * 176128, 352256);
            }
        } else if (warp == 9) {
            wait_count_warp(g_cnt + (lane & 7) * 32, epoch * 32);
        } else if (warp < 4) {
            sts128(sb + OFF_B + 16 * tid, 0x3f803f80u, 0x3f803f80u, 0x3f803f80u, 0x3f803f80u);
            for (int i = tid; i < 2 * ACC_SIZE / 4; i += 128) stg128(g_acc + 2 * j * ACC_SIZE + 4 * i, 0, 0, 0, 0);
            fence_async_smem();
            fence_gpu();
            bar_sync(1, 128);
            float acc[8];
            int i = 0;
#pragma unroll 1
            for (int job = 0; job < 10; job++) {
                const int n = (job >> 1) == 1 ? 4 : 8;
#pragma unroll 1
                for (int t = 0; t < n; t++, i++) {
                    mbar_wait(sb + BAR_FULLA + 8 * (i & 7), (i >> 3) & 1);
                    wg_fence();
#pragma unroll
                    for (int k = 0; k < 8; k++)
                        wgmma_n8_tt(acc + (k & 4), desc_lo(sb + OFF_A) + (((i & 7) * SLOT + k * 2048) >> 4), desc_lo(sb + OFF_B), (t | (k & 3)) != 0);
                    wg_commit();
                    wg_wait<1>();
                    mbar_arrive_n_if(sb + BAR_EMPTYA + 8 * ((i + 7) & 7), 2, lane == 0 && i > 0);
                }
                wg_wait<0>();
                fence_acc<8>(acc);
                const int q = lane & 3;
                const float v = q == 0 ? acc[0] : (q == 1 ? acc[2] : (q == 2 ? acc[4] : acc[6]));
                unsigned long long* dst = g_cs + ((2 * j + (job & 1)) * 5 + (job >> 1)) * 128 + (q >> 1) * 64 + 16 * warp + 8 * (q & 1) + (lane >> 2);
                asm volatile("st.relaxed.gpu.global.b64 [%0], %1;" ::"l"(dst), "l"(((unsigned long long)epoch << 32) | __float_as_uint(v)) : "memory");
            }
        }
        return;
    }

    float* const acc_j = g_acc + j * ACC_SIZE;
    unsigned* const cnt_j = g_cnt + j * 32;

    if (warp >= 8) {
        asm volatile("setmaxnreg.dec.sync.aligned.u32 72;");
        if (warp == 8) {
            if (lane == 0) {
                Ring r{0, 1};
#pragma unroll 1
                for (int i = 6; i < 56; i++) {
                    const uint32_t full = sb + BAR_FULLB + 8 * r.slot, dst = sb + OFF_B + r.slot * SLOT;
                    mbar_wait(sb + BAR_EMPTYB + 8 * r.slot, r.phase ^ 1);
                    if (i >= 8 && i < 12) {
                        mbar_arrive(full);
                    } else {
                        mbar_expect_tx(full, SLOT);
                        if (i < 8) {
                            tma3d(dst, &P.twkv, full, 64 * j, 64 * i, 1);
                        } else if (i < 20) {
                            tma2d(dst, i < 16 ? &P.twq : &P.two, full, 64 * j, 128 * (i & 3));
                        } else if (i < 44) {
                            const int c = (i - 20) >> 3, kt = (i - 20) & 7;
                            tma2d(dst, &P.twg, full, 176 * j + 64 * c, 64 * kt);
                            tma2d(dst + 8192, &P.twu, full, 176 * j + 64 * c, 64 * kt);
                        } else {
                            const int c = (i - 44) >> 2, jj = (i & 3) * 2;
                            tma2d(dst, &P.twd, full, 64 * j, 176 * jj + 64 * c);
                            tma2d(dst + 8192, &P.twd, full, 64 * j, 176 * (jj + 1) + 64 * c);
                        }
                    }
                    r.adv();
                }
            }
        } else if (warp == 9) {
            int r = (lane < 8) ? 1 : 6;
            int ready = (lane == j) ? 2 : 0;
            uint32_t it = 0;
            while (__any_sync(0xffffffffu, r < 6)) {
                const bool e = r < 6 && mbar_test(sb + BAR_EMPTYA + 8 * (lane & 7), (r - 1) & 1);
                const bool pending = __any_sync(0xffffffffu, r < 6 && ready >= r);
                if (r < 6 && ready < r && (e || !pending)) {
                    const uint4 f = ld_acquire4(g_flag + (m * 8 + lane) * 8 + (r < 3 ? 0 : 4));
                    if (r < 3) ready = (f.x == epoch && f.y == epoch) ? ((f.z == epoch && f.w == epoch) ? 2 : 1) : 0;
                    else ready = f.x == epoch ? (f.y == epoch ? (f.z == epoch ? 5 : 4) : 3) : 2;
                }
                if (e && ready >= r) {
                    const uint32_t full = sb + BAR_FULLA + 8 * lane;
                    if (r < 3 && lane == j) {
                        mbar_arrive(full);
                    } else {
                        fence_async_global();
                        mbar_expect_tx(full, SLOT);
                        const CUtensorMap* tm = r == 1 ? &P.to : (r == 2 ? &P.th : &P.thh);
                        const int c0 = r < 3 ? 64 * lane : 192 * lane + 64 * (r - 3);
                        tma2d(sb + OFF_A + lane * SLOT, tm, full, c0, 128 * m);
                    }
                    r++;
                }
                trap_if_gt(++it, 1u << 24);
            }
        } else {
            const int a = warp - 10;
            const unsigned long long* cs = g_cs + j * 640 + 2 * lane;
            {
                uint4 v0, v1;
                uint32_t it = 0;
                while (true) {
                    v0 = ld_tagged_rlx(cs + 128 * a); v1 = ld_tagged(cs + 128 * a + 64);
                    if (!__any_sync(0xffffffffu, v0.y != epoch || v0.w != epoch || v1.y != epoch || v1.w != epoch)) break;
                    __nanosleep(200);
                    trap_if_gt(++it, 1u << 22);
                }
                if (a == 0) {
                    sts64(sb + OFF_CS1 + 256 + 8 * lane, v0.x, v0.z);
                    sts64(sb + OFF_CS1 + 512 + 8 * lane, v1.x, v1.z);
                } else {
                    sts_f2(sb + OFF_CS1 + 8 * lane, __uint_as_float(v0.x) + __uint_as_float(v1.x), __uint_as_float(v0.z) + __uint_as_float(v1.z));
                }
                mbar_arrive(sb + (a ? BAR_CSQ : BAR_CS1));
            }
#pragma unroll 1
            for (int ev = 0; ev < 6; ev += (ev >= 2 + a) ? 2 - (ev == 2) : 1 + (ev == 2)) {
                if (lane == 0) {
                    mbar_wait(sb + BAR_PUB + 8 * (a * 6 + ev), 0);
                    fence_gpu();
                    if (ev == 0) red_relaxed(cnt_j, 1);
                    else st_relaxed(g_flag + role * 8 + (ev < 3 ? 2 * ev - 2 + a : ev + 1), epoch);
                }
                __syncwarp();
                if (ev == 2 && a == 0) {
#pragma unroll 1
                    for (int c = 0; c < 3; c++) {
                        uint4 vg, vu;
                        uint32_t it = 0;
                        do {
                            vg = ld_tagged_rlx(cs + 256 + 128 * c); vu = ld_tagged_rlx(cs + 320 + 128 * c);
                            trap_if_gt(++it, 1u << 22);
                        } while (__any_sync(0xffffffffu, vg.y != epoch || vg.w != epoch || vu.y != epoch || vu.w != epoch));
                        sts128(sb + OFF_CS3 + (32 * c + lane) * 16, vg.x, vg.z, vu.x, vu.z);
                    }
                    mbar_arrive(sb + BAR_CS3);
                }
            }
        }
    } else {
        asm volatile("setmaxnreg.inc.sync.aligned.u32 216;");
        const int w = warp >> 2, wv = warp & 3, g = lane >> 2, q = lane & 3;
        const int row_w = 128 * m + 16 * warp;
        const uint32_t sa = sb + OFF_A + w * 8192;
        const uint32_t dA = desc_lo(sa), dB = desc_lo(sb + OFF_B);
        const uint32_t pub = sb + BAR_PUB + 48 * w;
        const bool l0 = lane == 0;
        Ring rg{0, 0};
        int prev = 0;

        uint32_t wb[16];
        {
            const int row = 128 * m + 16 * j + 2 * warp + (lane >> 4);
            const uint4* v = xv;
            float f[32];
#pragma unroll
            for (int i = 0; i < 4; i++) {
                f[8 * i] = bf_lo(v[i].x); f[8 * i + 1] = bf_hi(v[i].x); f[8 * i + 2] = bf_lo(v[i].y); f[8 * i + 3] = bf_hi(v[i].y);
                f[8 * i + 4] = bf_lo(v[i].z); f[8 * i + 5] = bf_hi(v[i].z); f[8 * i + 6] = bf_lo(v[i].w); f[8 * i + 7] = bf_hi(v[i].w);
            }
            float s0 = 0.f, s1 = 0.f;
#pragma unroll
            for (int i = 0; i < 16; i++) { s0 += f[2 * i]; s1 += f[2 * i + 1]; }
            s0 += s1;
#pragma unroll
            for (int o = 8; o; o >>= 1) s0 += __shfl_xor_sync(0xffffffffu, s0, o);
            const float mean = s0 * (1.f / DM);
            s0 = 0.f; s1 = 0.f;
#pragma unroll
            for (int i = 0; i < 16; i++) {
                const float d0 = f[2 * i] - mean, d1 = f[2 * i + 1] - mean;
                s0 = fmaf(d0, d0, s0); s1 = fmaf(d1, d1, s1);
            }
            s0 += s1;
#pragma unroll
            for (int o = 8; o; o >>= 1) s0 += __shfl_xor_sync(0xffffffffu, s0, o);
            const float rs = rsqrtf(s0 * (1.f / DM) + 1e-5f);
            st_tagged_if(g_xstat + 2 * row, rs, -mean, epoch, (lane & 15) == 0);
        }
        constexpr float L2E = 1.4426950408889634f;
        uint32_t fp[16], fm[16];
        float fr[16];
        float rs0, nm0, rs1, nm1;
        {
            float acc[64];
#pragma unroll 1
            for (int kt = 0; kt < 8; kt++) {
                mbar_waitc(sb + BAR_FULLA + 8 * kt, 0);
                mbar_waitc(sb + BAR_FULLB + 8 * rg.slot, rg.phase);
                TL(20 + kt, tid == 0);
                wg_fence();
#pragma unroll
                for (int k = 0; k < 4; k++)
                    wgmma_n128(acc, dA + ((kt * SLOT + k * 32) >> 4), dB + ((rg.slot * SLOT + k * 2048) >> 4), (kt | k) != 0);
                wg_commit();
                wg_wait<1>();
                mbar_arrive_if(sb + BAR_EMPTYB + 8 * prev, l0 && kt > 0);
                prev = rg.slot; rg.adv();
            }
            {
                uint4 a, b;
                uint32_t it = 0;
                do {
                    a = ld_tagged_rlx(g_xstat + 2 * (row_w + g));
                    b = ld_tagged_rlx(g_xstat + 2 * (row_w + g + 8));
                    trap_if_gt(++it, 1u << 22);
                } while (__any_sync(0xffffffffu, a.y != epoch || a.w != epoch || b.y != epoch || b.w != epoch));
                rs0 = __uint_as_float(a.x); nm0 = __uint_as_float(a.z); rs1 = __uint_as_float(b.x); nm1 = __uint_as_float(b.z);
            }
#pragma unroll
            for (int i = 0; i < 8; i++) {
                wb[(i >> 1) * 4 + (i & 1)] = __byte_perm(wraw[2 * i], wraw[2 * i + 1], 0x5410);
                wb[(i >> 1) * 4 + 2 + (i & 1)] = __byte_perm(wraw[2 * i], wraw[2 * i + 1], 0x7632);
            }
            TL(17, tid == 0);
            mbar_waitc(sb + BAR_CS1, 0);
            TL(18, tid == 0);
            wg_wait<0>();
            fence_acc<64>(acc);
            mbar_arrive_if(sb + BAR_EMPTYB + 8 * prev, l0);
            TL(2, tid == 0);
#pragma unroll
            for (int i = 2; i < 6; i++) mbar_waitc(sb + BAR_FULLB + 8 * i, 1);
            const int lrow = 16 * warp + (lane & 15), ch = lane >> 4, sw = lane & 7;
            const uint32_t st = sb + OFF_B + 2 * SLOT + lrow * 128;
            uint32_t ka[16];
#pragma unroll
            for (int hh = 0; hh < 4; hh++)
                ln_frag<false>(acc + 8 * hh, sb + OFF_CS1 + (64 + 16 * hh + 2 * q) * 4, rs0, nm0, rs1, nm1, ka + 4 * hh);
#pragma unroll
            for (int hh = 0; hh < 4; hh++) {
                uint32_t a[4];
                ln_frag<true>(acc + 32 + 8 * hh, sb + OFF_CS1 + (128 + 16 * hh + 2 * q) * 4, rs0, nm0, rs1, nm1, a);
                stsm4(st + (2 + (hh >> 1)) * SLOT + (((2 * (hh & 1) + ch) ^ sw) << 4), a[0], a[1], a[2], a[3]);
            }
#pragma unroll
            for (int hh = 0; hh < 4; hh++) feature_map<true>(ka + 4 * hh, wb + 4 * hh, rs0 * L2E, rs1 * L2E, fp + 4 * hh, fm + 4 * hh, fr);
#pragma unroll
            for (int hh = 0; hh < 4; hh++) {
                stsm4(st + (hh >> 1) * SLOT + (((4 * (hh & 1) + ch) ^ sw) << 4), fp[4 * hh], fp[4 * hh + 1], fp[4 * hh + 2], fp[4 * hh + 3]);
                stsm4(st + (hh >> 1) * SLOT + (((4 * (hh & 1) + 2 + ch) ^ sw) << 4), fm[4 * hh], fm[4 * hh + 1], fm[4 * hh + 2], fm[4 * hh + 3]);
            }
            stsm4(st + (2 + ch) * SLOT + ((4 ^ sw) << 4), 0x3f803f80u, 0x3f803f80u, 0x3f803f80u, 0x3f803f80u);
            fence_async_smem();
            TL(19, tid == 0);
            bar_sync(1, 256);
            float kvd[20];
            wg_fence();
#pragma unroll
            for (int k = 0; k < 8; k++)
                wgmma_n40_tt(kvd, dB + (((2 + w) * SLOT + k * 2048) >> 4), dB + (((4 + w) * SLOT + k * 2048) >> 4), k != 0);
            wg_commit();
            wg_wait<0>();
            fence_acc<20>(kvd);
            const bool h1 = wv >= 2;
            const int f = 16 * warp + g;
            float* kvp = acc_j + ACC_KV + f * 16 + 2 * q;
            red_f32x2(kvp, h1 ? kvd[8] : kvd[0], h1 ? kvd[9] : kvd[1]);
            red_f32x2(kvp + 128, h1 ? kvd[10] : kvd[2], h1 ? kvd[11] : kvd[3]);
            red_f32x2(kvp + 8, h1 ? kvd[12] : kvd[4], h1 ? kvd[13] : kvd[5]);
            red_f32x2(kvp + 136, h1 ? kvd[14] : kvd[6], h1 ? kvd[15] : kvd[7]);
            red_f32_if(acc_j + ACC_Z + f + 8 * (q & 1), q ? kvd[18] : kvd[16], q < 2);
            __syncwarp();
            mbar_arrive_if(pub, l0);
            mbar_arrive_if(sb + BAR_EMPTYB + 8 * (2 + (lane & 3)), lane < 4);
            TL(3, tid == 0);
        }
        uint32_t res_lo[8], res_hi[8];
        const uint32_t own_rows = sb + OFF_A + j * SLOT + warp * 2048;
        {
            float acc[32];
            rg.slot = 0; rg.phase = 0;
#pragma unroll 1
            for (int b = 0; b < 4; b++) {
                mbar_waitc(sb + BAR_FULLB + 8 * rg.slot, rg.phase);
                wg_fence();
#pragma unroll
                for (int k = 0; k < 8; k++)
                    wgmma_n64(acc, dA + (((2 * b + (k >> 2)) * SLOT + (k & 3) * 32) >> 4), dB + ((rg.slot * SLOT + k * 2048) >> 4), (b | k) != 0);
                wg_commit();
                wg_wait<1>();
                mbar_arrive_if(sb + BAR_EMPTYB + 8 * prev, l0 && b > 0);
                prev = rg.slot; rg.adv();
            }
            wg_wait<0>();
            fence_acc<32>(acc);
            mbar_arrive_if(sb + BAR_EMPTYB + 8 * prev, l0);
            mbar_arrive_if(sb + BAR_EMPTYA + 8 * (lane & 7), lane < 8 && (lane | 1) != (j | 1));
            TL(4, tid == 0);
            mbar_waitc(sb + BAR_CSQ, 0);
            uint32_t qa[16];
#pragma unroll
            for (int hh = 0; hh < 4; hh++)
                ln_frag<false>(acc + 8 * hh, sb + OFF_CS1 + (16 * hh + 2 * q) * 4, rs0, nm0, rs1, nm1, qa + 4 * hh);
#pragma unroll
            for (int hh = 0; hh < 4; hh++) feature_map<false>(qa + 4 * hh, wb + 4 * hh, rs0 * L2E, rs1 * L2E, fp + 4 * hh, fm + 4 * hh, fr + 4 * hh);
#pragma unroll
            for (int b = 0; b < 4; b++)
                ldsm4(own_rows + (lane & 15) * 128 + (((2 * b + (lane >> 4)) ^ (lane & 7)) << 4),
                      res_lo[2 * b], res_hi[2 * b], res_lo[2 * b + 1], res_hi[2 * b + 1]);
            TL(5, tid == 0);
            if (warp == 0) wait_count_warp(cnt_j, epoch * 32);
            TL(6, tid == 0);
            bar_sync(1, 256);
            const uint32_t kvs = sb + OFF_A + (j ^ 1) * SLOT;
            {
                const float4 a0 = ld_l2_f4(acc_j + ACC_KV + 4 * tid), a1 = ld_l2_f4(acc_j + ACC_KV + 4 * (tid + 256));
                const float zz = ld_l2_f(acc_j + ACC_Z + (tid & 127));
                sts64(kvs + (tid >> 2) * 48 + (tid & 3) * 8, pack_bf16(a0.x, a0.y), pack_bf16(a0.z, a0.w));
                sts64(kvs + ((tid >> 2) + 64) * 48 + (tid & 3) * 8, pack_bf16(a1.x, a1.y), pack_bf16(a1.z, a1.w));
                const uint32_t z2 = pack_bf16(zz, zz);
                sts64(kvs + (tid & 127) * 48 + 32 + w * 8, z2, z2);
            }
            bar_sync(1, 256);
            uint32_t o_lo[8], o_hi[8];
#pragma unroll
            for (int hh = 0; hh < 4; hh++) {
                uint32_t b[8], zb[4];
                const uint32_t base = kvs + hh * 32 * 48;
                ldsm4t(base + (lane & 15) * 48 + (lane >> 4) * 16, b[0], b[1], b[2], b[3]);
                ldsm4t(base + (16 + (lane & 15)) * 48 + (lane >> 4) * 16, b[4], b[5], b[6], b[7]);
                ldsm4t(base + lane * 48 + 32, zb[0], zb[1], zb[2], zb[3]);
                float n0[4], n1[4], dn[4], m0[4], m1[4], dm[4];
                mma16816_z(n0, fp + 4 * hh, b[0], b[1]); mma16816_z(n1, fp + 4 * hh, b[2], b[3]); mma16816_z(dn, fp + 4 * hh, zb[0], zb[1]);
                mma16816_z(m0, fm + 4 * hh, b[4], b[5]); mma16816_z(m1, fm + 4 * hh, b[6], b[7]); mma16816_z(dm, fm + 4 * hh, zb[2], zb[3]);
                const float* r = fr + 4 * hh;
                const float i0 = rcp(fmaf(dn[0], r[0], fmaf(dm[0], r[2], 1e-6f))), i1 = rcp(fmaf(dn[2], r[1], fmaf(dm[2], r[3], 1e-6f)));
                const float p0 = r[0] * i0, q0 = r[2] * i0, p1 = r[1] * i1, q1 = r[3] * i1;
                o_lo[2 * hh] = pack_bf16(fmaf(n0[0], p0, m0[0] * q0), fmaf(n0[1], p0, m0[1] * q0));
                o_hi[2 * hh] = pack_bf16(fmaf(n0[2], p1, m0[2] * q1), fmaf(n0[3], p1, m0[3] * q1));
                o_lo[2 * hh + 1] = pack_bf16(fmaf(n1[0], p0, m1[0] * q0), fmaf(n1[1], p0, m1[1] * q0));
                o_hi[2 * hh + 1] = pack_bf16(fmaf(n1[2], p1, m1[2] * q1), fmaf(n1[3], p1, m1[3] * q1));
            }
            store_tile(own_rows, g_o + (size_t)row_w * DM + 64 * j, o_lo, o_hi, lane);
            fence_async_smem();
            __syncwarp();
            mbar_arrive_if(pub + 8, l0);
            mbar_arrive_if(sb + BAR_EMPTYA + 8 * (j ^ (lane & 1)), lane < 2);
            TL(7, tid == 0);
        }
        {
            float acc[32];
#pragma unroll
            for (int t = 0; t < 8; t++) {
                acc[4 * t] = bf_lo(res_lo[t]); acc[4 * t + 1] = bf_hi(res_lo[t]);
                acc[4 * t + 2] = bf_lo(res_hi[t]); acc[4 * t + 3] = bf_hi(res_hi[t]);
            }
            fence_acc<32>(acc);
#pragma unroll 1
            for (int kp = 0; kp < 4; kp++) {
                mbar_waitc(sb + BAR_FULLB + 8 * rg.slot, rg.phase);
#pragma unroll
                for (int hf = 0; hf < 2; hf++) {
                    const int kt = 2 * kp + hf;
                    mbar_waitc(sb + BAR_FULLA + 8 * kt, 1);
                    TL(8, kt == 0 && tid == 0);
                    wg_fence();
#pragma unroll
                    for (int k = 0; k < 4; k++)
                        wgmma_n64(acc, dA + ((kt * SLOT + k * 32) >> 4), dB + ((rg.slot * SLOT + (hf * 4 + k) * 2048) >> 4), 1);
                    wg_commit();
                    wg_wait<1>();
                    mbar_arrive_if(sb + BAR_EMPTYA + 8 * ((kt + 7) & 7), l0 && kt > 0 && kt - 1 != j);
                    if (hf == 0) mbar_arrive_if(sb + BAR_EMPTYB + 8 * prev, l0 && kt > 0);
                }
                prev = rg.slot; rg.adv();
            }
            wg_wait<0>();
            fence_acc<32>(acc);
            mbar_arrive_if(sb + BAR_EMPTYA + 8 * 7, l0 && j != 7);
            mbar_arrive_if(sb + BAR_EMPTYB + 8 * prev, l0);
            TL(9, tid == 0);
            float s0 = 0.f, s1 = 0.f;
#pragma unroll
            for (int t = 0; t < 8; t++) {
                res_lo[t] = pack_bf16(acc[4 * t], acc[4 * t + 1]);
                res_hi[t] = pack_bf16(acc[4 * t + 2], acc[4 * t + 3]);
                s0 += acc[4 * t] + acc[4 * t + 1];
                s1 += acc[4 * t + 2] + acc[4 * t + 3];
            }
            store_tile(own_rows, g_h + (size_t)row_w * DM + 64 * j, res_lo, res_hi, lane);
            s0 += __shfl_xor_sync(0xffffffffu, s0, 1); s1 += __shfl_xor_sync(0xffffffffu, s1, 1);
            s0 += __shfl_xor_sync(0xffffffffu, s0, 2); s1 += __shfl_xor_sync(0xffffffffu, s1, 2);
            const float mu0 = s0 * (1.f / 64), mu1 = s1 * (1.f / 64);
            float q0 = 0.f, q1 = 0.f;
#pragma unroll
            for (int t = 0; t < 8; t++) {
                float d;
                d = acc[4 * t] - mu0; q0 = fmaf(d, d, q0);
                d = acc[4 * t + 1] - mu0; q0 = fmaf(d, d, q0);
                d = acc[4 * t + 2] - mu1; q1 = fmaf(d, d, q1);
                d = acc[4 * t + 3] - mu1; q1 = fmaf(d, d, q1);
            }
            q0 += __shfl_xor_sync(0xffffffffu, q0, 1); q1 += __shfl_xor_sync(0xffffffffu, q1, 1);
            q0 += __shfl_xor_sync(0xffffffffu, q0, 2); q1 += __shfl_xor_sync(0xffffffffu, q1, 2);
            stg_f2_if(g_hstat + (row_w + g + 8 * (q & 1)) * 16 + 2 * j, q ? mu1 : mu0, q ? q1 : q0, q < 2);
            fence_async_smem();
            __syncwarp();
            mbar_arrive_if(pub + 16, l0);
            mbar_arrive_if(sb + BAR_EMPTYA + 8 * j, l0);
            TL(10, tid == 0);
        }
        if (w == 1) {
#pragma unroll 1
            for (int kt = 0; kt < 8; kt++) mbar_waitc(sb + BAR_FULLA + 8 * kt, 0);
            const float* sp = g_hstat + (128 * m + (tid & 127)) * 16;
            float4 v[4];
#pragma unroll
            for (int i = 0; i < 4; i++) v[i] = ld_l2_f4(sp + 4 * i);
            float mean = 0.f;
#pragma unroll
            for (int i = 0; i < 4; i++) mean += v[i].x + v[i].z;
            mean *= 0.125f;
            float m2 = 0.f, dv = 0.f;
#pragma unroll
            for (int i = 0; i < 4; i++) {
                m2 += v[i].y + v[i].w;
                dv = fmaf(v[i].x - mean, v[i].x - mean, dv); dv = fmaf(v[i].z - mean, v[i].z - mean, dv);
            }
            sts_f2(sb + OFF_CS1 + (tid & 127) * 8, -mean, __fdividef(1.f, fmaf(dv, 64.f, m2) * (1.f / DM) + 1e-5f));
            mbar_arrive(sb + BAR_CS3);
        }
        {
            float acc0[64], acc1[64];
            const uint32_t dA0 = desc_lo(sb + OFF_A);
#pragma unroll 1
            for (int c = w; c < 3; c += 2) {
                if (c > 0) bar_sync(1 + c, 256);
                rg.slot = (c == 2) ? 0 : 2 + 2 * c; rg.phase = (c == 0);
#pragma unroll 1
                for (int kt = 0; kt < 8; kt++) {
                    mbar_waitc(sb + BAR_FULLA + 8 * kt, 0);
                    mbar_waitc(sb + BAR_FULLB + 8 * rg.slot, rg.phase);
                    TL(44 + c * 2 + (kt == 1), (tid & 127) == 0 && kt < 2);
                    wg_fence();
#pragma unroll
                    for (int k = 0; k < 4; k++) {
                        const uint32_t db = dB + ((rg.slot * SLOT + k * 2048) >> 4);
                        wgmma_n128(acc0, dA0 + ((kt * SLOT + k * 32) >> 4), db, (kt | k) != 0);
                        wgmma_n128(acc1, dA0 + ((kt * SLOT + 8192 + k * 32) >> 4), db, (kt | k) != 0);
                    }
                    wg_commit();
                    wg_wait<1>();
                    mbar_arrive_n_if(sb + BAR_EMPTYB + 8 * prev, 2, l0 && kt > 0);
                    mbar_arrive_if(sb + BAR_EMPTYA + 8 * ((kt + 7) & 7), l0 && kt > 0 && c > 0);
                    prev = rg.slot; rg.adv();
                }
                bar_arrive(2 + c, 256);
                mbar_waitc(sb + BAR_CS3, 0);
                float nm[4];
#pragma unroll
                for (int i = 0; i < 4; i++) nm[i] = lds_f2(sb + OFF_CS1 + (64 * (i >> 1) + 16 * wv + g + 8 * (i & 1)) * 8).x;
                wg_wait<0>();
                fence_acc<64>(acc0); fence_acc<64>(acc1);
                mbar_arrive_n_if(sb + BAR_EMPTYB + 8 * prev, 2, l0);
                mbar_arrive_if(sb + BAR_EMPTYA + 8 * 7, l0 && c > 0);
                TL(11 + c, (tid & 127) == 0);
                __nv_bfloat16* hp = g_hh + (size_t)(128 * m + 16 * wv + g) * FFP + 192 * j + 64 * c + (q & 1) * 8 + (q >> 1) * 4;
#pragma unroll
                for (int tp = 0; tp < 4; tp++) {
                    if (tp < 3 || c < 2) {
                        const uint32_t ca = sb + OFF_CS3 + (32 * c + 8 * tp + q) * 16;
                        const float4 c0 = lds_f4(ca), c1 = lds_f4(ca + 64);
                        store_pair(hp + 16 * tp, hh_pair(acc0 + 8 * tp, c0, nm[0]), hh_pair(acc0 + 8 * tp + 4, c1, nm[0]), q & 1);
                        store_pair(hp + 8 * FFP + 16 * tp, hh_pair(acc0 + 8 * tp + 2, c0, nm[1]), hh_pair(acc0 + 8 * tp + 6, c1, nm[1]), q & 1);
                        store_pair(hp + 64 * FFP + 16 * tp, hh_pair(acc1 + 8 * tp, c0, nm[2]), hh_pair(acc1 + 8 * tp + 4, c1, nm[2]), q & 1);
                        store_pair(hp + 72 * FFP + 16 * tp, hh_pair(acc1 + 8 * tp + 2, c0, nm[3]), hh_pair(acc1 + 8 * tp + 6, c1, nm[3]), q & 1);
                    }
                }
                __syncwarp();
                mbar_arrive_if(pub + 24 + 8 * c, l0);
                TL(54 + c, (tid & 127) == 0);
            }
            if (w == 1) bar_sync(4, 256);
        }
        {
            float acc[32];
            rg.slot = 2; rg.phase = 1;
#define KT_P4(T, HF, NK)                                                                                    \
    do {                                                                                                    \
        const int s_ = (T) & 7;                                                                             \
        if (!(HF)) mbar_waitc(sb + BAR_FULLB + 8 * rg.slot, rg.phase);                                       \
        mbar_waitc(sb + BAR_FULLA + 8 * s_, (((T) >> 3) + 1) & 1);                                           \
        if (!(HF)) TL(30 + (T) / 2, tid == 0);                                                              \
        wg_fence();                                                                                         \
        _Pragma("unroll") for (int k = 0; k < (NK); k++)                                                    \
            wgmma_n64(acc, dA + ((s_ * SLOT + k * 32) >> 4), dB + ((rg.slot * SLOT + (HF) * 8192 + k * 2048) >> 4), ((T) | k) != 0); \
        wg_commit();                                                                                        \
        wg_wait<1>();                                                                                       \
        mbar_arrive_if(sb + BAR_EMPTYA + 8 * (((T) + 7) & 7), l0 && (T) > 0);                               \
        if (!(HF)) mbar_arrive_if(sb + BAR_EMPTYB + 8 * prev, l0 && (T) > 0);                               \
        if (HF) { prev = rg.slot; rg.adv(); }                                                               \
    } while (0)
#pragma unroll 1
            for (int t = 0; t < 16; t += 2) { KT_P4(t, 0, 4); KT_P4(t + 1, 1, 4); }
            TL(14, tid == 0);
#pragma unroll 1
            for (int t = 16; t < 24; t += 2) { KT_P4(t, 0, 3); KT_P4(t + 1, 1, 3); }
            wg_wait<0>();
            fence_acc<32>(acc);
            TL(15, tid == 0);
            const float r0 = lds_f2(sb + OFF_CS1 + (16 * warp + g) * 8).y, r1 = lds_f2(sb + OFF_CS1 + (16 * warp + g + 8) * 8).y;
#pragma unroll
            for (int t = 0; t < 8; t++) {
                res_lo[t] = pack_bf16(fmaf(acc[4 * t], r0, bf_lo(res_lo[t])), fmaf(acc[4 * t + 1], r0, bf_hi(res_lo[t])));
                res_hi[t] = pack_bf16(fmaf(acc[4 * t + 2], r1, bf_lo(res_hi[t])), fmaf(acc[4 * t + 3], r1, bf_hi(res_hi[t])));
            }
            store_tile(own_rows, P.out + (size_t)row_w * DM + 64 * j, res_lo, res_hi, lane);
            if (tid == 0 && role == 0) g_epoch = epoch;
            TL(16, tid == 0); TLG(1, tid == 0);
        }
    }
}

typedef CUresult (*EncodeFn)(CUtensorMap*, CUtensorMapDataType, cuuint32_t, void*, const cuuint64_t*, const cuuint64_t*,
                             const cuuint32_t*, const cuuint32_t*, CUtensorMapInterleave, CUtensorMapSwizzle,
                             CUtensorMapL2promotion, CUtensorMapFloatOOBfill);

static void make_map2d(EncodeFn enc, CUtensorMap* tm, const void* base, uint64_t cols, uint64_t rows, uint64_t pitch_elems,
                       uint32_t box_rows) {
    cuuint64_t gd[2] = {cols, rows};
    cuuint64_t gs[1] = {pitch_elems * 2};
    cuuint32_t bd[2] = {64, box_rows};
    cuuint32_t es[2] = {1, 1};
    enc(tm, CU_TENSOR_MAP_DATA_TYPE_BFLOAT16, 2, const_cast<void*>(base), gd, gs, bd, es, CU_TENSOR_MAP_INTERLEAVE_NONE,
        CU_TENSOR_MAP_SWIZZLE_128B, CU_TENSOR_MAP_L2_PROMOTION_L2_256B, CU_TENSOR_MAP_FLOAT_OOB_FILL_NONE);
}

}

extern "C" void kernel_launch(void* const* d_in, const int* in_sizes, int n_in, void* d_out, int out_size) {
    using namespace hk;
    (void)in_sizes; (void)n_in; (void)out_size;
    static EncodeFn enc = nullptr;
    static void *po = nullptr, *ph = nullptr, *phh = nullptr;
    static int std_layout = 0;
    if (!enc) {
        void* fn = nullptr;
        cudaDriverEntryPointQueryResult qr;
        cudaGetDriverEntryPoint("cuTensorMapEncodeTiled", &fn, cudaEnableDefault, &qr);
        enc = (EncodeFn)fn;
        cudaGetSymbolAddress(&po, g_o);
        cudaGetSymbolAddress(&ph, g_h);
        cudaGetSymbolAddress(&phh, g_hh);
        cudaFuncSetAttribute(fused_kernel, cudaFuncAttributeMaxDynamicSharedMemorySize, SMEM_BYTES);
        int dev = 0, sms = 0;
        cudaGetDevice(&dev);
        cudaDeviceGetAttribute(&sms, cudaDevAttrMultiProcessorCount, dev);
        cudaFuncSetAttribute(fused_kernel, cudaFuncAttributeNonPortableClusterSizeAllowed, 1);
        const int sizes[3] = {8, 9, 16}, want[3] = {15, 9, 7};
        bool ok = sms == NCTA;
        for (int i = 0; i < 3 && ok; i++) {
            cudaLaunchConfig_t cfg = {};
            cfg.gridDim = dim3(sizes[i] * 8); cfg.blockDim = dim3(NTHREADS); cfg.dynamicSmemBytes = SMEM_BYTES;
            cudaLaunchAttribute at;
            at.id = cudaLaunchAttributeClusterDimension;
            at.val.clusterDim.x = sizes[i]; at.val.clusterDim.y = 1; at.val.clusterDim.z = 1;
            cfg.attrs = &at; cfg.numAttrs = 1;
            int n = 0;
            ok = cudaOccupancyMaxActiveClusters(&n, fused_kernel, &cfg) == cudaSuccess && n == want[i];
        }
        (void)cudaGetLastError();
        std_layout = ok ? 1 : 0;
    }
    Params P;
    const __nv_bfloat16* x = (const __nv_bfloat16*)d_in[0];
    P.x = x;
    P.wqkv = (const __nv_bfloat16*)d_in[1];
    P.wphi = (const __nv_bfloat16*)d_in[2];
    P.wo = (const __nv_bfloat16*)d_in[3];
    P.wg = (const __nv_bfloat16*)d_in[5];
    P.wu = (const __nv_bfloat16*)d_in[6];
    P.wd = (const __nv_bfloat16*)d_in[7];
    P.out = (__nv_bfloat16*)d_out;
    P.use_smid = std_layout;
    for (int i = 0; i < NCTA; i++) {
        int role = i < 4 ? 128 + i : i - 4;
        if (std_layout) {
            const int tpc = i >> 1, odd = i & 1;
            if (tpc < 32) role = (tpc & 7) * 8 + (tpc >> 3) * 2 + odd;
            else if (tpc < 60) role = (8 + (tpc - 32) % 7) * 8 + ((tpc - 32) / 7) * 2 + odd;
            else if (tpc < 62) role = 128 + (tpc - 60) * 2 + odd;
            else role = 15 * 8 + (tpc - 62) * 2 + odd;
        }
        P.role[i] = (unsigned char)role;
    }
    make_map2d(enc, &P.tx, x, DM, SEQ, DM, 128);
    make_map2d(enc, &P.to, po, DM, SEQ, DM, 128);
    make_map2d(enc, &P.th, ph, DM, SEQ, DM, 128);
    make_map2d(enc, &P.thh, phh, FFP, SEQ, FFP, 128);
    make_map2d(enc, &P.twq, P.wqkv, 3 * DM, DM, 3 * DM, 128);
    make_map2d(enc, &P.two, P.wo, DM, DM, DM, 128);
    make_map2d(enc, &P.twg, P.wg, FF, DM, FF, 64);
    make_map2d(enc, &P.twu, P.wu, FF, DM, FF, 64);
    make_map2d(enc, &P.twd, P.wd, DM, FF, DM, 64);
    {
        cuuint64_t gd[3] = {(cuuint64_t)DM, (cuuint64_t)DM, 3};
        cuuint64_t gs[2] = {(cuuint64_t)3 * DM * 2, (cuuint64_t)DM * 2};
        cuuint32_t bd[3] = {64, 64, 2};
        cuuint32_t es[3] = {1, 1, 1};
        enc(&P.twkv, CU_TENSOR_MAP_DATA_TYPE_BFLOAT16, 3, const_cast<__nv_bfloat16*>(P.wqkv), gd, gs, bd, es,
            CU_TENSOR_MAP_INTERLEAVE_NONE, CU_TENSOR_MAP_SWIZZLE_128B, CU_TENSOR_MAP_L2_PROMOTION_L2_256B,
            CU_TENSOR_MAP_FLOAT_OOB_FILL_NONE);
    }
    fused_kernel<<<NCTA, NTHREADS, SMEM_BYTES>>>(P);
}
```

```cpp
#include <cuda_runtime.h>
#include <cuda_bf16.h>
#include <cuda.h>
#include <stdint.h>

namespace hk {

constexpr int SEQ = 2048, DM = 512, FF = 1376, FFP = 1536;
constexpr int NCTA = 132;
constexpr int NTHREADS = 384;
constexpr uint32_t SLOT = 16384;
constexpr uint32_t OFF_A = 0, OFF_B = 8 * SLOT, OFF_MISC = 14 * SLOT;
constexpr uint32_t BAR_FULLA = OFF_MISC + 0, BAR_EMPTYA = OFF_MISC + 64, BAR_FULLB = OFF_MISC + 128,
                   BAR_EMPTYB = OFF_MISC + 176, BAR_CS1 = OFF_MISC + 224, BAR_CS3 = OFF_MISC + 232,
                   BAR_PUB = OFF_MISC + 240,
                   BAR_CSQ = OFF_MISC + 336, BAR_CSV = OFF_MISC + 344;
constexpr uint32_t OFF_CS1 = OFF_MISC + 384;
constexpr uint32_t OFF_CS3 = OFF_CS1 + 1024;
constexpr uint32_t SMEM_BYTES = OFF_CS3 + 1536;
constexpr int NB = 6;
constexpr int AHEAD = 3;

constexpr int ACC_KV = 0, ACC_Z = 2048, ACC_SIZE = 2176;

__device__ __align__(1024) __nv_bfloat16 g_o[SEQ * DM];
__device__ __align__(1024) __nv_bfloat16 g_h[SEQ * DM];
__device__ __align__(1024) __nv_bfloat16 g_hh[SEQ * FFP];
__device__ __align__(128) float g_hstat[SEQ * 16];
__device__ __align__(128) unsigned long long g_xstat[SEQ * 2];
__device__ __align__(128) float g_acc[8 * ACC_SIZE];
__device__ __align__(128) unsigned g_cnt[8 * 32];
__device__ __align__(128) unsigned long long g_cs[8 * 6 * 128];
__device__ __align__(128) unsigned g_flag[16 * 8 * 8];
__device__ unsigned g_epoch = 1;

#define TL(i, pred) do {} while (0)
#define TLG(i, pred) do {} while (0)

struct Params {
    CUtensorMap tx, to, th, thh, twkv, twq, two, twg, twu, twd;
    const __nv_bfloat16 *x, *wqkv, *wphi, *wo, *wg, *wu, *wd;
    __nv_bfloat16* out;
    int use_smid;
    unsigned char role[NCTA];
};

__device__ __forceinline__ uint32_t smem_u32(const void* p) { return (uint32_t)__cvta_generic_to_shared(p); }
__device__ __forceinline__ void mbar_init(uint32_t bar, uint32_t cnt) {
    asm volatile("mbarrier.init.shared::cta.b64 [%0], %1;" ::"r"(bar), "r"(cnt) : "memory");
}
__device__ __forceinline__ void mbar_expect_tx(uint32_t bar, uint32_t bytes) {
    asm volatile("mbarrier.arrive.expect_tx.shared::cta.b64 _, [%0], %1;" ::"r"(bar), "r"(bytes) : "memory");
}
__device__ __forceinline__ void mbar_arrive(uint32_t bar) {
    asm volatile("mbarrier.arrive.shared::cta.b64 _, [%0];" ::"r"(bar) : "memory");
}
__device__ __forceinline__ void mbar_arrive_if(uint32_t bar, bool pred) {
    asm volatile("{.reg .pred p; setp.ne.u32 p, %1, 0; @p mbarrier.arrive.shared::cta.b64 _, [%0];}" ::"r"(bar), "r"((uint32_t)pred) : "memory");
}
__device__ __forceinline__ bool mbar_try(uint32_t bar, uint32_t parity) {
    uint32_t ok;
    asm volatile("{.reg .pred p; mbarrier.try_wait.parity.shared::cta.b64 p, [%1], %2; selp.u32 %0,1,0,p;}"
                 : "=r"(ok) : "r"(bar), "r"(parity) : "memory");
    return ok;
}
__device__ __forceinline__ bool mbar_test(uint32_t bar, uint32_t parity) {
    uint32_t ok;
    asm volatile("{.reg .pred p; mbarrier.test_wait.parity.shared::cta.b64 p, [%1], %2; selp.u32 %0,1,0,p;}"
                 : "=r"(ok) : "r"(bar), "r"(parity) : "memory");
    return ok;
}
__device__ __forceinline__ void trap_if_gt(uint32_t v, uint32_t lim) {
    asm volatile("{.reg .pred p; setp.gt.u32 p, %0, %1; @p trap;}" ::"r"(v), "r"(lim));
}
__device__ __forceinline__ void mbar_wait(uint32_t bar, uint32_t parity) {
    asm volatile("{\n"
                 ".reg .pred P1, P2;\n"
                 ".reg .u32 c;\n"
                 "mov.u32 c, 0;\n"
                 "LAB_WAIT:\n"
                 "mbarrier.try_wait.parity.shared::cta.b64 P1, [%0], %1;\n"
                 "@P1 bra LAB_DONE;\n"
                 "add.u32 c, c, 1;\n"
                 "setp.gt.u32 P2, c, 4194304;\n"
                 "@P2 trap;\n"
                 "bra LAB_WAIT;\n"
                 "LAB_DONE:\n"
                 "}" ::"r"(bar), "r"(parity) : "memory");
}
__device__ __forceinline__ void mbar_waitc(uint32_t bar, uint32_t parity) {
    asm volatile("{\n"
                 ".reg .pred P1;\n"
                 "LAB_WAIT:\n"
                 "mbarrier.try_wait.parity.shared::cta.b64 P1, [%0], %1;\n"
                 "@!P1 bra LAB_WAIT;\n"
                 "}" ::"r"(bar), "r"(parity) : "memory");
}
__device__ __forceinline__ void tma2d(uint32_t dst, const CUtensorMap* tm, uint32_t bar, int c0, int c1) {
    asm volatile("cp.async.bulk.tensor.2d.shared::cluster.global.mbarrier::complete_tx::bytes [%0], [%1, {%3, %4}], [%2];"
                 ::"r"(dst), "l"(tm), "r"(bar), "r"(c0), "r"(c1) : "memory");
}
__device__ __forceinline__ void tma3d(uint32_t dst, const CUtensorMap* tm, uint32_t bar, int c0, int c1, int c2) {
    asm volatile("cp.async.bulk.tensor.3d.shared::cluster.global.mbarrier::complete_tx::bytes [%0], [%1, {%3, %4, %5}], [%2];"
                 ::"r"(dst), "l"(tm), "r"(bar), "r"(c0), "r"(c1), "r"(c2) : "memory");
}
__device__ __forceinline__ bool elect_one() {
    uint32_t ok;
    asm volatile("{.reg .pred p; elect.sync _|p, 0xffffffff; selp.u32 %0, 1, 0, p;}" : "=r"(ok));
    return ok;
}
__device__ __forceinline__ void prefetch_tmap(const CUtensorMap* tm) {
    asm volatile("prefetch.tensormap [%0];" ::"l"(tm) : "memory");
}
__device__ __forceinline__ void prefetch_l2(const void* p, uint32_t bytes) {
    asm volatile("cp.async.bulk.prefetch.L2.global [%0], %1;" ::"l"(p), "r"(bytes) : "memory");
}
__device__ __forceinline__ unsigned ld_acquire(const unsigned* p) {
    unsigned v; asm volatile("ld.acquire.gpu.global.u32 %0, [%1];" : "=r"(v) : "l"(p) : "memory"); return v;
}
__device__ __forceinline__ uint4 ld_acquire4(const unsigned* p) {
    uint4 v;
    asm volatile("ld.acquire.gpu.global.v4.u32 {%0,%1,%2,%3}, [%4];" : "=r"(v.x), "=r"(v.y), "=r"(v.z), "=r"(v.w) : "l"(p) : "memory");
    return v;
}
__device__ __forceinline__ unsigned ld_relaxed(const unsigned* p) {
    unsigned v; asm volatile("ld.relaxed.gpu.global.u32 %0, [%1];" : "=r"(v) : "l"(p)); return v;
}
__device__ __forceinline__ void st_relaxed(unsigned* p, unsigned v) {
    asm volatile("st.relaxed.gpu.global.u32 [%0], %1;" ::"l"(p), "r"(v) : "memory");
}
__device__ __forceinline__ void red_relaxed(unsigned* p, unsigned v) {
    asm volatile("red.relaxed.gpu.global.add.u32 [%0], %1;" ::"l"(p), "r"(v) : "memory");
}
__device__ __forceinline__ void fence_gpu() { asm volatile("fence.acq_rel.gpu;" ::: "memory"); }
__device__ __forceinline__ void fence_async_smem() { asm volatile("fence.proxy.async.shared::cta;" ::: "memory"); }
__device__ __forceinline__ void fence_async_global() { asm volatile("fence.proxy.async.global;" ::: "memory"); }
__device__ __forceinline__ void wait_count(const unsigned* p, unsigned target) {
    uint32_t it = 0;
    while ((int)(ld_acquire(p) - target) < 0) trap_if_gt(++it, 1u << 22);
}
__device__ __forceinline__ void wait_count_warp(const unsigned* p, unsigned target) {
    uint32_t it = 0;
    while (__any_sync(0xffffffffu, (int)(ld_acquire(p) - target) < 0)) trap_if_gt(++it, 1u << 22);
}
__device__ __forceinline__ void red_f32(float* p, float a) {
    asm volatile("red.relaxed.gpu.global.add.f32 [%0], %1;" ::"l"(p), "f"(a) : "memory");
}
__device__ __forceinline__ void red_f32x2(float* p, float a, float b) {
    asm volatile("red.relaxed.gpu.global.add.v2.f32 [%0], {%1, %2};" ::"l"(p), "f"(a), "f"(b) : "memory");
}
__device__ __forceinline__ void red_f32x4(float* p, float a, float b, float c, float d) {
    asm volatile("red.relaxed.gpu.global.add.v4.f32 [%0], {%1, %2, %3, %4};" ::"l"(p), "f"(a), "f"(b), "f"(c), "f"(d) : "memory");
}
__device__ __forceinline__ float4 ld_l2_f4(const float* p) {
    float4 v;
    asm volatile("ld.relaxed.gpu.global.v4.f32 {%0,%1,%2,%3}, [%4];" : "=f"(v.x), "=f"(v.y), "=f"(v.z), "=f"(v.w) : "l"(p) : "memory");
    return v;
}
__device__ __forceinline__ float2 ld_l2_f2(const float* p) {
    float2 v;
    asm volatile("ld.relaxed.gpu.global.v2.f32 {%0,%1}, [%2];" : "=f"(v.x), "=f"(v.y) : "l"(p) : "memory");
    return v;
}
__device__ __forceinline__ float ld_l2_f(const float* p) {
    float v;
    asm volatile("ld.relaxed.gpu.global.f32 %0, [%1];" : "=f"(v) : "l"(p) : "memory");
    return v;
}
__device__ __forceinline__ uint4 ldg_nc(const void* p) {
    uint4 v;
    asm volatile("ld.global.nc.L1::no_allocate.v4.u32 {%0,%1,%2,%3}, [%4];" : "=r"(v.x), "=r"(v.y), "=r"(v.z), "=r"(v.w) : "l"(p));
    return v;
}
__device__ __forceinline__ void stg128(void* p, uint32_t a, uint32_t b, uint32_t c, uint32_t d) {
    asm volatile("st.global.v4.u32 [%0], {%1,%2,%3,%4};" ::"l"(p), "r"(a), "r"(b), "r"(c), "r"(d) : "memory");
}
__device__ __forceinline__ uint4 lds128(uint32_t a) {
    uint4 v;
    asm volatile("ld.shared.v4.u32 {%0,%1,%2,%3}, [%4];" : "=r"(v.x), "=r"(v.y), "=r"(v.z), "=r"(v.w) : "r"(a) : "memory");
    return v;
}
__device__ __forceinline__ float2 lds_f2(uint32_t a) {
    float2 v;
    asm volatile("ld.shared.v2.f32 {%0,%1}, [%2];" : "=f"(v.x), "=f"(v.y) : "r"(a) : "memory");
    return v;
}
__device__ __forceinline__ void sts_f2(uint32_t a, float x, float y) {
    asm volatile("st.shared.v2.f32 [%0], {%1,%2};" ::"r"(a), "f"(x), "f"(y) : "memory");
}
__device__ __forceinline__ void sts64(uint32_t a, uint32_t x, uint32_t y) {
    asm volatile("st.shared.v2.u32 [%0], {%1,%2};" ::"r"(a), "r"(x), "r"(y) : "memory");
}
__device__ __forceinline__ void sts128(uint32_t a, uint32_t x, uint32_t y, uint32_t z, uint32_t w) {
    asm volatile("st.shared.v4.u32 [%0], {%1,%2,%3,%4};" ::"r"(a), "r"(x), "r"(y), "r"(z), "r"(w) : "memory");
}
__device__ __forceinline__ void stsm4(uint32_t a, uint32_t r0, uint32_t r1, uint32_t r2, uint32_t r3) {
    asm volatile("stmatrix.sync.aligned.m8n8.x4.shared.b16 [%0], {%1,%2,%3,%4};" ::"r"(a), "r"(r0), "r"(r1), "r"(r2), "r"(r3) : "memory");
}
__device__ __forceinline__ void ldsm4(uint32_t a, uint32_t& r0, uint32_t& r1, uint32_t& r2, uint32_t& r3) {
    asm volatile("ldmatrix.sync.aligned.m8n8.x4.shared.b16 {%0,%1,%2,%3}, [%4];" : "=r"(r0), "=r"(r1), "=r"(r2), "=r"(r3) : "r"(a) : "memory");
}
__device__ __forceinline__ void ldsm4t(uint32_t a, uint32_t& r0, uint32_t& r1, uint32_t& r2, uint32_t& r3) {
    asm volatile("ldmatrix.sync.aligned.m8n8.x4.trans.shared.b16 {%0,%1,%2,%3}, [%4];" : "=r"(r0), "=r"(r1), "=r"(r2), "=r"(r3) : "r"(a) : "memory");
}
__device__ __forceinline__ void mma16816(float* c, const uint32_t* a, uint32_t b0, uint32_t b1) {
    asm("mma.sync.aligned.m16n8k16.row.col.f32.bf16.bf16.f32 {%0,%1,%2,%3}, {%4,%5,%6,%7}, {%8,%9}, {%0,%1,%2,%3};"
                 : "+f"(c[0]), "+f"(c[1]), "+f"(c[2]), "+f"(c[3])
                 : "r"(a[0]), "r"(a[1]), "r"(a[2]), "r"(a[3]), "r"(b0), "r"(b1));
}
__device__ __forceinline__ uint32_t pack_bf16(float lo, float hi) {
    uint32_t r; asm("cvt.rn.bf16x2.f32 %0, %1, %2;" : "=r"(r) : "f"(hi), "f"(lo)); return r;
}
__device__ __forceinline__ float bf_lo(uint32_t w) { return __uint_as_float(w << 16); }
__device__ __forceinline__ float bf_hi(uint32_t w) { return __uint_as_float(w & 0xffff0000u); }
__device__ __forceinline__ float ex2(float x) { float r; asm("ex2.approx.ftz.f32 %0, %1;" : "=f"(r) : "f"(x)); return r; }
__device__ __forceinline__ float rcp(float x) { float r; asm("rcp.approx.ftz.f32 %0, %1;" : "=f"(r) : "f"(x)); return r; }
__device__ __forceinline__ void bar_sync(int id, int n) { asm volatile("bar.sync %0, %1;" ::"r"(id), "r"(n) : "memory"); }

__device__ __forceinline__ uint32_t desc_lo(uint32_t addr) { return ((addr & 0x3FFFF) >> 4) | (512u << 16); }
#define DESC_HI "0x40000040"
__device__ __forceinline__ void wg_fence() { asm volatile("wgmma.fence.sync.aligned;" ::: "memory"); }
__device__ __forceinline__ void wg_commit() { asm volatile("wgmma.commit_group.sync.aligned;" ::: "memory"); }
template <int N> __device__ __forceinline__ void wg_wait() { asm volatile("wgmma.wait_group.sync.aligned %0;" ::"n"(N) : "memory"); }
template <int N> __device__ __forceinline__ void fence_acc(float* d) {
#pragma unroll
    for (int i = 0; i < N; i++) asm volatile("" : "+f"(d[i])::"memory");
}
#define R4(o) "+f"(d[o + 0]), "+f"(d[o + 1]), "+f"(d[o + 2]), "+f"(d[o + 3])
#define R8(o) R4(o), R4(o + 4)
__device__ __forceinline__ void wgmma_n128(float* d, uint32_t da, uint32_t db, int sc) {
    asm volatile("{.reg .pred p; .reg .b64 da, db; setp.ne.b32 p, %66, 0; mov.b64 da, {%64, " DESC_HI "}; mov.b64 db, {%65, " DESC_HI "};\n"
                 "wgmma.mma_async.sync.aligned.m64n128k16.f32.bf16.bf16 {%0,%1,%2,%3,%4,%5,%6,%7,%8,%9,%10,%11,%12,%13,%14,%15,%16,%17,%18,%19,%20,%21,%22,%23,%24,%25,%26,%27,%28,%29,%30,%31,"
                 "%32,%33,%34,%35,%36,%37,%38,%39,%40,%41,%42,%43,%44,%45,%46,%47,%48,%49,%50,%51,%52,%53,%54,%55,%56,%57,%58,%59,%60,%61,%62,%63}, da, db, p, 1, 1, 0, 1;}"
                 : R8(0), R8(8), R8(16), R8(24), R8(32), R8(40), R8(48), R8(56)
                 : "r"(da), "r"(db), "r"(sc));
}
__device__ __forceinline__ void wgmma_n64(float* d, uint32_t da, uint32_t db, int sc) {
    asm volatile("{.reg .pred p; .reg .b64 da, db; setp.ne.b32 p, %34, 0; mov.b64 da, {%32, " DESC_HI "}; mov.b64 db, {%33, " DESC_HI "};\n"
                 "wgmma.mma_async.sync.aligned.m64n64k16.f32.bf16.bf16 {%0,%1,%2,%3,%4,%5,%6,%7,%8,%9,%10,%11,%12,%13,%14,%15,%16,%17,%18,%19,%20,%21,%22,%23,%24,%25,%26,%27,%28,%29,%30,%31}, da, db, p, 1, 1, 0, 1;}"
                 : R8(0), R8(8), R8(16), R8(24)
                 : "r"(da), "r"(db), "r"(sc));
}
__device__ __forceinline__ void wgmma_n40_tt(float* d, uint32_t da, uint32_t db, int sc) {
    asm volatile("{.reg .pred p; .reg .b64 da, db; setp.ne.b32 p, %22, 0; mov.b64 da, {%20, " DESC_HI "}; mov.b64 db, {%21, " DESC_HI "};\n"
                 "wgmma.mma_async.sync.aligned.m64n40k16.f32.bf16.bf16 {%0,%1,%2,%3,%4,%5,%6,%7,%8,%9,%10,%11,%12,%13,%14,%15,%16,%17,%18,%19}, da, db, p, 1, 1, 1, 1;}"
                 : R8(0), R8(8), R4(16)
                 : "r"(da), "r"(db), "r"(sc));
}

__device__ __forceinline__ void wgmma_n8_tt(float* d, uint32_t da, uint32_t db, int sc) {
    asm volatile("{.reg .pred p; .reg .b64 da, db; setp.ne.b32 p, %6, 0; mov.b64 da, {%4, " DESC_HI "}; mov.b64 db, {%5, " DESC_HI "};\n"
                 "wgmma.mma_async.sync.aligned.m64n8k16.f32.bf16.bf16 {%0,%1,%2,%3}, da, db, p, 1, 1, 1, 1;}"
                 : R4(0)
                 : "r"(da), "r"(db), "r"(sc));
}

__device__ __forceinline__ void red_f32_if(float* p, float a, bool pred) {
    asm volatile("{.reg .pred p; setp.ne.u32 p, %2, 0; @p red.relaxed.gpu.global.add.f32 [%0], %1;}" ::"l"(p), "f"(a), "r"((uint32_t)pred) : "memory");
}
__device__ __forceinline__ void stg_f2_if(float* p, float a, float b, bool pred) {
    asm volatile("{.reg .pred p; setp.ne.u32 p, %3, 0; @p st.global.v2.f32 [%0], {%1,%2};}" ::"l"(p), "f"(a), "f"(b), "r"((uint32_t)pred) : "memory");
}
__device__ __forceinline__ void stg64(void* p, uint32_t a, uint32_t b) {
    asm volatile("st.global.v2.u32 [%0], {%1,%2};" ::"l"(p), "r"(a), "r"(b) : "memory");
}
__device__ __forceinline__ void store_pair(__nv_bfloat16* p, uint32_t r0, uint32_t r1, bool odd) {
    const uint32_t x = __shfl_xor_sync(0xffffffffu, odd ? r0 : r1, 1);
    stg64(p, odd ? x : r0, odd ? r1 : x);
}
__device__ __forceinline__ void mma16816_z(float* c, const uint32_t* a, uint32_t b0, uint32_t b1) {
    asm("mma.sync.aligned.m16n8k16.row.col.f32.bf16.bf16.f32 {%0,%1,%2,%3}, {%4,%5,%6,%7}, {%8,%9}, {%10,%10,%10,%10};"
                 : "=f"(c[0]), "=f"(c[1]), "=f"(c[2]), "=f"(c[3])
                 : "r"(a[0]), "r"(a[1]), "r"(a[2]), "r"(a[3]), "r"(b0), "r"(b1), "f"(0.f));
}
__device__ __forceinline__ uint32_t max2(uint32_t a, uint32_t b) { uint32_t r; asm("max.bf16x2 %0, %1, %2;" : "=r"(r) : "r"(a), "r"(b)); return r; }
__device__ __forceinline__ uint32_t min2(uint32_t a, uint32_t b) { uint32_t r; asm("min.bf16x2 %0, %1, %2;" : "=r"(r) : "r"(a), "r"(b)); return r; }
__device__ __forceinline__ void bar_arrive(int id, int n) { asm volatile("bar.arrive %0, %1;" ::"r"(id), "r"(n) : "memory"); }
__device__ __forceinline__ void mbar_arrive_n_if(uint32_t bar, uint32_t n, bool pred) {
    asm volatile("{.reg .pred p; setp.ne.u32 p, %1, 0; @p mbarrier.arrive.shared::cta.b64 _, [%0], %2;}" ::"r"(bar), "r"((uint32_t)pred), "r"(n) : "memory");
}
__device__ __forceinline__ float4 lds_f4(uint32_t a) {
    float4 v;
    asm volatile("ld.shared.v4.f32 {%0,%1,%2,%3}, [%4];" : "=f"(v.x), "=f"(v.y), "=f"(v.z), "=f"(v.w) : "r"(a) : "memory");
    return v;
}
__device__ __forceinline__ uint4 ld_tagged(const unsigned long long* p) {
    unsigned long long a, b;
    asm volatile("ld.acquire.gpu.global.v2.b64 {%0,%1}, [%2];" : "=l"(a), "=l"(b) : "l"(p) : "memory");
    return make_uint4((unsigned)a, (unsigned)(a >> 32), (unsigned)b, (unsigned)(b >> 32));
}
__device__ __forceinline__ uint4 ld_tagged_rlx(const unsigned long long* p) {
    unsigned long long a, b;
    asm volatile("ld.relaxed.gpu.global.v2.b64 {%0,%1}, [%2];" : "=l"(a), "=l"(b) : "l"(p) : "memory");
    return make_uint4((unsigned)a, (unsigned)(a >> 32), (unsigned)b, (unsigned)(b >> 32));
}
__device__ __forceinline__ void st_tagged_if(unsigned long long* p, float a, float b, unsigned tag, bool pred) {
    const unsigned long long t = (unsigned long long)tag << 32;
    asm volatile("{.reg .pred p; setp.ne.u32 p, %3, 0; @p st.relaxed.gpu.global.v2.b64 [%0], {%1,%2};}"
                 ::"l"(p), "l"(t | __float_as_uint(a)), "l"(t | __float_as_uint(b)), "r"((uint32_t)pred) : "memory");
}

__device__ __forceinline__ void store_tile(uint32_t tile_rows, __nv_bfloat16* gdst, const uint32_t* lo, const uint32_t* hi, int lane) {
    const int r = lane & 15;
#pragma unroll
    for (int b = 0; b < 4; b++)
        stsm4(tile_rows + r * 128 + (((2 * b + (lane >> 4)) ^ (r & 7)) << 4), lo[2 * b], hi[2 * b], lo[2 * b + 1], hi[2 * b + 1]);
    __syncwarp();
#pragma unroll
    for (int i = 0; i < 4; i++) {
        const int rr = 4 * i + (lane >> 3);
        const uint4 v = lds128(tile_rows + rr * 128 + (((lane & 7) ^ (rr & 7)) << 4));
        stg128(gdst + rr * DM + (lane & 7) * 8, v.x, v.y, v.z, v.w);
    }
}

template <bool NORM>
__device__ __forceinline__ void feature_map(const uint32_t* a, const uint32_t* wb, float c0, float c1, uint32_t* plus, uint32_t* minus, float* rs) {
    float p[8];
    mma16816_z(p, a, wb[0], wb[1]);
    mma16816_z(p + 4, a, wb[2], wb[3]);
    const uint32_t P0 = pack_bf16(p[0], p[2]), P1 = pack_bf16(p[1], p[3]), P2 = pack_bf16(p[4], p[6]), P3 = pack_bf16(p[5], p[7]);
    uint32_t mx = max2(max2(P0, P1), max2(P2, P3)), mn = min2(min2(P0, P1), min2(P2, P3));
#pragma unroll
    for (int s = 1; s <= 2; s <<= 1) {
        mx = max2(mx, __shfl_xor_sync(0xffffffffu, mx, s));
        mn = min2(mn, __shfl_xor_sync(0xffffffffu, mn, s));
    }
    const float mx0 = bf_lo(mx) * c0, mx1 = bf_hi(mx) * c1, mn0 = bf_lo(mn) * c0, mn1 = bf_hi(mn) * c1;
    p[0] = bf_lo(P0); p[2] = bf_hi(P0); p[1] = bf_lo(P1); p[3] = bf_hi(P1);
    p[4] = bf_lo(P2); p[6] = bf_hi(P2); p[5] = bf_lo(P3); p[7] = bf_hi(P3);
    float ep[8], em[8];
#pragma unroll
    for (int i = 0; i < 8; i++) {
        const bool r1 = (i & 2);
        ep[i] = ex2(fmaf(p[i], r1 ? c1 : c0, r1 ? -mx1 : -mx0));
        em[i] = ex2(fmaf(p[i], r1 ? -c1 : -c0, r1 ? mn1 : mn0));
    }
    float sp[4], sm[4];
#pragma unroll
    for (int i = 0; i < 4; i++) { plus[i] = pack_bf16(ep[2 * i], ep[2 * i + 1]); minus[i] = pack_bf16(em[2 * i], em[2 * i + 1]); }
    mma16816_z(sp, plus, 0x3f803f80u, 0x3f803f80u);
    mma16816_z(sm, minus, 0x3f803f80u, 0x3f803f80u);
    rs[0] = rcp(sp[0]); rs[1] = rcp(sp[2]); rs[2] = rcp(sm[0]); rs[3] = rcp(sm[2]);
    if (NORM) {
#pragma unroll
        for (int i = 0; i < 4; i++) {
            plus[i] = pack_bf16(ep[2 * i] * rs[i & 1], ep[2 * i + 1] * rs[i & 1]);
            minus[i] = pack_bf16(em[2 * i] * rs[2 + (i & 1)], em[2 * i + 1] * rs[2 + (i & 1)]);
        }
    }
}

template <bool SCALE>
__device__ __forceinline__ void ln_frag(const float* acc, uint32_t cs_addr, float rs0, float nm0, float rs1, float nm1, uint32_t* a) {
    const float2 c0 = lds_f2(cs_addr), c1 = lds_f2(cs_addr + 32);
    const float s0 = SCALE ? rs0 : 1.f, s1 = SCALE ? rs1 : 1.f;
    a[0] = pack_bf16(fmaf(nm0, c0.x, acc[0]) * s0, fmaf(nm0, c0.y, acc[1]) * s0);
    a[1] = pack_bf16(fmaf(nm1, c0.x, acc[2]) * s1, fmaf(nm1, c0.y, acc[3]) * s1);
    a[2] = pack_bf16(fmaf(nm0, c1.x, acc[4]) * s0, fmaf(nm0, c1.y, acc[5]) * s0);
    a[3] = pack_bf16(fmaf(nm1, c1.x, acc[6]) * s1, fmaf(nm1, c1.y, acc[7]) * s1);
}

__device__ __forceinline__ uint32_t hh_pair(const float* ag, float4 cs, float nmean) {
    const float g0 = fmaf(nmean, cs.x, ag[0]), g1 = fmaf(nmean, cs.y, ag[1]);
    const float u0 = fmaf(nmean, cs.z, ag[32]), u1 = fmaf(nmean, cs.w, ag[33]);
    return pack_bf16(g0 * u0, g1 * u1);
}

struct Ring {
    int slot; uint32_t phase;
    __device__ __forceinline__ void adv() { if (++slot == NB) { slot = 0; phase ^= 1; } }
};

__global__ void __launch_bounds__(NTHREADS, 1) fused_kernel(const __grid_constant__ Params P) {
    extern __shared__ __align__(1024) uint8_t smem_raw[];
    const uint32_t sb = smem_u32(smem_raw);
    const int tid = threadIdx.x, lane = tid & 31;
    const int warp = __shfl_sync(0xffffffffu, tid >> 5, 0);
    unsigned role = blockIdx.x;
    if (P.use_smid) asm volatile("mov.u32 %0, %%smid;" : "=r"(role));
    role = P.role[role];
    const int m = role >> 3, j = role & 7;
    const bool helper = role >= 128;

    TL(0, tid == 0); TLG(0, tid == 0);
    float* const acc_j = g_acc + j * ACC_SIZE;
    unsigned* const cnt_j = g_cnt + j * 32;

    if (__builtin_expect(warp >= 8, 1)) {
        asm volatile("setmaxnreg.dec.sync.aligned.u32 72;");
        if (elect_one()) {
            if (warp == 8) {
                if (!helper) {
#pragma unroll
                    for (int i = 0; i < NB; i++) mbar_init(sb + BAR_FULLB + 8 * i, 1);
#pragma unroll
                    for (int i = 0; i < 2; i++) {
                        mbar_expect_tx(sb + BAR_FULLB + 8 * i, SLOT);
                        tma3d(sb + OFF_B + i * SLOT, &P.twkv, sb + BAR_FULLB + 8 * i, 64 * j, 64 * i, 1);
                    }
                }
            } else if (warp == 9) {
#pragma unroll
                for (int i = 0; i < 8; i++) mbar_init(sb + BAR_FULLA + 8 * i, 1);
#pragma unroll
                for (int i = 0; i < 2; i++) {
                    mbar_expect_tx(sb + BAR_FULLA + 8 * i, SLOT);
                    tma2d(sb + OFF_A + i * SLOT, helper ? &P.twq : &P.tx, sb + BAR_FULLA + 8 * i, helper ? DM + 128 * j : 64 * i, 128 * (helper ? i : m));
                }
            } else if (warp == 10) {
#pragma unroll
                for (int i = 0; i < 16; i++) mbar_init(sb + BAR_CS1 + 8 * i, i == 1 ? 160 : ((i == 0 || i >= 14) ? 32 : 4));
                trap_if_gt(sb & 1023, 0);
                if (!helper) prefetch_l2(P.wqkv + (size_t)role * 6144, 12288);
            } else {
#pragma unroll
                for (int i = 0; i < 14; i++) mbar_init(sb + (i < 8 ? BAR_EMPTYA : BAR_EMPTYB - 64) + 8 * i, 8);
            }
        }
        __syncwarp();
        const unsigned epoch = ld_relaxed(&g_epoch);
        bar_sync(0, NTHREADS);
        if (helper) {
            if (warp == 8) {
                if (elect_one()) {
#pragma unroll 1
                    for (int i = 2; i < 72; i++) {
                        const uint32_t full = sb + BAR_FULLA + 8 * (i & 7), dst = sb + OFF_A + (i & 7) * SLOT;
                        mbar_wait(sb + BAR_EMPTYA + 8 * (i & 7), ((i >> 3) & 1) ^ 1);
                        mbar_expect_tx(full, SLOT);
                        if (i < 24) {
                            tma2d(dst, &P.twq, full, (i < 16 ? DM + 64 * (i & 8) : 0) + 128 * j + 16 * (i & 4), 128 * (i & 3));
                        } else {
                            const int u = (i >> 3) - 3, c0 = 176 * (2 * j + (u & 1)) + 64 * (u >> 1);
                            tma2d(dst, &P.twg, full, c0, 64 * (i & 7));
                            tma2d(dst + 8192, &P.twu, full, c0, 64 * (i & 7));
                        }
                    }
                    prefetch_l2(P.wd + (size_t)j * 176128, 352256);
                }
            } else if (warp == 9) {
                wait_count_warp(g_cnt + (lane & 7) * 32, epoch * 32);
            }
            return;
        }
        if (warp == 8) {
            if (elect_one()) {
                Ring r{2, 0};
#pragma unroll 1
                for (int i = 2; i < 56; i++) {
                    const uint32_t full = sb + BAR_FULLB + 8 * r.slot, dst = sb + OFF_B + r.slot * SLOT;
                    mbar_wait(sb + BAR_EMPTYB + 8 * r.slot, r.phase ^ 1);
                    if (i >= 8 && i < 12) {
                        mbar_arrive(full);
                    } else {
                        if (i >= AHEAD && i < 6) mbar_wait(full - 8 * AHEAD, 0);
                        mbar_expect_tx(full, SLOT);
                        if (i < 8) {
                            tma3d(dst, &P.twkv, full, 64 * j, 64 * i, 1);
                        } else if (i < 20) {
                            tma2d(dst, i < 16 ? &P.twq : &P.two, full, 64 * j, 128 * (i & 3));
                        } else if (i < 44) {
                            const int c = (i - 20) >> 3, kt = (i - 20) & 7;
                            tma2d(dst, &P.twg, full, 176 * j + 64 * c, 64 * kt);
                            tma2d(dst + 8192, &P.twu, full, 176 * j + 64 * c, 64 * kt);
                        } else {
                            const int c = (i - 44) >> 2, jj = (i & 3) * 2;
                            tma2d(dst, &P.twd, full, 64 * j, 176 * jj + 64 * c);
                            tma2d(dst + 8192, &P.twd, full, 64 * j, 176 * (jj + 1) + 64 * c);
                        }
                    }
                    r.adv();
                }
            }
            return;
        }
        if (warp == 9) {
            if (elect_one()) {
#pragma unroll 1
                for (int i = 2; i < 8; i++) {
                    if (i >= AHEAD) mbar_wait(sb + BAR_FULLA + 8 * (i - AHEAD), 0);
                    mbar_expect_tx(sb + BAR_FULLA + 8 * i, SLOT);
                    tma2d(sb + OFF_A + i * SLOT, &P.tx, sb + BAR_FULLA + 8 * i, 64 * i, 128 * m);
                }
#pragma unroll 1
                for (int i = 1; i < 10; i++) prefetch_tmap(&P.tx + i);
            }
            __syncwarp();
        }
        const unsigned long long* cs = g_cs + j * 768 + 2 * lane;
        {
            uint4 v;
            uint32_t it = 0;
            while (true) {
                v = ld_tagged(cs + (warp == 9 ? 256 : 128 * (warp - 10)));
                if (!__any_sync(0xffffffffu, v.y != epoch || v.w != epoch)) break;
                __nanosleep(100);
                trap_if_gt(++it, 1u << 22);
            }
            sts64(sb + OFF_CS1 + 256 * (warp - 9) + 8 * lane, v.x, v.z);
            mbar_arrive(sb + (warp == 9 ? BAR_CSQ : (warp == 10 ? BAR_CS1 : BAR_CSV)));
        }
        if (warp == 9) {
#pragma unroll 1
            for (int r = 1; r < 6; r++) {
                const CUtensorMap* tm = r == 1 ? &P.to : (r == 2 ? &P.th : &P.thh);
                const unsigned* fp = g_flag + (m * 8 + ((lane >> 1) & 7)) * 8 + (r < 3 ? 2 * r - 2 + (lane & 1) : r + 1);
                uint32_t ready = r < 3 ? 3u << (2 * j) : 0u, it = 0;
#pragma unroll 1
                for (int i = 0; i < 8; i++) {
                    while (((ready >> (2 * i)) & 3) != 3) {
                        ready |= __ballot_sync(0xffffffffu, ld_acquire(fp) == epoch);
                        trap_if_gt(++it, 1u << 22);
                    }
                    const uint32_t full = sb + BAR_FULLA + 8 * i;
                    mbar_wait(sb + BAR_EMPTYA + 8 * i, (r - 1) & 1);
                    if (elect_one()) {
                        if (r < 3 && i == j) {
                            mbar_arrive(full);
                        } else {
                            fence_async_global();
                            mbar_expect_tx(full, SLOT);
                            tma2d(sb + OFF_A + i * SLOT, tm, full, r < 3 ? 64 * i : 192 * i + 64 * (r - 3), 128 * m);
                        }
                    }
                    __syncwarp();
                }
            }
        } else {
            const int a = warp - 10;
#pragma unroll 1
            for (int ev = 0; ev < 6; ev += (ev >= 2 + a) ? 2 - (ev == 2) : 1 + (ev == 2)) {
                if (lane == 0) {
                    mbar_wait(sb + BAR_PUB + 8 * (a * 6 + ev), 0);
                    fence_gpu();
                    if (ev == 0) red_relaxed(cnt_j, 1);
                    else st_relaxed(g_flag + role * 8 + (ev < 3 ? 2 * ev - 2 + a : ev + 1), epoch);
                }
                __syncwarp();
                if (ev == 2 && a == 0) {
#pragma unroll 1
                    for (int c = 0; c < 3; c++) {
                        uint4 vg, vu;
                        uint32_t it = 0;
                        do {
                            vg = ld_tagged_rlx(cs + 384 + 128 * c); vu = ld_tagged_rlx(cs + 448 + 128 * c);
                            trap_if_gt(++it, 1u << 22);
                        } while (__any_sync(0xffffffffu, vg.y != epoch || vg.w != epoch || vu.y != epoch || vu.w != epoch));
                        sts128(sb + OFF_CS3 + (32 * c + lane) * 16, vg.x, vg.z, vu.x, vu.z);
                    }
                    mbar_arrive(sb + BAR_CS3);
                }
            }
        }
        return;
    }
    const unsigned epoch = ld_relaxed(&g_epoch);
    uint4 xv[4];
    uint32_t wraw[16];
    if (!helper) {
        const __nv_bfloat16* xp = P.x + (size_t)(128 * m + 16 * j + 2 * warp + (lane >> 4)) * DM + (lane & 15) * 8;
#pragma unroll
        for (int i = 0; i < 4; i++) xv[i] = ldg_nc(xp + 128 * i);
        const uint32_t* wp = reinterpret_cast<const uint32_t*>(P.wphi) + (4 * j) * 128 + (lane & 3) * 16 + (lane >> 2);
#pragma unroll
        for (int i = 0; i < 16; i++)
            asm volatile("ld.global.nc.u32 %0, [%1];" : "=r"(wraw[i]) : "l"(wp + (i >> 2) * 128 + ((i >> 1) & 1) * 64 + (i & 1) * 8));
    }
    asm volatile("setmaxnreg.inc.sync.aligned.u32 216;");
    bar_sync(0, NTHREADS);
    if (helper) {
        if (warp < 4) {
            sts128(sb + OFF_B + 16 * tid, 0x3f803f80u, 0x3f803f80u, 0x3f803f80u, 0x3f803f80u);
            for (int i = tid; i < 2 * ACC_SIZE / 4; i += 128) stg128(g_acc + 2 * j * ACC_SIZE + 4 * i, 0, 0, 0, 0);
            fence_async_smem();
            fence_gpu();
            bar_sync(1, 128);
            float acc[8];
            int i = 0;
#pragma unroll 1
            for (int job = 0; job < 12; job++) {
                const int n = job < 6 ? 4 : 8;
#pragma unroll 1
                for (int t = 0; t < n; t++, i++) {
                    mbar_wait(sb + BAR_FULLA + 8 * (i & 7), (i >> 3) & 1);
                    wg_fence();
#pragma unroll
                    for (int k = 0; k < 8; k++)
                        wgmma_n8_tt(acc + (k & 4), desc_lo(sb + OFF_A) + (((i & 7) * SLOT + k * 2048) >> 4), desc_lo(sb + OFF_B), (t | (k & 3)) != 0);
                    wg_commit();
                    wg_wait<1>();
                    mbar_arrive_n_if(sb + BAR_EMPTYA + 8 * ((i + 7) & 7), 2, lane == 0 && i > 0);
                }
                wg_wait<0>();
                fence_acc<8>(acc);
                const int q = lane & 3;
                const float lo = (q & 1) ? acc[2] : acc[0], hi = (q & 1) ? acc[6] : acc[4];
                const float v = job < 6 ? lo + hi : ((q & 2) ? hi : lo);
                unsigned long long* dst = g_cs + ((2 * j + (job & 1)) * 6 + (job >> 1)) * 128 + (q >> 1) * 64 + 16 * warp + 8 * (q & 1) + (lane >> 2);
                asm volatile("st.relaxed.gpu.global.b64 [%0], %1;" ::"l"(dst), "l"(((unsigned long long)epoch << 32) | __float_as_uint(v)) : "memory");
            }
        }
        return;
    }
    {
        const int w = warp >> 2, wv = warp & 3, g = lane >> 2, q = lane & 3;
        const int row_w = 128 * m + 16 * warp;
        const uint32_t sa = sb + OFF_A + w * 8192;
        const uint32_t dA = desc_lo(sa), dB = desc_lo(sb + OFF_B);
        const uint32_t pub = sb + BAR_PUB + 48 * w;
        const bool l0 = lane == 0;
        Ring rg{0, 0};
        int prev = 0;

        uint32_t wb[16];
        {
            const int row = 128 * m + 16 * j + 2 * warp + (lane >> 4);
            const uint4* v = xv;
            float f[32];
#pragma unroll
            for (int i = 0; i < 4; i++) {
                f[8 * i] = bf_lo(v[i].x); f[8 * i + 1] = bf_hi(v[i].x); f[8 * i + 2] = bf_lo(v[i].y); f[8 * i + 3] = bf_hi(v[i].y);
                f[8 * i + 4] = bf_lo(v[i].z); f[8 * i + 5] = bf_hi(v[i].z); f[8 * i + 6] = bf_lo(v[i].w); f[8 * i + 7] = bf_hi(v[i].w);
            }
            float s0 = 0.f, s1 = 0.f;
#pragma unroll
            for (int i = 0; i < 16; i++) { s0 += f[2 * i]; s1 += f[2 * i + 1]; }
            s0 += s1;
#pragma unroll
            for (int o = 8; o; o >>= 1) s0 += __shfl_xor_sync(0xffffffffu, s0, o);
            const float mean = s0 * (1.f / DM);
            s0 = 0.f; s1 = 0.f;
#pragma unroll
            for (int i = 0; i < 16; i++) {
                const float d0 = f[2 * i] - mean, d1 = f[2 * i + 1] - mean;
                s0 = fmaf(d0, d0, s0); s1 = fmaf(d1, d1, s1);
            }
            s0 += s1;
#pragma unroll
            for (int o = 8; o; o >>= 1) s0 += __shfl_xor_sync(0xffffffffu, s0, o);
            const float rs = rsqrtf(s0 * (1.f / DM) + 1e-5f);
            st_tagged_if(g_xstat + 2 * row, rs, -mean, epoch, (lane & 15) == 0);
        }
        constexpr float L2E = 1.4426950408889634f;
        TL(57, tid == 0);
        uint32_t fp[16], fm[16];
        float fr[16];
        float rs0, nm0, rs1, nm1;
        {
            float acc[64];
#pragma unroll 1
            for (int kt = 0; kt < 8; kt++) {
                mbar_waitc(sb + BAR_FULLA + 8 * kt, 0);
                mbar_waitc(sb + BAR_FULLB + 8 * rg.slot, rg.phase);
                TL(20 + kt, tid == 0);
                wg_fence();
#pragma unroll
                for (int k = 0; k < 4; k++)
                    wgmma_n128(acc, dA + ((kt * SLOT + k * 32) >> 4), dB + ((rg.slot * SLOT + k * 2048) >> 4), (kt | k) != 0);
                wg_commit();
                wg_wait<1>();
                mbar_arrive_if(sb + BAR_EMPTYB + 8 * prev, l0 && kt > 0);
                prev = rg.slot; rg.adv();
            }
            {
                uint4 a, b;
                uint32_t it = 0;
                do {
                    a = ld_tagged_rlx(g_xstat + 2 * (row_w + g));
                    b = ld_tagged_rlx(g_xstat + 2 * (row_w + g + 8));
                    trap_if_gt(++it, 1u << 22);
                } while (__any_sync(0xffffffffu, a.y != epoch || a.w != epoch || b.y != epoch || b.w != epoch));
                rs0 = __uint_as_float(a.x); nm0 = __uint_as_float(a.z); rs1 = __uint_as_float(b.x); nm1 = __uint_as_float(b.z);
            }
#pragma unroll
            for (int i = 0; i < 8; i++) {
                wb[(i >> 1) * 4 + (i & 1)] = __byte_perm(wraw[2 * i], wraw[2 * i + 1], 0x5410);
                wb[(i >> 1) * 4 + 2 + (i & 1)] = __byte_perm(wraw[2 * i], wraw[2 * i + 1], 0x7632);
            }
            TL(17, tid == 0);
            mbar_waitc(sb + BAR_CS1, 0);
            TL(18, tid == 0);
            wg_wait<0>();
            fence_acc<64>(acc);
            mbar_arrive_if(sb + BAR_EMPTYB + 8 * prev, l0);
            TL(2, tid == 0);
#pragma unroll
            for (int i = 2; i < 6; i++) mbar_waitc(sb + BAR_FULLB + 8 * i, 1);
            const int lrow = 16 * warp + (lane & 15), ch = lane >> 4, sw = lane & 7;
            const uint32_t st = sb + OFF_B + 2 * SLOT + lrow * 128;
            uint32_t ka[16];
#pragma unroll
            for (int hh = 0; hh < 4; hh++)
                ln_frag<false>(acc + 8 * hh, sb + OFF_CS1 + (64 + 16 * hh + 2 * q) * 4, rs0, nm0, rs1, nm1, ka + 4 * hh);
#pragma unroll
            for (int hh = 0; hh < 4; hh++) feature_map<true>(ka + 4 * hh, wb + 4 * hh, rs0 * L2E, rs1 * L2E, fp + 4 * hh, fm + 4 * hh, fr);
#pragma unroll
            for (int hh = 0; hh < 4; hh++) {
                stsm4(st + (hh >> 1) * SLOT + (((4 * (hh & 1) + ch) ^ sw) << 4), fp[4 * hh], fp[4 * hh + 1], fp[4 * hh + 2], fp[4 * hh + 3]);
                stsm4(st + (hh >> 1) * SLOT + (((4 * (hh & 1) + 2 + ch) ^ sw) << 4), fm[4 * hh], fm[4 * hh + 1], fm[4 * hh + 2], fm[4 * hh + 3]);
            }
            mbar_waitc(sb + BAR_CSV, 0);
#pragma unroll
            for (int hh = 0; hh < 4; hh++) {
                uint32_t a[4];
                ln_frag<true>(acc + 32 + 8 * hh, sb + OFF_CS1 + (128 + 16 * hh + 2 * q) * 4, rs0, nm0, rs1, nm1, a);
                stsm4(st + (2 + (hh >> 1)) * SLOT + (((2 * (hh & 1) + ch) ^ sw) << 4), a[0], a[1], a[2], a[3]);
            }
            stsm4(st + (2 + ch) * SLOT + ((4 ^ sw) << 4), 0x3f803f80u, 0x3f803f80u, 0x3f803f80u, 0x3f803f80u);
            fence_async_smem();
            bar_sync(1, 256);
            float kvd[20];
            wg_fence();
#pragma unroll
            for (int k = 0; k < 8; k++)
                wgmma_n40_tt(kvd, dB + (((2 + w) * SLOT + k * 2048) >> 4), dB + (((4 + w) * SLOT + k * 2048) >> 4), k != 0);
            wg_commit();
            wg_wait<0>();
            fence_acc<20>(kvd);
            const bool h1 = wv >= 2;
            const int f = 16 * warp + g;
            float* kvp = acc_j + ACC_KV + f * 16 + 2 * q;
            red_f32x2(kvp, h1 ? kvd[8] : kvd[0], h1 ? kvd[9] : kvd[1]);
            red_f32x2(kvp + 128, h1 ? kvd[10] : kvd[2], h1 ? kvd[11] : kvd[3]);
            red_f32x2(kvp + 8, h1 ? kvd[12] : kvd[4], h1 ? kvd[13] : kvd[5]);
            red_f32x2(kvp + 136, h1 ? kvd[14] : kvd[6], h1 ? kvd[15] : kvd[7]);
            red_f32_if(acc_j + ACC_Z + f + 8 * (q & 1), q ? kvd[18] : kvd[16], q < 2);
            __syncwarp();
            mbar_arrive_if(pub, l0);
            mbar_arrive_if(sb + BAR_EMPTYB + 8 * (2 + (lane & 3)), lane < 4);
            TL(3, tid == 0);
        }
        uint32_t res_lo[8], res_hi[8];
        const uint32_t own_rows = sb + OFF_A + j * SLOT + warp * 2048;
        {
            float acc[32];
            rg.slot = 0; rg.phase = 0;
#pragma unroll 1
            for (int b = 0; b < 4; b++) {
                mbar_waitc(sb + BAR_FULLB + 8 * rg.slot, rg.phase);
                wg_fence();
#pragma unroll
                for (int k = 0; k < 8; k++)
                    wgmma_n64(acc, dA + (((2 * b + (k >> 2)) * SLOT + (k & 3) * 32) >> 4), dB + ((rg.slot * SLOT + k * 2048) >> 4), (b | k) != 0);
                wg_commit();
                wg_wait<1>();
                mbar_arrive_if(sb + BAR_EMPTYB + 8 * prev, l0 && b > 0);
                prev = rg.slot; rg.adv();
            }
            wg_wait<0>();
            fence_acc<32>(acc);
            mbar_arrive_if(sb + BAR_EMPTYB + 8 * prev, l0);
            mbar_arrive_if(sb + BAR_EMPTYA + 8 * (lane & 7), lane < 8 && (lane | 1) != (j | 1));
            TL(4, tid == 0);
            mbar_waitc(sb + BAR_CSQ, 0);
            uint32_t qa[16];
#pragma unroll
            for (int hh = 0; hh < 4; hh++)
                ln_frag<false>(acc + 8 * hh, sb + OFF_CS1 + (16 * hh + 2 * q) * 4, rs0, nm0, rs1, nm1, qa + 4 * hh);
#pragma unroll
            for (int hh = 0; hh < 4; hh++) feature_map<false>(qa + 4 * hh, wb + 4 * hh, rs0 * L2E, rs1 * L2E, fp + 4 * hh, fm + 4 * hh, fr + 4 * hh);
#pragma unroll
            for (int b = 0; b < 4; b++)
                ldsm4(own_rows + (lane & 15) * 128 + (((2 * b + (lane >> 4)) ^ (lane & 7)) << 4),
                      res_lo[2 * b], res_hi[2 * b], res_lo[2 * b + 1], res_hi[2 * b + 1]);
            TL(5, tid == 0);
            if (warp == 0) wait_count_warp(cnt_j, epoch * 32);
            TL(6, tid == 0);
            bar_sync(1, 256);
            const uint32_t kvs = sb + OFF_A + (j ^ 1) * SLOT;
            {
                const float4 a0 = ld_l2_f4(acc_j + ACC_KV + 4 * tid), a1 = ld_l2_f4(acc_j + ACC_KV + 4 * (tid + 256));
                const float zz = ld_l2_f(acc_j + ACC_Z + (tid & 127));
                sts64(kvs + (tid >> 2) * 48 + (tid & 3) * 8, pack_bf16(a0.x, a0.y), pack_bf16(a0.z, a0.w));
                sts64(kvs + ((tid >> 2) + 64) * 48 + (tid & 3) * 8, pack_bf16(a1.x, a1.y), pack_bf16(a1.z, a1.w));
                const uint32_t z2 = pack_bf16(zz, zz);
                sts64(kvs + (tid & 127) * 48 + 32 + w * 8, z2, z2);
            }
            bar_sync(1, 256);
            uint32_t o_lo[8], o_hi[8];
#pragma unroll
            for (int hh = 0; hh < 4; hh++) {
                uint32_t b[8], zb[4];
                const uint32_t base = kvs + hh * 32 * 48;
                ldsm4t(base + (lane & 15) * 48 + (lane >> 4) * 16, b[0], b[1], b[2], b[3]);
                ldsm4t(base + (16 + (lane & 15)) * 48 + (lane >> 4) * 16, b[4], b[5], b[6], b[7]);
                ldsm4t(base + lane * 48 + 32, zb[0], zb[1], zb[2], zb[3]);
                float n0[4], n1[4], dn[4], m0[4], m1[4], dm[4];
                mma16816_z(n0, fp + 4 * hh, b[0], b[1]); mma16816_z(n1, fp + 4 * hh, b[2], b[3]); mma16816_z(dn, fp + 4 * hh, zb[0], zb[1]);
                mma16816_z(m0, fm + 4 * hh, b[4], b[5]); mma16816_z(m1, fm + 4 * hh, b[6], b[7]); mma16816_z(dm, fm + 4 * hh, zb[2], zb[3]);
                const float* r = fr + 4 * hh;
                const float i0 = rcp(fmaf(dn[0], r[0], fmaf(dm[0], r[2], 1e-6f))), i1 = rcp(fmaf(dn[2], r[1], fmaf(dm[2], r[3], 1e-6f)));
                const float p0 = r[0] * i0, q0 = r[2] * i0, p1 = r[1] * i1, q1 = r[3] * i1;
                o_lo[2 * hh] = pack_bf16(fmaf(n0[0], p0, m0[0] * q0), fmaf(n0[1], p0, m0[1] * q0));
                o_hi[2 * hh] = pack_bf16(fmaf(n0[2], p1, m0[2] * q1), fmaf(n0[3], p1, m0[3] * q1));
                o_lo[2 * hh + 1] = pack_bf16(fmaf(n1[0], p0, m1[0] * q0), fmaf(n1[1], p0, m1[1] * q0));
                o_hi[2 * hh + 1] = pack_bf16(fmaf(n1[2], p1, m1[2] * q1), fmaf(n1[3], p1, m1[3] * q1));
            }
            store_tile(own_rows, g_o + (size_t)row_w * DM + 64 * j, o_lo, o_hi, lane);
            fence_async_smem();
            __syncwarp();
            mbar_arrive_if(pub + 8, l0);
            mbar_arrive_if(sb + BAR_EMPTYA + 8 * (j ^ (lane & 1)), lane < 2);
            TL(7, tid == 0);
        }
        {
            float acc[32];
#pragma unroll
            for (int t = 0; t < 8; t++) {
                acc[4 * t] = bf_lo(res_lo[t]); acc[4 * t + 1] = bf_hi(res_lo[t]);
                acc[4 * t + 2] = bf_lo(res_hi[t]); acc[4 * t + 3] = bf_hi(res_hi[t]);
            }
            fence_acc<32>(acc);
#pragma unroll 1
            for (int kp = 0; kp < 4; kp++) {
                mbar_waitc(sb + BAR_FULLB + 8 * rg.slot, rg.phase);
#pragma unroll
                for (int hf = 0; hf < 2; hf++) {
                    const int kt = 2 * kp + hf;
                    mbar_waitc(sb + BAR_FULLA + 8 * kt, 1);
                    TL(8, kt == 0 && tid == 0);
                    wg_fence();
#pragma unroll
                    for (int k = 0; k < 4; k++)
                        wgmma_n64(acc, dA + ((kt * SLOT + k * 32) >> 4), dB + ((rg.slot * SLOT + (hf * 4 + k) * 2048) >> 4), 1);
                    wg_commit();
                    wg_wait<1>();
                    mbar_arrive_if(sb + BAR_EMPTYA + 8 * ((kt + 7) & 7), l0 && kt > 0 && kt - 1 != j);
                    if (hf == 0) mbar_arrive_if(sb + BAR_EMPTYB + 8 * prev, l0 && kt > 0);
                }
                prev = rg.slot; rg.adv();
            }
            wg_wait<0>();
            fence_acc<32>(acc);
            mbar_arrive_if(sb + BAR_EMPTYA + 8 * 7, l0 && j != 7);
            mbar_arrive_if(sb + BAR_EMPTYB + 8 * prev, l0);
            TL(9, tid == 0);
            float s0 = 0.f, s1 = 0.f;
#pragma unroll
            for (int t = 0; t < 8; t++) {
                res_lo[t] = pack_bf16(acc[4 * t], acc[4 * t + 1]);
                res_hi[t] = pack_bf16(acc[4 * t + 2], acc[4 * t + 3]);
                s0 += acc[4 * t] + acc[4 * t + 1];
                s1 += acc[4 * t + 2] + acc[4 * t + 3];
            }
            store_tile(own_rows, g_h + (size_t)row_w * DM + 64 * j, res_lo, res_hi, lane);
            s0 += __shfl_xor_sync(0xffffffffu, s0, 1); s1 += __shfl_xor_sync(0xffffffffu, s1, 1);
            s0 += __shfl_xor_sync(0xffffffffu, s0, 2); s1 += __shfl_xor_sync(0xffffffffu, s1, 2);
            const float mu0 = s0 * (1.f / 64), mu1 = s1 * (1.f / 64);
            float q0 = 0.f, q1 = 0.f;
#pragma unroll
            for (int t = 0; t < 8; t++) {
                float d;
                d = acc[4 * t] - mu0; q0 = fmaf(d, d, q0);
                d = acc[4 * t + 1] - mu0; q0 = fmaf(d, d, q0);
                d = acc[4 * t + 2] - mu1; q1 = fmaf(d, d, q1);
                d = acc[4 * t + 3] - mu1; q1 = fmaf(d, d, q1);
            }
            q0 += __shfl_xor_sync(0xffffffffu, q0, 1); q1 += __shfl_xor_sync(0xffffffffu, q1, 1);
            q0 += __shfl_xor_sync(0xffffffffu, q0, 2); q1 += __shfl_xor_sync(0xffffffffu, q1, 2);
            stg_f2_if(g_hstat + (row_w + g + 8 * (q & 1)) * 16 + 2 * j, q ? mu1 : mu0, q ? q1 : q0, q < 2);
            fence_async_smem();
            __syncwarp();
            mbar_arrive_if(pub + 16, l0);
            mbar_arrive_if(sb + BAR_EMPTYA + 8 * j, l0);
            TL(10, tid == 0);
        }
        if (w == 1) {
#pragma unroll 1
            for (int kt = 0; kt < 8; kt++) mbar_waitc(sb + BAR_FULLA + 8 * kt, 0);
            const float* sp = g_hstat + (128 * m + (tid & 127)) * 16;
            float4 v[4];
#pragma unroll
            for (int i = 0; i < 4; i++) v[i] = ld_l2_f4(sp + 4 * i);
            float mean = 0.f;
#pragma unroll
            for (int i = 0; i < 4; i++) mean += v[i].x + v[i].z;
            mean *= 0.125f;
            float m2 = 0.f, dv = 0.f;
#pragma unroll
            for (int i = 0; i < 4; i++) {
                m2 += v[i].y + v[i].w;
                dv = fmaf(v[i].x - mean, v[i].x - mean, dv); dv = fmaf(v[i].z - mean, v[i].z - mean, dv);
            }
            sts_f2(sb + OFF_CS1 + (tid & 127) * 8, -mean, __fdividef(1.f, fmaf(dv, 64.f, m2) * (1.f / DM) + 1e-5f));
            mbar_arrive(sb + BAR_CS3);
        }
        {
            float acc0[64], acc1[64];
            const uint32_t dA0 = desc_lo(sb + OFF_A);
#pragma unroll 1
            for (int c = w; c < 3; c += 2) {
                if (c > 0) bar_sync(1 + c, 256);
                rg.slot = (c == 2) ? 0 : 2 + 2 * c; rg.phase = (c == 0);
#pragma unroll 1
                for (int kt = 0; kt < 8; kt++) {
                    mbar_waitc(sb + BAR_FULLA + 8 * kt, 0);
                    mbar_waitc(sb + BAR_FULLB + 8 * rg.slot, rg.phase);
                    TL(44 + c * 2 + (kt == 1), (tid & 127) == 0 && kt < 2);
                    wg_fence();
#pragma unroll
                    for (int k = 0; k < 4; k++) {
                        const uint32_t db = dB + ((rg.slot * SLOT + k * 2048) >> 4);
                        wgmma_n128(acc0, dA0 + ((kt * SLOT + k * 32) >> 4), db, (kt | k) != 0);
                        wgmma_n128(acc1, dA0 + ((kt * SLOT + 8192 + k * 32) >> 4), db, (kt | k) != 0);
                    }
                    wg_commit();
                    wg_wait<1>();
                    mbar_arrive_n_if(sb + BAR_EMPTYB + 8 * prev, 2, l0 && kt > 0);
                    mbar_arrive_if(sb + BAR_EMPTYA + 8 * ((kt + 7) & 7), l0 && kt > 0 && c > 0);
                    prev = rg.slot; rg.adv();
                }
                bar_arrive(2 + c, 256);
                mbar_waitc(sb + BAR_CS3, 0);
                float nm[4];
#pragma unroll
                for (int i = 0; i < 4; i++) nm[i] = lds_f2(sb + OFF_CS1 + (64 * (i >> 1) + 16 * wv + g + 8 * (i & 1)) * 8).x;
                wg_wait<0>();
                fence_acc<64>(acc0); fence_acc<64>(acc1);
                mbar_arrive_n_if(sb + BAR_EMPTYB + 8 * prev, 2, l0);
                mbar_arrive_if(sb + BAR_EMPTYA + 8 * 7, l0 && c > 0);
                TL(11 + c, (tid & 127) == 0);
                __nv_bfloat16* hp = g_hh + (size_t)(128 * m + 16 * wv + g) * FFP + 192 * j + 64 * c + (q & 1) * 8 + (q >> 1) * 4;
#pragma unroll
                for (int tp = 0; tp < 4; tp++) {
                    if (tp < 3 || c < 2) {
                        const uint32_t ca = sb + OFF_CS3 + (32 * c + 8 * tp + q) * 16;
                        const float4 c0 = lds_f4(ca), c1 = lds_f4(ca + 64);
                        store_pair(hp + 16 * tp, hh_pair(acc0 + 8 * tp, c0, nm[0]), hh_pair(acc0 + 8 * tp + 4, c1, nm[0]), q & 1);
                        store_pair(hp + 8 * FFP + 16 * tp, hh_pair(acc0 + 8 * tp + 2, c0, nm[1]), hh_pair(acc0 + 8 * tp + 6, c1, nm[1]), q & 1);
                        store_pair(hp + 64 * FFP + 16 * tp, hh_pair(acc1 + 8 * tp, c0, nm[2]), hh_pair(acc1 + 8 * tp + 4, c1, nm[2]), q & 1);
                        store_pair(hp + 72 * FFP + 16 * tp, hh_pair(acc1 + 8 * tp + 2, c0, nm[3]), hh_pair(acc1 + 8 * tp + 6, c1, nm[3]), q & 1);
                    }
                }
                __syncwarp();
                mbar_arrive_if(pub + 24 + 8 * c, l0);
                TL(54 + c, (tid & 127) == 0);
            }
            if (w == 1) bar_sync(4, 256);
        }
        {
            float acc[32];
            rg.slot = 2; rg.phase = 1;
#define KT_P4(T, HF, NK)                                                                                    \
    do {                                                                                                    \
        const int s_ = (T) & 7;                                                                             \
        if (!(HF)) mbar_waitc(sb + BAR_FULLB + 8 * rg.slot, rg.phase);                                       \
        mbar_waitc(sb + BAR_FULLA + 8 * s_, (((T) >> 3) + 1) & 1);                                           \
        if (!(HF)) TL(30 + (T) / 2, tid == 0);                                                              \
        wg_fence();                                                                                         \
        _Pragma("unroll") for (int k = 0; k < (NK); k++)                                                    \
            wgmma_n64(acc, dA + ((s_ * SLOT + k * 32) >> 4), dB + ((rg.slot * SLOT + (HF) * 8192 + k * 2048) >> 4), ((T) | k) != 0); \
        wg_commit();                                                                                        \
        wg_wait<1>();                                                                                       \
        mbar_arrive_if(sb + BAR_EMPTYA + 8 * (((T) + 7) & 7), l0 && (T) > 0);                               \
        if (!(HF)) mbar_arrive_if(sb + BAR_EMPTYB + 8 * prev, l0 && (T) > 0);                               \
        if (HF) { prev = rg.slot; rg.adv(); }                                                               \
    } while (0)
#pragma unroll 1
            for (int t = 0; t < 16; t += 2) { KT_P4(t, 0, 4); KT_P4(t + 1, 1, 4); }
            TL(14, tid == 0);
#pragma unroll 1
            for (int t = 16; t < 24; t += 2) { KT_P4(t, 0, 3); KT_P4(t + 1, 1, 3); }
            wg_wait<0>();
            fence_acc<32>(acc);
            TL(15, tid == 0);
            const float r0 = lds_f2(sb + OFF_CS1 + (16 * warp + g) * 8).y, r1 = lds_f2(sb + OFF_CS1 + (16 * warp + g + 8) * 8).y;
#pragma unroll
            for (int t = 0; t < 8; t++) {
                res_lo[t] = pack_bf16(fmaf(acc[4 * t], r0, bf_lo(res_lo[t])), fmaf(acc[4 * t + 1], r0, bf_hi(res_lo[t])));
                res_hi[t] = pack_bf16(fmaf(acc[4 * t + 2], r1, bf_lo(res_hi[t])), fmaf(acc[4 * t + 3], r1, bf_hi(res_hi[t])));
            }
            store_tile(own_rows, P.out + (size_t)row_w * DM + 64 * j, res_lo, res_hi, lane);
            if (tid == 0 && role == 0) g_epoch = epoch + 1;
            TL(16, tid == 0); TLG(1, tid == 0);
        }
    }
}

typedef CUresult (*EncodeFn)(CUtensorMap*, CUtensorMapDataType, cuuint32_t, void*, const cuuint64_t*, const cuuint64_t*,
                             const cuuint32_t*, const cuuint32_t*, CUtensorMapInterleave, CUtensorMapSwizzle,
                             CUtensorMapL2promotion, CUtensorMapFloatOOBfill);

static void make_map2d(EncodeFn enc, CUtensorMap* tm, const void* base, uint64_t cols, uint64_t rows, uint64_t pitch_elems,
                       uint32_t box_rows) {
    cuuint64_t gd[2] = {cols, rows};
    cuuint64_t gs[1] = {pitch_elems * 2};
    cuuint32_t bd[2] = {64, box_rows};
    cuuint32_t es[2] = {1, 1};
    enc(tm, CU_TENSOR_MAP_DATA_TYPE_BFLOAT16, 2, const_cast<void*>(base), gd, gs, bd, es, CU_TENSOR_MAP_INTERLEAVE_NONE,
        CU_TENSOR_MAP_SWIZZLE_128B, CU_TENSOR_MAP_L2_PROMOTION_L2_256B, CU_TENSOR_MAP_FLOAT_OOB_FILL_NONE);
}

}

extern "C" void kernel_launch(void* const* d_in, const int* in_sizes, int n_in, void* d_out, int out_size) {
    using namespace hk;
    (void)in_sizes; (void)n_in; (void)out_size;
    static EncodeFn enc = nullptr;
    static void *po = nullptr, *ph = nullptr, *phh = nullptr;
    static int std_layout = 0;
    if (!enc) {
        void* fn = nullptr;
        cudaDriverEntryPointQueryResult qr;
        cudaGetDriverEntryPoint("cuTensorMapEncodeTiled", &fn, cudaEnableDefault, &qr);
        enc = (EncodeFn)fn;
        cudaGetSymbolAddress(&po, g_o);
        cudaGetSymbolAddress(&ph, g_h);
        cudaGetSymbolAddress(&phh, g_hh);
        cudaFuncSetAttribute(fused_kernel, cudaFuncAttributeMaxDynamicSharedMemorySize, SMEM_BYTES);
        int dev = 0, sms = 0;
        cudaGetDevice(&dev);
        cudaDeviceGetAttribute(&sms, cudaDevAttrMultiProcessorCount, dev);
        cudaFuncSetAttribute(fused_kernel, cudaFuncAttributeNonPortableClusterSizeAllowed, 1);
        const int sizes[3] = {8, 9, 16}, want[3] = {15, 9, 7};
        bool ok = sms == NCTA;
        for (int i = 0; i < 3 && ok; i++) {
            cudaLaunchConfig_t cfg = {};
            cfg.gridDim = dim3(sizes[i] * 8); cfg.blockDim = dim3(NTHREADS); cfg.dynamicSmemBytes = SMEM_BYTES;
            cudaLaunchAttribute at;
            at.id = cudaLaunchAttributeClusterDimension;
            at.val.clusterDim.x = sizes[i]; at.val.clusterDim.y = 1; at.val.clusterDim.z = 1;
            cfg.attrs = &at; cfg.numAttrs = 1;
            int n = 0;
            ok = cudaOccupancyMaxActiveClusters(&n, fused_kernel, &cfg) == cudaSuccess && n == want[i];
        }
        (void)cudaGetLastError();
        std_layout = ok ? 1 : 0;
    }
    Params P;
    const __nv_bfloat16* x = (const __nv_bfloat16*)d_in[0];
    P.x = x;
    P.wqkv = (const __nv_bfloat16*)d_in[1];
    P.wphi = (const __nv_bfloat16*)d_in[2];
    P.wo = (const __nv_bfloat16*)d_in[3];
    P.wg = (const __nv_bfloat16*)d_in[5];
    P.wu = (const __nv_bfloat16*)d_in[6];
    P.wd = (const __nv_bfloat16*)d_in[7];
    P.out = (__nv_bfloat16*)d_out;
    P.use_smid = std_layout;
    for (int i = 0; i < NCTA; i++) {
        int role = i < 4 ? 128 + i : i - 4;
        if (std_layout) {
            const int tpc = i >> 1, odd = i & 1;
            if (tpc < 32) role = (tpc & 7) * 8 + (tpc >> 3) * 2 + odd;
            else if (tpc < 60) role = (8 + (tpc - 32) % 7) * 8 + ((tpc - 32) / 7) * 2 + odd;
            else if (tpc < 62) role = 128 + (tpc - 60) * 2 + odd;
            else role = 15 * 8 + (tpc - 62) * 2 + odd;
        }
        P.role[i] = (unsigned char)role;
    }
    make_map2d(enc, &P.tx, x, DM, SEQ, DM, 128);
    make_map2d(enc, &P.to, po, DM, SEQ, DM, 128);
    make_map2d(enc, &P.th, ph, DM, SEQ, DM, 128);
    make_map2d(enc, &P.thh, phh, FFP, SEQ, FFP, 128);
    make_map2d(enc, &P.twq, P.wqkv, 3 * DM, DM, 3 * DM, 128);
    make_map2d(enc, &P.two, P.wo, DM, DM, DM, 128);
    make_map2d(enc, &P.twg, P.wg, FF, DM, FF, 64);
    make_map2d(enc, &P.twu, P.wu, FF, DM, FF, 64);
    make_map2d(enc, &P.twd, P.wd, DM, FF, DM, 64);
    {
        cuuint64_t gd[3] = {(cuuint64_t)DM, (cuuint64_t)DM, 3};
        cuuint64_t gs[2] = {(cuuint64_t)3 * DM * 2, (cuuint64_t)DM * 2};
        cuuint32_t bd[3] = {64, 64, 2};
        cuuint32_t es[3] = {1, 1, 1};
        enc(&P.twkv, CU_TENSOR_MAP_DATA_TYPE_BFLOAT16, 3, const_cast<__nv_bfloat16*>(P.wqkv), gd, gs, bd, es,
            CU_TENSOR_MAP_INTERLEAVE_NONE, CU_TENSOR_MAP_SWIZZLE_128B, CU_TENSOR_MAP_L2_PROMOTION_L2_256B,
            CU_TENSOR_MAP_FLOAT_OOB_FILL_NONE);
    }
    fused_kernel<<<NCTA, NTHREADS, SMEM_BYTES>>>(P);
}
```

```cpp
#include <cuda_runtime.h>
#include <cuda_bf16.h>
#include <cuda.h>
#include <stdint.h>

namespace hk {

constexpr int SEQ = 2048, DM = 512, FF = 1376, FFP = 1536;
constexpr int NCTA = 132;
constexpr int NTHREADS = 384;
constexpr uint32_t SLOT = 16384;
constexpr uint32_t OFF_A = 0, OFF_B = 8 * SLOT, OFF_MISC = 14 * SLOT;
constexpr uint32_t BAR_FULLA = OFF_MISC + 0, BAR_EMPTYA = OFF_MISC + 64, BAR_FULLB = OFF_MISC + 128,
                   BAR_EMPTYB = OFF_MISC + 176, BAR_CS1 = OFF_MISC + 224, BAR_CS3 = OFF_MISC + 232,
                   BAR_PUB = OFF_MISC + 240,
                   BAR_CSQ = OFF_MISC + 336, BAR_CSV = OFF_MISC + 344;
constexpr uint32_t OFF_CS1 = OFF_MISC + 384;
constexpr uint32_t OFF_CS3 = OFF_CS1 + 1024;
constexpr uint32_t SMEM_BYTES = OFF_CS3 + 1536;
constexpr int NB = 6;
constexpr int AHEAD = 3;

constexpr int ACC_KV = 0, ACC_Z = 2048, ACC_SIZE = 2176;

__device__ __align__(1024) __nv_bfloat16 g_o[SEQ * DM];
__device__ __align__(1024) __nv_bfloat16 g_h[SEQ * DM];
__device__ __align__(1024) __nv_bfloat16 g_hh[SEQ * FFP];
__device__ __align__(128) float g_hstat[SEQ * 16];
__device__ __align__(128) unsigned long long g_xstat[SEQ * 2];
__device__ __align__(128) float g_acc[8 * ACC_SIZE];
__device__ __align__(128) unsigned g_cnt[8 * 32];
__device__ __align__(128) unsigned long long g_cs[8 * 6 * 128];
__device__ __align__(128) unsigned g_flag[16 * 8 * 8];
__device__ unsigned g_epoch = 1;

#define TL(i, pred) do {} while (0)
#define TLG(i, pred) do {} while (0)

struct Params {
    CUtensorMap tx, to, th, thh, twkv, twq, two, twg, twu, twd;
    const __nv_bfloat16 *x, *wqkv, *wphi, *wo, *wg, *wu, *wd;
    __nv_bfloat16* out;
    int use_smid;
    unsigned char role[NCTA];
};

__device__ __forceinline__ uint32_t smem_u32(const void* p) { return (uint32_t)__cvta_generic_to_shared(p); }
__device__ __forceinline__ void mbar_init(uint32_t bar, uint32_t cnt) {
    asm volatile("mbarrier.init.shared::cta.b64 [%0], %1;" ::"r"(bar), "r"(cnt) : "memory");
}
__device__ __forceinline__ void mbar_expect_tx(uint32_t bar, uint32_t bytes) {
    asm volatile("mbarrier.arrive.expect_tx.shared::cta.b64 _, [%0], %1;" ::"r"(bar), "r"(bytes) : "memory");
}
__device__ __forceinline__ void mbar_arrive(uint32_t bar) {
    asm volatile("mbarrier.arrive.shared::cta.b64 _, [%0];" ::"r"(bar) : "memory");
}
__device__ __forceinline__ void mbar_arrive_if(uint32_t bar, bool pred) {
    asm volatile("{.reg .pred p; setp.ne.u32 p, %1, 0; @p mbarrier.arrive.shared::cta.b64 _, [%0];}" ::"r"(bar), "r"((uint32_t)pred) : "memory");
}
__device__ __forceinline__ bool mbar_try(uint32_t bar, uint32_t parity) {
    uint32_t ok;
    asm volatile("{.reg .pred p; mbarrier.try_wait.parity.shared::cta.b64 p, [%1], %2; selp.u32 %0,1,0,p;}"
                 : "=r"(ok) : "r"(bar), "r"(parity) : "memory");
    return ok;
}
__device__ __forceinline__ bool mbar_test(uint32_t bar, uint32_t parity) {
    uint32_t ok;
    asm volatile("{.reg .pred p; mbarrier.test_wait.parity.shared::cta.b64 p, [%1], %2; selp.u32 %0,1,0,p;}"
                 : "=r"(ok) : "r"(bar), "r"(parity) : "memory");
    return ok;
}
__device__ __forceinline__ void trap_if_gt(uint32_t v, uint32_t lim) {
    asm volatile("{.reg .pred p; setp.gt.u32 p, %0, %1; @p trap;}" ::"r"(v), "r"(lim));
}
__device__ __forceinline__ void mbar_wait(uint32_t bar, uint32_t parity) {
    asm volatile("{\n"
                 ".reg .pred P1, P2;\n"
                 ".reg .u32 c;\n"
                 "mov.u32 c, 0;\n"
                 "LAB_WAIT:\n"
                 "mbarrier.try_wait.parity.shared::cta.b64 P1, [%0], %1;\n"
                 "@P1 bra LAB_DONE;\n"
                 "add.u32 c, c, 1;\n"
                 "setp.gt.u32 P2, c, 4194304;\n"
                 "@P2 trap;\n"
                 "bra LAB_WAIT;\n"
                 "LAB_DONE:\n"
                 "}" ::"r"(bar), "r"(parity) : "memory");
}
__device__ __forceinline__ void mbar_waitc(uint32_t bar, uint32_t parity) {
    asm volatile("{\n"
                 ".reg .pred P1;\n"
                 "LAB_WAIT:\n"
                 "mbarrier.try_wait.parity.shared::cta.b64 P1, [%0], %1;\n"
                 "@!P1 bra LAB_WAIT;\n"
                 "}" ::"r"(bar), "r"(parity) : "memory");
}
__device__ __forceinline__ void tma2d(uint32_t dst, const CUtensorMap* tm, uint32_t bar, int c0, int c1) {
    asm volatile("cp.async.bulk.tensor.2d.shared::cluster.global.mbarrier::complete_tx::bytes [%0], [%1, {%3, %4}], [%2];"
                 ::"r"(dst), "l"(tm), "r"(bar), "r"(c0), "r"(c1) : "memory");
}
__device__ __forceinline__ void tma3d(uint32_t dst, const CUtensorMap* tm, uint32_t bar, int c0, int c1, int c2) {
    asm volatile("cp.async.bulk.tensor.3d.shared::cluster.global.mbarrier::complete_tx::bytes [%0], [%1, {%3, %4, %5}], [%2];"
                 ::"r"(dst), "l"(tm), "r"(bar), "r"(c0), "r"(c1), "r"(c2) : "memory");
}
__device__ __forceinline__ bool elect_one() {
    uint32_t ok;
    asm volatile("{.reg .pred p; elect.sync _|p, 0xffffffff; selp.u32 %0, 1, 0, p;}" : "=r"(ok));
    return ok;
}
__device__ __forceinline__ void prefetch_tmap(const CUtensorMap* tm) {
    asm volatile("prefetch.tensormap [%0];" ::"l"(tm) : "memory");
}
__device__ __forceinline__ void prefetch_l2(const void* p, uint32_t bytes) {
    asm volatile("cp.async.bulk.prefetch.L2.global [%0], %1;" ::"l"(p), "r"(bytes) : "memory");
}
__device__ __forceinline__ unsigned ld_acquire(const unsigned* p) {
    unsigned v; asm volatile("ld.acquire.gpu.global.u32 %0, [%1];" : "=r"(v) : "l"(p) : "memory"); return v;
}
__device__ __forceinline__ uint4 ld_acquire4(const unsigned* p) {
    uint4 v;
    asm volatile("ld.acquire.gpu.global.v4.u32 {%0,%1,%2,%3}, [%4];" : "=r"(v.x), "=r"(v.y), "=r"(v.z), "=r"(v.w) : "l"(p) : "memory");
    return v;
}
__device__ __forceinline__ unsigned ld_relaxed(const unsigned* p) {
    unsigned v; asm volatile("ld.relaxed.gpu.global.u32 %0, [%1];" : "=r"(v) : "l"(p)); return v;
}
__device__ __forceinline__ void st_relaxed(unsigned* p, unsigned v) {
    asm volatile("st.relaxed.gpu.global.u32 [%0], %1;" ::"l"(p), "r"(v) : "memory");
}
__device__ __forceinline__ void red_relaxed(unsigned* p, unsigned v) {
    asm volatile("red.relaxed.gpu.global.add.u32 [%0], %1;" ::"l"(p), "r"(v) : "memory");
}
__device__ __forceinline__ void fence_gpu() { asm volatile("fence.acq_rel.gpu;" ::: "memory"); }
__device__ __forceinline__ void fence_async_smem() { asm volatile("fence.proxy.async.shared::cta;" ::: "memory"); }
__device__ __forceinline__ void fence_async_global() { asm volatile("fence.proxy.async.global;" ::: "memory"); }
__device__ __forceinline__ void wait_count(const unsigned* p, unsigned target) {
    uint32_t it = 0;
    while ((int)(ld_acquire(p) - target) < 0) trap_if_gt(++it, 1u << 22);
}
__device__ __forceinline__ void wait_count_warp(const unsigned* p, unsigned target) {
    uint32_t it = 0;
    while (__any_sync(0xffffffffu, (int)(ld_acquire(p) - target) < 0)) trap_if_gt(++it, 1u << 22);
}
__device__ __forceinline__ void red_f32(float* p, float a) {
    asm volatile("red.relaxed.gpu.global.add.f32 [%0], %1;" ::"l"(p), "f"(a) : "memory");
}
__device__ __forceinline__ void red_f32x2(float* p, float a, float b) {
    asm volatile("red.relaxed.gpu.global.add.v2.f32 [%0], {%1, %2};" ::"l"(p), "f"(a), "f"(b) : "memory");
}
__device__ __forceinline__ void red_f32x4(float* p, float a, float b, float c, float d) {
    asm volatile("red.relaxed.gpu.global.add.v4.f32 [%0], {%1, %2, %3, %4};" ::"l"(p), "f"(a), "f"(b), "f"(c), "f"(d) : "memory");
}
__device__ __forceinline__ float4 ld_l2_f4(const float* p) {
    float4 v;
    asm volatile("ld.relaxed.gpu.global.v4.f32 {%0,%1,%2,%3}, [%4];" : "=f"(v.x), "=f"(v.y), "=f"(v.z), "=f"(v.w) : "l"(p) : "memory");
    return v;
}
__device__ __forceinline__ float2 ld_l2_f2(const float* p) {
    float2 v;
    asm volatile("ld.relaxed.gpu.global.v2.f32 {%0,%1}, [%2];" : "=f"(v.x), "=f"(v.y) : "l"(p) : "memory");
    return v;
}
__device__ __forceinline__ float ld_l2_f(const float* p) {
    float v;
    asm volatile("ld.relaxed.gpu.global.f32 %0, [%1];" : "=f"(v) : "l"(p) : "memory");
    return v;
}
__device__ __forceinline__ uint4 ldg_nc(const void* p) {
    uint4 v;
    asm volatile("ld.global.nc.L1::no_allocate.v4.u32 {%0,%1,%2,%3}, [%4];" : "=r"(v.x), "=r"(v.y), "=r"(v.z), "=r"(v.w) : "l"(p));
    return v;
}
__device__ __forceinline__ void stg128(void* p, uint32_t a, uint32_t b, uint32_t c, uint32_t d) {
    asm volatile("st.global.v4.u32 [%0], {%1,%2,%3,%4};" ::"l"(p), "r"(a), "r"(b), "r"(c), "r"(d) : "memory");
}
__device__ __forceinline__ uint4 lds128(uint32_t a) {
    uint4 v;
    asm volatile("ld.shared.v4.u32 {%0,%1,%2,%3}, [%4];" : "=r"(v.x), "=r"(v.y), "=r"(v.z), "=r"(v.w) : "r"(a) : "memory");
    return v;
}
__device__ __forceinline__ float2 lds_f2(uint32_t a) {
    float2 v;
    asm volatile("ld.shared.v2.f32 {%0,%1}, [%2];" : "=f"(v.x), "=f"(v.y) : "r"(a) : "memory");
    return v;
}
__device__ __forceinline__ void sts_f2(uint32_t a, float x, float y) {
    asm volatile("st.shared.v2.f32 [%0], {%1,%2};" ::"r"(a), "f"(x), "f"(y) : "memory");
}
__device__ __forceinline__ void sts64(uint32_t a, uint32_t x, uint32_t y) {
    asm volatile("st.shared.v2.u32 [%0], {%1,%2};" ::"r"(a), "r"(x), "r"(y) : "memory");
}
__device__ __forceinline__ void sts128(uint32_t a, uint32_t x, uint32_t y, uint32_t z, uint32_t w) {
    asm volatile("st.shared.v4.u32 [%0], {%1,%2,%3,%4};" ::"r"(a), "r"(x), "r"(y), "r"(z), "r"(w) : "memory");
}
__device__ __forceinline__ void stsm4(uint32_t a, uint32_t r0, uint32_t r1, uint32_t r2, uint32_t r3) {
    asm volatile("stmatrix.sync.aligned.m8n8.x4.shared.b16 [%0], {%1,%2,%3,%4};" ::"r"(a), "r"(r0), "r"(r1), "r"(r2), "r"(r3) : "memory");
}
__device__ __forceinline__ void ldsm4(uint32_t a, uint32_t& r0, uint32_t& r1, uint32_t& r2, uint32_t& r3) {
    asm volatile("ldmatrix.sync.aligned.m8n8.x4.shared.b16 {%0,%1,%2,%3}, [%4];" : "=r"(r0), "=r"(r1), "=r"(r2), "=r"(r3) : "r"(a) : "memory");
}
__device__ __forceinline__ void ldsm4t(uint32_t a, uint32_t& r0, uint32_t& r1, uint32_t& r2, uint32_t& r3) {
    asm volatile("ldmatrix.sync.aligned.m8n8.x4.trans.shared.b16 {%0,%1,%2,%3}, [%4];" : "=r"(r0), "=r"(r1), "=r"(r2), "=r"(r3) : "r"(a) : "memory");
}
__device__ __forceinline__ void mma16816(float* c, const uint32_t* a, uint32_t b0, uint32_t b1) {
    asm("mma.sync.aligned.m16n8k16.row.col.f32.bf16.bf16.f32 {%0,%1,%2,%3}, {%4,%5,%6,%7}, {%8,%9}, {%0,%1,%2,%3};"
                 : "+f"(c[0]), "+f"(c[1]), "+f"(c[2]), "+f"(c[3])
                 : "r"(a[0]), "r"(a[1]), "r"(a[2]), "r"(a[3]), "r"(b0), "r"(b1));
}
__device__ __forceinline__ uint32_t pack_bf16(float lo, float hi) {
    uint32_t r; asm("cvt.rn.bf16x2.f32 %0, %1, %2;" : "=r"(r) : "f"(hi), "f"(lo)); return r;
}
__device__ __forceinline__ float bf_lo(uint32_t w) { return __uint_as_float(w << 16); }
__device__ __forceinline__ float bf_hi(uint32_t w) { return __uint_as_float(w & 0xffff0000u); }
__device__ __forceinline__ float ex2(float x) { float r; asm("ex2.approx.ftz.f32 %0, %1;" : "=f"(r) : "f"(x)); return r; }
__device__ __forceinline__ float rcp(float x) { float r; asm("rcp.approx.ftz.f32 %0, %1;" : "=f"(r) : "f"(x)); return r; }
__device__ __forceinline__ void bar_sync(int id, int n) { asm volatile("bar.sync %0, %1;" ::"r"(id), "r"(n) : "memory"); }

__device__ __forceinline__ uint32_t desc_lo(uint32_t addr) { return ((addr & 0x3FFFF) >> 4) | (512u << 16); }
#define DESC_HI "0x40000040"
__device__ __forceinline__ void wg_fence() { asm volatile("wgmma.fence.sync.aligned;" ::: "memory"); }
__device__ __forceinline__ void wg_commit() { asm volatile("wgmma.commit_group.sync.aligned;" ::: "memory"); }
template <int N> __device__ __forceinline__ void wg_wait() { asm volatile("wgmma.wait_group.sync.aligned %0;" ::"n"(N) : "memory"); }
template <int N> __device__ __forceinline__ void fence_acc(float* d) {
#pragma unroll
    for (int i = 0; i < N; i++) asm volatile("" : "+f"(d[i])::"memory");
}
#define R4(o) "+f"(d[o + 0]), "+f"(d[o + 1]), "+f"(d[o + 2]), "+f"(d[o + 3])
#define R8(o) R4(o), R4(o + 4)
__device__ __forceinline__ void wgmma_n128(float* d, uint32_t da, uint32_t db, int sc) {
    asm volatile("{.reg .pred p; .reg .b64 da, db; setp.ne.b32 p, %66, 0; mov.b64 da, {%64, " DESC_HI "}; mov.b64 db, {%65, " DESC_HI "};\n"
                 "wgmma.mma_async.sync.aligned.m64n128k16.f32.bf16.bf16 {%0,%1,%2,%3,%4,%5,%6,%7,%8,%9,%10,%11,%12,%13,%14,%15,%16,%17,%18,%19,%20,%21,%22,%23,%24,%25,%26,%27,%28,%29,%30,%31,"
                 "%32,%33,%34,%35,%36,%37,%38,%39,%40,%41,%42,%43,%44,%45,%46,%47,%48,%49,%50,%51,%52,%53,%54,%55,%56,%57,%58,%59,%60,%61,%62,%63}, da, db, p, 1, 1, 0, 1;}"
                 : R8(0), R8(8), R8(16), R8(24), R8(32), R8(40), R8(48), R8(56)
                 : "r"(da), "r"(db), "r"(sc));
}
__device__ __forceinline__ void wgmma_n64(float* d, uint32_t da, uint32_t db, int sc) {
    asm volatile("{.reg .pred p; .reg .b64 da, db; setp.ne.b32 p, %34, 0; mov.b64 da, {%32, " DESC_HI "}; mov.b64 db, {%33, " DESC_HI "};\n"
                 "wgmma.mma_async.sync.aligned.m64n64k16.f32.bf16.bf16 {%0,%1,%2,%3,%4,%5,%6,%7,%8,%9,%10,%11,%12,%13,%14,%15,%16,%17,%18,%19,%20,%21,%22,%23,%24,%25,%26,%27,%28,%29,%30,%31}, da, db, p, 1, 1, 0, 1;}"
                 : R8(0), R8(8), R8(16), R8(24)
                 : "r"(da), "r"(db), "r"(sc));
}
__device__ __forceinline__ void wgmma_n40_tt(float* d, uint32_t da, uint32_t db, int sc) {
    asm volatile("{.reg .pred p; .reg .b64 da, db; setp.ne.b32 p, %22, 0; mov.b64 da, {%20, " DESC_HI "}; mov.b64 db, {%21, " DESC_HI "};\n"
                 "wgmma.mma_async.sync.aligned.m64n40k16.f32.bf16.bf16 {%0,%1,%2,%3,%4,%5,%6,%7,%8,%9,%10,%11,%12,%13,%14,%15,%16,%17,%18,%19}, da, db, p, 1, 1, 1, 1;}"
                 : R8(0), R8(8), R4(16)
                 : "r"(da), "r"(db), "r"(sc));
}

__device__ __forceinline__ void wgmma_n8_tt(float* d, uint32_t da, uint32_t db, int sc) {
    asm volatile("{.reg .pred p; .reg .b64 da, db; setp.ne.b32 p, %6, 0; mov.b64 da, {%4, " DESC_HI "}; mov.b64 db, {%5, " DESC_HI "};\n"
                 "wgmma.mma_async.sync.aligned.m64n8k16.f32.bf16.bf16 {%0,%1,%2,%3}, da, db, p, 1, 1, 1, 1;}"
                 : R4(0)
                 : "r"(da), "r"(db), "r"(sc));
}

__device__ __forceinline__ void red_f32_if(float* p, float a, bool pred) {
    asm volatile("{.reg .pred p; setp.ne.u32 p, %2, 0; @p red.relaxed.gpu.global.add.f32 [%0], %1;}" ::"l"(p), "f"(a), "r"((uint32_t)pred) : "memory");
}
__device__ __forceinline__ void stg_f2_if(float* p, float a, float b, bool pred) {
    asm volatile("{.reg .pred p; setp.ne.u32 p, %3, 0; @p st.global.v2.f32 [%0], {%1,%2};}" ::"l"(p), "f"(a), "f"(b), "r"((uint32_t)pred) : "memory");
}
__device__ __forceinline__ void stg64(void* p, uint32_t a, uint32_t b) {
    asm volatile("st.global.v2.u32 [%0], {%1,%2};" ::"l"(p), "r"(a), "r"(b) : "memory");
}
__device__ __forceinline__ void store_pair(__nv_bfloat16* p, uint32_t r0, uint32_t r1, bool odd) {
    const uint32_t x = __shfl_xor_sync(0xffffffffu, odd ? r0 : r1, 1);
    stg64(p, odd ? x : r0, odd ? r1 : x);
}
__device__ __forceinline__ void mma16816_z(float* c, const uint32_t* a, uint32_t b0, uint32_t b1) {
    asm("mma.sync.aligned.m16n8k16.row.col.f32.bf16.bf16.f32 {%0,%1,%2,%3}, {%4,%5,%6,%7}, {%8,%9}, {%10,%10,%10,%10};"
                 : "=f"(c[0]), "=f"(c[1]), "=f"(c[2]), "=f"(c[3])
                 : "r"(a[0]), "r"(a[1]), "r"(a[2]), "r"(a[3]), "r"(b0), "r"(b1), "f"(0.f));
}
__device__ __forceinline__ uint32_t max2(uint32_t a, uint32_t b) { uint32_t r; asm("max.bf16x2 %0, %1, %2;" : "=r"(r) : "r"(a), "r"(b)); return r; }
__device__ __forceinline__ uint32_t min2(uint32_t a, uint32_t b) { uint32_t r; asm("min.bf16x2 %0, %1, %2;" : "=r"(r) : "r"(a), "r"(b)); return r; }
__device__ __forceinline__ void bar_arrive(int id, int n) { asm volatile("bar.arrive %0, %1;" ::"r"(id), "r"(n) : "memory"); }
__device__ __forceinline__ void mbar_arrive_n_if(uint32_t bar, uint32_t n, bool pred) {
    asm volatile("{.reg .pred p; setp.ne.u32 p, %1, 0; @p mbarrier.arrive.shared::cta.b64 _, [%0], %2;}" ::"r"(bar), "r"((uint32_t)pred), "r"(n) : "memory");
}
__device__ __forceinline__ float4 lds_f4(uint32_t a) {
    float4 v;
    asm volatile("ld.shared.v4.f32 {%0,%1,%2,%3}, [%4];" : "=f"(v.x), "=f"(v.y), "=f"(v.z), "=f"(v.w) : "r"(a) : "memory");
    return v;
}
__device__ __forceinline__ uint4 ld_tagged(const unsigned long long* p) {
    unsigned long long a, b;
    asm volatile("ld.acquire.gpu.global.v2.b64 {%0,%1}, [%2];" : "=l"(a), "=l"(b) : "l"(p) : "memory");
    return make_uint4((unsigned)a, (unsigned)(a >> 32), (unsigned)b, (unsigned)(b >> 32));
}
__device__ __forceinline__ uint4 ld_tagged_rlx(const unsigned long long* p) {
    unsigned long long a, b;
    asm volatile("ld.relaxed.gpu.global.v2.b64 {%0,%1}, [%2];" : "=l"(a), "=l"(b) : "l"(p) : "memory");
    return make_uint4((unsigned)a, (unsigned)(a >> 32), (unsigned)b, (unsigned)(b >> 32));
}
__device__ __forceinline__ void st_tagged_if(unsigned long long* p, float a, float b, unsigned tag, bool pred) {
    const unsigned long long t = (unsigned long long)tag << 32;
    asm volatile("{.reg .pred p; setp.ne.u32 p, %3, 0; @p st.relaxed.gpu.global.v2.b64 [%0], {%1,%2};}"
                 ::"l"(p), "l"(t | __float_as_uint(a)), "l"(t | __float_as_uint(b)), "r"((uint32_t)pred) : "memory");
}

__device__ __forceinline__ void store_tile(uint32_t tile_rows, __nv_bfloat16* gdst, const uint32_t* lo, const uint32_t* hi, int lane) {
    const int r = lane & 15;
#pragma unroll
    for (int b = 0; b < 4; b++)
        stsm4(tile_rows + r * 128 + (((2 * b + (lane >> 4)) ^ (r & 7)) << 4), lo[2 * b], hi[2 * b], lo[2 * b + 1], hi[2 * b + 1]);
    __syncwarp();
#pragma unroll
    for (int i = 0; i < 4; i++) {
        const int rr = 4 * i + (lane >> 3);
        const uint4 v = lds128(tile_rows + rr * 128 + (((lane & 7) ^ (rr & 7)) << 4));
        stg128(gdst + rr * DM + (lane & 7) * 8, v.x, v.y, v.z, v.w);
    }
}

template <bool NORM>
__device__ __forceinline__ void feature_map(const uint32_t* a, const uint32_t* wb, float c0, float c1, uint32_t* plus, uint32_t* minus, float* rs) {
    float p[8];
    mma16816_z(p, a, wb[0], wb[1]);
    mma16816_z(p + 4, a, wb[2], wb[3]);
    const uint32_t P0 = pack_bf16(p[0], p[2]), P1 = pack_bf16(p[1], p[3]), P2 = pack_bf16(p[4], p[6]), P3 = pack_bf16(p[5], p[7]);
    uint32_t mx = max2(max2(P0, P1), max2(P2, P3)), mn = min2(min2(P0, P1), min2(P2, P3));
#pragma unroll
    for (int s = 1; s <= 2; s <<= 1) {
        mx = max2(mx, __shfl_xor_sync(0xffffffffu, mx, s));
        mn = min2(mn, __shfl_xor_sync(0xffffffffu, mn, s));
    }
    const float mx0 = bf_lo(mx) * c0, mx1 = bf_hi(mx) * c1, mn0 = bf_lo(mn) * c0, mn1 = bf_hi(mn) * c1;
    p[0] = bf_lo(P0); p[2] = bf_hi(P0); p[1] = bf_lo(P1); p[3] = bf_hi(P1);
    p[4] = bf_lo(P2); p[6] = bf_hi(P2); p[5] = bf_lo(P3); p[7] = bf_hi(P3);
    float ep[8], em[8];
#pragma unroll
    for (int i = 0; i < 8; i++) {
        const bool r1 = (i & 2);
        ep[i] = ex2(fmaf(p[i], r1 ? c1 : c0, r1 ? -mx1 : -mx0));
        em[i] = ex2(fmaf(p[i], r1 ? -c1 : -c0, r1 ? mn1 : mn0));
    }
    float sp[4], sm[4];
#pragma unroll
    for (int i = 0; i < 4; i++) { plus[i] = pack_bf16(ep[2 * i], ep[2 * i + 1]); minus[i] = pack_bf16(em[2 * i], em[2 * i + 1]); }
    mma16816_z(sp, plus, 0x3f803f80u, 0x3f803f80u);
    mma16816_z(sm, minus, 0x3f803f80u, 0x3f803f80u);
    rs[0] = rcp(sp[0]); rs[1] = rcp(sp[2]); rs[2] = rcp(sm[0]); rs[3] = rcp(sm[2]);
    if (NORM) {
#pragma unroll
        for (int i = 0; i < 4; i++) {
            plus[i] = pack_bf16(ep[2 * i] * rs[i & 1], ep[2 * i + 1] * rs[i & 1]);
            minus[i] = pack_bf16(em[2 * i] * rs[2 + (i & 1)], em[2 * i + 1] * rs[2 + (i & 1)]);
        }
    }
}

template <bool SCALE>
__device__ __forceinline__ void ln_frag(const float* acc, uint32_t cs_addr, float rs0, float nm0, float rs1, float nm1, uint32_t* a) {
    const float2 c0 = lds_f2(cs_addr), c1 = lds_f2(cs_addr + 32);
    const float s0 = SCALE ? rs0 : 1.f, s1 = SCALE ? rs1 : 1.f;
    a[0] = pack_bf16(fmaf(nm0, c0.x, acc[0]) * s0, fmaf(nm0, c0.y, acc[1]) * s0);
    a[1] = pack_bf16(fmaf(nm1, c0.x, acc[2]) * s1, fmaf(nm1, c0.y, acc[3]) * s1);
    a[2] = pack_bf16(fmaf(nm0, c1.x, acc[4]) * s0, fmaf(nm0, c1.y, acc[5]) * s0);
    a[3] = pack_bf16(fmaf(nm1, c1.x, acc[6]) * s1, fmaf(nm1, c1.y, acc[7]) * s1);
}

__device__ __forceinline__ uint32_t hh_pair(const float* ag, float4 cs, float nmean) {
    const float g0 = fmaf(nmean, cs.x, ag[0]), g1 = fmaf(nmean, cs.y, ag[1]);
    const float u0 = fmaf(nmean, cs.z, ag[32]), u1 = fmaf(nmean, cs.w, ag[33]);
    return pack_bf16(g0 * u0, g1 * u1);
}

struct Ring {
    int slot; uint32_t phase;
    __device__ __forceinline__ void adv() { if (++slot == NB) { slot = 0; phase ^= 1; } }
};

__global__ void __launch_bounds__(NTHREADS, 1) fused_kernel(const __grid_constant__ Params P) {
    extern __shared__ __align__(1024) uint8_t smem_raw[];
    const uint32_t sb = smem_u32(smem_raw);
    const int tid = threadIdx.x, lane = tid & 31;
    const int warp = __shfl_sync(0xffffffffu, tid >> 5, 0);
    unsigned role = blockIdx.x;
    if (P.use_smid) asm volatile("mov.u32 %0, %%smid;" : "=r"(role));
    role = P.role[role];
    const int m = role >> 3, j = role & 7;
    const bool helper = role >= 128;

    TL(0, tid == 0); TLG(0, tid == 0);
    float* const acc_j = g_acc + j * ACC_SIZE;
    unsigned* const cnt_j = g_cnt + j * 32;

    if (__builtin_expect(warp >= 8, 1)) {
        asm volatile("setmaxnreg.dec.sync.aligned.u32 72;");
        if (elect_one()) {
            if (warp == 8) {
                if (!helper) {
#pragma unroll
                    for (int i = 0; i < NB; i++) mbar_init(sb + BAR_FULLB + 8 * i, 1);
#pragma unroll
                    for (int i = 0; i < 2; i++) {
                        mbar_expect_tx(sb + BAR_FULLB + 8 * i, SLOT);
                        tma3d(sb + OFF_B + i * SLOT, &P.twkv, sb + BAR_FULLB + 8 * i, 64 * j, 64 * i, 1);
                    }
                }
            } else if (warp == 9) {
#pragma unroll
                for (int i = 0; i < 8; i++) mbar_init(sb + BAR_FULLA + 8 * i, 1);
#pragma unroll
                for (int i = 0; i < 2; i++) {
                    mbar_expect_tx(sb + BAR_FULLA + 8 * i, SLOT);
                    tma2d(sb + OFF_A + i * SLOT, helper ? &P.twq : &P.tx, sb + BAR_FULLA + 8 * i, helper ? DM + 128 * j : 64 * i, 128 * (helper ? i : m));
                }
            } else if (warp == 10) {
#pragma unroll
                for (int i = 0; i < 16; i++) mbar_init(sb + BAR_CS1 + 8 * i, i == 1 ? 160 : ((i == 0 || i >= 14) ? 32 : 4));
                trap_if_gt(sb & 1023, 0);
            } else {
#pragma unroll
                for (int i = 0; i < 14; i++) mbar_init(sb + (i < 8 ? BAR_EMPTYA : BAR_EMPTYB - 64) + 8 * i, 8);
            }
        }
        __syncwarp();
        const unsigned epoch = ld_relaxed(&g_epoch);
        bar_sync(0, NTHREADS);
        if (helper) {
            if (warp == 8) {
                if (elect_one()) {
#pragma unroll 1
                    for (int i = 2; i < 72; i++) {
                        const uint32_t full = sb + BAR_FULLA + 8 * (i & 7), dst = sb + OFF_A + (i & 7) * SLOT;
                        mbar_wait(sb + BAR_EMPTYA + 8 * (i & 7), ((i >> 3) & 1) ^ 1);
                        mbar_expect_tx(full, SLOT);
                        if (i < 24) {
                            tma2d(dst, &P.twq, full, (i < 16 ? DM + 64 * (i & 8) : 0) + 128 * j + 16 * (i & 4), 128 * (i & 3));
                        } else {
                            const int u = (i >> 3) - 3, c0 = 176 * (2 * j + (u & 1)) + 64 * (u >> 1);
                            tma2d(dst, &P.twg, full, c0, 64 * (i & 7));
                            tma2d(dst + 8192, &P.twu, full, c0, 64 * (i & 7));
                        }
                    }
                    prefetch_l2(P.wd + (size_t)j * 176128, 352256);
                }
            } else if (warp == 9) {
                wait_count_warp(g_cnt + (lane & 7) * 32, epoch * 32);
            }
            return;
        }
        if (warp == 8) {
            if (elect_one()) {
                if (m >= 3 && m < 8)
                    asm volatile("cp.async.bulk.prefetch.tensor.3d.L2.global [%0, {%1, %2, %3}];" ::"l"(&P.twkv), "r"(64 * j), "r"(64 * m), "r"(1) : "memory");
                if (j >= 3)
                    asm volatile("cp.async.bulk.prefetch.tensor.2d.L2.global [%0, {%1, %2}];" ::"l"(&P.tx), "r"(64 * j), "r"(128 * m) : "memory");
                Ring r{2, 0};
#pragma unroll 1
                for (int i = 2; i < 56; i++) {
                    const uint32_t full = sb + BAR_FULLB + 8 * r.slot, dst = sb + OFF_B + r.slot * SLOT;
                    mbar_wait(sb + BAR_EMPTYB + 8 * r.slot, r.phase ^ 1);
                    if (i >= 8 && i < 12) {
                        mbar_arrive(full);
                    } else {
                        if (i >= AHEAD && i < 6) mbar_wait(full - 8 * AHEAD, 0);
                        mbar_expect_tx(full, SLOT);
                        if (i < 8) {
                            tma3d(dst, &P.twkv, full, 64 * j, 64 * i, 1);
                        } else if (i < 20) {
                            tma2d(dst, i < 16 ? &P.twq : &P.two, full, 64 * j, 128 * (i & 3));
                        } else if (i < 44) {
                            const int c = (i - 20) >> 3, kt = (i - 20) & 7;
                            tma2d(dst, &P.twg, full, 176 * j + 64 * c, 64 * kt);
                            tma2d(dst + 8192, &P.twu, full, 176 * j + 64 * c, 64 * kt);
                        } else {
                            const int c = (i - 44) >> 2, jj = (i & 3) * 2;
                            tma2d(dst, &P.twd, full, 64 * j, 176 * jj + 64 * c);
                            tma2d(dst + 8192, &P.twd, full, 64 * j, 176 * (jj + 1) + 64 * c);
                        }
                    }
                    r.adv();
                }
            }
            return;
        }
        if (warp == 9) {
            if (elect_one()) {
#pragma unroll 1
                for (int i = 2; i < 8; i++) {
                    if (i >= AHEAD + 1) mbar_wait(sb + BAR_FULLA + 8 * (i - AHEAD - 1), 0);
                    mbar_expect_tx(sb + BAR_FULLA + 8 * i, SLOT);
                    tma2d(sb + OFF_A + i * SLOT, &P.tx, sb + BAR_FULLA + 8 * i, 64 * i, 128 * m);
                }
#pragma unroll 1
                for (int i = 1; i < 10; i++) prefetch_tmap(&P.tx + i);
            }
            __syncwarp();
        }
        if (warp >= 10) {
            const int row = 16 * j + 8 * (warp - 10) + (lane >> 2);
            const uint32_t ra = sb + OFF_A + row * 128;
            float sh = 0.f, s0 = 0.f, s1 = 0.f, q0 = 0.f, q1 = 0.f;
#pragma unroll 1
            for (int kt = 0; kt < 8; kt++) {
                mbar_wait(sb + BAR_FULLA + 8 * kt, 0);
                if (kt == 0) sh = bf_lo(lds128(ra + ((row & 7) << 4)).x);
#pragma unroll
                for (int i = 0; i < 2; i++) {
                    const uint4 v = lds128(ra + kt * SLOT + (((2 * (lane & 3) + i) ^ (row & 7)) << 4));
                    const uint32_t ww[4] = {v.x, v.y, v.z, v.w};
#pragma unroll
                    for (int e = 0; e < 4; e++) {
                        const float d0 = bf_lo(ww[e]) - sh, d1 = bf_hi(ww[e]) - sh;
                        s0 += d0; q0 = fmaf(d0, d0, q0);
                        s1 += d1; q1 = fmaf(d1, d1, q1);
                    }
                }
            }
            s0 += s1; q0 += q1;
#pragma unroll
            for (int o = 1; o <= 2; o <<= 1) { s0 += __shfl_xor_sync(0xffffffffu, s0, o); q0 += __shfl_xor_sync(0xffffffffu, q0, o); }
            const float md = s0 * (1.f / DM);
            const float rs = rsqrtf(fmaxf(q0 * (1.f / DM) - md * md, 0.f) + 1e-5f);
            st_tagged_if(g_xstat + 2 * (128 * m + row), rs, -(sh + md), epoch, (lane & 3) == 0);
        }
        const unsigned long long* cs = g_cs + j * 768 + 2 * lane;
        {
            uint4 v;
            uint32_t it = 0;
            while (true) {
                v = ld_tagged(cs + (warp == 9 ? 256 : 128 * (warp - 10)));
                if (!__any_sync(0xffffffffu, v.y != epoch || v.w != epoch)) break;
                __nanosleep(100);
                trap_if_gt(++it, 1u << 22);
            }
            sts64(sb + OFF_CS1 + 256 * (warp - 9) + 8 * lane, v.x, v.z);
            mbar_arrive(sb + (warp == 9 ? BAR_CSQ : (warp == 10 ? BAR_CS1 : BAR_CSV)));
        }
        if (warp == 9) {
#pragma unroll 1
            for (int r = 1; r < 6; r++) {
                const CUtensorMap* tm = r == 1 ? &P.to : (r == 2 ? &P.th : &P.thh);
                const unsigned* fp = g_flag + (m * 8 + ((lane >> 1) & 7)) * 8 + (r < 3 ? 2 * r - 2 + (lane & 1) : r + 1);
                uint32_t ready = r < 3 ? 3u << (2 * j) : 0u, it = 0;
#pragma unroll 1
                for (int i = 0; i < 8; i++) {
                    while (((ready >> (2 * i)) & 3) != 3) {
                        ready |= __ballot_sync(0xffffffffu, ld_acquire(fp) == epoch);
                        trap_if_gt(++it, 1u << 22);
                    }
                    const uint32_t full = sb + BAR_FULLA + 8 * i;
                    mbar_wait(sb + BAR_EMPTYA + 8 * i, (r - 1) & 1);
                    if (elect_one()) {
                        if (r < 3 && i == j) {
                            mbar_arrive(full);
                        } else {
                            fence_async_global();
                            mbar_expect_tx(full, SLOT);
                            tma2d(sb + OFF_A + i * SLOT, tm, full, r < 3 ? 64 * i : 192 * i + 64 * (r - 3), 128 * m);
                        }
                    }
                    __syncwarp();
                }
            }
        } else {
            const int a = warp - 10;
#pragma unroll 1
            for (int ev = 0; ev < 6; ev += (ev >= 2 + a) ? 2 - (ev == 2) : 1 + (ev == 2)) {
                if (lane == 0) {
                    mbar_wait(sb + BAR_PUB + 8 * (a * 6 + ev), 0);
                    fence_gpu();
                    if (ev == 0) red_relaxed(cnt_j, 1);
                    else st_relaxed(g_flag + role * 8 + (ev < 3 ? 2 * ev - 2 + a : ev + 1), epoch);
                }
                __syncwarp();
                if (ev == 2 && a == 0) {
#pragma unroll 1
                    for (int c = 0; c < 3; c++) {
                        uint4 vg, vu;
                        uint32_t it = 0;
                        do {
                            vg = ld_tagged_rlx(cs + 384 + 128 * c); vu = ld_tagged_rlx(cs + 448 + 128 * c);
                            trap_if_gt(++it, 1u << 22);
                        } while (__any_sync(0xffffffffu, vg.y != epoch || vg.w != epoch || vu.y != epoch || vu.w != epoch));
                        sts128(sb + OFF_CS3 + (32 * c + lane) * 16, vg.x, vg.z, vu.x, vu.z);
                    }
                    mbar_arrive(sb + BAR_CS3);
                }
            }
        }
        return;
    }
    const unsigned epoch = ld_relaxed(&g_epoch);
    uint32_t wraw[16];
    if (!helper) {
        const uint32_t* wp = reinterpret_cast<const uint32_t*>(P.wphi) + (4 * j) * 128 + (lane & 3) * 16 + (lane >> 2);
#pragma unroll
        for (int i = 0; i < 16; i++)
            asm volatile("ld.global.nc.u32 %0, [%1];" : "=r"(wraw[i]) : "l"(wp + (i >> 2) * 128 + ((i >> 1) & 1) * 64 + (i & 1) * 8));
    }
    asm volatile("setmaxnreg.inc.sync.aligned.u32 216;");
    bar_sync(0, NTHREADS);
    if (helper) {
        if (warp < 4) {
            sts128(sb + OFF_B + 16 * tid, 0x3f803f80u, 0x3f803f80u, 0x3f803f80u, 0x3f803f80u);
            for (int i = tid; i < 2 * ACC_SIZE / 4; i += 128) stg128(g_acc + 2 * j * ACC_SIZE + 4 * i, 0, 0, 0, 0);
            fence_async_smem();
            fence_gpu();
            bar_sync(1, 128);
            float acc[8];
            int i = 0;
#pragma unroll 1
            for (int job = 0; job < 12; job++) {
                const int n = job < 6 ? 4 : 8;
#pragma unroll 1
                for (int t = 0; t < n; t++, i++) {
                    mbar_wait(sb + BAR_FULLA + 8 * (i & 7), (i >> 3) & 1);
                    wg_fence();
#pragma unroll
                    for (int k = 0; k < 8; k++)
                        wgmma_n8_tt(acc + (k & 4), desc_lo(sb + OFF_A) + (i & 7) * (SLOT >> 4) + 128 * k, desc_lo(sb + OFF_B), (t | (k & 3)) != 0);
                    wg_commit();
                    wg_wait<1>();
                    mbar_arrive_n_if(sb + BAR_EMPTYA + 8 * ((i + 7) & 7), 2, lane == 0 && i > 0);
                }
                wg_wait<0>();
                fence_acc<8>(acc);
                const int q = lane & 3;
                const float lo = (q & 1) ? acc[2] : acc[0], hi = (q & 1) ? acc[6] : acc[4];
                const float v = job < 6 ? lo + hi : ((q & 2) ? hi : lo);
                unsigned long long* dst = g_cs + ((2 * j + (job & 1)) * 6 + (job >> 1)) * 128 + (q >> 1) * 64 + 16 * warp + 8 * (q & 1) + (lane >> 2);
                asm volatile("st.relaxed.gpu.global.b64 [%0], %1;" ::"l"(dst), "l"(((unsigned long long)epoch << 32) | __float_as_uint(v)) : "memory");
            }
        }
        return;
    }
    {
        const int w = warp >> 2, wv = warp & 3, g = lane >> 2, q = lane & 3;
        const int row_w = 128 * m + 16 * warp;
        const uint32_t sa = sb + OFF_A + w * 8192;
        const uint32_t dA = desc_lo(sa), dB = desc_lo(sb + OFF_B);
        const uint32_t pub = sb + BAR_PUB + 48 * w;
        const bool l0 = lane == 0;
        Ring rg{0, 0};
        int prev = 0;

        uint32_t wb[16];
        constexpr float L2E = 1.4426950408889634f;
        TL(57, tid == 0);
        uint32_t fp[16], fm[16];
        float fr[16];
        float rs0, nm0, rs1, nm1;
        {
            float acc[64];
#pragma unroll 1
            for (int kt = 0; kt < 8; kt++) {
                mbar_waitc(sb + BAR_FULLA + 8 * kt, 0);
                mbar_waitc(sb + BAR_FULLB + 8 * rg.slot, rg.phase);
                TL(20 + kt, tid == 0);
                const uint32_t da = dA + kt * (SLOT >> 4), db = dB + rg.slot * (SLOT >> 4);
                wg_fence();
#pragma unroll
                for (int k = 0; k < 4; k++) wgmma_n128(acc, da + 2 * k, db + 128 * k, (kt | k) != 0);
                wg_commit();
                wg_wait<1>();
                mbar_arrive_if(sb + BAR_EMPTYB + 8 * prev, l0 && kt > 0);
                prev = rg.slot; rg.adv();
            }
            {
                uint4 a, b;
                uint32_t it = 0;
                do {
                    a = ld_tagged_rlx(g_xstat + 2 * (row_w + g));
                    b = ld_tagged_rlx(g_xstat + 2 * (row_w + g + 8));
                    trap_if_gt(++it, 1u << 22);
                } while (__any_sync(0xffffffffu, a.y != epoch || a.w != epoch || b.y != epoch || b.w != epoch));
                rs0 = __uint_as_float(a.x); nm0 = __uint_as_float(a.z); rs1 = __uint_as_float(b.x); nm1 = __uint_as_float(b.z);
            }
#pragma unroll
            for (int i = 0; i < 8; i++) {
                wb[(i >> 1) * 4 + (i & 1)] = __byte_perm(wraw[2 * i], wraw[2 * i + 1], 0x5410);
                wb[(i >> 1) * 4 + 2 + (i & 1)] = __byte_perm(wraw[2 * i], wraw[2 * i + 1], 0x7632);
            }
            TL(17, tid == 0);
            mbar_waitc(sb + BAR_CS1, 0);
            TL(18, tid == 0);
            wg_wait<0>();
            fence_acc<64>(acc);
            mbar_arrive_if(sb + BAR_EMPTYB + 8 * prev, l0);
            TL(2, tid == 0);
#pragma unroll
            for (int i = 2; i < 6; i++) mbar_waitc(sb + BAR_FULLB + 8 * i, 1);
            const int lrow = 16 * warp + (lane & 15), ch = lane >> 4, sw = lane & 7;
            const uint32_t st = sb + OFF_B + 2 * SLOT + lrow * 128;
            uint32_t ka[16];
#pragma unroll
            for (int hh = 0; hh < 4; hh++)
                ln_frag<false>(acc + 8 * hh, sb + OFF_CS1 + (64 + 16 * hh + 2 * q) * 4, rs0, nm0, rs1, nm1, ka + 4 * hh);
#pragma unroll
            for (int hh = 0; hh < 4; hh++) feature_map<true>(ka + 4 * hh, wb + 4 * hh, rs0 * L2E, rs1 * L2E, fp + 4 * hh, fm + 4 * hh, fr);
#pragma unroll
            for (int hh = 0; hh < 4; hh++) {
                stsm4(st + (hh >> 1) * SLOT + (((4 * (hh & 1) + ch) ^ sw) << 4), fp[4 * hh], fp[4 * hh + 1], fp[4 * hh + 2], fp[4 * hh + 3]);
                stsm4(st + (hh >> 1) * SLOT + (((4 * (hh & 1) + 2 + ch) ^ sw) << 4), fm[4 * hh], fm[4 * hh + 1], fm[4 * hh + 2], fm[4 * hh + 3]);
            }
            mbar_waitc(sb + BAR_CSV, 0);
#pragma unroll
            for (int hh = 0; hh < 4; hh++) {
                uint32_t a[4];
                ln_frag<true>(acc + 32 + 8 * hh, sb + OFF_CS1 + (128 + 16 * hh + 2 * q) * 4, rs0, nm0, rs1, nm1, a);
                stsm4(st + (2 + (hh >> 1)) * SLOT + (((2 * (hh & 1) + ch) ^ sw) << 4), a[0], a[1], a[2], a[3]);
            }
            stsm4(st + (2 + ch) * SLOT + ((4 ^ sw) << 4), 0x3f803f80u, 0x3f803f80u, 0x3f803f80u, 0x3f803f80u);
            fence_async_smem();
            bar_sync(1, 256);
            float kvd[20];
            wg_fence();
#pragma unroll
            for (int k = 0; k < 8; k++)
                wgmma_n40_tt(kvd, dB + (2 + w) * (SLOT >> 4) + 128 * k, dB + (4 + w) * (SLOT >> 4) + 128 * k, k != 0);
            wg_commit();
            wg_wait<0>();
            fence_acc<20>(kvd);
            const bool h1 = wv >= 2;
            const int f = 16 * warp + g;
            float* kvp = acc_j + ACC_KV + f * 16 + 2 * q;
            red_f32x2(kvp, h1 ? kvd[8] : kvd[0], h1 ? kvd[9] : kvd[1]);
            red_f32x2(kvp + 128, h1 ? kvd[10] : kvd[2], h1 ? kvd[11] : kvd[3]);
            red_f32x2(kvp + 8, h1 ? kvd[12] : kvd[4], h1 ? kvd[13] : kvd[5]);
            red_f32x2(kvp + 136, h1 ? kvd[14] : kvd[6], h1 ? kvd[15] : kvd[7]);
            red_f32_if(acc_j + ACC_Z + f + 8 * (q & 1), q ? kvd[18] : kvd[16], q < 2);
            __syncwarp();
            mbar_arrive_if(pub, l0);
            mbar_arrive_if(sb + BAR_EMPTYB + 8 * (2 + (lane & 3)), lane < 4);
            TL(3, tid == 0);
        }
        uint32_t res_lo[8], res_hi[8];
        const uint32_t own_rows = sb + OFF_A + j * SLOT + warp * 2048;
        {
            float acc[32];
            rg.slot = 0; rg.phase = 0;
#pragma unroll 1
            for (int b = 0; b < 4; b++) {
                mbar_waitc(sb + BAR_FULLB + 8 * rg.slot, rg.phase);
                const uint32_t da = dA + b * (2 * SLOT >> 4), db = dB + rg.slot * (SLOT >> 4);
                wg_fence();
#pragma unroll
                for (int k = 0; k < 8; k++) wgmma_n64(acc, da + (k >> 2) * (SLOT >> 4) + (k & 3) * 2, db + 128 * k, (b | k) != 0);
                wg_commit();
                wg_wait<1>();
                mbar_arrive_if(sb + BAR_EMPTYB + 8 * prev, l0 && b > 0);
                prev = rg.slot; rg.adv();
            }
            wg_wait<0>();
            fence_acc<32>(acc);
            mbar_arrive_if(sb + BAR_EMPTYB + 8 * prev, l0);
            mbar_arrive_if(sb + BAR_EMPTYA + 8 * (lane & 7), lane < 8 && (lane | 1) != (j | 1));
            TL(4, tid == 0);
            mbar_waitc(sb + BAR_CSQ, 0);
            uint32_t qa[16];
#pragma unroll
            for (int hh = 0; hh < 4; hh++)
                ln_frag<false>(acc + 8 * hh, sb + OFF_CS1 + (16 * hh + 2 * q) * 4, rs0, nm0, rs1, nm1, qa + 4 * hh);
#pragma unroll
            for (int hh = 0; hh < 4; hh++) feature_map<false>(qa + 4 * hh, wb + 4 * hh, rs0 * L2E, rs1 * L2E, fp + 4 * hh, fm + 4 * hh, fr + 4 * hh);
#pragma unroll
            for (int b = 0; b < 4; b++)
                ldsm4(own_rows + (lane & 15) * 128 + (((2 * b + (lane >> 4)) ^ (lane & 7)) << 4),
                      res_lo[2 * b], res_hi[2 * b], res_lo[2 * b + 1], res_hi[2 * b + 1]);
            TL(5, tid == 0);
            if (warp == 0) wait_count_warp(cnt_j, epoch * 32);
            TL(6, tid == 0);
            bar_sync(1, 256);
            const uint32_t kvs = sb + OFF_A + (j ^ 1) * SLOT;
            {
                const float4 a0 = ld_l2_f4(acc_j + ACC_KV + 4 * tid), a1 = ld_l2_f4(acc_j + ACC_KV + 4 * (tid + 256));
                const float zz = ld_l2_f(acc_j + ACC_Z + (tid & 127));
                sts64(kvs + (tid >> 2) * 48 + (tid & 3) * 8, pack_bf16(a0.x, a0.y), pack_bf16(a0.z, a0.w));
                sts64(kvs + ((tid >> 2) + 64) * 48 + (tid & 3) * 8, pack_bf16(a1.x, a1.y), pack_bf16(a1.z, a1.w));
                const uint32_t z2 = pack_bf16(zz, zz);
                sts64(kvs + (tid & 127) * 48 + 32 + w * 8, z2, z2);
            }
            bar_sync(1, 256);
            uint32_t o_lo[8], o_hi[8];
#pragma unroll
            for (int hh = 0; hh < 4; hh++) {
                uint32_t b[8], zb[4];
                const uint32_t base = kvs + hh * 32 * 48;
                ldsm4t(base + (lane & 15) * 48 + (lane >> 4) * 16, b[0], b[1], b[2], b[3]);
                ldsm4t(base + (16 + (lane & 15)) * 48 + (lane >> 4) * 16, b[4], b[5], b[6], b[7]);
                ldsm4t(base + lane * 48 + 32, zb[0], zb[1], zb[2], zb[3]);
                float n0[4], n1[4], dn[4], m0[4], m1[4], dm[4];
                mma16816_z(n0, fp + 4 * hh, b[0], b[1]); mma16816_z(n1, fp + 4 * hh, b[2], b[3]); mma16816_z(dn, fp + 4 * hh, zb[0], zb[1]);
                mma16816_z(m0, fm + 4 * hh, b[4], b[5]); mma16816_z(m1, fm + 4 * hh, b[6], b[7]); mma16816_z(dm, fm + 4 * hh, zb[2], zb[3]);
                const float* r = fr + 4 * hh;
                const float i0 = rcp(fmaf(dn[0], r[0], fmaf(dm[0], r[2], 1e-6f))), i1 = rcp(fmaf(dn[2], r[1], fmaf(dm[2], r[3], 1e-6f)));
                const float p0 = r[0] * i0, q0 = r[2] * i0, p1 = r[1] * i1, q1 = r[3] * i1;
                o_lo[2 * hh] = pack_bf16(fmaf(n0[0], p0, m0[0] * q0), fmaf(n0[1], p0, m0[1] * q0));
                o_hi[2 * hh] = pack_bf16(fmaf(n0[2], p1, m0[2] * q1), fmaf(n0[3], p1, m0[3] * q1));
                o_lo[2 * hh + 1] = pack_bf16(fmaf(n1[0], p0, m1[0] * q0), fmaf(n1[1], p0, m1[1] * q0));
                o_hi[2 * hh + 1] = pack_bf16(fmaf(n1[2], p1, m1[2] * q1), fmaf(n1[3], p1, m1[3] * q1));
            }
            store_tile(own_rows, g_o + (size_t)row_w * DM + 64 * j, o_lo, o_hi, lane);
            fence_async_smem();
            __syncwarp();
            mbar_arrive_if(pub + 8, l0);
            mbar_arrive_if(sb + BAR_EMPTYA + 8 * (j ^ (lane & 1)), lane < 2);
            TL(7, tid == 0);
        }
        {
            float acc[32];
#pragma unroll
            for (int t = 0; t < 8; t++) {
                acc[4 * t] = bf_lo(res_lo[t]); acc[4 * t + 1] = bf_hi(res_lo[t]);
                acc[4 * t + 2] = bf_lo(res_hi[t]); acc[4 * t + 3] = bf_hi(res_hi[t]);
            }
            fence_acc<32>(acc);
#pragma unroll 1
            for (int kp = 0; kp < 4; kp++) {
                mbar_waitc(sb + BAR_FULLB + 8 * rg.slot, rg.phase);
#pragma unroll
                for (int hf = 0; hf < 2; hf++) {
                    const int kt = 2 * kp + hf;
                    mbar_waitc(sb + BAR_FULLA + 8 * kt, 1);
                    TL(8, kt == 0 && tid == 0);
                    const uint32_t da = dA + kp * (2 * SLOT >> 4), db = dB + rg.slot * (SLOT >> 4);
                    wg_fence();
#pragma unroll
                    for (int k = 0; k < 4; k++) wgmma_n64(acc, da + hf * (SLOT >> 4) + 2 * k, db + (hf * 4 + k) * 128, 1);
                    wg_commit();
                    wg_wait<1>();
                    mbar_arrive_if(sb + BAR_EMPTYA + 8 * ((kt + 7) & 7), l0 && kt > 0 && kt - 1 != j);
                    if (hf == 0) mbar_arrive_if(sb + BAR_EMPTYB + 8 * prev, l0 && kt > 0);
                }
                prev = rg.slot; rg.adv();
            }
            wg_wait<0>();
            fence_acc<32>(acc);
            mbar_arrive_if(sb + BAR_EMPTYA + 8 * 7, l0 && j != 7);
            mbar_arrive_if(sb + BAR_EMPTYB + 8 * prev, l0);
            TL(9, tid == 0);
            float s0 = 0.f, s1 = 0.f;
#pragma unroll
            for (int t = 0; t < 8; t++) {
                res_lo[t] = pack_bf16(acc[4 * t], acc[4 * t + 1]);
                res_hi[t] = pack_bf16(acc[4 * t + 2], acc[4 * t + 3]);
                s0 += acc[4 * t] + acc[4 * t + 1];
                s1 += acc[4 * t + 2] + acc[4 * t + 3];
            }
            store_tile(own_rows, g_h + (size_t)row_w * DM + 64 * j, res_lo, res_hi, lane);
            s0 += __shfl_xor_sync(0xffffffffu, s0, 1); s1 += __shfl_xor_sync(0xffffffffu, s1, 1);
            s0 += __shfl_xor_sync(0xffffffffu, s0, 2); s1 += __shfl_xor_sync(0xffffffffu, s1, 2);
            const float mu0 = s0 * (1.f / 64), mu1 = s1 * (1.f / 64);
            float q0 = 0.f, q1 = 0.f;
#pragma unroll
            for (int t = 0; t < 8; t++) {
                float d;
                d = acc[4 * t] - mu0; q0 = fmaf(d, d, q0);
                d = acc[4 * t + 1] - mu0; q0 = fmaf(d, d, q0);
                d = acc[4 * t + 2] - mu1; q1 = fmaf(d, d, q1);
                d = acc[4 * t + 3] - mu1; q1 = fmaf(d, d, q1);
            }
            q0 += __shfl_xor_sync(0xffffffffu, q0, 1); q1 += __shfl_xor_sync(0xffffffffu, q1, 1);
            q0 += __shfl_xor_sync(0xffffffffu, q0, 2); q1 += __shfl_xor_sync(0xffffffffu, q1, 2);
            stg_f2_if(g_hstat + (row_w + g + 8 * (q & 1)) * 16 + 2 * j, q ? mu1 : mu0, q ? q1 : q0, q < 2);
            fence_async_smem();
            __syncwarp();
            mbar_arrive_if(pub + 16, l0);
            mbar_arrive_if(sb + BAR_EMPTYA + 8 * j, l0);
            TL(10, tid == 0);
        }
        if (w == 1) {
#pragma unroll 1
            for (int kt = 0; kt < 8; kt++) mbar_waitc(sb + BAR_FULLA + 8 * kt, 0);
            const float* sp = g_hstat + (128 * m + (tid & 127)) * 16;
            float4 v[4];
#pragma unroll
            for (int i = 0; i < 4; i++) v[i] = ld_l2_f4(sp + 4 * i);
            float mean = 0.f;
#pragma unroll
            for (int i = 0; i < 4; i++) mean += v[i].x + v[i].z;
            mean *= 0.125f;
            float m2 = 0.f, dv = 0.f;
#pragma unroll
            for (int i = 0; i < 4; i++) {
                m2 += v[i].y + v[i].w;
                dv = fmaf(v[i].x - mean, v[i].x - mean, dv); dv = fmaf(v[i].z - mean, v[i].z - mean, dv);
            }
            sts_f2(sb + OFF_CS1 + (tid & 127) * 8, -mean, __fdividef(1.f, fmaf(dv, 64.f, m2) * (1.f / DM) + 1e-5f));
            mbar_arrive(sb + BAR_CS3);
        }
        {
            float acc0[64], acc1[64];
            const uint32_t dA0 = desc_lo(sb + OFF_A);
#pragma unroll 1
            for (int c = w; c < 3; c += 2) {
                if (c > 0) bar_sync(1 + c, 256);
                rg.slot = (c == 2) ? 0 : 2 + 2 * c; rg.phase = (c == 0);
#pragma unroll 1
                for (int kt = 0; kt < 8; kt++) {
                    mbar_waitc(sb + BAR_FULLA + 8 * kt, 0);
                    mbar_waitc(sb + BAR_FULLB + 8 * rg.slot, rg.phase);
                    TL(44 + c * 2 + (kt == 1), (tid & 127) == 0 && kt < 2);
                    const uint32_t da = dA0 + kt * (SLOT >> 4), db = dB + rg.slot * (SLOT >> 4);
                    wg_fence();
#pragma unroll
                    for (int k = 0; k < 4; k++) {
                        wgmma_n128(acc0, da + 2 * k, db + 128 * k, (kt | k) != 0);
                        wgmma_n128(acc1, da + 512 + 2 * k, db + 128 * k, (kt | k) != 0);
                    }
                    wg_commit();
                    wg_wait<1>();
                    mbar_arrive_n_if(sb + BAR_EMPTYB + 8 * prev, 2, l0 && kt > 0);
                    mbar_arrive_if(sb + BAR_EMPTYA + 8 * ((kt + 7) & 7), l0 && kt > 0 && c > 0);
                    prev = rg.slot; rg.adv();
                }
                bar_arrive(2 + c, 256);
                mbar_waitc(sb + BAR_CS3, 0);
                float nm[4];
#pragma unroll
                for (int i = 0; i < 4; i++) nm[i] = lds_f2(sb + OFF_CS1 + (64 * (i >> 1) + 16 * wv + g + 8 * (i & 1)) * 8).x;
                wg_wait<0>();
                fence_acc<64>(acc0); fence_acc<64>(acc1);
                mbar_arrive_n_if(sb + BAR_EMPTYB + 8 * prev, 2, l0);
                mbar_arrive_if(sb + BAR_EMPTYA + 8 * 7, l0 && c > 0);
                TL(11 + c, (tid & 127) == 0);
                __nv_bfloat16* hp = g_hh + (size_t)(128 * m + 16 * wv + g) * FFP + 192 * j + 64 * c + (q & 1) * 8 + (q >> 1) * 4;
#pragma unroll
                for (int tp = 0; tp < 4; tp++) {
                    if (tp < 3 || c < 2) {
                        const uint32_t ca = sb + OFF_CS3 + (32 * c + 8 * tp + q) * 16;
                        const float4 c0 = lds_f4(ca), c1 = lds_f4(ca + 64);
                        store_pair(hp + 16 * tp, hh_pair(acc0 + 8 * tp, c0, nm[0]), hh_pair(acc0 + 8 * tp + 4, c1, nm[0]), q & 1);
                        store_pair(hp + 8 * FFP + 16 * tp, hh_pair(acc0 + 8 * tp + 2, c0, nm[1]), hh_pair(acc0 + 8 * tp + 6, c1, nm[1]), q & 1);
                        store_pair(hp + 64 * FFP + 16 * tp, hh_pair(acc1 + 8 * tp, c0, nm[2]), hh_pair(acc1 + 8 * tp + 4, c1, nm[2]), q & 1);
                        store_pair(hp + 72 * FFP + 16 * tp, hh_pair(acc1 + 8 * tp + 2, c0, nm[3]), hh_pair(acc1 + 8 * tp + 6, c1, nm[3]), q & 1);
                    }
                }
                __syncwarp();
                mbar_arrive_if(pub + 24 + 8 * c, l0);
                TL(54 + c, (tid & 127) == 0);
            }
        }
        {
            float acc[32];
            const uint32_t xch = sb + OFF_B + (tid & 127) * 16;
            if (w == 1) {
                float acc0[32];
                bar_sync(4, 256);
                rg.slot = 2; rg.phase = 1;
                const uint32_t dA0 = desc_lo(sb + OFF_A);
#define KT_P4(T, HF, NK)                                                                                    \
    do {                                                                                                    \
        const int s_ = (T) & 7;                                                                             \
        if (!(HF)) mbar_waitc(sb + BAR_FULLB + 8 * rg.slot, rg.phase);                                      \
        mbar_waitc(sb + BAR_FULLA + 8 * s_, (((T) >> 3) + 1) & 1);                                          \
        if (!(HF)) TL(30 + (T) / 2, tid == 128);                                                            \
        const uint32_t da_ = dA0 + s_ * (SLOT >> 4), db_ = dB + rg.slot * (SLOT >> 4) + (HF) * 512;         \
        wg_fence();                                                                                         \
        _Pragma("unroll") for (int k = 0; k < (NK); k++) {                                                  \
            wgmma_n64(acc0, da_ + 2 * k, db_ + 128 * k, ((T) | k) != 0);                                    \
            wgmma_n64(acc, da_ + 512 + 2 * k, db_ + 128 * k, ((T) | k) != 0);                               \
        }                                                                                                   \
        wg_commit();                                                                                        \
        wg_wait<1>();                                                                                       \
        mbar_arrive_n_if(sb + BAR_EMPTYA + 8 * (((T) + 7) & 7), 2, l0 && (T) > 0);                          \
        if (!(HF)) mbar_arrive_n_if(sb + BAR_EMPTYB + 8 * prev, 2, l0 && (T) > 0);                          \
        if (HF) { prev = rg.slot; rg.adv(); }                                                               \
    } while (0)
#pragma unroll 1
                for (int t = 0; t < 16; t += 2) { KT_P4(t, 0, 4); KT_P4(t + 1, 1, 4); }
#pragma unroll 1
                for (int t = 16; t < 24; t += 2) { KT_P4(t, 0, 3); KT_P4(t + 1, 1, 3); }
                wg_wait<0>();
                fence_acc<32>(acc0); fence_acc<32>(acc);
                TL(15, tid == 128);
#pragma unroll
                for (int t = 0; t < 8; t++)
                    sts128(xch + 2 * SLOT + t * 2048, __float_as_uint(acc0[4 * t]), __float_as_uint(acc0[4 * t + 1]),
                           __float_as_uint(acc0[4 * t + 2]), __float_as_uint(acc0[4 * t + 3]));
                bar_sync(5, 256);
            } else {
                bar_sync(5, 256);
#pragma unroll
                for (int t = 0; t < 8; t++) {
                    const float4 v = lds_f4(xch + 2 * SLOT + t * 2048);
                    acc[4 * t] = v.x; acc[4 * t + 1] = v.y; acc[4 * t + 2] = v.z; acc[4 * t + 3] = v.w;
                }
            }
            const float r0 = lds_f2(sb + OFF_CS1 + (16 * warp + g) * 8).y, r1 = lds_f2(sb + OFF_CS1 + (16 * warp + g + 8) * 8).y;
#pragma unroll
            for (int t = 0; t < 8; t++) {
                res_lo[t] = pack_bf16(fmaf(acc[4 * t], r0, bf_lo(res_lo[t])), fmaf(acc[4 * t + 1], r0, bf_hi(res_lo[t])));
                res_hi[t] = pack_bf16(fmaf(acc[4 * t + 2], r1, bf_lo(res_hi[t])), fmaf(acc[4 * t + 3], r1, bf_hi(res_hi[t])));
            }
            store_tile(own_rows, P.out + (size_t)row_w * DM + 64 * j, res_lo, res_hi, lane);
            if (tid == 0 && role == 0) g_epoch = epoch + 1;
            TL(16, tid == 0); TLG(1, tid == 0);
        }
    }
}

typedef CUresult (*EncodeFn)(CUtensorMap*, CUtensorMapDataType, cuuint32_t, void*, const cuuint64_t*, const cuuint64_t*,
                             const cuuint32_t*, const cuuint32_t*, CUtensorMapInterleave, CUtensorMapSwizzle,
                             CUtensorMapL2promotion, CUtensorMapFloatOOBfill);

static void make_map2d(EncodeFn enc, CUtensorMap* tm, const void* base, uint64_t cols, uint64_t rows, uint64_t pitch_elems,
                       uint32_t box_rows) {
    cuuint64_t gd[2] = {cols, rows};
    cuuint64_t gs[1] = {pitch_elems * 2};
    cuuint32_t bd[2] = {64, box_rows};
    cuuint32_t es[2] = {1, 1};
    enc(tm, CU_TENSOR_MAP_DATA_TYPE_BFLOAT16, 2, const_cast<void*>(base), gd, gs, bd, es, CU_TENSOR_MAP_INTERLEAVE_NONE,
        CU_TENSOR_MAP_SWIZZLE_128B, CU_TENSOR_MAP_L2_PROMOTION_L2_256B, CU_TENSOR_MAP_FLOAT_OOB_FILL_NONE);
}

}

extern "C" void kernel_launch(void* const* d_in, const int* in_sizes, int n_in, void* d_out, int out_size) {
    using namespace hk;
    (void)in_sizes; (void)n_in; (void)out_size;
    static EncodeFn enc = nullptr;
    static void *po = nullptr, *ph = nullptr, *phh = nullptr;
    static int std_layout = 0;
    if (!enc) {
        void* fn = nullptr;
        cudaDriverEntryPointQueryResult qr;
        cudaGetDriverEntryPoint("cuTensorMapEncodeTiled", &fn, cudaEnableDefault, &qr);
        enc = (EncodeFn)fn;
        cudaGetSymbolAddress(&po, g_o);
        cudaGetSymbolAddress(&ph, g_h);
        cudaGetSymbolAddress(&phh, g_hh);
        cudaFuncSetAttribute(fused_kernel, cudaFuncAttributeMaxDynamicSharedMemorySize, SMEM_BYTES);
        int dev = 0, sms = 0;
        cudaGetDevice(&dev);
        cudaDeviceGetAttribute(&sms, cudaDevAttrMultiProcessorCount, dev);
        cudaFuncSetAttribute(fused_kernel, cudaFuncAttributeNonPortableClusterSizeAllowed, 1);
        const int sizes[3] = {8, 9, 16}, want[3] = {15, 9, 7};
        bool ok = sms == NCTA;
        for (int i = 0; i < 3 && ok; i++) {
            cudaLaunchConfig_t cfg = {};
            cfg.gridDim = dim3(sizes[i] * 8); cfg.blockDim = dim3(NTHREADS); cfg.dynamicSmemBytes = SMEM_BYTES;
            cudaLaunchAttribute at;
            at.id = cudaLaunchAttributeClusterDimension;
            at.val.clusterDim.x = sizes[i]; at.val.clusterDim.y = 1; at.val.clusterDim.z = 1;
            cfg.attrs = &at; cfg.numAttrs = 1;
            int n = 0;
            ok = cudaOccupancyMaxActiveClusters(&n, fused_kernel, &cfg) == cudaSuccess && n == want[i];
        }
        (void)cudaGetLastError();
        std_layout = ok ? 1 : 0;
    }
    Params P;
    const __nv_bfloat16* x = (const __nv_bfloat16*)d_in[0];
    P.x = x;
    P.wqkv = (const __nv_bfloat16*)d_in[1];
    P.wphi = (const __nv_bfloat16*)d_in[2];
    P.wo = (const __nv_bfloat16*)d_in[3];
    P.wg = (const __nv_bfloat16*)d_in[5];
    P.wu = (const __nv_bfloat16*)d_in[6];
    P.wd = (const __nv_bfloat16*)d_in[7];
    P.out = (__nv_bfloat16*)d_out;
    P.use_smid = std_layout;
    for (int i = 0; i < NCTA; i++) {
        int role = i < 4 ? 128 + i : i - 4;
        if (std_layout) {
            const int tpc = i >> 1, odd = i & 1;
            if (tpc < 32) role = (tpc & 7) * 8 + (tpc >> 3) * 2 + odd;
            else if (tpc < 60) role = (8 + (tpc - 32) % 7) * 8 + ((tpc - 32) / 7) * 2 + odd;
            else if (tpc < 62) role = 128 + (tpc - 60) * 2 + odd;
            else role = 15 * 8 + (tpc - 62) * 2 + odd;
        }
        P.role[i] = (unsigned char)role;
    }
    make_map2d(enc, &P.tx, x, DM, SEQ, DM, 128);
    make_map2d(enc, &P.to, po, DM, SEQ, DM, 128);
    make_map2d(enc, &P.th, ph, DM, SEQ, DM, 128);
    make_map2d(enc, &P.thh, phh, FFP, SEQ, FFP, 128);
    make_map2d(enc, &P.twq, P.wqkv, 3 * DM, DM, 3 * DM, 128);
    make_map2d(enc, &P.two, P.wo, DM, DM, DM, 128);
    make_map2d(enc, &P.twg, P.wg, FF, DM, FF, 64);
    make_map2d(enc, &P.twu, P.wu, FF, DM, FF, 64);
    make_map2d(enc, &P.twd, P.wd, DM, FF, DM, 64);
    {
        cuuint64_t gd[3] = {(cuuint64_t)DM, (cuuint64_t)DM, 3};
        cuuint64_t gs[2] = {(cuuint64_t)3 * DM * 2, (cuuint64_t)DM * 2};
        cuuint32_t bd[3] = {64, 64, 2};
        cuuint32_t es[3] = {1, 1, 1};
        enc(&P.twkv, CU_TENSOR_MAP_DATA_TYPE_BFLOAT16, 3, const_cast<__nv_bfloat16*>(P.wqkv), gd, gs, bd, es,
            CU_TENSOR_MAP_INTERLEAVE_NONE, CU_TENSOR_MAP_SWIZZLE_128B, CU_TENSOR_MAP_L2_PROMOTION_L2_256B,
            CU_TENSOR_MAP_FLOAT_OOB_FILL_NONE);
    }
    fused_kernel<<<NCTA, NTHREADS, SMEM_BYTES>>>(P);
}
```

```cpp
#include <cuda_runtime.h>
#include <cuda_bf16.h>
#include <cuda.h>
#include <stdint.h>

namespace hk {

constexpr int SEQ = 2048, DM = 512, FF = 1376, FFP = 1536;
constexpr int NCTA = 132;
constexpr int NTHREADS = 384;
constexpr uint32_t SLOT = 16384;
constexpr uint32_t OFF_A = 0, OFF_B = 8 * SLOT, OFF_MISC = 14 * SLOT;
constexpr uint32_t BAR_FULLA = OFF_MISC + 0, BAR_EMPTYA = OFF_MISC + 64, BAR_FULLB = OFF_MISC + 128,
                   BAR_EMPTYB = OFF_MISC + 176, BAR_CS1 = OFF_MISC + 224, BAR_CS3 = OFF_MISC + 232,
                   BAR_PUB = OFF_MISC + 240,
                   BAR_CSQ = OFF_MISC + 336, BAR_CSV = OFF_MISC + 344;
constexpr uint32_t OFF_CS1 = OFF_MISC + 384;
constexpr uint32_t OFF_CS3 = OFF_CS1 + 1024;
constexpr uint32_t SMEM_BYTES = OFF_CS3 + 1536;
constexpr int NB = 6;
constexpr int AHEAD = 3;

constexpr int ACC_KV = 0, ACC_Z = 2048, ACC_SIZE = 2176;

__device__ __align__(1024) __nv_bfloat16 g_o[SEQ * DM];
__device__ __align__(1024) __nv_bfloat16 g_h[SEQ * DM];
__device__ __align__(1024) __nv_bfloat16 g_hh[SEQ * FFP];
__device__ __align__(128) float g_hstat[SEQ * 16];
__device__ __align__(128) unsigned long long g_xstat[SEQ * 2];
__device__ __align__(128) float g_acc[8 * ACC_SIZE];
__device__ __align__(128) unsigned g_cnt[8 * 32];
__device__ __align__(128) unsigned long long g_cs[8 * 6 * 128];
__device__ __align__(128) unsigned g_flag[16 * 5 * 32];
__device__ unsigned g_epoch = 1;

#define TL(i, pred) do {} while (0)
#define TLG(i, pred) do {} while (0)

struct Params {
    CUtensorMap tx, to, th, thh, twkv, twq, two, twg, twu, twd;
    const __nv_bfloat16 *x, *wqkv, *wphi, *wo, *wg, *wu, *wd;
    __nv_bfloat16* out;
    int use_smid;
    unsigned char role[NCTA];
};

__device__ __forceinline__ uint32_t smem_u32(const void* p) { return (uint32_t)__cvta_generic_to_shared(p); }
__device__ __forceinline__ void mbar_init(uint32_t bar, uint32_t cnt) {
    asm volatile("mbarrier.init.shared::cta.b64 [%0], %1;" ::"r"(bar), "r"(cnt) : "memory");
}
__device__ __forceinline__ void mbar_expect_tx(uint32_t bar, uint32_t bytes) {
    asm volatile("mbarrier.arrive.expect_tx.shared::cta.b64 _, [%0], %1;" ::"r"(bar), "r"(bytes) : "memory");
}
__device__ __forceinline__ void mbar_arrive(uint32_t bar) {
    asm volatile("mbarrier.arrive.shared::cta.b64 _, [%0];" ::"r"(bar) : "memory");
}
__device__ __forceinline__ void mbar_arrive_if(uint32_t bar, bool pred) {
    asm volatile("{.reg .pred p; setp.ne.u32 p, %1, 0; @p mbarrier.arrive.shared::cta.b64 _, [%0];}" ::"r"(bar), "r"((uint32_t)pred) : "memory");
}
__device__ __forceinline__ bool mbar_try(uint32_t bar, uint32_t parity) {
    uint32_t ok;
    asm volatile("{.reg .pred p; mbarrier.try_wait.parity.shared::cta.b64 p, [%1], %2; selp.u32 %0,1,0,p;}"
                 : "=r"(ok) : "r"(bar), "r"(parity) : "memory");
    return ok;
}
__device__ __forceinline__ bool mbar_test(uint32_t bar, uint32_t parity) {
    uint32_t ok;
    asm volatile("{.reg .pred p; mbarrier.test_wait.parity.shared::cta.b64 p, [%1], %2; selp.u32 %0,1,0,p;}"
                 : "=r"(ok) : "r"(bar), "r"(parity) : "memory");
    return ok;
}
__device__ __forceinline__ void trap_if_gt(uint32_t v, uint32_t lim) {
    asm volatile("{.reg .pred p; setp.gt.u32 p, %0, %1; @p trap;}" ::"r"(v), "r"(lim));
}
__device__ __forceinline__ void mbar_wait(uint32_t bar, uint32_t parity) {
    asm volatile("{\n"
                 ".reg .pred P1, P2;\n"
                 ".reg .u32 c;\n"
                 "mov.u32 c, 0;\n"
                 "LAB_WAIT:\n"
                 "mbarrier.try_wait.parity.shared::cta.b64 P1, [%0], %1;\n"
                 "@P1 bra LAB_DONE;\n"
                 "add.u32 c, c, 1;\n"
                 "setp.gt.u32 P2, c, 4194304;\n"
                 "@P2 trap;\n"
                 "bra LAB_WAIT;\n"
                 "LAB_DONE:\n"
                 "}" ::"r"(bar), "r"(parity) : "memory");
}
__device__ __forceinline__ void mbar_waitc(uint32_t bar, uint32_t parity) {
    asm volatile("{\n"
                 ".reg .pred P1;\n"
                 "LAB_WAIT:\n"
                 "mbarrier.try_wait.parity.shared::cta.b64 P1, [%0], %1;\n"
                 "@!P1 bra LAB_WAIT;\n"
                 "}" ::"r"(bar), "r"(parity) : "memory");
}
__device__ __forceinline__ void tma2d(uint32_t dst, const CUtensorMap* tm, uint32_t bar, int c0, int c1) {
    asm volatile("cp.async.bulk.tensor.2d.shared::cluster.global.mbarrier::complete_tx::bytes [%0], [%1, {%3, %4}], [%2];"
                 ::"r"(dst), "l"(tm), "r"(bar), "r"(c0), "r"(c1) : "memory");
}
__device__ __forceinline__ void tma3d(uint32_t dst, const CUtensorMap* tm, uint32_t bar, int c0, int c1, int c2) {
    asm volatile("cp.async.bulk.tensor.3d.shared::cluster.global.mbarrier::complete_tx::bytes [%0], [%1, {%3, %4, %5}], [%2];"
                 ::"r"(dst), "l"(tm), "r"(bar), "r"(c0), "r"(c1), "r"(c2) : "memory");
}
__device__ __forceinline__ bool elect_one() {
    uint32_t ok;
    asm volatile("{.reg .pred p; elect.sync _|p, 0xffffffff; selp.u32 %0, 1, 0, p;}" : "=r"(ok));
    return ok;
}
__device__ __forceinline__ void prefetch_tmap(const CUtensorMap* tm) {
    asm volatile("prefetch.tensormap [%0];" ::"l"(tm) : "memory");
}
__device__ __forceinline__ void prefetch_l2(const void* p, uint32_t bytes) {
    asm volatile("cp.async.bulk.prefetch.L2.global [%0], %1;" ::"l"(p), "r"(bytes) : "memory");
}
__device__ __forceinline__ unsigned ld_acquire(const unsigned* p) {
    unsigned v; asm volatile("ld.acquire.gpu.global.u32 %0, [%1];" : "=r"(v) : "l"(p) : "memory"); return v;
}
__device__ __forceinline__ uint4 ld_acquire4(const unsigned* p) {
    uint4 v;
    asm volatile("ld.acquire.gpu.global.v4.u32 {%0,%1,%2,%3}, [%4];" : "=r"(v.x), "=r"(v.y), "=r"(v.z), "=r"(v.w) : "l"(p) : "memory");
    return v;
}
__device__ __forceinline__ unsigned ld_relaxed(const unsigned* p) {
    unsigned v; asm volatile("ld.relaxed.gpu.global.u32 %0, [%1];" : "=r"(v) : "l"(p)); return v;
}
__device__ __forceinline__ void st_relaxed(unsigned* p, unsigned v) {
    asm volatile("st.relaxed.gpu.global.u32 [%0], %1;" ::"l"(p), "r"(v) : "memory");
}
__device__ __forceinline__ void red_relaxed(unsigned* p, unsigned v) {
    asm volatile("red.relaxed.gpu.global.add.u32 [%0], %1;" ::"l"(p), "r"(v) : "memory");
}
__device__ __forceinline__ void fence_gpu() { asm volatile("fence.acq_rel.gpu;" ::: "memory"); }
__device__ __forceinline__ void fence_async_smem() { asm volatile("fence.proxy.async.shared::cta;" ::: "memory"); }
__device__ __forceinline__ void fence_async_global() { asm volatile("fence.proxy.async.global;" ::: "memory"); }
__device__ __forceinline__ void wait_count(const unsigned* p, unsigned target) {
    uint32_t it = 0;
    while ((int)(ld_acquire(p) - target) < 0) trap_if_gt(++it, 1u << 22);
}
__device__ __forceinline__ void wait_count_warp(const unsigned* p, unsigned target) {
    uint32_t it = 0;
    while (__any_sync(0xffffffffu, (int)(ld_acquire(p) - target) < 0)) trap_if_gt(++it, 1u << 22);
}
__device__ __forceinline__ void red_f32(float* p, float a) {
    asm volatile("red.relaxed.gpu.global.add.f32 [%0], %1;" ::"l"(p), "f"(a) : "memory");
}
__device__ __forceinline__ void red_f32x2(float* p, float a, float b) {
    asm volatile("red.relaxed.gpu.global.add.v2.f32 [%0], {%1, %2};" ::"l"(p), "f"(a), "f"(b) : "memory");
}
__device__ __forceinline__ void red_f32x4(float* p, float a, float b, float c, float d) {
    asm volatile("red.relaxed.gpu.global.add.v4.f32 [%0], {%1, %2, %3, %4};" ::"l"(p), "f"(a), "f"(b), "f"(c), "f"(d) : "memory");
}
__device__ __forceinline__ float4 ld_l2_f4(const float* p) {
    float4 v;
    asm volatile("ld.relaxed.gpu.global.v4.f32 {%0,%1,%2,%3}, [%4];" : "=f"(v.x), "=f"(v.y), "=f"(v.z), "=f"(v.w) : "l"(p) : "memory");
    return v;
}
__device__ __forceinline__ float2 ld_l2_f2(const float* p) {
    float2 v;
    asm volatile("ld.relaxed.gpu.global.v2.f32 {%0,%1}, [%2];" : "=f"(v.x), "=f"(v.y) : "l"(p) : "memory");
    return v;
}
__device__ __forceinline__ float ld_l2_f(const float* p) {
    float v;
    asm volatile("ld.relaxed.gpu.global.f32 %0, [%1];" : "=f"(v) : "l"(p) : "memory");
    return v;
}
__device__ __forceinline__ uint4 ldg_nc(const void* p) {
    uint4 v;
    asm volatile("ld.global.nc.L1::no_allocate.v4.u32 {%0,%1,%2,%3}, [%4];" : "=r"(v.x), "=r"(v.y), "=r"(v.z), "=r"(v.w) : "l"(p));
    return v;
}
__device__ __forceinline__ void stg128(void* p, uint32_t a, uint32_t b, uint32_t c, uint32_t d) {
    asm volatile("st.global.v4.u32 [%0], {%1,%2,%3,%4};" ::"l"(p), "r"(a), "r"(b), "r"(c), "r"(d) : "memory");
}
__device__ __forceinline__ uint4 lds128(uint32_t a) {
    uint4 v;
    asm volatile("ld.shared.v4.u32 {%0,%1,%2,%3}, [%4];" : "=r"(v.x), "=r"(v.y), "=r"(v.z), "=r"(v.w) : "r"(a) : "memory");
    return v;
}
__device__ __forceinline__ float2 lds_f2(uint32_t a) {
    float2 v;
    asm volatile("ld.shared.v2.f32 {%0,%1}, [%2];" : "=f"(v.x), "=f"(v.y) : "r"(a) : "memory");
    return v;
}
__device__ __forceinline__ void sts_f2(uint32_t a, float x, float y) {
    asm volatile("st.shared.v2.f32 [%0], {%1,%2};" ::"r"(a), "f"(x), "f"(y) : "memory");
}
__device__ __forceinline__ void sts64(uint32_t a, uint32_t x, uint32_t y) {
    asm volatile("st.shared.v2.u32 [%0], {%1,%2};" ::"r"(a), "r"(x), "r"(y) : "memory");
}
__device__ __forceinline__ void sts128(uint32_t a, uint32_t x, uint32_t y, uint32_t z, uint32_t w) {
    asm volatile("st.shared.v4.u32 [%0], {%1,%2,%3,%4};" ::"r"(a), "r"(x), "r"(y), "r"(z), "r"(w) : "memory");
}
__device__ __forceinline__ void stsm4(uint32_t a, uint32_t r0, uint32_t r1, uint32_t r2, uint32_t r3) {
    asm volatile("stmatrix.sync.aligned.m8n8.x4.shared.b16 [%0], {%1,%2,%3,%4};" ::"r"(a), "r"(r0), "r"(r1), "r"(r2), "r"(r3) : "memory");
}
__device__ __forceinline__ void ldsm4(uint32_t a, uint32_t& r0, uint32_t& r1, uint32_t& r2, uint32_t& r3) {
    asm volatile("ldmatrix.sync.aligned.m8n8.x4.shared.b16 {%0,%1,%2,%3}, [%4];" : "=r"(r0), "=r"(r1), "=r"(r2), "=r"(r3) : "r"(a) : "memory");
}
__device__ __forceinline__ void ldsm4t(uint32_t a, uint32_t& r0, uint32_t& r1, uint32_t& r2, uint32_t& r3) {
    asm volatile("ldmatrix.sync.aligned.m8n8.x4.trans.shared.b16 {%0,%1,%2,%3}, [%4];" : "=r"(r0), "=r"(r1), "=r"(r2), "=r"(r3) : "r"(a) : "memory");
}
__device__ __forceinline__ void mma16816(float* c, const uint32_t* a, uint32_t b0, uint32_t b1) {
    asm("mma.sync.aligned.m16n8k16.row.col.f32.bf16.bf16.f32 {%0,%1,%2,%3}, {%4,%5,%6,%7}, {%8,%9}, {%0,%1,%2,%3};"
                 : "+f"(c[0]), "+f"(c[1]), "+f"(c[2]), "+f"(c[3])
                 : "r"(a[0]), "r"(a[1]), "r"(a[2]), "r"(a[3]), "r"(b0), "r"(b1));
}
__device__ __forceinline__ uint32_t pack_bf16(float lo, float hi) {
    uint32_t r; asm("cvt.rn.bf16x2.f32 %0, %1, %2;" : "=r"(r) : "f"(hi), "f"(lo)); return r;
}
__device__ __forceinline__ float bf_lo(uint32_t w) { return __uint_as_float(w << 16); }
__device__ __forceinline__ float bf_hi(uint32_t w) { return __uint_as_float(w & 0xffff0000u); }
__device__ __forceinline__ float ex2(float x) { float r; asm("ex2.approx.ftz.f32 %0, %1;" : "=f"(r) : "f"(x)); return r; }
__device__ __forceinline__ float rcp(float x) { float r; asm("rcp.approx.ftz.f32 %0, %1;" : "=f"(r) : "f"(x)); return r; }
__device__ __forceinline__ void bar_sync(int id, int n) { asm volatile("bar.sync %0, %1;" ::"r"(id), "r"(n) : "memory"); }

__device__ __forceinline__ uint32_t desc_lo(uint32_t addr) { return ((addr & 0x3FFFF) >> 4) | (512u << 16); }
#define DESC_HI "0x40000040"
__device__ __forceinline__ void wg_fence() { asm volatile("wgmma.fence.sync.aligned;" ::: "memory"); }
__device__ __forceinline__ void wg_commit() { asm volatile("wgmma.commit_group.sync.aligned;" ::: "memory"); }
template <int N> __device__ __forceinline__ void wg_wait() { asm volatile("wgmma.wait_group.sync.aligned %0;" ::"n"(N) : "memory"); }
template <int N> __device__ __forceinline__ void fence_acc(float* d) {
#pragma unroll
    for (int i = 0; i < N; i++) asm volatile("" : "+f"(d[i])::"memory");
}
#define R4(o) "+f"(d[o + 0]), "+f"(d[o + 1]), "+f"(d[o + 2]), "+f"(d[o + 3])
#define R8(o) R4(o), R4(o + 4)
__device__ __forceinline__ void wgmma_n128(float* d, uint32_t da, uint32_t db, int sc) {
    asm volatile("{.reg .pred p; .reg .b64 da, db; setp.ne.b32 p, %66, 0; mov.b64 da, {%64, " DESC_HI "}; mov.b64 db, {%65, " DESC_HI "};\n"
                 "wgmma.mma_async.sync.aligned.m64n128k16.f32.bf16.bf16 {%0,%1,%2,%3,%4,%5,%6,%7,%8,%9,%10,%11,%12,%13,%14,%15,%16,%17,%18,%19,%20,%21,%22,%23,%24,%25,%26,%27,%28,%29,%30,%31,"
                 "%32,%33,%34,%35,%36,%37,%38,%39,%40,%41,%42,%43,%44,%45,%46,%47,%48,%49,%50,%51,%52,%53,%54,%55,%56,%57,%58,%59,%60,%61,%62,%63}, da, db, p, 1, 1, 0, 1;}"
                 : R8(0), R8(8), R8(16), R8(24), R8(32), R8(40), R8(48), R8(56)
                 : "r"(da), "r"(db), "r"(sc));
}
__device__ __forceinline__ void wgmma_n64(float* d, uint32_t da, uint32_t db, int sc) {
    asm volatile("{.reg .pred p; .reg .b64 da, db; setp.ne.b32 p, %34, 0; mov.b64 da, {%32, " DESC_HI "}; mov.b64 db, {%33, " DESC_HI "};\n"
                 "wgmma.mma_async.sync.aligned.m64n64k16.f32.bf16.bf16 {%0,%1,%2,%3,%4,%5,%6,%7,%8,%9,%10,%11,%12,%13,%14,%15,%16,%17,%18,%19,%20,%21,%22,%23,%24,%25,%26,%27,%28,%29,%30,%31}, da, db, p, 1, 1, 0, 1;}"
                 : R8(0), R8(8), R8(16), R8(24)
                 : "r"(da), "r"(db), "r"(sc));
}
__device__ __forceinline__ void wgmma_n40_tt(float* d, uint32_t da, uint32_t db, int sc) {
    asm volatile("{.reg .pred p; .reg .b64 da, db; setp.ne.b32 p, %22, 0; mov.b64 da, {%20, " DESC_HI "}; mov.b64 db, {%21, " DESC_HI "};\n"
                 "wgmma.mma_async.sync.aligned.m64n40k16.f32.bf16.bf16 {%0,%1,%2,%3,%4,%5,%6,%7,%8,%9,%10,%11,%12,%13,%14,%15,%16,%17,%18,%19}, da, db, p, 1, 1, 1, 1;}"
                 : R8(0), R8(8), R4(16)
                 : "r"(da), "r"(db), "r"(sc));
}

__device__ __forceinline__ void wgmma_n8_tt(float* d, uint32_t da, uint32_t db, int sc) {
    asm volatile("{.reg .pred p; .reg .b64 da, db; setp.ne.b32 p, %6, 0; mov.b64 da, {%4, " DESC_HI "}; mov.b64 db, {%5, " DESC_HI "};\n"
                 "wgmma.mma_async.sync.aligned.m64n8k16.f32.bf16.bf16 {%0,%1,%2,%3}, da, db, p, 1, 1, 1, 1;}"
                 : R4(0)
                 : "r"(da), "r"(db), "r"(sc));
}

__device__ __forceinline__ void red_f32_if(float* p, float a, bool pred) {
    asm volatile("{.reg .pred p; setp.ne.u32 p, %2, 0; @p red.relaxed.gpu.global.add.f32 [%0], %1;}" ::"l"(p), "f"(a), "r"((uint32_t)pred) : "memory");
}
__device__ __forceinline__ void stg_f2_if(float* p, float a, float b, bool pred) {
    asm volatile("{.reg .pred p; setp.ne.u32 p, %3, 0; @p st.global.v2.f32 [%0], {%1,%2};}" ::"l"(p), "f"(a), "f"(b), "r"((uint32_t)pred) : "memory");
}
__device__ __forceinline__ void stg64(void* p, uint32_t a, uint32_t b) {
    asm volatile("st.global.v2.u32 [%0], {%1,%2};" ::"l"(p), "r"(a), "r"(b) : "memory");
}
__device__ __forceinline__ void store_pair(__nv_bfloat16* p, uint32_t r0, uint32_t r1, bool odd) {
    const uint32_t x = __shfl_xor_sync(0xffffffffu, odd ? r0 : r1, 1);
    stg64(p, odd ? x : r0, odd ? r1 : x);
}
__device__ __forceinline__ void mma16816_z(float* c, const uint32_t* a, uint32_t b0, uint32_t b1) {
    asm("mma.sync.aligned.m16n8k16.row.col.f32.bf16.bf16.f32 {%0,%1,%2,%3}, {%4,%5,%6,%7}, {%8,%9}, {%10,%10,%10,%10};"
                 : "=f"(c[0]), "=f"(c[1]), "=f"(c[2]), "=f"(c[3])
                 : "r"(a[0]), "r"(a[1]), "r"(a[2]), "r"(a[3]), "r"(b0), "r"(b1), "f"(0.f));
}
__device__ __forceinline__ uint32_t max2(uint32_t a, uint32_t b) { uint32_t r; asm("max.bf16x2 %0, %1, %2;" : "=r"(r) : "r"(a), "r"(b)); return r; }
__device__ __forceinline__ uint32_t min2(uint32_t a, uint32_t b) { uint32_t r; asm("min.bf16x2 %0, %1, %2;" : "=r"(r) : "r"(a), "r"(b)); return r; }
__device__ __forceinline__ void bar_arrive(int id, int n) { asm volatile("bar.arrive %0, %1;" ::"r"(id), "r"(n) : "memory"); }
__device__ __forceinline__ void mbar_arrive_n_if(uint32_t bar, uint32_t n, bool pred) {
    asm volatile("{.reg .pred p; setp.ne.u32 p, %1, 0; @p mbarrier.arrive.shared::cta.b64 _, [%0], %2;}" ::"r"(bar), "r"((uint32_t)pred), "r"(n) : "memory");
}
__device__ __forceinline__ float4 lds_f4(uint32_t a) {
    float4 v;
    asm volatile("ld.shared.v4.f32 {%0,%1,%2,%3}, [%4];" : "=f"(v.x), "=f"(v.y), "=f"(v.z), "=f"(v.w) : "r"(a) : "memory");
    return v;
}
__device__ __forceinline__ uint4 ld_tagged(const unsigned long long* p) {
    unsigned long long a, b;
    asm volatile("ld.acquire.gpu.global.v2.b64 {%0,%1}, [%2];" : "=l"(a), "=l"(b) : "l"(p) : "memory");
    return make_uint4((unsigned)a, (unsigned)(a >> 32), (unsigned)b, (unsigned)(b >> 32));
}
__device__ __forceinline__ uint4 ld_tagged_rlx(const unsigned long long* p) {
    unsigned long long a, b;
    asm volatile("ld.relaxed.gpu.global.v2.b64 {%0,%1}, [%2];" : "=l"(a), "=l"(b) : "l"(p) : "memory");
    return make_uint4((unsigned)a, (unsigned)(a >> 32), (unsigned)b, (unsigned)(b >> 32));
}
__device__ __forceinline__ void st_tagged_if(unsigned long long* p, float a, float b, unsigned tag, bool pred) {
    const unsigned long long t = (unsigned long long)tag << 32;
    asm volatile("{.reg .pred p; setp.ne.u32 p, %3, 0; @p st.relaxed.gpu.global.v2.b64 [%0], {%1,%2};}"
                 ::"l"(p), "l"(t | __float_as_uint(a)), "l"(t | __float_as_uint(b)), "r"((uint32_t)pred) : "memory");
}

__device__ __forceinline__ void store_tile(uint32_t tile_rows, __nv_bfloat16* gdst, const uint32_t* lo, const uint32_t* hi, int lane) {
    const int r = lane & 15;
#pragma unroll
    for (int b = 0; b < 4; b++)
        stsm4(tile_rows + r * 128 + (((2 * b + (lane >> 4)) ^ (r & 7)) << 4), lo[2 * b], hi[2 * b], lo[2 * b + 1], hi[2 * b + 1]);
    __syncwarp();
#pragma unroll
    for (int i = 0; i < 4; i++) {
        const int rr = 4 * i + (lane >> 3);
        const uint4 v = lds128(tile_rows + rr * 128 + (((lane & 7) ^ (rr & 7)) << 4));
        stg128(gdst + rr * DM + (lane & 7) * 8, v.x, v.y, v.z, v.w);
    }
}

template <bool NORM>
__device__ __forceinline__ void feature_map(const uint32_t* a, const uint32_t* wb, float c0, float c1, uint32_t* plus, uint32_t* minus, float* rs) {
    float p[8];
    mma16816_z(p, a, wb[0], wb[1]);
    mma16816_z(p + 4, a, wb[2], wb[3]);
    const uint32_t P0 = pack_bf16(p[0], p[2]), P1 = pack_bf16(p[1], p[3]), P2 = pack_bf16(p[4], p[6]), P3 = pack_bf16(p[5], p[7]);
    uint32_t mx = max2(max2(P0, P1), max2(P2, P3)), mn = min2(min2(P0, P1), min2(P2, P3));
#pragma unroll
    for (int s = 1; s <= 2; s <<= 1) {
        mx = max2(mx, __shfl_xor_sync(0xffffffffu, mx, s));
        mn = min2(mn, __shfl_xor_sync(0xffffffffu, mn, s));
    }
    const float mx0 = bf_lo(mx) * c0, mx1 = bf_hi(mx) * c1, mn0 = bf_lo(mn) * c0, mn1 = bf_hi(mn) * c1;
    p[0] = bf_lo(P0); p[2] = bf_hi(P0); p[1] = bf_lo(P1); p[3] = bf_hi(P1);
    p[4] = bf_lo(P2); p[6] = bf_hi(P2); p[5] = bf_lo(P3); p[7] = bf_hi(P3);
    float ep[8], em[8];
#pragma unroll
    for (int i = 0; i < 8; i++) {
        const bool r1 = (i & 2);
        ep[i] = ex2(fmaf(p[i], r1 ? c1 : c0, r1 ? -mx1 : -mx0));
        em[i] = ex2(fmaf(p[i], r1 ? -c1 : -c0, r1 ? mn1 : mn0));
    }
    float sp[4], sm[4];
#pragma unroll
    for (int i = 0; i < 4; i++) { plus[i] = pack_bf16(ep[2 * i], ep[2 * i + 1]); minus[i] = pack_bf16(em[2 * i], em[2 * i + 1]); }
    mma16816_z(sp, plus, 0x3f803f80u, 0x3f803f80u);
    mma16816_z(sm, minus, 0x3f803f80u, 0x3f803f80u);
    rs[0] = rcp(sp[0]); rs[1] = rcp(sp[2]); rs[2] = rcp(sm[0]); rs[3] = rcp(sm[2]);
    if (NORM) {
#pragma unroll
        for (int i = 0; i < 4; i++) {
            plus[i] = pack_bf16(ep[2 * i] * rs[i & 1], ep[2 * i + 1] * rs[i & 1]);
            minus[i] = pack_bf16(em[2 * i] * rs[2 + (i & 1)], em[2 * i + 1] * rs[2 + (i & 1)]);
        }
    }
}

template <bool SCALE>
__device__ __forceinline__ void ln_frag(const float* acc, uint32_t cs_addr, float rs0, float nm0, float rs1, float nm1, uint32_t* a) {
    const float2 c0 = lds_f2(cs_addr), c1 = lds_f2(cs_addr + 32);
    const float s0 = SCALE ? rs0 : 1.f, s1 = SCALE ? rs1 : 1.f;
    a[0] = pack_bf16(fmaf(nm0, c0.x, acc[0]) * s0, fmaf(nm0, c0.y, acc[1]) * s0);
    a[1] = pack_bf16(fmaf(nm1, c0.x, acc[2]) * s1, fmaf(nm1, c0.y, acc[3]) * s1);
    a[2] = pack_bf16(fmaf(nm0, c1.x, acc[4]) * s0, fmaf(nm0, c1.y, acc[5]) * s0);
    a[3] = pack_bf16(fmaf(nm1, c1.x, acc[6]) * s1, fmaf(nm1, c1.y, acc[7]) * s1);
}

__device__ __forceinline__ uint32_t hh_pair(const float* ag, float4 cs, float nmean) {
    const float g0 = fmaf(nmean, cs.x, ag[0]), g1 = fmaf(nmean, cs.y, ag[1]);
    const float u0 = fmaf(nmean, cs.z, ag[32]), u1 = fmaf(nmean, cs.w, ag[33]);
    return pack_bf16(g0 * u0, g1 * u1);
}

struct Ring {
    int slot; uint32_t phase;
    __device__ __forceinline__ void adv() { if (++slot == NB) { slot = 0; phase ^= 1; } }
};

__global__ void __launch_bounds__(NTHREADS, 1) fused_kernel(const __grid_constant__ Params P) {
    extern __shared__ __align__(1024) uint8_t smem_raw[];
    const uint32_t sb = smem_u32(smem_raw);
    const int tid = threadIdx.x, lane = tid & 31;
    const int warp = __shfl_sync(0xffffffffu, tid >> 5, 0);
    unsigned role = blockIdx.x;
    if (P.use_smid) asm volatile("mov.u32 %0, %%smid;" : "=r"(role));
    role = P.role[role];
    const int m = role >> 3, j = role & 7;
    const bool helper = role >= 128;

    TL(0, tid == 0); TLG(0, tid == 0);
    float* const acc_j = g_acc + j * ACC_SIZE;
    unsigned* const cnt_j = g_cnt + j * 32;

    if (__builtin_expect(warp >= 8, 1)) {
        asm volatile("setmaxnreg.dec.sync.aligned.u32 72;");
        if (elect_one()) {
            if (warp == 8) {
                if (!helper) {
#pragma unroll
                    for (int i = 0; i < NB; i++) mbar_init(sb + BAR_FULLB + 8 * i, 1);
#pragma unroll
                    for (int i = 0; i < 2; i++) {
                        mbar_expect_tx(sb + BAR_FULLB + 8 * i, SLOT);
                        tma3d(sb + OFF_B + i * SLOT, &P.twkv, sb + BAR_FULLB + 8 * i, 64 * j, 64 * i, 1);
                    }
                }
            } else if (warp == 9) {
#pragma unroll
                for (int i = 0; i < 8; i++) mbar_init(sb + BAR_FULLA + 8 * i, 1);
#pragma unroll
                for (int i = 0; i < 2; i++) {
                    mbar_expect_tx(sb + BAR_FULLA + 8 * i, SLOT);
                    tma2d(sb + OFF_A + i * SLOT, helper ? &P.twq : &P.tx, sb + BAR_FULLA + 8 * i, helper ? DM + 128 * j : 64 * i, 128 * (helper ? i : m));
                }
            } else if (warp == 10) {
#pragma unroll
                for (int i = 0; i < 16; i++) mbar_init(sb + BAR_CS1 + 8 * i, i == 1 ? 160 : ((i == 0 || i >= 14) ? 32 : 4));
                trap_if_gt(sb & 1023, 0);
            } else {
#pragma unroll
                for (int i = 0; i < 14; i++) mbar_init(sb + (i < 8 ? BAR_EMPTYA : BAR_EMPTYB - 64) + 8 * i, 8);
            }
        }
        __syncwarp();
        const unsigned epoch = ld_relaxed(&g_epoch);
        bar_sync(0, NTHREADS);
        if (helper) {
            if (warp == 8) {
                if (elect_one()) {
#pragma unroll 1
                    for (int i = 2; i < 72; i++) {
                        const uint32_t full = sb + BAR_FULLA + 8 * (i & 7), dst = sb + OFF_A + (i & 7) * SLOT;
                        mbar_wait(sb + BAR_EMPTYA + 8 * (i & 7), ((i >> 3) & 1) ^ 1);
                        mbar_expect_tx(full, SLOT);
                        if (i < 24) {
                            tma2d(dst, &P.twq, full, (i < 16 ? DM + 64 * (i & 8) : 0) + 128 * j + 16 * (i & 4), 128 * (i & 3));
                        } else {
                            const int u = (i >> 3) - 3, c0 = 176 * (2 * j + (u & 1)) + 64 * (u >> 1);
                            tma2d(dst, &P.twg, full, c0, 64 * (i & 7));
                            tma2d(dst + 8192, &P.twu, full, c0, 64 * (i & 7));
                        }
                    }
                    prefetch_l2(P.wd + (size_t)j * 176128, 352256);
                }
            } else if (warp == 9) {
                wait_count_warp(g_cnt + (lane & 7) * 32, epoch * 32);
            }
            return;
        }
        if (warp == 8) {
            if (elect_one()) {
                if (m >= 3 && m < 8)
                    asm volatile("cp.async.bulk.prefetch.tensor.3d.L2.global [%0, {%1, %2, %3}];" ::"l"(&P.twkv), "r"(64 * j), "r"(64 * m), "r"(1) : "memory");
                if (j >= 3)
                    asm volatile("cp.async.bulk.prefetch.tensor.2d.L2.global [%0, {%1, %2}];" ::"l"(&P.tx), "r"(64 * j), "r"(128 * m) : "memory");
                Ring r{2, 0};
#pragma unroll 1
                for (int i = 2; i < 56; i++) {
                    const uint32_t full = sb + BAR_FULLB + 8 * r.slot, dst = sb + OFF_B + r.slot * SLOT;
                    mbar_wait(sb + BAR_EMPTYB + 8 * r.slot, r.phase ^ 1);
                    if (i >= 8 && i < 12) {
                        mbar_arrive(full);
                    } else {
                        if (i >= AHEAD && i < 6) mbar_wait(full - 8 * AHEAD, 0);
                        TL(64 + i, i >= 40);
                        mbar_expect_tx(full, SLOT);
                        if (i < 8) {
                            tma3d(dst, &P.twkv, full, 64 * j, 64 * i, 1);
                        } else if (i < 20) {
                            tma2d(dst, i < 16 ? &P.twq : &P.two, full, 64 * j, 128 * (i & 3));
                        } else if (i < 44) {
                            const int c = (i - 20) >> 3, kt = (i - 20) & 7;
                            tma2d(dst, &P.twg, full, 176 * j + 64 * c, 64 * kt);
                            tma2d(dst + 8192, &P.twu, full, 176 * j + 64 * c, 64 * kt);
                        } else {
                            const int c = (i - 44) >> 2, jj = (i & 3) * 2;
                            tma2d(dst, &P.twd, full, 64 * j, 176 * jj + 64 * c);
                            tma2d(dst + 8192, &P.twd, full, 64 * j, 176 * (jj + 1) + 64 * c);
                        }
                    }
                    r.adv();
                }
            }
            return;
        }
        if (warp == 9) {
            if (elect_one()) {
#pragma unroll 1
                for (int i = 2; i < 8; i++) {
                    if (i >= AHEAD + 1) mbar_wait(sb + BAR_FULLA + 8 * (i - AHEAD - 1), 0);
                    mbar_expect_tx(sb + BAR_FULLA + 8 * i, SLOT);
                    tma2d(sb + OFF_A + i * SLOT, &P.tx, sb + BAR_FULLA + 8 * i, 64 * i, 128 * m);
                }
#pragma unroll 1
                for (int i = 1; i < 10; i++) prefetch_tmap(&P.tx + i);
#pragma unroll 1
                for (int r = 1; r < 6; r++) {
                    const CUtensorMap* tm = &P.tx + min(r, 3);
                    const int cstep = r < 3 ? 64 : 192, cbase = r < 3 ? 0 : 64 * (r - 3), skip = r < 3 ? j : 8;
                    wait_count(g_flag + (m * 5 + r - 1) * 32, epoch * 16);
#pragma unroll 1
                    for (int t = 0; t < 8; t++) {
                        if (t == skip) continue;
                        mbar_wait(sb + BAR_EMPTYA + 8 * t, (r - 1) & 1);
                        TL(56 + 8 * r + t, true);
                        mbar_expect_tx(sb + BAR_FULLA + 8 * t, SLOT);
                        tma2d(sb + OFF_A + t * SLOT, tm, sb + BAR_FULLA + 8 * t, cbase + cstep * t, 128 * m);
                    }
                }
            }
            return;
        }
        const int a = warp - 10;
        {
            const int row = 16 * j + 8 * a + (lane >> 2);
            const uint32_t ra = sb + OFF_A + row * 128;
            float sh = 0.f, s0 = 0.f, s1 = 0.f, q0 = 0.f, q1 = 0.f;
#pragma unroll 1
            for (int kt = 0; kt < 8; kt++) {
                mbar_wait(sb + BAR_FULLA + 8 * kt, 0);
                if (kt == 0) sh = bf_lo(lds128(ra + ((row & 7) << 4)).x);
#pragma unroll
                for (int i = 0; i < 2; i++) {
                    const uint4 v = lds128(ra + kt * SLOT + (((2 * (lane & 3) + i) ^ (row & 7)) << 4));
                    const uint32_t ww[4] = {v.x, v.y, v.z, v.w};
#pragma unroll
                    for (int e = 0; e < 4; e++) {
                        const float d0 = bf_lo(ww[e]) - sh, d1 = bf_hi(ww[e]) - sh;
                        s0 += d0; q0 = fmaf(d0, d0, q0);
                        s1 += d1; q1 = fmaf(d1, d1, q1);
                    }
                }
            }
            s0 += s1; q0 += q1;
#pragma unroll
            for (int o = 1; o <= 2; o <<= 1) { s0 += __shfl_xor_sync(0xffffffffu, s0, o); q0 += __shfl_xor_sync(0xffffffffu, q0, o); }
            const float md = s0 * (1.f / DM);
            const float rs = rsqrtf(fmaxf(q0 * (1.f / DM) - md * md, 0.f) + 1e-5f);
            st_tagged_if(g_xstat + 2 * (128 * m + row), rs, -(sh + md), epoch, (lane & 3) == 0);
        }
        const unsigned long long* cs = g_cs + j * 768 + 2 * lane;
#pragma unroll 1
        for (int ev = -1; ev < 6; ev += (ev >= 2 + a) ? 2 - (ev == 2) : 1 + (ev == 2)) {
            if (ev >= 0) {
                mbar_wait(sb + BAR_PUB + 8 * (a * 6 + ev), 0);
                if (elect_one()) {
                    fence_async_global();
                    fence_gpu();
                    red_relaxed(ev == 0 ? cnt_j : g_flag + (m * 5 + ev - 1) * 32, ev < 3 ? 1 : 2);
                }
                __syncwarp();
            }
            const int nj = ev < 0 || (ev == 0 && a == 1) ? 1 : (ev == 2 && a == 0 ? 6 : 0);
#pragma unroll 1
            for (int c = 0; c < nj; c++) {
                uint4 v;
                uint32_t it = 0;
                while (true) {
                    v = ld_tagged(cs + (ev < 0 ? 128 * a : (ev == 0 ? 256 : 384 + 64 * c)));
                    if (!__any_sync(0xffffffffu, v.y != epoch || v.w != epoch)) break;
                    __nanosleep(100);
                    trap_if_gt(++it, 1u << 22);
                }
                sts64(ev == 2 ? sb + OFF_CS3 + (32 * (c >> 1) + lane) * 16 + 8 * (c & 1) : sb + OFF_CS1 + (ev < 0 ? 256 * (a + 1) : 0) + 8 * lane, v.x, v.z);
            }
            if (nj) mbar_arrive(sb + (ev == 2 ? BAR_CS3 : (ev == 0 ? BAR_CSQ : (a ? BAR_CSV : BAR_CS1))));
        }
        return;
    }
    const unsigned epoch = ld_relaxed(&g_epoch);
    uint32_t wraw[16];
    if (!helper) {
        const uint32_t* wp = reinterpret_cast<const uint32_t*>(P.wphi) + (4 * j) * 128 + (lane & 3) * 16 + (lane >> 2);
#pragma unroll
        for (int i = 0; i < 16; i++)
            asm volatile("ld.global.nc.u32 %0, [%1];" : "=r"(wraw[i]) : "l"(wp + (i >> 2) * 128 + ((i >> 1) & 1) * 64 + (i & 1) * 8));
    }
    asm volatile("setmaxnreg.inc.sync.aligned.u32 216;");
    bar_sync(0, NTHREADS);
    if (helper) {
        if (warp < 4) {
            sts128(sb + OFF_B + 16 * tid, 0x3f803f80u, 0x3f803f80u, 0x3f803f80u, 0x3f803f80u);
            for (int i = tid; i < 2 * ACC_SIZE / 4; i += 128) stg128(g_acc + 2 * j * ACC_SIZE + 4 * i, 0, 0, 0, 0);
            fence_async_smem();
            fence_gpu();
            bar_sync(1, 128);
            float acc[8];
            int i = 0;
#pragma unroll 1
            for (int job = 0; job < 12; job++) {
                const int n = job < 6 ? 4 : 8;
#pragma unroll 1
                for (int t = 0; t < n; t++, i++) {
                    mbar_wait(sb + BAR_FULLA + 8 * (i & 7), (i >> 3) & 1);
                    wg_fence();
#pragma unroll
                    for (int k = 0; k < 8; k++)
                        wgmma_n8_tt(acc + (k & 4), desc_lo(sb + OFF_A) + (i & 7) * (SLOT >> 4) + 128 * k, desc_lo(sb + OFF_B), (t | (k & 3)) != 0);
                    wg_commit();
                    wg_wait<1>();
                    mbar_arrive_n_if(sb + BAR_EMPTYA + 8 * ((i + 7) & 7), 2, lane == 0 && i > 0);
                }
                wg_wait<0>();
                fence_acc<8>(acc);
                const int q = lane & 3;
                const float lo = (q & 1) ? acc[2] : acc[0], hi = (q & 1) ? acc[6] : acc[4];
                const float v = job < 6 ? lo + hi : ((q & 2) ? hi : lo);
                unsigned long long* dst = g_cs + ((2 * j + (job & 1)) * 6 + (job >> 1)) * 128 + (q >> 1) * 64 + 16 * warp + 8 * (q & 1) + (lane >> 2);
                asm volatile("st.relaxed.gpu.global.b64 [%0], %1;" ::"l"(dst), "l"(((unsigned long long)epoch << 32) | __float_as_uint(v)) : "memory");
            }
        }
        return;
    }
    {
        const int w = warp >> 2, wv = warp & 3, g = lane >> 2, q = lane & 3;
        const int row_w = 128 * m + 16 * warp;
        const uint32_t sa = sb + OFF_A + w * 8192;
        const uint32_t dA = desc_lo(sa), dB = desc_lo(sb + OFF_B);
        const uint32_t pub = sb + BAR_PUB + 48 * w;
        const bool l0 = lane == 0;
        Ring rg{0, 0};
        int prev = 0;

        uint32_t wb[16];
        constexpr float L2E = 1.4426950408889634f;
        uint32_t fp[16], fm[16];
        float fr[16];
        float rs0, nm0, rs1, nm1;
        {
            float acc[64];
#pragma unroll 1
            for (int kt = 0; kt < 8; kt++) {
                mbar_waitc(sb + BAR_FULLA + 8 * kt, 0);
                mbar_waitc(sb + BAR_FULLB + 8 * rg.slot, rg.phase);
                const uint32_t da = dA + kt * (SLOT >> 4), db = dB + rg.slot * (SLOT >> 4);
                wg_fence();
#pragma unroll
                for (int k = 0; k < 4; k++) wgmma_n128(acc, da + 2 * k, db + 128 * k, (kt | k) != 0);
                wg_commit();
                wg_wait<1>();
                mbar_arrive_if(sb + BAR_EMPTYB + 8 * prev, l0 && kt > 0);
                prev = rg.slot; rg.adv();
            }
            {
                uint4 a, b;
                uint32_t it = 0;
                do {
                    a = ld_tagged_rlx(g_xstat + 2 * (row_w + g));
                    b = ld_tagged_rlx(g_xstat + 2 * (row_w + g + 8));
                    trap_if_gt(++it, 1u << 22);
                } while (__any_sync(0xffffffffu, a.y != epoch || a.w != epoch || b.y != epoch || b.w != epoch));
                rs0 = __uint_as_float(a.x); nm0 = __uint_as_float(a.z); rs1 = __uint_as_float(b.x); nm1 = __uint_as_float(b.z);
            }
#pragma unroll
            for (int i = 0; i < 8; i++) {
                wb[(i >> 1) * 4 + (i & 1)] = __byte_perm(wraw[2 * i], wraw[2 * i + 1], 0x5410);
                wb[(i >> 1) * 4 + 2 + (i & 1)] = __byte_perm(wraw[2 * i], wraw[2 * i + 1], 0x7632);
            }
            TL(17, tid == 0);
            mbar_waitc(sb + BAR_CS1, 0);
            TL(18, tid == 0);
            wg_wait<0>();
            fence_acc<64>(acc);
            mbar_arrive_if(sb + BAR_EMPTYB + 8 * prev, l0);
            TL(2, tid == 0);
#pragma unroll
            for (int i = 2; i < 6; i++) mbar_waitc(sb + BAR_FULLB + 8 * i, 1);
            const int lrow = 16 * warp + (lane & 15), ch = lane >> 4, sw = lane & 7;
            const uint32_t st = sb + OFF_B + 2 * SLOT + lrow * 128;
            uint32_t ka[16];
#pragma unroll
            for (int hh = 0; hh < 4; hh++)
                ln_frag<false>(acc + 8 * hh, sb + OFF_CS1 + (64 + 16 * hh + 2 * q) * 4, rs0, nm0, rs1, nm1, ka + 4 * hh);
#pragma unroll
            for (int hh = 0; hh < 4; hh++) feature_map<true>(ka + 4 * hh, wb + 4 * hh, rs0 * L2E, rs1 * L2E, fp + 4 * hh, fm + 4 * hh, fr);
#pragma unroll
            for (int hh = 0; hh < 4; hh++) {
                stsm4(st + (hh >> 1) * SLOT + (((4 * (hh & 1) + ch) ^ sw) << 4), fp[4 * hh], fp[4 * hh + 1], fp[4 * hh + 2], fp[4 * hh + 3]);
                stsm4(st + (hh >> 1) * SLOT + (((4 * (hh & 1) + 2 + ch) ^ sw) << 4), fm[4 * hh], fm[4 * hh + 1], fm[4 * hh + 2], fm[4 * hh + 3]);
            }
            mbar_waitc(sb + BAR_CSV, 0);
#pragma unroll
            for (int hh = 0; hh < 4; hh++) {
                uint32_t a[4];
                ln_frag<true>(acc + 32 + 8 * hh, sb + OFF_CS1 + (128 + 16 * hh + 2 * q) * 4, rs0, nm0, rs1, nm1, a);
                stsm4(st + (2 + (hh >> 1)) * SLOT + (((2 * (hh & 1) + ch) ^ sw) << 4), a[0], a[1], a[2], a[3]);
            }
            stsm4(st + (2 + ch) * SLOT + ((4 ^ sw) << 4), 0x3f803f80u, 0x3f803f80u, 0x3f803f80u, 0x3f803f80u);
            fence_async_smem();
            bar_sync(1, 256);
            float kvd[20];
            wg_fence();
#pragma unroll
            for (int k = 0; k < 8; k++)
                wgmma_n40_tt(kvd, dB + (2 + w) * (SLOT >> 4) + 128 * k, dB + (4 + w) * (SLOT >> 4) + 128 * k, k != 0);
            wg_commit();
            wg_wait<0>();
            fence_acc<20>(kvd);
            const bool h1 = wv >= 2;
            const int f = 16 * warp + g;
            float* kvp = acc_j + ACC_KV + f * 16 + 2 * q;
            red_f32x2(kvp, h1 ? kvd[8] : kvd[0], h1 ? kvd[9] : kvd[1]);
            red_f32x2(kvp + 128, h1 ? kvd[10] : kvd[2], h1 ? kvd[11] : kvd[3]);
            red_f32x2(kvp + 8, h1 ? kvd[12] : kvd[4], h1 ? kvd[13] : kvd[5]);
            red_f32x2(kvp + 136, h1 ? kvd[14] : kvd[6], h1 ? kvd[15] : kvd[7]);
            red_f32_if(acc_j + ACC_Z + f + 8 * (q & 1), q ? kvd[18] : kvd[16], q < 2);
            __syncwarp();
            mbar_arrive_if(pub, l0);
            mbar_arrive_if(sb + BAR_EMPTYB + 8 * (2 + (lane & 3)), lane < 4);
            TL(3, tid == 0);
        }
        uint32_t res_lo[8], res_hi[8];
        const uint32_t own_rows = sb + OFF_A + j * SLOT + warp * 2048;
        {
            float acc[32];
            rg.slot = 0; rg.phase = 0;
#pragma unroll 1
            for (int b = 0; b < 4; b++) {
                mbar_waitc(sb + BAR_FULLB + 8 * rg.slot, rg.phase);
                const uint32_t da = dA + b * (2 * SLOT >> 4), db = dB + rg.slot * (SLOT >> 4);
                wg_fence();
#pragma unroll
                for (int k = 0; k < 8; k++) wgmma_n64(acc, da + (k >> 2) * (SLOT >> 4) + (k & 3) * 2, db + 128 * k, (b | k) != 0);
                wg_commit();
                wg_wait<1>();
                mbar_arrive_if(sb + BAR_EMPTYB + 8 * prev, l0 && b > 0);
                prev = rg.slot; rg.adv();
            }
            wg_wait<0>();
            fence_acc<32>(acc);
            mbar_arrive_if(sb + BAR_EMPTYB + 8 * prev, l0);
            mbar_arrive_if(sb + BAR_EMPTYA + 8 * (lane & 7), lane < 8 && (lane | 1) != (j | 1));
            TL(4, tid == 0);
            mbar_waitc(sb + BAR_CSQ, 0);
            uint32_t qa[16];
#pragma unroll
            for (int hh = 0; hh < 4; hh++)
                ln_frag<false>(acc + 8 * hh, sb + OFF_CS1 + (16 * hh + 2 * q) * 4, rs0, nm0, rs1, nm1, qa + 4 * hh);
#pragma unroll
            for (int hh = 0; hh < 4; hh++) feature_map<false>(qa + 4 * hh, wb + 4 * hh, rs0 * L2E, rs1 * L2E, fp + 4 * hh, fm + 4 * hh, fr + 4 * hh);
#pragma unroll
            for (int b = 0; b < 4; b++)
                ldsm4(own_rows + (lane & 15) * 128 + (((2 * b + (lane >> 4)) ^ (lane & 7)) << 4),
                      res_lo[2 * b], res_hi[2 * b], res_lo[2 * b + 1], res_hi[2 * b + 1]);
            TL(5, tid == 0);
            if (warp == 0) wait_count_warp(cnt_j, epoch * 32);
            TL(6, tid == 0);
            bar_sync(1, 256);
            const uint32_t kvs = sb + OFF_A + (j ^ 1) * SLOT;
            {
                const float4 a0 = ld_l2_f4(acc_j + ACC_KV + 4 * tid), a1 = ld_l2_f4(acc_j + ACC_KV + 4 * (tid + 256));
                const float zz = ld_l2_f(acc_j + ACC_Z + (tid & 127));
                sts64(kvs + (tid >> 2) * 48 + (tid & 3) * 8, pack_bf16(a0.x, a0.y), pack_bf16(a0.z, a0.w));
                sts64(kvs + ((tid >> 2) + 64) * 48 + (tid & 3) * 8, pack_bf16(a1.x, a1.y), pack_bf16(a1.z, a1.w));
                const uint32_t z2 = pack_bf16(zz, zz);
                sts64(kvs + (tid & 127) * 48 + 32 + w * 8, z2, z2);
            }
            bar_sync(1, 256);
            uint32_t o_lo[8], o_hi[8];
#pragma unroll
            for (int hh = 0; hh < 4; hh++) {
                uint32_t b[8], zb[4];
                const uint32_t base = kvs + hh * 32 * 48;
                ldsm4t(base + (lane & 15) * 48 + (lane >> 4) * 16, b[0], b[1], b[2], b[3]);
                ldsm4t(base + (16 + (lane & 15)) * 48 + (lane >> 4) * 16, b[4], b[5], b[6], b[7]);
                ldsm4t(base + lane * 48 + 32, zb[0], zb[1], zb[2], zb[3]);
                float n0[4], n1[4], dn[4], m0[4], m1[4], dm[4];
                mma16816_z(n0, fp + 4 * hh, b[0], b[1]); mma16816_z(n1, fp + 4 * hh, b[2], b[3]); mma16816_z(dn, fp + 4 * hh, zb[0], zb[1]);
                mma16816_z(m0, fm + 4 * hh, b[4], b[5]); mma16816_z(m1, fm + 4 * hh, b[6], b[7]); mma16816_z(dm, fm + 4 * hh, zb[2], zb[3]);
                const float* r = fr + 4 * hh;
                const float i0 = rcp(fmaf(dn[0], r[0], fmaf(dm[0], r[2], 1e-6f))), i1 = rcp(fmaf(dn[2], r[1], fmaf(dm[2], r[3], 1e-6f)));
                const float p0 = r[0] * i0, q0 = r[2] * i0, p1 = r[1] * i1, q1 = r[3] * i1;
                o_lo[2 * hh] = pack_bf16(fmaf(n0[0], p0, m0[0] * q0), fmaf(n0[1], p0, m0[1] * q0));
                o_hi[2 * hh] = pack_bf16(fmaf(n0[2], p1, m0[2] * q1), fmaf(n0[3], p1, m0[3] * q1));
                o_lo[2 * hh + 1] = pack_bf16(fmaf(n1[0], p0, m1[0] * q0), fmaf(n1[1], p0, m1[1] * q0));
                o_hi[2 * hh + 1] = pack_bf16(fmaf(n1[2], p1, m1[2] * q1), fmaf(n1[3], p1, m1[3] * q1));
            }
            store_tile(own_rows, g_o + (size_t)row_w * DM + 64 * j, o_lo, o_hi, lane);
            fence_async_smem();
            __syncwarp();
            mbar_arrive_if(pub + 8, l0);
            mbar_arrive_if(sb + BAR_EMPTYA + 8 * (j ^ 1), l0);
            TL(7, tid == 0);
        }
        {
            float acc[32];
#pragma unroll
            for (int t = 0; t < 8; t++) {
                acc[4 * t] = bf_lo(res_lo[t]); acc[4 * t + 1] = bf_hi(res_lo[t]);
                acc[4 * t + 2] = bf_lo(res_hi[t]); acc[4 * t + 3] = bf_hi(res_hi[t]);
            }
            fence_acc<32>(acc);
#pragma unroll 1
            for (int kp = 0; kp < 4; kp++) {
                mbar_waitc(sb + BAR_FULLB + 8 * rg.slot, rg.phase);
#pragma unroll
                for (int hf = 0; hf < 2; hf++) {
                    const int kt = 2 * kp + hf;
                    mbar_waitc(sb + BAR_FULLA + 8 * kt, kt != j);
                    TL(8, kt == 0 && tid == 0);
                    const uint32_t da = dA + kp * (2 * SLOT >> 4), db = dB + rg.slot * (SLOT >> 4);
                    wg_fence();
#pragma unroll
                    for (int k = 0; k < 4; k++) wgmma_n64(acc, da + hf * (SLOT >> 4) + 2 * k, db + (hf * 4 + k) * 128, 1);
                    wg_commit();
                    wg_wait<1>();
                    mbar_arrive_if(sb + BAR_EMPTYA + 8 * ((kt + 7) & 7), l0 && kt > 0 && kt - 1 != j);
                    if (hf == 0) mbar_arrive_if(sb + BAR_EMPTYB + 8 * prev, l0 && kt > 0);
                }
                prev = rg.slot; rg.adv();
            }
            wg_wait<0>();
            fence_acc<32>(acc);
            mbar_arrive_if(sb + BAR_EMPTYA + 8 * 7, l0 && j != 7);
            mbar_arrive_if(sb + BAR_EMPTYB + 8 * prev, l0);
            TL(9, tid == 0);
            float s0 = 0.f, s1 = 0.f;
#pragma unroll
            for (int t = 0; t < 8; t++) {
                res_lo[t] = pack_bf16(acc[4 * t], acc[4 * t + 1]);
                res_hi[t] = pack_bf16(acc[4 * t + 2], acc[4 * t + 3]);
                s0 += acc[4 * t] + acc[4 * t + 1];
                s1 += acc[4 * t + 2] + acc[4 * t + 3];
            }
            store_tile(own_rows, g_h + (size_t)row_w * DM + 64 * j, res_lo, res_hi, lane);
            s0 += __shfl_xor_sync(0xffffffffu, s0, 1); s1 += __shfl_xor_sync(0xffffffffu, s1, 1);
            s0 += __shfl_xor_sync(0xffffffffu, s0, 2); s1 += __shfl_xor_sync(0xffffffffu, s1, 2);
            const float mu0 = s0 * (1.f / 64), mu1 = s1 * (1.f / 64);
            float q0 = 0.f, q1 = 0.f;
#pragma unroll
            for (int t = 0; t < 8; t++) {
                float d;
                d = acc[4 * t] - mu0; q0 = fmaf(d, d, q0);
                d = acc[4 * t + 1] - mu0; q0 = fmaf(d, d, q0);
                d = acc[4 * t + 2] - mu1; q1 = fmaf(d, d, q1);
                d = acc[4 * t + 3] - mu1; q1 = fmaf(d, d, q1);
            }
            q0 += __shfl_xor_sync(0xffffffffu, q0, 1); q1 += __shfl_xor_sync(0xffffffffu, q1, 1);
            q0 += __shfl_xor_sync(0xffffffffu, q0, 2); q1 += __shfl_xor_sync(0xffffffffu, q1, 2);
            stg_f2_if(g_hstat + (row_w + g + 8 * (q & 1)) * 16 + 2 * j, q ? mu1 : mu0, q ? q1 : q0, q < 2);
            fence_async_smem();
            __syncwarp();
            mbar_arrive_if(pub + 16, l0);
            bar_sync(1, 256);
            TL(10, tid == 0);
        }
        if (w == 1) {
#pragma unroll 1
            for (int kt = 0; kt < 8; kt++) mbar_waitc(sb + BAR_FULLA + 8 * kt, 0);
            const float* sp = g_hstat + (128 * m + (tid & 127)) * 16;
            float4 v[4];
#pragma unroll
            for (int i = 0; i < 4; i++) v[i] = ld_l2_f4(sp + 4 * i);
            float mean = 0.f;
#pragma unroll
            for (int i = 0; i < 4; i++) mean += v[i].x + v[i].z;
            mean *= 0.125f;
            float m2 = 0.f, dv = 0.f;
#pragma unroll
            for (int i = 0; i < 4; i++) {
                m2 += v[i].y + v[i].w;
                dv = fmaf(v[i].x - mean, v[i].x - mean, dv); dv = fmaf(v[i].z - mean, v[i].z - mean, dv);
            }
            sts_f2(sb + OFF_CS1 + (tid & 127) * 8, -mean, __fdividef(1.f, fmaf(dv, 64.f, m2) * (1.f / DM) + 1e-5f));
            mbar_arrive(sb + BAR_CS3);
        }
        {
            float acc0[64], acc1[64];
            const uint32_t dA0 = desc_lo(sb + OFF_A);
#pragma unroll 1
            for (int c = w; c < 3; c += 2) {
                if (c > 0) bar_sync(1 + c, 256);
                rg.slot = (c == 2) ? 0 : 2 + 2 * c; rg.phase = (c == 0);
#pragma unroll 1
                for (int kt = 0; kt < 8; kt++) {
                    mbar_waitc(sb + BAR_FULLA + 8 * kt, 0);
                    mbar_waitc(sb + BAR_FULLB + 8 * rg.slot, rg.phase);
                    TL(44 + c * 2 + (kt == 1), (tid & 127) == 0 && kt < 2);
                    const uint32_t da = dA0 + kt * (SLOT >> 4), db = dB + rg.slot * (SLOT >> 4);
                    wg_fence();
#pragma unroll
                    for (int k = 0; k < 4; k++) {
                        wgmma_n128(acc0, da + 2 * k, db + 128 * k, (kt | k) != 0);
                        wgmma_n128(acc1, da + 512 + 2 * k, db + 128 * k, (kt | k) != 0);
                    }
                    wg_commit();
                    wg_wait<1>();
                    mbar_arrive_n_if(sb + BAR_EMPTYB + 8 * prev, 2, l0 && kt > 0);
                    mbar_arrive_if(sb + BAR_EMPTYA + 8 * ((kt + 7) & 7), l0 && kt > 0 && c > 0);
                    prev = rg.slot; rg.adv();
                }
                bar_arrive(2 + c, 256);
                mbar_waitc(sb + BAR_CS3, 0);
                float nm[4];
#pragma unroll
                for (int i = 0; i < 4; i++) nm[i] = lds_f2(sb + OFF_CS1 + (64 * (i >> 1) + 16 * wv + g + 8 * (i & 1)) * 8).x;
                wg_wait<0>();
                fence_acc<64>(acc0); fence_acc<64>(acc1);
                mbar_arrive_n_if(sb + BAR_EMPTYB + 8 * prev, 2, l0);
                mbar_arrive_if(sb + BAR_EMPTYA + 8 * 7, l0 && c > 0);
                TL(11 + c, (tid & 127) == 0);
                __nv_bfloat16* hp = g_hh + (size_t)(128 * m + 16 * wv + g) * FFP + 192 * j + 64 * c + (q & 1) * 8 + (q >> 1) * 4;
#pragma unroll
                for (int tp = 0; tp < 4; tp++) {
                    if (tp < 3 || c < 2) {
                        const uint32_t ca = sb + OFF_CS3 + (32 * c + 8 * tp + q) * 16;
                        const float4 c0 = lds_f4(ca), c1 = lds_f4(ca + 64);
                        store_pair(hp + 16 * tp, hh_pair(acc0 + 8 * tp, c0, nm[0]), hh_pair(acc0 + 8 * tp + 4, c1, nm[0]), q & 1);
                        store_pair(hp + 8 * FFP + 16 * tp, hh_pair(acc0 + 8 * tp + 2, c0, nm[1]), hh_pair(acc0 + 8 * tp + 6, c1, nm[1]), q & 1);
                        store_pair(hp + 64 * FFP + 16 * tp, hh_pair(acc1 + 8 * tp, c0, nm[2]), hh_pair(acc1 + 8 * tp + 4, c1, nm[2]), q & 1);
                        store_pair(hp + 72 * FFP + 16 * tp, hh_pair(acc1 + 8 * tp + 2, c0, nm[3]), hh_pair(acc1 + 8 * tp + 6, c1, nm[3]), q & 1);
                    }
                }
                __syncwarp();
                mbar_arrive_if(pub + 24 + 8 * c, l0);
                TL(54 + c, (tid & 127) == 0);
            }
        }
        {
            float acc[32];
            const uint32_t xch = sb + OFF_B + (tid & 127) * 16;
            if (w == 1) {
                float acc0[32];
                bar_sync(4, 256);
                rg.slot = 2; rg.phase = 1;
                const uint32_t dA0 = desc_lo(sb + OFF_A);
#define KT_P4(T, HF, NK)                                                                                    \
    do {                                                                                                    \
        const int s_ = (T) & 7;                                                                             \
        if (!(HF)) mbar_waitc(sb + BAR_FULLB + 8 * rg.slot, rg.phase);                                      \
        mbar_waitc(sb + BAR_FULLA + 8 * s_, (((T) >> 3) + 1) & 1);                                          \
        if (!(HF)) TL(30 + (T) / 2, tid == 128);                                                            \
        const uint32_t da_ = dA0 + s_ * (SLOT >> 4), db_ = dB + rg.slot * (SLOT >> 4) + (HF) * 512;         \
        wg_fence();                                                                                         \
        _Pragma("unroll") for (int k = 0; k < (NK); k++) {                                                  \
            wgmma_n64(acc0, da_ + 2 * k, db_ + 128 * k, ((T) | k) != 0);                                    \
            wgmma_n64(acc, da_ + 512 + 2 * k, db_ + 128 * k, ((T) | k) != 0);                               \
        }                                                                                                   \
        wg_commit();                                                                                        \
        wg_wait<1>();                                                                                       \
        mbar_arrive_n_if(sb + BAR_EMPTYA + 8 * (((T) + 7) & 7), 2, l0 && (T) > 0);                          \
        if (!(HF)) mbar_arrive_n_if(sb + BAR_EMPTYB + 8 * prev, 2, l0 && (T) > 0);                          \
        if (HF) { prev = rg.slot; rg.adv(); }                                                               \
    } while (0)
#pragma unroll 1
                for (int t = 0; t < 16; t += 2) { KT_P4(t, 0, 4); KT_P4(t + 1, 1, 4); }
#pragma unroll 1
                for (int t = 16; t < 24; t += 2) { KT_P4(t, 0, 3); KT_P4(t + 1, 1, 3); }
                wg_wait<0>();
                fence_acc<32>(acc0); fence_acc<32>(acc);
                TL(15, tid == 128);
#pragma unroll
                for (int t = 0; t < 8; t++)
                    sts128(xch + 2 * SLOT + t * 2048, __float_as_uint(acc0[4 * t]), __float_as_uint(acc0[4 * t + 1]),
                           __float_as_uint(acc0[4 * t + 2]), __float_as_uint(acc0[4 * t + 3]));
                bar_sync(5, 256);
            } else {
                bar_sync(5, 256);
#pragma unroll
                for (int t = 0; t < 8; t++) {
                    const float4 v = lds_f4(xch + 2 * SLOT + t * 2048);
                    acc[4 * t] = v.x; acc[4 * t + 1] = v.y; acc[4 * t + 2] = v.z; acc[4 * t + 3] = v.w;
                }
            }
            const float r0 = lds_f2(sb + OFF_CS1 + (16 * warp + g) * 8).y, r1 = lds_f2(sb + OFF_CS1 + (16 * warp + g + 8) * 8).y;
#pragma unroll
            for (int t = 0; t < 8; t++) {
                res_lo[t] = pack_bf16(fmaf(acc[4 * t], r0, bf_lo(res_lo[t])), fmaf(acc[4 * t + 1], r0, bf_hi(res_lo[t])));
                res_hi[t] = pack_bf16(fmaf(acc[4 * t + 2], r1, bf_lo(res_hi[t])), fmaf(acc[4 * t + 3], r1, bf_hi(res_hi[t])));
            }
            store_tile(own_rows, P.out + (size_t)row_w * DM + 64 * j, res_lo, res_hi, lane);
            if (tid == 0 && role == 0) g_epoch = epoch + 1;
            TL(16, tid == 0); TLG(1, tid == 0);
        }
    }
}

typedef CUresult (*EncodeFn)(CUtensorMap*, CUtensorMapDataType, cuuint32_t, void*, const cuuint64_t*, const cuuint64_t*,
                             const cuuint32_t*, const cuuint32_t*, CUtensorMapInterleave, CUtensorMapSwizzle,
                             CUtensorMapL2promotion, CUtensorMapFloatOOBfill);

static void make_map2d(EncodeFn enc, CUtensorMap* tm, const void* base, uint64_t cols, uint64_t rows, uint64_t pitch_elems,
                       uint32_t box_rows) {
    cuuint64_t gd[2] = {cols, rows};
    cuuint64_t gs[1] = {pitch_elems * 2};
    cuuint32_t bd[2] = {64, box_rows};
    cuuint32_t es[2] = {1, 1};
    enc(tm, CU_TENSOR_MAP_DATA_TYPE_BFLOAT16, 2, const_cast<void*>(base), gd, gs, bd, es, CU_TENSOR_MAP_INTERLEAVE_NONE,
        CU_TENSOR_MAP_SWIZZLE_128B, CU_TENSOR_MAP_L2_PROMOTION_L2_256B, CU_TENSOR_MAP_FLOAT_OOB_FILL_NONE);
}

}

extern "C" void kernel_launch(void* const* d_in, const int* in_sizes, int n_in, void* d_out, int out_size) {
    using namespace hk;
    (void)in_sizes; (void)n_in; (void)out_size;
    static EncodeFn enc = nullptr;
    static void *po = nullptr, *ph = nullptr, *phh = nullptr;
    static int std_layout = 0;
    if (!enc) {
        void* fn = nullptr;
        cudaDriverEntryPointQueryResult qr;
        cudaGetDriverEntryPoint("cuTensorMapEncodeTiled", &fn, cudaEnableDefault, &qr);
        enc = (EncodeFn)fn;
        cudaGetSymbolAddress(&po, g_o);
        cudaGetSymbolAddress(&ph, g_h);
        cudaGetSymbolAddress(&phh, g_hh);
        cudaFuncSetAttribute(fused_kernel, cudaFuncAttributeMaxDynamicSharedMemorySize, SMEM_BYTES);
        int dev = 0, sms = 0;
        cudaGetDevice(&dev);
        cudaDeviceGetAttribute(&sms, cudaDevAttrMultiProcessorCount, dev);
        cudaFuncSetAttribute(fused_kernel, cudaFuncAttributeNonPortableClusterSizeAllowed, 1);
        const int sizes[3] = {8, 9, 16}, want[3] = {15, 9, 7};
        bool ok = sms == NCTA;
        for (int i = 0; i < 3 && ok; i++) {
            cudaLaunchConfig_t cfg = {};
            cfg.gridDim = dim3(sizes[i] * 8); cfg.blockDim = dim3(NTHREADS); cfg.dynamicSmemBytes = SMEM_BYTES;
            cudaLaunchAttribute at;
            at.id = cudaLaunchAttributeClusterDimension;
            at.val.clusterDim.x = sizes[i]; at.val.clusterDim.y = 1; at.val.clusterDim.z = 1;
            cfg.attrs = &at; cfg.numAttrs = 1;
            int n = 0;
            ok = cudaOccupancyMaxActiveClusters(&n, fused_kernel, &cfg) == cudaSuccess && n == want[i];
        }
        (void)cudaGetLastError();
        std_layout = ok ? 1 : 0;
    }
    Params P;
    const __nv_bfloat16* x = (const __nv_bfloat16*)d_in[0];
    P.x = x;
    P.wqkv = (const __nv_bfloat16*)d_in[1];
    P.wphi = (const __nv_bfloat16*)d_in[2];
    P.wo = (const __nv_bfloat16*)d_in[3];
    P.wg = (const __nv_bfloat16*)d_in[5];
    P.wu = (const __nv_bfloat16*)d_in[6];
    P.wd = (const __nv_bfloat16*)d_in[7];
    P.out = (__nv_bfloat16*)d_out;
    P.use_smid = std_layout;
    for (int i = 0; i < NCTA; i++) {
        int role = i < 4 ? 128 + i : i - 4;
        if (std_layout) {
            const int tpc = i >> 1, odd = i & 1;
            if (tpc < 32) role = (tpc & 7) * 8 + (tpc >> 3) * 2 + odd;
            else if (tpc < 60) role = (8 + (tpc - 32) % 7) * 8 + ((tpc - 32) / 7) * 2 + odd;
            else if (tpc < 62) role = 128 + (tpc - 60) * 2 + odd;
            else role = 15 * 8 + (tpc - 62) * 2 + odd;
        }
        P.role[i] = (unsigned char)role;
    }
    make_map2d(enc, &P.tx, x, DM, SEQ, DM, 128);
    make_map2d(enc, &P.to, po, DM, SEQ, DM, 128);
    make_map2d(enc, &P.th, ph, DM, SEQ, DM, 128);
    make_map2d(enc, &P.thh, phh, FFP, SEQ, FFP, 128);
    make_map2d(enc, &P.twq, P.wqkv, 3 * DM, DM, 3 * DM, 128);
    make_map2d(enc, &P.two, P.wo, DM, DM, DM, 128);
    make_map2d(enc, &P.twg, P.wg, FF, DM, FF, 64);
    make_map2d(enc, &P.twu, P.wu, FF, DM, FF, 64);
    make_map2d(enc, &P.twd, P.wd, DM, FF, DM, 64);
    {
        cuuint64_t gd[3] = {(cuuint64_t)DM, (cuuint64_t)DM, 3};
        cuuint64_t gs[2] = {(cuuint64_t)3 * DM * 2, (cuuint64_t)DM * 2};
        cuuint32_t bd[3] = {64, 64, 2};
        cuuint32_t es[3] = {1, 1, 1};
        enc(&P.twkv, CU_TENSOR_MAP_DATA_TYPE_BFLOAT16, 3, const_cast<__nv_bfloat16*>(P.wqkv), gd, gs, bd, es,
            CU_TENSOR_MAP_INTERLEAVE_NONE, CU_TENSOR_MAP_SWIZZLE_128B, CU_TENSOR_MAP_L2_PROMOTION_L2_256B,
            CU_TENSOR_MAP_FLOAT_OOB_FILL_NONE);
    }
    fused_kernel<<<NCTA, NTHREADS, SMEM_BYTES>>>(P);
}
```

```cpp
#include <cuda_runtime.h>
#include <cuda_bf16.h>
#include <cuda.h>
#include <stdint.h>

namespace hk {

constexpr int SEQ = 2048, DM = 512, FF = 1376, FFP = 1536;
constexpr int NCTA = 132;
constexpr int NTHREADS = 384;
constexpr uint32_t SLOT = 16384;
constexpr uint32_t OFF_A = 0, OFF_B = 8 * SLOT, OFF_MISC = 14 * SLOT;
constexpr uint32_t BAR_FULLA = OFF_MISC + 0, BAR_EMPTYA = OFF_MISC + 64, BAR_FULLB = OFF_MISC + 128,
                   BAR_EMPTYB = OFF_MISC + 176, BAR_CS1 = OFF_MISC + 224, BAR_CS3 = OFF_MISC + 232,
                   BAR_CSQ = OFF_MISC + 240, BAR_CSV = OFF_MISC + 248;
constexpr uint32_t OFF_CS1 = OFF_MISC + 384;
constexpr uint32_t OFF_CS3 = OFF_CS1 + 1024;
constexpr uint32_t SMEM_BYTES = OFF_CS3 + 1536;
constexpr int NB = 6;
constexpr int AHEAD = 3;

constexpr int ACC_KV = 0, ACC_Z = 2048, ACC_SIZE = 2176;

__device__ __align__(1024) __nv_bfloat16 g_o[SEQ * DM];
__device__ __align__(1024) __nv_bfloat16 g_h[SEQ * DM];
__device__ __align__(1024) __nv_bfloat16 g_hh[SEQ * FFP];
__device__ __align__(128) float g_hstat[SEQ * 16];
__device__ __align__(128) unsigned long long g_xstat[SEQ * 2];
__device__ __align__(128) float g_acc[8 * ACC_SIZE];
__device__ __align__(128) unsigned g_cnt[8 * 32];
__device__ __align__(128) unsigned long long g_cs[8 * 6 * 128];
__device__ __align__(128) unsigned g_flag[16 * 5 * 32];
__device__ unsigned g_epoch = 1;

#define TL(i, pred) do {} while (0)
#define TLG(i, pred) do {} while (0)

struct Params {
    CUtensorMap tx, to, th, thh, twkv, twq, two, twg, twu, twd;
    const __nv_bfloat16 *x, *wqkv, *wphi, *wo, *wg, *wu, *wd;
    __nv_bfloat16* out;
    int use_smid;
    unsigned zero;
    unsigned char role[NCTA];
};

__device__ __forceinline__ uint32_t smem_u32(const void* p) { return (uint32_t)__cvta_generic_to_shared(p); }
__device__ __forceinline__ void mbar_init(uint32_t bar, uint32_t cnt) {
    asm volatile("mbarrier.init.shared::cta.b64 [%0], %1;" ::"r"(bar), "r"(cnt) : "memory");
}
__device__ __forceinline__ void mbar_expect_tx(uint32_t bar, uint32_t bytes) {
    asm volatile("mbarrier.arrive.expect_tx.shared::cta.b64 _, [%0], %1;" ::"r"(bar), "r"(bytes) : "memory");
}
__device__ __forceinline__ void mbar_arrive(uint32_t bar) {
    asm volatile("mbarrier.arrive.shared::cta.b64 _, [%0];" ::"r"(bar) : "memory");
}
__device__ __forceinline__ void mbar_arrive_if(uint32_t bar, bool pred) {
    asm volatile("{.reg .pred p; setp.ne.u32 p, %1, 0; @p mbarrier.arrive.shared::cta.b64 _, [%0];}" ::"r"(bar), "r"((uint32_t)pred) : "memory");
}
__device__ __forceinline__ bool mbar_try(uint32_t bar, uint32_t parity) {
    uint32_t ok;
    asm volatile("{.reg .pred p; mbarrier.try_wait.parity.shared::cta.b64 p, [%1], %2; selp.u32 %0,1,0,p;}"
                 : "=r"(ok) : "r"(bar), "r"(parity) : "memory");
    return ok;
}
__device__ __forceinline__ bool mbar_test(uint32_t bar, uint32_t parity) {
    uint32_t ok;
    asm volatile("{.reg .pred p; mbarrier.test_wait.parity.shared::cta.b64 p, [%1], %2; selp.u32 %0,1,0,p;}"
                 : "=r"(ok) : "r"(bar), "r"(parity) : "memory");
    return ok;
}
__device__ __forceinline__ void trap_if_gt(uint32_t v, uint32_t lim) {
    asm volatile("{.reg .pred p; setp.gt.u32 p, %0, %1; @p trap;}" ::"r"(v), "r"(lim));
}
__device__ __forceinline__ void mbar_wait(uint32_t bar, uint32_t parity) {
    asm volatile("{\n"
                 ".reg .pred P1, P2;\n"
                 ".reg .u32 c;\n"
                 "mov.u32 c, 0;\n"
                 "LAB_WAIT:\n"
                 "mbarrier.try_wait.parity.shared::cta.b64 P1, [%0], %1;\n"
                 "@P1 bra LAB_DONE;\n"
                 "add.u32 c, c, 1;\n"
                 "setp.gt.u32 P2, c, 4194304;\n"
                 "@P2 trap;\n"
                 "bra LAB_WAIT;\n"
                 "LAB_DONE:\n"
                 "}" ::"r"(bar), "r"(parity) : "memory");
}
__device__ __forceinline__ void mbar_waitc(uint32_t bar, uint32_t parity) {
    asm volatile("{\n"
                 ".reg .pred P1;\n"
                 "LAB_WAIT:\n"
                 "mbarrier.try_wait.parity.shared::cta.b64 P1, [%0], %1;\n"
                 "@!P1 bra LAB_WAIT;\n"
                 "}" ::"r"(bar), "r"(parity) : "memory");
}
__device__ __forceinline__ void tma2d(uint32_t dst, const CUtensorMap* tm, uint32_t bar, int c0, int c1) {
    asm volatile("cp.async.bulk.tensor.2d.shared::cluster.global.mbarrier::complete_tx::bytes [%0], [%1, {%3, %4}], [%2];"
                 ::"r"(dst), "l"(tm), "r"(bar), "r"(c0), "r"(c1) : "memory");
}
__device__ __forceinline__ void tma3d(uint32_t dst, const CUtensorMap* tm, uint32_t bar, int c0, int c1, int c2) {
    asm volatile("cp.async.bulk.tensor.3d.shared::cluster.global.mbarrier::complete_tx::bytes [%0], [%1, {%3, %4, %5}], [%2];"
                 ::"r"(dst), "l"(tm), "r"(bar), "r"(c0), "r"(c1), "r"(c2) : "memory");
}
__device__ __forceinline__ bool elect_one() {
    uint32_t ok;
    asm volatile("{.reg .pred p; elect.sync _|p, 0xffffffff; selp.u32 %0, 1, 0, p;}" : "=r"(ok));
    return ok;
}
__device__ __forceinline__ void prefetch_tmap(const CUtensorMap* tm) {
    asm volatile("prefetch.tensormap [%0];" ::"l"(tm) : "memory");
}
__device__ __forceinline__ void prefetch_l2(const void* p, uint32_t bytes) {
    asm volatile("cp.async.bulk.prefetch.L2.global [%0], %1;" ::"l"(p), "r"(bytes) : "memory");
}
__device__ __forceinline__ unsigned ld_acquire(const unsigned* p) {
    unsigned v; asm volatile("ld.acquire.gpu.global.u32 %0, [%1];" : "=r"(v) : "l"(p) : "memory"); return v;
}
__device__ __forceinline__ uint4 ld_acquire4(const unsigned* p) {
    uint4 v;
    asm volatile("ld.acquire.gpu.global.v4.u32 {%0,%1,%2,%3}, [%4];" : "=r"(v.x), "=r"(v.y), "=r"(v.z), "=r"(v.w) : "l"(p) : "memory");
    return v;
}
__device__ __forceinline__ unsigned ld_relaxed(const unsigned* p) {
    unsigned v; asm volatile("ld.relaxed.gpu.global.u32 %0, [%1];" : "=r"(v) : "l"(p)); return v;
}
__device__ __forceinline__ void st_relaxed(unsigned* p, unsigned v) {
    asm volatile("st.relaxed.gpu.global.u32 [%0], %1;" ::"l"(p), "r"(v) : "memory");
}
__device__ __forceinline__ void red_relaxed(unsigned* p, unsigned v) {
    asm volatile("red.relaxed.gpu.global.add.u32 [%0], %1;" ::"l"(p), "r"(v) : "memory");
}
__device__ __forceinline__ void fence_gpu() { asm volatile("fence.acq_rel.gpu;" ::: "memory"); }
__device__ __forceinline__ void fence_async_smem() { asm volatile("fence.proxy.async.shared::cta;" ::: "memory"); }
__device__ __forceinline__ void fence_async_global() { asm volatile("fence.proxy.async.global;" ::: "memory"); }
__device__ __forceinline__ void wait_count(const unsigned* p, unsigned target) {
    uint32_t it = 0;
    while ((int)(ld_acquire(p) - target) < 0) trap_if_gt(++it, 1u << 22);
}
__device__ __forceinline__ void wait_count_warp(const unsigned* p, unsigned target) {
    uint32_t it = 0;
    while (__any_sync(0xffffffffu, (int)(ld_acquire(p) - target) < 0)) trap_if_gt(++it, 1u << 22);
}
__device__ __forceinline__ void red_f32(float* p, float a) {
    asm volatile("red.relaxed.gpu.global.add.f32 [%0], %1;" ::"l"(p), "f"(a) : "memory");
}
__device__ __forceinline__ void red_f32x2(float* p, float a, float b) {
    asm volatile("red.relaxed.gpu.global.add.v2.f32 [%0], {%1, %2};" ::"l"(p), "f"(a), "f"(b) : "memory");
}
__device__ __forceinline__ void red_f32x4(float* p, float a, float b, float c, float d) {
    asm volatile("red.relaxed.gpu.global.add.v4.f32 [%0], {%1, %2, %3, %4};" ::"l"(p), "f"(a), "f"(b), "f"(c), "f"(d) : "memory");
}
__device__ __forceinline__ float4 ld_l2_f4(const float* p) {
    float4 v;
    asm volatile("ld.relaxed.gpu.global.v4.f32 {%0,%1,%2,%3}, [%4];" : "=f"(v.x), "=f"(v.y), "=f"(v.z), "=f"(v.w) : "l"(p) : "memory");
    return v;
}
__device__ __forceinline__ float2 ld_l2_f2(const float* p) {
    float2 v;
    asm volatile("ld.relaxed.gpu.global.v2.f32 {%0,%1}, [%2];" : "=f"(v.x), "=f"(v.y) : "l"(p) : "memory");
    return v;
}
__device__ __forceinline__ float ld_l2_f(const float* p) {
    float v;
    asm volatile("ld.relaxed.gpu.global.f32 %0, [%1];" : "=f"(v) : "l"(p) : "memory");
    return v;
}
__device__ __forceinline__ uint4 ldg_nc(const void* p) {
    uint4 v;
    asm volatile("ld.global.nc.L1::no_allocate.v4.u32 {%0,%1,%2,%3}, [%4];" : "=r"(v.x), "=r"(v.y), "=r"(v.z), "=r"(v.w) : "l"(p));
    return v;
}
__device__ __forceinline__ void stg128(void* p, uint32_t a, uint32_t b, uint32_t c, uint32_t d) {
    asm volatile("st.global.v4.u32 [%0], {%1,%2,%3,%4};" ::"l"(p), "r"(a), "r"(b), "r"(c), "r"(d) : "memory");
}
__device__ __forceinline__ uint4 lds128(uint32_t a) {
    uint4 v;
    asm volatile("ld.shared.v4.u32 {%0,%1,%2,%3}, [%4];" : "=r"(v.x), "=r"(v.y), "=r"(v.z), "=r"(v.w) : "r"(a) : "memory");
    return v;
}
__device__ __forceinline__ float2 lds_f2(uint32_t a) {
    float2 v;
    asm volatile("ld.shared.v2.f32 {%0,%1}, [%2];" : "=f"(v.x), "=f"(v.y) : "r"(a) : "memory");
    return v;
}
__device__ __forceinline__ void sts_f2(uint32_t a, float x, float y) {
    asm volatile("st.shared.v2.f32 [%0], {%1,%2};" ::"r"(a), "f"(x), "f"(y) : "memory");
}
__device__ __forceinline__ void sts64(uint32_t a, uint32_t x, uint32_t y) {
    asm volatile("st.shared.v2.u32 [%0], {%1,%2};" ::"r"(a), "r"(x), "r"(y) : "memory");
}
__device__ __forceinline__ void sts128(uint32_t a, uint32_t x, uint32_t y, uint32_t z, uint32_t w) {
    asm volatile("st.shared.v4.u32 [%0], {%1,%2,%3,%4};" ::"r"(a), "r"(x), "r"(y), "r"(z), "r"(w) : "memory");
}
__device__ __forceinline__ void stsm4(uint32_t a, uint32_t r0, uint32_t r1, uint32_t r2, uint32_t r3) {
    asm volatile("stmatrix.sync.aligned.m8n8.x4.shared.b16 [%0], {%1,%2,%3,%4};" ::"r"(a), "r"(r0), "r"(r1), "r"(r2), "r"(r3) : "memory");
}
__device__ __forceinline__ void ldsm4(uint32_t a, uint32_t& r0, uint32_t& r1, uint32_t& r2, uint32_t& r3) {
    asm volatile("ldmatrix.sync.aligned.m8n8.x4.shared.b16 {%0,%1,%2,%3}, [%4];" : "=r"(r0), "=r"(r1), "=r"(r2), "=r"(r3) : "r"(a) : "memory");
}
__device__ __forceinline__ void ldsm4t(uint32_t a, uint32_t& r0, uint32_t& r1, uint32_t& r2, uint32_t& r3) {
    asm volatile("ldmatrix.sync.aligned.m8n8.x4.trans.shared.b16 {%0,%1,%2,%3}, [%4];" : "=r"(r0), "=r"(r1), "=r"(r2), "=r"(r3) : "r"(a) : "memory");
}
__device__ __forceinline__ void mma16816(float* c, const uint32_t* a, uint32_t b0, uint32_t b1) {
    asm("mma.sync.aligned.m16n8k16.row.col.f32.bf16.bf16.f32 {%0,%1,%2,%3}, {%4,%5,%6,%7}, {%8,%9}, {%0,%1,%2,%3};"
                 : "+f"(c[0]), "+f"(c[1]), "+f"(c[2]), "+f"(c[3])
                 : "r"(a[0]), "r"(a[1]), "r"(a[2]), "r"(a[3]), "r"(b0), "r"(b1));
}
__device__ __forceinline__ uint32_t pack_bf16(float lo, float hi) {
    uint32_t r; asm("cvt.rn.bf16x2.f32 %0, %1, %2;" : "=r"(r) : "f"(hi), "f"(lo)); return r;
}
__device__ __forceinline__ float bf_lo(uint32_t w) { return __uint_as_float(w << 16); }
__device__ __forceinline__ float bf_hi(uint32_t w) { return __uint_as_float(w & 0xffff0000u); }
__device__ __forceinline__ float ex2(float x) { float r; asm("ex2.approx.ftz.f32 %0, %1;" : "=f"(r) : "f"(x)); return r; }
__device__ __forceinline__ float rcp(float x) { float r; asm("rcp.approx.ftz.f32 %0, %1;" : "=f"(r) : "f"(x)); return r; }
__device__ __forceinline__ void bar_sync(int id, int n) { asm volatile("bar.sync %0, %1;" ::"r"(id), "r"(n) : "memory"); }

typedef unsigned long long desc_t;
__device__ __forceinline__ desc_t desc_lo(uint32_t addr) { return (desc_t)(((addr & 0x3FFFF) >> 4) | (512u << 16)) | (0x40000040ull << 32); }
__device__ __forceinline__ void wg_fence() { asm volatile("wgmma.fence.sync.aligned;" ::: "memory"); }
__device__ __forceinline__ void wg_commit() { asm volatile("wgmma.commit_group.sync.aligned;" ::: "memory"); }
template <int N> __device__ __forceinline__ void wg_wait() { asm volatile("wgmma.wait_group.sync.aligned %0;" ::"n"(N) : "memory"); }
template <int N> __device__ __forceinline__ void fence_acc(float* d) {
#pragma unroll
    for (int i = 0; i < N; i++) asm volatile("" : "+f"(d[i])::"memory");
}
#define R4(o) "+f"(d[o + 0]), "+f"(d[o + 1]), "+f"(d[o + 2]), "+f"(d[o + 3])
#define R8(o) R4(o), R4(o + 4)
__device__ __forceinline__ void wgmma_n128(float* d, desc_t da, desc_t db, int sc) {
    asm volatile("{.reg .pred p; setp.ne.b32 p, %66, 0;\n"
                 "wgmma.mma_async.sync.aligned.m64n128k16.f32.bf16.bf16 {%0,%1,%2,%3,%4,%5,%6,%7,%8,%9,%10,%11,%12,%13,%14,%15,%16,%17,%18,%19,%20,%21,%22,%23,%24,%25,%26,%27,%28,%29,%30,%31,"
                 "%32,%33,%34,%35,%36,%37,%38,%39,%40,%41,%42,%43,%44,%45,%46,%47,%48,%49,%50,%51,%52,%53,%54,%55,%56,%57,%58,%59,%60,%61,%62,%63}, %64, %65, p, 1, 1, 0, 1;}"
                 : R8(0), R8(8), R8(16), R8(24), R8(32), R8(40), R8(48), R8(56)
                 : "l"(da), "l"(db), "r"(sc));
}
__device__ __forceinline__ void wgmma_n64(float* d, desc_t da, desc_t db, int sc) {
    asm volatile("{.reg .pred p; setp.ne.b32 p, %34, 0;\n"
                 "wgmma.mma_async.sync.aligned.m64n64k16.f32.bf16.bf16 {%0,%1,%2,%3,%4,%5,%6,%7,%8,%9,%10,%11,%12,%13,%14,%15,%16,%17,%18,%19,%20,%21,%22,%23,%24,%25,%26,%27,%28,%29,%30,%31}, %32, %33, p, 1, 1, 0, 1;}"
                 : R8(0), R8(8), R8(16), R8(24)
                 : "l"(da), "l"(db), "r"(sc));
}
__device__ __forceinline__ void wgmma_n40_tt(float* d, desc_t da, desc_t db, int sc) {
    asm volatile("{.reg .pred p; setp.ne.b32 p, %22, 0;\n"
                 "wgmma.mma_async.sync.aligned.m64n40k16.f32.bf16.bf16 {%0,%1,%2,%3,%4,%5,%6,%7,%8,%9,%10,%11,%12,%13,%14,%15,%16,%17,%18,%19}, %20, %21, p, 1, 1, 1, 1;}"
                 : R8(0), R8(8), R4(16)
                 : "l"(da), "l"(db), "r"(sc));
}

__device__ __forceinline__ void wgmma_n8_tt(float* d, desc_t da, desc_t db, int sc) {
    asm volatile("{.reg .pred p; setp.ne.b32 p, %6, 0;\n"
                 "wgmma.mma_async.sync.aligned.m64n8k16.f32.bf16.bf16 {%0,%1,%2,%3}, %4, %5, p, 1, 1, 1, 1;}"
                 : R4(0)
                 : "l"(da), "l"(db), "r"(sc));
}

__device__ __forceinline__ uint32_t readback(const void* p) {
    uint32_t v; asm volatile("ld.relaxed.gpu.global.u32 %0, [%1];" : "=r"(v) : "l"(p) : "memory"); return v;
}
__device__ __forceinline__ uint32_t atom_f32x2(float* p, float a, float b) {
    float x, y;
    asm volatile("atom.relaxed.gpu.global.add.v2.f32 {%0,%1}, [%2], {%3,%4};" : "=f"(x), "=f"(y) : "l"(p), "f"(a), "f"(b) : "memory");
    return __float_as_uint(x);
}
__device__ __forceinline__ uint32_t atom_f32_if(float* p, float a, bool pred) {
    float x = 0.f;
    asm volatile("{.reg .pred p; setp.ne.u32 p, %3, 0; @p atom.relaxed.gpu.global.add.f32 %0, [%1], %2;}" : "+f"(x) : "l"(p), "f"(a), "r"((uint32_t)pred) : "memory");
    return __float_as_uint(x);
}
__device__ __forceinline__ void signal_after(unsigned* cnt, uint32_t ack, uint32_t zero, bool pred) {
    asm volatile("{.reg .pred p; setp.ne.u32 p, %2, 0; @p red.relaxed.gpu.global.add.u32 [%0], %1;}"
                 ::"l"(cnt), "r"((ack & zero) + 1), "r"((uint32_t)pred) : "memory");
}
__device__ __forceinline__ void red_f32_if(float* p, float a, bool pred) {
    asm volatile("{.reg .pred p; setp.ne.u32 p, %2, 0; @p red.relaxed.gpu.global.add.f32 [%0], %1;}" ::"l"(p), "f"(a), "r"((uint32_t)pred) : "memory");
}
__device__ __forceinline__ void stg_f2_if(float* p, float a, float b, bool pred) {
    asm volatile("{.reg .pred p; setp.ne.u32 p, %3, 0; @p st.global.v2.f32 [%0], {%1,%2};}" ::"l"(p), "f"(a), "f"(b), "r"((uint32_t)pred) : "memory");
}
__device__ __forceinline__ void stg64(void* p, uint32_t a, uint32_t b) {
    asm volatile("st.global.v2.u32 [%0], {%1,%2};" ::"l"(p), "r"(a), "r"(b) : "memory");
}
__device__ __forceinline__ uint32_t store_pair(__nv_bfloat16* p, uint32_t r0, uint32_t r1, bool odd) {
    const uint32_t x = __shfl_xor_sync(0xffffffffu, odd ? r0 : r1, 1);
    stg64(p, odd ? x : r0, odd ? r1 : x);
    return readback(p);
}
__device__ __forceinline__ void mma16816_z(float* c, const uint32_t* a, uint32_t b0, uint32_t b1) {
    asm("mma.sync.aligned.m16n8k16.row.col.f32.bf16.bf16.f32 {%0,%1,%2,%3}, {%4,%5,%6,%7}, {%8,%9}, {%10,%10,%10,%10};"
                 : "=f"(c[0]), "=f"(c[1]), "=f"(c[2]), "=f"(c[3])
                 : "r"(a[0]), "r"(a[1]), "r"(a[2]), "r"(a[3]), "r"(b0), "r"(b1), "f"(0.f));
}
__device__ __forceinline__ uint32_t max2(uint32_t a, uint32_t b) { uint32_t r; asm("max.bf16x2 %0, %1, %2;" : "=r"(r) : "r"(a), "r"(b)); return r; }
__device__ __forceinline__ uint32_t min2(uint32_t a, uint32_t b) { uint32_t r; asm("min.bf16x2 %0, %1, %2;" : "=r"(r) : "r"(a), "r"(b)); return r; }
__device__ __forceinline__ void bar_arrive(int id, int n) { asm volatile("bar.arrive %0, %1;" ::"r"(id), "r"(n) : "memory"); }
__device__ __forceinline__ void mbar_arrive_n_if(uint32_t bar, uint32_t n, bool pred) {
    asm volatile("{.reg .pred p; setp.ne.u32 p, %1, 0; @p mbarrier.arrive.shared::cta.b64 _, [%0], %2;}" ::"r"(bar), "r"((uint32_t)pred), "r"(n) : "memory");
}
__device__ __forceinline__ float4 lds_f4(uint32_t a) {
    float4 v;
    asm volatile("ld.shared.v4.f32 {%0,%1,%2,%3}, [%4];" : "=f"(v.x), "=f"(v.y), "=f"(v.z), "=f"(v.w) : "r"(a) : "memory");
    return v;
}
__device__ __forceinline__ uint4 ld_tagged(const unsigned long long* p) {
    unsigned long long a, b;
    asm volatile("ld.acquire.gpu.global.v2.b64 {%0,%1}, [%2];" : "=l"(a), "=l"(b) : "l"(p) : "memory");
    return make_uint4((unsigned)a, (unsigned)(a >> 32), (unsigned)b, (unsigned)(b >> 32));
}
__device__ __forceinline__ uint4 ld_tagged_rlx(const unsigned long long* p) {
    unsigned long long a, b;
    asm volatile("ld.relaxed.gpu.global.v2.b64 {%0,%1}, [%2];" : "=l"(a), "=l"(b) : "l"(p) : "memory");
    return make_uint4((unsigned)a, (unsigned)(a >> 32), (unsigned)b, (unsigned)(b >> 32));
}
__device__ __forceinline__ void st_tagged_if(unsigned long long* p, float a, float b, unsigned tag, bool pred) {
    const unsigned long long t = (unsigned long long)tag << 32;
    asm volatile("{.reg .pred p; setp.ne.u32 p, %3, 0; @p st.relaxed.gpu.global.v2.b64 [%0], {%1,%2};}"
                 ::"l"(p), "l"(t | __float_as_uint(a)), "l"(t | __float_as_uint(b)), "r"((uint32_t)pred) : "memory");
}

template <bool ACK>
__device__ __forceinline__ uint32_t store_tile(uint32_t tile_rows, __nv_bfloat16* gdst, const uint32_t* lo, const uint32_t* hi, int lane) {
    const int r = lane & 15;
#pragma unroll
    for (int b = 0; b < 4; b++)
        stsm4(tile_rows + r * 128 + (((2 * b + (lane >> 4)) ^ (r & 7)) << 4), lo[2 * b], hi[2 * b], lo[2 * b + 1], hi[2 * b + 1]);
    __syncwarp();
    uint32_t ack = 0;
#pragma unroll
    for (int i = 0; i < 4; i++) {
        const int rr = 4 * i + (lane >> 3);
        const uint4 v = lds128(tile_rows + rr * 128 + (((lane & 7) ^ (rr & 7)) << 4));
        stg128(gdst + rr * DM + (lane & 7) * 8, v.x, v.y, v.z, v.w);
    }
    if (ACK) {
#pragma unroll
        for (int i = 0; i < 4; i++) ack |= readback(gdst + (4 * i + (lane >> 3)) * DM + (lane & 7) * 8);
    }
    return ack;
}

template <bool NORM>
__device__ __forceinline__ void feature_map(const uint32_t* a, const uint32_t* wb, float c0, float c1, uint32_t* plus, uint32_t* minus, float* rs) {
    float p[8];
    mma16816_z(p, a, wb[0], wb[1]);
    mma16816_z(p + 4, a, wb[2], wb[3]);
    const uint32_t P0 = pack_bf16(p[0], p[2]), P1 = pack_bf16(p[1], p[3]), P2 = pack_bf16(p[4], p[6]), P3 = pack_bf16(p[5], p[7]);
    uint32_t mx = max2(max2(P0, P1), max2(P2, P3)), mn = min2(min2(P0, P1), min2(P2, P3));
#pragma unroll
    for (int s = 1; s <= 2; s <<= 1) {
        mx = max2(mx, __shfl_xor_sync(0xffffffffu, mx, s));
        mn = min2(mn, __shfl_xor_sync(0xffffffffu, mn, s));
    }
    const float mx0 = bf_lo(mx) * c0, mx1 = bf_hi(mx) * c1, mn0 = bf_lo(mn) * c0, mn1 = bf_hi(mn) * c1;
    p[0] = bf_lo(P0); p[2] = bf_hi(P0); p[1] = bf_lo(P1); p[3] = bf_hi(P1);
    p[4] = bf_lo(P2); p[6] = bf_hi(P2); p[5] = bf_lo(P3); p[7] = bf_hi(P3);
    float ep[8], em[8];
#pragma unroll
    for (int i = 0; i < 8; i++) {
        const bool r1 = (i & 2);
        ep[i] = ex2(fmaf(p[i], r1 ? c1 : c0, r1 ? -mx1 : -mx0));
        em[i] = ex2(fmaf(p[i], r1 ? -c1 : -c0, r1 ? mn1 : mn0));
    }
    float sp[4], sm[4];
#pragma unroll
    for (int i = 0; i < 4; i++) { plus[i] = pack_bf16(ep[2 * i], ep[2 * i + 1]); minus[i] = pack_bf16(em[2 * i], em[2 * i + 1]); }
    mma16816_z(sp, plus, 0x3f803f80u, 0x3f803f80u);
    mma16816_z(sm, minus, 0x3f803f80u, 0x3f803f80u);
    rs[0] = rcp(sp[0]); rs[1] = rcp(sp[2]); rs[2] = rcp(sm[0]); rs[3] = rcp(sm[2]);
    if (NORM) {
#pragma unroll
        for (int i = 0; i < 4; i++) {
            plus[i] = pack_bf16(ep[2 * i] * rs[i & 1], ep[2 * i + 1] * rs[i & 1]);
            minus[i] = pack_bf16(em[2 * i] * rs[2 + (i & 1)], em[2 * i + 1] * rs[2 + (i & 1)]);
        }
    }
}

template <bool SCALE>
__device__ __forceinline__ void ln_frag(const float* acc, uint32_t cs_addr, float rs0, float nm0, float rs1, float nm1, uint32_t* a) {
    const float2 c0 = lds_f2(cs_addr), c1 = lds_f2(cs_addr + 32);
    const float s0 = SCALE ? rs0 : 1.f, s1 = SCALE ? rs1 : 1.f;
    a[0] = pack_bf16(fmaf(nm0, c0.x, acc[0]) * s0, fmaf(nm0, c0.y, acc[1]) * s0);
    a[1] = pack_bf16(fmaf(nm1, c0.x, acc[2]) * s1, fmaf(nm1, c0.y, acc[3]) * s1);
    a[2] = pack_bf16(fmaf(nm0, c1.x, acc[4]) * s0, fmaf(nm0, c1.y, acc[5]) * s0);
    a[3] = pack_bf16(fmaf(nm1, c1.x, acc[6]) * s1, fmaf(nm1, c1.y, acc[7]) * s1);
}

__device__ __forceinline__ uint32_t hh_pair(const float* ag, float4 cs, float nmean) {
    const float g0 = fmaf(nmean, cs.x, ag[0]), g1 = fmaf(nmean, cs.y, ag[1]);
    const float u0 = fmaf(nmean, cs.z, ag[32]), u1 = fmaf(nmean, cs.w, ag[33]);
    return pack_bf16(g0 * u0, g1 * u1);
}

struct Ring {
    int slot; uint32_t phase;
    __device__ __forceinline__ void adv() { if (++slot == NB) { slot = 0; phase ^= 1; } }
};

__global__ void __launch_bounds__(NTHREADS, 1) fused_kernel(const __grid_constant__ Params P) {
    extern __shared__ __align__(1024) uint8_t smem_raw[];
    const uint32_t sb = smem_u32(smem_raw);
    const int tid = threadIdx.x, lane = tid & 31;
    const int warp = __shfl_sync(0xffffffffu, tid >> 5, 0);
    unsigned role = blockIdx.x;
    if (P.use_smid) asm volatile("mov.u32 %0, %%smid;" : "=r"(role));
    role = P.role[role];
    const int m = role >> 3, j = role & 7;
    const bool helper = role >= 128;

    TL(0, tid == 0); TLG(0, tid == 0);
    float* const acc_j = g_acc + j * ACC_SIZE;
    unsigned* const cnt_j = g_cnt + j * 32;

    if (__builtin_expect(warp >= 8, 1)) {
        asm volatile("setmaxnreg.dec.sync.aligned.u32 72;");
        if (elect_one()) {
            if (warp == 8) {
                if (!helper) {
#pragma unroll
                    for (int i = 0; i < NB; i++) mbar_init(sb + BAR_FULLB + 8 * i, 1);
#pragma unroll
                    for (int i = 0; i < 2; i++) {
                        mbar_expect_tx(sb + BAR_FULLB + 8 * i, SLOT);
                        tma3d(sb + OFF_B + i * SLOT, &P.twkv, sb + BAR_FULLB + 8 * i, 64 * j, 64 * i, 1);
                    }
                }
            } else if (warp == 9) {
#pragma unroll
                for (int i = 0; i < 8; i++) mbar_init(sb + BAR_FULLA + 8 * i, 1);
#pragma unroll
                for (int i = 0; i < 2; i++) {
                    mbar_expect_tx(sb + BAR_FULLA + 8 * i, SLOT);
                    tma2d(sb + OFF_A + i * SLOT, helper ? &P.twq : &P.tx, sb + BAR_FULLA + 8 * i, helper ? DM + 128 * j : 64 * i, 128 * (helper ? i : m));
                }
            } else if (warp == 10) {
#pragma unroll
                for (int i = 0; i < 4; i++) mbar_init(sb + BAR_CS1 + 8 * i, i == 1 ? 160 : 32);
                trap_if_gt(sb & 1023, 0);
            } else {
#pragma unroll
                for (int i = 0; i < 14; i++) mbar_init(sb + (i < 8 ? BAR_EMPTYA : BAR_EMPTYB - 64) + 8 * i, 8);
            }
        }
        __syncwarp();
        const unsigned epoch = ld_relaxed(&g_epoch);
        bar_sync(0, NTHREADS);
        if (helper) {
            if (warp == 8) {
                if (elect_one()) {
#pragma unroll 1
                    for (int i = 2; i < 72; i++) {
                        const uint32_t full = sb + BAR_FULLA + 8 * (i & 7), dst = sb + OFF_A + (i & 7) * SLOT;
                        mbar_wait(sb + BAR_EMPTYA + 8 * (i & 7), ((i >> 3) & 1) ^ 1);
                        mbar_expect_tx(full, SLOT);
                        if (i < 24) {
                            tma2d(dst, &P.twq, full, (i < 16 ? DM + 64 * (i & 8) : 0) + 128 * j + 16 * (i & 4), 128 * (i & 3));
                        } else {
                            const int u = (i >> 3) - 3, c0 = 176 * (2 * j + (u & 1)) + 64 * (u >> 1);
                            tma2d(dst, &P.twg, full, c0, 64 * (i & 7));
                            tma2d(dst + 8192, &P.twu, full, c0, 64 * (i & 7));
                        }
                    }
                    prefetch_l2(P.wd + (size_t)j * 176128, 352256);
                }
            } else if (warp == 9) {
                wait_count_warp(g_cnt + (lane & 7) * 32, epoch * 128);
            }
            return;
        }
        if (warp == 8) {
            if (elect_one()) {
                if (m >= 3 && m < 8)
                    asm volatile("cp.async.bulk.prefetch.tensor.3d.L2.global [%0, {%1, %2, %3}];" ::"l"(&P.twkv), "r"(64 * j), "r"(64 * m), "r"(1) : "memory");
                if (j >= 3)
                    asm volatile("cp.async.bulk.prefetch.tensor.2d.L2.global [%0, {%1, %2}];" ::"l"(&P.tx), "r"(64 * j), "r"(128 * m) : "memory");
                Ring r{2, 0};
#pragma unroll 1
                for (int i = 2; i < 56; i++) {
                    const uint32_t full = sb + BAR_FULLB + 8 * r.slot, dst = sb + OFF_B + r.slot * SLOT;
                    mbar_wait(sb + BAR_EMPTYB + 8 * r.slot, r.phase ^ 1);
                    if (i >= 8 && i < 12) {
                        mbar_arrive(full);
                    } else {
                        if (i >= AHEAD && i < 6) mbar_wait(full - 8 * AHEAD, 0);
                        mbar_expect_tx(full, SLOT);
                        if (i < 8) {
                            tma3d(dst, &P.twkv, full, 64 * j, 64 * i, 1);
                        } else if (i < 20) {
                            tma2d(dst, i < 16 ? &P.twq : &P.two, full, 64 * j, 128 * (i & 3));
                        } else if (i < 44) {
                            const int c = (i - 20) >> 3, kt = (i - 20) & 7;
                            tma2d(dst, &P.twg, full, 176 * j + 64 * c, 64 * kt);
                            tma2d(dst + 8192, &P.twu, full, 176 * j + 64 * c, 64 * kt);
                        } else {
                            const int c = (i - 44) >> 2, jj = (i & 3) * 2;
                            tma2d(dst, &P.twd, full, 64 * j, 176 * jj + 64 * c);
                            tma2d(dst + 8192, &P.twd, full, 64 * j, 176 * (jj + 1) + 64 * c);
                        }
                    }
                    r.adv();
                }
            }
            return;
        }
        if (warp == 9) {
            if (elect_one()) {
#pragma unroll 1
                for (int i = 2; i < 8; i++) {
                    if (i >= AHEAD + 1) mbar_wait(sb + BAR_FULLA + 8 * (i - AHEAD - 1), 0);
                    mbar_expect_tx(sb + BAR_FULLA + 8 * i, SLOT);
                    tma2d(sb + OFF_A + i * SLOT, &P.tx, sb + BAR_FULLA + 8 * i, 64 * i, 128 * m);
                }
#pragma unroll 1
                for (int i = 1; i < 10; i++) prefetch_tmap(&P.tx + i);
#pragma unroll 1
                for (int r = 1; r < 6; r++) {
                    const CUtensorMap* tm = &P.tx + min(r, 3);
                    const int cstep = r < 3 ? 64 : 192, cbase = r < 3 ? 0 : 64 * (r - 3), skip = r < 3 ? j : 8;
                    wait_count(g_flag + (m * 5 + r - 1) * 32, epoch * (r < 3 ? 64 : 32));
#pragma unroll 1
                    for (int t = 0; t < 8; t++) {
                        if (t == skip) continue;
                        mbar_wait(sb + BAR_EMPTYA + 8 * t, (r - 1) & 1);
                        TL(56 + 8 * r + (t == 7), t == 7 || t == (skip == 0));
                        mbar_expect_tx(sb + BAR_FULLA + 8 * t, SLOT);
                        tma2d(sb + OFF_A + t * SLOT, tm, sb + BAR_FULLA + 8 * t, cbase + cstep * t, 128 * m);
                    }
                }
            }
            return;
        }
        const int a = warp - 10;
        {
            const int row = 16 * j + 8 * a + (lane >> 2);
            const uint32_t ra = sb + OFF_A + row * 128;
            float sh = 0.f, s0 = 0.f, s1 = 0.f, q0 = 0.f, q1 = 0.f;
#pragma unroll 1
            for (int kt = 0; kt < 8; kt++) {
                mbar_wait(sb + BAR_FULLA + 8 * kt, 0);
                if (kt == 0) sh = bf_lo(lds128(ra + ((row & 7) << 4)).x);
#pragma unroll
                for (int i = 0; i < 2; i++) {
                    const uint4 v = lds128(ra + kt * SLOT + (((2 * (lane & 3) + i) ^ (row & 7)) << 4));
                    const uint32_t ww[4] = {v.x, v.y, v.z, v.w};
#pragma unroll
                    for (int e = 0; e < 4; e++) {
                        const float d0 = bf_lo(ww[e]) - sh, d1 = bf_hi(ww[e]) - sh;
                        s0 += d0; q0 = fmaf(d0, d0, q0);
                        s1 += d1; q1 = fmaf(d1, d1, q1);
                    }
                }
            }
            s0 += s1; q0 += q1;
#pragma unroll
            for (int o = 1; o <= 2; o <<= 1) { s0 += __shfl_xor_sync(0xffffffffu, s0, o); q0 += __shfl_xor_sync(0xffffffffu, q0, o); }
            const float md = s0 * (1.f / DM);
            const float rs = rsqrtf(fmaxf(q0 * (1.f / DM) - md * md, 0.f) + 1e-5f);
            st_tagged_if(g_xstat + 2 * (128 * m + row), rs, -(sh + md), epoch, (lane & 3) == 0);
        }
        const unsigned long long* cs = g_cs + j * 768 + 2 * lane;
#pragma unroll 1
        for (int c = 0; c < (a ? 2 : 7); c++) {
            uint4 v;
            uint32_t it = 0;
            while (true) {
                v = ld_tagged(cs + (a ? 128 + 128 * c : (c ? 320 + 64 * c : 0)));
                if (!__any_sync(0xffffffffu, v.y != epoch || v.w != epoch)) break;
                __nanosleep(100);
                trap_if_gt(++it, 1u << 22);
            }
            sts64(a || !c ? sb + OFF_CS1 + (a ? 512 - 512 * c : 256) + 8 * lane : sb + OFF_CS3 + (32 * ((c - 1) >> 1) + lane) * 16 + 8 * ((c - 1) & 1), v.x, v.z);
            if (a || c == 0 || c == 6) mbar_arrive(sb + (a ? (c ? BAR_CSQ : BAR_CSV) : (c ? BAR_CS3 : BAR_CS1)));
        }
        return;
    }
    const unsigned epoch = ld_relaxed(&g_epoch);
    uint32_t wraw[16];
    if (!helper) {
        const uint32_t* wp = reinterpret_cast<const uint32_t*>(P.wphi) + (4 * j) * 128 + (lane & 3) * 16 + (lane >> 2);
#pragma unroll
        for (int i = 0; i < 16; i++)
            asm volatile("ld.global.nc.u32 %0, [%1];" : "=r"(wraw[i]) : "l"(wp + (i >> 2) * 128 + ((i >> 1) & 1) * 64 + (i & 1) * 8));
    }
    asm volatile("setmaxnreg.inc.sync.aligned.u32 216;");
    bar_sync(0, NTHREADS);
    if (helper) {
        if (warp < 4) {
            sts128(sb + OFF_B + 16 * tid, 0x3f803f80u, 0x3f803f80u, 0x3f803f80u, 0x3f803f80u);
            for (int i = tid; i < 2 * ACC_SIZE / 4; i += 128) stg128(g_acc + 2 * j * ACC_SIZE + 4 * i, 0, 0, 0, 0);
            fence_async_smem();
            fence_gpu();
            bar_sync(1, 128);
            float acc[8];
            int i = 0;
#pragma unroll 1
            for (int job = 0; job < 12; job++) {
                const int n = job < 6 ? 4 : 8;
#pragma unroll 1
                for (int t = 0; t < n; t++, i++) {
                    mbar_wait(sb + BAR_FULLA + 8 * (i & 7), (i >> 3) & 1);
                    wg_fence();
#pragma unroll
                    for (int k = 0; k < 8; k++)
                        wgmma_n8_tt(acc + (k & 4), desc_lo(sb + OFF_A) + (i & 7) * (SLOT >> 4) + 128 * k, desc_lo(sb + OFF_B), (t | (k & 3)) != 0);
                    wg_commit();
                    wg_wait<1>();
                    mbar_arrive_n_if(sb + BAR_EMPTYA + 8 * ((i + 7) & 7), 2, lane == 0 && i > 0);
                }
                wg_wait<0>();
                fence_acc<8>(acc);
                const int q = lane & 3;
                const float lo = (q & 1) ? acc[2] : acc[0], hi = (q & 1) ? acc[6] : acc[4];
                const float v = job < 6 ? lo + hi : ((q & 2) ? hi : lo);
                unsigned long long* dst = g_cs + ((2 * j + (job & 1)) * 6 + (job >> 1)) * 128 + (q >> 1) * 64 + 16 * warp + 8 * (q & 1) + (lane >> 2);
                asm volatile("st.relaxed.gpu.global.b64 [%0], %1;" ::"l"(dst), "l"(((unsigned long long)epoch << 32) | __float_as_uint(v)) : "memory");
            }
        }
        return;
    }
    {
        const int w = warp >> 2, wv = warp & 3, g = lane >> 2, q = lane & 3;
        const int row_w = 128 * m + 16 * warp;
        const uint32_t sa = sb + OFF_A + w * 8192;
        const desc_t dA = desc_lo(sa), dB = desc_lo(sb + OFF_B);
        unsigned* const flag_m = g_flag + m * 160;
        const bool l0 = lane == 0;
        Ring rg{0, 0};
        int prev = 0;

        uint32_t wb[16];
        constexpr float L2E = 1.4426950408889634f;
        uint32_t fp[16], fm[16];
        float fr[16];
        float rs0, nm0, rs1, nm1;
        uint32_t kv_ack;
        {
            float acc[64];
#pragma unroll 1
            for (int kt = 0; kt < 8; kt++) {
                mbar_waitc(sb + BAR_FULLA + 8 * kt, 0);
                mbar_waitc(sb + BAR_FULLB + 8 * rg.slot, rg.phase);
                const desc_t da = dA + kt * (SLOT >> 4), db = dB + rg.slot * (SLOT >> 4);
                wg_fence();
#pragma unroll
                for (int k = 0; k < 4; k++) wgmma_n128(acc, da + 2 * k, db + 128 * k, (kt | k) != 0);
                wg_commit();
                wg_wait<1>();
                mbar_arrive_if(sb + BAR_EMPTYB + 8 * prev, l0 && kt > 0);
                prev = rg.slot; rg.adv();
            }
            {
                uint4 a, b;
                uint32_t it = 0;
                do {
                    a = ld_tagged_rlx(g_xstat + 2 * (row_w + g));
                    b = ld_tagged_rlx(g_xstat + 2 * (row_w + g + 8));
                    trap_if_gt(++it, 1u << 22);
                } while (__any_sync(0xffffffffu, a.y != epoch || a.w != epoch || b.y != epoch || b.w != epoch));
                rs0 = __uint_as_float(a.x); nm0 = __uint_as_float(a.z); rs1 = __uint_as_float(b.x); nm1 = __uint_as_float(b.z);
            }
#pragma unroll
            for (int i = 0; i < 8; i++) {
                wb[(i >> 1) * 4 + (i & 1)] = __byte_perm(wraw[2 * i], wraw[2 * i + 1], 0x5410);
                wb[(i >> 1) * 4 + 2 + (i & 1)] = __byte_perm(wraw[2 * i], wraw[2 * i + 1], 0x7632);
            }
            TL(17, tid == 0);
            mbar_waitc(sb + BAR_CS1, 0);
            TL(18, tid == 0);
            wg_wait<0>();
            fence_acc<64>(acc);
            mbar_arrive_if(sb + BAR_EMPTYB + 8 * prev, l0);
            TL(2, tid == 0);
#pragma unroll
            for (int i = 2; i < 6; i++) mbar_waitc(sb + BAR_FULLB + 8 * i, 1);
            const int lrow = 16 * warp + (lane & 15), ch = lane >> 4, sw = lane & 7;
            const uint32_t st = sb + OFF_B + 2 * SLOT + lrow * 128;
            uint32_t ka[16];
#pragma unroll
            for (int hh = 0; hh < 4; hh++)
                ln_frag<false>(acc + 8 * hh, sb + OFF_CS1 + (64 + 16 * hh + 2 * q) * 4, rs0, nm0, rs1, nm1, ka + 4 * hh);
#pragma unroll
            for (int hh = 0; hh < 4; hh++) feature_map<true>(ka + 4 * hh, wb + 4 * hh, rs0 * L2E, rs1 * L2E, fp + 4 * hh, fm + 4 * hh, fr);
#pragma unroll
            for (int hh = 0; hh < 4; hh++) {
                stsm4(st + (hh >> 1) * SLOT + (((4 * (hh & 1) + ch) ^ sw) << 4), fp[4 * hh], fp[4 * hh + 1], fp[4 * hh + 2], fp[4 * hh + 3]);
                stsm4(st + (hh >> 1) * SLOT + (((4 * (hh & 1) + 2 + ch) ^ sw) << 4), fm[4 * hh], fm[4 * hh + 1], fm[4 * hh + 2], fm[4 * hh + 3]);
            }
            mbar_waitc(sb + BAR_CSV, 0);
#pragma unroll
            for (int hh = 0; hh < 4; hh++) {
                uint32_t a[4];
                ln_frag<true>(acc + 32 + 8 * hh, sb + OFF_CS1 + (128 + 16 * hh + 2 * q) * 4, rs0, nm0, rs1, nm1, a);
                stsm4(st + (2 + (hh >> 1)) * SLOT + (((2 * (hh & 1) + ch) ^ sw) << 4), a[0], a[1], a[2], a[3]);
            }
            stsm4(st + (2 + ch) * SLOT + ((4 ^ sw) << 4), 0x3f803f80u, 0x3f803f80u, 0x3f803f80u, 0x3f803f80u);
            fence_async_smem();
            bar_sync(1, 256);
            float kvd[20];
            wg_fence();
#pragma unroll
            for (int k = 0; k < 8; k++)
                wgmma_n40_tt(kvd, dB + (2 + w) * (SLOT >> 4) + 128 * k, dB + (4 + w) * (SLOT >> 4) + 128 * k, k != 0);
            wg_commit();
            wg_wait<0>();
            fence_acc<20>(kvd);
            const bool h1 = wv >= 2;
            const int f = 16 * warp + g;
            float* kvp = acc_j + ACC_KV + f * 16 + 2 * q;
            kv_ack = atom_f32x2(kvp, h1 ? kvd[8] : kvd[0], h1 ? kvd[9] : kvd[1]);
            kv_ack |= atom_f32x2(kvp + 128, h1 ? kvd[10] : kvd[2], h1 ? kvd[11] : kvd[3]);
            kv_ack |= atom_f32x2(kvp + 8, h1 ? kvd[12] : kvd[4], h1 ? kvd[13] : kvd[5]);
            kv_ack |= atom_f32x2(kvp + 136, h1 ? kvd[14] : kvd[6], h1 ? kvd[15] : kvd[7]);
            kv_ack |= atom_f32_if(acc_j + ACC_Z + f + 8 * (q & 1), q ? kvd[18] : kvd[16], q < 2);
            mbar_arrive_if(sb + BAR_EMPTYB + 8 * (2 + (lane & 3)), lane < 4);
            signal_after(cnt_j, kv_ack, P.zero, l0);
            TL(3, tid == 0);
        }
        uint32_t res_lo[8], res_hi[8];
        const uint32_t own_rows = sb + OFF_A + j * SLOT + warp * 2048;
        {
            float acc[32];
            rg.slot = 0; rg.phase = 0;
#pragma unroll 1
            for (int b = 0; b < 4; b++) {
                mbar_waitc(sb + BAR_FULLB + 8 * rg.slot, rg.phase);
                const desc_t da = dA + b * (2 * SLOT >> 4), db = dB + rg.slot * (SLOT >> 4);
                wg_fence();
#pragma unroll
                for (int k = 0; k < 8; k++) wgmma_n64(acc, da + (k >> 2) * (SLOT >> 4) + (k & 3) * 2, db + 128 * k, (b | k) != 0);
                wg_commit();
                wg_wait<1>();
                mbar_arrive_if(sb + BAR_EMPTYB + 8 * prev, l0 && b > 0);
                prev = rg.slot; rg.adv();
            }
            wg_wait<0>();
            fence_acc<32>(acc);
            mbar_arrive_if(sb + BAR_EMPTYB + 8 * prev, l0);
            mbar_arrive_if(sb + BAR_EMPTYA + 8 * (lane & 7), lane < 8 && (lane | 1) != (j | 1));
            TL(4, tid == 0);
            mbar_waitc(sb + BAR_CSQ, 0);
            uint32_t qa[16];
#pragma unroll
            for (int hh = 0; hh < 4; hh++)
                ln_frag<false>(acc + 8 * hh, sb + OFF_CS1 + (16 * hh + 2 * q) * 4, rs0, nm0, rs1, nm1, qa + 4 * hh);
#pragma unroll
            for (int hh = 0; hh < 4; hh++) feature_map<false>(qa + 4 * hh, wb + 4 * hh, rs0 * L2E, rs1 * L2E, fp + 4 * hh, fm + 4 * hh, fr + 4 * hh);
#pragma unroll
            for (int b = 0; b < 4; b++)
                ldsm4(own_rows + (lane & 15) * 128 + (((2 * b + (lane >> 4)) ^ (lane & 7)) << 4),
                      res_lo[2 * b], res_hi[2 * b], res_lo[2 * b + 1], res_hi[2 * b + 1]);
            TL(5, tid == 0);
            if (warp == 0) wait_count_warp(cnt_j, epoch * 128);
            TL(6, tid == 0);
            bar_sync(1, 256);
            const uint32_t kvs = sb + OFF_A + (j ^ 1) * SLOT;
            {
                const float4 a0 = ld_l2_f4(acc_j + ACC_KV + 4 * tid), a1 = ld_l2_f4(acc_j + ACC_KV + 4 * (tid + 256));
                const float zz = ld_l2_f(acc_j + ACC_Z + (tid & 127));
                sts64(kvs + (tid >> 2) * 48 + (tid & 3) * 8, pack_bf16(a0.x, a0.y), pack_bf16(a0.z, a0.w));
                sts64(kvs + ((tid >> 2) + 64) * 48 + (tid & 3) * 8, pack_bf16(a1.x, a1.y), pack_bf16(a1.z, a1.w));
                const uint32_t z2 = pack_bf16(zz, zz);
                sts64(kvs + (tid & 127) * 48 + 32 + w * 8, z2, z2);
            }
            bar_sync(1, 256);
            uint32_t o_lo[8], o_hi[8];
#pragma unroll
            for (int hh = 0; hh < 4; hh++) {
                uint32_t b[8], zb[4];
                const uint32_t base = kvs + hh * 32 * 48;
                ldsm4t(base + (lane & 15) * 48 + (lane >> 4) * 16, b[0], b[1], b[2], b[3]);
                ldsm4t(base + (16 + (lane & 15)) * 48 + (lane >> 4) * 16, b[4], b[5], b[6], b[7]);
                ldsm4t(base + lane * 48 + 32, zb[0], zb[1], zb[2], zb[3]);
                float n0[4], n1[4], dn[4], m0[4], m1[4], dm[4];
                mma16816_z(n0, fp + 4 * hh, b[0], b[1]); mma16816_z(n1, fp + 4 * hh, b[2], b[3]); mma16816_z(dn, fp + 4 * hh, zb[0], zb[1]);
                mma16816_z(m0, fm + 4 * hh, b[4], b[5]); mma16816_z(m1, fm + 4 * hh, b[6], b[7]); mma16816_z(dm, fm + 4 * hh, zb[2], zb[3]);
                const float* r = fr + 4 * hh;
                const float i0 = rcp(fmaf(dn[0], r[0], fmaf(dm[0], r[2], 1e-6f))), i1 = rcp(fmaf(dn[2], r[1], fmaf(dm[2], r[3], 1e-6f)));
                const float p0 = r[0] * i0, q0 = r[2] * i0, p1 = r[1] * i1, q1 = r[3] * i1;
                o_lo[2 * hh] = pack_bf16(fmaf(n0[0], p0, m0[0] * q0), fmaf(n0[1], p0, m0[1] * q0));
                o_hi[2 * hh] = pack_bf16(fmaf(n0[2], p1, m0[2] * q1), fmaf(n0[3], p1, m0[3] * q1));
                o_lo[2 * hh + 1] = pack_bf16(fmaf(n1[0], p0, m1[0] * q0), fmaf(n1[1], p0, m1[1] * q0));
                o_hi[2 * hh + 1] = pack_bf16(fmaf(n1[2], p1, m1[2] * q1), fmaf(n1[3], p1, m1[3] * q1));
            }
            const uint32_t ack = store_tile<true>(own_rows, g_o + (size_t)row_w * DM + 64 * j, o_lo, o_hi, lane);
            fence_async_smem();
            signal_after(flag_m, ack, P.zero, l0);
            mbar_arrive_if(sb + BAR_EMPTYA + 8 * (j ^ 1), l0);
            TL(7, tid == 0);
        }
        {
            float acc[32];
#pragma unroll
            for (int t = 0; t < 8; t++) {
                acc[4 * t] = bf_lo(res_lo[t]); acc[4 * t + 1] = bf_hi(res_lo[t]);
                acc[4 * t + 2] = bf_lo(res_hi[t]); acc[4 * t + 3] = bf_hi(res_hi[t]);
            }
            fence_acc<32>(acc);
#pragma unroll 1
            for (int kp = 0; kp < 4; kp++) {
                mbar_waitc(sb + BAR_FULLB + 8 * rg.slot, rg.phase);
#pragma unroll
                for (int hf = 0; hf < 2; hf++) {
                    const int kt = 2 * kp + hf;
                    mbar_waitc(sb + BAR_FULLA + 8 * kt, kt != j);
                    TL(8, kt == 0 && tid == 0);
                    const desc_t da = dA + kp * (2 * SLOT >> 4), db = dB + rg.slot * (SLOT >> 4);
                    wg_fence();
#pragma unroll
                    for (int k = 0; k < 4; k++) wgmma_n64(acc, da + hf * (SLOT >> 4) + 2 * k, db + (hf * 4 + k) * 128, 1);
                    wg_commit();
                    wg_wait<1>();
                    mbar_arrive_if(sb + BAR_EMPTYA + 8 * ((kt + 7) & 7), l0 && kt > 0 && kt - 1 != j);
                    if (hf == 0) mbar_arrive_if(sb + BAR_EMPTYB + 8 * prev, l0 && kt > 0);
                }
                prev = rg.slot; rg.adv();
            }
            wg_wait<0>();
            fence_acc<32>(acc);
            mbar_arrive_if(sb + BAR_EMPTYA + 8 * 7, l0 && j != 7);
            mbar_arrive_if(sb + BAR_EMPTYB + 8 * prev, l0);
            TL(9, tid == 0);
            float s0 = 0.f, s1 = 0.f;
#pragma unroll
            for (int t = 0; t < 8; t++) {
                res_lo[t] = pack_bf16(acc[4 * t], acc[4 * t + 1]);
                res_hi[t] = pack_bf16(acc[4 * t + 2], acc[4 * t + 3]);
                s0 += acc[4 * t] + acc[4 * t + 1];
                s1 += acc[4 * t + 2] + acc[4 * t + 3];
            }
            uint32_t ack = store_tile<true>(own_rows, g_h + (size_t)row_w * DM + 64 * j, res_lo, res_hi, lane);
            s0 += __shfl_xor_sync(0xffffffffu, s0, 1); s1 += __shfl_xor_sync(0xffffffffu, s1, 1);
            s0 += __shfl_xor_sync(0xffffffffu, s0, 2); s1 += __shfl_xor_sync(0xffffffffu, s1, 2);
            const float mu0 = s0 * (1.f / 64), mu1 = s1 * (1.f / 64);
            float q0 = 0.f, q1 = 0.f;
#pragma unroll
            for (int t = 0; t < 8; t++) {
                float d;
                d = acc[4 * t] - mu0; q0 = fmaf(d, d, q0);
                d = acc[4 * t + 1] - mu0; q0 = fmaf(d, d, q0);
                d = acc[4 * t + 2] - mu1; q1 = fmaf(d, d, q1);
                d = acc[4 * t + 3] - mu1; q1 = fmaf(d, d, q1);
            }
            q0 += __shfl_xor_sync(0xffffffffu, q0, 1); q1 += __shfl_xor_sync(0xffffffffu, q1, 1);
            q0 += __shfl_xor_sync(0xffffffffu, q0, 2); q1 += __shfl_xor_sync(0xffffffffu, q1, 2);
            stg_f2_if(g_hstat + (row_w + g + 8 * (q & 1)) * 16 + 2 * j, q ? mu1 : mu0, q ? q1 : q0, q < 2);
            ack |= readback(g_hstat + (row_w + g + 8 * (q & 1)) * 16 + 2 * j);
            fence_async_smem();
            signal_after(flag_m + 32, ack, P.zero, l0);
            bar_sync(1, 256);
            TL(10, tid == 0);
        }
        if (w == 1) {
#pragma unroll 1
            for (int kt = 0; kt < 8; kt++) mbar_waitc(sb + BAR_FULLA + 8 * kt, 0);
            const float* sp = g_hstat + (128 * m + (tid & 127)) * 16;
            float4 v[4];
#pragma unroll
            for (int i = 0; i < 4; i++) v[i] = ld_l2_f4(sp + 4 * i);
            float mean = 0.f;
#pragma unroll
            for (int i = 0; i < 4; i++) mean += v[i].x + v[i].z;
            mean *= 0.125f;
            float m2 = 0.f, dv = 0.f;
#pragma unroll
            for (int i = 0; i < 4; i++) {
                m2 += v[i].y + v[i].w;
                dv = fmaf(v[i].x - mean, v[i].x - mean, dv); dv = fmaf(v[i].z - mean, v[i].z - mean, dv);
            }
            sts_f2(sb + OFF_CS1 + (tid & 127) * 8, -mean, __fdividef(1.f, fmaf(dv, 64.f, m2) * (1.f / DM) + 1e-5f));
            mbar_arrive(sb + BAR_CS3);
        }
        {
            float acc0[64], acc1[64];
            const desc_t dA0 = desc_lo(sb + OFF_A);
#pragma unroll 1
            for (int c = w; c < 3; c += 2) {
                if (c > 0) bar_sync(1 + c, 256);
                rg.slot = (c == 2) ? 0 : 2 + 2 * c; rg.phase = (c == 0);
#pragma unroll 1
                for (int kt = 0; kt < 8; kt++) {
                    mbar_waitc(sb + BAR_FULLA + 8 * kt, 0);
                    mbar_waitc(sb + BAR_FULLB + 8 * rg.slot, rg.phase);
                    TL(44 + c * 2 + (kt == 1), (tid & 127) == 0 && kt < 2);
                    const desc_t da = dA0 + kt * (SLOT >> 4), db = dB + rg.slot * (SLOT >> 4);
                    wg_fence();
#pragma unroll
                    for (int k = 0; k < 4; k++) {
                        wgmma_n128(acc0, da + 2 * k, db + 128 * k, (kt | k) != 0);
                        wgmma_n128(acc1, da + 512 + 2 * k, db + 128 * k, (kt | k) != 0);
                    }
                    wg_commit();
                    wg_wait<1>();
                    mbar_arrive_n_if(sb + BAR_EMPTYB + 8 * prev, 2, l0 && kt > 0);
                    mbar_arrive_if(sb + BAR_EMPTYA + 8 * ((kt + 7) & 7), l0 && kt > 0 && c > 0);
                    prev = rg.slot; rg.adv();
                }
                bar_arrive(2 + c, 256);
                mbar_waitc(sb + BAR_CS3, 0);
                float nm[4];
#pragma unroll
                for (int i = 0; i < 4; i++) nm[i] = lds_f2(sb + OFF_CS1 + (64 * (i >> 1) + 16 * wv + g + 8 * (i & 1)) * 8).x;
                wg_wait<0>();
                fence_acc<64>(acc0); fence_acc<64>(acc1);
                mbar_arrive_n_if(sb + BAR_EMPTYB + 8 * prev, 2, l0);
                mbar_arrive_if(sb + BAR_EMPTYA + 8 * 7, l0 && c > 0);
                TL(11 + c, (tid & 127) == 0);
                uint32_t ack = 0;
                __nv_bfloat16* hp = g_hh + (size_t)(128 * m + 16 * wv + g) * FFP + 192 * j + 64 * c + (q & 1) * 8 + (q >> 1) * 4;
#pragma unroll
                for (int tp = 0; tp < 4; tp++) {
                    if (tp < 3 || c < 2) {
                        const uint32_t ca = sb + OFF_CS3 + (32 * c + 8 * tp + q) * 16;
                        const float4 c0 = lds_f4(ca), c1 = lds_f4(ca + 64);
                        ack |= store_pair(hp + 16 * tp, hh_pair(acc0 + 8 * tp, c0, nm[0]), hh_pair(acc0 + 8 * tp + 4, c1, nm[0]), q & 1);
                        ack |= store_pair(hp + 8 * FFP + 16 * tp, hh_pair(acc0 + 8 * tp + 2, c0, nm[1]), hh_pair(acc0 + 8 * tp + 6, c1, nm[1]), q & 1);
                        ack |= store_pair(hp + 64 * FFP + 16 * tp, hh_pair(acc1 + 8 * tp, c0, nm[2]), hh_pair(acc1 + 8 * tp + 4, c1, nm[2]), q & 1);
                        ack |= store_pair(hp + 72 * FFP + 16 * tp, hh_pair(acc1 + 8 * tp + 2, c0, nm[3]), hh_pair(acc1 + 8 * tp + 6, c1, nm[3]), q & 1);
                    }
                }
                signal_after(flag_m + 64 + 32 * c, ack, P.zero, l0);
                TL(54 + c, (tid & 127) == 0);
            }
        }
        {
            float acc[32];
            const uint32_t xch = sb + OFF_B + (tid & 127) * 16;
            if (w == 1) {
                float acc0[32];
                bar_sync(4, 256);
                rg.slot = 2; rg.phase = 1;
                const desc_t dA0 = desc_lo(sb + OFF_A);
#define KT_P4(T, HF, NK)                                                                                    \
    do {                                                                                                    \
        const int s_ = (T) & 7;                                                                             \
        if (!(HF)) mbar_waitc(sb + BAR_FULLB + 8 * rg.slot, rg.phase);                                      \
        mbar_waitc(sb + BAR_FULLA + 8 * s_, (((T) >> 3) + 1) & 1);                                          \
        if (!(HF)) TL(30 + (T) / 2, tid == 128);                                                            \
        const desc_t da_ = dA0 + s_ * (SLOT >> 4), db_ = dB + rg.slot * (SLOT >> 4) + (HF) * 512;         \
        wg_fence();                                                                                         \
        _Pragma("unroll") for (int k = 0; k < (NK); k++) {                                                  \
            wgmma_n64(acc0, da_ + 2 * k, db_ + 128 * k, ((T) | k) != 0);                                    \
            wgmma_n64(acc, da_ + 512 + 2 * k, db_ + 128 * k, ((T) | k) != 0);                               \
        }                                                                                                   \
        wg_commit();                                                                                        \
        wg_wait<1>();                                                                                       \
        mbar_arrive_n_if(sb + BAR_EMPTYA + 8 * (((T) + 7) & 7), 2, l0 && (T) > 0);                          \
        if (!(HF)) mbar_arrive_n_if(sb + BAR_EMPTYB + 8 * prev, 2, l0 && (T) > 0);                          \
        if (HF) { prev = rg.slot; rg.adv(); }                                                               \
    } while (0)
#pragma unroll 1
                for (int t = 0; t < 16; t += 2) { KT_P4(t, 0, 4); KT_P4(t + 1, 1, 4); }
#pragma unroll 1
                for (int t = 16; t < 24; t += 2) { KT_P4(t, 0, 3); KT_P4(t + 1, 1, 3); }
                wg_wait<0>();
                fence_acc<32>(acc0); fence_acc<32>(acc);
                TL(15, tid == 128);
#pragma unroll
                for (int t = 0; t < 8; t++)
                    sts128(xch + 2 * SLOT + t * 2048, __float_as_uint(acc0[4 * t]), __float_as_uint(acc0[4 * t + 1]),
                           __float_as_uint(acc0[4 * t + 2]), __float_as_uint(acc0[4 * t + 3]));
                bar_sync(5, 256);
            } else {
                bar_sync(5, 256);
#pragma unroll
                for (int t = 0; t < 8; t++) {
                    const float4 v = lds_f4(xch + 2 * SLOT + t * 2048);
                    acc[4 * t] = v.x; acc[4 * t + 1] = v.y; acc[4 * t + 2] = v.z; acc[4 * t + 3] = v.w;
                }
            }
            const float r0 = lds_f2(sb + OFF_CS1 + (16 * warp + g) * 8).y, r1 = lds_f2(sb + OFF_CS1 + (16 * warp + g + 8) * 8).y;
#pragma unroll
            for (int t = 0; t < 8; t++) {
                res_lo[t] = pack_bf16(fmaf(acc[4 * t], r0, bf_lo(res_lo[t])), fmaf(acc[4 * t + 1], r0, bf_hi(res_lo[t])));
                res_hi[t] = pack_bf16(fmaf(acc[4 * t + 2], r1, bf_lo(res_hi[t])), fmaf(acc[4 * t + 3], r1, bf_hi(res_hi[t])));
            }
            store_tile<false>(own_rows, P.out + (size_t)row_w * DM + 64 * j, res_lo, res_hi, lane);
            if (tid == 0 && role == 0) g_epoch = epoch + 1;
            TL(16, tid == 0); TLG(1, tid == 0);
        }
    }
}

typedef CUresult (*EncodeFn)(CUtensorMap*, CUtensorMapDataType, cuuint32_t, void*, const cuuint64_t*, const cuuint64_t*,
                             const cuuint32_t*, const cuuint32_t*, CUtensorMapInterleave, CUtensorMapSwizzle,
                             CUtensorMapL2promotion, CUtensorMapFloatOOBfill);

static void make_map2d(EncodeFn enc, CUtensorMap* tm, const void* base, uint64_t cols, uint64_t rows, uint64_t pitch_elems,
                       uint32_t box_rows) {
    cuuint64_t gd[2] = {cols, rows};
    cuuint64_t gs[1] = {pitch_elems * 2};
    cuuint32_t bd[2] = {64, box_rows};
    cuuint32_t es[2] = {1, 1};
    enc(tm, CU_TENSOR_MAP_DATA_TYPE_BFLOAT16, 2, const_cast<void*>(base), gd, gs, bd, es, CU_TENSOR_MAP_INTERLEAVE_NONE,
        CU_TENSOR_MAP_SWIZZLE_128B, CU_TENSOR_MAP_L2_PROMOTION_L2_256B, CU_TENSOR_MAP_FLOAT_OOB_FILL_NONE);
}

}

extern "C" void kernel_launch(void* const* d_in, const int* in_sizes, int n_in, void* d_out, int out_size) {
    using namespace hk;
    (void)in_sizes; (void)n_in; (void)out_size;
    static EncodeFn enc = nullptr;
    static void *po = nullptr, *ph = nullptr, *phh = nullptr;
    static int std_layout = 0;
    if (!enc) {
        void* fn = nullptr;
        cudaDriverEntryPointQueryResult qr;
        cudaGetDriverEntryPoint("cuTensorMapEncodeTiled", &fn, cudaEnableDefault, &qr);
        enc = (EncodeFn)fn;
        cudaGetSymbolAddress(&po, g_o);
        cudaGetSymbolAddress(&ph, g_h);
        cudaGetSymbolAddress(&phh, g_hh);
        cudaFuncSetAttribute(fused_kernel, cudaFuncAttributeMaxDynamicSharedMemorySize, SMEM_BYTES);
        int dev = 0, sms = 0;
        cudaGetDevice(&dev);
        cudaDeviceGetAttribute(&sms, cudaDevAttrMultiProcessorCount, dev);
        cudaFuncSetAttribute(fused_kernel, cudaFuncAttributeNonPortableClusterSizeAllowed, 1);
        const int sizes[3] = {8, 9, 16}, want[3] = {15, 9, 7};
        bool ok = sms == NCTA;
        for (int i = 0; i < 3 && ok; i++) {
            cudaLaunchConfig_t cfg = {};
            cfg.gridDim = dim3(sizes[i] * 8); cfg.blockDim = dim3(NTHREADS); cfg.dynamicSmemBytes = SMEM_BYTES;
            cudaLaunchAttribute at;
            at.id = cudaLaunchAttributeClusterDimension;
            at.val.clusterDim.x = sizes[i]; at.val.clusterDim.y = 1; at.val.clusterDim.z = 1;
            cfg.attrs = &at; cfg.numAttrs = 1;
            int n = 0;
            ok = cudaOccupancyMaxActiveClusters(&n, fused_kernel, &cfg) == cudaSuccess && n == want[i];
        }
        (void)cudaGetLastError();
        std_layout = ok ? 1 : 0;
    }
    Params P;
    const __nv_bfloat16* x = (const __nv_bfloat16*)d_in[0];
    P.x = x;
    P.wqkv = (const __nv_bfloat16*)d_in[1];
    P.wphi = (const __nv_bfloat16*)d_in[2];
    P.wo = (const __nv_bfloat16*)d_in[3];
    P.wg = (const __nv_bfloat16*)d_in[5];
    P.wu = (const __nv_bfloat16*)d_in[6];
    P.wd = (const __nv_bfloat16*)d_in[7];
    P.out = (__nv_bfloat16*)d_out;
    P.use_smid = std_layout;
    P.zero = 0;
    for (int i = 0; i < NCTA; i++) {
        int role = i < 4 ? 128 + i : i - 4;
        if (std_layout) {
            const int tpc = i >> 1, odd = i & 1;
            if (tpc < 32) role = (tpc & 7) * 8 + (tpc >> 3) * 2 + odd;
            else if (tpc < 60) role = (8 + (tpc - 32) % 7) * 8 + ((tpc - 32) / 7) * 2 + odd;
            else if (tpc < 62) role = 128 + (tpc - 60) * 2 + odd;
            else role = 15 * 8 + (tpc - 62) * 2 + odd;
        }
        P.role[i] = (unsigned char)role;
    }
    make_map2d(enc, &P.tx, x, DM, SEQ, DM, 128);
    make_map2d(enc, &P.to, po, DM, SEQ, DM, 128);
    make_map2d(enc, &P.th, ph, DM, SEQ, DM, 128);
    make_map2d(enc, &P.thh, phh, FFP, SEQ, FFP, 128);
    make_map2d(enc, &P.twq, P.wqkv, 3 * DM, DM, 3 * DM, 128);
    make_map2d(enc, &P.two, P.wo, DM, DM, DM, 128);
    make_map2d(enc, &P.twg, P.wg, FF, DM, FF, 64);
    make_map2d(enc, &P.twu, P.wu, FF, DM, FF, 64);
    make_map2d(enc, &P.twd, P.wd, DM, FF, DM, 64);
    {
        cuuint64_t gd[3] = {(cuuint64_t)DM, (cuuint64_t)DM, 3};
        cuuint64_t gs[2] = {(cuuint64_t)3 * DM * 2, (cuuint64_t)DM * 2};
        cuuint32_t bd[3] = {64, 64, 2};
        cuuint32_t es[3] = {1, 1, 1};
        enc(&P.twkv, CU_TENSOR_MAP_DATA_TYPE_BFLOAT16, 3, const_cast<__nv_bfloat16*>(P.wqkv), gd, gs, bd, es,
            CU_TENSOR_MAP_INTERLEAVE_NONE, CU_TENSOR_MAP_SWIZZLE_128B, CU_TENSOR_MAP_L2_PROMOTION_L2_256B,
            CU_TENSOR_MAP_FLOAT_OOB_FILL_NONE);
    }
    fused_kernel<<<NCTA, NTHREADS, SMEM_BYTES>>>(P);
}
```

```cpp
#include <cuda_runtime.h>
#include <cuda_bf16.h>
#include <cuda.h>
#include <stdint.h>

namespace hk {

constexpr int SEQ = 2048, DM = 512, FF = 1376, FFP = 1536;
constexpr int NCTA = 132;
constexpr int NTHREADS = 384;
constexpr uint32_t SLOT = 16384;
constexpr uint32_t OFF_A = 0, OFF_B = 8 * SLOT, OFF_MISC = 14 * SLOT;
constexpr uint32_t BAR_FULLA = OFF_MISC + 0, BAR_EMPTYA = OFF_MISC + 64, BAR_FULLB = OFF_MISC + 128,
                   BAR_EMPTYB = OFF_MISC + 176, BAR_CS1 = OFF_MISC + 224, BAR_CS3 = OFF_MISC + 232,
                   BAR_CSQ = OFF_MISC + 240, BAR_CSV = OFF_MISC + 248;
constexpr uint32_t OFF_CS1 = OFF_MISC + 384;
constexpr uint32_t OFF_CS3 = OFF_CS1 + 1024;
constexpr uint32_t SMEM_BYTES = OFF_CS3 + 1536;
constexpr int NB = 6;
constexpr int AHEAD = 3;

constexpr int ACC_KV = 0, ACC_Z = 2048, ACC_SIZE = 2176;

__device__ __align__(1024) __nv_bfloat16 g_o[SEQ * DM];
__device__ __align__(1024) __nv_bfloat16 g_h[SEQ * DM];
__device__ __align__(1024) __nv_bfloat16 g_hh[SEQ * FFP];
__device__ __align__(128) float g_hstat[SEQ * 16];
__device__ __align__(128) unsigned long long g_xstat[SEQ * 2];
__device__ __align__(128) float g_acc[8 * ACC_SIZE];
__device__ __align__(128) unsigned g_cnt[8 * 32];
__device__ __align__(128) unsigned long long g_cs[8 * 6 * 128];
__device__ __align__(128) unsigned g_flag[16 * 5 * 32];
__device__ unsigned g_epoch = 1;

#define TL(i, pred) do {} while (0)
#define TLG(i, pred) do {} while (0)

struct Params {
    CUtensorMap tx, to, th, thh, twkv, twq, two, twg, twu, twd;
    const __nv_bfloat16 *x, *wqkv, *wphi, *wo, *wg, *wu, *wd;
    __nv_bfloat16* out;
    int use_smid;
    unsigned zero;
    unsigned char role[NCTA];
};

__device__ __forceinline__ uint32_t smem_u32(const void* p) { return (uint32_t)__cvta_generic_to_shared(p); }
__device__ __forceinline__ void mbar_init(uint32_t bar, uint32_t cnt) {
    asm volatile("mbarrier.init.shared::cta.b64 [%0], %1;" ::"r"(bar), "r"(cnt) : "memory");
}
__device__ __forceinline__ void mbar_expect_tx(uint32_t bar, uint32_t bytes) {
    asm volatile("mbarrier.arrive.expect_tx.shared::cta.b64 _, [%0], %1;" ::"r"(bar), "r"(bytes) : "memory");
}
__device__ __forceinline__ void mbar_arrive(uint32_t bar) {
    asm volatile("mbarrier.arrive.shared::cta.b64 _, [%0];" ::"r"(bar) : "memory");
}
__device__ __forceinline__ void mbar_arrive_if(uint32_t bar, bool pred) {
    asm volatile("{.reg .pred p; setp.ne.u32 p, %1, 0; @p mbarrier.arrive.shared::cta.b64 _, [%0];}" ::"r"(bar), "r"((uint32_t)pred) : "memory");
}
__device__ __forceinline__ bool mbar_try(uint32_t bar, uint32_t parity) {
    uint32_t ok;
    asm volatile("{.reg .pred p; mbarrier.try_wait.parity.shared::cta.b64 p, [%1], %2; selp.u32 %0,1,0,p;}"
                 : "=r"(ok) : "r"(bar), "r"(parity) : "memory");
    return ok;
}
__device__ __forceinline__ bool mbar_test(uint32_t bar, uint32_t parity) {
    uint32_t ok;
    asm volatile("{.reg .pred p; mbarrier.test_wait.parity.shared::cta.b64 p, [%1], %2; selp.u32 %0,1,0,p;}"
                 : "=r"(ok) : "r"(bar), "r"(parity) : "memory");
    return ok;
}
__device__ __forceinline__ void trap_if_gt(uint32_t v, uint32_t lim) {
    asm volatile("{.reg .pred p; setp.gt.u32 p, %0, %1; @p trap;}" ::"r"(v), "r"(lim));
}
__device__ __forceinline__ void mbar_wait(uint32_t bar, uint32_t parity) {
    asm volatile("{\n"
                 ".reg .pred P1, P2;\n"
                 ".reg .u32 c;\n"
                 "mov.u32 c, 0;\n"
                 "LAB_WAIT:\n"
                 "mbarrier.try_wait.parity.shared::cta.b64 P1, [%0], %1;\n"
                 "@P1 bra LAB_DONE;\n"
                 "add.u32 c, c, 1;\n"
                 "setp.gt.u32 P2, c, 4194304;\n"
                 "@P2 trap;\n"
                 "bra LAB_WAIT;\n"
                 "LAB_DONE:\n"
                 "}" ::"r"(bar), "r"(parity) : "memory");
}
__device__ __forceinline__ void mbar_waitc(uint32_t bar, uint32_t parity) {
    asm volatile("{\n"
                 ".reg .pred P1;\n"
                 "LAB_WAIT:\n"
                 "mbarrier.try_wait.parity.shared::cta.b64 P1, [%0], %1;\n"
                 "@!P1 bra LAB_WAIT;\n"
                 "}" ::"r"(bar), "r"(parity) : "memory");
}
__device__ __forceinline__ void tma2d(uint32_t dst, const CUtensorMap* tm, uint32_t bar, int c0, int c1) {
    asm volatile("cp.async.bulk.tensor.2d.shared::cluster.global.mbarrier::complete_tx::bytes [%0], [%1, {%3, %4}], [%2];"
                 ::"r"(dst), "l"(tm), "r"(bar), "r"(c0), "r"(c1) : "memory");
}
__device__ __forceinline__ void tma3d(uint32_t dst, const CUtensorMap* tm, uint32_t bar, int c0, int c1, int c2) {
    asm volatile("cp.async.bulk.tensor.3d.shared::cluster.global.mbarrier::complete_tx::bytes [%0], [%1, {%3, %4, %5}], [%2];"
                 ::"r"(dst), "l"(tm), "r"(bar), "r"(c0), "r"(c1), "r"(c2) : "memory");
}
__device__ __forceinline__ bool elect_one() {
    uint32_t ok;
    asm volatile("{.reg .pred p; elect.sync _|p, 0xffffffff; selp.u32 %0, 1, 0, p;}" : "=r"(ok));
    return ok;
}
__device__ __forceinline__ void prefetch_tmap(const CUtensorMap* tm) {
    asm volatile("prefetch.tensormap [%0];" ::"l"(tm) : "memory");
}
__device__ __forceinline__ void prefetch_l2(const void* p, uint32_t bytes) {
    asm volatile("cp.async.bulk.prefetch.L2.global [%0], %1;" ::"l"(p), "r"(bytes) : "memory");
}
__device__ __forceinline__ unsigned ld_acquire(const unsigned* p) {
    unsigned v; asm volatile("ld.acquire.gpu.global.u32 %0, [%1];" : "=r"(v) : "l"(p) : "memory"); return v;
}
__device__ __forceinline__ uint4 ld_acquire4(const unsigned* p) {
    uint4 v;
    asm volatile("ld.acquire.gpu.global.v4.u32 {%0,%1,%2,%3}, [%4];" : "=r"(v.x), "=r"(v.y), "=r"(v.z), "=r"(v.w) : "l"(p) : "memory");
    return v;
}
__device__ __forceinline__ unsigned ld_relaxed(const unsigned* p) {
    unsigned v; asm volatile("ld.relaxed.gpu.global.u32 %0, [%1];" : "=r"(v) : "l"(p)); return v;
}
__device__ __forceinline__ void st_relaxed(unsigned* p, unsigned v) {
    asm volatile("st.relaxed.gpu.global.u32 [%0], %1;" ::"l"(p), "r"(v) : "memory");
}
__device__ __forceinline__ void red_relaxed(unsigned* p, unsigned v) {
    asm volatile("red.relaxed.gpu.global.add.u32 [%0], %1;" ::"l"(p), "r"(v) : "memory");
}
__device__ __forceinline__ void fence_gpu() { asm volatile("fence.acq_rel.gpu;" ::: "memory"); }
__device__ __forceinline__ void fence_async_smem() { asm volatile("fence.proxy.async.shared::cta;" ::: "memory"); }
__device__ __forceinline__ void fence_async_global() { asm volatile("fence.proxy.async.global;" ::: "memory"); }
__device__ __forceinline__ void wait_count(const unsigned* p, unsigned target) {
    uint32_t it = 0;
    while ((int)(ld_acquire(p) - target) < 0) trap_if_gt(++it, 1u << 22);
}
__device__ __forceinline__ void wait_count_warp(const unsigned* p, unsigned target) {
    uint32_t it = 0;
    while (__any_sync(0xffffffffu, (int)(ld_acquire(p) - target) < 0)) trap_if_gt(++it, 1u << 22);
}
__device__ __forceinline__ void red_f32(float* p, float a) {
    asm volatile("red.relaxed.gpu.global.add.f32 [%0], %1;" ::"l"(p), "f"(a) : "memory");
}
__device__ __forceinline__ void red_f32x2(float* p, float a, float b) {
    asm volatile("red.relaxed.gpu.global.add.v2.f32 [%0], {%1, %2};" ::"l"(p), "f"(a), "f"(b) : "memory");
}
__device__ __forceinline__ void red_f32x4(float* p, float a, float b, float c, float d) {
    asm volatile("red.relaxed.gpu.global.add.v4.f32 [%0], {%1, %2, %3, %4};" ::"l"(p), "f"(a), "f"(b), "f"(c), "f"(d) : "memory");
}
__device__ __forceinline__ float4 ld_l2_f4(const float* p) {
    float4 v;
    asm volatile("ld.relaxed.gpu.global.v4.f32 {%0,%1,%2,%3}, [%4];" : "=f"(v.x), "=f"(v.y), "=f"(v.z), "=f"(v.w) : "l"(p) : "memory");
    return v;
}
__device__ __forceinline__ float2 ld_l2_f2(const float* p) {
    float2 v;
    asm volatile("ld.relaxed.gpu.global.v2.f32 {%0,%1}, [%2];" : "=f"(v.x), "=f"(v.y) : "l"(p) : "memory");
    return v;
}
__device__ __forceinline__ float ld_l2_f(const float* p) {
    float v;
    asm volatile("ld.relaxed.gpu.global.f32 %0, [%1];" : "=f"(v) : "l"(p) : "memory");
    return v;
}
__device__ __forceinline__ uint4 ldg_nc(const void* p) {
    uint4 v;
    asm volatile("ld.global.nc.L1::no_allocate.v4.u32 {%0,%1,%2,%3}, [%4];" : "=r"(v.x), "=r"(v.y), "=r"(v.z), "=r"(v.w) : "l"(p));
    return v;
}
__device__ __forceinline__ void stg128(void* p, uint32_t a, uint32_t b, uint32_t c, uint32_t d) {
    asm volatile("st.global.v4.u32 [%0], {%1,%2,%3,%4};" ::"l"(p), "r"(a), "r"(b), "r"(c), "r"(d) : "memory");
}
__device__ __forceinline__ uint4 lds128(uint32_t a) {
    uint4 v;
    asm volatile("ld.shared.v4.u32 {%0,%1,%2,%3}, [%4];" : "=r"(v.x), "=r"(v.y), "=r"(v.z), "=r"(v.w) : "r"(a) : "memory");
    return v;
}
__device__ __forceinline__ float2 lds_f2(uint32_t a) {
    float2 v;
    asm volatile("ld.shared.v2.f32 {%0,%1}, [%2];" : "=f"(v.x), "=f"(v.y) : "r"(a) : "memory");
    return v;
}
__device__ __forceinline__ void sts_f2(uint32_t a, float x, float y) {
    asm volatile("st.shared.v2.f32 [%0], {%1,%2};" ::"r"(a), "f"(x), "f"(y) : "memory");
}
__device__ __forceinline__ void sts64(uint32_t a, uint32_t x, uint32_t y) {
    asm volatile("st.shared.v2.u32 [%0], {%1,%2};" ::"r"(a), "r"(x), "r"(y) : "memory");
}
__device__ __forceinline__ void sts128(uint32_t a, uint32_t x, uint32_t y, uint32_t z, uint32_t w) {
    asm volatile("st.shared.v4.u32 [%0], {%1,%2,%3,%4};" ::"r"(a), "r"(x), "r"(y), "r"(z), "r"(w) : "memory");
}
__device__ __forceinline__ void stsm4(uint32_t a, uint32_t r0, uint32_t r1, uint32_t r2, uint32_t r3) {
    asm volatile("stmatrix.sync.aligned.m8n8.x4.shared.b16 [%0], {%1,%2,%3,%4};" ::"r"(a), "r"(r0), "r"(r1), "r"(r2), "r"(r3) : "memory");
}
__device__ __forceinline__ void ldsm4(uint32_t a, uint32_t& r0, uint32_t& r1, uint32_t& r2, uint32_t& r3) {
    asm volatile("ldmatrix.sync.aligned.m8n8.x4.shared.b16 {%0,%1,%2,%3}, [%4];" : "=r"(r0), "=r"(r1), "=r"(r2), "=r"(r3) : "r"(a) : "memory");
}
__device__ __forceinline__ void ldsm4t(uint32_t a, uint32_t& r0, uint32_t& r1, uint32_t& r2, uint32_t& r3) {
    asm volatile("ldmatrix.sync.aligned.m8n8.x4.trans.shared.b16 {%0,%1,%2,%3}, [%4];" : "=r"(r0), "=r"(r1), "=r"(r2), "=r"(r3) : "r"(a) : "memory");
}
__device__ __forceinline__ void mma16816(float* c, const uint32_t* a, uint32_t b0, uint32_t b1) {
    asm("mma.sync.aligned.m16n8k16.row.col.f32.bf16.bf16.f32 {%0,%1,%2,%3}, {%4,%5,%6,%7}, {%8,%9}, {%0,%1,%2,%3};"
                 : "+f"(c[0]), "+f"(c[1]), "+f"(c[2]), "+f"(c[3])
                 : "r"(a[0]), "r"(a[1]), "r"(a[2]), "r"(a[3]), "r"(b0), "r"(b1));
}
__device__ __forceinline__ uint32_t pack_bf16(float lo, float hi) {
    uint32_t r; asm("cvt.rn.bf16x2.f32 %0, %1, %2;" : "=r"(r) : "f"(hi), "f"(lo)); return r;
}
__device__ __forceinline__ float bf_lo(uint32_t w) { return __uint_as_float(w << 16); }
__device__ __forceinline__ float bf_hi(uint32_t w) { return __uint_as_float(w & 0xffff0000u); }
__device__ __forceinline__ float ex2(float x) { float r; asm("ex2.approx.ftz.f32 %0, %1;" : "=f"(r) : "f"(x)); return r; }
__device__ __forceinline__ float rcp(float x) { float r; asm("rcp.approx.ftz.f32 %0, %1;" : "=f"(r) : "f"(x)); return r; }
__device__ __forceinline__ void bar_sync(int id, int n) { asm volatile("bar.sync %0, %1;" ::"r"(id), "r"(n) : "memory"); }

typedef unsigned long long desc_t;
__device__ __forceinline__ desc_t desc_lo(uint32_t addr) { return (desc_t)(((addr & 0x3FFFF) >> 4) | (512u << 16)) | (0x40000040ull << 32); }
__device__ __forceinline__ void wg_fence() { asm volatile("wgmma.fence.sync.aligned;" ::: "memory"); }
__device__ __forceinline__ void wg_commit() { asm volatile("wgmma.commit_group.sync.aligned;" ::: "memory"); }
template <int N> __device__ __forceinline__ void wg_wait() { asm volatile("wgmma.wait_group.sync.aligned %0;" ::"n"(N) : "memory"); }
template <int N> __device__ __forceinline__ void fence_acc(float* d) {
#pragma unroll
    for (int i = 0; i < N; i++) asm volatile("" : "+f"(d[i])::"memory");
}
#define R4(o) "+f"(d[o + 0]), "+f"(d[o + 1]), "+f"(d[o + 2]), "+f"(d[o + 3])
#define R8(o) R4(o), R4(o + 4)
__device__ __forceinline__ void wgmma_n128(float* d, desc_t da, desc_t db, int sc) {
    asm volatile("{.reg .pred p; setp.ne.b32 p, %66, 0;\n"
                 "wgmma.mma_async.sync.aligned.m64n128k16.f32.bf16.bf16 {%0,%1,%2,%3,%4,%5,%6,%7,%8,%9,%10,%11,%12,%13,%14,%15,%16,%17,%18,%19,%20,%21,%22,%23,%24,%25,%26,%27,%28,%29,%30,%31,"
                 "%32,%33,%34,%35,%36,%37,%38,%39,%40,%41,%42,%43,%44,%45,%46,%47,%48,%49,%50,%51,%52,%53,%54,%55,%56,%57,%58,%59,%60,%61,%62,%63}, %64, %65, p, 1, 1, 0, 1;}"
                 : R8(0), R8(8), R8(16), R8(24), R8(32), R8(40), R8(48), R8(56)
                 : "l"(da), "l"(db), "r"(sc));
}
__device__ __forceinline__ void wgmma_n64(float* d, desc_t da, desc_t db, int sc) {
    asm volatile("{.reg .pred p; setp.ne.b32 p, %34, 0;\n"
                 "wgmma.mma_async.sync.aligned.m64n64k16.f32.bf16.bf16 {%0,%1,%2,%3,%4,%5,%6,%7,%8,%9,%10,%11,%12,%13,%14,%15,%16,%17,%18,%19,%20,%21,%22,%23,%24,%25,%26,%27,%28,%29,%30,%31}, %32, %33, p, 1, 1, 0, 1;}"
                 : R8(0), R8(8), R8(16), R8(24)
                 : "l"(da), "l"(db), "r"(sc));
}
__device__ __forceinline__ void wgmma_n40_tt(float* d, desc_t da, desc_t db, int sc) {
    asm volatile("{.reg .pred p; setp.ne.b32 p, %22, 0;\n"
                 "wgmma.mma_async.sync.aligned.m64n40k16.f32.bf16.bf16 {%0,%1,%2,%3,%4,%5,%6,%7,%8,%9,%10,%11,%12,%13,%14,%15,%16,%17,%18,%19}, %20, %21, p, 1, 1, 1, 1;}"
                 : R8(0), R8(8), R4(16)
                 : "l"(da), "l"(db), "r"(sc));
}

__device__ __forceinline__ void wgmma_n8_tt(float* d, desc_t da, desc_t db, int sc) {
    asm volatile("{.reg .pred p; setp.ne.b32 p, %6, 0;\n"
                 "wgmma.mma_async.sync.aligned.m64n8k16.f32.bf16.bf16 {%0,%1,%2,%3}, %4, %5, p, 1, 1, 1, 1;}"
                 : R4(0)
                 : "l"(da), "l"(db), "r"(sc));
}

__device__ __forceinline__ uint32_t readback(const void* p) {
    uint32_t v; asm volatile("ld.relaxed.gpu.global.u32 %0, [%1];" : "=r"(v) : "l"(p) : "memory"); return v;
}
__device__ __forceinline__ uint32_t atom_f32x2(float* p, float a, float b) {
    float x, y;
    asm volatile("atom.relaxed.gpu.global.add.v2.f32 {%0,%1}, [%2], {%3,%4};" : "=f"(x), "=f"(y) : "l"(p), "f"(a), "f"(b) : "memory");
    return __float_as_uint(x);
}
__device__ __forceinline__ uint32_t atom_f32_if(float* p, float a, bool pred) {
    float x = 0.f;
    asm volatile("{.reg .pred p; setp.ne.u32 p, %3, 0; @p atom.relaxed.gpu.global.add.f32 %0, [%1], %2;}" : "+f"(x) : "l"(p), "f"(a), "r"((uint32_t)pred) : "memory");
    return __float_as_uint(x);
}
__device__ __forceinline__ void signal_after(unsigned* cnt, uint32_t ack, uint32_t zero, bool pred) {
    asm volatile("{.reg .pred p; setp.ne.u32 p, %2, 0; @p red.relaxed.gpu.global.add.u32 [%0], %1;}"
                 ::"l"(cnt), "r"((ack & zero) + 1), "r"((uint32_t)pred) : "memory");
}
__device__ __forceinline__ void red_f32_if(float* p, float a, bool pred) {
    asm volatile("{.reg .pred p; setp.ne.u32 p, %2, 0; @p red.relaxed.gpu.global.add.f32 [%0], %1;}" ::"l"(p), "f"(a), "r"((uint32_t)pred) : "memory");
}
__device__ __forceinline__ void stg_f2_if(float* p, float a, float b, bool pred) {
    asm volatile("{.reg .pred p; setp.ne.u32 p, %3, 0; @p st.global.v2.f32 [%0], {%1,%2};}" ::"l"(p), "f"(a), "f"(b), "r"((uint32_t)pred) : "memory");
}
__device__ __forceinline__ void stg64(void* p, uint32_t a, uint32_t b) {
    asm volatile("st.global.v2.u32 [%0], {%1,%2};" ::"l"(p), "r"(a), "r"(b) : "memory");
}
__device__ __forceinline__ uint32_t store_pair(__nv_bfloat16* p, uint32_t r0, uint32_t r1, bool odd) {
    const uint32_t x = __shfl_xor_sync(0xffffffffu, odd ? r0 : r1, 1);
    stg64(p, odd ? x : r0, odd ? r1 : x);
    return readback(p);
}
__device__ __forceinline__ void mma16816_z(float* c, const uint32_t* a, uint32_t b0, uint32_t b1) {
    asm("mma.sync.aligned.m16n8k16.row.col.f32.bf16.bf16.f32 {%0,%1,%2,%3}, {%4,%5,%6,%7}, {%8,%9}, {%10,%10,%10,%10};"
                 : "=f"(c[0]), "=f"(c[1]), "=f"(c[2]), "=f"(c[3])
                 : "r"(a[0]), "r"(a[1]), "r"(a[2]), "r"(a[3]), "r"(b0), "r"(b1), "f"(0.f));
}
__device__ __forceinline__ uint32_t max2(uint32_t a, uint32_t b) { uint32_t r; asm("max.bf16x2 %0, %1, %2;" : "=r"(r) : "r"(a), "r"(b)); return r; }
__device__ __forceinline__ uint32_t min2(uint32_t a, uint32_t b) { uint32_t r; asm("min.bf16x2 %0, %1, %2;" : "=r"(r) : "r"(a), "r"(b)); return r; }
__device__ __forceinline__ void bar_arrive(int id, int n) { asm volatile("bar.arrive %0, %1;" ::"r"(id), "r"(n) : "memory"); }
__device__ __forceinline__ void mbar_arrive_n_if(uint32_t bar, uint32_t n, bool pred) {
    asm volatile("{.reg .pred p; setp.ne.u32 p, %1, 0; @p mbarrier.arrive.shared::cta.b64 _, [%0], %2;}" ::"r"(bar), "r"((uint32_t)pred), "r"(n) : "memory");
}
__device__ __forceinline__ float4 lds_f4(uint32_t a) {
    float4 v;
    asm volatile("ld.shared.v4.f32 {%0,%1,%2,%3}, [%4];" : "=f"(v.x), "=f"(v.y), "=f"(v.z), "=f"(v.w) : "r"(a) : "memory");
    return v;
}
__device__ __forceinline__ uint4 ld_tagged(const unsigned long long* p) {
    unsigned long long a, b;
    asm volatile("ld.acquire.gpu.global.v2.b64 {%0,%1}, [%2];" : "=l"(a), "=l"(b) : "l"(p) : "memory");
    return make_uint4((unsigned)a, (unsigned)(a >> 32), (unsigned)b, (unsigned)(b >> 32));
}
__device__ __forceinline__ uint4 ld_tagged_rlx(const unsigned long long* p) {
    unsigned long long a, b;
    asm volatile("ld.relaxed.gpu.global.v2.b64 {%0,%1}, [%2];" : "=l"(a), "=l"(b) : "l"(p) : "memory");
    return make_uint4((unsigned)a, (unsigned)(a >> 32), (unsigned)b, (unsigned)(b >> 32));
}
__device__ __forceinline__ void st_tagged_if(unsigned long long* p, float a, float b, unsigned tag, bool pred) {
    const unsigned long long t = (unsigned long long)tag << 32;
    asm volatile("{.reg .pred p; setp.ne.u32 p, %3, 0; @p st.relaxed.gpu.global.v2.b64 [%0], {%1,%2};}"
                 ::"l"(p), "l"(t | __float_as_uint(a)), "l"(t | __float_as_uint(b)), "r"((uint32_t)pred) : "memory");
}

template <bool ACK>
__device__ __forceinline__ uint32_t store_tile(uint32_t tile_rows, __nv_bfloat16* gdst, const uint32_t* lo, const uint32_t* hi, int lane) {
    const int r = lane & 15;
#pragma unroll
    for (int b = 0; b < 4; b++)
        stsm4(tile_rows + r * 128 + (((2 * b + (lane >> 4)) ^ (r & 7)) << 4), lo[2 * b], hi[2 * b], lo[2 * b + 1], hi[2 * b + 1]);
    __syncwarp();
    uint32_t ack = 0;
#pragma unroll
    for (int i = 0; i < 4; i++) {
        const int rr = 4 * i + (lane >> 3);
        const uint4 v = lds128(tile_rows + rr * 128 + (((lane & 7) ^ (rr & 7)) << 4));
        stg128(gdst + rr * DM + (lane & 7) * 8, v.x, v.y, v.z, v.w);
    }
    if (ACK) {
#pragma unroll
        for (int i = 0; i < 4; i++) ack |= readback(gdst + (4 * i + (lane >> 3)) * DM + (lane & 7) * 8);
    }
    return ack;
}

template <bool NORM>
__device__ __forceinline__ void feature_map(const uint32_t* a, const uint32_t* wb, float c0, float c1, uint32_t* plus, uint32_t* minus, float* rs) {
    float p[8];
    mma16816_z(p, a, wb[0], wb[1]);
    mma16816_z(p + 4, a, wb[2], wb[3]);
    const uint32_t P0 = pack_bf16(p[0], p[2]), P1 = pack_bf16(p[1], p[3]), P2 = pack_bf16(p[4], p[6]), P3 = pack_bf16(p[5], p[7]);
    uint32_t mx = max2(max2(P0, P1), max2(P2, P3)), mn = min2(min2(P0, P1), min2(P2, P3));
#pragma unroll
    for (int s = 1; s <= 2; s <<= 1) {
        mx = max2(mx, __shfl_xor_sync(0xffffffffu, mx, s));
        mn = min2(mn, __shfl_xor_sync(0xffffffffu, mn, s));
    }
    const float mx0 = bf_lo(mx) * c0, mx1 = bf_hi(mx) * c1, mn0 = bf_lo(mn) * c0, mn1 = bf_hi(mn) * c1;
    p[0] = bf_lo(P0); p[2] = bf_hi(P0); p[1] = bf_lo(P1); p[3] = bf_hi(P1);
    p[4] = bf_lo(P2); p[6] = bf_hi(P2); p[5] = bf_lo(P3); p[7] = bf_hi(P3);
    float ep[8], em[8];
#pragma unroll
    for (int i = 0; i < 8; i++) {
        const bool r1 = (i & 2);
        ep[i] = ex2(fmaf(p[i], r1 ? c1 : c0, r1 ? -mx1 : -mx0));
        em[i] = ex2(fmaf(p[i], r1 ? -c1 : -c0, r1 ? mn1 : mn0));
    }
    float sp[4], sm[4];
#pragma unroll
    for (int i = 0; i < 4; i++) { plus[i] = pack_bf16(ep[2 * i], ep[2 * i + 1]); minus[i] = pack_bf16(em[2 * i], em[2 * i + 1]); }
    mma16816_z(sp, plus, 0x3f803f80u, 0x3f803f80u);
    mma16816_z(sm, minus, 0x3f803f80u, 0x3f803f80u);
    rs[0] = rcp(sp[0]); rs[1] = rcp(sp[2]); rs[2] = rcp(sm[0]); rs[3] = rcp(sm[2]);
    if (NORM) {
#pragma unroll
        for (int i = 0; i < 4; i++) {
            plus[i] = pack_bf16(ep[2 * i] * rs[i & 1], ep[2 * i + 1] * rs[i & 1]);
            minus[i] = pack_bf16(em[2 * i] * rs[2 + (i & 1)], em[2 * i + 1] * rs[2 + (i & 1)]);
        }
    }
}

template <bool SCALE>
__device__ __forceinline__ void ln_frag(const float* acc, uint32_t cs_addr, float rs0, float nm0, float rs1, float nm1, uint32_t* a) {
    const float2 c0 = lds_f2(cs_addr), c1 = lds_f2(cs_addr + 32);
    const float s0 = SCALE ? rs0 : 1.f, s1 = SCALE ? rs1 : 1.f;
    a[0] = pack_bf16(fmaf(nm0, c0.x, acc[0]) * s0, fmaf(nm0, c0.y, acc[1]) * s0);
    a[1] = pack_bf16(fmaf(nm1, c0.x, acc[2]) * s1, fmaf(nm1, c0.y, acc[3]) * s1);
    a[2] = pack_bf16(fmaf(nm0, c1.x, acc[4]) * s0, fmaf(nm0, c1.y, acc[5]) * s0);
    a[3] = pack_bf16(fmaf(nm1, c1.x, acc[6]) * s1, fmaf(nm1, c1.y, acc[7]) * s1);
}

__device__ __forceinline__ uint32_t hh_pair(const float* ag, float4 cs, float nmean) {
    const float g0 = fmaf(nmean, cs.x, ag[0]), g1 = fmaf(nmean, cs.y, ag[1]);
    const float u0 = fmaf(nmean, cs.z, ag[32]), u1 = fmaf(nmean, cs.w, ag[33]);
    return pack_bf16(g0 * u0, g1 * u1);
}

struct Ring {
    int slot; uint32_t phase;
    __device__ __forceinline__ void adv() { if (++slot == NB) { slot = 0; phase ^= 1; } }
};

__global__ void __launch_bounds__(NTHREADS, 1) fused_kernel(const __grid_constant__ Params P) {
    extern __shared__ __align__(1024) uint8_t smem_raw[];
    const uint32_t sb = smem_u32(smem_raw);
    const int tid = threadIdx.x, lane = tid & 31;
    const int warp = __shfl_sync(0xffffffffu, tid >> 5, 0);
    unsigned role = blockIdx.x;
    if (P.use_smid) asm volatile("mov.u32 %0, %%smid;" : "=r"(role));
    role = P.role[role];
    const int m = role >> 3, j = role & 7;
    const bool helper = role >= 128;

    TL(0, tid == 0); TLG(0, tid == 0);
    float* const acc_j = g_acc + j * ACC_SIZE;
    unsigned* const cnt_j = g_cnt + j * 32;

    if (__builtin_expect(warp >= 8, 1)) {
        asm volatile("setmaxnreg.dec.sync.aligned.u32 72;");
        if (elect_one()) {
            if (warp == 8) {
                if (!helper) {
#pragma unroll
                    for (int i = 0; i < NB; i++) mbar_init(sb + BAR_FULLB + 8 * i, 1);
#pragma unroll
                    for (int i = 0; i < 2; i++) {
                        mbar_expect_tx(sb + BAR_FULLB + 8 * i, SLOT);
                        tma3d(sb + OFF_B + i * SLOT, &P.twkv, sb + BAR_FULLB + 8 * i, 64 * j, 64 * i, 1);
                    }
                }
            } else if (warp == 9) {
#pragma unroll
                for (int i = 0; i < 8; i++) mbar_init(sb + BAR_FULLA + 8 * i, 1);
#pragma unroll
                for (int i = 0; i < 2; i++) {
                    mbar_expect_tx(sb + BAR_FULLA + 8 * i, SLOT);
                    tma2d(sb + OFF_A + i * SLOT, helper ? &P.twq : &P.tx, sb + BAR_FULLA + 8 * i, helper ? DM + 128 * j : 64 * i, 128 * (helper ? i : m));
                }
            } else if (warp == 10) {
#pragma unroll
                for (int i = 0; i < 4; i++) mbar_init(sb + BAR_CS1 + 8 * i, i == 1 ? 160 : 32);
                trap_if_gt(sb & 1023, 0);
            } else {
#pragma unroll
                for (int i = 0; i < 14; i++) mbar_init(sb + (i < 8 ? BAR_EMPTYA : BAR_EMPTYB - 64) + 8 * i, 8);
            }
        }
        __syncwarp();
        const unsigned epoch = ld_relaxed(&g_epoch);
        bar_sync(0, NTHREADS);
        if (helper) {
            if (warp == 8) {
                if (elect_one()) {
#pragma unroll 1
                    for (int i = 2; i < 72; i++) {
                        const uint32_t full = sb + BAR_FULLA + 8 * (i & 7), dst = sb + OFF_A + (i & 7) * SLOT;
                        mbar_wait(sb + BAR_EMPTYA + 8 * (i & 7), ((i >> 3) & 1) ^ 1);
                        mbar_expect_tx(full, SLOT);
                        if (i < 24) {
                            tma2d(dst, &P.twq, full, (i < 16 ? DM + 64 * (i & 8) : 0) + 128 * j + 16 * (i & 4), 128 * (i & 3));
                        } else {
                            const int u = (i >> 3) - 3, c0 = 176 * (2 * j + (u & 1)) + 64 * (u >> 1);
                            tma2d(dst, &P.twg, full, c0, 64 * (i & 7));
                            tma2d(dst + 8192, &P.twu, full, c0, 64 * (i & 7));
                        }
                    }
                    prefetch_l2(P.wd + (size_t)j * 176128, 352256);
                }
            } else if (warp == 9) {
                wait_count_warp(g_cnt + (lane & 7) * 32, epoch * 128);
            }
            return;
        }
        if (warp == 8) {
            if (elect_one()) {
                if (m >= 3 && m < 8)
                    asm volatile("cp.async.bulk.prefetch.tensor.3d.L2.global [%0, {%1, %2, %3}];" ::"l"(&P.twkv), "r"(64 * j), "r"(64 * m), "r"(1) : "memory");
                if (j >= 3)
                    asm volatile("cp.async.bulk.prefetch.tensor.2d.L2.global [%0, {%1, %2}];" ::"l"(&P.tx), "r"(64 * j), "r"(128 * m) : "memory");
                Ring r{2, 0};
#pragma unroll 1
                for (int i = 2; i < 56; i++) {
                    const uint32_t full = sb + BAR_FULLB + 8 * r.slot, dst = sb + OFF_B + r.slot * SLOT;
                    mbar_wait(sb + BAR_EMPTYB + 8 * r.slot, r.phase ^ 1);
                    if (i >= 8 && i < 12) {
                        mbar_arrive(full);
                    } else {
                        if (i >= AHEAD && i < 6) mbar_wait(full - 8 * AHEAD, 0);
                        mbar_expect_tx(full, SLOT);
                        if (i < 8) {
                            tma3d(dst, &P.twkv, full, 64 * j, 64 * i, 1);
                        } else if (i < 20) {
                            tma2d(dst, i < 16 ? &P.twq : &P.two, full, 64 * j, 128 * (i & 3));
                        } else if (i < 44) {
                            const int c = (i - 20) >> 3, kt = (i - 20) & 7;
                            tma2d(dst, &P.twg, full, 176 * j + 64 * c, 64 * kt);
                            tma2d(dst + 8192, &P.twu, full, 176 * j + 64 * c, 64 * kt);
                        } else {
                            const int c = (i - 44) >> 2, jj = (i & 3) * 2;
                            tma2d(dst, &P.twd, full, 64 * j, 176 * jj + 64 * c);
                            tma2d(dst + 8192, &P.twd, full, 64 * j, 176 * (jj + 1) + 64 * c);
                        }
                    }
                    r.adv();
                }
            }
            return;
        }
        if (warp == 9) {
            if (elect_one()) {
#pragma unroll 1
                for (int i = 2; i < 8; i++) {
                    if (i >= AHEAD + 1) mbar_wait(sb + BAR_FULLA + 8 * (i - AHEAD - 1), 0);
                    mbar_expect_tx(sb + BAR_FULLA + 8 * i, SLOT);
                    tma2d(sb + OFF_A + i * SLOT, &P.tx, sb + BAR_FULLA + 8 * i, 64 * i, 128 * m);
                }
#pragma unroll 1
                for (int i = 1; i < 10; i++) prefetch_tmap(&P.tx + i);
#pragma unroll 1
                for (int r = 1; r < 6; r++) {
                    const CUtensorMap* tm = &P.tx + min(r, 3);
                    const int cstep = r < 3 ? 64 : 192, cbase = r < 3 ? 0 : 64 * (r - 3), skip = r < 3 ? j : 8;
                    wait_count(g_flag + (m * 5 + r - 1) * 32, epoch * (r < 3 ? 64 : 32));
#pragma unroll 1
                    for (int t = 0; t < 8; t++) {
                        if (t == skip) continue;
                        mbar_wait(sb + BAR_EMPTYA + 8 * t, (r - 1) & 1);
                        TL(56 + 8 * r + (t == 7), t == 7 || t == (skip == 0));
                        mbar_expect_tx(sb + BAR_FULLA + 8 * t, SLOT);
                        tma2d(sb + OFF_A + t * SLOT, tm, sb + BAR_FULLA + 8 * t, cbase + cstep * t, 128 * m);
                    }
                }
            }
            return;
        }
        const int a = warp - 10;
        {
            const int row = 16 * j + 8 * a + (lane >> 2);
            const uint32_t ra = sb + OFF_A + row * 128;
            float sh = 0.f, s0 = 0.f, s1 = 0.f, q0 = 0.f, q1 = 0.f;
#pragma unroll 1
            for (int kt = 0; kt < 8; kt++) {
                mbar_wait(sb + BAR_FULLA + 8 * kt, 0);
                if (kt == 0) sh = bf_lo(lds128(ra + ((row & 7) << 4)).x);
#pragma unroll
                for (int i = 0; i < 2; i++) {
                    const uint4 v = lds128(ra + kt * SLOT + (((2 * (lane & 3) + i) ^ (row & 7)) << 4));
                    const uint32_t ww[4] = {v.x, v.y, v.z, v.w};
#pragma unroll
                    for (int e = 0; e < 4; e++) {
                        const float d0 = bf_lo(ww[e]) - sh, d1 = bf_hi(ww[e]) - sh;
                        s0 += d0; q0 = fmaf(d0, d0, q0);
                        s1 += d1; q1 = fmaf(d1, d1, q1);
                    }
                }
            }
            s0 += s1; q0 += q1;
#pragma unroll
            for (int o = 1; o <= 2; o <<= 1) { s0 += __shfl_xor_sync(0xffffffffu, s0, o); q0 += __shfl_xor_sync(0xffffffffu, q0, o); }
            const float md = s0 * (1.f / DM);
            const float rs = rsqrtf(fmaxf(q0 * (1.f / DM) - md * md, 0.f) + 1e-5f);
            st_tagged_if(g_xstat + 2 * (128 * m + row), rs, -(sh + md), epoch, (lane & 3) == 0);
        }
        const unsigned long long* cs = g_cs + j * 768 + 2 * lane;
#pragma unroll 1
        for (int c = 0; c < (a ? 2 : 7); c++) {
            uint4 v;
            uint32_t it = 0;
            while (true) {
                v = ld_tagged(cs + (a ? 128 + 128 * c : (c ? 320 + 64 * c : 0)));
                if (!__any_sync(0xffffffffu, v.y != epoch || v.w != epoch)) break;
                __nanosleep(100);
                trap_if_gt(++it, 1u << 22);
            }
            sts64(a || !c ? sb + OFF_CS1 + (a ? 512 - 512 * c : 256) + 8 * lane : sb + OFF_CS3 + (32 * ((c - 1) >> 1) + lane) * 16 + 8 * ((c - 1) & 1), v.x, v.z);
            if (a || c == 0 || c == 6) mbar_arrive(sb + (a ? (c ? BAR_CSQ : BAR_CSV) : (c ? BAR_CS3 : BAR_CS1)));
        }
        return;
    }
    const unsigned epoch = ld_relaxed(&g_epoch);
    uint32_t wraw[16];
    if (!helper) {
        const uint32_t* wp = reinterpret_cast<const uint32_t*>(P.wphi) + (4 * j) * 128 + (lane & 3) * 16 + (lane >> 2);
#pragma unroll
        for (int i = 0; i < 16; i++)
            asm volatile("ld.global.nc.u32 %0, [%1];" : "=r"(wraw[i]) : "l"(wp + (i >> 2) * 128 + ((i >> 1) & 1) * 64 + (i & 1) * 8));
    }
    asm volatile("setmaxnreg.inc.sync.aligned.u32 216;");
    bar_sync(0, NTHREADS);
    if (helper) {
        if (warp < 4) {
            sts128(sb + OFF_B + 16 * tid, 0x3f803f80u, 0x3f803f80u, 0x3f803f80u, 0x3f803f80u);
            for (int i = tid; i < 2 * ACC_SIZE / 4; i += 128) stg128(g_acc + 2 * j * ACC_SIZE + 4 * i, 0, 0, 0, 0);
            fence_async_smem();
            fence_gpu();
            bar_sync(1, 128);
            float acc[8];
            int i = 0;
#pragma unroll 1
            for (int job = 0; job < 12; job++) {
                const int n = job < 6 ? 4 : 8;
#pragma unroll 1
                for (int t = 0; t < n; t++, i++) {
                    mbar_wait(sb + BAR_FULLA + 8 * (i & 7), (i >> 3) & 1);
                    wg_fence();
#pragma unroll
                    for (int k = 0; k < 8; k++)
                        wgmma_n8_tt(acc + (k & 4), desc_lo(sb + OFF_A) + (i & 7) * (SLOT >> 4) + 128 * k, desc_lo(sb + OFF_B), (t | (k & 3)) != 0);
                    wg_commit();
                    wg_wait<1>();
                    mbar_arrive_n_if(sb + BAR_EMPTYA + 8 * ((i + 7) & 7), 2, lane == 0 && i > 0);
                }
                wg_wait<0>();
                fence_acc<8>(acc);
                const int q = lane & 3;
                const float lo = (q & 1) ? acc[2] : acc[0], hi = (q & 1) ? acc[6] : acc[4];
                const float v = job < 6 ? lo + hi : ((q & 2) ? hi : lo);
                unsigned long long* dst = g_cs + ((2 * j + (job & 1)) * 6 + (job >> 1)) * 128 + (q >> 1) * 64 + 16 * warp + 8 * (q & 1) + (lane >> 2);
                asm volatile("st.relaxed.gpu.global.b64 [%0], %1;" ::"l"(dst), "l"(((unsigned long long)epoch << 32) | __float_as_uint(v)) : "memory");
            }
        }
        return;
    }
    {
        const int w = warp >> 2, wv = warp & 3, g = lane >> 2, q = lane & 3;
        const int row_w = 128 * m + 16 * warp;
        const uint32_t sa = sb + OFF_A + w * 8192;
        const desc_t dA = desc_lo(sa), dB = desc_lo(sb + OFF_B);
        unsigned* const flag_m = g_flag + m * 160;
        const bool l0 = lane == 0;
        Ring rg{0, 0};
        int prev = 0;

        uint32_t wb[16];
        constexpr float L2E = 1.4426950408889634f;
        uint32_t fp[16], fm[16];
        float fr[16];
        float rs0, nm0, rs1, nm1;
        uint32_t kv_ack;
        {
            float acc[64];
#pragma unroll 1
            for (int kt = 0; kt < 8; kt++) {
                mbar_waitc(sb + BAR_FULLA + 8 * kt, 0);
                mbar_waitc(sb + BAR_FULLB + 8 * rg.slot, rg.phase);
                const desc_t da = dA + kt * (SLOT >> 4), db = dB + rg.slot * (SLOT >> 4);
                wg_fence();
#pragma unroll
                for (int k = 0; k < 4; k++) wgmma_n128(acc, da + 2 * k, db + 128 * k, (kt | k) != 0);
                wg_commit();
                wg_wait<1>();
                mbar_arrive_if(sb + BAR_EMPTYB + 8 * prev, l0 && kt > 0);
                prev = rg.slot; rg.adv();
            }
            {
                uint4 a, b;
                uint32_t it = 0;
                do {
                    a = ld_tagged_rlx(g_xstat + 2 * (row_w + g));
                    b = ld_tagged_rlx(g_xstat + 2 * (row_w + g + 8));
                    trap_if_gt(++it, 1u << 22);
                } while (__any_sync(0xffffffffu, a.y != epoch || a.w != epoch || b.y != epoch || b.w != epoch));
                rs0 = __uint_as_float(a.x); nm0 = __uint_as_float(a.z); rs1 = __uint_as_float(b.x); nm1 = __uint_as_float(b.z);
            }
#pragma unroll
            for (int i = 0; i < 8; i++) {
                wb[(i >> 1) * 4 + (i & 1)] = __byte_perm(wraw[2 * i], wraw[2 * i + 1], 0x5410);
                wb[(i >> 1) * 4 + 2 + (i & 1)] = __byte_perm(wraw[2 * i], wraw[2 * i + 1], 0x7632);
            }
            TL(17, tid == 0);
            mbar_waitc(sb + BAR_CS1, 0);
            TL(18, tid == 0);
            wg_wait<0>();
            fence_acc<64>(acc);
            mbar_arrive_if(sb + BAR_EMPTYB + 8 * prev, l0);
            TL(2, tid == 0);
#pragma unroll
            for (int i = 2; i < 6; i++) mbar_waitc(sb + BAR_FULLB + 8 * i, 1);
            const int lrow = 16 * warp + (lane & 15), ch = lane >> 4, sw = lane & 7;
            const uint32_t st = sb + OFF_B + 2 * SLOT + lrow * 128;
            uint32_t ka[16];
#pragma unroll
            for (int hh = 0; hh < 4; hh++)
                ln_frag<false>(acc + 8 * hh, sb + OFF_CS1 + (64 + 16 * hh + 2 * q) * 4, rs0, nm0, rs1, nm1, ka + 4 * hh);
#pragma unroll
            for (int hh = 0; hh < 4; hh++) feature_map<true>(ka + 4 * hh, wb + 4 * hh, rs0 * L2E, rs1 * L2E, fp + 4 * hh, fm + 4 * hh, fr);
#pragma unroll
            for (int hh = 0; hh < 4; hh++) {
                stsm4(st + (hh >> 1) * SLOT + (((4 * (hh & 1) + ch) ^ sw) << 4), fp[4 * hh], fp[4 * hh + 1], fp[4 * hh + 2], fp[4 * hh + 3]);
                stsm4(st + (hh >> 1) * SLOT + (((4 * (hh & 1) + 2 + ch) ^ sw) << 4), fm[4 * hh], fm[4 * hh + 1], fm[4 * hh + 2], fm[4 * hh + 3]);
            }
            mbar_waitc(sb + BAR_CSV, 0);
#pragma unroll
            for (int hh = 0; hh < 4; hh++) {
                uint32_t a[4];
                ln_frag<true>(acc + 32 + 8 * hh, sb + OFF_CS1 + (128 + 16 * hh + 2 * q) * 4, rs0, nm0, rs1, nm1, a);
                stsm4(st + (2 + (hh >> 1)) * SLOT + (((2 * (hh & 1) + ch) ^ sw) << 4), a[0], a[1], a[2], a[3]);
            }
            stsm4(st + (2 + ch) * SLOT + ((4 ^ sw) << 4), 0x3f803f80u, 0x3f803f80u, 0x3f803f80u, 0x3f803f80u);
            fence_async_smem();
            bar_sync(1, 256);
            float kvd[20];
            wg_fence();
#pragma unroll
            for (int k = 0; k < 8; k++)
                wgmma_n40_tt(kvd, dB + (2 + w) * (SLOT >> 4) + 128 * k, dB + (4 + w) * (SLOT >> 4) + 128 * k, k != 0);
            wg_commit();
            wg_wait<0>();
            fence_acc<20>(kvd);
            const bool h1 = wv >= 2;
            const int f = 16 * warp + g;
            float* kvp = acc_j + ACC_KV + f * 16 + 2 * q;
            kv_ack = atom_f32x2(kvp, h1 ? kvd[8] : kvd[0], h1 ? kvd[9] : kvd[1]);
            kv_ack |= atom_f32x2(kvp + 128, h1 ? kvd[10] : kvd[2], h1 ? kvd[11] : kvd[3]);
            kv_ack |= atom_f32x2(kvp + 8, h1 ? kvd[12] : kvd[4], h1 ? kvd[13] : kvd[5]);
            kv_ack |= atom_f32x2(kvp + 136, h1 ? kvd[14] : kvd[6], h1 ? kvd[15] : kvd[7]);
            kv_ack |= atom_f32_if(acc_j + ACC_Z + f + 8 * (q & 1), q ? kvd[18] : kvd[16], q < 2);
            mbar_arrive_if(sb + BAR_EMPTYB + 8 * (2 + (lane & 3)), lane < 4);
            signal_after(cnt_j, kv_ack, P.zero, l0);
            TL(3, tid == 0);
        }
        uint32_t res_lo[8], res_hi[8];
        const uint32_t own_rows = sb + OFF_A + j * SLOT + warp * 2048;
        {
            float acc[32];
            rg.slot = 0; rg.phase = 0;
#pragma unroll 1
            for (int b = 0; b < 4; b++) {
                mbar_waitc(sb + BAR_FULLB + 8 * rg.slot, rg.phase);
                const desc_t da = dA + b * (2 * SLOT >> 4), db = dB + rg.slot * (SLOT >> 4);
                wg_fence();
#pragma unroll
                for (int k = 0; k < 8; k++) wgmma_n64(acc, da + (k >> 2) * (SLOT >> 4) + (k & 3) * 2, db + 128 * k, (b | k) != 0);
                wg_commit();
                wg_wait<1>();
                mbar_arrive_if(sb + BAR_EMPTYB + 8 * prev, l0 && b > 0);
                prev = rg.slot; rg.adv();
            }
            wg_wait<0>();
            fence_acc<32>(acc);
            mbar_arrive_if(sb + BAR_EMPTYB + 8 * prev, l0);
            mbar_arrive_if(sb + BAR_EMPTYA + 8 * (lane & 7), lane < 8 && (lane | 1) != (j | 1));
            TL(4, tid == 0);
            mbar_waitc(sb + BAR_CSQ, 0);
            uint32_t qa[16];
#pragma unroll
            for (int hh = 0; hh < 4; hh++)
                ln_frag<false>(acc + 8 * hh, sb + OFF_CS1 + (16 * hh + 2 * q) * 4, rs0, nm0, rs1, nm1, qa + 4 * hh);
#pragma unroll
            for (int hh = 0; hh < 4; hh++) feature_map<false>(qa + 4 * hh, wb + 4 * hh, rs0 * L2E, rs1 * L2E, fp + 4 * hh, fm + 4 * hh, fr + 4 * hh);
#pragma unroll
            for (int b = 0; b < 4; b++)
                ldsm4(own_rows + (lane & 15) * 128 + (((2 * b + (lane >> 4)) ^ (lane & 7)) << 4),
                      res_lo[2 * b], res_hi[2 * b], res_lo[2 * b + 1], res_hi[2 * b + 1]);
            TL(5, tid == 0);
            if (warp == 0) wait_count_warp(cnt_j, epoch * 128);
            TL(6, tid == 0);
            bar_sync(1, 256);
            const uint32_t kvs = sb + OFF_A + (j ^ 1) * SLOT;
            {
                const float4 a0 = ld_l2_f4(acc_j + ACC_KV + 4 * tid), a1 = ld_l2_f4(acc_j + ACC_KV + 4 * (tid + 256));
                const float zz = ld_l2_f(acc_j + ACC_Z + (tid & 127));
                sts64(kvs + (tid >> 2) * 48 + (tid & 3) * 8, pack_bf16(a0.x, a0.y), pack_bf16(a0.z, a0.w));
                sts64(kvs + ((tid >> 2) + 64) * 48 + (tid & 3) * 8, pack_bf16(a1.x, a1.y), pack_bf16(a1.z, a1.w));
                const uint32_t z2 = pack_bf16(zz, zz);
                sts64(kvs + (tid & 127) * 48 + 32 + w * 8, z2, z2);
            }
            bar_sync(1, 256);
            uint32_t o_lo[8], o_hi[8];
#pragma unroll
            for (int hh = 0; hh < 4; hh++) {
                uint32_t b[8], zb[4];
                const uint32_t base = kvs + hh * 32 * 48;
                ldsm4t(base + (lane & 15) * 48 + (lane >> 4) * 16, b[0], b[1], b[2], b[3]);
                ldsm4t(base + (16 + (lane & 15)) * 48 + (lane >> 4) * 16, b[4], b[5], b[6], b[7]);
                ldsm4t(base + lane * 48 + 32, zb[0], zb[1], zb[2], zb[3]);
                float n0[4], n1[4], dn[4], m0[4], m1[4], dm[4];
                mma16816_z(n0, fp + 4 * hh, b[0], b[1]); mma16816_z(n1, fp + 4 * hh, b[2], b[3]); mma16816_z(dn, fp + 4 * hh, zb[0], zb[1]);
                mma16816_z(m0, fm + 4 * hh, b[4], b[5]); mma16816_z(m1, fm + 4 * hh, b[6], b[7]); mma16816_z(dm, fm + 4 * hh, zb[2], zb[3]);
                const float* r = fr + 4 * hh;
                const float i0 = rcp(fmaf(dn[0], r[0], fmaf(dm[0], r[2], 1e-6f))), i1 = rcp(fmaf(dn[2], r[1], fmaf(dm[2], r[3], 1e-6f)));
                const float p0 = r[0] * i0, q0 = r[2] * i0, p1 = r[1] * i1, q1 = r[3] * i1;
                o_lo[2 * hh] = pack_bf16(fmaf(n0[0], p0, m0[0] * q0), fmaf(n0[1], p0, m0[1] * q0));
                o_hi[2 * hh] = pack_bf16(fmaf(n0[2], p1, m0[2] * q1), fmaf(n0[3], p1, m0[3] * q1));
                o_lo[2 * hh + 1] = pack_bf16(fmaf(n1[0], p0, m1[0] * q0), fmaf(n1[1], p0, m1[1] * q0));
                o_hi[2 * hh + 1] = pack_bf16(fmaf(n1[2], p1, m1[2] * q1), fmaf(n1[3], p1, m1[3] * q1));
            }
            const uint32_t ack = store_tile<true>(own_rows, g_o + (size_t)row_w * DM + 64 * j, o_lo, o_hi, lane);
            fence_async_smem();
            signal_after(flag_m, ack, P.zero, l0);
            mbar_arrive_if(sb + BAR_EMPTYA + 8 * (j ^ 1), l0);
            TL(7, tid == 0);
        }
        {
            float acc[32];
#pragma unroll
            for (int t = 0; t < 8; t++) {
                acc[4 * t] = bf_lo(res_lo[t]); acc[4 * t + 1] = bf_hi(res_lo[t]);
                acc[4 * t + 2] = bf_lo(res_hi[t]); acc[4 * t + 3] = bf_hi(res_hi[t]);
            }
            fence_acc<32>(acc);
#pragma unroll 1
            for (int kp = 0; kp < 4; kp++) {
                mbar_waitc(sb + BAR_FULLB + 8 * rg.slot, rg.phase);
#pragma unroll
                for (int hf = 0; hf < 2; hf++) {
                    const int kt = 2 * kp + hf;
                    mbar_waitc(sb + BAR_FULLA + 8 * kt, kt != j);
                    TL(8, kt == 0 && tid == 0);
                    const desc_t da = dA + kp * (2 * SLOT >> 4), db = dB + rg.slot * (SLOT >> 4);
                    wg_fence();
#pragma unroll
                    for (int k = 0; k < 4; k++) wgmma_n64(acc, da + hf * (SLOT >> 4) + 2 * k, db + (hf * 4 + k) * 128, 1);
                    wg_commit();
                    wg_wait<1>();
                    mbar_arrive_if(sb + BAR_EMPTYA + 8 * ((kt + 7) & 7), l0 && kt > 0 && kt - 1 != j);
                    if (hf == 0) mbar_arrive_if(sb + BAR_EMPTYB + 8 * prev, l0 && kt > 0);
                }
                prev = rg.slot; rg.adv();
            }
            wg_wait<0>();
            fence_acc<32>(acc);
            mbar_arrive_if(sb + BAR_EMPTYA + 8 * 7, l0 && j != 7);
            mbar_arrive_if(sb + BAR_EMPTYB + 8 * prev, l0);
            TL(9, tid == 0);
            float s0 = 0.f, s1 = 0.f;
#pragma unroll
            for (int t = 0; t < 8; t++) {
                res_lo[t] = pack_bf16(acc[4 * t], acc[4 * t + 1]);
                res_hi[t] = pack_bf16(acc[4 * t + 2], acc[4 * t + 3]);
                s0 += acc[4 * t] + acc[4 * t + 1];
                s1 += acc[4 * t + 2] + acc[4 * t + 3];
            }
            uint32_t ack = store_tile<true>(own_rows, g_h + (size_t)row_w * DM + 64 * j, res_lo, res_hi, lane);
            s0 += __shfl_xor_sync(0xffffffffu, s0, 1); s1 += __shfl_xor_sync(0xffffffffu, s1, 1);
            s0 += __shfl_xor_sync(0xffffffffu, s0, 2); s1 += __shfl_xor_sync(0xffffffffu, s1, 2);
            const float mu0 = s0 * (1.f / 64), mu1 = s1 * (1.f / 64);
            float q0 = 0.f, q1 = 0.f;
#pragma unroll
            for (int t = 0; t < 8; t++) {
                float d;
                d = acc[4 * t] - mu0; q0 = fmaf(d, d, q0);
                d = acc[4 * t + 1] - mu0; q0 = fmaf(d, d, q0);
                d = acc[4 * t + 2] - mu1; q1 = fmaf(d, d, q1);
                d = acc[4 * t + 3] - mu1; q1 = fmaf(d, d, q1);
            }
            q0 += __shfl_xor_sync(0xffffffffu, q0, 1); q1 += __shfl_xor_sync(0xffffffffu, q1, 1);
            q0 += __shfl_xor_sync(0xffffffffu, q0, 2); q1 += __shfl_xor_sync(0xffffffffu, q1, 2);
            stg_f2_if(g_hstat + (role * 128 + 16 * warp + g + 8 * (q & 1)) * 2, q ? mu1 : mu0, q ? q1 : q0, q < 2);
            ack |= readback(g_hstat + (role * 128 + 16 * warp + g + 8 * (q & 1)) * 2);
            fence_async_smem();
            signal_after(flag_m + 32, ack, P.zero, l0);
            bar_sync(1, 256);
            TL(10, tid == 0);
        }
        if (w == 1) {
#pragma unroll 1
            for (int kt = 0; kt < 8; kt++) mbar_waitc(sb + BAR_FULLA + 8 * kt, 0);
            const float* sp = g_hstat + (1024 * m + (tid & 127)) * 2;
            float2 v[8];
#pragma unroll
            for (int i = 0; i < 8; i++) v[i] = ld_l2_f2(sp + 256 * i);
            float mean = 0.f;
#pragma unroll
            for (int i = 0; i < 8; i++) mean += v[i].x;
            mean *= 0.125f;
            float m2 = 0.f, dv = 0.f;
#pragma unroll
            for (int i = 0; i < 8; i++) { m2 += v[i].y; dv = fmaf(v[i].x - mean, v[i].x - mean, dv); }
            sts_f2(sb + OFF_CS1 + (tid & 127) * 8, -mean, __fdividef(1.f, fmaf(dv, 64.f, m2) * (1.f / DM) + 1e-5f));
            mbar_arrive(sb + BAR_CS3);
        }
        {
            float acc0[64], acc1[64];
            const desc_t dA0 = desc_lo(sb + OFF_A);
#pragma unroll 1
            for (int c = w; c < 3; c += 2) {
                if (c > 0) bar_sync(1 + c, 256);
                rg.slot = (c == 2) ? 0 : 2 + 2 * c; rg.phase = (c == 0);
#pragma unroll 1
                for (int kt = 0; kt < 8; kt++) {
                    mbar_waitc(sb + BAR_FULLA + 8 * kt, 0);
                    mbar_waitc(sb + BAR_FULLB + 8 * rg.slot, rg.phase);
                    TL(44 + c * 2 + (kt == 1), (tid & 127) == 0 && kt < 2);
                    const desc_t da = dA0 + kt * (SLOT >> 4), db = dB + rg.slot * (SLOT >> 4);
                    wg_fence();
#pragma unroll
                    for (int k = 0; k < 4; k++) {
                        wgmma_n128(acc0, da + 2 * k, db + 128 * k, (kt | k) != 0);
                        wgmma_n128(acc1, da + 512 + 2 * k, db + 128 * k, (kt | k) != 0);
                    }
                    wg_commit();
                    wg_wait<1>();
                    mbar_arrive_n_if(sb + BAR_EMPTYB + 8 * prev, 2, l0 && kt > 0);
                    mbar_arrive_if(sb + BAR_EMPTYA + 8 * ((kt + 7) & 7), l0 && kt > 0 && c > 0);
                    prev = rg.slot; rg.adv();
                }
                bar_arrive(2 + c, 256);
                mbar_waitc(sb + BAR_CS3, 0);
                float nm[4];
#pragma unroll
                for (int i = 0; i < 4; i++) nm[i] = lds_f2(sb + OFF_CS1 + (64 * (i >> 1) + 16 * wv + g + 8 * (i & 1)) * 8).x;
                wg_wait<0>();
                fence_acc<64>(acc0); fence_acc<64>(acc1);
                mbar_arrive_if(sb + BAR_EMPTYA + 8 * 7, l0 && c > 0);
                TL(11 + c, (tid & 127) == 0);
                bar_sync(6 + w, 128);
                const uint32_t stg = sb + OFF_B + prev * SLOT + wv * 2048;
                {
                    const uint32_t sa_ = stg + (lane & 15) * 128;
#pragma unroll
                    for (int tp = 0; tp < 4; tp++) {
                        const uint32_t ca = sb + OFF_CS3 + (32 * c + 8 * tp + q) * 16;
                        const float4 c0 = lds_f4(ca), c1 = lds_f4(ca + 64);
                        const uint32_t o = ((2 * tp + (lane >> 4)) ^ (lane & 7)) << 4;
                        stsm4(sa_ + o, hh_pair(acc0 + 8 * tp, c0, nm[0]), hh_pair(acc0 + 8 * tp + 2, c0, nm[1]),
                              hh_pair(acc0 + 8 * tp + 4, c1, nm[0]), hh_pair(acc0 + 8 * tp + 6, c1, nm[1]));
                        stsm4(sa_ + 8192 + o, hh_pair(acc1 + 8 * tp, c0, nm[2]), hh_pair(acc1 + 8 * tp + 2, c0, nm[3]),
                              hh_pair(acc1 + 8 * tp + 4, c1, nm[2]), hh_pair(acc1 + 8 * tp + 6, c1, nm[3]));
                    }
                }
                __syncwarp();
                __nv_bfloat16* hp = g_hh + (size_t)(128 * m + 16 * wv + (lane >> 3)) * FFP + 192 * j + 64 * c + (lane & 7) * 8;
#pragma unroll
                for (int i = 0; i < 8; i++) {
                    const int rr = 4 * (i & 3) + (lane >> 3);
                    const uint4 v = lds128(stg + (i >> 2) * 8192 + rr * 128 + (((lane & 7) ^ (rr & 7)) << 4));
                    stg128(hp + ((i >> 2) * 64 + 4 * (i & 3)) * FFP, v.x, v.y, v.z, v.w);
                }
                fence_async_smem();
                __syncwarp();
                mbar_arrive_n_if(sb + BAR_EMPTYB + 8 * prev, 2, l0);
                uint32_t ack = 0;
#pragma unroll
                for (int i = 0; i < 8; i++) ack |= readback(hp + ((i >> 2) * 64 + 4 * (i & 3)) * FFP);
                signal_after(flag_m + 64 + 32 * c, ack, P.zero, l0);
                TL(54 + c, (tid & 127) == 0);
            }
        }
        {
            float acc[32];
            const uint32_t xch = sb + OFF_B + (tid & 127) * 16;
            if (w == 1) {
                float acc0[32];
                bar_sync(4, 256);
                rg.slot = 2; rg.phase = 1;
                const desc_t dA0 = desc_lo(sb + OFF_A);
#define KT_P4(T, HF, NK)                                                                                    \
    do {                                                                                                    \
        const int s_ = (T) & 7;                                                                             \
        if (!(HF)) mbar_waitc(sb + BAR_FULLB + 8 * rg.slot, rg.phase);                                      \
        mbar_waitc(sb + BAR_FULLA + 8 * s_, (((T) >> 3) + 1) & 1);                                          \
        if (!(HF)) TL(30 + (T) / 2, tid == 128);                                                            \
        const desc_t da_ = dA0 + s_ * (SLOT >> 4), db_ = dB + rg.slot * (SLOT >> 4) + (HF) * 512;         \
        wg_fence();                                                                                         \
        _Pragma("unroll") for (int k = 0; k < (NK); k++) {                                                  \
            wgmma_n64(acc0, da_ + 2 * k, db_ + 128 * k, ((T) | k) != 0);                                    \
            wgmma_n64(acc, da_ + 512 + 2 * k, db_ + 128 * k, ((T) | k) != 0);                               \
        }                                                                                                   \
        wg_commit();                                                                                        \
        wg_wait<1>();                                                                                       \
        mbar_arrive_n_if(sb + BAR_EMPTYA + 8 * (((T) + 7) & 7), 2, l0 && (T) > 0);                          \
        if (!(HF)) mbar_arrive_n_if(sb + BAR_EMPTYB + 8 * prev, 2, l0 && (T) > 0);                          \
        if (HF) { prev = rg.slot; rg.adv(); }                                                               \
    } while (0)
#pragma unroll 1
                for (int t = 0; t < 16; t += 2) { KT_P4(t, 0, 4); KT_P4(t + 1, 1, 4); }
#pragma unroll 1
                for (int t = 16; t < 24; t += 2) { KT_P4(t, 0, 3); KT_P4(t + 1, 1, 3); }
                wg_wait<0>();
                fence_acc<32>(acc0); fence_acc<32>(acc);
                TL(15, tid == 128);
#pragma unroll
                for (int t = 0; t < 8; t++)
                    sts128(xch + 2 * SLOT + t * 2048, __float_as_uint(acc0[4 * t]), __float_as_uint(acc0[4 * t + 1]),
                           __float_as_uint(acc0[4 * t + 2]), __float_as_uint(acc0[4 * t + 3]));
                bar_sync(5, 256);
            } else {
                bar_sync(5, 256);
#pragma unroll
                for (int t = 0; t < 8; t++) {
                    const float4 v = lds_f4(xch + 2 * SLOT + t * 2048);
                    acc[4 * t] = v.x; acc[4 * t + 1] = v.y; acc[4 * t + 2] = v.z; acc[4 * t + 3] = v.w;
                }
            }
            const float r0 = lds_f2(sb + OFF_CS1 + (16 * warp + g) * 8).y, r1 = lds_f2(sb + OFF_CS1 + (16 * warp + g + 8) * 8).y;
#pragma unroll
            for (int t = 0; t < 8; t++) {
                res_lo[t] = pack_bf16(fmaf(acc[4 * t], r0, bf_lo(res_lo[t])), fmaf(acc[4 * t + 1], r0, bf_hi(res_lo[t])));
                res_hi[t] = pack_bf16(fmaf(acc[4 * t + 2], r1, bf_lo(res_hi[t])), fmaf(acc[4 * t + 3], r1, bf_hi(res_hi[t])));
            }
            store_tile<false>(own_rows, P.out + (size_t)row_w * DM + 64 * j, res_lo, res_hi, lane);
            if (tid == 0 && role == 0) g_epoch = epoch + 1;
            TL(16, tid == 0); TLG(1, tid == 0);
        }
    }
}

typedef CUresult (*EncodeFn)(CUtensorMap*, CUtensorMapDataType, cuuint32_t, void*, const cuuint64_t*, const cuuint64_t*,
                             const cuuint32_t*, const cuuint32_t*, CUtensorMapInterleave, CUtensorMapSwizzle,
                             CUtensorMapL2promotion, CUtensorMapFloatOOBfill);

static void make_map2d(EncodeFn enc, CUtensorMap* tm, const void* base, uint64_t cols, uint64_t rows, uint64_t pitch_elems,
                       uint32_t box_rows) {
    cuuint64_t gd[2] = {cols, rows};
    cuuint64_t gs[1] = {pitch_elems * 2};
    cuuint32_t bd[2] = {64, box_rows};
    cuuint32_t es[2] = {1, 1};
    enc(tm, CU_TENSOR_MAP_DATA_TYPE_BFLOAT16, 2, const_cast<void*>(base), gd, gs, bd, es, CU_TENSOR_MAP_INTERLEAVE_NONE,
        CU_TENSOR_MAP_SWIZZLE_128B, CU_TENSOR_MAP_L2_PROMOTION_L2_256B, CU_TENSOR_MAP_FLOAT_OOB_FILL_NONE);
}

}

extern "C" void kernel_launch(void* const* d_in, const int* in_sizes, int n_in, void* d_out, int out_size) {
    using namespace hk;
    (void)in_sizes; (void)n_in; (void)out_size;
    static EncodeFn enc = nullptr;
    static void *po = nullptr, *ph = nullptr, *phh = nullptr;
    static int std_layout = 0;
    if (!enc) {
        void* fn = nullptr;
        cudaDriverEntryPointQueryResult qr;
        cudaGetDriverEntryPoint("cuTensorMapEncodeTiled", &fn, cudaEnableDefault, &qr);
        enc = (EncodeFn)fn;
        cudaGetSymbolAddress(&po, g_o);
        cudaGetSymbolAddress(&ph, g_h);
        cudaGetSymbolAddress(&phh, g_hh);
        cudaFuncSetAttribute(fused_kernel, cudaFuncAttributeMaxDynamicSharedMemorySize, SMEM_BYTES);
        int dev = 0, sms = 0;
        cudaGetDevice(&dev);
        cudaDeviceGetAttribute(&sms, cudaDevAttrMultiProcessorCount, dev);
        cudaFuncSetAttribute(fused_kernel, cudaFuncAttributeNonPortableClusterSizeAllowed, 1);
        const int sizes[3] = {8, 9, 16}, want[3] = {15, 9, 7};
        bool ok = sms == NCTA;
        for (int i = 0; i < 3 && ok; i++) {
            cudaLaunchConfig_t cfg = {};
            cfg.gridDim = dim3(sizes[i] * 8); cfg.blockDim = dim3(NTHREADS); cfg.dynamicSmemBytes = SMEM_BYTES;
            cudaLaunchAttribute at;
            at.id = cudaLaunchAttributeClusterDimension;
            at.val.clusterDim.x = sizes[i]; at.val.clusterDim.y = 1; at.val.clusterDim.z = 1;
            cfg.attrs = &at; cfg.numAttrs = 1;
            int n = 0;
            ok = cudaOccupancyMaxActiveClusters(&n, fused_kernel, &cfg) == cudaSuccess && n == want[i];
        }
        (void)cudaGetLastError();
        std_layout = ok ? 1 : 0;
    }
    Params P;
    const __nv_bfloat16* x = (const __nv_bfloat16*)d_in[0];
    P.x = x;
    P.wqkv = (const __nv_bfloat16*)d_in[1];
    P.wphi = (const __nv_bfloat16*)d_in[2];
    P.wo = (const __nv_bfloat16*)d_in[3];
    P.wg = (const __nv_bfloat16*)d_in[5];
    P.wu = (const __nv_bfloat16*)d_in[6];
    P.wd = (const __nv_bfloat16*)d_in[7];
    P.out = (__nv_bfloat16*)d_out;
    P.use_smid = std_layout;
    P.zero = 0;
    for (int i = 0; i < NCTA; i++) {
        int role = i < 4 ? 128 + i : i - 4;
        if (std_layout) {
            const int tpc = i >> 1, odd = i & 1;
            if (tpc < 32) role = (tpc & 7) * 8 + (tpc >> 3) * 2 + odd;
            else if (tpc < 60) role = (8 + (tpc - 32) % 7) * 8 + ((tpc - 32) / 7) * 2 + odd;
            else if (tpc < 62) role = 128 + (tpc - 60) * 2 + odd;
            else role = 15 * 8 + (tpc - 62) * 2 + odd;
        }
        P.role[i] = (unsigned char)role;
    }
    make_map2d(enc, &P.tx, x, DM, SEQ, DM, 128);
    make_map2d(enc, &P.to, po, DM, SEQ, DM, 128);
    make_map2d(enc, &P.th, ph, DM, SEQ, DM, 128);
    make_map2d(enc, &P.thh, phh, FFP, SEQ, FFP, 128);
    make_map2d(enc, &P.twq, P.wqkv, 3 * DM, DM, 3 * DM, 128);
    make_map2d(enc, &P.two, P.wo, DM, DM, DM, 128);
    make_map2d(enc, &P.twg, P.wg, FF, DM, FF, 64);
    make_map2d(enc, &P.twu, P.wu, FF, DM, FF, 64);
    make_map2d(enc, &P.twd, P.wd, DM, FF, DM, 64);
    {
        cuuint64_t gd[3] = {(cuuint64_t)DM, (cuuint64_t)DM, 3};
        cuuint64_t gs[2] = {(cuuint64_t)3 * DM * 2, (cuuint64_t)DM * 2};
        cuuint32_t bd[3] = {64, 64, 2};
        cuuint32_t es[3] = {1, 1, 1};
        enc(&P.twkv, CU_TENSOR_MAP_DATA_TYPE_BFLOAT16, 3, const_cast<__nv_bfloat16*>(P.wqkv), gd, gs, bd, es,
            CU_TENSOR_MAP_INTERLEAVE_NONE, CU_TENSOR_MAP_SWIZZLE_128B, CU_TENSOR_MAP_L2_PROMOTION_L2_256B,
            CU_TENSOR_MAP_FLOAT_OOB_FILL_NONE);
    }
    fused_kernel<<<NCTA, NTHREADS, SMEM_BYTES>>>(P);
}
```

```cpp
#include <cuda_runtime.h>
#include <cuda_bf16.h>
#include <cuda.h>
#include <stdint.h>

namespace hk {

constexpr int SEQ = 2048, DM = 512, FF = 1376, FFP = 1536;
constexpr int NCTA = 132;
constexpr int NTHREADS = 384;
constexpr uint32_t SLOT = 16384;
constexpr uint32_t OFF_A = 0, OFF_B = 8 * SLOT, OFF_MISC = 14 * SLOT;
constexpr uint32_t BAR_FULLA = OFF_MISC + 0, BAR_EMPTYA = OFF_MISC + 64, BAR_FULLB = OFF_MISC + 128,
                   BAR_EMPTYB = OFF_MISC + 176, BAR_CS1 = OFF_MISC + 224, BAR_CS3 = OFF_MISC + 232,
                   BAR_CSQ = OFF_MISC + 240, BAR_CSV = OFF_MISC + 248;
constexpr uint32_t OFF_CS1 = OFF_MISC + 384;
constexpr uint32_t OFF_CS3 = OFF_CS1 + 1024;
constexpr uint32_t SMEM_BYTES = OFF_CS3 + 1536;
constexpr int NB = 6;
constexpr int AHEAD = 3;

constexpr int ACC_KV = 0, ACC_Z = 2048, ACC_SIZE = 2176;

__device__ __align__(1024) __nv_bfloat16 g_o[SEQ * DM];
__device__ __align__(1024) __nv_bfloat16 g_h[SEQ * DM];
__device__ __align__(1024) __nv_bfloat16 g_hh[SEQ * FFP];
__device__ __align__(128) float g_hstat[SEQ * 16];
__device__ __align__(128) unsigned long long g_xstat[SEQ * 2];
__device__ __align__(128) float g_acc[8 * ACC_SIZE];
__device__ __align__(128) unsigned g_cnt[8 * 32];
__device__ __align__(128) unsigned long long g_cs[8 * 6 * 128];
__device__ __align__(128) unsigned g_flag[16 * 5 * 32];
__device__ unsigned g_epoch = 1;

#define TL(i, pred) do {} while (0)
#define TLG(i, pred) do {} while (0)

struct Params {
    CUtensorMap tx, to, th, thh, twkv, twq, two, twg, twu, twd, twg2, twu2;
    const __nv_bfloat16 *x, *wqkv, *wphi, *wo, *wg, *wu, *wd;
    __nv_bfloat16* out;
    int use_smid;
    unsigned zero;
    unsigned char role[NCTA];
};

__device__ __forceinline__ uint32_t smem_u32(const void* p) { return (uint32_t)__cvta_generic_to_shared(p); }
__device__ __forceinline__ void mbar_init(uint32_t bar, uint32_t cnt) {
    asm volatile("mbarrier.init.shared::cta.b64 [%0], %1;" ::"r"(bar), "r"(cnt) : "memory");
}
__device__ __forceinline__ void mbar_expect_tx(uint32_t bar, uint32_t bytes) {
    asm volatile("mbarrier.arrive.expect_tx.shared::cta.b64 _, [%0], %1;" ::"r"(bar), "r"(bytes) : "memory");
}
__device__ __forceinline__ void mbar_arrive(uint32_t bar) {
    asm volatile("mbarrier.arrive.shared::cta.b64 _, [%0];" ::"r"(bar) : "memory");
}
__device__ __forceinline__ void mbar_arrive_if(uint32_t bar, bool pred) {
    asm volatile("{.reg .pred p; setp.ne.u32 p, %1, 0; @p mbarrier.arrive.shared::cta.b64 _, [%0];}" ::"r"(bar), "r"((uint32_t)pred) : "memory");
}
__device__ __forceinline__ bool mbar_try(uint32_t bar, uint32_t parity) {
    uint32_t ok;
    asm volatile("{.reg .pred p; mbarrier.try_wait.parity.shared::cta.b64 p, [%1], %2; selp.u32 %0,1,0,p;}"
                 : "=r"(ok) : "r"(bar), "r"(parity) : "memory");
    return ok;
}
__device__ __forceinline__ bool mbar_test(uint32_t bar, uint32_t parity) {
    uint32_t ok;
    asm volatile("{.reg .pred p; mbarrier.test_wait.parity.shared::cta.b64 p, [%1], %2; selp.u32 %0,1,0,p;}"
                 : "=r"(ok) : "r"(bar), "r"(parity) : "memory");
    return ok;
}
__device__ __forceinline__ void trap_if_gt(uint32_t v, uint32_t lim) {
    asm volatile("{.reg .pred p; setp.gt.u32 p, %0, %1; @p trap;}" ::"r"(v), "r"(lim));
}
__device__ __forceinline__ void mbar_wait(uint32_t bar, uint32_t parity) {
    asm volatile("{\n"
                 ".reg .pred P1, P2;\n"
                 ".reg .u32 c;\n"
                 "mov.u32 c, 0;\n"
                 "LAB_WAIT:\n"
                 "mbarrier.try_wait.parity.shared::cta.b64 P1, [%0], %1;\n"
                 "@P1 bra LAB_DONE;\n"
                 "add.u32 c, c, 1;\n"
                 "setp.gt.u32 P2, c, 4194304;\n"
                 "@P2 trap;\n"
                 "bra LAB_WAIT;\n"
                 "LAB_DONE:\n"
                 "}" ::"r"(bar), "r"(parity) : "memory");
}
__device__ __forceinline__ void mbar_waitc(uint32_t bar, uint32_t parity) {
    asm volatile("{\n"
                 ".reg .pred P1;\n"
                 "LAB_WAIT:\n"
                 "mbarrier.try_wait.parity.shared::cta.b64 P1, [%0], %1;\n"
                 "@!P1 bra LAB_WAIT;\n"
                 "}" ::"r"(bar), "r"(parity) : "memory");
}
__device__ __forceinline__ void tma2d(uint32_t dst, const CUtensorMap* tm, uint32_t bar, int c0, int c1) {
    asm volatile("cp.async.bulk.tensor.2d.shared::cluster.global.mbarrier::complete_tx::bytes [%0], [%1, {%3, %4}], [%2];"
                 ::"r"(dst), "l"(tm), "r"(bar), "r"(c0), "r"(c1) : "memory");
}
__device__ __forceinline__ void tma3d(uint32_t dst, const CUtensorMap* tm, uint32_t bar, int c0, int c1, int c2) {
    asm volatile("cp.async.bulk.tensor.3d.shared::cluster.global.mbarrier::complete_tx::bytes [%0], [%1, {%3, %4, %5}], [%2];"
                 ::"r"(dst), "l"(tm), "r"(bar), "r"(c0), "r"(c1), "r"(c2) : "memory");
}
__device__ __forceinline__ bool elect_one() {
    uint32_t ok;
    asm volatile("{.reg .pred p; elect.sync _|p, 0xffffffff; selp.u32 %0, 1, 0, p;}" : "=r"(ok));
    return ok;
}
__device__ __forceinline__ void prefetch_tmap(const CUtensorMap* tm) {
    asm volatile("prefetch.tensormap [%0];" ::"l"(tm) : "memory");
}
__device__ __forceinline__ void prefetch_l2(const void* p, uint32_t bytes) {
    asm volatile("cp.async.bulk.prefetch.L2.global [%0], %1;" ::"l"(p), "r"(bytes) : "memory");
}
__device__ __forceinline__ unsigned ld_acquire(const unsigned* p) {
    unsigned v; asm volatile("ld.acquire.gpu.global.u32 %0, [%1];" : "=r"(v) : "l"(p) : "memory"); return v;
}
__device__ __forceinline__ uint4 ld_acquire4(const unsigned* p) {
    uint4 v;
    asm volatile("ld.acquire.gpu.global.v4.u32 {%0,%1,%2,%3}, [%4];" : "=r"(v.x), "=r"(v.y), "=r"(v.z), "=r"(v.w) : "l"(p) : "memory");
    return v;
}
__device__ __forceinline__ unsigned ld_relaxed(const unsigned* p) {
    unsigned v; asm volatile("ld.relaxed.gpu.global.u32 %0, [%1];" : "=r"(v) : "l"(p)); return v;
}
__device__ __forceinline__ void st_relaxed(unsigned* p, unsigned v) {
    asm volatile("st.relaxed.gpu.global.u32 [%0], %1;" ::"l"(p), "r"(v) : "memory");
}
__device__ __forceinline__ void red_relaxed(unsigned* p, unsigned v) {
    asm volatile("red.relaxed.gpu.global.add.u32 [%0], %1;" ::"l"(p), "r"(v) : "memory");
}
__device__ __forceinline__ void fence_gpu() { asm volatile("fence.acq_rel.gpu;" ::: "memory"); }
__device__ __forceinline__ void fence_async_smem() { asm volatile("fence.proxy.async.shared::cta;" ::: "memory"); }
__device__ __forceinline__ void fence_async_global() { asm volatile("fence.proxy.async.global;" ::: "memory"); }
__device__ __forceinline__ void wait_count(const unsigned* p, unsigned target) {
    uint32_t it = 0;
    while ((int)(ld_acquire(p) - target) < 0) trap_if_gt(++it, 1u << 22);
}
__device__ __forceinline__ void wait_count_warp(const unsigned* p, unsigned target) {
    uint32_t it = 0;
    while (__any_sync(0xffffffffu, (int)(ld_acquire(p) - target) < 0)) trap_if_gt(++it, 1u << 22);
}
__device__ __forceinline__ void red_f32(float* p, float a) {
    asm volatile("red.relaxed.gpu.global.add.f32 [%0], %1;" ::"l"(p), "f"(a) : "memory");
}
__device__ __forceinline__ void red_f32x2(float* p, float a, float b) {
    asm volatile("red.relaxed.gpu.global.add.v2.f32 [%0], {%1, %2};" ::"l"(p), "f"(a), "f"(b) : "memory");
}
__device__ __forceinline__ void red_f32x4(float* p, float a, float b, float c, float d) {
    asm volatile("red.relaxed.gpu.global.add.v4.f32 [%0], {%1, %2, %3, %4};" ::"l"(p), "f"(a), "f"(b), "f"(c), "f"(d) : "memory");
}
__device__ __forceinline__ float4 ld_l2_f4(const float* p) {
    float4 v;
    asm volatile("ld.relaxed.gpu.global.v4.f32 {%0,%1,%2,%3}, [%4];" : "=f"(v.x), "=f"(v.y), "=f"(v.z), "=f"(v.w) : "l"(p) : "memory");
    return v;
}
__device__ __forceinline__ float2 ld_l2_f2(const float* p) {
    float2 v;
    asm volatile("ld.relaxed.gpu.global.v2.f32 {%0,%1}, [%2];" : "=f"(v.x), "=f"(v.y) : "l"(p) : "memory");
    return v;
}
__device__ __forceinline__ float ld_l2_f(const float* p) {
    float v;
    asm volatile("ld.relaxed.gpu.global.f32 %0, [%1];" : "=f"(v) : "l"(p) : "memory");
    return v;
}
__device__ __forceinline__ uint4 ldg_nc(const void* p) {
    uint4 v;
    asm volatile("ld.global.nc.L1::no_allocate.v4.u32 {%0,%1,%2,%3}, [%4];" : "=r"(v.x), "=r"(v.y), "=r"(v.z), "=r"(v.w) : "l"(p));
    return v;
}
__device__ __forceinline__ void stg128(void* p, uint32_t a, uint32_t b, uint32_t c, uint32_t d) {
    asm volatile("st.global.v4.u32 [%0], {%1,%2,%3,%4};" ::"l"(p), "r"(a), "r"(b), "r"(c), "r"(d) : "memory");
}
__device__ __forceinline__ uint4 lds128(uint32_t a) {
    uint4 v;
    asm volatile("ld.shared.v4.u32 {%0,%1,%2,%3}, [%4];" : "=r"(v.x), "=r"(v.y), "=r"(v.z), "=r"(v.w) : "r"(a) : "memory");
    return v;
}
__device__ __forceinline__ float2 lds_f2(uint32_t a) {
    float2 v;
    asm volatile("ld.shared.v2.f32 {%0,%1}, [%2];" : "=f"(v.x), "=f"(v.y) : "r"(a) : "memory");
    return v;
}
__device__ __forceinline__ void sts_f2(uint32_t a, float x, float y) {
    asm volatile("st.shared.v2.f32 [%0], {%1,%2};" ::"r"(a), "f"(x), "f"(y) : "memory");
}
__device__ __forceinline__ void sts64(uint32_t a, uint32_t x, uint32_t y) {
    asm volatile("st.shared.v2.u32 [%0], {%1,%2};" ::"r"(a), "r"(x), "r"(y) : "memory");
}
__device__ __forceinline__ void sts128(uint32_t a, uint32_t x, uint32_t y, uint32_t z, uint32_t w) {
    asm volatile("st.shared.v4.u32 [%0], {%1,%2,%3,%4};" ::"r"(a), "r"(x), "r"(y), "r"(z), "r"(w) : "memory");
}
__device__ __forceinline__ void stsm4(uint32_t a, uint32_t r0, uint32_t r1, uint32_t r2, uint32_t r3) {
    asm volatile("stmatrix.sync.aligned.m8n8.x4.shared.b16 [%0], {%1,%2,%3,%4};" ::"r"(a), "r"(r0), "r"(r1), "r"(r2), "r"(r3) : "memory");
}
__device__ __forceinline__ void ldsm4(uint32_t a, uint32_t& r0, uint32_t& r1, uint32_t& r2, uint32_t& r3) {
    asm volatile("ldmatrix.sync.aligned.m8n8.x4.shared.b16 {%0,%1,%2,%3}, [%4];" : "=r"(r0), "=r"(r1), "=r"(r2), "=r"(r3) : "r"(a) : "memory");
}
__device__ __forceinline__ void ldsm4t(uint32_t a, uint32_t& r0, uint32_t& r1, uint32_t& r2, uint32_t& r3) {
    asm volatile("ldmatrix.sync.aligned.m8n8.x4.trans.shared.b16 {%0,%1,%2,%3}, [%4];" : "=r"(r0), "=r"(r1), "=r"(r2), "=r"(r3) : "r"(a) : "memory");
}
__device__ __forceinline__ void mma16816(float* c, const uint32_t* a, uint32_t b0, uint32_t b1) {
    asm("mma.sync.aligned.m16n8k16.row.col.f32.bf16.bf16.f32 {%0,%1,%2,%3}, {%4,%5,%6,%7}, {%8,%9}, {%0,%1,%2,%3};"
                 : "+f"(c[0]), "+f"(c[1]), "+f"(c[2]), "+f"(c[3])
                 : "r"(a[0]), "r"(a[1]), "r"(a[2]), "r"(a[3]), "r"(b0), "r"(b1));
}
__device__ __forceinline__ uint32_t pack_bf16(float lo, float hi) {
    uint32_t r; asm("cvt.rn.bf16x2.f32 %0, %1, %2;" : "=r"(r) : "f"(hi), "f"(lo)); return r;
}
__device__ __forceinline__ float bf_lo(uint32_t w) { return __uint_as_float(w << 16); }
__device__ __forceinline__ float bf_hi(uint32_t w) { return __uint_as_float(w & 0xffff0000u); }
__device__ __forceinline__ float ex2(float x) { float r; asm("ex2.approx.ftz.f32 %0, %1;" : "=f"(r) : "f"(x)); return r; }
__device__ __forceinline__ float rcp(float x) { float r; asm("rcp.approx.ftz.f32 %0, %1;" : "=f"(r) : "f"(x)); return r; }
__device__ __forceinline__ void bar_sync(int id, int n) { asm volatile("bar.sync %0, %1;" ::"r"(id), "r"(n) : "memory"); }

typedef unsigned long long desc_t;
__device__ __forceinline__ desc_t desc_lo(uint32_t addr) { return (desc_t)(((addr & 0x3FFFF) >> 4) | (512u << 16)) | (0x40000040ull << 32); }
__device__ __forceinline__ void wg_fence() { asm volatile("wgmma.fence.sync.aligned;" ::: "memory"); }
__device__ __forceinline__ void wg_commit() { asm volatile("wgmma.commit_group.sync.aligned;" ::: "memory"); }
template <int N> __device__ __forceinline__ void wg_wait() { asm volatile("wgmma.wait_group.sync.aligned %0;" ::"n"(N) : "memory"); }
template <int N> __device__ __forceinline__ void fence_acc(float* d) {
#pragma unroll
    for (int i = 0; i < N; i++) asm volatile("" : "+f"(d[i])::"memory");
}
#define R4(o) "+f"(d[o + 0]), "+f"(d[o + 1]), "+f"(d[o + 2]), "+f"(d[o + 3])
#define R8(o) R4(o), R4(o + 4)
__device__ __forceinline__ void wgmma_n128(float* d, desc_t da, desc_t db, int sc) {
    asm volatile("{.reg .pred p; setp.ne.b32 p, %66, 0;\n"
                 "wgmma.mma_async.sync.aligned.m64n128k16.f32.bf16.bf16 {%0,%1,%2,%3,%4,%5,%6,%7,%8,%9,%10,%11,%12,%13,%14,%15,%16,%17,%18,%19,%20,%21,%22,%23,%24,%25,%26,%27,%28,%29,%30,%31,"
                 "%32,%33,%34,%35,%36,%37,%38,%39,%40,%41,%42,%43,%44,%45,%46,%47,%48,%49,%50,%51,%52,%53,%54,%55,%56,%57,%58,%59,%60,%61,%62,%63}, %64, %65, p, 1, 1, 0, 1;}"
                 : R8(0), R8(8), R8(16), R8(24), R8(32), R8(40), R8(48), R8(56)
                 : "l"(da), "l"(db), "r"(sc));
}
__device__ __forceinline__ void wgmma_n256(float* d, desc_t da, desc_t db, int sc) {
    asm volatile("{.reg .pred p; setp.ne.b32 p, %130, 0;\n"
                 "wgmma.mma_async.sync.aligned.m64n256k16.f32.bf16.bf16 {%0,%1,%2,%3,%4,%5,%6,%7,%8,%9,%10,%11,%12,%13,%14,%15,%16,%17,%18,%19,%20,%21,%22,%23,%24,%25,%26,%27,%28,%29,%30,%31,%32,%33,%34,%35,%36,%37,%38,%39,%40,%41,%42,%43,%44,%45,%46,%47,%48,%49,%50,%51,%52,%53,%54,%55,%56,%57,%58,%59,%60,%61,%62,%63,%64,%65,%66,%67,%68,%69,%70,%71,%72,%73,%74,%75,%76,%77,%78,%79,%80,%81,%82,%83,%84,%85,%86,%87,%88,%89,%90,%91,%92,%93,%94,%95,%96,%97,%98,%99,%100,%101,%102,%103,%104,%105,%106,%107,%108,%109,%110,%111,%112,%113,%114,%115,%116,%117,%118,%119,%120,%121,%122,%123,%124,%125,%126,%127}, %128, %129, p, 1, 1, 0, 1;}"
                 : R8(0), R8(8), R8(16), R8(24), R8(32), R8(40), R8(48), R8(56), R8(64), R8(72), R8(80), R8(88), R8(96), R8(104), R8(112), R8(120)
                 : "l"(da), "l"(db), "r"(sc));
}
__device__ __forceinline__ void wgmma_n112(float* d, desc_t da, desc_t db, int sc) {
    asm volatile("{.reg .pred p; setp.ne.b32 p, %58, 0;\n"
                 "wgmma.mma_async.sync.aligned.m64n112k16.f32.bf16.bf16 {%0,%1,%2,%3,%4,%5,%6,%7,%8,%9,%10,%11,%12,%13,%14,%15,%16,%17,%18,%19,%20,%21,%22,%23,%24,%25,%26,%27,%28,%29,%30,%31,%32,%33,%34,%35,%36,%37,%38,%39,%40,%41,%42,%43,%44,%45,%46,%47,%48,%49,%50,%51,%52,%53,%54,%55}, %56, %57, p, 1, 1, 0, 1;}"
                 : R8(0), R8(8), R8(16), R8(24), R8(32), R8(40), R8(48)
                 : "l"(da), "l"(db), "r"(sc));
}
__device__ __forceinline__ void wgmma_n64(float* d, desc_t da, desc_t db, int sc) {
    asm volatile("{.reg .pred p; setp.ne.b32 p, %34, 0;\n"
                 "wgmma.mma_async.sync.aligned.m64n64k16.f32.bf16.bf16 {%0,%1,%2,%3,%4,%5,%6,%7,%8,%9,%10,%11,%12,%13,%14,%15,%16,%17,%18,%19,%20,%21,%22,%23,%24,%25,%26,%27,%28,%29,%30,%31}, %32, %33, p, 1, 1, 0, 1;}"
                 : R8(0), R8(8), R8(16), R8(24)
                 : "l"(da), "l"(db), "r"(sc));
}
__device__ __forceinline__ void wgmma_n40_tt(float* d, desc_t da, desc_t db, int sc) {
    asm volatile("{.reg .pred p; setp.ne.b32 p, %22, 0;\n"
                 "wgmma.mma_async.sync.aligned.m64n40k16.f32.bf16.bf16 {%0,%1,%2,%3,%4,%5,%6,%7,%8,%9,%10,%11,%12,%13,%14,%15,%16,%17,%18,%19}, %20, %21, p, 1, 1, 1, 1;}"
                 : R8(0), R8(8), R4(16)
                 : "l"(da), "l"(db), "r"(sc));
}

__device__ __forceinline__ void wgmma_n8_tt(float* d, desc_t da, desc_t db, int sc) {
    asm volatile("{.reg .pred p; setp.ne.b32 p, %6, 0;\n"
                 "wgmma.mma_async.sync.aligned.m64n8k16.f32.bf16.bf16 {%0,%1,%2,%3}, %4, %5, p, 1, 1, 1, 1;}"
                 : R4(0)
                 : "l"(da), "l"(db), "r"(sc));
}

__device__ __forceinline__ uint32_t readback(const void* p) {
    uint32_t v; asm volatile("ld.relaxed.gpu.global.u32 %0, [%1];" : "=r"(v) : "l"(p) : "memory"); return v;
}
__device__ __forceinline__ uint32_t atom_f32x2(float* p, float a, float b) {
    float x, y;
    asm volatile("atom.relaxed.gpu.global.add.v2.f32 {%0,%1}, [%2], {%3,%4};" : "=f"(x), "=f"(y) : "l"(p), "f"(a), "f"(b) : "memory");
    return __float_as_uint(x);
}
__device__ __forceinline__ uint32_t atom_f32_if(float* p, float a, bool pred) {
    float x = 0.f;
    asm volatile("{.reg .pred p; setp.ne.u32 p, %3, 0; @p atom.relaxed.gpu.global.add.f32 %0, [%1], %2;}" : "+f"(x) : "l"(p), "f"(a), "r"((uint32_t)pred) : "memory");
    return __float_as_uint(x);
}
__device__ __forceinline__ void signal_after(unsigned* cnt, uint32_t ack, uint32_t zero, bool pred) {
    asm volatile("{.reg .pred p; setp.ne.u32 p, %2, 0; @p red.relaxed.gpu.global.add.u32 [%0], %1;}"
                 ::"l"(cnt), "r"((ack & zero) + 1), "r"((uint32_t)pred) : "memory");
}
__device__ __forceinline__ void signal_late(unsigned* cnt, const uint32_t* a, uint32_t zero, bool pred) {
    uint32_t v;
    asm volatile("{.reg .b32 t; lop3.b32 t, %1, %2, %3, 0xfe; lop3.b32 t, t, %4, %5, 0xfe; lop3.b32 t, t, %6, %7, 0xfe; or.b32 %0, t, %8;}"
                 : "=r"(v) : "r"(a[0]), "r"(a[1]), "r"(a[2]), "r"(a[3]), "r"(a[4]), "r"(a[5]), "r"(a[6]), "r"(a[7]));
    signal_after(cnt, v, zero, pred);
}
__device__ __forceinline__ void red_f32_if(float* p, float a, bool pred) {
    asm volatile("{.reg .pred p; setp.ne.u32 p, %2, 0; @p red.relaxed.gpu.global.add.f32 [%0], %1;}" ::"l"(p), "f"(a), "r"((uint32_t)pred) : "memory");
}
__device__ __forceinline__ void stg_f2_if(float* p, float a, float b, bool pred) {
    asm volatile("{.reg .pred p; setp.ne.u32 p, %3, 0; @p st.global.v2.f32 [%0], {%1,%2};}" ::"l"(p), "f"(a), "f"(b), "r"((uint32_t)pred) : "memory");
}
__device__ __forceinline__ void stg64(void* p, uint32_t a, uint32_t b) {
    asm volatile("st.global.v2.u32 [%0], {%1,%2};" ::"l"(p), "r"(a), "r"(b) : "memory");
}
__device__ __forceinline__ void mma16816_z(float* c, const uint32_t* a, uint32_t b0, uint32_t b1) {
    asm("mma.sync.aligned.m16n8k16.row.col.f32.bf16.bf16.f32 {%0,%1,%2,%3}, {%4,%5,%6,%7}, {%8,%9}, {%10,%10,%10,%10};"
                 : "=f"(c[0]), "=f"(c[1]), "=f"(c[2]), "=f"(c[3])
                 : "r"(a[0]), "r"(a[1]), "r"(a[2]), "r"(a[3]), "r"(b0), "r"(b1), "f"(0.f));
}
__device__ __forceinline__ uint32_t max2(uint32_t a, uint32_t b) { uint32_t r; asm("max.bf16x2 %0, %1, %2;" : "=r"(r) : "r"(a), "r"(b)); return r; }
__device__ __forceinline__ uint32_t min2(uint32_t a, uint32_t b) { uint32_t r; asm("min.bf16x2 %0, %1, %2;" : "=r"(r) : "r"(a), "r"(b)); return r; }
__device__ __forceinline__ void bar_arrive(int id, int n) { asm volatile("bar.arrive %0, %1;" ::"r"(id), "r"(n) : "memory"); }
__device__ __forceinline__ void mbar_arrive_n_if(uint32_t bar, uint32_t n, bool pred) {
    asm volatile("{.reg .pred p; setp.ne.u32 p, %1, 0; @p mbarrier.arrive.shared::cta.b64 _, [%0], %2;}" ::"r"(bar), "r"((uint32_t)pred), "r"(n) : "memory");
}
__device__ __forceinline__ float4 lds_f4(uint32_t a) {
    float4 v;
    asm volatile("ld.shared.v4.f32 {%0,%1,%2,%3}, [%4];" : "=f"(v.x), "=f"(v.y), "=f"(v.z), "=f"(v.w) : "r"(a) : "memory");
    return v;
}
__device__ __forceinline__ uint4 ld_tagged(const unsigned long long* p) {
    unsigned long long a, b;
    asm volatile("ld.acquire.gpu.global.v2.b64 {%0,%1}, [%2];" : "=l"(a), "=l"(b) : "l"(p) : "memory");
    return make_uint4((unsigned)a, (unsigned)(a >> 32), (unsigned)b, (unsigned)(b >> 32));
}
__device__ __forceinline__ uint4 ld_tagged_rlx(const unsigned long long* p) {
    unsigned long long a, b;
    asm volatile("ld.relaxed.gpu.global.v2.b64 {%0,%1}, [%2];" : "=l"(a), "=l"(b) : "l"(p) : "memory");
    return make_uint4((unsigned)a, (unsigned)(a >> 32), (unsigned)b, (unsigned)(b >> 32));
}
__device__ __forceinline__ void st_tagged_if(unsigned long long* p, float a, float b, unsigned tag, bool pred) {
    const unsigned long long t = (unsigned long long)tag << 32;
    asm volatile("{.reg .pred p; setp.ne.u32 p, %3, 0; @p st.relaxed.gpu.global.v2.b64 [%0], {%1,%2};}"
                 ::"l"(p), "l"(t | __float_as_uint(a)), "l"(t | __float_as_uint(b)), "r"((uint32_t)pred) : "memory");
}

template <bool ACK>
__device__ __forceinline__ uint32_t store_tile(uint32_t tile_rows, __nv_bfloat16* gdst, const uint32_t* lo, const uint32_t* hi, int lane) {
    const int r = lane & 15;
#pragma unroll
    for (int b = 0; b < 4; b++)
        stsm4(tile_rows + r * 128 + (((2 * b + (lane >> 4)) ^ (r & 7)) << 4), lo[2 * b], hi[2 * b], lo[2 * b + 1], hi[2 * b + 1]);
    __syncwarp();
    uint32_t ack = 0;
#pragma unroll
    for (int i = 0; i < 4; i++) {
        const int rr = 4 * i + (lane >> 3);
        const uint4 v = lds128(tile_rows + rr * 128 + (((lane & 7) ^ (rr & 7)) << 4));
        stg128(gdst + rr * DM + (lane & 7) * 8, v.x, v.y, v.z, v.w);
    }
    if (ACK) {
#pragma unroll
        for (int i = 0; i < 4; i++) ack |= readback(gdst + (4 * i + (lane >> 3)) * DM + (lane & 7) * 8);
    }
    return ack;
}

template <bool NORM>
__device__ __forceinline__ void feature_map(const uint32_t* a, const uint32_t* wb, float c0, float c1, uint32_t* plus, uint32_t* minus, float* rs) {
    float p[8];
    mma16816_z(p, a, wb[0], wb[1]);
    mma16816_z(p + 4, a, wb[2], wb[3]);
    const uint32_t P0 = pack_bf16(p[0], p[2]), P1 = pack_bf16(p[1], p[3]), P2 = pack_bf16(p[4], p[6]), P3 = pack_bf16(p[5], p[7]);
    uint32_t mx = max2(max2(P0, P1), max2(P2, P3)), mn = min2(min2(P0, P1), min2(P2, P3));
#pragma unroll
    for (int s = 1; s <= 2; s <<= 1) {
        mx = max2(mx, __shfl_xor_sync(0xffffffffu, mx, s));
        mn = min2(mn, __shfl_xor_sync(0xffffffffu, mn, s));
    }
    const float mx0 = bf_lo(mx) * c0, mx1 = bf_hi(mx) * c1, mn0 = bf_lo(mn) * c0, mn1 = bf_hi(mn) * c1;
    p[0] = bf_lo(P0); p[2] = bf_hi(P0); p[1] = bf_lo(P1); p[3] = bf_hi(P1);
    p[4] = bf_lo(P2); p[6] = bf_hi(P2); p[5] = bf_lo(P3); p[7] = bf_hi(P3);
    float ep[8], em[8];
#pragma unroll
    for (int i = 0; i < 8; i++) {
        const bool r1 = (i & 2);
        ep[i] = ex2(fmaf(p[i], r1 ? c1 : c0, r1 ? -mx1 : -mx0));
        em[i] = ex2(fmaf(p[i], r1 ? -c1 : -c0, r1 ? mn1 : mn0));
    }
    float sp[4], sm[4];
#pragma unroll
    for (int i = 0; i < 4; i++) { plus[i] = pack_bf16(ep[2 * i], ep[2 * i + 1]); minus[i] = pack_bf16(em[2 * i], em[2 * i + 1]); }
    mma16816_z(sp, plus, 0x3f803f80u, 0x3f803f80u);
    mma16816_z(sm, minus, 0x3f803f80u, 0x3f803f80u);
    rs[0] = rcp(sp[0]); rs[1] = rcp(sp[2]); rs[2] = rcp(sm[0]); rs[3] = rcp(sm[2]);
    if (NORM) {
#pragma unroll
        for (int i = 0; i < 4; i++) {
            plus[i] = pack_bf16(ep[2 * i] * rs[i & 1], ep[2 * i + 1] * rs[i & 1]);
            minus[i] = pack_bf16(em[2 * i] * rs[2 + (i & 1)], em[2 * i + 1] * rs[2 + (i & 1)]);
        }
    }
}

template <bool SCALE>
__device__ __forceinline__ void ln_frag(const float* acc, uint32_t cs_addr, float rs0, float nm0, float rs1, float nm1, uint32_t* a) {
    const float2 c0 = lds_f2(cs_addr), c1 = lds_f2(cs_addr + 32);
    const float s0 = SCALE ? rs0 : 1.f, s1 = SCALE ? rs1 : 1.f;
    a[0] = pack_bf16(fmaf(nm0, c0.x, acc[0]) * s0, fmaf(nm0, c0.y, acc[1]) * s0);
    a[1] = pack_bf16(fmaf(nm1, c0.x, acc[2]) * s1, fmaf(nm1, c0.y, acc[3]) * s1);
    a[2] = pack_bf16(fmaf(nm0, c1.x, acc[4]) * s0, fmaf(nm0, c1.y, acc[5]) * s0);
    a[3] = pack_bf16(fmaf(nm1, c1.x, acc[6]) * s1, fmaf(nm1, c1.y, acc[7]) * s1);
}

template <int UP>
__device__ __forceinline__ uint32_t hh_pair(const float* ag, float4 cs, float nmean) {
    const float g0 = fmaf(nmean, cs.x, ag[0]), g1 = fmaf(nmean, cs.y, ag[1]);
    const float u0 = fmaf(nmean, cs.z, ag[UP]), u1 = fmaf(nmean, cs.w, ag[UP + 1]);
    return pack_bf16(g0 * u0, g1 * u1);
}
template <int UP, int NTP>
__device__ __forceinline__ void hh_store(const float* acc, uint32_t cs3, float nm0, float nm1, uint32_t stg, __nv_bfloat16* hp, int lane, uint32_t* ack) {
#pragma unroll
    for (int tp = 0; tp < NTP; tp++) {
        const float4 c0 = lds_f4(cs3 + tp * 128), c1 = lds_f4(cs3 + tp * 128 + 64);
        stsm4(stg + (lane & 15) * 128 + (((2 * tp + (lane >> 4)) ^ (lane & 7)) << 4), hh_pair<UP>(acc + 8 * tp, c0, nm0),
              hh_pair<UP>(acc + 8 * tp + 2, c0, nm1), hh_pair<UP>(acc + 8 * tp + 4, c1, nm0), hh_pair<UP>(acc + 8 * tp + 6, c1, nm1));
    }
    __syncwarp();
#pragma unroll
    for (int i = 0; i < 4; i++) {
        const int rr = 4 * i + (lane >> 3);
        const uint4 v = lds128(stg + rr * 128 + (((lane & 7) ^ (rr & 7)) << 4));
        stg128(hp + 4 * i * FFP, v.x, v.y, v.z, v.w);
    }
#pragma unroll
    for (int i = 0; i < 4; i++) ack[i] = readback(hp + 4 * i * FFP);
}

struct Ring {
    int slot; uint32_t phase;
    __device__ __forceinline__ void adv() { if (++slot == NB) { slot = 0; phase ^= 1; } }
};

__global__ void __launch_bounds__(NTHREADS, 1) fused_kernel(const __grid_constant__ Params P) {
    extern __shared__ __align__(1024) uint8_t smem_raw[];
    const uint32_t sb = smem_u32(smem_raw);
    const int tid = threadIdx.x, lane = tid & 31;
    const int warp = __shfl_sync(0xffffffffu, tid >> 5, 0);
    unsigned role = blockIdx.x;
    if (P.use_smid) asm volatile("mov.u32 %0, %%smid;" : "=r"(role));
    role = P.role[role];
    const int m = role >> 3, j = role & 7;
    const bool helper = role >= 128;

    TL(0, tid == 0); TLG(0, tid == 0);
    float* const acc_j = g_acc + j * ACC_SIZE;
    unsigned* const cnt_j = g_cnt + j * 32;

    if (__builtin_expect(warp >= 8, 1)) {
        asm volatile("setmaxnreg.dec.sync.aligned.u32 72;");
        if (elect_one()) {
            if (warp == 8) {
                if (!helper) {
#pragma unroll
                    for (int i = 0; i < NB; i++) mbar_init(sb + BAR_FULLB + 8 * i, 1);
#pragma unroll
                    for (int i = 0; i < 2; i++) {
                        mbar_expect_tx(sb + BAR_FULLB + 8 * i, SLOT);
                        tma3d(sb + OFF_B + i * SLOT, &P.twkv, sb + BAR_FULLB + 8 * i, 64 * j, 64 * i, 1);
                    }
                }
            } else if (warp == 9) {
#pragma unroll
                for (int i = 0; i < 8; i++) mbar_init(sb + BAR_FULLA + 8 * i, 1);
#pragma unroll
                for (int i = 0; i < 2; i++) {
                    mbar_expect_tx(sb + BAR_FULLA + 8 * i, SLOT);
                    tma2d(sb + OFF_A + i * SLOT, helper ? &P.twq : &P.tx, sb + BAR_FULLA + 8 * i, helper ? DM + 128 * j : 64 * i, 128 * (helper ? i : m));
                }
            } else if (warp == 10) {
#pragma unroll
                for (int i = 0; i < 4; i++) mbar_init(sb + BAR_CS1 + 8 * i, i == 1 ? 96 : 32);
                trap_if_gt(sb & 1023, 0);
            } else {
#pragma unroll
                for (int i = 0; i < 14; i++) mbar_init(sb + (i < 8 ? BAR_EMPTYA : BAR_EMPTYB - 64) + 8 * i, 8);
            }
        }
        __syncwarp();
        const unsigned epoch = ld_relaxed(&g_epoch);
        bar_sync(0, NTHREADS);
        if (helper) {
            if (warp == 8) {
                if (elect_one()) {
#pragma unroll 1
                    for (int i = 2; i < 72; i++) {
                        const uint32_t full = sb + BAR_FULLA + 8 * (i & 7), dst = sb + OFF_A + (i & 7) * SLOT;
                        mbar_wait(sb + BAR_EMPTYA + 8 * (i & 7), ((i >> 3) & 1) ^ 1);
                        mbar_expect_tx(full, SLOT);
                        if (i < 24) {
                            tma2d(dst, &P.twq, full, (i < 16 ? DM + 64 * (i & 8) : 0) + 128 * j + 16 * (i & 4), 128 * (i & 3));
                        } else {
                            const int u = (i >> 3) - 3, c0 = 176 * (2 * j + (u & 1)) + 64 * (u >> 1);
                            tma2d(dst, &P.twg, full, c0, 64 * (i & 7));
                            tma2d(dst + 8192, &P.twu, full, c0, 64 * (i & 7));
                        }
                    }
                    prefetch_l2(P.wd + (size_t)j * 176128, 352256);
                }
            } else if (warp == 9) {
                wait_count_warp(g_cnt + (lane & 7) * 32, epoch * 128);
            }
            return;
        }
        if (warp == 8) {
            if (elect_one()) {
                if (m >= 3 && m < 8)
                    asm volatile("cp.async.bulk.prefetch.tensor.3d.L2.global [%0, {%1, %2, %3}];" ::"l"(&P.twkv), "r"(64 * j), "r"(64 * m), "r"(1) : "memory");
                if (j >= 3)
                    asm volatile("cp.async.bulk.prefetch.tensor.2d.L2.global [%0, {%1, %2}];" ::"l"(&P.tx), "r"(64 * j), "r"(128 * m) : "memory");
                Ring r{2, 0};
#pragma unroll 1
                for (int i = 2; i < 56; i++) {
                    const uint32_t full = sb + BAR_FULLB + 8 * r.slot, dst = sb + OFF_B + r.slot * SLOT;
                    mbar_wait(sb + BAR_EMPTYB + 8 * r.slot, r.phase ^ 1);
                    if (i >= 8 && i < 12) {
                        mbar_arrive(full);
                    } else {
                        if (i >= AHEAD && i < 6) mbar_wait(full - 8 * AHEAD, 0);
                        mbar_expect_tx(full, SLOT);
                        if (i < 8) {
                            tma3d(dst, &P.twkv, full, 64 * j, 64 * i, 1);
                        } else if (i < 20) {
                            tma2d(dst, i < 16 ? &P.twq : &P.two, full, 64 * j, 128 * (i & 3));
                        } else if (i < 36) {
                            tma3d(dst, &P.twg2, full, 176 * j, 32 * (i - 20), 0);
                            tma3d(dst + 8192, &P.twu2, full, 176 * j, 32 * (i - 20), 0);
                        } else if (i < 44) {
                            tma2d(dst, &P.twg, full, 176 * j + 128, 64 * (i - 36));
                            tma2d(dst + 8192, &P.twu, full, 176 * j + 128, 64 * (i - 36));
                        } else {
                            const int c = (i - 44) >> 2, jj = (i & 3) * 2;
                            tma2d(dst, &P.twd, full, 64 * j, 176 * jj + 64 * c);
                            tma2d(dst + 8192, &P.twd, full, 64 * j, 176 * (jj + 1) + 64 * c);
                        }
                    }
                    r.adv();
                }
            }
            return;
        }
        if (warp == 9) {
            if (elect_one()) {
#pragma unroll 1
                for (int i = 2; i < 8; i++) {
                    if (i >= AHEAD + 1) mbar_wait(sb + BAR_FULLA + 8 * (i - AHEAD - 1), 0);
                    mbar_expect_tx(sb + BAR_FULLA + 8 * i, SLOT);
                    tma2d(sb + OFF_A + i * SLOT, &P.tx, sb + BAR_FULLA + 8 * i, 64 * i, 128 * m);
                }
#pragma unroll 1
                for (int i = 1; i < 12; i++) prefetch_tmap(&P.tx + i);
#pragma unroll 1
                for (int r = 1; r < 6; r++) {
                    const CUtensorMap* tm = &P.tx + min(r, 3);
                    const int cstep = r < 3 ? 64 : 192, cbase = r < 3 ? 0 : 64 * (r - 3), skip = r < 3 ? j : 8;
                    wait_count(g_flag + (m * 5 + r - 1 - (r > 3)) * 32, epoch * 64);
#pragma unroll 1
                    for (int t = 0; t < 8; t++) {
                        if (t == skip) continue;
                        mbar_wait(sb + BAR_EMPTYA + 8 * t, (r - 1) & 1);
                        TL(56 + 8 * r + (t == 7), t == 7 || t == (skip == 0));
                        mbar_expect_tx(sb + BAR_FULLA + 8 * t, SLOT);
                        tma2d(sb + OFF_A + t * SLOT, tm, sb + BAR_FULLA + 8 * t, cbase + cstep * t, 128 * m);
                    }
                }
            }
            return;
        }
        const int a = warp - 10;
        {
            const int row = 16 * j + 8 * a + (lane >> 2);
            const uint32_t ra = sb + OFF_A + row * 128;
            float sh = 0.f, s0 = 0.f, s1 = 0.f, q0 = 0.f, q1 = 0.f;
#pragma unroll 1
            for (int kt = 0; kt < 8; kt++) {
                mbar_wait(sb + BAR_FULLA + 8 * kt, 0);
                if (kt == 0) sh = bf_lo(lds128(ra + ((row & 7) << 4)).x);
#pragma unroll
                for (int i = 0; i < 2; i++) {
                    const uint4 v = lds128(ra + kt * SLOT + (((2 * (lane & 3) + i) ^ (row & 7)) << 4));
                    const uint32_t ww[4] = {v.x, v.y, v.z, v.w};
#pragma unroll
                    for (int e = 0; e < 4; e++) {
                        const float d0 = bf_lo(ww[e]) - sh, d1 = bf_hi(ww[e]) - sh;
                        s0 += d0; q0 = fmaf(d0, d0, q0);
                        s1 += d1; q1 = fmaf(d1, d1, q1);
                    }
                }
            }
            s0 += s1; q0 += q1;
#pragma unroll
            for (int o = 1; o <= 2; o <<= 1) { s0 += __shfl_xor_sync(0xffffffffu, s0, o); q0 += __shfl_xor_sync(0xffffffffu, q0, o); }
            const float md = s0 * (1.f / DM);
            const float rs = rsqrtf(fmaxf(q0 * (1.f / DM) - md * md, 0.f) + 1e-5f);
            st_tagged_if(g_xstat + 2 * (128 * m + row), rs, -(sh + md), epoch, (lane & 3) == 0);
        }
        const unsigned long long* cs = g_cs + j * 768 + 2 * lane;
#pragma unroll 1
        for (int c = 0; c < (a ? 2 : 7); c++) {
            uint4 v;
            uint32_t it = 0;
            while (true) {
                v = ld_tagged(cs + (a ? 128 + 128 * c : (c ? 320 + 64 * c : 0)));
                if (!__any_sync(0xffffffffu, v.y != epoch || v.w != epoch)) break;
                __nanosleep(100);
                trap_if_gt(++it, 1u << 22);
            }
            sts64(a || !c ? sb + OFF_CS1 + (a ? 512 - 512 * c : 256) + 8 * lane : sb + OFF_CS3 + (32 * ((c - 1) >> 1) + lane) * 16 + 8 * ((c - 1) & 1), v.x, v.z);
            if (a || c == 0 || c == 6) mbar_arrive(sb + (a ? (c ? BAR_CSQ : BAR_CSV) : (c ? BAR_CS3 : BAR_CS1)));
        }
        {
            uint32_t it = 0;
            while (__any_sync(0xffffffffu, (int)(ld_acquire(g_flag + (m * 5 + 1) * 32) - epoch * 64) < 0)) {
                __nanosleep(500);
                trap_if_gt(++it, 1u << 22);
            }
        }
#pragma unroll 1
        for (int rr = 0; rr < 2; rr++) {
            const int row = 64 * rr + 32 * a + lane;
            const float* sp = g_hstat + (1024 * m + row) * 2;
            float2 v[8];
#pragma unroll
            for (int i = 0; i < 8; i++) v[i] = ld_l2_f2(sp + 256 * i);
            float mean = 0.f;
#pragma unroll
            for (int i = 0; i < 8; i++) mean += v[i].x;
            mean *= 0.125f;
            float m2 = 0.f, dv = 0.f;
#pragma unroll
            for (int i = 0; i < 8; i++) { m2 += v[i].y; dv = fmaf(v[i].x - mean, v[i].x - mean, dv); }
            sts_f2(sb + OFF_CS1 + row * 8, -mean, __fdividef(1.f, fmaf(dv, 64.f, m2) * (1.f / DM) + 1e-5f));
        }
        mbar_arrive(sb + BAR_CS3);
        return;
    }
    const unsigned epoch = ld_relaxed(&g_epoch);
    uint32_t wraw[16];
    if (!helper) {
        const uint32_t* wp = reinterpret_cast<const uint32_t*>(P.wphi) + (4 * j) * 128 + (lane & 3) * 16 + (lane >> 2);
#pragma unroll
        for (int i = 0; i < 16; i++)
            asm volatile("ld.global.nc.u32 %0, [%1];" : "=r"(wraw[i]) : "l"(wp + (i >> 2) * 128 + ((i >> 1) & 1) * 64 + (i & 1) * 8));
    }
    asm volatile("setmaxnreg.inc.sync.aligned.u32 216;");
    bar_sync(0, NTHREADS);
    if (helper) {
        if (warp < 4) {
            sts128(sb + OFF_B + 16 * tid, 0x3f803f80u, 0x3f803f80u, 0x3f803f80u, 0x3f803f80u);
            for (int i = tid; i < 2 * ACC_SIZE / 4; i += 128) stg128(g_acc + 2 * j * ACC_SIZE + 4 * i, 0, 0, 0, 0);
            fence_async_smem();
            fence_gpu();
            bar_sync(1, 128);
            float acc[8];
            int i = 0;
#pragma unroll 1
            for (int job = 0; job < 12; job++) {
                const int n = job < 6 ? 4 : 8;
#pragma unroll 1
                for (int t = 0; t < n; t++, i++) {
                    mbar_wait(sb + BAR_FULLA + 8 * (i & 7), (i >> 3) & 1);
                    wg_fence();
#pragma unroll
                    for (int k = 0; k < 8; k++)
                        wgmma_n8_tt(acc + (k & 4), desc_lo(sb + OFF_A) + (i & 7) * (SLOT >> 4) + 128 * k, desc_lo(sb + OFF_B), (t | (k & 3)) != 0);
                    wg_commit();
                    wg_wait<1>();
                    mbar_arrive_n_if(sb + BAR_EMPTYA + 8 * ((i + 7) & 7), 2, lane == 0 && i > 0);
                }
                wg_wait<0>();
                fence_acc<8>(acc);
                const int q = lane & 3;
                const float lo = (q & 1) ? acc[2] : acc[0], hi = (q & 1) ? acc[6] : acc[4];
                const float v = job < 6 ? lo + hi : ((q & 2) ? hi : lo);
                unsigned long long* dst = g_cs + ((2 * j + (job & 1)) * 6 + (job >> 1)) * 128 + (q >> 1) * 64 + 16 * warp + 8 * (q & 1) + (lane >> 2);
                asm volatile("st.relaxed.gpu.global.b64 [%0], %1;" ::"l"(dst), "l"(((unsigned long long)epoch << 32) | __float_as_uint(v)) : "memory");
            }
        }
        return;
    }
    {
        const int w = warp >> 2, wv = warp & 3, g = lane >> 2, q = lane & 3;
        const int row_w = 128 * m + 16 * warp;
        const uint32_t sa = sb + OFF_A + w * 8192;
        const desc_t dA = desc_lo(sa), dB = desc_lo(sb + OFF_B);
        unsigned* const flag_m = g_flag + m * 160;
        const bool l0 = lane == 0;
        Ring rg{0, 0};
        int prev = 0;

        uint32_t wb[16];
        constexpr float L2E = 1.4426950408889634f;
        uint32_t fp[16], fm[16];
        float fr[16];
        float rs0, nm0, rs1, nm1;
        uint32_t kv_ack[8];
        {
            float acc[64];
#pragma unroll 1
            for (int kt = 0; kt < 8; kt++) {
                mbar_waitc(sb + BAR_FULLA + 8 * kt, 0);
                mbar_waitc(sb + BAR_FULLB + 8 * rg.slot, rg.phase);
                const desc_t da = dA + kt * (SLOT >> 4), db = dB + rg.slot * (SLOT >> 4);
                wg_fence();
#pragma unroll
                for (int k = 0; k < 4; k++) wgmma_n128(acc, da + 2 * k, db + 128 * k, (kt | k) != 0);
                wg_commit();
                wg_wait<1>();
                mbar_arrive_if(sb + BAR_EMPTYB + 8 * prev, l0 && kt > 0);
                prev = rg.slot; rg.adv();
            }
            {
                uint4 a, b;
                uint32_t it = 0;
                do {
                    a = ld_tagged_rlx(g_xstat + 2 * (row_w + g));
                    b = ld_tagged_rlx(g_xstat + 2 * (row_w + g + 8));
                    trap_if_gt(++it, 1u << 22);
                } while (__any_sync(0xffffffffu, a.y != epoch || a.w != epoch || b.y != epoch || b.w != epoch));
                rs0 = __uint_as_float(a.x); nm0 = __uint_as_float(a.z); rs1 = __uint_as_float(b.x); nm1 = __uint_as_float(b.z);
            }
#pragma unroll
            for (int i = 0; i < 8; i++) {
                wb[(i >> 1) * 4 + (i & 1)] = __byte_perm(wraw[2 * i], wraw[2 * i + 1], 0x5410);
                wb[(i >> 1) * 4 + 2 + (i & 1)] = __byte_perm(wraw[2 * i], wraw[2 * i + 1], 0x7632);
            }
            TL(17, tid == 0);
            mbar_waitc(sb + BAR_CS1, 0);
            TL(18, tid == 0);
            wg_wait<0>();
            fence_acc<64>(acc);
            mbar_arrive_if(sb + BAR_EMPTYB + 8 * prev, l0);
            TL(2, tid == 0);
#pragma unroll
            for (int i = 2; i < 6; i++) mbar_waitc(sb + BAR_FULLB + 8 * i, 1);
            const int lrow = 16 * warp + (lane & 15), ch = lane >> 4, sw = lane & 7;
            const uint32_t st = sb + OFF_B + 2 * SLOT + lrow * 128;
            uint32_t ka[16];
#pragma unroll
            for (int hh = 0; hh < 4; hh++)
                ln_frag<false>(acc + 8 * hh, sb + OFF_CS1 + (64 + 16 * hh + 2 * q) * 4, rs0, nm0, rs1, nm1, ka + 4 * hh);
#pragma unroll
            for (int hh = 0; hh < 4; hh++) feature_map<true>(ka + 4 * hh, wb + 4 * hh, rs0 * L2E, rs1 * L2E, fp + 4 * hh, fm + 4 * hh, fr);
#pragma unroll
            for (int hh = 0; hh < 4; hh++) {
                stsm4(st + (hh >> 1) * SLOT + (((4 * (hh & 1) + ch) ^ sw) << 4), fp[4 * hh], fp[4 * hh + 1], fp[4 * hh + 2], fp[4 * hh + 3]);
                stsm4(st + (hh >> 1) * SLOT + (((4 * (hh & 1) + 2 + ch) ^ sw) << 4), fm[4 * hh], fm[4 * hh + 1], fm[4 * hh + 2], fm[4 * hh + 3]);
            }
            mbar_waitc(sb + BAR_CSV, 0);
#pragma unroll
            for (int hh = 0; hh < 4; hh++) {
                uint32_t a[4];
                ln_frag<true>(acc + 32 + 8 * hh, sb + OFF_CS1 + (128 + 16 * hh + 2 * q) * 4, rs0, nm0, rs1, nm1, a);
                stsm4(st + (2 + (hh >> 1)) * SLOT + (((2 * (hh & 1) + ch) ^ sw) << 4), a[0], a[1], a[2], a[3]);
            }
            stsm4(st + (2 + ch) * SLOT + ((4 ^ sw) << 4), 0x3f803f80u, 0x3f803f80u, 0x3f803f80u, 0x3f803f80u);
            fence_async_smem();
            bar_sync(1, 256);
            float kvd[20];
            wg_fence();
#pragma unroll
            for (int k = 0; k < 8; k++)
                wgmma_n40_tt(kvd, dB + (2 + w) * (SLOT >> 4) + 128 * k, dB + (4 + w) * (SLOT >> 4) + 128 * k, k != 0);
            wg_commit();
            wg_wait<0>();
            fence_acc<20>(kvd);
            const bool h1 = wv >= 2;
            const int f = 16 * warp + g;
            float* kvp = acc_j + ACC_KV + f * 16 + 2 * q;
            kv_ack[0] = kv_ack[5] = kv_ack[6] = kv_ack[7] = atom_f32x2(kvp, h1 ? kvd[8] : kvd[0], h1 ? kvd[9] : kvd[1]);
            kv_ack[1] = atom_f32x2(kvp + 128, h1 ? kvd[10] : kvd[2], h1 ? kvd[11] : kvd[3]);
            kv_ack[2] = atom_f32x2(kvp + 8, h1 ? kvd[12] : kvd[4], h1 ? kvd[13] : kvd[5]);
            kv_ack[3] = atom_f32x2(kvp + 136, h1 ? kvd[14] : kvd[6], h1 ? kvd[15] : kvd[7]);
            kv_ack[4] = atom_f32_if(acc_j + ACC_Z + f + 8 * (q & 1), q ? kvd[18] : kvd[16], q < 2);
            mbar_arrive_if(sb + BAR_EMPTYB + 8 * (2 + (lane & 3)), lane < 4);
            TL(3, tid == 0);
        }
        uint32_t res_lo[8], res_hi[8];
        const uint32_t own_rows = sb + OFF_A + j * SLOT + warp * 2048;
        {
            float acc[32];
            rg.slot = 0; rg.phase = 0;
#pragma unroll 1
            for (int b = 0; b < 4; b++) {
                mbar_waitc(sb + BAR_FULLB + 8 * rg.slot, rg.phase);
                const desc_t da = dA + b * (2 * SLOT >> 4), db = dB + rg.slot * (SLOT >> 4);
                wg_fence();
#pragma unroll
                for (int k = 0; k < 8; k++) wgmma_n64(acc, da + (k >> 2) * (SLOT >> 4) + (k & 3) * 2, db + 128 * k, (b | k) != 0);
                wg_commit();
                wg_wait<1>();
                mbar_arrive_if(sb + BAR_EMPTYB + 8 * prev, l0 && b > 0);
                if (b == 1) { signal_late(cnt_j, kv_ack, P.zero, l0); TL(19, tid == 0); }
                prev = rg.slot; rg.adv();
            }
            wg_wait<0>();
            fence_acc<32>(acc);
            mbar_arrive_if(sb + BAR_EMPTYB + 8 * prev, l0);
            mbar_arrive_if(sb + BAR_EMPTYA + 8 * (lane & 7), lane < 8 && (lane | 1) != (j | 1));
            TL(4, tid == 0);
            mbar_waitc(sb + BAR_CSQ, 0);
            uint32_t qa[16];
#pragma unroll
            for (int hh = 0; hh < 4; hh++)
                ln_frag<false>(acc + 8 * hh, sb + OFF_CS1 + (16 * hh + 2 * q) * 4, rs0, nm0, rs1, nm1, qa + 4 * hh);
#pragma unroll
            for (int hh = 0; hh < 4; hh++) feature_map<false>(qa + 4 * hh, wb + 4 * hh, rs0 * L2E, rs1 * L2E, fp + 4 * hh, fm + 4 * hh, fr + 4 * hh);
#pragma unroll
            for (int b = 0; b < 4; b++)
                ldsm4(own_rows + (lane & 15) * 128 + (((2 * b + (lane >> 4)) ^ (lane & 7)) << 4),
                      res_lo[2 * b], res_hi[2 * b], res_lo[2 * b + 1], res_hi[2 * b + 1]);
            TL(5, tid == 0);
            if (warp == 0) wait_count_warp(cnt_j, epoch * 128);
            TL(6, tid == 0);
            bar_sync(1, 256);
            const uint32_t kvs = sb + OFF_A + (j ^ 1) * SLOT;
            {
                const float4 a0 = ld_l2_f4(acc_j + ACC_KV + 4 * tid), a1 = ld_l2_f4(acc_j + ACC_KV + 4 * (tid + 256));
                const float zz = ld_l2_f(acc_j + ACC_Z + (tid & 127));
                sts64(kvs + (tid >> 2) * 48 + (tid & 3) * 8, pack_bf16(a0.x, a0.y), pack_bf16(a0.z, a0.w));
                sts64(kvs + ((tid >> 2) + 64) * 48 + (tid & 3) * 8, pack_bf16(a1.x, a1.y), pack_bf16(a1.z, a1.w));
                const uint32_t z2 = pack_bf16(zz, zz);
                sts64(kvs + (tid & 127) * 48 + 32 + w * 8, z2, z2);
            }
            bar_sync(1, 256);
            uint32_t o_lo[8], o_hi[8];
#pragma unroll
            for (int hh = 0; hh < 4; hh++) {
                uint32_t b[8], zb[4];
                const uint32_t base = kvs + hh * 32 * 48;
                ldsm4t(base + (lane & 15) * 48 + (lane >> 4) * 16, b[0], b[1], b[2], b[3]);
                ldsm4t(base + (16 + (lane & 15)) * 48 + (lane >> 4) * 16, b[4], b[5], b[6], b[7]);
                ldsm4t(base + lane * 48 + 32, zb[0], zb[1], zb[2], zb[3]);
                float n0[4], n1[4], dn[4], m0[4], m1[4], dm[4];
                mma16816_z(n0, fp + 4 * hh, b[0], b[1]); mma16816_z(n1, fp + 4 * hh, b[2], b[3]); mma16816_z(dn, fp + 4 * hh, zb[0], zb[1]);
                mma16816_z(m0, fm + 4 * hh, b[4], b[5]); mma16816_z(m1, fm + 4 * hh, b[6], b[7]); mma16816_z(dm, fm + 4 * hh, zb[2], zb[3]);
                const float* r = fr + 4 * hh;
                const float i0 = rcp(fmaf(dn[0], r[0], fmaf(dm[0], r[2], 1e-6f))), i1 = rcp(fmaf(dn[2], r[1], fmaf(dm[2], r[3], 1e-6f)));
                const float p0 = r[0] * i0, q0 = r[2] * i0, p1 = r[1] * i1, q1 = r[3] * i1;
                o_lo[2 * hh] = pack_bf16(fmaf(n0[0], p0, m0[0] * q0), fmaf(n0[1], p0, m0[1] * q0));
                o_hi[2 * hh] = pack_bf16(fmaf(n0[2], p1, m0[2] * q1), fmaf(n0[3], p1, m0[3] * q1));
                o_lo[2 * hh + 1] = pack_bf16(fmaf(n1[0], p0, m1[0] * q0), fmaf(n1[1], p0, m1[1] * q0));
                o_hi[2 * hh + 1] = pack_bf16(fmaf(n1[2], p1, m1[2] * q1), fmaf(n1[3], p1, m1[3] * q1));
            }
            const uint32_t ack = store_tile<true>(own_rows, g_o + (size_t)row_w * DM + 64 * j, o_lo, o_hi, lane);
            fence_async_smem();
            signal_after(flag_m, ack, P.zero, l0);
            mbar_arrive_if(sb + BAR_EMPTYA + 8 * (j ^ 1), l0);
            TL(7, tid == 0);
        }
        {
            float acc[32];
#pragma unroll
            for (int t = 0; t < 8; t++) {
                acc[4 * t] = bf_lo(res_lo[t]); acc[4 * t + 1] = bf_hi(res_lo[t]);
                acc[4 * t + 2] = bf_lo(res_hi[t]); acc[4 * t + 3] = bf_hi(res_hi[t]);
            }
            fence_acc<32>(acc);
#pragma unroll 1
            for (int kp = 0; kp < 4; kp++) {
                mbar_waitc(sb + BAR_FULLB + 8 * rg.slot, rg.phase);
#pragma unroll
                for (int hf = 0; hf < 2; hf++) {
                    const int kt = 2 * kp + hf;
                    mbar_waitc(sb + BAR_FULLA + 8 * kt, kt != j);
                    TL(8, kt == 0 && tid == 0);
                    const desc_t da = dA + kp * (2 * SLOT >> 4), db = dB + rg.slot * (SLOT >> 4);
                    wg_fence();
#pragma unroll
                    for (int k = 0; k < 4; k++) wgmma_n64(acc, da + hf * (SLOT >> 4) + 2 * k, db + (hf * 4 + k) * 128, 1);
                    wg_commit();
                    wg_wait<1>();
                    mbar_arrive_if(sb + BAR_EMPTYA + 8 * ((kt + 7) & 7), l0 && kt > 0 && kt - 1 != j);
                    if (hf == 0) mbar_arrive_if(sb + BAR_EMPTYB + 8 * prev, l0 && kt > 0);
                }
                prev = rg.slot; rg.adv();
            }
            wg_wait<0>();
            fence_acc<32>(acc);
            mbar_arrive_if(sb + BAR_EMPTYA + 8 * 7, l0 && j != 7);
            mbar_arrive_if(sb + BAR_EMPTYB + 8 * prev, l0);
            TL(9, tid == 0);
            float s0 = 0.f, s1 = 0.f;
#pragma unroll
            for (int t = 0; t < 8; t++) {
                res_lo[t] = pack_bf16(acc[4 * t], acc[4 * t + 1]);
                res_hi[t] = pack_bf16(acc[4 * t + 2], acc[4 * t + 3]);
                s0 += acc[4 * t] + acc[4 * t + 1];
                s1 += acc[4 * t + 2] + acc[4 * t + 3];
            }
            uint32_t ack = store_tile<true>(own_rows, g_h + (size_t)row_w * DM + 64 * j, res_lo, res_hi, lane);
            s0 += __shfl_xor_sync(0xffffffffu, s0, 1); s1 += __shfl_xor_sync(0xffffffffu, s1, 1);
            s0 += __shfl_xor_sync(0xffffffffu, s0, 2); s1 += __shfl_xor_sync(0xffffffffu, s1, 2);
            const float mu0 = s0 * (1.f / 64), mu1 = s1 * (1.f / 64);
            float q0 = 0.f, q1 = 0.f;
#pragma unroll
            for (int t = 0; t < 8; t++) {
                float d;
                d = acc[4 * t] - mu0; q0 = fmaf(d, d, q0);
                d = acc[4 * t + 1] - mu0; q0 = fmaf(d, d, q0);
                d = acc[4 * t + 2] - mu1; q1 = fmaf(d, d, q1);
                d = acc[4 * t + 3] - mu1; q1 = fmaf(d, d, q1);
            }
            q0 += __shfl_xor_sync(0xffffffffu, q0, 1); q1 += __shfl_xor_sync(0xffffffffu, q1, 1);
            q0 += __shfl_xor_sync(0xffffffffu, q0, 2); q1 += __shfl_xor_sync(0xffffffffu, q1, 2);
            stg_f2_if(g_hstat + (role * 128 + 16 * warp + g + 8 * (q & 1)) * 2, q ? mu1 : mu0, q ? q1 : q0, q < 2);
            ack |= readback(g_hstat + (role * 128 + 16 * warp + g + 8 * (q & 1)) * 2);
            fence_async_smem();
            signal_after(flag_m + 32, ack, P.zero, l0);
            TL(10, tid == 0);
        }
        uint32_t ack[8];
        {
            __nv_bfloat16* const hp = g_hh + (size_t)(row_w + (lane >> 3)) * FFP + 192 * j + (lane & 7) * 8;
            const uint32_t cs3 = sb + OFF_CS3 + q * 16;
            float nm0, nm1;
            int prev2 = 0;
            {
                float acc[128];
                const desc_t dB4 = dB - (256ull << 16);
#pragma unroll 1
                for (int i = 0; i < 16; i++) {
                    mbar_waitc(sb + BAR_FULLA + 8 * (i >> 1), 0);
                    mbar_waitc(sb + BAR_FULLB + 8 * rg.slot, rg.phase);
                    TL(44 + i, tid == 0 && i < 4);
                    const desc_t da = dA + (i >> 1) * (SLOT >> 4) + (i & 1) * 4, db = dB4 + rg.slot * (SLOT >> 4);
                    wg_fence();
                    wgmma_n256(acc, da, db, i != 0);
                    wgmma_n256(acc, da + 2, db + 128, 1);
                    wg_commit();
                    wg_wait<1>();
                    mbar_arrive_if(sb + BAR_EMPTYB + 8 * prev, l0 && i > 0 && i < 15);
                    prev2 = prev; prev = rg.slot; rg.adv();
                }
                mbar_waitc(sb + BAR_CS3, 0);
                nm0 = lds_f2(sb + OFF_CS1 + (16 * warp + g) * 8).x; nm1 = lds_f2(sb + OFF_CS1 + (16 * warp + g + 8) * 8).x;
                wg_wait<0>();
                fence_acc<128>(acc);
                TL(11, tid == 0);
                bar_sync(1, 256);
                hh_store<64, 4>(acc, cs3, nm0, nm1, sb + OFF_B + prev2 * SLOT + warp * 2048, hp, lane, ack);
                mbar_arrive_if(sb + BAR_EMPTYB + 8 * prev2, l0);
                hh_store<64, 4>(acc + 32, cs3 + 512, nm0, nm1, sb + OFF_B + prev * SLOT + warp * 2048, hp + 64, lane, ack + 4);
                mbar_arrive_if(sb + BAR_EMPTYB + 8 * prev, l0);
                TL(50, tid == 0);
            }
            {
                float acc[56];
#pragma unroll 1
                for (int kt = 0; kt < 8; kt++) {
                    mbar_waitc(sb + BAR_FULLB + 8 * rg.slot, rg.phase);
                    const desc_t da = dA + kt * (SLOT >> 4), db = dB + rg.slot * (SLOT >> 4);
                    wg_fence();
#pragma unroll
                    for (int k = 0; k < 4; k++) wgmma_n112(acc, da + 2 * k, db + 128 * k, (kt | k) != 0);
                    wg_commit();
                    wg_wait<1>();
                    mbar_arrive_if(sb + BAR_EMPTYB + 8 * prev, l0 && kt > 0);
                    mbar_arrive_if(sb + BAR_EMPTYA + 8 * ((kt + 7) & 7), l0 && kt > 0);
                    if (kt == 1) { signal_late(flag_m + 64, ack, P.zero, l0); TL(54, tid == 0); }
                    prev = rg.slot; rg.adv();
                }
                wg_wait<0>();
                fence_acc<56>(acc);
                mbar_arrive_if(sb + BAR_EMPTYA + 8 * 7, l0);
                TL(13, tid == 0);
                bar_sync(1, 256);
                hh_store<32, 3>(acc, cs3 + 1024, nm0, nm1, sb + OFF_B + prev * SLOT + warp * 2048, hp + 128, lane, ack);
                mbar_arrive_if(sb + BAR_EMPTYB + 8 * prev, l0);
                TL(52, tid == 0);
            }
        }
        {
            float acc[32];
#define KT_P4(T, HF, NK)                                                                                    \
    do {                                                                                                    \
        const int s_ = (T) & 7;                                                                             \
        if (!(HF)) mbar_waitc(sb + BAR_FULLB + 8 * rg.slot, rg.phase);                                      \
        mbar_waitc(sb + BAR_FULLA + 8 * s_, (((T) >> 3) + 1) & 1);                                          \
        if (!(HF)) TL(30 + (T) / 2, tid == 0);                                                              \
        const desc_t da_ = dA + s_ * (SLOT >> 4), db_ = dB + rg.slot * (SLOT >> 4) + (HF) * 512;            \
        wg_fence();                                                                                         \
        _Pragma("unroll") for (int k = 0; k < (NK); k++) wgmma_n64(acc, da_ + 2 * k, db_ + 128 * k, ((T) | k) != 0); \
        wg_commit();                                                                                        \
        wg_wait<1>();                                                                                       \
        mbar_arrive_if(sb + BAR_EMPTYA + 8 * (((T) + 7) & 7), l0 && (T) > 0);                               \
        if (!(HF)) mbar_arrive_if(sb + BAR_EMPTYB + 8 * prev, l0 && (T) > 0);                               \
        if (HF) { prev = rg.slot; rg.adv(); }                                                               \
    } while (0)
#pragma unroll 1
            for (int t = 0; t < 16; t += 2) {
                KT_P4(t, 0, 4); KT_P4(t + 1, 1, 4);
                if (t == 0) { signal_late(flag_m + 96, ack, P.zero, l0); TL(56, tid == 0); }
            }
#pragma unroll 1
            for (int t = 16; t < 24; t += 2) { KT_P4(t, 0, 3); KT_P4(t + 1, 1, 3); }
            wg_wait<0>();
            fence_acc<32>(acc);
            TL(15, tid == 0);
            const float r0 = lds_f2(sb + OFF_CS1 + (16 * warp + g) * 8).y, r1 = lds_f2(sb + OFF_CS1 + (16 * warp + g + 8) * 8).y;
#pragma unroll
            for (int t = 0; t < 8; t++) {
                res_lo[t] = pack_bf16(fmaf(acc[4 * t], r0, bf_lo(res_lo[t])), fmaf(acc[4 * t + 1], r0, bf_hi(res_lo[t])));
                res_hi[t] = pack_bf16(fmaf(acc[4 * t + 2], r1, bf_lo(res_hi[t])), fmaf(acc[4 * t + 3], r1, bf_hi(res_hi[t])));
            }
            store_tile<false>(own_rows, P.out + (size_t)row_w * DM + 64 * j, res_lo, res_hi, lane);
            if (tid == 0 && role == 0) g_epoch = epoch + 1;
            TL(16, tid == 0); TLG(1, tid == 0);
        }
    }
}

typedef CUresult (*EncodeFn)(CUtensorMap*, CUtensorMapDataType, cuuint32_t, void*, const cuuint64_t*, const cuuint64_t*,
                             const cuuint32_t*, const cuuint32_t*, CUtensorMapInterleave, CUtensorMapSwizzle,
                             CUtensorMapL2promotion, CUtensorMapFloatOOBfill);

static void make_map2d(EncodeFn enc, CUtensorMap* tm, const void* base, uint64_t cols, uint64_t rows, uint64_t pitch_elems,
                       uint32_t box_rows) {
    cuuint64_t gd[2] = {cols, rows};
    cuuint64_t gs[1] = {pitch_elems * 2};
    cuuint32_t bd[2] = {64, box_rows};
    cuuint32_t es[2] = {1, 1};
    enc(tm, CU_TENSOR_MAP_DATA_TYPE_BFLOAT16, 2, const_cast<void*>(base), gd, gs, bd, es, CU_TENSOR_MAP_INTERLEAVE_NONE,
        CU_TENSOR_MAP_SWIZZLE_128B, CU_TENSOR_MAP_L2_PROMOTION_L2_256B, CU_TENSOR_MAP_FLOAT_OOB_FILL_NONE);
}

}

extern "C" void kernel_launch(void* const* d_in, const int* in_sizes, int n_in, void* d_out, int out_size) {
    using namespace hk;
    (void)in_sizes; (void)n_in; (void)out_size;
    static EncodeFn enc = nullptr;
    static void *po = nullptr, *ph = nullptr, *phh = nullptr;
    static int std_layout = 0;
    if (!enc) {
        void* fn = nullptr;
        cudaDriverEntryPointQueryResult qr;
        cudaGetDriverEntryPoint("cuTensorMapEncodeTiled", &fn, cudaEnableDefault, &qr);
        enc = (EncodeFn)fn;
        cudaGetSymbolAddress(&po, g_o);
        cudaGetSymbolAddress(&ph, g_h);
        cudaGetSymbolAddress(&phh, g_hh);
        cudaFuncSetAttribute(fused_kernel, cudaFuncAttributeMaxDynamicSharedMemorySize, SMEM_BYTES);
        int dev = 0, sms = 0;
        cudaGetDevice(&dev);
        cudaDeviceGetAttribute(&sms, cudaDevAttrMultiProcessorCount, dev);
        cudaFuncSetAttribute(fused_kernel, cudaFuncAttributeNonPortableClusterSizeAllowed, 1);
        const int sizes[3] = {8, 9, 16}, want[3] = {15, 9, 7};
        bool ok = sms == NCTA;
        for (int i = 0; i < 3 && ok; i++) {
            cudaLaunchConfig_t cfg = {};
            cfg.gridDim = dim3(sizes[i] * 8); cfg.blockDim = dim3(NTHREADS); cfg.dynamicSmemBytes = SMEM_BYTES;
            cudaLaunchAttribute at;
            at.id = cudaLaunchAttributeClusterDimension;
            at.val.clusterDim.x = sizes[i]; at.val.clusterDim.y = 1; at.val.clusterDim.z = 1;
            cfg.attrs = &at; cfg.numAttrs = 1;
            int n = 0;
            ok = cudaOccupancyMaxActiveClusters(&n, fused_kernel, &cfg) == cudaSuccess && n == want[i];
        }
        (void)cudaGetLastError();
        std_layout = ok ? 1 : 0;
    }
    Params P;
    const __nv_bfloat16* x = (const __nv_bfloat16*)d_in[0];
    P.x = x;
    P.wqkv = (const __nv_bfloat16*)d_in[1];
    P.wphi = (const __nv_bfloat16*)d_in[2];
    P.wo = (const __nv_bfloat16*)d_in[3];
    P.wg = (const __nv_bfloat16*)d_in[5];
    P.wu = (const __nv_bfloat16*)d_in[6];
    P.wd = (const __nv_bfloat16*)d_in[7];
    P.out = (__nv_bfloat16*)d_out;
    P.use_smid = std_layout;
    P.zero = 0;
    for (int i = 0; i < NCTA; i++) {
        int role = i < 4 ? 128 + i : i - 4;
        if (std_layout) {
            const int tpc = i >> 1, odd = i & 1;
            if (tpc < 32) role = (tpc & 7) * 8 + (tpc >> 3) * 2 + odd;
            else if (tpc < 60) role = (8 + (tpc - 32) % 7) * 8 + ((tpc - 32) / 7) * 2 + odd;
            else if (tpc < 62) role = 128 + (tpc - 60) * 2 + odd;
            else role = 15 * 8 + (tpc - 62) * 2 + odd;
        }
        P.role[i] = (unsigned char)role;
    }
    make_map2d(enc, &P.tx, x, DM, SEQ, DM, 128);
    make_map2d(enc, &P.to, po, DM, SEQ, DM, 128);
    make_map2d(enc, &P.th, ph, DM, SEQ, DM, 128);
    make_map2d(enc, &P.thh, phh, FFP, SEQ, FFP, 128);
    make_map2d(enc, &P.twq, P.wqkv, 3 * DM, DM, 3 * DM, 128);
    make_map2d(enc, &P.two, P.wo, DM, DM, DM, 128);
    make_map2d(enc, &P.twg, P.wg, FF, DM, FF, 64);
    make_map2d(enc, &P.twu, P.wu, FF, DM, FF, 64);
    make_map2d(enc, &P.twd, P.wd, DM, FF, DM, 64);
    {
        cuuint64_t gd[3] = {(cuuint64_t)DM, (cuuint64_t)DM, 3};
        cuuint64_t gs[2] = {(cuuint64_t)3 * DM * 2, (cuuint64_t)DM * 2};
        cuuint32_t bd[3] = {64, 64, 2};
        cuuint32_t es[3] = {1, 1, 1};
        enc(&P.twkv, CU_TENSOR_MAP_DATA_TYPE_BFLOAT16, 3, const_cast<__nv_bfloat16*>(P.wqkv), gd, gs, bd, es,
            CU_TENSOR_MAP_INTERLEAVE_NONE, CU_TENSOR_MAP_SWIZZLE_128B, CU_TENSOR_MAP_L2_PROMOTION_L2_256B,
            CU_TENSOR_MAP_FLOAT_OOB_FILL_NONE);
    }
    for (int i = 0; i < 2; i++) {
        cuuint64_t gd[3] = {(cuuint64_t)FF - 64, (cuuint64_t)DM, 2};
        cuuint64_t gs[2] = {(cuuint64_t)FF * 2, 128};
        cuuint32_t bd[3] = {64, 32, 2};
        cuuint32_t es[3] = {1, 1, 1};
        enc(i ? &P.twu2 : &P.twg2, CU_TENSOR_MAP_DATA_TYPE_BFLOAT16, 3, const_cast<__nv_bfloat16*>(i ? P.wu : P.wg), gd, gs, bd, es,
            CU_TENSOR_MAP_INTERLEAVE_NONE, CU_TENSOR_MAP_SWIZZLE_128B, CU_TENSOR_MAP_L2_PROMOTION_L2_256B,
            CU_TENSOR_MAP_FLOAT_OOB_FILL_NONE);
    }
    fused_kernel<<<NCTA, NTHREADS, SMEM_BYTES>>>(P);
}
```

```cpp
#include <cuda_runtime.h>
#include <cuda_bf16.h>
#include <cuda.h>
#include <stdint.h>

namespace hk {

constexpr int SEQ = 2048, DM = 512, FF = 1376, FFP = 1536;
constexpr int NCTA = 132;
constexpr int NTHREADS = 384;
constexpr uint32_t SLOT = 16384;
constexpr uint32_t OFF_A = 0, OFF_B = 8 * SLOT, OFF_MISC = 14 * SLOT;
constexpr uint32_t BAR_FULLA = OFF_MISC + 0, BAR_EMPTYA = OFF_MISC + 64, BAR_FULLB = OFF_MISC + 128,
                   BAR_EMPTYB = OFF_MISC + 176, BAR_CS1 = OFF_MISC + 224, BAR_CS3 = OFF_MISC + 232,
                   BAR_CSQ = OFF_MISC + 240, BAR_CSV = OFF_MISC + 248,
                   BAR_STG = OFF_MISC + 256;
constexpr uint32_t OFF_CS1 = OFF_MISC + 384;
constexpr uint32_t OFF_CS3 = OFF_CS1 + 1024;
constexpr uint32_t SMEM_BYTES = OFF_CS3 + 1536;
constexpr int NB = 6;
constexpr int AHEAD = 3;

constexpr int ACC_KV = 0, ACC_Z = 2048, ACC_SIZE = 2176;

__device__ __align__(1024) __nv_bfloat16 g_o[SEQ * DM];
__device__ __align__(1024) __nv_bfloat16 g_h[SEQ * DM];
__device__ __align__(1024) __nv_bfloat16 g_hh[SEQ * FFP];
__device__ __align__(128) float g_hstat[SEQ * 16];
__device__ __align__(128) unsigned long long g_xstat[SEQ * 2];
__device__ __align__(128) float g_acc[8 * ACC_SIZE];
__device__ __align__(128) unsigned g_cnt[8 * 32];
__device__ __align__(128) unsigned long long g_cs[8 * 6 * 128];
__device__ __align__(128) unsigned g_flag[16 * 5 * 32];
__device__ unsigned g_epoch = 1;

#define TL(i, pred) do {} while (0)
#define TLG(i, pred) do {} while (0)

struct Params {
    CUtensorMap tx, to, th, thh, twkv, twq, two, twg, twu, twd, twg2, twu2;
    const __nv_bfloat16 *x, *wqkv, *wphi, *wo, *wg, *wu, *wd;
    __nv_bfloat16* out;
    int use_smid;
    unsigned zero;
    unsigned char role[NCTA];
};

__device__ __forceinline__ uint32_t smem_u32(const void* p) { return (uint32_t)__cvta_generic_to_shared(p); }
__device__ __forceinline__ void mbar_init(uint32_t bar, uint32_t cnt) {
    asm volatile("mbarrier.init.shared::cta.b64 [%0], %1;" ::"r"(bar), "r"(cnt) : "memory");
}
__device__ __forceinline__ void mbar_expect_tx(uint32_t bar, uint32_t bytes) {
    asm volatile("mbarrier.arrive.expect_tx.shared::cta.b64 _, [%0], %1;" ::"r"(bar), "r"(bytes) : "memory");
}
__device__ __forceinline__ void mbar_arrive(uint32_t bar) {
    asm volatile("mbarrier.arrive.shared::cta.b64 _, [%0];" ::"r"(bar) : "memory");
}
__device__ __forceinline__ void mbar_arrive_if(uint32_t bar, bool pred) {
    asm volatile("{.reg .pred p; setp.ne.u32 p, %1, 0; @p mbarrier.arrive.shared::cta.b64 _, [%0];}" ::"r"(bar), "r"((uint32_t)pred) : "memory");
}
__device__ __forceinline__ bool mbar_try(uint32_t bar, uint32_t parity) {
    uint32_t ok;
    asm volatile("{.reg .pred p; mbarrier.try_wait.parity.shared::cta.b64 p, [%1], %2; selp.u32 %0,1,0,p;}"
                 : "=r"(ok) : "r"(bar), "r"(parity) : "memory");
    return ok;
}
__device__ __forceinline__ bool mbar_test(uint32_t bar, uint32_t parity) {
    uint32_t ok;
    asm volatile("{.reg .pred p; mbarrier.test_wait.parity.shared::cta.b64 p, [%1], %2; selp.u32 %0,1,0,p;}"
                 : "=r"(ok) : "r"(bar), "r"(parity) : "memory");
    return ok;
}
__device__ __forceinline__ void trap_if_gt(uint32_t v, uint32_t lim) {
    asm volatile("{.reg .pred p; setp.gt.u32 p, %0, %1; @p trap;}" ::"r"(v), "r"(lim));
}
__device__ __forceinline__ void mbar_wait(uint32_t bar, uint32_t parity) {
    asm volatile("{\n"
                 ".reg .pred P1, P2;\n"
                 ".reg .u32 c;\n"
                 "mov.u32 c, 0;\n"
                 "LAB_WAIT:\n"
                 "mbarrier.try_wait.parity.shared::cta.b64 P1, [%0], %1;\n"
                 "@P1 bra LAB_DONE;\n"
                 "add.u32 c, c, 1;\n"
                 "setp.gt.u32 P2, c, 4194304;\n"
                 "@P2 trap;\n"
                 "bra LAB_WAIT;\n"
                 "LAB_DONE:\n"
                 "}" ::"r"(bar), "r"(parity) : "memory");
}
__device__ __forceinline__ void mbar_waitc(uint32_t bar, uint32_t parity) {
    asm volatile("{\n"
                 ".reg .pred P1;\n"
                 "LAB_WAIT:\n"
                 "mbarrier.try_wait.parity.shared::cta.b64 P1, [%0], %1;\n"
                 "@!P1 bra LAB_WAIT;\n"
                 "}" ::"r"(bar), "r"(parity) : "memory");
}
__device__ __forceinline__ void tma2d(uint32_t dst, const CUtensorMap* tm, uint32_t bar, int c0, int c1) {
    asm volatile("cp.async.bulk.tensor.2d.shared::cluster.global.mbarrier::complete_tx::bytes [%0], [%1, {%3, %4}], [%2];"
                 ::"r"(dst), "l"(tm), "r"(bar), "r"(c0), "r"(c1) : "memory");
}
__device__ __forceinline__ void tma3d(uint32_t dst, const CUtensorMap* tm, uint32_t bar, int c0, int c1, int c2) {
    asm volatile("cp.async.bulk.tensor.3d.shared::cluster.global.mbarrier::complete_tx::bytes [%0], [%1, {%3, %4, %5}], [%2];"
                 ::"r"(dst), "l"(tm), "r"(bar), "r"(c0), "r"(c1), "r"(c2) : "memory");
}
__device__ __forceinline__ bool elect_one() {
    uint32_t ok;
    asm volatile("{.reg .pred p; elect.sync _|p, 0xffffffff; selp.u32 %0, 1, 0, p;}" : "=r"(ok));
    return ok;
}
__device__ __forceinline__ void prefetch_tmap(const CUtensorMap* tm) {
    asm volatile("prefetch.tensormap [%0];" ::"l"(tm) : "memory");
}
__device__ __forceinline__ void prefetch_l2(const void* p, uint32_t bytes) {
    asm volatile("cp.async.bulk.prefetch.L2.global [%0], %1;" ::"l"(p), "r"(bytes) : "memory");
}
__device__ __forceinline__ unsigned ld_acquire(const unsigned* p) {
    unsigned v; asm volatile("ld.acquire.gpu.global.u32 %0, [%1];" : "=r"(v) : "l"(p) : "memory"); return v;
}
__device__ __forceinline__ uint4 ld_acquire4(const unsigned* p) {
    uint4 v;
    asm volatile("ld.acquire.gpu.global.v4.u32 {%0,%1,%2,%3}, [%4];" : "=r"(v.x), "=r"(v.y), "=r"(v.z), "=r"(v.w) : "l"(p) : "memory");
    return v;
}
__device__ __forceinline__ unsigned ld_relaxed(const unsigned* p) {
    unsigned v; asm volatile("ld.relaxed.gpu.global.u32 %0, [%1];" : "=r"(v) : "l"(p)); return v;
}
__device__ __forceinline__ void st_relaxed(unsigned* p, unsigned v) {
    asm volatile("st.relaxed.gpu.global.u32 [%0], %1;" ::"l"(p), "r"(v) : "memory");
}
__device__ __forceinline__ void red_relaxed(unsigned* p, unsigned v) {
    asm volatile("red.relaxed.gpu.global.add.u32 [%0], %1;" ::"l"(p), "r"(v) : "memory");
}
__device__ __forceinline__ void fence_gpu() { asm volatile("fence.acq_rel.gpu;" ::: "memory"); }
__device__ __forceinline__ void fence_async_smem() { asm volatile("fence.proxy.async.shared::cta;" ::: "memory"); }
__device__ __forceinline__ void fence_async_global() { asm volatile("fence.proxy.async.global;" ::: "memory"); }
__device__ __forceinline__ void wait_count(const unsigned* p, unsigned target) {
    uint32_t it = 0;
    while ((int)(ld_acquire(p) - target) < 0) trap_if_gt(++it, 1u << 22);
}
__device__ __forceinline__ void wait_count_warp(const unsigned* p, unsigned target) {
    uint32_t it = 0;
    while (__any_sync(0xffffffffu, (int)(ld_acquire(p) - target) < 0)) trap_if_gt(++it, 1u << 22);
}
__device__ __forceinline__ void red_f32(float* p, float a) {
    asm volatile("red.relaxed.gpu.global.add.f32 [%0], %1;" ::"l"(p), "f"(a) : "memory");
}
__device__ __forceinline__ void red_f32x2(float* p, float a, float b) {
    asm volatile("red.relaxed.gpu.global.add.v2.f32 [%0], {%1, %2};" ::"l"(p), "f"(a), "f"(b) : "memory");
}
__device__ __forceinline__ void red_f32x4(float* p, float a, float b, float c, float d) {
    asm volatile("red.relaxed.gpu.global.add.v4.f32 [%0], {%1, %2, %3, %4};" ::"l"(p), "f"(a), "f"(b), "f"(c), "f"(d) : "memory");
}
__device__ __forceinline__ float4 ld_l2_f4(const float* p) {
    float4 v;
    asm volatile("ld.relaxed.gpu.global.v4.f32 {%0,%1,%2,%3}, [%4];" : "=f"(v.x), "=f"(v.y), "=f"(v.z), "=f"(v.w) : "l"(p) : "memory");
    return v;
}
__device__ __forceinline__ float2 ld_l2_f2(const float* p) {
    float2 v;
    asm volatile("ld.relaxed.gpu.global.v2.f32 {%0,%1}, [%2];" : "=f"(v.x), "=f"(v.y) : "l"(p) : "memory");
    return v;
}
__device__ __forceinline__ float ld_l2_f(const float* p) {
    float v;
    asm volatile("ld.relaxed.gpu.global.f32 %0, [%1];" : "=f"(v) : "l"(p) : "memory");
    return v;
}
__device__ __forceinline__ uint4 ldg_nc(const void* p) {
    uint4 v;
    asm volatile("ld.global.nc.L1::no_allocate.v4.u32 {%0,%1,%2,%3}, [%4];" : "=r"(v.x), "=r"(v.y), "=r"(v.z), "=r"(v.w) : "l"(p));
    return v;
}
__device__ __forceinline__ void stg128(void* p, uint32_t a, uint32_t b, uint32_t c, uint32_t d) {
    asm volatile("st.global.v4.u32 [%0], {%1,%2,%3,%4};" ::"l"(p), "r"(a), "r"(b), "r"(c), "r"(d) : "memory");
}
__device__ __forceinline__ uint4 lds128(uint32_t a) {
    uint4 v;
    asm volatile("ld.shared.v4.u32 {%0,%1,%2,%3}, [%4];" : "=r"(v.x), "=r"(v.y), "=r"(v.z), "=r"(v.w) : "r"(a) : "memory");
    return v;
}
__device__ __forceinline__ float2 lds_f2(uint32_t a) {
    float2 v;
    asm volatile("ld.shared.v2.f32 {%0,%1}, [%2];" : "=f"(v.x), "=f"(v.y) : "r"(a) : "memory");
    return v;
}
__device__ __forceinline__ void sts_f2(uint32_t a, float x, float y) {
    asm volatile("st.shared.v2.f32 [%0], {%1,%2};" ::"r"(a), "f"(x), "f"(y) : "memory");
}
__device__ __forceinline__ void sts64(uint32_t a, uint32_t x, uint32_t y) {
    asm volatile("st.shared.v2.u32 [%0], {%1,%2};" ::"r"(a), "r"(x), "r"(y) : "memory");
}
__device__ __forceinline__ void sts128(uint32_t a, uint32_t x, uint32_t y, uint32_t z, uint32_t w) {
    asm volatile("st.shared.v4.u32 [%0], {%1,%2,%3,%4};" ::"r"(a), "r"(x), "r"(y), "r"(z), "r"(w) : "memory");
}
__device__ __forceinline__ void stsm4(uint32_t a, uint32_t r0, uint32_t r1, uint32_t r2, uint32_t r3) {
    asm volatile("stmatrix.sync.aligned.m8n8.x4.shared.b16 [%0], {%1,%2,%3,%4};" ::"r"(a), "r"(r0), "r"(r1), "r"(r2), "r"(r3) : "memory");
}
__device__ __forceinline__ void stsm4t(uint32_t a, uint32_t r0, uint32_t r1, uint32_t r2, uint32_t r3) {
    asm volatile("stmatrix.sync.aligned.m8n8.x4.trans.shared.b16 [%0], {%1,%2,%3,%4};" ::"r"(a), "r"(r0), "r"(r1), "r"(r2), "r"(r3) : "memory");
}
__device__ __forceinline__ void tma_store2d(const CUtensorMap* tm, uint32_t src, int c0, int c1) {
    asm volatile("cp.async.bulk.tensor.2d.global.shared::cta.bulk_group [%0, {%2, %3}], [%1];" ::"l"(tm), "r"(src), "r"(c0), "r"(c1) : "memory");
    asm volatile("cp.async.bulk.commit_group;" ::: "memory");
}
__device__ __forceinline__ void ldsm4(uint32_t a, uint32_t& r0, uint32_t& r1, uint32_t& r2, uint32_t& r3) {
    asm volatile("ldmatrix.sync.aligned.m8n8.x4.shared.b16 {%0,%1,%2,%3}, [%4];" : "=r"(r0), "=r"(r1), "=r"(r2), "=r"(r3) : "r"(a) : "memory");
}
__device__ __forceinline__ void ldsm4t(uint32_t a, uint32_t& r0, uint32_t& r1, uint32_t& r2, uint32_t& r3) {
    asm volatile("ldmatrix.sync.aligned.m8n8.x4.trans.shared.b16 {%0,%1,%2,%3}, [%4];" : "=r"(r0), "=r"(r1), "=r"(r2), "=r"(r3) : "r"(a) : "memory");
}
__device__ __forceinline__ void mma16816(float* c, const uint32_t* a, uint32_t b0, uint32_t b1) {
    asm("mma.sync.aligned.m16n8k16.row.col.f32.bf16.bf16.f32 {%0,%1,%2,%3}, {%4,%5,%6,%7}, {%8,%9}, {%0,%1,%2,%3};"
                 : "+f"(c[0]), "+f"(c[1]), "+f"(c[2]), "+f"(c[3])
                 : "r"(a[0]), "r"(a[1]), "r"(a[2]), "r"(a[3]), "r"(b0), "r"(b1));
}
__device__ __forceinline__ uint32_t pack_bf16(float lo, float hi) {
    uint32_t r; asm("cvt.rn.bf16x2.f32 %0, %1, %2;" : "=r"(r) : "f"(hi), "f"(lo)); return r;
}
__device__ __forceinline__ float bf_lo(uint32_t w) { return __uint_as_float(w << 16); }
__device__ __forceinline__ float bf_hi(uint32_t w) { return __uint_as_float(w & 0xffff0000u); }
__device__ __forceinline__ float ex2(float x) { float r; asm("ex2.approx.ftz.f32 %0, %1;" : "=f"(r) : "f"(x)); return r; }
__device__ __forceinline__ float rcp(float x) { float r; asm("rcp.approx.ftz.f32 %0, %1;" : "=f"(r) : "f"(x)); return r; }
__device__ __forceinline__ void bar_sync(int id, int n) { asm volatile("bar.sync %0, %1;" ::"r"(id), "r"(n) : "memory"); }

typedef unsigned long long desc_t;
__device__ __forceinline__ desc_t desc_lo(uint32_t addr) { return (desc_t)(((addr & 0x3FFFF) >> 4) | (512u << 16)) | (0x40000040ull << 32); }
__device__ __forceinline__ void wg_fence() { asm volatile("wgmma.fence.sync.aligned;" ::: "memory"); }
__device__ __forceinline__ void wg_commit() { asm volatile("wgmma.commit_group.sync.aligned;" ::: "memory"); }
template <int N> __device__ __forceinline__ void wg_wait() { asm volatile("wgmma.wait_group.sync.aligned %0;" ::"n"(N) : "memory"); }
template <int N> __device__ __forceinline__ void fence_acc(float* d) {
#pragma unroll
    for (int i = 0; i < N; i++) asm volatile("" : "+f"(d[i])::"memory");
}
#define R4(o) "+f"(d[o + 0]), "+f"(d[o + 1]), "+f"(d[o + 2]), "+f"(d[o + 3])
#define R8(o) R4(o), R4(o + 4)
__device__ __forceinline__ void wgmma_n128(float* d, desc_t da, desc_t db, int sc) {
    asm volatile("{.reg .pred p; setp.ne.b32 p, %66, 0;\n"
                 "wgmma.mma_async.sync.aligned.m64n128k16.f32.bf16.bf16 {%0,%1,%2,%3,%4,%5,%6,%7,%8,%9,%10,%11,%12,%13,%14,%15,%16,%17,%18,%19,%20,%21,%22,%23,%24,%25,%26,%27,%28,%29,%30,%31,"
                 "%32,%33,%34,%35,%36,%37,%38,%39,%40,%41,%42,%43,%44,%45,%46,%47,%48,%49,%50,%51,%52,%53,%54,%55,%56,%57,%58,%59,%60,%61,%62,%63}, %64, %65, p, 1, 1, 0, 1;}"
                 : R8(0), R8(8), R8(16), R8(24), R8(32), R8(40), R8(48), R8(56)
                 : "l"(da), "l"(db), "r"(sc));
}
__device__ __forceinline__ void wgmma_n256(float* d, desc_t da, desc_t db, int sc) {
    asm volatile("{.reg .pred p; setp.ne.b32 p, %130, 0;\n"
                 "wgmma.mma_async.sync.aligned.m64n256k16.f32.bf16.bf16 {%0,%1,%2,%3,%4,%5,%6,%7,%8,%9,%10,%11,%12,%13,%14,%15,%16,%17,%18,%19,%20,%21,%22,%23,%24,%25,%26,%27,%28,%29,%30,%31,%32,%33,%34,%35,%36,%37,%38,%39,%40,%41,%42,%43,%44,%45,%46,%47,%48,%49,%50,%51,%52,%53,%54,%55,%56,%57,%58,%59,%60,%61,%62,%63,%64,%65,%66,%67,%68,%69,%70,%71,%72,%73,%74,%75,%76,%77,%78,%79,%80,%81,%82,%83,%84,%85,%86,%87,%88,%89,%90,%91,%92,%93,%94,%95,%96,%97,%98,%99,%100,%101,%102,%103,%104,%105,%106,%107,%108,%109,%110,%111,%112,%113,%114,%115,%116,%117,%118,%119,%120,%121,%122,%123,%124,%125,%126,%127}, %128, %129, p, 1, 1, 0, 1;}"
                 : R8(0), R8(8), R8(16), R8(24), R8(32), R8(40), R8(48), R8(56), R8(64), R8(72), R8(80), R8(88), R8(96), R8(104), R8(112), R8(120)
                 : "l"(da), "l"(db), "r"(sc));
}
__device__ __forceinline__ void wgmma_n112(float* d, desc_t da, desc_t db, int sc) {
    asm volatile("{.reg .pred p; setp.ne.b32 p, %58, 0;\n"
                 "wgmma.mma_async.sync.aligned.m64n112k16.f32.bf16.bf16 {%0,%1,%2,%3,%4,%5,%6,%7,%8,%9,%10,%11,%12,%13,%14,%15,%16,%17,%18,%19,%20,%21,%22,%23,%24,%25,%26,%27,%28,%29,%30,%31,%32,%33,%34,%35,%36,%37,%38,%39,%40,%41,%42,%43,%44,%45,%46,%47,%48,%49,%50,%51,%52,%53,%54,%55}, %56, %57, p, 1, 1, 0, 1;}"
                 : R8(0), R8(8), R8(16), R8(24), R8(32), R8(40), R8(48)
                 : "l"(da), "l"(db), "r"(sc));
}
__device__ __forceinline__ void wgmma_n128_tn(float* d, desc_t da, desc_t db, int sc) {
    asm volatile("{.reg .pred p; setp.ne.b32 p, %66, 0;\n"
                 "wgmma.mma_async.sync.aligned.m64n128k16.f32.bf16.bf16 {%0,%1,%2,%3,%4,%5,%6,%7,%8,%9,%10,%11,%12,%13,%14,%15,%16,%17,%18,%19,%20,%21,%22,%23,%24,%25,%26,%27,%28,%29,%30,%31,%32,%33,%34,%35,%36,%37,%38,%39,%40,%41,%42,%43,%44,%45,%46,%47,%48,%49,%50,%51,%52,%53,%54,%55,%56,%57,%58,%59,%60,%61,%62,%63}, %64, %65, p, 1, 1, 1, 0;}"
                 : R8(0), R8(8), R8(16), R8(24), R8(32), R8(40), R8(48), R8(56)
                 : "l"(da), "l"(db), "r"(sc));
}
__device__ __forceinline__ void wgmma_n64(float* d, desc_t da, desc_t db, int sc) {
    asm volatile("{.reg .pred p; setp.ne.b32 p, %34, 0;\n"
                 "wgmma.mma_async.sync.aligned.m64n64k16.f32.bf16.bf16 {%0,%1,%2,%3,%4,%5,%6,%7,%8,%9,%10,%11,%12,%13,%14,%15,%16,%17,%18,%19,%20,%21,%22,%23,%24,%25,%26,%27,%28,%29,%30,%31}, %32, %33, p, 1, 1, 0, 1;}"
                 : R8(0), R8(8), R8(16), R8(24)
                 : "l"(da), "l"(db), "r"(sc));
}
__device__ __forceinline__ void wgmma_n40_tt(float* d, desc_t da, desc_t db, int sc) {
    asm volatile("{.reg .pred p; setp.ne.b32 p, %22, 0;\n"
                 "wgmma.mma_async.sync.aligned.m64n40k16.f32.bf16.bf16 {%0,%1,%2,%3,%4,%5,%6,%7,%8,%9,%10,%11,%12,%13,%14,%15,%16,%17,%18,%19}, %20, %21, p, 1, 1, 1, 1;}"
                 : R8(0), R8(8), R4(16)
                 : "l"(da), "l"(db), "r"(sc));
}

__device__ __forceinline__ void wgmma_n8_tt(float* d, desc_t da, desc_t db, int sc) {
    asm volatile("{.reg .pred p; setp.ne.b32 p, %6, 0;\n"
                 "wgmma.mma_async.sync.aligned.m64n8k16.f32.bf16.bf16 {%0,%1,%2,%3}, %4, %5, p, 1, 1, 1, 1;}"
                 : R4(0)
                 : "l"(da), "l"(db), "r"(sc));
}

__device__ __forceinline__ uint32_t readback(const void* p) {
    uint32_t v; asm volatile("ld.relaxed.gpu.global.u32 %0, [%1];" : "=r"(v) : "l"(p) : "memory"); return v;
}
__device__ __forceinline__ uint32_t atom_f32x2(float* p, float a, float b) {
    float x, y;
    asm volatile("atom.relaxed.gpu.global.add.v2.f32 {%0,%1}, [%2], {%3,%4};" : "=f"(x), "=f"(y) : "l"(p), "f"(a), "f"(b) : "memory");
    return __float_as_uint(x);
}
__device__ __forceinline__ uint32_t atom_f32_if(float* p, float a, bool pred) {
    float x = 0.f;
    asm volatile("{.reg .pred p; setp.ne.u32 p, %3, 0; @p atom.relaxed.gpu.global.add.f32 %0, [%1], %2;}" : "+f"(x) : "l"(p), "f"(a), "r"((uint32_t)pred) : "memory");
    return __float_as_uint(x);
}
__device__ __forceinline__ void signal_after(unsigned* cnt, uint32_t ack, uint32_t zero, bool pred) {
    asm volatile("{.reg .pred p; setp.ne.u32 p, %2, 0; @p red.relaxed.gpu.global.add.u32 [%0], %1;}"
                 ::"l"(cnt), "r"((ack & zero) + 1), "r"((uint32_t)pred) : "memory");
}
__device__ __forceinline__ void signal_late(unsigned* cnt, const uint32_t* a, uint32_t zero, bool pred) {
    uint32_t v;
    asm volatile("{.reg .b32 t; lop3.b32 t, %1, %2, %3, 0xfe; lop3.b32 t, t, %4, %5, 0xfe; lop3.b32 t, t, %6, %7, 0xfe; or.b32 %0, t, %8;}"
                 : "=r"(v) : "r"(a[0]), "r"(a[1]), "r"(a[2]), "r"(a[3]), "r"(a[4]), "r"(a[5]), "r"(a[6]), "r"(a[7]));
    signal_after(cnt, v, zero, pred);
}
__device__ __forceinline__ void red_f32_if(float* p, float a, bool pred) {
    asm volatile("{.reg .pred p; setp.ne.u32 p, %2, 0; @p red.relaxed.gpu.global.add.f32 [%0], %1;}" ::"l"(p), "f"(a), "r"((uint32_t)pred) : "memory");
}
__device__ __forceinline__ void stg_f2_if(float* p, float a, float b, bool pred) {
    asm volatile("{.reg .pred p; setp.ne.u32 p, %3, 0; @p st.global.v2.f32 [%0], {%1,%2};}" ::"l"(p), "f"(a), "f"(b), "r"((uint32_t)pred) : "memory");
}
__device__ __forceinline__ void stg64(void* p, uint32_t a, uint32_t b) {
    asm volatile("st.global.v2.u32 [%0], {%1,%2};" ::"l"(p), "r"(a), "r"(b) : "memory");
}
__device__ __forceinline__ void mma16816_z(float* c, const uint32_t* a, uint32_t b0, uint32_t b1) {
    asm("mma.sync.aligned.m16n8k16.row.col.f32.bf16.bf16.f32 {%0,%1,%2,%3}, {%4,%5,%6,%7}, {%8,%9}, {%10,%10,%10,%10};"
                 : "=f"(c[0]), "=f"(c[1]), "=f"(c[2]), "=f"(c[3])
                 : "r"(a[0]), "r"(a[1]), "r"(a[2]), "r"(a[3]), "r"(b0), "r"(b1), "f"(0.f));
}
__device__ __forceinline__ uint32_t max2(uint32_t a, uint32_t b) { uint32_t r; asm("max.bf16x2 %0, %1, %2;" : "=r"(r) : "r"(a), "r"(b)); return r; }
__device__ __forceinline__ uint32_t min2(uint32_t a, uint32_t b) { uint32_t r; asm("min.bf16x2 %0, %1, %2;" : "=r"(r) : "r"(a), "r"(b)); return r; }
__device__ __forceinline__ void bar_arrive(int id, int n) { asm volatile("bar.arrive %0, %1;" ::"r"(id), "r"(n) : "memory"); }
__device__ __forceinline__ void mbar_arrive_n_if(uint32_t bar, uint32_t n, bool pred) {
    asm volatile("{.reg .pred p; setp.ne.u32 p, %1, 0; @p mbarrier.arrive.shared::cta.b64 _, [%0], %2;}" ::"r"(bar), "r"((uint32_t)pred), "r"(n) : "memory");
}
__device__ __forceinline__ float4 lds_f4(uint32_t a) {
    float4 v;
    asm volatile("ld.shared.v4.f32 {%0,%1,%2,%3}, [%4];" : "=f"(v.x), "=f"(v.y), "=f"(v.z), "=f"(v.w) : "r"(a) : "memory");
    return v;
}
__device__ __forceinline__ uint4 ld_tagged(const unsigned long long* p) {
    unsigned long long a, b;
    asm volatile("ld.acquire.gpu.global.v2.b64 {%0,%1}, [%2];" : "=l"(a), "=l"(b) : "l"(p) : "memory");
    return make_uint4((unsigned)a, (unsigned)(a >> 32), (unsigned)b, (unsigned)(b >> 32));
}
__device__ __forceinline__ uint4 ld_tagged_rlx(const unsigned long long* p) {
    unsigned long long a, b;
    asm volatile("ld.relaxed.gpu.global.v2.b64 {%0,%1}, [%2];" : "=l"(a), "=l"(b) : "l"(p) : "memory");
    return make_uint4((unsigned)a, (unsigned)(a >> 32), (unsigned)b, (unsigned)(b >> 32));
}
__device__ __forceinline__ void st_tagged_if(unsigned long long* p, float a, float b, unsigned tag, bool pred) {
    const unsigned long long t = (unsigned long long)tag << 32;
    asm volatile("{.reg .pred p; setp.ne.u32 p, %3, 0; @p st.relaxed.gpu.global.v2.b64 [%0], {%1,%2};}"
                 ::"l"(p), "l"(t | __float_as_uint(a)), "l"(t | __float_as_uint(b)), "r"((uint32_t)pred) : "memory");
}

template <bool ACK>
__device__ __forceinline__ uint32_t store_tile(uint32_t tile_rows, __nv_bfloat16* gdst, const uint32_t* lo, const uint32_t* hi, int lane) {
    const int r = lane & 15;
#pragma unroll
    for (int b = 0; b < 4; b++)
        stsm4(tile_rows + r * 128 + (((2 * b + (lane >> 4)) ^ (r & 7)) << 4), lo[2 * b], hi[2 * b], lo[2 * b + 1], hi[2 * b + 1]);
    __syncwarp();
    uint32_t ack = 0;
#pragma unroll
    for (int i = 0; i < 4; i++) {
        const int rr = 4 * i + (lane >> 3);
        const uint4 v = lds128(tile_rows + rr * 128 + (((lane & 7) ^ (rr & 7)) << 4));
        stg128(gdst + rr * DM + (lane & 7) * 8, v.x, v.y, v.z, v.w);
    }
    if (ACK) {
#pragma unroll
        for (int i = 0; i < 4; i++) ack |= readback(gdst + (4 * i + (lane >> 3)) * DM + (lane & 7) * 8);
    }
    return ack;
}

template <bool NORM>
__device__ __forceinline__ void feature_map(const uint32_t* a, const uint32_t* wb, float c0, float c1, uint32_t* plus, uint32_t* minus, float* rs) {
    float p[8];
    mma16816_z(p, a, wb[0], wb[1]);
    mma16816_z(p + 4, a, wb[2], wb[3]);
    const uint32_t P0 = pack_bf16(p[0], p[2]), P1 = pack_bf16(p[1], p[3]), P2 = pack_bf16(p[4], p[6]), P3 = pack_bf16(p[5], p[7]);
    uint32_t mx = max2(max2(P0, P1), max2(P2, P3)), mn = min2(min2(P0, P1), min2(P2, P3));
#pragma unroll
    for (int s = 1; s <= 2; s <<= 1) {
        mx = max2(mx, __shfl_xor_sync(0xffffffffu, mx, s));
        mn = min2(mn, __shfl_xor_sync(0xffffffffu, mn, s));
    }
    const float mx0 = bf_lo(mx) * c0, mx1 = bf_hi(mx) * c1, mn0 = bf_lo(mn) * c0, mn1 = bf_hi(mn) * c1;
    p[0] = bf_lo(P0); p[2] = bf_hi(P0); p[1] = bf_lo(P1); p[3] = bf_hi(P1);
    p[4] = bf_lo(P2); p[6] = bf_hi(P2); p[5] = bf_lo(P3); p[7] = bf_hi(P3);
    float ep[8], em[8];
#pragma unroll
    for (int i = 0; i < 8; i++) {
        const bool r1 = (i & 2);
        ep[i] = ex2(fmaf(p[i], r1 ? c1 : c0, r1 ? -mx1 : -mx0));
        em[i] = ex2(fmaf(p[i], r1 ? -c1 : -c0, r1 ? mn1 : mn0));
    }
    float sp[4], sm[4];
#pragma unroll
    for (int i = 0; i < 4; i++) { plus[i] = pack_bf16(ep[2 * i], ep[2 * i + 1]); minus[i] = pack_bf16(em[2 * i], em[2 * i + 1]); }
    mma16816_z(sp, plus, 0x3f803f80u, 0x3f803f80u);
    mma16816_z(sm, minus, 0x3f803f80u, 0x3f803f80u);
    rs[0] = rcp(sp[0]); rs[1] = rcp(sp[2]); rs[2] = rcp(sm[0]); rs[3] = rcp(sm[2]);
    if (NORM) {
#pragma unroll
        for (int i = 0; i < 4; i++) {
            plus[i] = pack_bf16(ep[2 * i] * rs[i & 1], ep[2 * i + 1] * rs[i & 1]);
            minus[i] = pack_bf16(em[2 * i] * rs[2 + (i & 1)], em[2 * i + 1] * rs[2 + (i & 1)]);
        }
    }
}

template <bool SCALE>
__device__ __forceinline__ void ln_frag(const float* acc, uint32_t cs_addr, float rs0, float nm0, float rs1, float nm1, uint32_t* a) {
    const float2 c0 = lds_f2(cs_addr), c1 = lds_f2(cs_addr + 32);
    const float s0 = SCALE ? rs0 : 1.f, s1 = SCALE ? rs1 : 1.f;
    a[0] = pack_bf16(fmaf(nm0, c0.x, acc[0]) * s0, fmaf(nm0, c0.y, acc[1]) * s0);
    a[1] = pack_bf16(fmaf(nm1, c0.x, acc[2]) * s1, fmaf(nm1, c0.y, acc[3]) * s1);
    a[2] = pack_bf16(fmaf(nm0, c1.x, acc[4]) * s0, fmaf(nm0, c1.y, acc[5]) * s0);
    a[3] = pack_bf16(fmaf(nm1, c1.x, acc[6]) * s1, fmaf(nm1, c1.y, acc[7]) * s1);
}

template <int UP>
__device__ __forceinline__ uint32_t hh_pair(const float* ag, float4 cs, float nmean) {
    const float g0 = fmaf(nmean, cs.x, ag[0]), g1 = fmaf(nmean, cs.y, ag[1]);
    const float u0 = fmaf(nmean, cs.z, ag[UP]), u1 = fmaf(nmean, cs.w, ag[UP + 1]);
    return pack_bf16(g0 * u0, g1 * u1);
}
template <int UP, int NTP>
__device__ __forceinline__ void hh_stage(const float* acc, uint32_t cs3, float nm0, float nm1, uint32_t stg, int lane) {
#pragma unroll
    for (int tp = 0; tp < NTP; tp++) {
        const float4 c0 = lds_f4(cs3 + tp * 128), c1 = lds_f4(cs3 + tp * 128 + 64);
        stsm4(stg + (lane & 15) * 128 + (((2 * tp + (lane >> 4)) ^ (lane & 7)) << 4), hh_pair<UP>(acc + 8 * tp, c0, nm0),
              hh_pair<UP>(acc + 8 * tp + 2, c0, nm1), hh_pair<UP>(acc + 8 * tp + 4, c1, nm0), hh_pair<UP>(acc + 8 * tp + 6, c1, nm1));
    }
    fence_async_smem();
    __syncwarp();
}

struct Ring {
    int slot; uint32_t phase;
    __device__ __forceinline__ void adv() { if (++slot == NB) { slot = 0; phase ^= 1; } }
};

__global__ void __launch_bounds__(NTHREADS, 1) fused_kernel(const __grid_constant__ Params P) {
    extern __shared__ __align__(1024) uint8_t smem_raw[];
    const uint32_t sb = smem_u32(smem_raw);
    const int tid = threadIdx.x, lane = tid & 31;
    const int warp = __shfl_sync(0xffffffffu, tid >> 5, 0);
    unsigned role = blockIdx.x;
    if (P.use_smid) asm volatile("mov.u32 %0, %%smid;" : "=r"(role));
    role = P.role[role];
    const int m = role >> 3, j = role & 7;
    const bool helper = role >= 128;

    TL(0, tid == 0); TLG(0, tid == 0);
    float* const acc_j = g_acc + j * ACC_SIZE;
    unsigned* const cnt_j = g_cnt + j * 32;

    if (__builtin_expect(warp >= 8, 1)) {
        asm volatile("setmaxnreg.dec.sync.aligned.u32 72;");
        if (elect_one()) {
            if (warp == 8) {
                if (!helper) {
#pragma unroll
                    for (int i = 0; i < NB; i++) mbar_init(sb + BAR_FULLB + 8 * i, 1);
#pragma unroll
                    for (int i = 0; i < 2; i++) {
                        mbar_expect_tx(sb + BAR_FULLB + 8 * i, SLOT);
                        tma3d(sb + OFF_B + i * SLOT, &P.twkv, sb + BAR_FULLB + 8 * i, 64 * j, 64 * i, 1);
                    }
                }
            } else if (warp == 9) {
#pragma unroll
                for (int i = 0; i < 8; i++) mbar_init(sb + BAR_FULLA + 8 * i, 1);
#pragma unroll
                for (int i = 0; i < 2; i++) {
                    mbar_expect_tx(sb + BAR_FULLA + 8 * i, SLOT);
                    tma2d(sb + OFF_A + i * SLOT, helper ? &P.twq : &P.tx, sb + BAR_FULLA + 8 * i, helper ? DM + 128 * j : 64 * i, 128 * (helper ? i : m));
                }
            } else if (warp == 10) {
#pragma unroll
                for (int i = 0; i < 7; i++) mbar_init(sb + BAR_CS1 + 8 * i, i == 1 ? 96 : (i < 4 ? 32 : 8));
                trap_if_gt(sb & 1023, 0);
            } else {
#pragma unroll
                for (int i = 0; i < 14; i++) mbar_init(sb + (i < 8 ? BAR_EMPTYA : BAR_EMPTYB - 64) + 8 * i, 8);
            }
        }
        __syncwarp();
        const unsigned epoch = ld_relaxed(&g_epoch);
        bar_sync(0, NTHREADS);
        if (helper) {
            if (warp == 8) {
                if (elect_one()) {
#pragma unroll 1
                    for (int i = 2; i < 72; i++) {
                        const uint32_t full = sb + BAR_FULLA + 8 * (i & 7), dst = sb + OFF_A + (i & 7) * SLOT;
                        mbar_wait(sb + BAR_EMPTYA + 8 * (i & 7), ((i >> 3) & 1) ^ 1);
                        mbar_expect_tx(full, SLOT);
                        if (i < 24) {
                            tma2d(dst, &P.twq, full, (i < 16 ? DM + 64 * (i & 8) : 0) + 128 * j + 16 * (i & 4), 128 * (i & 3));
                        } else {
                            const int u = (i >> 3) - 3, c0 = 176 * (2 * j + (u & 1)) + 64 * (u >> 1);
                            tma2d(dst, &P.twg, full, c0, 64 * (i & 7));
                            tma2d(dst + 8192, &P.twu, full, c0, 64 * (i & 7));
                        }
                    }
                    prefetch_l2(P.wd + (size_t)j * 176128, 352256);
                }
            } else if (warp == 9) {
                wait_count_warp(g_cnt + (lane & 7) * 32, epoch * 128);
            }
            return;
        }
        if (warp == 8) {
            if (elect_one()) {
                if (m >= 3 && m < 8)
                    asm volatile("cp.async.bulk.prefetch.tensor.3d.L2.global [%0, {%1, %2, %3}];" ::"l"(&P.twkv), "r"(64 * j), "r"(64 * m), "r"(1) : "memory");
                if (j >= 3)
                    asm volatile("cp.async.bulk.prefetch.tensor.2d.L2.global [%0, {%1, %2}];" ::"l"(&P.tx), "r"(64 * j), "r"(128 * m) : "memory");
                Ring r{2, 0};
#pragma unroll 1
                for (int i = 2; i < 56; i++) {
                    const uint32_t full = sb + BAR_FULLB + 8 * r.slot, dst = sb + OFF_B + r.slot * SLOT;
                    mbar_wait(sb + BAR_EMPTYB + 8 * r.slot, r.phase ^ 1);
                    if (i >= 8 && i < 12) {
                        mbar_arrive(full);
                    } else {
                        if (i >= AHEAD && i < 6) mbar_wait(full - 8 * AHEAD, 0);
                        mbar_expect_tx(full, SLOT);
                        if (i < 8) {
                            tma3d(dst, &P.twkv, full, 64 * j, 64 * i, 1);
                        } else if (i < 20) {
                            tma2d(dst, i < 16 ? &P.twq : &P.two, full, 64 * j, 128 * (i & 3));
                        } else if (i < 36) {
                            tma3d(dst, &P.twg2, full, 176 * j, 32 * (i - 20), 0);
                            tma3d(dst + 8192, &P.twu2, full, 176 * j, 32 * (i - 20), 0);
                        } else if (i < 44) {
                            tma2d(dst, &P.twg, full, 176 * j + 128, 64 * (i - 36));
                            tma2d(dst + 8192, &P.twu, full, 176 * j + 128, 64 * (i - 36));
                        } else {
                            const int c = (i - 44) >> 2, jj = (i & 3) * 2;
                            tma2d(dst, &P.twd, full, 64 * j, 176 * jj + 64 * c);
                            tma2d(dst + 8192, &P.twd, full, 64 * j, 176 * (jj + 1) + 64 * c);
                        }
                    }
                    r.adv();
                }
            }
            return;
        }
        if (warp == 9) {
            if (elect_one()) {
#pragma unroll 1
                for (int i = 2; i < 8; i++) {
                    if (i >= AHEAD + 1) mbar_wait(sb + BAR_FULLA + 8 * (i - AHEAD - 1), 0);
                    mbar_expect_tx(sb + BAR_FULLA + 8 * i, SLOT);
                    tma2d(sb + OFF_A + i * SLOT, &P.tx, sb + BAR_FULLA + 8 * i, 64 * i, 128 * m);
                }
#pragma unroll 1
                for (int i = 1; i < 12; i++) prefetch_tmap(&P.tx + i);
#pragma unroll 1
                for (int r = 1; r < 6; r++) {
                    const CUtensorMap* tm = &P.tx + min(r, 3);
                    const int cstep = r < 3 ? 64 : 192, cbase = r < 3 ? 0 : 64 * (r - 3), skip = r < 3 ? j : 8;
                    wait_count(g_flag + (m * 5 + r - 1) * 32, epoch * (r < 3 ? 64 : 8));
                    TL(64 + r, true);
#pragma unroll 1
                    for (int t = 0; t < 8; t++) {
                        if (t == skip) continue;
                        mbar_wait(sb + BAR_EMPTYA + 8 * t, (r - 1) & 1);
                        mbar_expect_tx(sb + BAR_FULLA + 8 * t, SLOT);
                        tma2d(sb + OFF_A + t * SLOT, tm, sb + BAR_FULLA + 8 * t, cbase + cstep * t, 128 * m);
                    }
                }
            }
            return;
        }
        const int a = warp - 10;
        {
            const int row = 16 * j + 8 * a + (lane >> 2);
            const uint32_t ra = sb + OFF_A + row * 128;
            float sh = 0.f, s0 = 0.f, s1 = 0.f, q0 = 0.f, q1 = 0.f;
#pragma unroll 1
            for (int kt = 0; kt < 8; kt++) {
                mbar_wait(sb + BAR_FULLA + 8 * kt, 0);
                if (kt == 0) sh = bf_lo(lds128(ra + ((row & 7) << 4)).x);
#pragma unroll
                for (int i = 0; i < 2; i++) {
                    const uint4 v = lds128(ra + kt * SLOT + (((2 * (lane & 3) + i) ^ (row & 7)) << 4));
                    const uint32_t ww[4] = {v.x, v.y, v.z, v.w};
#pragma unroll
                    for (int e = 0; e < 4; e++) {
                        const float d0 = bf_lo(ww[e]) - sh, d1 = bf_hi(ww[e]) - sh;
                        s0 += d0; q0 = fmaf(d0, d0, q0);
                        s1 += d1; q1 = fmaf(d1, d1, q1);
                    }
                }
            }
            s0 += s1; q0 += q1;
#pragma unroll
            for (int o = 1; o <= 2; o <<= 1) { s0 += __shfl_xor_sync(0xffffffffu, s0, o); q0 += __shfl_xor_sync(0xffffffffu, q0, o); }
            const float md = s0 * (1.f / DM);
            const float rs = rsqrtf(fmaxf(q0 * (1.f / DM) - md * md, 0.f) + 1e-5f);
            st_tagged_if(g_xstat + 2 * (128 * m + row), rs, -(sh + md), epoch, (lane & 3) == 0);
        }
        const unsigned long long* cs = g_cs + j * 768 + 2 * lane;
#pragma unroll 1
        for (int c = 0; c < (a ? 2 : 7); c++) {
            uint4 v;
            uint32_t it = 0;
            while (true) {
                v = ld_tagged(cs + (a ? 128 + 128 * c : (c ? 320 + 64 * c : 0)));
                if (!__any_sync(0xffffffffu, v.y != epoch || v.w != epoch)) break;
                __nanosleep(100);
                trap_if_gt(++it, 1u << 22);
            }
            sts64(a || !c ? sb + OFF_CS1 + (a ? 512 - 512 * c : 256) + 8 * lane : sb + OFF_CS3 + (32 * ((c - 1) >> 1) + lane) * 16 + 8 * ((c - 1) & 1), v.x, v.z);
            if (a || c == 0 || c == 6) mbar_arrive(sb + (a ? (c ? BAR_CSQ : BAR_CSV) : (c ? BAR_CS3 : BAR_CS1)));
        }
        {
            uint32_t it = 0;
            while (__any_sync(0xffffffffu, (int)(ld_acquire(g_flag + (m * 5 + 1) * 32) - epoch * 64) < 0)) {
                __nanosleep(500);
                trap_if_gt(++it, 1u << 22);
            }
        }
#pragma unroll 1
        for (int rr = 0; rr < 2; rr++) {
            const int row = 64 * rr + 32 * a + lane;
            const float* sp = g_hstat + (1024 * m + row) * 2;
            float2 v[8];
#pragma unroll
            for (int i = 0; i < 8; i++) v[i] = ld_l2_f2(sp + 256 * i);
            float mean = 0.f;
#pragma unroll
            for (int i = 0; i < 8; i++) mean += v[i].x;
            mean *= 0.125f;
            float m2 = 0.f, dv = 0.f;
#pragma unroll
            for (int i = 0; i < 8; i++) { m2 += v[i].y; dv = fmaf(v[i].x - mean, v[i].x - mean, dv); }
            sts_f2(sb + OFF_CS1 + row * 8, -mean, __fdividef(1.f, fmaf(dv, 64.f, m2) * (1.f / DM) + 1e-5f));
        }
        mbar_arrive(sb + BAR_CS3);
#pragma unroll 1
        for (int c = a; c < 3; c += 2) {
            const int slot = c == 2 ? 1 : 4 + c;
            mbar_wait(sb + BAR_STG + 8 * c, 0);
            if (elect_one()) {
                tma_store2d(&P.thh, sb + OFF_B + slot * SLOT, 192 * j + 64 * c, 128 * m);
                asm volatile("cp.async.bulk.wait_group.read 0;" ::: "memory");
                mbar_arrive_n_if(sb + BAR_EMPTYB + 8 * slot, 8, true);
                asm volatile("cp.async.bulk.wait_group 0;" ::: "memory");
            }
            __syncwarp();
            TL(60 + c, lane == 0);
            uint32_t ack = 0;
#pragma unroll
            for (int i = 0; i < 4; i++) ack |= readback(g_hh + (size_t)(128 * m + 32 * i + lane) * FFP + 192 * j + 64 * c);
            signal_after(g_flag + (m * 5 + 2 + c) * 32, ack, P.zero, lane == 0);
            TL(54 + c, lane == 0);
        }
        return;
    }
    const unsigned epoch = ld_relaxed(&g_epoch);
    uint32_t wraw[16];
    if (!helper) {
        const uint32_t* wp = reinterpret_cast<const uint32_t*>(P.wphi) + (4 * j) * 128 + (lane & 3) * 16 + (lane >> 2);
#pragma unroll
        for (int i = 0; i < 16; i++)
            asm volatile("ld.global.nc.u32 %0, [%1];" : "=r"(wraw[i]) : "l"(wp + (i >> 2) * 128 + ((i >> 1) & 1) * 64 + (i & 1) * 8));
    }
    asm volatile("setmaxnreg.inc.sync.aligned.u32 216;");
    bar_sync(0, NTHREADS);
    if (helper) {
        if (warp < 4) {
            sts128(sb + OFF_B + 16 * tid, 0x3f803f80u, 0x3f803f80u, 0x3f803f80u, 0x3f803f80u);
            for (int i = tid; i < 2 * ACC_SIZE / 4; i += 128) stg128(g_acc + 2 * j * ACC_SIZE + 4 * i, 0, 0, 0, 0);
            fence_async_smem();
            fence_gpu();
            bar_sync(1, 128);
            float acc[8];
            int i = 0;
#pragma unroll 1
            for (int job = 0; job < 12; job++) {
                const int n = job < 6 ? 4 : 8;
#pragma unroll 1
                for (int t = 0; t < n; t++, i++) {
                    mbar_wait(sb + BAR_FULLA + 8 * (i & 7), (i >> 3) & 1);
                    wg_fence();
#pragma unroll
                    for (int k = 0; k < 8; k++)
                        wgmma_n8_tt(acc + (k & 4), desc_lo(sb + OFF_A) + (i & 7) * (SLOT >> 4) + 128 * k, desc_lo(sb + OFF_B), (t | (k & 3)) != 0);
                    wg_commit();
                    wg_wait<1>();
                    mbar_arrive_n_if(sb + BAR_EMPTYA + 8 * ((i + 7) & 7), 2, lane == 0 && i > 0);
                }
                wg_wait<0>();
                fence_acc<8>(acc);
                const int q = lane & 3;
                const float lo = (q & 1) ? acc[2] : acc[0], hi = (q & 1) ? acc[6] : acc[4];
                const float v = job < 6 ? lo + hi : ((q & 2) ? hi : lo);
                unsigned long long* dst = g_cs + ((2 * j + (job & 1)) * 6 + (job >> 1)) * 128 + (q >> 1) * 64 + 16 * warp + 8 * (q & 1) + (lane >> 2);
                asm volatile("st.relaxed.gpu.global.b64 [%0], %1;" ::"l"(dst), "l"(((unsigned long long)epoch << 32) | __float_as_uint(v)) : "memory");
            }
        }
        return;
    }
    {
        const int w = warp >> 2, wv = warp & 3, g = lane >> 2, q = lane & 3;
        const int row_w = 128 * m + 16 * warp;
        const uint32_t sa = sb + OFF_A + w * 8192;
        const desc_t dA = desc_lo(sa), dB = desc_lo(sb + OFF_B);
        unsigned* const flag_m = g_flag + m * 160;
        const bool l0 = lane == 0;
        Ring rg{0, 0};
        int prev = 0;

        uint32_t wb[16];
        constexpr float L2E = 1.4426950408889634f;
        uint32_t fp[16], fm[16];
        float fr[16];
        float rs0, nm0, rs1, nm1;
        uint32_t kv_ack[8];
        {
            float acc[64];
#pragma unroll 1
            for (int kt = 0; kt < 8; kt++) {
                mbar_waitc(sb + BAR_FULLA + 8 * kt, 0);
                mbar_waitc(sb + BAR_FULLB + 8 * rg.slot, rg.phase);
                const desc_t da = dA + kt * (SLOT >> 4), db = dB + rg.slot * (SLOT >> 4);
                wg_fence();
#pragma unroll
                for (int k = 0; k < 4; k++) wgmma_n128(acc, da + 2 * k, db + 128 * k, (kt | k) != 0);
                wg_commit();
                wg_wait<1>();
                mbar_arrive_if(sb + BAR_EMPTYB + 8 * prev, l0 && kt > 0);
                prev = rg.slot; rg.adv();
            }
            {
                uint4 a, b;
                uint32_t it = 0;
                do {
                    a = ld_tagged_rlx(g_xstat + 2 * (row_w + g));
                    b = ld_tagged_rlx(g_xstat + 2 * (row_w + g + 8));
                    trap_if_gt(++it, 1u << 22);
                } while (__any_sync(0xffffffffu, a.y != epoch || a.w != epoch || b.y != epoch || b.w != epoch));
                rs0 = __uint_as_float(a.x); nm0 = __uint_as_float(a.z); rs1 = __uint_as_float(b.x); nm1 = __uint_as_float(b.z);
            }
#pragma unroll
            for (int i = 0; i < 8; i++) {
                wb[(i >> 1) * 4 + (i & 1)] = __byte_perm(wraw[2 * i], wraw[2 * i + 1], 0x5410);
                wb[(i >> 1) * 4 + 2 + (i & 1)] = __byte_perm(wraw[2 * i], wraw[2 * i + 1], 0x7632);
            }
            TL(17, tid == 0);
            mbar_waitc(sb + BAR_CS1, 0);
            wg_wait<0>();
            fence_acc<64>(acc);
            mbar_arrive_if(sb + BAR_EMPTYB + 8 * prev, l0);
            TL(2, tid == 0);
#pragma unroll
            for (int i = 2; i < 6; i++) mbar_waitc(sb + BAR_FULLB + 8 * i, 1);
            const int lrow = 16 * warp + (lane & 15), ch = lane >> 4, sw = lane & 7;
            const uint32_t st = sb + OFF_B + 2 * SLOT + lrow * 128;
            uint32_t ka[16];
#pragma unroll
            for (int hh = 0; hh < 4; hh++)
                ln_frag<false>(acc + 8 * hh, sb + OFF_CS1 + (64 + 16 * hh + 2 * q) * 4, rs0, nm0, rs1, nm1, ka + 4 * hh);
#pragma unroll
            for (int hh = 0; hh < 4; hh++) feature_map<true>(ka + 4 * hh, wb + 4 * hh, rs0 * L2E, rs1 * L2E, fp + 4 * hh, fm + 4 * hh, fr);
#pragma unroll
            for (int hh = 0; hh < 4; hh++) {
                stsm4(st + (hh >> 1) * SLOT + (((4 * (hh & 1) + ch) ^ sw) << 4), fp[4 * hh], fp[4 * hh + 1], fp[4 * hh + 2], fp[4 * hh + 3]);
                stsm4(st + (hh >> 1) * SLOT + (((4 * (hh & 1) + 2 + ch) ^ sw) << 4), fm[4 * hh], fm[4 * hh + 1], fm[4 * hh + 2], fm[4 * hh + 3]);
            }
            mbar_waitc(sb + BAR_CSV, 0);
#pragma unroll
            for (int hh = 0; hh < 4; hh++) {
                uint32_t a[4];
                ln_frag<true>(acc + 32 + 8 * hh, sb + OFF_CS1 + (128 + 16 * hh + 2 * q) * 4, rs0, nm0, rs1, nm1, a);
                stsm4(st + (2 + (hh >> 1)) * SLOT + (((2 * (hh & 1) + ch) ^ sw) << 4), a[0], a[1], a[2], a[3]);
            }
            stsm4(st + (2 + ch) * SLOT + ((4 ^ sw) << 4), 0x3f803f80u, 0x3f803f80u, 0x3f803f80u, 0x3f803f80u);
            fence_async_smem();
            bar_sync(1, 256);
            float kvd[20];
            wg_fence();
#pragma unroll
            for (int k = 0; k < 8; k++)
                wgmma_n40_tt(kvd, dB + (2 + w) * (SLOT >> 4) + 128 * k, dB + (4 + w) * (SLOT >> 4) + 128 * k, k != 0);
            wg_commit();
            wg_wait<0>();
            fence_acc<20>(kvd);
            const bool h1 = wv >= 2;
            const int f = 16 * warp + g;
            float* kvp = acc_j + ACC_KV + f * 16 + 2 * q;
            kv_ack[0] = kv_ack[5] = kv_ack[6] = kv_ack[7] = atom_f32x2(kvp, h1 ? kvd[8] : kvd[0], h1 ? kvd[9] : kvd[1]);
            kv_ack[1] = atom_f32x2(kvp + 128, h1 ? kvd[10] : kvd[2], h1 ? kvd[11] : kvd[3]);
            kv_ack[2] = atom_f32x2(kvp + 8, h1 ? kvd[12] : kvd[4], h1 ? kvd[13] : kvd[5]);
            kv_ack[3] = atom_f32x2(kvp + 136, h1 ? kvd[14] : kvd[6], h1 ? kvd[15] : kvd[7]);
            kv_ack[4] = atom_f32_if(acc_j + ACC_Z + f + 8 * (q & 1), q ? kvd[18] : kvd[16], q < 2);
            mbar_arrive_if(sb + BAR_EMPTYB + 8 * (2 + (lane & 3)), lane < 4);
            TL(3, tid == 0);
        }
        uint32_t res_lo[8], res_hi[8];
        const uint32_t own_rows = sb + OFF_A + j * SLOT + warp * 2048;
        {
            float acc[32];
            rg.slot = 0; rg.phase = 0;
#pragma unroll 1
            for (int b = 0; b < 4; b++) {
                mbar_waitc(sb + BAR_FULLB + 8 * rg.slot, rg.phase);
                const desc_t da = dA + b * (2 * SLOT >> 4), db = dB + rg.slot * (SLOT >> 4);
                wg_fence();
#pragma unroll
                for (int k = 0; k < 8; k++) wgmma_n64(acc, da + (k >> 2) * (SLOT >> 4) + (k & 3) * 2, db + 128 * k, (b | k) != 0);
                wg_commit();
                wg_wait<1>();
                mbar_arrive_if(sb + BAR_EMPTYB + 8 * prev, l0 && b > 0);
                if (b == 1) { signal_late(cnt_j, kv_ack, P.zero, l0); TL(19, tid == 0); }
                prev = rg.slot; rg.adv();
            }
            wg_wait<0>();
            fence_acc<32>(acc);
            mbar_arrive_if(sb + BAR_EMPTYB + 8 * prev, l0);
            mbar_arrive_if(sb + BAR_EMPTYA + 8 * (lane & 7), lane < 8 && (lane | 1) != (j | 1));
            TL(4, tid == 0);
            mbar_waitc(sb + BAR_CSQ, 0);
            uint32_t qa[16];
#pragma unroll
            for (int hh = 0; hh < 4; hh++)
                ln_frag<false>(acc + 8 * hh, sb + OFF_CS1 + (16 * hh + 2 * q) * 4, rs0, nm0, rs1, nm1, qa + 4 * hh);
#pragma unroll
            for (int hh = 0; hh < 4; hh++) feature_map<false>(qa + 4 * hh, wb + 4 * hh, rs0 * L2E, rs1 * L2E, fp + 4 * hh, fm + 4 * hh, fr + 4 * hh);
#pragma unroll
            for (int b = 0; b < 4; b++)
                ldsm4(own_rows + (lane & 15) * 128 + (((2 * b + (lane >> 4)) ^ (lane & 7)) << 4),
                      res_lo[2 * b], res_hi[2 * b], res_lo[2 * b + 1], res_hi[2 * b + 1]);
            if (warp == 0) wait_count_warp(cnt_j, epoch * 128);
            TL(6, tid == 0);
            bar_sync(1, 256);
            const uint32_t kvs = sb + OFF_A + (j ^ 1) * SLOT;
            {
                const float4 a0 = ld_l2_f4(acc_j + ACC_KV + 4 * tid), a1 = ld_l2_f4(acc_j + ACC_KV + 4 * (tid + 256));
                const float zz = ld_l2_f(acc_j + ACC_Z + (tid & 127));
                sts64(kvs + (tid >> 2) * 48 + (tid & 3) * 8, pack_bf16(a0.x, a0.y), pack_bf16(a0.z, a0.w));
                sts64(kvs + ((tid >> 2) + 64) * 48 + (tid & 3) * 8, pack_bf16(a1.x, a1.y), pack_bf16(a1.z, a1.w));
                const uint32_t z2 = pack_bf16(zz, zz);
                sts64(kvs + (tid & 127) * 48 + 32 + w * 8, z2, z2);
            }
            bar_sync(1, 256);
            uint32_t o_lo[8], o_hi[8];
#pragma unroll
            for (int hh = 0; hh < 4; hh++) {
                uint32_t b[8], zb[4];
                const uint32_t base = kvs + hh * 32 * 48;
                ldsm4t(base + (lane & 15) * 48 + (lane >> 4) * 16, b[0], b[1], b[2], b[3]);
                ldsm4t(base + (16 + (lane & 15)) * 48 + (lane >> 4) * 16, b[4], b[5], b[6], b[7]);
                ldsm4t(base + lane * 48 + 32, zb[0], zb[1], zb[2], zb[3]);
                float n0[4], n1[4], dn[4], m0[4], m1[4], dm[4];
                mma16816_z(n0, fp + 4 * hh, b[0], b[1]); mma16816_z(n1, fp + 4 * hh, b[2], b[3]); mma16816_z(dn, fp + 4 * hh, zb[0], zb[1]);
                mma16816_z(m0, fm + 4 * hh, b[4], b[5]); mma16816_z(m1, fm + 4 * hh, b[6], b[7]); mma16816_z(dm, fm + 4 * hh, zb[2], zb[3]);
                const float* r = fr + 4 * hh;
                const float i0 = rcp(fmaf(dn[0], r[0], fmaf(dm[0], r[2], 1e-6f))), i1 = rcp(fmaf(dn[2], r[1], fmaf(dm[2], r[3], 1e-6f)));
                const float p0 = r[0] * i0, q0 = r[2] * i0, p1 = r[1] * i1, q1 = r[3] * i1;
                o_lo[2 * hh] = pack_bf16(fmaf(n0[0], p0, m0[0] * q0), fmaf(n0[1], p0, m0[1] * q0));
                o_hi[2 * hh] = pack_bf16(fmaf(n0[2], p1, m0[2] * q1), fmaf(n0[3], p1, m0[3] * q1));
                o_lo[2 * hh + 1] = pack_bf16(fmaf(n1[0], p0, m1[0] * q0), fmaf(n1[1], p0, m1[1] * q0));
                o_hi[2 * hh + 1] = pack_bf16(fmaf(n1[2], p1, m1[2] * q1), fmaf(n1[3], p1, m1[3] * q1));
            }
            const uint32_t ack = store_tile<true>(own_rows, g_o + (size_t)row_w * DM + 64 * j, o_lo, o_hi, lane);
            fence_async_smem();
            signal_after(flag_m, ack, P.zero, l0);
            mbar_arrive_if(sb + BAR_EMPTYA + 8 * (j ^ 1), l0);
            TL(7, tid == 0);
        }
        {
            float acc[32];
#pragma unroll
            for (int t = 0; t < 8; t++) {
                acc[4 * t] = bf_lo(res_lo[t]); acc[4 * t + 1] = bf_hi(res_lo[t]);
                acc[4 * t + 2] = bf_lo(res_hi[t]); acc[4 * t + 3] = bf_hi(res_hi[t]);
            }
            fence_acc<32>(acc);
#pragma unroll 1
            for (int kp = 0; kp < 4; kp++) {
                mbar_waitc(sb + BAR_FULLB + 8 * rg.slot, rg.phase);
#pragma unroll
                for (int hf = 0; hf < 2; hf++) {
                    const int kt = 2 * kp + hf;
                    mbar_waitc(sb + BAR_FULLA + 8 * kt, kt != j);
                    TL(8, kt == 0 && tid == 0);
                    const desc_t da = dA + kp * (2 * SLOT >> 4), db = dB + rg.slot * (SLOT >> 4);
                    wg_fence();
#pragma unroll
                    for (int k = 0; k < 4; k++) wgmma_n64(acc, da + hf * (SLOT >> 4) + 2 * k, db + (hf * 4 + k) * 128, 1);
                    wg_commit();
                    wg_wait<1>();
                    mbar_arrive_if(sb + BAR_EMPTYA + 8 * ((kt + 7) & 7), l0 && kt > 0 && kt - 1 != j);
                    if (hf == 0) mbar_arrive_if(sb + BAR_EMPTYB + 8 * prev, l0 && kt > 0);
                }
                prev = rg.slot; rg.adv();
            }
            wg_wait<0>();
            fence_acc<32>(acc);
            mbar_arrive_if(sb + BAR_EMPTYA + 8 * 7, l0 && j != 7);
            mbar_arrive_if(sb + BAR_EMPTYB + 8 * prev, l0);
            TL(9, tid == 0);
            float s0 = 0.f, s1 = 0.f;
#pragma unroll
            for (int t = 0; t < 8; t++) {
                res_lo[t] = pack_bf16(acc[4 * t], acc[4 * t + 1]);
                res_hi[t] = pack_bf16(acc[4 * t + 2], acc[4 * t + 3]);
                s0 += acc[4 * t] + acc[4 * t + 1];
                s1 += acc[4 * t + 2] + acc[4 * t + 3];
            }
            uint32_t ack = store_tile<true>(own_rows, g_h + (size_t)row_w * DM + 64 * j, res_lo, res_hi, lane);
            s0 += __shfl_xor_sync(0xffffffffu, s0, 1); s1 += __shfl_xor_sync(0xffffffffu, s1, 1);
            s0 += __shfl_xor_sync(0xffffffffu, s0, 2); s1 += __shfl_xor_sync(0xffffffffu, s1, 2);
            const float mu0 = s0 * (1.f / 64), mu1 = s1 * (1.f / 64);
            float q0 = 0.f, q1 = 0.f;
#pragma unroll
            for (int t = 0; t < 8; t++) {
                float d;
                d = acc[4 * t] - mu0; q0 = fmaf(d, d, q0);
                d = acc[4 * t + 1] - mu0; q0 = fmaf(d, d, q0);
                d = acc[4 * t + 2] - mu1; q1 = fmaf(d, d, q1);
                d = acc[4 * t + 3] - mu1; q1 = fmaf(d, d, q1);
            }
            q0 += __shfl_xor_sync(0xffffffffu, q0, 1); q1 += __shfl_xor_sync(0xffffffffu, q1, 1);
            q0 += __shfl_xor_sync(0xffffffffu, q0, 2); q1 += __shfl_xor_sync(0xffffffffu, q1, 2);
            stg_f2_if(g_hstat + (role * 128 + 16 * warp + g + 8 * (q & 1)) * 2, q ? mu1 : mu0, q ? q1 : q0, q < 2);
            ack |= readback(g_hstat + (role * 128 + 16 * warp + g + 8 * (q & 1)) * 2);
            fence_async_smem();
            signal_after(flag_m + 32, ack, P.zero, l0);
            TL(10, tid == 0);
        }
        {
            const uint32_t cs3 = sb + OFF_CS3 + q * 16;
            float nm0, nm1;
            {
                float acc[128];
                const desc_t dB4 = dB - (256ull << 16);
#pragma unroll 1
                for (int i = 0; i < 16; i++) {
                    mbar_waitc(sb + BAR_FULLA + 8 * (i >> 1), 0);
                    mbar_waitc(sb + BAR_FULLB + 8 * rg.slot, rg.phase);
                    TL(44, tid == 0 && i == 2);
                    const desc_t da = dA + (i >> 1) * (SLOT >> 4) + (i & 1) * 4, db = dB4 + rg.slot * (SLOT >> 4);
                    wg_fence();
                    wgmma_n256(acc, da, db, i != 0);
                    wgmma_n256(acc, da + 2, db + 128, 1);
                    wg_commit();
                    wg_wait<1>();
                    mbar_arrive_if(sb + BAR_EMPTYB + 8 * prev, l0 && i > 0 && i < 15);
                    prev = rg.slot; rg.adv();
                }
                mbar_waitc(sb + BAR_CS3, 0);
                nm0 = lds_f2(sb + OFF_CS1 + (16 * warp + g) * 8).x; nm1 = lds_f2(sb + OFF_CS1 + (16 * warp + g + 8) * 8).x;
                wg_wait<0>();
                fence_acc<128>(acc);
                TL(11, tid == 0);
                bar_sync(1, 256);
                hh_stage<64, 4>(acc, cs3, nm0, nm1, sb + OFF_B + 4 * SLOT + warp * 2048, lane);
                mbar_arrive_if(sb + BAR_STG, l0);
                hh_stage<64, 4>(acc + 32, cs3 + 512, nm0, nm1, sb + OFF_B + 5 * SLOT + warp * 2048, lane);
                mbar_arrive_if(sb + BAR_STG + 8, l0);
                TL(50, tid == 0);
            }
            {
                float acc[56];
#pragma unroll 1
                for (int kt = 0; kt < 8; kt++) {
                    mbar_waitc(sb + BAR_FULLB + 8 * rg.slot, rg.phase);
                    const desc_t da = dA + kt * (SLOT >> 4), db = dB + rg.slot * (SLOT >> 4);
                    wg_fence();
#pragma unroll
                    for (int k = 0; k < 4; k++) wgmma_n112(acc, da + 2 * k, db + 128 * k, (kt | k) != 0);
                    wg_commit();
                    wg_wait<1>();
                    mbar_arrive_if(sb + BAR_EMPTYB + 8 * prev, l0 && kt > 0);
                    mbar_arrive_if(sb + BAR_EMPTYA + 8 * ((kt + 7) & 7), l0 && kt > 0);
                    prev = rg.slot; rg.adv();
                }
                wg_wait<0>();
                fence_acc<56>(acc);
                mbar_arrive_if(sb + BAR_EMPTYA + 8 * 7, l0);
                TL(13, tid == 0);
                bar_sync(1, 256);
                hh_stage<32, 3>(acc, cs3 + 1024, nm0, nm1, sb + OFF_B + 1 * SLOT + warp * 2048, lane);
                mbar_arrive_if(sb + BAR_STG + 16, l0);
                TL(52, tid == 0);
            }
        }
        {
            float acc[64];
            const desc_t dA0 = desc_lo(sb + OFF_A);
#define KT_P4(I, NK)                                                                                        \
    do {                                                                                                    \
        const int s_ = (2 * (I) + w) & 7;                                                                   \
        mbar_waitc(sb + BAR_FULLB + 8 * rg.slot, rg.phase);                                                 \
        mbar_waitc(sb + BAR_FULLA + 8 * s_, (((I) >> 2) + 1) & 1);                                          \
        TL(30 + (I), tid == 0);                                                                             \
        const desc_t dh_ = dA0 + s_ * (SLOT >> 4), dw_ = dB + rg.slot * (SLOT >> 4) + w * 512;              \
        wg_fence();                                                                                         \
        _Pragma("unroll") for (int k = 0; k < (NK); k++) wgmma_n128_tn(acc, dw_ + 128 * k, dh_ + 2 * k, ((I) | k) != 0); \
        wg_commit();                                                                                        \
        wg_wait<1>();                                                                                       \
        mbar_arrive_n_if(sb + BAR_EMPTYA + 8 * ((s_ + 6) & 7), 2, l0 && (I) > 0);                           \
        mbar_arrive_if(sb + BAR_EMPTYB + 8 * prev, l0 && (I) > 0);                                          \
        prev = rg.slot; rg.adv();                                                                           \
    } while (0)
#pragma unroll 1
            for (int i = 0; i < 8; i++) KT_P4(i, 4);
#pragma unroll 1
            for (int i = 8; i < 12; i++) KT_P4(i, 3);
            const uint32_t tile = sb + OFF_A + w * SLOT;
#pragma unroll
            for (int b = 0; b < 4; b++)
                stsm4(tile + (16 * wv + (lane & 15)) * 128 + (((2 * b + (lane >> 4)) ^ (lane & 7)) << 4),
                      res_lo[2 * b], res_hi[2 * b], res_lo[2 * b + 1], res_hi[2 * b + 1]);
            wg_wait<0>();
            fence_acc<64>(acc);
            TL(15, tid == 0);
            const uint32_t xch = sb + OFF_A + 2 * SLOT + (tid & 127) * 16;
            if (w) {
#pragma unroll
                for (int t = 0; t < 8; t++) {
                    sts128(xch + SLOT + t * 2048, __float_as_uint(acc[4 * t]), __float_as_uint(acc[4 * t + 1]),
                           __float_as_uint(acc[4 * t + 2]), __float_as_uint(acc[4 * t + 3]));
                }
#pragma unroll
                for (int t = 0; t < 32; t++) acc[t] = acc[32 + t];
            } else {
#pragma unroll
                for (int t = 0; t < 8; t++)
                    sts128(xch + t * 2048, __float_as_uint(acc[32 + 4 * t]), __float_as_uint(acc[33 + 4 * t]),
                           __float_as_uint(acc[34 + 4 * t]), __float_as_uint(acc[35 + 4 * t]));
            }
            bar_sync(1, 256);
            const uint32_t blk = tile + ((lane & 7) + (lane >> 4) * 8) * 128 + (((2 * wv + ((lane >> 3) & 1)) ^ (lane & 7)) << 4);
#pragma unroll
            for (int tp = 0; tp < 4; tp++) {
                uint32_t hr[4];
                ldsm4t(blk + tp * 2048, hr[0], hr[1], hr[2], hr[3]);
#pragma unroll
                for (int u = 0; u < 2; u++) {
                    const int t = 2 * tp + u;
                    const float4 o = lds_f4(xch + (w ^ 1) * SLOT + t * 2048);
                    const float4 st = lds_f4(sb + OFF_CS1 + (64 * w + 8 * t + 2 * q) * 8);
                    hr[2 * u] = pack_bf16(fmaf(acc[4 * t] + o.x, st.y, bf_lo(hr[2 * u])), fmaf(acc[4 * t + 1] + o.y, st.w, bf_hi(hr[2 * u])));
                    hr[2 * u + 1] = pack_bf16(fmaf(acc[4 * t + 2] + o.z, st.y, bf_lo(hr[2 * u + 1])), fmaf(acc[4 * t + 3] + o.w, st.w, bf_hi(hr[2 * u + 1])));
                }
                stsm4t(blk + tp * 2048, hr[0], hr[1], hr[2], hr[3]);
            }
            bar_sync(2 + w, 128);
#pragma unroll
            for (int i = 0; i < 4; i++) {
                const int rr = 16 * wv + 4 * i + (lane >> 3);
                const uint4 v = lds128(tile + rr * 128 + (((lane & 7) ^ (rr & 7)) << 4));
                stg128(P.out + (size_t)(128 * m + 64 * w + rr) * DM + 64 * j + (lane & 7) * 8, v.x, v.y, v.z, v.w);
            }
            if (tid == 0 && role == 0) g_epoch = epoch + 1;
            TL(16, tid == 0); TLG(1, tid == 0);
        }
    }
}

typedef CUresult (*EncodeFn)(CUtensorMap*, CUtensorMapDataType, cuuint32_t, void*, const cuuint64_t*, const cuuint64_t*,
                             const cuuint32_t*, const cuuint32_t*, CUtensorMapInterleave, CUtensorMapSwizzle,
                             CUtensorMapL2promotion, CUtensorMapFloatOOBfill);

static void make_map2d(EncodeFn enc, CUtensorMap* tm, const void* base, uint64_t cols, uint64_t rows, uint64_t pitch_elems,
                       uint32_t box_rows) {
    cuuint64_t gd[2] = {cols, rows};
    cuuint64_t gs[1] = {pitch_elems * 2};
    cuuint32_t bd[2] = {64, box_rows};
    cuuint32_t es[2] = {1, 1};
    enc(tm, CU_TENSOR_MAP_DATA_TYPE_BFLOAT16, 2, const_cast<void*>(base), gd, gs, bd, es, CU_TENSOR_MAP_INTERLEAVE_NONE,
        CU_TENSOR_MAP_SWIZZLE_128B, CU_TENSOR_MAP_L2_PROMOTION_L2_256B, CU_TENSOR_MAP_FLOAT_OOB_FILL_NONE);
}

}

extern "C" void kernel_launch(void* const* d_in, const int* in_sizes, int n_in, void* d_out, int out_size) {
    using namespace hk;
    (void)in_sizes; (void)n_in; (void)out_size;
    static EncodeFn enc = nullptr;
    static void *po = nullptr, *ph = nullptr, *phh = nullptr;
    static int std_layout = 0;
    if (!enc) {
        void* fn = nullptr;
        cudaDriverEntryPointQueryResult qr;
        cudaGetDriverEntryPoint("cuTensorMapEncodeTiled", &fn, cudaEnableDefault, &qr);
        enc = (EncodeFn)fn;
        cudaGetSymbolAddress(&po, g_o);
        cudaGetSymbolAddress(&ph, g_h);
        cudaGetSymbolAddress(&phh, g_hh);
        cudaFuncSetAttribute(fused_kernel, cudaFuncAttributeMaxDynamicSharedMemorySize, SMEM_BYTES);
        int dev = 0, sms = 0;
        cudaGetDevice(&dev);
        cudaDeviceGetAttribute(&sms, cudaDevAttrMultiProcessorCount, dev);
        cudaFuncSetAttribute(fused_kernel, cudaFuncAttributeNonPortableClusterSizeAllowed, 1);
        const int sizes[3] = {8, 9, 16}, want[3] = {15, 9, 7};
        bool ok = sms == NCTA;
        for (int i = 0; i < 3 && ok; i++) {
            cudaLaunchConfig_t cfg = {};
            cfg.gridDim = dim3(sizes[i] * 8); cfg.blockDim = dim3(NTHREADS); cfg.dynamicSmemBytes = SMEM_BYTES;
            cudaLaunchAttribute at;
            at.id = cudaLaunchAttributeClusterDimension;
            at.val.clusterDim.x = sizes[i]; at.val.clusterDim.y = 1; at.val.clusterDim.z = 1;
            cfg.attrs = &at; cfg.numAttrs = 1;
            int n = 0;
            ok = cudaOccupancyMaxActiveClusters(&n, fused_kernel, &cfg) == cudaSuccess && n == want[i];
        }
        (void)cudaGetLastError();
        std_layout = ok ? 1 : 0;
    }
    Params P;
    const __nv_bfloat16* x = (const __nv_bfloat16*)d_in[0];
    P.x = x;
    P.wqkv = (const __nv_bfloat16*)d_in[1];
    P.wphi = (const __nv_bfloat16*)d_in[2];
    P.wo = (const __nv_bfloat16*)d_in[3];
    P.wg = (const __nv_bfloat16*)d_in[5];
    P.wu = (const __nv_bfloat16*)d_in[6];
    P.wd = (const __nv_bfloat16*)d_in[7];
    P.out = (__nv_bfloat16*)d_out;
    P.use_smid = std_layout;
    P.zero = 0;
    for (int i = 0; i < NCTA; i++) {
        int role = i < 4 ? 128 + i : i - 4;
        if (std_layout) {
            const int tpc = i >> 1, odd = i & 1;
            if (tpc < 32) role = (tpc & 7) * 8 + (tpc >> 3) * 2 + odd;
            else if (tpc < 60) role = (8 + (tpc - 32) % 7) * 8 + ((tpc - 32) / 7) * 2 + odd;
            else if (tpc < 62) role = 128 + (tpc - 60) * 2 + odd;
            else role = 15 * 8 + (tpc - 62) * 2 + odd;
        }
        P.role[i] = (unsigned char)role;
    }
    make_map2d(enc, &P.tx, x, DM, SEQ, DM, 128);
    make_map2d(enc, &P.to, po, DM, SEQ, DM, 128);
    make_map2d(enc, &P.th, ph, DM, SEQ, DM, 128);
    make_map2d(enc, &P.thh, phh, FFP, SEQ, FFP, 128);
    make_map2d(enc, &P.twq, P.wqkv, 3 * DM, DM, 3 * DM, 128);
    make_map2d(enc, &P.two, P.wo, DM, DM, DM, 128);
    make_map2d(enc, &P.twg, P.wg, FF, DM, FF, 64);
    make_map2d(enc, &P.twu, P.wu, FF, DM, FF, 64);
    make_map2d(enc, &P.twd, P.wd, DM, FF, DM, 64);
    {
        cuuint64_t gd[3] = {(cuuint64_t)DM, (cuuint64_t)DM, 3};
        cuuint64_t gs[2] = {(cuuint64_t)3 * DM * 2, (cuuint64_t)DM * 2};
        cuuint32_t bd[3] = {64, 64, 2};
        cuuint32_t es[3] = {1, 1, 1};
        enc(&P.twkv, CU_TENSOR_MAP_DATA_TYPE_BFLOAT16, 3, const_cast<__nv_bfloat16*>(P.wqkv), gd, gs, bd, es,
            CU_TENSOR_MAP_INTERLEAVE_NONE, CU_TENSOR_MAP_SWIZZLE_128B, CU_TENSOR_MAP_L2_PROMOTION_L2_256B,
            CU_TENSOR_MAP_FLOAT_OOB_FILL_NONE);
    }
    for (int i = 0; i < 2; i++) {
        cuuint64_t gd[3] = {(cuuint64_t)FF - 64, (cuuint64_t)DM, 2};
        cuuint64_t gs[2] = {(cuuint64_t)FF * 2, 128};
        cuuint32_t bd[3] = {64, 32, 2};
        cuuint32_t es[3] = {1, 1, 1};
        enc(i ? &P.twu2 : &P.twg2, CU_TENSOR_MAP_DATA_TYPE_BFLOAT16, 3, const_cast<__nv_bfloat16*>(i ? P.wu : P.wg), gd, gs, bd, es,
            CU_TENSOR_MAP_INTERLEAVE_NONE, CU_TENSOR_MAP_SWIZZLE_128B, CU_TENSOR_MAP_L2_PROMOTION_L2_256B,
            CU_TENSOR_MAP_FLOAT_OOB_FILL_NONE);
    }
    fused_kernel<<<NCTA, NTHREADS, SMEM_BYTES>>>(P);
}
```

```cpp
#include <cuda_runtime.h>
#include <cuda_bf16.h>
#include <cuda.h>
#include <stdint.h>

namespace hk {

constexpr int SEQ = 2048, DM = 512, FF = 1376, FFP = 1536;
constexpr int NCTA = 132;
constexpr int NTHREADS = 384;
constexpr uint32_t SLOT = 16384;
constexpr uint32_t OFF_A = 0, OFF_B = 8 * SLOT, OFF_MISC = 14 * SLOT;
constexpr uint32_t BAR_FULLA = OFF_MISC + 0, BAR_EMPTYA = OFF_MISC + 64, BAR_FULLB = OFF_MISC + 128,
                   BAR_EMPTYB = OFF_MISC + 176, BAR_CS1 = OFF_MISC + 224, BAR_CS3 = OFF_MISC + 232,
                   BAR_CSQ = OFF_MISC + 240, BAR_CSV = OFF_MISC + 248,
                   BAR_STG = OFF_MISC + 256,
                   BAR_HST = OFF_MISC + 280;
constexpr uint32_t OFF_CS1 = OFF_MISC + 384;
constexpr uint32_t OFF_CS3 = OFF_CS1 + 1024;
constexpr uint32_t SMEM_BYTES = OFF_CS3 + 1536;
constexpr int NB = 6;
constexpr int AHEAD = 3;

constexpr int ACC_KV = 0, ACC_Z = 2048, ACC_SIZE = 2176;

__device__ __align__(1024) uint4 g_o[16 * 8 * 4 * 256];
__device__ __align__(1024) uint4 g_h[16 * 8 * 8 * 128];
__device__ __align__(1024) __nv_bfloat16 g_hh[SEQ * FFP];
__device__ __align__(128) unsigned long long g_hstat[SEQ * 16];
__device__ __align__(128) unsigned long long g_xstat[SEQ * 2];
__device__ __align__(128) float g_acc[8 * ACC_SIZE];
__device__ __align__(128) unsigned g_cnt[8 * 32];
__device__ __align__(128) unsigned long long g_cs[8 * 6 * 128];
__device__ __align__(128) unsigned g_flag[16 * 3 * 32];
__device__ unsigned g_epoch = 1;

#define TL(i, pred) do {} while (0)
#define TLG(i, pred) do {} while (0)

struct Params {
    CUtensorMap tx, thh, twkv, twq, two, twg, twu, twd, twg2, twu2;
    const __nv_bfloat16 *x, *wqkv, *wphi, *wo, *wg, *wu, *wd;
    __nv_bfloat16* out;
    int use_smid;
    unsigned zero;
    unsigned char role[NCTA];
};

__device__ __forceinline__ uint32_t smem_u32(const void* p) { return (uint32_t)__cvta_generic_to_shared(p); }
__device__ __forceinline__ void mbar_init(uint32_t bar, uint32_t cnt) {
    asm volatile("mbarrier.init.shared::cta.b64 [%0], %1;" ::"r"(bar), "r"(cnt) : "memory");
}
__device__ __forceinline__ void mbar_expect_tx(uint32_t bar, uint32_t bytes) {
    asm volatile("mbarrier.arrive.expect_tx.shared::cta.b64 _, [%0], %1;" ::"r"(bar), "r"(bytes) : "memory");
}
__device__ __forceinline__ void mbar_arrive(uint32_t bar) {
    asm volatile("mbarrier.arrive.shared::cta.b64 _, [%0];" ::"r"(bar) : "memory");
}
__device__ __forceinline__ void mbar_arrive_if(uint32_t bar, bool pred) {
    asm volatile("{.reg .pred p; setp.ne.u32 p, %1, 0; @p mbarrier.arrive.shared::cta.b64 _, [%0];}" ::"r"(bar), "r"((uint32_t)pred) : "memory");
}
__device__ __forceinline__ bool mbar_try(uint32_t bar, uint32_t parity) {
    uint32_t ok;
    asm volatile("{.reg .pred p; mbarrier.try_wait.parity.shared::cta.b64 p, [%1], %2; selp.u32 %0,1,0,p;}"
                 : "=r"(ok) : "r"(bar), "r"(parity) : "memory");
    return ok;
}
__device__ __forceinline__ bool mbar_test(uint32_t bar, uint32_t parity) {
    uint32_t ok;
    asm volatile("{.reg .pred p; mbarrier.test_wait.parity.shared::cta.b64 p, [%1], %2; selp.u32 %0,1,0,p;}"
                 : "=r"(ok) : "r"(bar), "r"(parity) : "memory");
    return ok;
}
__device__ __forceinline__ void trap_if_gt(uint32_t v, uint32_t lim) {
    asm volatile("{.reg .pred p; setp.gt.u32 p, %0, %1; @p trap;}" ::"r"(v), "r"(lim));
}
__device__ __forceinline__ void mbar_wait(uint32_t bar, uint32_t parity) {
    asm volatile("{\n"
                 ".reg .pred P1, P2;\n"
                 ".reg .u32 c;\n"
                 "mov.u32 c, 0;\n"
                 "LAB_WAIT:\n"
                 "mbarrier.try_wait.parity.shared::cta.b64 P1, [%0], %1;\n"
                 "@P1 bra LAB_DONE;\n"
                 "add.u32 c, c, 1;\n"
                 "setp.gt.u32 P2, c, 4194304;\n"
                 "@P2 trap;\n"
                 "bra LAB_WAIT;\n"
                 "LAB_DONE:\n"
                 "}" ::"r"(bar), "r"(parity) : "memory");
}
__device__ __forceinline__ void mbar_waitc(uint32_t bar, uint32_t parity) {
    asm volatile("{\n"
                 ".reg .pred P1;\n"
                 "LAB_WAIT:\n"
                 "mbarrier.try_wait.parity.shared::cta.b64 P1, [%0], %1;\n"
                 "@!P1 bra LAB_WAIT;\n"
                 "}" ::"r"(bar), "r"(parity) : "memory");
}
__device__ __forceinline__ void tma2d(uint32_t dst, const CUtensorMap* tm, uint32_t bar, int c0, int c1) {
    asm volatile("cp.async.bulk.tensor.2d.shared::cluster.global.mbarrier::complete_tx::bytes [%0], [%1, {%3, %4}], [%2];"
                 ::"r"(dst), "l"(tm), "r"(bar), "r"(c0), "r"(c1) : "memory");
}
__device__ __forceinline__ void tma3d(uint32_t dst, const CUtensorMap* tm, uint32_t bar, int c0, int c1, int c2) {
    asm volatile("cp.async.bulk.tensor.3d.shared::cluster.global.mbarrier::complete_tx::bytes [%0], [%1, {%3, %4, %5}], [%2];"
                 ::"r"(dst), "l"(tm), "r"(bar), "r"(c0), "r"(c1), "r"(c2) : "memory");
}
__device__ __forceinline__ bool elect_one() {
    uint32_t ok;
    asm volatile("{.reg .pred p; elect.sync _|p, 0xffffffff; selp.u32 %0, 1, 0, p;}" : "=r"(ok));
    return ok;
}
__device__ __forceinline__ void prefetch_tmap(const CUtensorMap* tm) {
    asm volatile("prefetch.tensormap [%0];" ::"l"(tm) : "memory");
}
__device__ __forceinline__ void prefetch_l2(const void* p, uint32_t bytes) {
    asm volatile("cp.async.bulk.prefetch.L2.global [%0], %1;" ::"l"(p), "r"(bytes) : "memory");
}
__device__ __forceinline__ unsigned ld_acquire(const unsigned* p) {
    unsigned v; asm volatile("ld.acquire.gpu.global.u32 %0, [%1];" : "=r"(v) : "l"(p) : "memory"); return v;
}
__device__ __forceinline__ uint4 ld_acquire4(const unsigned* p) {
    uint4 v;
    asm volatile("ld.acquire.gpu.global.v4.u32 {%0,%1,%2,%3}, [%4];" : "=r"(v.x), "=r"(v.y), "=r"(v.z), "=r"(v.w) : "l"(p) : "memory");
    return v;
}
__device__ __forceinline__ unsigned ld_relaxed(const unsigned* p) {
    unsigned v; asm volatile("ld.relaxed.gpu.global.u32 %0, [%1];" : "=r"(v) : "l"(p)); return v;
}
__device__ __forceinline__ void st_relaxed(unsigned* p, unsigned v) {
    asm volatile("st.relaxed.gpu.global.u32 [%0], %1;" ::"l"(p), "r"(v) : "memory");
}
__device__ __forceinline__ void red_relaxed(unsigned* p, unsigned v) {
    asm volatile("red.relaxed.gpu.global.add.u32 [%0], %1;" ::"l"(p), "r"(v) : "memory");
}
__device__ __forceinline__ void fence_gpu() { asm volatile("fence.acq_rel.gpu;" ::: "memory"); }
__device__ __forceinline__ void fence_async_smem() { asm volatile("fence.proxy.async.shared::cta;" ::: "memory"); }
__device__ __forceinline__ void fence_async_global() { asm volatile("fence.proxy.async.global;" ::: "memory"); }
__device__ __forceinline__ void wait_count(const unsigned* p, unsigned target) {
    uint32_t it = 0;
    while ((int)(ld_acquire(p) - target) < 0) trap_if_gt(++it, 1u << 22);
}
__device__ __forceinline__ void wait_count_warp(const unsigned* p, unsigned target) {
    uint32_t it = 0;
    while (__any_sync(0xffffffffu, (int)(ld_acquire(p) - target) < 0)) trap_if_gt(++it, 1u << 22);
}
__device__ __forceinline__ void red_f32(float* p, float a) {
    asm volatile("red.relaxed.gpu.global.add.f32 [%0], %1;" ::"l"(p), "f"(a) : "memory");
}
__device__ __forceinline__ void red_f32x2(float* p, float a, float b) {
    asm volatile("red.relaxed.gpu.global.add.v2.f32 [%0], {%1, %2};" ::"l"(p), "f"(a), "f"(b) : "memory");
}
__device__ __forceinline__ void red_f32x4(float* p, float a, float b, float c, float d) {
    asm volatile("red.relaxed.gpu.global.add.v4.f32 [%0], {%1, %2, %3, %4};" ::"l"(p), "f"(a), "f"(b), "f"(c), "f"(d) : "memory");
}
__device__ __forceinline__ float4 ld_l2_f4(const float* p) {
    float4 v;
    asm volatile("ld.relaxed.gpu.global.v4.f32 {%0,%1,%2,%3}, [%4];" : "=f"(v.x), "=f"(v.y), "=f"(v.z), "=f"(v.w) : "l"(p) : "memory");
    return v;
}
__device__ __forceinline__ float2 ld_l2_f2(const float* p) {
    float2 v;
    asm volatile("ld.relaxed.gpu.global.v2.f32 {%0,%1}, [%2];" : "=f"(v.x), "=f"(v.y) : "l"(p) : "memory");
    return v;
}
__device__ __forceinline__ float ld_l2_f(const float* p) {
    float v;
    asm volatile("ld.relaxed.gpu.global.f32 %0, [%1];" : "=f"(v) : "l"(p) : "memory");
    return v;
}
__device__ __forceinline__ uint4 ldg_nc(const void* p) {
    uint4 v;
    asm volatile("ld.global.nc.L1::no_allocate.v4.u32 {%0,%1,%2,%3}, [%4];" : "=r"(v.x), "=r"(v.y), "=r"(v.z), "=r"(v.w) : "l"(p));
    return v;
}
__device__ __forceinline__ void stg128(void* p, uint32_t a, uint32_t b, uint32_t c, uint32_t d) {
    asm volatile("st.global.v4.u32 [%0], {%1,%2,%3,%4};" ::"l"(p), "r"(a), "r"(b), "r"(c), "r"(d) : "memory");
}
__device__ __forceinline__ uint4 lds128(uint32_t a) {
    uint4 v;
    asm volatile("ld.shared.v4.u32 {%0,%1,%2,%3}, [%4];" : "=r"(v.x), "=r"(v.y), "=r"(v.z), "=r"(v.w) : "r"(a) : "memory");
    return v;
}
__device__ __forceinline__ float2 lds_f2(uint32_t a) {
    float2 v;
    asm volatile("ld.shared.v2.f32 {%0,%1}, [%2];" : "=f"(v.x), "=f"(v.y) : "r"(a) : "memory");
    return v;
}
__device__ __forceinline__ void sts_f2(uint32_t a, float x, float y) {
    asm volatile("st.shared.v2.f32 [%0], {%1,%2};" ::"r"(a), "f"(x), "f"(y) : "memory");
}
__device__ __forceinline__ void sts64(uint32_t a, uint32_t x, uint32_t y) {
    asm volatile("st.shared.v2.u32 [%0], {%1,%2};" ::"r"(a), "r"(x), "r"(y) : "memory");
}
__device__ __forceinline__ void sts128(uint32_t a, uint32_t x, uint32_t y, uint32_t z, uint32_t w) {
    asm volatile("st.shared.v4.u32 [%0], {%1,%2,%3,%4};" ::"r"(a), "r"(x), "r"(y), "r"(z), "r"(w) : "memory");
}
__device__ __forceinline__ void stsm4(uint32_t a, uint32_t r0, uint32_t r1, uint32_t r2, uint32_t r3) {
    asm volatile("stmatrix.sync.aligned.m8n8.x4.shared.b16 [%0], {%1,%2,%3,%4};" ::"r"(a), "r"(r0), "r"(r1), "r"(r2), "r"(r3) : "memory");
}
__device__ __forceinline__ void stsm4t(uint32_t a, uint32_t r0, uint32_t r1, uint32_t r2, uint32_t r3) {
    asm volatile("stmatrix.sync.aligned.m8n8.x4.trans.shared.b16 [%0], {%1,%2,%3,%4};" ::"r"(a), "r"(r0), "r"(r1), "r"(r2), "r"(r3) : "memory");
}
__device__ __forceinline__ void tma_store2d(const CUtensorMap* tm, uint32_t src, int c0, int c1) {
    asm volatile("cp.async.bulk.tensor.2d.global.shared::cta.bulk_group [%0, {%2, %3}], [%1];" ::"l"(tm), "r"(src), "r"(c0), "r"(c1) : "memory");
    asm volatile("cp.async.bulk.commit_group;" ::: "memory");
}
__device__ __forceinline__ void ldsm4(uint32_t a, uint32_t& r0, uint32_t& r1, uint32_t& r2, uint32_t& r3) {
    asm volatile("ldmatrix.sync.aligned.m8n8.x4.shared.b16 {%0,%1,%2,%3}, [%4];" : "=r"(r0), "=r"(r1), "=r"(r2), "=r"(r3) : "r"(a) : "memory");
}
__device__ __forceinline__ void ldsm4t(uint32_t a, uint32_t& r0, uint32_t& r1, uint32_t& r2, uint32_t& r3) {
    asm volatile("ldmatrix.sync.aligned.m8n8.x4.trans.shared.b16 {%0,%1,%2,%3}, [%4];" : "=r"(r0), "=r"(r1), "=r"(r2), "=r"(r3) : "r"(a) : "memory");
}
__device__ __forceinline__ void mma16816(float* c, const uint32_t* a, uint32_t b0, uint32_t b1) {
    asm("mma.sync.aligned.m16n8k16.row.col.f32.bf16.bf16.f32 {%0,%1,%2,%3}, {%4,%5,%6,%7}, {%8,%9}, {%0,%1,%2,%3};"
                 : "+f"(c[0]), "+f"(c[1]), "+f"(c[2]), "+f"(c[3])
                 : "r"(a[0]), "r"(a[1]), "r"(a[2]), "r"(a[3]), "r"(b0), "r"(b1));
}
__device__ __forceinline__ uint32_t pack_bf16(float lo, float hi) {
    uint32_t r; asm("cvt.rn.bf16x2.f32 %0, %1, %2;" : "=r"(r) : "f"(hi), "f"(lo)); return r;
}
__device__ __forceinline__ float bf_lo(uint32_t w) { return __uint_as_float(w << 16); }
__device__ __forceinline__ float bf_hi(uint32_t w) { return __uint_as_float(w & 0xffff0000u); }
__device__ __forceinline__ float ex2(float x) { float r; asm("ex2.approx.ftz.f32 %0, %1;" : "=f"(r) : "f"(x)); return r; }
__device__ __forceinline__ float rcp(float x) { float r; asm("rcp.approx.ftz.f32 %0, %1;" : "=f"(r) : "f"(x)); return r; }
__device__ __forceinline__ void bar_sync(int id, int n) { asm volatile("bar.sync %0, %1;" ::"r"(id), "r"(n) : "memory"); }

typedef unsigned long long desc_t;
__device__ __forceinline__ desc_t desc_lo(uint32_t addr) { return (desc_t)(((addr & 0x3FFFF) >> 4) | (512u << 16)) | (0x40000040ull << 32); }
__device__ __forceinline__ void wg_fence() { asm volatile("wgmma.fence.sync.aligned;" ::: "memory"); }
__device__ __forceinline__ void wg_commit() { asm volatile("wgmma.commit_group.sync.aligned;" ::: "memory"); }
template <int N> __device__ __forceinline__ void wg_wait() { asm volatile("wgmma.wait_group.sync.aligned %0;" ::"n"(N) : "memory"); }
template <int N> __device__ __forceinline__ void fence_acc(float* d) {
#pragma unroll
    for (int i = 0; i < N; i++) asm volatile("" : "+f"(d[i])::"memory");
}
#define R4(o) "+f"(d[o + 0]), "+f"(d[o + 1]), "+f"(d[o + 2]), "+f"(d[o + 3])
#define R8(o) R4(o), R4(o + 4)
__device__ __forceinline__ void wgmma_n128(float* d, desc_t da, desc_t db, int sc) {
    asm volatile("{.reg .pred p; setp.ne.b32 p, %66, 0;\n"
                 "wgmma.mma_async.sync.aligned.m64n128k16.f32.bf16.bf16 {%0,%1,%2,%3,%4,%5,%6,%7,%8,%9,%10,%11,%12,%13,%14,%15,%16,%17,%18,%19,%20,%21,%22,%23,%24,%25,%26,%27,%28,%29,%30,%31,"
                 "%32,%33,%34,%35,%36,%37,%38,%39,%40,%41,%42,%43,%44,%45,%46,%47,%48,%49,%50,%51,%52,%53,%54,%55,%56,%57,%58,%59,%60,%61,%62,%63}, %64, %65, p, 1, 1, 0, 1;}"
                 : R8(0), R8(8), R8(16), R8(24), R8(32), R8(40), R8(48), R8(56)
                 : "l"(da), "l"(db), "r"(sc));
}
__device__ __forceinline__ void wgmma_n256(float* d, desc_t da, desc_t db, int sc) {
    asm volatile("{.reg .pred p; setp.ne.b32 p, %130, 0;\n"
                 "wgmma.mma_async.sync.aligned.m64n256k16.f32.bf16.bf16 {%0,%1,%2,%3,%4,%5,%6,%7,%8,%9,%10,%11,%12,%13,%14,%15,%16,%17,%18,%19,%20,%21,%22,%23,%24,%25,%26,%27,%28,%29,%30,%31,%32,%33,%34,%35,%36,%37,%38,%39,%40,%41,%42,%43,%44,%45,%46,%47,%48,%49,%50,%51,%52,%53,%54,%55,%56,%57,%58,%59,%60,%61,%62,%63,%64,%65,%66,%67,%68,%69,%70,%71,%72,%73,%74,%75,%76,%77,%78,%79,%80,%81,%82,%83,%84,%85,%86,%87,%88,%89,%90,%91,%92,%93,%94,%95,%96,%97,%98,%99,%100,%101,%102,%103,%104,%105,%106,%107,%108,%109,%110,%111,%112,%113,%114,%115,%116,%117,%118,%119,%120,%121,%122,%123,%124,%125,%126,%127}, %128, %129, p, 1, 1, 0, 1;}"
                 : R8(0), R8(8), R8(16), R8(24), R8(32), R8(40), R8(48), R8(56), R8(64), R8(72), R8(80), R8(88), R8(96), R8(104), R8(112), R8(120)
                 : "l"(da), "l"(db), "r"(sc));
}
__device__ __forceinline__ void wgmma_n112(float* d, desc_t da, desc_t db, int sc) {
    asm volatile("{.reg .pred p; setp.ne.b32 p, %58, 0;\n"
                 "wgmma.mma_async.sync.aligned.m64n112k16.f32.bf16.bf16 {%0,%1,%2,%3,%4,%5,%6,%7,%8,%9,%10,%11,%12,%13,%14,%15,%16,%17,%18,%19,%20,%21,%22,%23,%24,%25,%26,%27,%28,%29,%30,%31,%32,%33,%34,%35,%36,%37,%38,%39,%40,%41,%42,%43,%44,%45,%46,%47,%48,%49,%50,%51,%52,%53,%54,%55}, %56, %57, p, 1, 1, 0, 1;}"
                 : R8(0), R8(8), R8(16), R8(24), R8(32), R8(40), R8(48)
                 : "l"(da), "l"(db), "r"(sc));
}
__device__ __forceinline__ void wgmma_n128_tn(float* d, desc_t da, desc_t db, int sc) {
    asm volatile("{.reg .pred p; setp.ne.b32 p, %66, 0;\n"
                 "wgmma.mma_async.sync.aligned.m64n128k16.f32.bf16.bf16 {%0,%1,%2,%3,%4,%5,%6,%7,%8,%9,%10,%11,%12,%13,%14,%15,%16,%17,%18,%19,%20,%21,%22,%23,%24,%25,%26,%27,%28,%29,%30,%31,%32,%33,%34,%35,%36,%37,%38,%39,%40,%41,%42,%43,%44,%45,%46,%47,%48,%49,%50,%51,%52,%53,%54,%55,%56,%57,%58,%59,%60,%61,%62,%63}, %64, %65, p, 1, 1, 1, 0;}"
                 : R8(0), R8(8), R8(16), R8(24), R8(32), R8(40), R8(48), R8(56)
                 : "l"(da), "l"(db), "r"(sc));
}
__device__ __forceinline__ void wgmma_n64(float* d, desc_t da, desc_t db, int sc) {
    asm volatile("{.reg .pred p; setp.ne.b32 p, %34, 0;\n"
                 "wgmma.mma_async.sync.aligned.m64n64k16.f32.bf16.bf16 {%0,%1,%2,%3,%4,%5,%6,%7,%8,%9,%10,%11,%12,%13,%14,%15,%16,%17,%18,%19,%20,%21,%22,%23,%24,%25,%26,%27,%28,%29,%30,%31}, %32, %33, p, 1, 1, 0, 1;}"
                 : R8(0), R8(8), R8(16), R8(24)
                 : "l"(da), "l"(db), "r"(sc));
}
__device__ __forceinline__ void wgmma_n40_tt(float* d, desc_t da, desc_t db, int sc) {
    asm volatile("{.reg .pred p; setp.ne.b32 p, %22, 0;\n"
                 "wgmma.mma_async.sync.aligned.m64n40k16.f32.bf16.bf16 {%0,%1,%2,%3,%4,%5,%6,%7,%8,%9,%10,%11,%12,%13,%14,%15,%16,%17,%18,%19}, %20, %21, p, 1, 1, 1, 1;}"
                 : R8(0), R8(8), R4(16)
                 : "l"(da), "l"(db), "r"(sc));
}

__device__ __forceinline__ void wgmma_n8_tt(float* d, desc_t da, desc_t db, int sc) {
    asm volatile("{.reg .pred p; setp.ne.b32 p, %6, 0;\n"
                 "wgmma.mma_async.sync.aligned.m64n8k16.f32.bf16.bf16 {%0,%1,%2,%3}, %4, %5, p, 1, 1, 1, 1;}"
                 : R4(0)
                 : "l"(da), "l"(db), "r"(sc));
}

__device__ __forceinline__ uint32_t readback(const void* p) {
    uint32_t v; asm volatile("ld.relaxed.gpu.global.u32 %0, [%1];" : "=r"(v) : "l"(p) : "memory"); return v;
}
__device__ __forceinline__ uint32_t atom_f32x2(float* p, float a, float b) {
    float x, y;
    asm volatile("atom.relaxed.gpu.global.add.v2.f32 {%0,%1}, [%2], {%3,%4};" : "=f"(x), "=f"(y) : "l"(p), "f"(a), "f"(b) : "memory");
    return __float_as_uint(x);
}
__device__ __forceinline__ uint32_t atom_f32_if(float* p, float a, bool pred) {
    float x = 0.f;
    asm volatile("{.reg .pred p; setp.ne.u32 p, %3, 0; @p atom.relaxed.gpu.global.add.f32 %0, [%1], %2;}" : "+f"(x) : "l"(p), "f"(a), "r"((uint32_t)pred) : "memory");
    return __float_as_uint(x);
}
__device__ __forceinline__ void signal_after(unsigned* cnt, uint32_t ack, uint32_t zero, bool pred) {
    asm volatile("{.reg .pred p; setp.ne.u32 p, %2, 0; @p red.relaxed.gpu.global.add.u32 [%0], %1;}"
                 ::"l"(cnt), "r"((ack & zero) + 1), "r"((uint32_t)pred) : "memory");
}
__device__ __forceinline__ void signal_late(unsigned* cnt, const uint32_t* a, uint32_t zero, bool pred) {
    uint32_t v;
    asm volatile("{.reg .b32 t; lop3.b32 t, %1, %2, %3, 0xfe; lop3.b32 t, t, %4, %5, 0xfe; lop3.b32 t, t, %6, %7, 0xfe; or.b32 %0, t, %8;}"
                 : "=r"(v) : "r"(a[0]), "r"(a[1]), "r"(a[2]), "r"(a[3]), "r"(a[4]), "r"(a[5]), "r"(a[6]), "r"(a[7]));
    signal_after(cnt, v, zero, pred);
}
__device__ __forceinline__ void red_f32_if(float* p, float a, bool pred) {
    asm volatile("{.reg .pred p; setp.ne.u32 p, %2, 0; @p red.relaxed.gpu.global.add.f32 [%0], %1;}" ::"l"(p), "f"(a), "r"((uint32_t)pred) : "memory");
}
__device__ __forceinline__ void stg_f2_if(float* p, float a, float b, bool pred) {
    asm volatile("{.reg .pred p; setp.ne.u32 p, %3, 0; @p st.global.v2.f32 [%0], {%1,%2};}" ::"l"(p), "f"(a), "f"(b), "r"((uint32_t)pred) : "memory");
}
__device__ __forceinline__ void stg64(void* p, uint32_t a, uint32_t b) {
    asm volatile("st.global.v2.u32 [%0], {%1,%2};" ::"l"(p), "r"(a), "r"(b) : "memory");
}
__device__ __forceinline__ void mma16816_z(float* c, const uint32_t* a, uint32_t b0, uint32_t b1) {
    asm("mma.sync.aligned.m16n8k16.row.col.f32.bf16.bf16.f32 {%0,%1,%2,%3}, {%4,%5,%6,%7}, {%8,%9}, {%10,%10,%10,%10};"
                 : "=f"(c[0]), "=f"(c[1]), "=f"(c[2]), "=f"(c[3])
                 : "r"(a[0]), "r"(a[1]), "r"(a[2]), "r"(a[3]), "r"(b0), "r"(b1), "f"(0.f));
}
__device__ __forceinline__ uint32_t max2(uint32_t a, uint32_t b) { uint32_t r; asm("max.bf16x2 %0, %1, %2;" : "=r"(r) : "r"(a), "r"(b)); return r; }
__device__ __forceinline__ uint32_t min2(uint32_t a, uint32_t b) { uint32_t r; asm("min.bf16x2 %0, %1, %2;" : "=r"(r) : "r"(a), "r"(b)); return r; }
__device__ __forceinline__ void bar_arrive(int id, int n) { asm volatile("bar.arrive %0, %1;" ::"r"(id), "r"(n) : "memory"); }
__device__ __forceinline__ void mbar_arrive_n_if(uint32_t bar, uint32_t n, bool pred) {
    asm volatile("{.reg .pred p; setp.ne.u32 p, %1, 0; @p mbarrier.arrive.shared::cta.b64 _, [%0], %2;}" ::"r"(bar), "r"((uint32_t)pred), "r"(n) : "memory");
}
__device__ __forceinline__ float4 lds_f4(uint32_t a) {
    float4 v;
    asm volatile("ld.shared.v4.f32 {%0,%1,%2,%3}, [%4];" : "=f"(v.x), "=f"(v.y), "=f"(v.z), "=f"(v.w) : "r"(a) : "memory");
    return v;
}
__device__ __forceinline__ uint4 ld_tagged(const unsigned long long* p) {
    unsigned long long a, b;
    asm volatile("ld.acquire.gpu.global.v2.b64 {%0,%1}, [%2];" : "=l"(a), "=l"(b) : "l"(p) : "memory");
    return make_uint4((unsigned)a, (unsigned)(a >> 32), (unsigned)b, (unsigned)(b >> 32));
}
__device__ __forceinline__ uint4 ld_tagged_rlx(const unsigned long long* p) {
    unsigned long long a, b;
    asm volatile("ld.relaxed.gpu.global.v2.b64 {%0,%1}, [%2];" : "=l"(a), "=l"(b) : "l"(p) : "memory");
    return make_uint4((unsigned)a, (unsigned)(a >> 32), (unsigned)b, (unsigned)(b >> 32));
}
__device__ __forceinline__ void st_tagged_if(unsigned long long* p, float a, float b, unsigned tag, bool pred) {
    const unsigned long long t = (unsigned long long)tag << 32;
    asm volatile("{.reg .pred p; setp.ne.u32 p, %3, 0; @p st.relaxed.gpu.global.v2.b64 [%0], {%1,%2};}"
                 ::"l"(p), "l"(t | __float_as_uint(a)), "l"(t | __float_as_uint(b)), "r"((uint32_t)pred) : "memory");
}

__device__ __forceinline__ void ll_store(uint4* p, uint32_t a, uint32_t b, uint32_t c, uint32_t d) {
    a = a ? a : 0x8000u; c = c ? c : 0x8000u;
    asm volatile("{.reg .b64 x, y; mov.b64 x, {%1,%2}; mov.b64 y, {%3,%4}; st.relaxed.gpu.global.v2.b64 [%0], {x, y};}"
                 ::"l"(p), "r"(a), "r"(b), "r"(c), "r"(d) : "memory");
}
__device__ __forceinline__ void ll_load(const uint4* p, uint32_t* v) {
    asm volatile("{.reg .b64 x, y; ld.relaxed.gpu.global.v2.b64 {x, y}, [%4]; mov.b64 {%0,%1}, x; mov.b64 {%2,%3}, y;}"
                 : "=r"(v[0]), "=r"(v[1]), "=r"(v[2]), "=r"(v[3]) : "l"(p) : "memory");
}
template <int STRIDE>
__device__ __forceinline__ void ll_wait4(const uint4* p, uint32_t* v) {
    asm volatile("{\n"
                 ".reg .pred p; .reg .b32 a, b; .reg .b64 x, y;\n"
                 "LL_CHECK:\n"
                 "min.u32 a, %0, %2; min.u32 b, %4, %6; min.u32 a, a, %8; min.u32 b, b, %10; min.u32 a, a, %12; min.u32 b, b, %14; min.u32 a, a, b;\n"
                 "setp.eq.u32 p, a, 0; vote.sync.any.pred p, p, 0xffffffff;\n"
                 "@!p bra.uni LL_DONE;\n"
                 "ld.relaxed.gpu.global.v2.b64 {x, y}, [%16]; mov.b64 {%0,%1}, x; mov.b64 {%2,%3}, y;\n"
                 "ld.relaxed.gpu.global.v2.b64 {x, y}, [%16+%17]; mov.b64 {%4,%5}, x; mov.b64 {%6,%7}, y;\n"
                 "ld.relaxed.gpu.global.v2.b64 {x, y}, [%16+%18]; mov.b64 {%8,%9}, x; mov.b64 {%10,%11}, y;\n"
                 "ld.relaxed.gpu.global.v2.b64 {x, y}, [%16+%19]; mov.b64 {%12,%13}, x; mov.b64 {%14,%15}, y;\n"
                 "bra.uni LL_CHECK;\n"
                 "LL_DONE:\n"
                 "}"
                 : "+r"(v[0]), "+r"(v[1]), "+r"(v[2]), "+r"(v[3]), "+r"(v[4]), "+r"(v[5]), "+r"(v[6]), "+r"(v[7]),
                   "+r"(v[8]), "+r"(v[9]), "+r"(v[10]), "+r"(v[11]), "+r"(v[12]), "+r"(v[13]), "+r"(v[14]), "+r"(v[15])
                 : "l"(p), "n"(STRIDE * 16), "n"(STRIDE * 32), "n"(STRIDE * 48) : "memory");
}
__device__ __forceinline__ void wgmma_n64_rs(float* d, const uint32_t* a, desc_t db) {
    asm volatile("wgmma.mma_async.sync.aligned.m64n64k16.f32.bf16.bf16 {%0,%1,%2,%3,%4,%5,%6,%7,%8,%9,%10,%11,%12,%13,%14,%15,%16,%17,%18,%19,%20,%21,%22,%23,%24,%25,%26,%27,%28,%29,%30,%31}, {%32,%33,%34,%35}, %36, 1, 1, 1, 1;"
                 : R8(0), R8(8), R8(16), R8(24)
                 : "r"(a[0]), "r"(a[1]), "r"(a[2]), "r"(a[3]), "l"(db));
}

template <bool NORM>
__device__ __forceinline__ void feature_map(const uint32_t* a, const uint32_t* wb, float c0, float c1, uint32_t* plus, uint32_t* minus, float* rs) {
    float p[8];
    mma16816_z(p, a, wb[0], wb[1]);
    mma16816_z(p + 4, a, wb[2], wb[3]);
    const uint32_t P0 = pack_bf16(p[0], p[2]), P1 = pack_bf16(p[1], p[3]), P2 = pack_bf16(p[4], p[6]), P3 = pack_bf16(p[5], p[7]);
    uint32_t mx = max2(max2(P0, P1), max2(P2, P3)), mn = min2(min2(P0, P1), min2(P2, P3));
#pragma unroll
    for (int s = 1; s <= 2; s <<= 1) {
        mx = max2(mx, __shfl_xor_sync(0xffffffffu, mx, s));
        mn = min2(mn, __shfl_xor_sync(0xffffffffu, mn, s));
    }
    const float mx0 = bf_lo(mx) * c0, mx1 = bf_hi(mx) * c1, mn0 = bf_lo(mn) * c0, mn1 = bf_hi(mn) * c1;
    p[0] = bf_lo(P0); p[2] = bf_hi(P0); p[1] = bf_lo(P1); p[3] = bf_hi(P1);
    p[4] = bf_lo(P2); p[6] = bf_hi(P2); p[5] = bf_lo(P3); p[7] = bf_hi(P3);
    float ep[8], em[8];
#pragma unroll
    for (int i = 0; i < 8; i++) {
        const bool r1 = (i & 2);
        ep[i] = ex2(fmaf(p[i], r1 ? c1 : c0, r1 ? -mx1 : -mx0));
        em[i] = ex2(fmaf(p[i], r1 ? -c1 : -c0, r1 ? mn1 : mn0));
    }
    float sp[4], sm[4];
#pragma unroll
    for (int i = 0; i < 4; i++) { plus[i] = pack_bf16(ep[2 * i], ep[2 * i + 1]); minus[i] = pack_bf16(em[2 * i], em[2 * i + 1]); }
    mma16816_z(sp, plus, 0x3f803f80u, 0x3f803f80u);
    mma16816_z(sm, minus, 0x3f803f80u, 0x3f803f80u);
    rs[0] = rcp(sp[0]); rs[1] = rcp(sp[2]); rs[2] = rcp(sm[0]); rs[3] = rcp(sm[2]);
    if (NORM) {
#pragma unroll
        for (int i = 0; i < 4; i++) {
            plus[i] = pack_bf16(ep[2 * i] * rs[i & 1], ep[2 * i + 1] * rs[i & 1]);
            minus[i] = pack_bf16(em[2 * i] * rs[2 + (i & 1)], em[2 * i + 1] * rs[2 + (i & 1)]);
        }
    }
}

template <bool SCALE>
__device__ __forceinline__ void ln_frag(const float* acc, uint32_t cs_addr, float rs0, float nm0, float rs1, float nm1, uint32_t* a) {
    const float2 c0 = lds_f2(cs_addr), c1 = lds_f2(cs_addr + 32);
    const float s0 = SCALE ? rs0 : 1.f, s1 = SCALE ? rs1 : 1.f;
    a[0] = pack_bf16(fmaf(nm0, c0.x, acc[0]) * s0, fmaf(nm0, c0.y, acc[1]) * s0);
    a[1] = pack_bf16(fmaf(nm1, c0.x, acc[2]) * s1, fmaf(nm1, c0.y, acc[3]) * s1);
    a[2] = pack_bf16(fmaf(nm0, c1.x, acc[4]) * s0, fmaf(nm0, c1.y, acc[5]) * s0);
    a[3] = pack_bf16(fmaf(nm1, c1.x, acc[6]) * s1, fmaf(nm1, c1.y, acc[7]) * s1);
}

template <int UP>
__device__ __forceinline__ uint32_t hh_pair(const float* ag, float4 cs, float nmean) {
    const float g0 = fmaf(nmean, cs.x, ag[0]), g1 = fmaf(nmean, cs.y, ag[1]);
    const float u0 = fmaf(nmean, cs.z, ag[UP]), u1 = fmaf(nmean, cs.w, ag[UP + 1]);
    return pack_bf16(g0 * u0, g1 * u1);
}
template <int UP, int NTP>
__device__ __forceinline__ void hh_stage(const float* acc, uint32_t cs3, float nm0, float nm1, uint32_t stg, int lane) {
#pragma unroll
    for (int tp = 0; tp < NTP; tp++) {
        const float4 c0 = lds_f4(cs3 + tp * 128), c1 = lds_f4(cs3 + tp * 128 + 64);
        stsm4(stg + (lane & 15) * 128 + (((2 * tp + (lane >> 4)) ^ (lane & 7)) << 4), hh_pair<UP>(acc + 8 * tp, c0, nm0),
              hh_pair<UP>(acc + 8 * tp + 2, c0, nm1), hh_pair<UP>(acc + 8 * tp + 4, c1, nm0), hh_pair<UP>(acc + 8 * tp + 6, c1, nm1));
    }
    fence_async_smem();
    __syncwarp();
}

struct Ring {
    int slot; uint32_t phase;
    __device__ __forceinline__ void adv() { if (++slot == NB) { slot = 0; phase ^= 1; } }
};

__global__ void __launch_bounds__(NTHREADS, 1) fused_kernel(const __grid_constant__ Params P) {
    extern __shared__ __align__(1024) uint8_t smem_raw[];
    const uint32_t sb = smem_u32(smem_raw);
    const int tid = threadIdx.x, lane = tid & 31;
    const int warp = __shfl_sync(0xffffffffu, tid >> 5, 0);
    unsigned role = blockIdx.x;
    if (P.use_smid) asm volatile("mov.u32 %0, %%smid;" : "=r"(role));
    role = P.role[role];
    const int m = role >> 3, j = role & 7;
    const bool helper = role >= 128;

    TL(0, tid == 0); TLG(0, tid == 0);
    float* const acc_j = g_acc + j * ACC_SIZE;
    unsigned* const cnt_j = g_cnt + j * 32;

    if (__builtin_expect(warp >= 8, 1)) {
        asm volatile("setmaxnreg.dec.sync.aligned.u32 72;");
        if (elect_one()) {
            if (warp == 8) {
                if (!helper) {
#pragma unroll
                    for (int i = 0; i < NB; i++) mbar_init(sb + BAR_FULLB + 8 * i, 1);
#pragma unroll
                    for (int i = 0; i < 2; i++) {
                        mbar_expect_tx(sb + BAR_FULLB + 8 * i, SLOT);
                        tma3d(sb + OFF_B + i * SLOT, &P.twkv, sb + BAR_FULLB + 8 * i, 64 * j, 64 * i, 1);
                    }
                }
            } else if (warp == 9) {
#pragma unroll
                for (int i = 0; i < 8; i++) mbar_init(sb + BAR_FULLA + 8 * i, 1);
#pragma unroll
                for (int i = 0; i < 2; i++) {
                    mbar_expect_tx(sb + BAR_FULLA + 8 * i, SLOT);
                    tma2d(sb + OFF_A + i * SLOT, helper ? &P.twq : &P.tx, sb + BAR_FULLA + 8 * i, helper ? DM + 128 * j : 64 * i, 128 * (helper ? i : m));
                }
            } else if (warp == 10) {
#pragma unroll
                for (int i = 0; i < 8; i++) mbar_init(sb + BAR_CS1 + 8 * i, i == 1 ? 96 : (i < 4 ? 32 : 8));
                trap_if_gt(sb & 1023, 0);
            } else {
#pragma unroll
                for (int i = 0; i < 14; i++) mbar_init(sb + (i < 8 ? BAR_EMPTYA : BAR_EMPTYB - 64) + 8 * i, 8);
            }
        }
        __syncwarp();
        const unsigned epoch = ld_relaxed(&g_epoch);
        bar_sync(0, NTHREADS);
        if (helper) {
            if (warp == 8) {
                if (elect_one()) {
#pragma unroll 1
                    for (int i = 2; i < 72; i++) {
                        const uint32_t full = sb + BAR_FULLA + 8 * (i & 7), dst = sb + OFF_A + (i & 7) * SLOT;
                        mbar_wait(sb + BAR_EMPTYA + 8 * (i & 7), ((i >> 3) & 1) ^ 1);
                        mbar_expect_tx(full, SLOT);
                        if (i < 24) {
                            tma2d(dst, &P.twq, full, (i < 16 ? DM + 64 * (i & 8) : 0) + 128 * j + 16 * (i & 4), 128 * (i & 3));
                        } else {
                            const int u = (i >> 3) - 3, c0 = 176 * (2 * j + (u & 1)) + 64 * (u >> 1);
                            tma2d(dst, &P.twg, full, c0, 64 * (i & 7));
                            tma2d(dst + 8192, &P.twu, full, c0, 64 * (i & 7));
                        }
                    }
                    prefetch_l2(P.wd + (size_t)j * 176128, 352256);
                }
            } else if (warp == 9) {
                wait_count_warp(g_cnt + (lane & 7) * 32, epoch * 128);
            }
            return;
        }
        if (warp == 8) {
            if (elect_one()) {
                if (m >= 3 && m < 8)
                    asm volatile("cp.async.bulk.prefetch.tensor.3d.L2.global [%0, {%1, %2, %3}];" ::"l"(&P.twkv), "r"(64 * j), "r"(64 * m), "r"(1) : "memory");
                if (j >= 3)
                    asm volatile("cp.async.bulk.prefetch.tensor.2d.L2.global [%0, {%1, %2}];" ::"l"(&P.tx), "r"(64 * j), "r"(128 * m) : "memory");
                Ring r{2, 0};
#pragma unroll 1
                for (int i = 2; i < 56; i++) {
                    const uint32_t full = sb + BAR_FULLB + 8 * r.slot, dst = sb + OFF_B + r.slot * SLOT;
                    mbar_wait(sb + BAR_EMPTYB + 8 * r.slot, r.phase ^ 1);
                    if (i >= 8 && i < 12) {
                        mbar_arrive(full);
                    } else {
                        if (i >= AHEAD && i < 6) mbar_wait(full - 8 * AHEAD, 0);
                        mbar_expect_tx(full, SLOT);
                        if (i < 8) {
                            tma3d(dst, &P.twkv, full, 64 * j, 64 * i, 1);
                        } else if (i < 16) {
                            tma2d(dst, &P.twq, full, 64 * j, 128 * (i & 3));
                        } else if (i >= 20 && i < 36) {
                            const int k0 = 64 * ((j + ((i - 20) >> 1)) & 7) + 32 * (i & 1);
                            tma3d(dst, &P.twg2, full, 176 * j, k0, 0);
                            tma3d(dst + 8192, &P.twu2, full, 176 * j, k0, 0);
                        } else {
                            const int e = 2 * (i & 3);
                            const bool wo = i < 20, gu = !wo && i < 44;
                            const int c0 = gu ? 176 * j + 128 : 64 * j;
                            const int r0 = wo ? 64 * ((j + e) & 7) : (gu ? 64 * (i - 36) : 176 * e + 64 * ((i - 44) >> 2));
                            const int r1 = wo ? 64 * ((j + e + 1) & 7) : (gu ? r0 : r0 + 176);
                            tma2d(dst, wo ? &P.two : (gu ? &P.twg : &P.twd), full, c0, r0);
                            tma2d(dst + 8192, wo ? &P.two : (gu ? &P.twu : &P.twd), full, c0, r1);
                        }
                    }
                    r.adv();
                }
            }
            return;
        }
        if (warp == 9) {
            if (elect_one()) {
#pragma unroll 1
                for (int i = 2; i < 8; i++) {
                    if (i >= AHEAD + 1) mbar_wait(sb + BAR_FULLA + 8 * (i - AHEAD - 1), 0);
                    mbar_expect_tx(sb + BAR_FULLA + 8 * i, SLOT);
                    tma2d(sb + OFF_A + i * SLOT, &P.tx, sb + BAR_FULLA + 8 * i, 64 * i, 128 * m);
                }
#pragma unroll 1
                for (int i = 1; i < 10; i++) prefetch_tmap(&P.tx + i);
#pragma unroll 1
                for (int c = 0; c < 3; c++) {
                    mbar_wait(sb + BAR_EMPTYA, c & 1);
                    wait_count(g_flag + (m * 3 + c) * 32, epoch * 8);
                    TL(64 + c, true);
#pragma unroll 1
                    for (int t = 0; t < 8; t++) {
                        mbar_wait(sb + BAR_EMPTYA + 8 * t, c & 1);
                        mbar_expect_tx(sb + BAR_FULLA + 8 * t, SLOT);
                        tma2d(sb + OFF_A + t * SLOT, &P.thh, sb + BAR_FULLA + 8 * t, 64 * c + 192 * t, 128 * m);
                    }
                }
            }
            return;
        }
        const int a = warp - 10;
        {
            const int row = 16 * j + 8 * a + (lane >> 2);
            const uint32_t ra = sb + OFF_A + row * 128;
            float sh = 0.f, s0 = 0.f, s1 = 0.f, q0 = 0.f, q1 = 0.f;
#pragma unroll 1
            for (int kt = 0; kt < 8; kt++) {
                mbar_wait(sb + BAR_FULLA + 8 * kt, 0);
                if (kt == 0) sh = bf_lo(lds128(ra + ((row & 7) << 4)).x);
#pragma unroll
                for (int i = 0; i < 2; i++) {
                    const uint4 v = lds128(ra + kt * SLOT + (((2 * (lane & 3) + i) ^ (row & 7)) << 4));
                    const uint32_t ww[4] = {v.x, v.y, v.z, v.w};
#pragma unroll
                    for (int e = 0; e < 4; e++) {
                        const float d0 = bf_lo(ww[e]) - sh, d1 = bf_hi(ww[e]) - sh;
                        s0 += d0; q0 = fmaf(d0, d0, q0);
                        s1 += d1; q1 = fmaf(d1, d1, q1);
                    }
                }
            }
            s0 += s1; q0 += q1;
#pragma unroll
            for (int o = 1; o <= 2; o <<= 1) { s0 += __shfl_xor_sync(0xffffffffu, s0, o); q0 += __shfl_xor_sync(0xffffffffu, q0, o); }
            const float md = s0 * (1.f / DM);
            const float rs = rsqrtf(fmaxf(q0 * (1.f / DM) - md * md, 0.f) + 1e-5f);
            st_tagged_if(g_xstat + 2 * (128 * m + row), rs, -(sh + md), epoch, (lane & 3) == 0);
        }
        const unsigned long long* cs = g_cs + j * 768 + 2 * lane;
#pragma unroll 1
        for (int c = 0; c < (a ? 2 : 7); c++) {
            uint4 v;
            uint32_t it = 0;
            while (true) {
                v = ld_tagged(cs + (a ? 128 + 128 * c : (c ? 320 + 64 * c : 0)));
                if (!__any_sync(0xffffffffu, v.y != epoch || v.w != epoch)) break;
                __nanosleep(100);
                trap_if_gt(++it, 1u << 22);
            }
            sts64(a || !c ? sb + OFF_CS1 + (a ? 512 - 512 * c : 256) + 8 * lane : sb + OFF_CS3 + (32 * ((c - 1) >> 1) + lane) * 16 + 8 * ((c - 1) & 1), v.x, v.z);
            if (a || c == 0 || c == 6) mbar_arrive(sb + (a ? (c ? BAR_CSQ : BAR_CSV) : (c ? BAR_CS3 : BAR_CS1)));
        }
        mbar_wait(sb + BAR_HST, 0);
#pragma unroll 1
        for (int rr = 0; rr < 2; rr++) {
            const int row = 64 * rr + 32 * a + lane;
            uint4 v[8];
            uint32_t it = 0;
            while (true) {
                bool bad = false;
#pragma unroll
                for (int i = 0; i < 8; i++) v[i] = ld_tagged_rlx(g_hstat + (1024 * m + 128 * i + row) * 2);
#pragma unroll
                for (int i = 0; i < 8; i++) bad |= v[i].y != epoch || v[i].w != epoch;
                if (!__any_sync(0xffffffffu, bad)) break;
                __nanosleep(300);
                trap_if_gt(++it, 1u << 22);
            }
            float mean = 0.f;
#pragma unroll
            for (int i = 0; i < 8; i++) mean += __uint_as_float(v[i].x);
            mean *= 0.125f;
            float m2 = 0.f, dv = 0.f;
#pragma unroll
            for (int i = 0; i < 8; i++) { const float d = __uint_as_float(v[i].x) - mean; m2 += __uint_as_float(v[i].z); dv = fmaf(d, d, dv); }
            sts_f2(sb + OFF_CS1 + row * 8, -mean, __fdividef(1.f, fmaf(dv, 64.f, m2) * (1.f / DM) + 1e-5f));
        }
        mbar_arrive(sb + BAR_CS3);
#pragma unroll 1
        for (int c = a; c < 3; c += 2) {
            const int slot = c == 2 ? 1 : 4 + c;
            mbar_wait(sb + BAR_STG + 8 * c, 0);
            if (elect_one()) {
                tma_store2d(&P.thh, sb + OFF_B + slot * SLOT, 192 * j + 64 * c, 128 * m);
                asm volatile("cp.async.bulk.wait_group.read 0;" ::: "memory");
                mbar_arrive_n_if(sb + BAR_EMPTYB + 8 * slot, 8, true);
                asm volatile("cp.async.bulk.wait_group 0;" ::: "memory");
            }
            __syncwarp();
            TL(60 + c, lane == 0);
            uint32_t ack = 0;
#pragma unroll
            for (int i = 0; i < 4; i++) ack |= readback(g_hh + (size_t)(128 * m + 32 * i + lane) * FFP + 192 * j + 64 * c);
            signal_after(g_flag + (m * 3 + c) * 32, ack, P.zero, lane == 0);
            TL(54 + c, lane == 0);
        }
        return;
    }
    const unsigned epoch = ld_relaxed(&g_epoch);
    uint32_t wraw[16];
    if (!helper) {
        const uint32_t* wp = reinterpret_cast<const uint32_t*>(P.wphi) + (4 * j) * 128 + (lane & 3) * 16 + (lane >> 2);
#pragma unroll
        for (int i = 0; i < 16; i++)
            asm volatile("ld.global.nc.u32 %0, [%1];" : "=r"(wraw[i]) : "l"(wp + (i >> 2) * 128 + ((i >> 1) & 1) * 64 + (i & 1) * 8));
    }
    asm volatile("setmaxnreg.inc.sync.aligned.u32 216;");
    bar_sync(0, NTHREADS);
    if (helper) {
        if (warp < 4) {
            sts128(sb + OFF_B + 16 * tid, 0x3f803f80u, 0x3f803f80u, 0x3f803f80u, 0x3f803f80u);
            for (int i = tid; i < 2 * ACC_SIZE / 4; i += 128) stg128(g_acc + 2 * j * ACC_SIZE + 4 * i, 0, 0, 0, 0);
            fence_async_smem();
            fence_gpu();
            bar_sync(1, 128);
            float acc[8];
            int i = 0;
#pragma unroll 1
            for (int job = 0; job < 12; job++) {
                const int n = job < 6 ? 4 : 8;
#pragma unroll 1
                for (int t = 0; t < n; t++, i++) {
                    mbar_wait(sb + BAR_FULLA + 8 * (i & 7), (i >> 3) & 1);
                    wg_fence();
#pragma unroll
                    for (int k = 0; k < 8; k++)
                        wgmma_n8_tt(acc + (k & 4), desc_lo(sb + OFF_A) + (i & 7) * (SLOT >> 4) + 128 * k, desc_lo(sb + OFF_B), (t | (k & 3)) != 0);
                    wg_commit();
                    wg_wait<1>();
                    mbar_arrive_n_if(sb + BAR_EMPTYA + 8 * ((i + 7) & 7), 2, lane == 0 && i > 0);
                }
                wg_wait<0>();
                fence_acc<8>(acc);
                const int q = lane & 3;
                const float lo = (q & 1) ? acc[2] : acc[0], hi = (q & 1) ? acc[6] : acc[4];
                const float v = job < 6 ? lo + hi : ((q & 2) ? hi : lo);
                unsigned long long* dst = g_cs + ((2 * j + (job & 1)) * 6 + (job >> 1)) * 128 + (q >> 1) * 64 + 16 * warp + 8 * (q & 1) + (lane >> 2);
                asm volatile("st.relaxed.gpu.global.b64 [%0], %1;" ::"l"(dst), "l"(((unsigned long long)epoch << 32) | __float_as_uint(v)) : "memory");
            }
        }
        return;
    }
    {
        const int w = warp >> 2, wv = warp & 3, g = lane >> 2, q = lane & 3;
        const int row_w = 128 * m + 16 * warp;
        const uint32_t sa = sb + OFF_A + w * 8192;
        const desc_t dA = desc_lo(sa), dB = desc_lo(sb + OFF_B);
        const bool l0 = lane == 0;
        Ring rg{0, 0};
        int prev = 0;

        uint32_t wb[16];
        constexpr float L2E = 1.4426950408889634f;
        uint32_t fp[16], fm[16];
        float fr[16];
        float rs0, nm0, rs1, nm1;
        uint32_t kv_ack[8];
        {
            float acc[64];
#pragma unroll 1
            for (int kt = 0; kt < 8; kt++) {
                mbar_waitc(sb + BAR_FULLA + 8 * kt, 0);
                mbar_waitc(sb + BAR_FULLB + 8 * rg.slot, rg.phase);
                const desc_t da = dA + kt * (SLOT >> 4), db = dB + rg.slot * (SLOT >> 4);
                wg_fence();
#pragma unroll
                for (int k = 0; k < 4; k++) wgmma_n128(acc, da + 2 * k, db + 128 * k, (kt | k) != 0);
                wg_commit();
                wg_wait<1>();
                mbar_arrive_if(sb + BAR_EMPTYB + 8 * prev, l0 && kt > 0);
                prev = rg.slot; rg.adv();
            }
            {
                uint4 a, b;
                do {
                    a = ld_tagged_rlx(g_xstat + 2 * (row_w + g));
                    b = ld_tagged_rlx(g_xstat + 2 * (row_w + g + 8));
                } while (__any_sync(0xffffffffu, a.y != epoch || a.w != epoch || b.y != epoch || b.w != epoch));
                rs0 = __uint_as_float(a.x); nm0 = __uint_as_float(a.z); rs1 = __uint_as_float(b.x); nm1 = __uint_as_float(b.z);
            }
#pragma unroll
            for (int i = 0; i < 8; i++) {
                wb[(i >> 1) * 4 + (i & 1)] = __byte_perm(wraw[2 * i], wraw[2 * i + 1], 0x5410);
                wb[(i >> 1) * 4 + 2 + (i & 1)] = __byte_perm(wraw[2 * i], wraw[2 * i + 1], 0x7632);
            }
            TL(17, tid == 0);
            mbar_waitc(sb + BAR_CS1, 0);
            wg_wait<0>();
            fence_acc<64>(acc);
            mbar_arrive_if(sb + BAR_EMPTYB + 8 * prev, l0);
            TL(2, tid == 0);
#pragma unroll
            for (int i = 2; i < 6; i++) mbar_waitc(sb + BAR_FULLB + 8 * i, 1);
            const int lrow = 16 * warp + (lane & 15), ch = lane >> 4, sw = lane & 7;
            const uint32_t st = sb + OFF_B + 2 * SLOT + lrow * 128;
            uint32_t ka[16];
#pragma unroll
            for (int hh = 0; hh < 4; hh++)
                ln_frag<false>(acc + 8 * hh, sb + OFF_CS1 + (64 + 16 * hh + 2 * q) * 4, rs0, nm0, rs1, nm1, ka + 4 * hh);
#pragma unroll
            for (int hh = 0; hh < 4; hh++) feature_map<true>(ka + 4 * hh, wb + 4 * hh, rs0 * L2E, rs1 * L2E, fp + 4 * hh, fm + 4 * hh, fr);
#pragma unroll
            for (int hh = 0; hh < 4; hh++) {
                stsm4(st + (hh >> 1) * SLOT + (((4 * (hh & 1) + ch) ^ sw) << 4), fp[4 * hh], fp[4 * hh + 1], fp[4 * hh + 2], fp[4 * hh + 3]);
                stsm4(st + (hh >> 1) * SLOT + (((4 * (hh & 1) + 2 + ch) ^ sw) << 4), fm[4 * hh], fm[4 * hh + 1], fm[4 * hh + 2], fm[4 * hh + 3]);
            }
            mbar_waitc(sb + BAR_CSV, 0);
#pragma unroll
            for (int hh = 0; hh < 4; hh++) {
                uint32_t a[4];
                ln_frag<true>(acc + 32 + 8 * hh, sb + OFF_CS1 + (128 + 16 * hh + 2 * q) * 4, rs0, nm0, rs1, nm1, a);
                stsm4(st + (2 + (hh >> 1)) * SLOT + (((2 * (hh & 1) + ch) ^ sw) << 4), a[0], a[1], a[2], a[3]);
            }
            stsm4(st + (2 + ch) * SLOT + ((4 ^ sw) << 4), 0x3f803f80u, 0x3f803f80u, 0x3f803f80u, 0x3f803f80u);
            fence_async_smem();
            bar_sync(1, 256);
            float kvd[20];
            wg_fence();
#pragma unroll
            for (int k = 0; k < 8; k++)
                wgmma_n40_tt(kvd, dB + (2 + w) * (SLOT >> 4) + 128 * k, dB + (4 + w) * (SLOT >> 4) + 128 * k, k != 0);
            wg_commit();
            wg_wait<0>();
            fence_acc<20>(kvd);
            const bool h1 = wv >= 2;
            const int f = 16 * warp + g;
            float* kvp = acc_j + ACC_KV + f * 16 + 2 * q;
            kv_ack[0] = kv_ack[5] = kv_ack[6] = kv_ack[7] = atom_f32x2(kvp, h1 ? kvd[8] : kvd[0], h1 ? kvd[9] : kvd[1]);
            kv_ack[1] = atom_f32x2(kvp + 128, h1 ? kvd[10] : kvd[2], h1 ? kvd[11] : kvd[3]);
            kv_ack[2] = atom_f32x2(kvp + 8, h1 ? kvd[12] : kvd[4], h1 ? kvd[13] : kvd[5]);
            kv_ack[3] = atom_f32x2(kvp + 136, h1 ? kvd[14] : kvd[6], h1 ? kvd[15] : kvd[7]);
            kv_ack[4] = atom_f32_if(acc_j + ACC_Z + f + 8 * (q & 1), q ? kvd[18] : kvd[16], q < 2);
            mbar_arrive_if(sb + BAR_EMPTYB + 8 * (2 + (lane & 3)), lane < 4);
            TL(3, tid == 0);
        }
        uint32_t res_lo[8], res_hi[8], of[128];
        uint4* const o_own = g_o + (role * 4) * 256 + tid;
        uint4* const h_own = g_h + (role * 8 + warp) * 128 + lane;
        const uint32_t own_rows = sb + OFF_A + j * SLOT + warp * 2048;
        {
            float acc[32];
            rg.slot = 0; rg.phase = 0;
#pragma unroll 1
            for (int b = 0; b < 4; b++) {
                mbar_waitc(sb + BAR_FULLB + 8 * rg.slot, rg.phase);
                const desc_t da = dA + b * (2 * SLOT >> 4), db = dB + rg.slot * (SLOT >> 4);
                wg_fence();
#pragma unroll
                for (int k = 0; k < 8; k++) wgmma_n64(acc, da + (k >> 2) * (SLOT >> 4) + (k & 3) * 2, db + 128 * k, (b | k) != 0);
                wg_commit();
                wg_wait<1>();
                mbar_arrive_if(sb + BAR_EMPTYB + 8 * prev, l0 && b > 0);
                if (b == 1) { signal_late(cnt_j, kv_ack, P.zero, l0); TL(19, tid == 0); }
                prev = rg.slot; rg.adv();
            }
            wg_wait<0>();
            fence_acc<32>(acc);
            mbar_arrive_if(sb + BAR_EMPTYB + 8 * prev, l0);
            TL(4, tid == 0);
            mbar_waitc(sb + BAR_CSQ, 0);
            uint32_t qa[16];
#pragma unroll
            for (int hh = 0; hh < 4; hh++)
                ln_frag<false>(acc + 8 * hh, sb + OFF_CS1 + (16 * hh + 2 * q) * 4, rs0, nm0, rs1, nm1, qa + 4 * hh);
#pragma unroll
            for (int hh = 0; hh < 4; hh++) feature_map<false>(qa + 4 * hh, wb + 4 * hh, rs0 * L2E, rs1 * L2E, fp + 4 * hh, fm + 4 * hh, fr + 4 * hh);
#pragma unroll
            for (int b = 0; b < 4; b++)
                ldsm4(own_rows + (lane & 15) * 128 + (((2 * b + (lane >> 4)) ^ (lane & 7)) << 4),
                      res_lo[2 * b], res_hi[2 * b], res_lo[2 * b + 1], res_hi[2 * b + 1]);
            if (warp == 0) while (__any_sync(0xffffffffu, (int)(ld_acquire(cnt_j) - epoch * 128) < 0)) {}
            TL(6, tid == 0);
            bar_sync(1, 256);
            const uint32_t kvs = sb + OFF_A + ((j + 7) & 7) * SLOT;
            {
                const float4 a0 = ld_l2_f4(acc_j + ACC_KV + 4 * tid), a1 = ld_l2_f4(acc_j + ACC_KV + 4 * (tid + 256));
                const float zz = ld_l2_f(acc_j + ACC_Z + (tid & 127));
                sts64(kvs + (tid >> 2) * 48 + (tid & 3) * 8, pack_bf16(a0.x, a0.y), pack_bf16(a0.z, a0.w));
                sts64(kvs + ((tid >> 2) + 64) * 48 + (tid & 3) * 8, pack_bf16(a1.x, a1.y), pack_bf16(a1.z, a1.w));
                const uint32_t z2 = pack_bf16(zz, zz);
                sts64(kvs + (tid & 127) * 48 + 32 + w * 8, z2, z2);
            }
            bar_sync(1, 256);
#pragma unroll
            for (int hh = 0; hh < 4; hh++) {
                uint32_t b[8], zb[4];
                const uint32_t base = kvs + hh * 32 * 48;
                ldsm4t(base + (lane & 15) * 48 + (lane >> 4) * 16, b[0], b[1], b[2], b[3]);
                ldsm4t(base + (16 + (lane & 15)) * 48 + (lane >> 4) * 16, b[4], b[5], b[6], b[7]);
                ldsm4t(base + lane * 48 + 32, zb[0], zb[1], zb[2], zb[3]);
                float n0[4], n1[4], dn[4], m0[4], m1[4], dm[4];
                mma16816_z(n0, fp + 4 * hh, b[0], b[1]); mma16816_z(n1, fp + 4 * hh, b[2], b[3]); mma16816_z(dn, fp + 4 * hh, zb[0], zb[1]);
                mma16816_z(m0, fm + 4 * hh, b[4], b[5]); mma16816_z(m1, fm + 4 * hh, b[6], b[7]); mma16816_z(dm, fm + 4 * hh, zb[2], zb[3]);
                const float* r = fr + 4 * hh;
                const float i0 = rcp(fmaf(dn[0], r[0], fmaf(dm[0], r[2], 1e-6f))), i1 = rcp(fmaf(dn[2], r[1], fmaf(dm[2], r[3], 1e-6f)));
                const float p0 = r[0] * i0, q0 = r[2] * i0, p1 = r[1] * i1, q1 = r[3] * i1;
                of[4 * hh] = pack_bf16(fmaf(n0[0], p0, m0[0] * q0), fmaf(n0[1], p0, m0[1] * q0));
                of[4 * hh + 1] = pack_bf16(fmaf(n0[2], p1, m0[2] * q1), fmaf(n0[3], p1, m0[3] * q1));
                of[4 * hh + 2] = pack_bf16(fmaf(n1[0], p0, m1[0] * q0), fmaf(n1[1], p0, m1[1] * q0));
                of[4 * hh + 3] = pack_bf16(fmaf(n1[2], p1, m1[2] * q1), fmaf(n1[3], p1, m1[3] * q1));
                ll_store(o_own + hh * 256, of[4 * hh], of[4 * hh + 1], of[4 * hh + 2], of[4 * hh + 3]);
            }
            TL(7, tid == 0);
        }
        {
            float acc[32];
#pragma unroll
            for (int t = 0; t < 8; t++) {
                acc[4 * t] = bf_lo(res_lo[t]); acc[4 * t + 1] = bf_hi(res_lo[t]);
                acc[4 * t + 2] = bf_lo(res_hi[t]); acc[4 * t + 3] = bf_hi(res_hi[t]);
            }
            fence_acc<32>(acc);
            mbar_waitc(sb + BAR_FULLB + 8 * 4, 0); mbar_waitc(sb + BAR_FULLB + 8 * 5, 0);
            mbar_waitc(sb + BAR_FULLB + 8 * 0, 1); mbar_waitc(sb + BAR_FULLB + 8 * 1, 1);
            const uint4* om = g_o + (m * 32) * 256 + tid;
#pragma unroll
            for (int sl = 0; sl < 8; sl++) {
                if (sl > 0) ll_wait4<256>(om + ((j + sl) & 7) * 1024, of + 16 * sl);
                if (sl == 1) TL(8, tid == 0);
                wg_fence();
#pragma unroll
                for (int k = 0; k < 4; k++) wgmma_n64_rs(acc, of + 16 * sl + 4 * k, dB + ((4 + (sl >> 1)) % 6) * (SLOT >> 4) + (sl & 1) * 512 + 128 * k);
                wg_commit();
                if (sl == 0) {
#pragma unroll
                    for (int t = 1; t < 8; t++)
#pragma unroll
                        for (int i = 0; i < 4; i++) ll_load(om + ((j + t) & 7) * 1024 + i * 256, of + 16 * t + 4 * i);
                }
            }
            wg_wait<0>();
            fence_acc<32>(acc);
            mbar_arrive_if(sb + BAR_EMPTYB + 8 * ((4 + lane) % 6), lane < 4);
            rg.slot = 2; rg.phase = 1;
            TL(9, tid == 0);
            float s0 = 0.f, s1 = 0.f;
#pragma unroll
            for (int t = 0; t < 8; t++) {
                res_lo[t] = pack_bf16(acc[4 * t], acc[4 * t + 1]);
                res_hi[t] = pack_bf16(acc[4 * t + 2], acc[4 * t + 3]);
                s0 += acc[4 * t] + acc[4 * t + 1];
                s1 += acc[4 * t + 2] + acc[4 * t + 3];
            }
#pragma unroll
            for (int b = 0; b < 4; b++)
                stsm4(own_rows + (lane & 15) * 128 + (((2 * b + (lane >> 4)) ^ (lane & 7)) << 4),
                      res_lo[2 * b], res_hi[2 * b], res_lo[2 * b + 1], res_hi[2 * b + 1]);
            fence_async_smem();
            __syncwarp();
#pragma unroll
            for (int i = 0; i < 4; i++) {
                const uint4 v = lds128(own_rows + i * 512 + lane * 16);
                ll_store(h_own + 32 * i, v.x, v.y, v.z, v.w);
            }
            s0 += __shfl_xor_sync(0xffffffffu, s0, 1); s1 += __shfl_xor_sync(0xffffffffu, s1, 1);
            s0 += __shfl_xor_sync(0xffffffffu, s0, 2); s1 += __shfl_xor_sync(0xffffffffu, s1, 2);
            const float mu0 = s0 * (1.f / 64), mu1 = s1 * (1.f / 64);
            float q0 = 0.f, q1 = 0.f;
#pragma unroll
            for (int t = 0; t < 8; t++) {
                float d;
                d = acc[4 * t] - mu0; q0 = fmaf(d, d, q0);
                d = acc[4 * t + 1] - mu0; q0 = fmaf(d, d, q0);
                d = acc[4 * t + 2] - mu1; q1 = fmaf(d, d, q1);
                d = acc[4 * t + 3] - mu1; q1 = fmaf(d, d, q1);
            }
            q0 += __shfl_xor_sync(0xffffffffu, q0, 1); q1 += __shfl_xor_sync(0xffffffffu, q1, 1);
            q0 += __shfl_xor_sync(0xffffffffu, q0, 2); q1 += __shfl_xor_sync(0xffffffffu, q1, 2);
            st_tagged_if(g_hstat + (role * 128 + 16 * warp + g + 8 * (q & 1)) * 2, q ? mu1 : mu0, q ? q1 : q0, epoch, q < 2);
            mbar_arrive_if(sb + BAR_HST, l0);
            TL(10, tid == 0);
        }
        {
            const uint32_t cs3 = sb + OFF_CS3 + q * 16;
            float nm0, nm1;
            {
                float acc[128];
                const desc_t dB4 = dB - (256ull << 16);
                const uint4* hm = g_h + (m * 64 + warp) * 128 + lane;
                uint32_t hb[16];
#pragma unroll
                for (int i = 0; i < 4; i++) ll_load(hm + ((j + 1) & 7) * 1024 + 32 * i, hb + 4 * i);
#pragma unroll 1
                for (int sl = 0; sl < 8; sl++) {
                    const desc_t da = dA + ((j + sl) & 7) * (SLOT >> 4);
#pragma unroll
                    for (int hf = 0; hf < 2; hf++) {
                        mbar_waitc(sb + BAR_FULLB + 8 * rg.slot, rg.phase);
                        const desc_t db = dB4 + rg.slot * (SLOT >> 4);
                        wg_fence();
                        wgmma_n256(acc, da + 4 * hf, db, (sl | hf) != 0);
                        wgmma_n256(acc, da + 4 * hf + 2, db + 128, 1);
                        wg_commit();
                        wg_wait<1>();
                        mbar_arrive_if(sb + BAR_EMPTYB + 8 * prev, l0 && (hf ? sl < 7 : sl > 0));
                        prev = rg.slot; rg.adv();
                    }
                    if (sl < 7) {
                        ll_wait4<32>(hm + ((j + sl + 1) & 7) * 1024, hb);
                        TL(44 + sl, tid == 0 && sl < 4);
                        const uint32_t dst = sb + OFF_A + ((j + sl + 1) & 7) * SLOT + warp * 2048 + lane * 16;
#pragma unroll
                        for (int i = 0; i < 4; i++) sts128(dst + i * 512, hb[4 * i], hb[4 * i + 1], hb[4 * i + 2], hb[4 * i + 3]);
                        fence_async_smem();
                        __syncwarp();
#pragma unroll
                        for (int i = 0; i < 4; i++) ll_load(hm + ((j + sl + 2) & 7) * 1024 + 32 * i, hb + 4 * i);
                    }
                }
                mbar_waitc(sb + BAR_CS3, 0);
                nm0 = lds_f2(sb + OFF_CS1 + (16 * warp + g) * 8).x; nm1 = lds_f2(sb + OFF_CS1 + (16 * warp + g + 8) * 8).x;
                wg_wait<0>();
                fence_acc<128>(acc);
                TL(11, tid == 0);
                bar_sync(1, 256);
                hh_stage<64, 4>(acc, cs3, nm0, nm1, sb + OFF_B + 4 * SLOT + warp * 2048, lane);
                mbar_arrive_if(sb + BAR_STG, l0);
                hh_stage<64, 4>(acc + 32, cs3 + 512, nm0, nm1, sb + OFF_B + 5 * SLOT + warp * 2048, lane);
                mbar_arrive_if(sb + BAR_STG + 8, l0);
                TL(50, tid == 0);
            }
            {
                float acc[56];
#pragma unroll 1
                for (int kt = 0; kt < 8; kt++) {
                    mbar_waitc(sb + BAR_FULLB + 8 * rg.slot, rg.phase);
                    const desc_t da = dA + kt * (SLOT >> 4), db = dB + rg.slot * (SLOT >> 4);
                    wg_fence();
#pragma unroll
                    for (int k = 0; k < 4; k++) wgmma_n112(acc, da + 2 * k, db + 128 * k, (kt | k) != 0);
                    wg_commit();
                    wg_wait<1>();
                    mbar_arrive_if(sb + BAR_EMPTYB + 8 * prev, l0 && kt > 0);
                    mbar_arrive_if(sb + BAR_EMPTYA + 8 * ((kt + 7) & 7), l0 && kt > 0);
                    if (kt >= 4) stg128(o_own + (kt - 4) * 256, 0, 0, 0, 0);
                    prev = rg.slot; rg.adv();
                }
                wg_wait<0>();
                fence_acc<56>(acc);
                mbar_arrive_if(sb + BAR_EMPTYA + 8 * 7, l0);
                TL(13, tid == 0);
                bar_sync(1, 256);
                hh_stage<32, 3>(acc, cs3 + 1024, nm0, nm1, sb + OFF_B + 1 * SLOT + warp * 2048, lane);
                mbar_arrive_if(sb + BAR_STG + 16, l0);
                TL(52, tid == 0);
            }
        }
        {
            float acc[64];
            const desc_t dA0 = desc_lo(sb + OFF_A);
#define KT_P4(I, NK)                                                                                        \
    do {                                                                                                    \
        const int s_ = (2 * (I) + w) & 7;                                                                   \
        mbar_waitc(sb + BAR_FULLB + 8 * rg.slot, rg.phase);                                                 \
        mbar_waitc(sb + BAR_FULLA + 8 * s_, (((I) >> 2) + 1) & 1);                                          \
        TL(30 + (I), tid == 0);                                                                             \
        const desc_t dh_ = dA0 + s_ * (SLOT >> 4), dw_ = dB + rg.slot * (SLOT >> 4) + w * 512;              \
        wg_fence();                                                                                         \
        _Pragma("unroll") for (int k = 0; k < (NK); k++) wgmma_n128_tn(acc, dw_ + 128 * k, dh_ + 2 * k, ((I) | k) != 0); \
        wg_commit();                                                                                        \
        wg_wait<1>();                                                                                       \
        mbar_arrive_n_if(sb + BAR_EMPTYA + 8 * ((s_ + 6) & 7), 2, l0 && (I) > 0);                           \
        mbar_arrive_if(sb + BAR_EMPTYB + 8 * prev, l0 && (I) > 0);                                          \
        prev = rg.slot; rg.adv();                                                                           \
    } while (0)
#pragma unroll 1
            for (int i = 0; i < 8; i++) KT_P4(i, 4);
#pragma unroll 1
            for (int i = 8; i < 12; i++) {
                KT_P4(i, 3);
                stg128(h_own + 32 * (i - 8), 0, 0, 0, 0);
            }
            const uint32_t tile = sb + OFF_A + w * SLOT;
#pragma unroll
            for (int b = 0; b < 4; b++)
                stsm4(tile + (16 * wv + (lane & 15)) * 128 + (((2 * b + (lane >> 4)) ^ (lane & 7)) << 4),
                      res_lo[2 * b], res_hi[2 * b], res_lo[2 * b + 1], res_hi[2 * b + 1]);
            wg_wait<0>();
            fence_acc<64>(acc);
            TL(15, tid == 0);
            const uint32_t xch = sb + OFF_A + 2 * SLOT + (tid & 127) * 16;
            if (w) {
#pragma unroll
                for (int t = 0; t < 8; t++) {
                    sts128(xch + SLOT + t * 2048, __float_as_uint(acc[4 * t]), __float_as_uint(acc[4 * t + 1]),
                           __float_as_uint(acc[4 * t + 2]), __float_as_uint(acc[4 * t + 3]));
                }
#pragma unroll
                for (int t = 0; t < 32; t++) acc[t] = acc[32 + t];
            } else {
#pragma unroll
                for (int t = 0; t < 8; t++)
                    sts128(xch + t * 2048, __float_as_uint(acc[32 + 4 * t]), __float_as_uint(acc[33 + 4 * t]),
                           __float_as_uint(acc[34 + 4 * t]), __float_as_uint(acc[35 + 4 * t]));
            }
            bar_sync(1, 256);
            const uint32_t blk = tile + ((lane & 7) + (lane >> 4) * 8) * 128 + (((2 * wv + ((lane >> 3) & 1)) ^ (lane & 7)) << 4);
#pragma unroll
            for (int tp = 0; tp < 4; tp++) {
                uint32_t hr[4];
                ldsm4t(blk + tp * 2048, hr[0], hr[1], hr[2], hr[3]);
#pragma unroll
                for (int u = 0; u < 2; u++) {
                    const int t = 2 * tp + u;
                    const float4 o = lds_f4(xch + (w ^ 1) * SLOT + t * 2048);
                    const float4 st = lds_f4(sb + OFF_CS1 + (64 * w + 8 * t + 2 * q) * 8);
                    hr[2 * u] = pack_bf16(fmaf(acc[4 * t] + o.x, st.y, bf_lo(hr[2 * u])), fmaf(acc[4 * t + 1] + o.y, st.w, bf_hi(hr[2 * u])));
                    hr[2 * u + 1] = pack_bf16(fmaf(acc[4 * t + 2] + o.z, st.y, bf_lo(hr[2 * u + 1])), fmaf(acc[4 * t + 3] + o.w, st.w, bf_hi(hr[2 * u + 1])));
                }
                stsm4t(blk + tp * 2048, hr[0], hr[1], hr[2], hr[3]);
            }
            bar_sync(2 + w, 128);
#pragma unroll
            for (int i = 0; i < 4; i++) {
                const int rr = 16 * wv + 4 * i + (lane >> 3);
                const uint4 v = lds128(tile + rr * 128 + (((lane & 7) ^ (rr & 7)) << 4));
                stg128(P.out + (size_t)(128 * m + 64 * w + rr) * DM + 64 * j + (lane & 7) * 8, v.x, v.y, v.z, v.w);
            }
            if (tid == 0 && role == 0) g_epoch = epoch + 1;
            TL(16, tid == 0); TLG(1, tid == 0);
        }
    }
}

typedef CUresult (*EncodeFn)(CUtensorMap*, CUtensorMapDataType, cuuint32_t, void*, const cuuint64_t*, const cuuint64_t*,
                             const cuuint32_t*, const cuuint32_t*, CUtensorMapInterleave, CUtensorMapSwizzle,
                             CUtensorMapL2promotion, CUtensorMapFloatOOBfill);

static void make_map2d(EncodeFn enc, CUtensorMap* tm, const void* base, uint64_t cols, uint64_t rows, uint64_t pitch_elems,
                       uint32_t box_rows) {
    cuuint64_t gd[2] = {cols, rows};
    cuuint64_t gs[1] = {pitch_elems * 2};
    cuuint32_t bd[2] = {64, box_rows};
    cuuint32_t es[2] = {1, 1};
    enc(tm, CU_TENSOR_MAP_DATA_TYPE_BFLOAT16, 2, const_cast<void*>(base), gd, gs, bd, es, CU_TENSOR_MAP_INTERLEAVE_NONE,
        CU_TENSOR_MAP_SWIZZLE_128B, CU_TENSOR_MAP_L2_PROMOTION_L2_256B, CU_TENSOR_MAP_FLOAT_OOB_FILL_NONE);
}

}

extern "C" void kernel_launch(void* const* d_in, const int* in_sizes, int n_in, void* d_out, int out_size) {
    using namespace hk;
    (void)in_sizes; (void)n_in; (void)out_size;
    static EncodeFn enc = nullptr;
    static void* phh = nullptr;
    static int std_layout = 0;
    if (!enc) {
        void* fn = nullptr;
        cudaDriverEntryPointQueryResult qr;
        cudaGetDriverEntryPoint("cuTensorMapEncodeTiled", &fn, cudaEnableDefault, &qr);
        enc = (EncodeFn)fn;
        cudaGetSymbolAddress(&phh, g_hh);
        cudaFuncSetAttribute(fused_kernel, cudaFuncAttributeMaxDynamicSharedMemorySize, SMEM_BYTES);
        int dev = 0, sms = 0;
        cudaGetDevice(&dev);
        cudaDeviceGetAttribute(&sms, cudaDevAttrMultiProcessorCount, dev);
        cudaFuncSetAttribute(fused_kernel, cudaFuncAttributeNonPortableClusterSizeAllowed, 1);
        const int sizes[3] = {8, 9, 16}, want[3] = {15, 9, 7};
        bool ok = sms == NCTA;
        for (int i = 0; i < 3 && ok; i++) {
            cudaLaunchConfig_t cfg = {};
            cfg.gridDim = dim3(sizes[i] * 8); cfg.blockDim = dim3(NTHREADS); cfg.dynamicSmemBytes = SMEM_BYTES;
            cudaLaunchAttribute at;
            at.id = cudaLaunchAttributeClusterDimension;
            at.val.clusterDim.x = sizes[i]; at.val.clusterDim.y = 1; at.val.clusterDim.z = 1;
            cfg.attrs = &at; cfg.numAttrs = 1;
            int n = 0;
            ok = cudaOccupancyMaxActiveClusters(&n, fused_kernel, &cfg) == cudaSuccess && n == want[i];
        }
        (void)cudaGetLastError();
        std_layout = ok ? 1 : 0;
    }
    Params P;
    const __nv_bfloat16* x = (const __nv_bfloat16*)d_in[0];
    P.x = x;
    P.wqkv = (const __nv_bfloat16*)d_in[1];
    P.wphi = (const __nv_bfloat16*)d_in[2];
    P.wo = (const __nv_bfloat16*)d_in[3];
    P.wg = (const __nv_bfloat16*)d_in[5];
    P.wu = (const __nv_bfloat16*)d_in[6];
    P.wd = (const __nv_bfloat16*)d_in[7];
    P.out = (__nv_bfloat16*)d_out;
    P.use_smid = std_layout;
    P.zero = 0;
    for (int i = 0; i < NCTA; i++) {
        int role = i < 4 ? 128 + i : i - 4;
        if (std_layout) {
            const int tpc = i >> 1, odd = i & 1;
            if (tpc < 32) role = (tpc & 7) * 8 + (tpc >> 3) * 2 + odd;
            else if (tpc < 60) role = (8 + (tpc - 32) % 7) * 8 + ((tpc - 32) / 7) * 2 + odd;
            else if (tpc < 62) role = 128 + (tpc - 60) * 2 + odd;
            else role = 15 * 8 + (tpc - 62) * 2 + odd;
        }
        P.role[i] = (unsigned char)role;
    }
    make_map2d(enc, &P.tx, x, DM, SEQ, DM, 128);
    make_map2d(enc, &P.thh, phh, FFP, SEQ, FFP, 128);
    make_map2d(enc, &P.twq, P.wqkv, 3 * DM, DM, 3 * DM, 128);
    make_map2d(enc, &P.two, P.wo, DM, DM, DM, 64);
    make_map2d(enc, &P.twg, P.wg, FF, DM, FF, 64);
    make_map2d(enc, &P.twu, P.wu, FF, DM, FF, 64);
    make_map2d(enc, &P.twd, P.wd, DM, FF, DM, 64);
    {
        cuuint64_t gd[3] = {(cuuint64_t)DM, (cuuint64_t)DM, 3};
        cuuint64_t gs[2] = {(cuuint64_t)3 * DM * 2, (cuuint64_t)DM * 2};
        cuuint32_t bd[3] = {64, 64, 2};
        cuuint32_t es[3] = {1, 1, 1};
        enc(&P.twkv, CU_TENSOR_MAP_DATA_TYPE_BFLOAT16, 3, const_cast<__nv_bfloat16*>(P.wqkv), gd, gs, bd, es,
            CU_TENSOR_MAP_INTERLEAVE_NONE, CU_TENSOR_MAP_SWIZZLE_128B, CU_TENSOR_MAP_L2_PROMOTION_L2_256B,
            CU_TENSOR_MAP_FLOAT_OOB_FILL_NONE);
    }
    for (int i = 0; i < 2; i++) {
        cuuint64_t gd[3] = {(cuuint64_t)FF - 64, (cuuint64_t)DM, 2};
        cuuint64_t gs[2] = {(cuuint64_t)FF * 2, 128};
        cuuint32_t bd[3] = {64, 32, 2};
        cuuint32_t es[3] = {1, 1, 1};
        enc(i ? &P.twu2 : &P.twg2, CU_TENSOR_MAP_DATA_TYPE_BFLOAT16, 3, const_cast<__nv_bfloat16*>(i ? P.wu : P.wg), gd, gs, bd, es,
            CU_TENSOR_MAP_INTERLEAVE_NONE, CU_TENSOR_MAP_SWIZZLE_128B, CU_TENSOR_MAP_L2_PROMOTION_L2_256B,
            CU_TENSOR_MAP_FLOAT_OOB_FILL_NONE);
    }
    fused_kernel<<<NCTA, NTHREADS, SMEM_BYTES>>>(P);
}
```

```cpp
#include <cuda_runtime.h>
#include <cuda_bf16.h>
#include <cuda.h>
#include <stdint.h>

namespace hk {

constexpr int SEQ = 2048, DM = 512, FF = 1376, FFP = 1536;
constexpr int NCTA = 132;
constexpr int NTHREADS = 384;
constexpr uint32_t SLOT = 16384;
constexpr uint32_t OFF_A = 0, OFF_B = 8 * SLOT, OFF_MISC = 14 * SLOT;
constexpr uint32_t BAR_FULLA = OFF_MISC + 0, BAR_EMPTYA = OFF_MISC + 64, BAR_FULLB = OFF_MISC + 128,
                   BAR_EMPTYB = OFF_MISC + 176, BAR_CS1 = OFF_MISC + 224, BAR_CS3 = OFF_MISC + 232,
                   BAR_CSQ = OFF_MISC + 240, BAR_CSV = OFF_MISC + 248,
                   BAR_STG = OFF_MISC + 256;
constexpr uint32_t OFF_CS1 = OFF_MISC + 384;
constexpr uint32_t OFF_CS3 = OFF_CS1 + 1024;
constexpr uint32_t OFF_XST = OFF_CS3;
constexpr uint32_t SMEM_BYTES = OFF_CS3 + 1536;
constexpr int NB = 6;
constexpr int AHEAD = 3;

constexpr int ACC_KV = 0, ACC_Z = 2048, ACC_SIZE = 2176;

__device__ __align__(1024) __nv_bfloat16 g_o[SEQ * DM];
__device__ __align__(1024) __nv_bfloat16 g_h[SEQ * DM];
__device__ __align__(1024) __nv_bfloat16 g_hh[SEQ * FFP];
__device__ __align__(128) float g_hstat[SEQ * 16];
__device__ __align__(128) unsigned long long g_xstat[SEQ * 2];
__device__ __align__(128) float g_acc[8 * ACC_SIZE];
__device__ __align__(128) unsigned g_cnt[8 * 32];
__device__ __align__(128) unsigned long long g_cs[8 * 6 * 128];
__device__ __align__(128) unsigned g_flag[16 * 5 * 32];
__device__ unsigned g_epoch = 1;

#define TL(i, pred) do {} while (0)
#define TLG(i, pred) do {} while (0)

struct Params {
    CUtensorMap tx, to, th, thh, twkv, twq, two, twg, twu, twd, twg2, twu2;
    const __nv_bfloat16 *x, *wqkv, *wphi, *wo, *wg, *wu, *wd;
    __nv_bfloat16* out;
    int use_smid;
    unsigned zero;
    unsigned char role[NCTA];
};

__device__ __forceinline__ uint32_t smem_u32(const void* p) { return (uint32_t)__cvta_generic_to_shared(p); }
__device__ __forceinline__ void mbar_init(uint32_t bar, uint32_t cnt) {
    asm volatile("mbarrier.init.shared::cta.b64 [%0], %1;" ::"r"(bar), "r"(cnt) : "memory");
}
__device__ __forceinline__ void mbar_expect_tx(uint32_t bar, uint32_t bytes) {
    asm volatile("mbarrier.arrive.expect_tx.shared::cta.b64 _, [%0], %1;" ::"r"(bar), "r"(bytes) : "memory");
}
__device__ __forceinline__ void mbar_arrive(uint32_t bar) {
    asm volatile("mbarrier.arrive.shared::cta.b64 _, [%0];" ::"r"(bar) : "memory");
}
__device__ __forceinline__ void mbar_arrive_if(uint32_t bar, bool pred) {
    asm volatile("{.reg .pred p; setp.ne.u32 p, %1, 0; @p mbarrier.arrive.shared::cta.b64 _, [%0];}" ::"r"(bar), "r"((uint32_t)pred) : "memory");
}
__device__ __forceinline__ bool mbar_try(uint32_t bar, uint32_t parity) {
    uint32_t ok;
    asm volatile("{.reg .pred p; mbarrier.try_wait.parity.shared::cta.b64 p, [%1], %2; selp.u32 %0,1,0,p;}"
                 : "=r"(ok) : "r"(bar), "r"(parity) : "memory");
    return ok;
}
__device__ __forceinline__ bool mbar_test(uint32_t bar, uint32_t parity) {
    uint32_t ok;
    asm volatile("{.reg .pred p; mbarrier.test_wait.parity.shared::cta.b64 p, [%1], %2; selp.u32 %0,1,0,p;}"
                 : "=r"(ok) : "r"(bar), "r"(parity) : "memory");
    return ok;
}
__device__ __forceinline__ void trap_if_gt(uint32_t v, uint32_t lim) {
    asm volatile("{.reg .pred p; setp.gt.u32 p, %0, %1; @p trap;}" ::"r"(v), "r"(lim));
}
__device__ __forceinline__ void mbar_wait(uint32_t bar, uint32_t parity) {
    asm volatile("{\n"
                 ".reg .pred P1, P2;\n"
                 ".reg .u32 c;\n"
                 "mov.u32 c, 0;\n"
                 "LAB_WAIT:\n"
                 "mbarrier.try_wait.parity.shared::cta.b64 P1, [%0], %1;\n"
                 "@P1 bra LAB_DONE;\n"
                 "add.u32 c, c, 1;\n"
                 "setp.gt.u32 P2, c, 4194304;\n"
                 "@P2 trap;\n"
                 "bra LAB_WAIT;\n"
                 "LAB_DONE:\n"
                 "}" ::"r"(bar), "r"(parity) : "memory");
}
__device__ __forceinline__ void mbar_waitc(uint32_t bar, uint32_t parity) {
    asm volatile("{\n"
                 ".reg .pred P1;\n"
                 "LAB_WAIT:\n"
                 "mbarrier.try_wait.parity.shared::cta.b64 P1, [%0], %1;\n"
                 "@!P1 bra LAB_WAIT;\n"
                 "}" ::"r"(bar), "r"(parity) : "memory");
}
__device__ __forceinline__ void tma2d(uint32_t dst, const CUtensorMap* tm, uint32_t bar, int c0, int c1) {
    asm volatile("cp.async.bulk.tensor.2d.shared::cluster.global.mbarrier::complete_tx::bytes [%0], [%1, {%3, %4}], [%2];"
                 ::"r"(dst), "l"(tm), "r"(bar), "r"(c0), "r"(c1) : "memory");
}
__device__ __forceinline__ void tma3d(uint32_t dst, const CUtensorMap* tm, uint32_t bar, int c0, int c1, int c2) {
    asm volatile("cp.async.bulk.tensor.3d.shared::cluster.global.mbarrier::complete_tx::bytes [%0], [%1, {%3, %4, %5}], [%2];"
                 ::"r"(dst), "l"(tm), "r"(bar), "r"(c0), "r"(c1), "r"(c2) : "memory");
}
__device__ __forceinline__ bool elect_one() {
    uint32_t ok;
    asm volatile("{.reg .pred p; elect.sync _|p, 0xffffffff; selp.u32 %0, 1, 0, p;}" : "=r"(ok));
    return ok;
}
__device__ __forceinline__ void prefetch_tmap(const CUtensorMap* tm) {
    asm volatile("prefetch.tensormap [%0];" ::"l"(tm) : "memory");
}
__device__ __forceinline__ void prefetch_l2(const void* p, uint32_t bytes) {
    asm volatile("cp.async.bulk.prefetch.L2.global [%0], %1;" ::"l"(p), "r"(bytes) : "memory");
}
__device__ __forceinline__ unsigned ld_acquire(const unsigned* p) {
    unsigned v; asm volatile("ld.acquire.gpu.global.u32 %0, [%1];" : "=r"(v) : "l"(p) : "memory"); return v;
}
__device__ __forceinline__ uint4 ld_acquire4(const unsigned* p) {
    uint4 v;
    asm volatile("ld.acquire.gpu.global.v4.u32 {%0,%1,%2,%3}, [%4];" : "=r"(v.x), "=r"(v.y), "=r"(v.z), "=r"(v.w) : "l"(p) : "memory");
    return v;
}
__device__ __forceinline__ unsigned ld_relaxed(const unsigned* p) {
    unsigned v; asm volatile("ld.relaxed.gpu.global.u32 %0, [%1];" : "=r"(v) : "l"(p)); return v;
}
__device__ __forceinline__ void st_relaxed(unsigned* p, unsigned v) {
    asm volatile("st.relaxed.gpu.global.u32 [%0], %1;" ::"l"(p), "r"(v) : "memory");
}
__device__ __forceinline__ void red_relaxed(unsigned* p, unsigned v) {
    asm volatile("red.relaxed.gpu.global.add.u32 [%0], %1;" ::"l"(p), "r"(v) : "memory");
}
__device__ __forceinline__ void fence_gpu() { asm volatile("fence.acq_rel.gpu;" ::: "memory"); }
__device__ __forceinline__ void fence_async_smem() { asm volatile("fence.proxy.async.shared::cta;" ::: "memory"); }
__device__ __forceinline__ void fence_async_global() { asm volatile("fence.proxy.async.global;" ::: "memory"); }
__device__ __forceinline__ void wait_count(const unsigned* p, unsigned target) {
    uint32_t it = 0;
    while ((int)(ld_acquire(p) - target) < 0) trap_if_gt(++it, 1u << 22);
}
__device__ __forceinline__ void wait_count_warp(const unsigned* p, unsigned target) {
    uint32_t it = 0;
    while (__any_sync(0xffffffffu, (int)(ld_acquire(p) - target) < 0)) trap_if_gt(++it, 1u << 22);
}
__device__ __forceinline__ void red_f32(float* p, float a) {
    asm volatile("red.relaxed.gpu.global.add.f32 [%0], %1;" ::"l"(p), "f"(a) : "memory");
}
__device__ __forceinline__ void red_f32x2(float* p, float a, float b) {
    asm volatile("red.relaxed.gpu.global.add.v2.f32 [%0], {%1, %2};" ::"l"(p), "f"(a), "f"(b) : "memory");
}
__device__ __forceinline__ void red_f32x4(float* p, float a, float b, float c, float d) {
    asm volatile("red.relaxed.gpu.global.add.v4.f32 [%0], {%1, %2, %3, %4};" ::"l"(p), "f"(a), "f"(b), "f"(c), "f"(d) : "memory");
}
__device__ __forceinline__ float4 ld_l2_f4(const float* p) {
    float4 v;
    asm volatile("ld.relaxed.gpu.global.v4.f32 {%0,%1,%2,%3}, [%4];" : "=f"(v.x), "=f"(v.y), "=f"(v.z), "=f"(v.w) : "l"(p) : "memory");
    return v;
}
__device__ __forceinline__ float2 ld_l2_f2(const float* p) {
    float2 v;
    asm volatile("ld.relaxed.gpu.global.v2.f32 {%0,%1}, [%2];" : "=f"(v.x), "=f"(v.y) : "l"(p) : "memory");
    return v;
}
__device__ __forceinline__ float ld_l2_f(const float* p) {
    float v;
    asm volatile("ld.relaxed.gpu.global.f32 %0, [%1];" : "=f"(v) : "l"(p) : "memory");
    return v;
}
__device__ __forceinline__ uint4 ldg_nc(const void* p) {
    uint4 v;
    asm volatile("ld.global.nc.L1::no_allocate.v4.u32 {%0,%1,%2,%3}, [%4];" : "=r"(v.x), "=r"(v.y), "=r"(v.z), "=r"(v.w) : "l"(p));
    return v;
}
__device__ __forceinline__ void stg128(void* p, uint32_t a, uint32_t b, uint32_t c, uint32_t d) {
    asm volatile("st.global.v4.u32 [%0], {%1,%2,%3,%4};" ::"l"(p), "r"(a), "r"(b), "r"(c), "r"(d) : "memory");
}
__device__ __forceinline__ uint4 lds128(uint32_t a) {
    uint4 v;
    asm volatile("ld.shared.v4.u32 {%0,%1,%2,%3}, [%4];" : "=r"(v.x), "=r"(v.y), "=r"(v.z), "=r"(v.w) : "r"(a) : "memory");
    return v;
}
__device__ __forceinline__ float2 lds_f2(uint32_t a) {
    float2 v;
    asm volatile("ld.shared.v2.f32 {%0,%1}, [%2];" : "=f"(v.x), "=f"(v.y) : "r"(a) : "memory");
    return v;
}
__device__ __forceinline__ void sts_f2(uint32_t a, float x, float y) {
    asm volatile("st.shared.v2.f32 [%0], {%1,%2};" ::"r"(a), "f"(x), "f"(y) : "memory");
}
__device__ __forceinline__ void sts64(uint32_t a, uint32_t x, uint32_t y) {
    asm volatile("st.shared.v2.u32 [%0], {%1,%2};" ::"r"(a), "r"(x), "r"(y) : "memory");
}
__device__ __forceinline__ void sts128(uint32_t a, uint32_t x, uint32_t y, uint32_t z, uint32_t w) {
    asm volatile("st.shared.v4.u32 [%0], {%1,%2,%3,%4};" ::"r"(a), "r"(x), "r"(y), "r"(z), "r"(w) : "memory");
}
__device__ __forceinline__ void stsm4(uint32_t a, uint32_t r0, uint32_t r1, uint32_t r2, uint32_t r3) {
    asm volatile("stmatrix.sync.aligned.m8n8.x4.shared.b16 [%0], {%1,%2,%3,%4};" ::"r"(a), "r"(r0), "r"(r1), "r"(r2), "r"(r3) : "memory");
}
__device__ __forceinline__ void stsm4t(uint32_t a, uint32_t r0, uint32_t r1, uint32_t r2, uint32_t r3) {
    asm volatile("stmatrix.sync.aligned.m8n8.x4.trans.shared.b16 [%0], {%1,%2,%3,%4};" ::"r"(a), "r"(r0), "r"(r1), "r"(r2), "r"(r3) : "memory");
}
__device__ __forceinline__ void tma_store2d(const CUtensorMap* tm, uint32_t src, int c0, int c1) {
    asm volatile("cp.async.bulk.tensor.2d.global.shared::cta.bulk_group [%0, {%2, %3}], [%1];" ::"l"(tm), "r"(src), "r"(c0), "r"(c1) : "memory");
    asm volatile("cp.async.bulk.commit_group;" ::: "memory");
}
__device__ __forceinline__ void ldsm4(uint32_t a, uint32_t& r0, uint32_t& r1, uint32_t& r2, uint32_t& r3) {
    asm volatile("ldmatrix.sync.aligned.m8n8.x4.shared.b16 {%0,%1,%2,%3}, [%4];" : "=r"(r0), "=r"(r1), "=r"(r2), "=r"(r3) : "r"(a) : "memory");
}
__device__ __forceinline__ void ldsm4t(uint32_t a, uint32_t& r0, uint32_t& r1, uint32_t& r2, uint32_t& r3) {
    asm volatile("ldmatrix.sync.aligned.m8n8.x4.trans.shared.b16 {%0,%1,%2,%3}, [%4];" : "=r"(r0), "=r"(r1), "=r"(r2), "=r"(r3) : "r"(a) : "memory");
}
__device__ __forceinline__ void mma16816(float* c, const uint32_t* a, uint32_t b0, uint32_t b1) {
    asm("mma.sync.aligned.m16n8k16.row.col.f32.bf16.bf16.f32 {%0,%1,%2,%3}, {%4,%5,%6,%7}, {%8,%9}, {%0,%1,%2,%3};"
                 : "+f"(c[0]), "+f"(c[1]), "+f"(c[2]), "+f"(c[3])
                 : "r"(a[0]), "r"(a[1]), "r"(a[2]), "r"(a[3]), "r"(b0), "r"(b1));
}
__device__ __forceinline__ uint32_t pack_bf16(float lo, float hi) {
    uint32_t r; asm("cvt.rn.bf16x2.f32 %0, %1, %2;" : "=r"(r) : "f"(hi), "f"(lo)); return r;
}
__device__ __forceinline__ float bf_lo(uint32_t w) { return __uint_as_float(w << 16); }
__device__ __forceinline__ float bf_hi(uint32_t w) { return __uint_as_float(w & 0xffff0000u); }
__device__ __forceinline__ float ex2(float x) { float r; asm("ex2.approx.ftz.f32 %0, %1;" : "=f"(r) : "f"(x)); return r; }
__device__ __forceinline__ float rcp(float x) { float r; asm("rcp.approx.ftz.f32 %0, %1;" : "=f"(r) : "f"(x)); return r; }
__device__ __forceinline__ void bar_sync(int id, int n) { asm volatile("bar.sync %0, %1;" ::"r"(id), "r"(n) : "memory"); }

typedef unsigned long long desc_t;
__device__ __forceinline__ desc_t desc_lo(uint32_t addr) { return (desc_t)(((addr & 0x3FFFF) >> 4) | (512u << 16)) | (0x40000040ull << 32); }
__device__ __forceinline__ void wg_fence() { asm volatile("wgmma.fence.sync.aligned;" ::: "memory"); }
__device__ __forceinline__ void wg_commit() { asm volatile("wgmma.commit_group.sync.aligned;" ::: "memory"); }
template <int N> __device__ __forceinline__ void wg_wait() { asm volatile("wgmma.wait_group.sync.aligned %0;" ::"n"(N) : "memory"); }
template <int N> __device__ __forceinline__ void fence_acc(float* d) {
#pragma unroll
    for (int i = 0; i < N; i++) asm volatile("" : "+f"(d[i])::"memory");
}
#define R4(o) "+f"(d[o + 0]), "+f"(d[o + 1]), "+f"(d[o + 2]), "+f"(d[o + 3])
#define R8(o) R4(o), R4(o + 4)
__device__ __forceinline__ void wgmma_n128(float* d, desc_t da, desc_t db, int sc) {
    asm volatile("{.reg .pred p; setp.ne.b32 p, %66, 0;\n"
                 "wgmma.mma_async.sync.aligned.m64n128k16.f32.bf16.bf16 {%0,%1,%2,%3,%4,%5,%6,%7,%8,%9,%10,%11,%12,%13,%14,%15,%16,%17,%18,%19,%20,%21,%22,%23,%24,%25,%26,%27,%28,%29,%30,%31,"
                 "%32,%33,%34,%35,%36,%37,%38,%39,%40,%41,%42,%43,%44,%45,%46,%47,%48,%49,%50,%51,%52,%53,%54,%55,%56,%57,%58,%59,%60,%61,%62,%63}, %64, %65, p, 1, 1, 0, 1;}"
                 : R8(0), R8(8), R8(16), R8(24), R8(32), R8(40), R8(48), R8(56)
                 : "l"(da), "l"(db), "r"(sc));
}
__device__ __forceinline__ void wgmma_n256(float* d, desc_t da, desc_t db, int sc) {
    asm volatile("{.reg .pred p; setp.ne.b32 p, %130, 0;\n"
                 "wgmma.mma_async.sync.aligned.m64n256k16.f32.bf16.bf16 {%0,%1,%2,%3,%4,%5,%6,%7,%8,%9,%10,%11,%12,%13,%14,%15,%16,%17,%18,%19,%20,%21,%22,%23,%24,%25,%26,%27,%28,%29,%30,%31,%32,%33,%34,%35,%36,%37,%38,%39,%40,%41,%42,%43,%44,%45,%46,%47,%48,%49,%50,%51,%52,%53,%54,%55,%56,%57,%58,%59,%60,%61,%62,%63,%64,%65,%66,%67,%68,%69,%70,%71,%72,%73,%74,%75,%76,%77,%78,%79,%80,%81,%82,%83,%84,%85,%86,%87,%88,%89,%90,%91,%92,%93,%94,%95,%96,%97,%98,%99,%100,%101,%102,%103,%104,%105,%106,%107,%108,%109,%110,%111,%112,%113,%114,%115,%116,%117,%118,%119,%120,%121,%122,%123,%124,%125,%126,%127}, %128, %129, p, 1, 1, 0, 1;}"
                 : R8(0), R8(8), R8(16), R8(24), R8(32), R8(40), R8(48), R8(56), R8(64), R8(72), R8(80), R8(88), R8(96), R8(104), R8(112), R8(120)
                 : "l"(da), "l"(db), "r"(sc));
}
__device__ __forceinline__ void wgmma_n112(float* d, desc_t da, desc_t db, int sc) {
    asm volatile("{.reg .pred p; setp.ne.b32 p, %58, 0;\n"
                 "wgmma.mma_async.sync.aligned.m64n112k16.f32.bf16.bf16 {%0,%1,%2,%3,%4,%5,%6,%7,%8,%9,%10,%11,%12,%13,%14,%15,%16,%17,%18,%19,%20,%21,%22,%23,%24,%25,%26,%27,%28,%29,%30,%31,%32,%33,%34,%35,%36,%37,%38,%39,%40,%41,%42,%43,%44,%45,%46,%47,%48,%49,%50,%51,%52,%53,%54,%55}, %56, %57, p, 1, 1, 0, 1;}"
                 : R8(0), R8(8), R8(16), R8(24), R8(32), R8(40), R8(48)
                 : "l"(da), "l"(db), "r"(sc));
}
__device__ __forceinline__ void wgmma_n128_tn(float* d, desc_t da, desc_t db, int sc) {
    asm volatile("{.reg .pred p; setp.ne.b32 p, %66, 0;\n"
                 "wgmma.mma_async.sync.aligned.m64n128k16.f32.bf16.bf16 {%0,%1,%2,%3,%4,%5,%6,%7,%8,%9,%10,%11,%12,%13,%14,%15,%16,%17,%18,%19,%20,%21,%22,%23,%24,%25,%26,%27,%28,%29,%30,%31,%32,%33,%34,%35,%36,%37,%38,%39,%40,%41,%42,%43,%44,%45,%46,%47,%48,%49,%50,%51,%52,%53,%54,%55,%56,%57,%58,%59,%60,%61,%62,%63}, %64, %65, p, 1, 1, 1, 0;}"
                 : R8(0), R8(8), R8(16), R8(24), R8(32), R8(40), R8(48), R8(56)
                 : "l"(da), "l"(db), "r"(sc));
}
__device__ __forceinline__ void wgmma_n64(float* d, desc_t da, desc_t db, int sc) {
    asm volatile("{.reg .pred p; setp.ne.b32 p, %34, 0;\n"
                 "wgmma.mma_async.sync.aligned.m64n64k16.f32.bf16.bf16 {%0,%1,%2,%3,%4,%5,%6,%7,%8,%9,%10,%11,%12,%13,%14,%15,%16,%17,%18,%19,%20,%21,%22,%23,%24,%25,%26,%27,%28,%29,%30,%31}, %32, %33, p, 1, 1, 0, 1;}"
                 : R8(0), R8(8), R8(16), R8(24)
                 : "l"(da), "l"(db), "r"(sc));
}
__device__ __forceinline__ void wgmma_n40_tt(float* d, desc_t da, desc_t db, int sc) {
    asm volatile("{.reg .pred p; setp.ne.b32 p, %22, 0;\n"
                 "wgmma.mma_async.sync.aligned.m64n40k16.f32.bf16.bf16 {%0,%1,%2,%3,%4,%5,%6,%7,%8,%9,%10,%11,%12,%13,%14,%15,%16,%17,%18,%19}, %20, %21, p, 1, 1, 1, 1;}"
                 : R8(0), R8(8), R4(16)
                 : "l"(da), "l"(db), "r"(sc));
}

__device__ __forceinline__ void wgmma_n8_tt(float* d, desc_t da, desc_t db, int sc) {
    asm volatile("{.reg .pred p; setp.ne.b32 p, %6, 0;\n"
                 "wgmma.mma_async.sync.aligned.m64n8k16.f32.bf16.bf16 {%0,%1,%2,%3}, %4, %5, p, 1, 1, 1, 1;}"
                 : R4(0)
                 : "l"(da), "l"(db), "r"(sc));
}

__device__ __forceinline__ uint32_t readback(const void* p) {
    uint32_t v; asm volatile("ld.relaxed.gpu.global.u32 %0, [%1];" : "=r"(v) : "l"(p) : "memory"); return v;
}
__device__ __forceinline__ uint32_t atom_f32x2(float* p, float a, float b) {
    float x, y;
    asm volatile("atom.relaxed.gpu.global.add.v2.f32 {%0,%1}, [%2], {%3,%4};" : "=f"(x), "=f"(y) : "l"(p), "f"(a), "f"(b) : "memory");
    return __float_as_uint(x);
}
__device__ __forceinline__ uint32_t atom_f32_if(float* p, float a, bool pred) {
    float x = 0.f;
    asm volatile("{.reg .pred p; setp.ne.u32 p, %3, 0; @p atom.relaxed.gpu.global.add.f32 %0, [%1], %2;}" : "+f"(x) : "l"(p), "f"(a), "r"((uint32_t)pred) : "memory");
    return __float_as_uint(x);
}
__device__ __forceinline__ void signal_after(unsigned* cnt, uint32_t ack, uint32_t zero, bool pred) {
    asm volatile("{.reg .pred p; setp.ne.u32 p, %2, 0; @p red.relaxed.gpu.global.add.u32 [%0], %1;}"
                 ::"l"(cnt), "r"((ack & zero) + 1), "r"((uint32_t)pred) : "memory");
}
__device__ __forceinline__ void signal_late(unsigned* cnt, const uint32_t* a, uint32_t zero, bool pred) {
    uint32_t v;
    asm volatile("{.reg .b32 t; lop3.b32 t, %1, %2, %3, 0xfe; lop3.b32 t, t, %4, %5, 0xfe; lop3.b32 t, t, %6, %7, 0xfe; or.b32 %0, t, %8;}"
                 : "=r"(v) : "r"(a[0]), "r"(a[1]), "r"(a[2]), "r"(a[3]), "r"(a[4]), "r"(a[5]), "r"(a[6]), "r"(a[7]));
    signal_after(cnt, v, zero, pred);
}
__device__ __forceinline__ void red_f32_if(float* p, float a, bool pred) {
    asm volatile("{.reg .pred p; setp.ne.u32 p, %2, 0; @p red.relaxed.gpu.global.add.f32 [%0], %1;}" ::"l"(p), "f"(a), "r"((uint32_t)pred) : "memory");
}
__device__ __forceinline__ void stg_f2_if(float* p, float a, float b, bool pred) {
    asm volatile("{.reg .pred p; setp.ne.u32 p, %3, 0; @p st.global.v2.f32 [%0], {%1,%2};}" ::"l"(p), "f"(a), "f"(b), "r"((uint32_t)pred) : "memory");
}
__device__ __forceinline__ void stg64(void* p, uint32_t a, uint32_t b) {
    asm volatile("st.global.v2.u32 [%0], {%1,%2};" ::"l"(p), "r"(a), "r"(b) : "memory");
}
__device__ __forceinline__ void mma16816_z(float* c, const uint32_t* a, uint32_t b0, uint32_t b1) {
    asm("mma.sync.aligned.m16n8k16.row.col.f32.bf16.bf16.f32 {%0,%1,%2,%3}, {%4,%5,%6,%7}, {%8,%9}, {%10,%10,%10,%10};"
                 : "=f"(c[0]), "=f"(c[1]), "=f"(c[2]), "=f"(c[3])
                 : "r"(a[0]), "r"(a[1]), "r"(a[2]), "r"(a[3]), "r"(b0), "r"(b1), "f"(0.f));
}
__device__ __forceinline__ uint32_t max2(uint32_t a, uint32_t b) { uint32_t r; asm("max.bf16x2 %0, %1, %2;" : "=r"(r) : "r"(a), "r"(b)); return r; }
__device__ __forceinline__ uint32_t min2(uint32_t a, uint32_t b) { uint32_t r; asm("min.bf16x2 %0, %1, %2;" : "=r"(r) : "r"(a), "r"(b)); return r; }
__device__ __forceinline__ void bar_arrive(int id, int n) { asm volatile("bar.arrive %0, %1;" ::"r"(id), "r"(n) : "memory"); }
__device__ __forceinline__ void mbar_arrive_n_if(uint32_t bar, uint32_t n, bool pred) {
    asm volatile("{.reg .pred p; setp.ne.u32 p, %1, 0; @p mbarrier.arrive.shared::cta.b64 _, [%0], %2;}" ::"r"(bar), "r"((uint32_t)pred), "r"(n) : "memory");
}
__device__ __forceinline__ float4 lds_f4(uint32_t a) {
    float4 v;
    asm volatile("ld.shared.v4.f32 {%0,%1,%2,%3}, [%4];" : "=f"(v.x), "=f"(v.y), "=f"(v.z), "=f"(v.w) : "r"(a) : "memory");
    return v;
}
__device__ __forceinline__ uint4 ld_tagged(const unsigned long long* p) {
    unsigned long long a, b;
    asm volatile("ld.acquire.gpu.global.v2.b64 {%0,%1}, [%2];" : "=l"(a), "=l"(b) : "l"(p) : "memory");
    return make_uint4((unsigned)a, (unsigned)(a >> 32), (unsigned)b, (unsigned)(b >> 32));
}
__device__ __forceinline__ uint4 ld_tagged_rlx(const unsigned long long* p) {
    unsigned long long a, b;
    asm volatile("ld.relaxed.gpu.global.v2.b64 {%0,%1}, [%2];" : "=l"(a), "=l"(b) : "l"(p) : "memory");
    return make_uint4((unsigned)a, (unsigned)(a >> 32), (unsigned)b, (unsigned)(b >> 32));
}
__device__ __forceinline__ void st_tagged_if(unsigned long long* p, float a, float b, unsigned tag, bool pred) {
    const unsigned long long t = (unsigned long long)tag << 32;
    asm volatile("{.reg .pred p; setp.ne.u32 p, %3, 0; @p st.relaxed.gpu.global.v2.b64 [%0], {%1,%2};}"
                 ::"l"(p), "l"(t | __float_as_uint(a)), "l"(t | __float_as_uint(b)), "r"((uint32_t)pred) : "memory");
}

template <bool ACK>
__device__ __forceinline__ uint32_t store_tile(uint32_t tile_rows, __nv_bfloat16* gdst, const uint32_t* lo, const uint32_t* hi, int lane) {
    const int r = lane & 15;
#pragma unroll
    for (int b = 0; b < 4; b++)
        stsm4(tile_rows + r * 128 + (((2 * b + (lane >> 4)) ^ (r & 7)) << 4), lo[2 * b], hi[2 * b], lo[2 * b + 1], hi[2 * b + 1]);
    __syncwarp();
    uint32_t ack = 0;
#pragma unroll
    for (int i = 0; i < 4; i++) {
        const int rr = 4 * i + (lane >> 3);
        const uint4 v = lds128(tile_rows + rr * 128 + (((lane & 7) ^ (rr & 7)) << 4));
        stg128(gdst + rr * DM + (lane & 7) * 8, v.x, v.y, v.z, v.w);
    }
    if (ACK) {
#pragma unroll
        for (int i = 0; i < 4; i++) ack |= readback(gdst + (4 * i + (lane >> 3)) * DM + (lane & 7) * 8);
    }
    return ack;
}

__device__ __forceinline__ void feature_map(const uint32_t* a, const uint32_t* wb, float c0, float c1, uint32_t* plus, uint32_t* minus) {
    float p[8];
    mma16816_z(p, a, wb[0], wb[1]);
    mma16816_z(p + 4, a, wb[2], wb[3]);
    const uint32_t P0 = pack_bf16(p[0], p[2]), P1 = pack_bf16(p[1], p[3]), P2 = pack_bf16(p[4], p[6]), P3 = pack_bf16(p[5], p[7]);
    uint32_t mx = max2(max2(P0, P1), max2(P2, P3)), mn = min2(min2(P0, P1), min2(P2, P3));
#pragma unroll
    for (int s = 1; s <= 2; s <<= 1) {
        mx = max2(mx, __shfl_xor_sync(0xffffffffu, mx, s));
        mn = min2(mn, __shfl_xor_sync(0xffffffffu, mn, s));
    }
    const float mx0 = bf_lo(mx) * c0, mx1 = bf_hi(mx) * c1, mn0 = bf_lo(mn) * c0, mn1 = bf_hi(mn) * c1;
    p[0] = bf_lo(P0); p[2] = bf_hi(P0); p[1] = bf_lo(P1); p[3] = bf_hi(P1);
    p[4] = bf_lo(P2); p[6] = bf_hi(P2); p[5] = bf_lo(P3); p[7] = bf_hi(P3);
    float ep[8], em[8];
#pragma unroll
    for (int i = 0; i < 8; i++) {
        const bool r1 = (i & 2);
        ep[i] = ex2(fmaf(p[i], r1 ? c1 : c0, r1 ? -mx1 : -mx0));
        em[i] = ex2(fmaf(p[i], r1 ? -c1 : -c0, r1 ? mn1 : mn0));
    }
    float sp[4], sm[4];
#pragma unroll
    for (int i = 0; i < 4; i++) { plus[i] = pack_bf16(ep[2 * i], ep[2 * i + 1]); minus[i] = pack_bf16(em[2 * i], em[2 * i + 1]); }
    mma16816_z(sp, plus, 0x3f803f80u, 0x3f803f80u);
    mma16816_z(sm, minus, 0x3f803f80u, 0x3f803f80u);
    const float rs[4] = {rcp(sp[0]), rcp(sp[2]), rcp(sm[0]), rcp(sm[2])};
#pragma unroll
    for (int i = 0; i < 4; i++) {
        plus[i] = pack_bf16(ep[2 * i] * rs[i & 1], ep[2 * i + 1] * rs[i & 1]);
        minus[i] = pack_bf16(em[2 * i] * rs[2 + (i & 1)], em[2 * i + 1] * rs[2 + (i & 1)]);
    }
}

template <bool SCALE>
__device__ __forceinline__ void ln_frag(const float* acc, uint32_t cs_addr, float rs0, float nm0, float rs1, float nm1, uint32_t* a) {
    const float2 c0 = lds_f2(cs_addr), c1 = lds_f2(cs_addr + 32);
    const float s0 = SCALE ? rs0 : 1.f, s1 = SCALE ? rs1 : 1.f;
    a[0] = pack_bf16(fmaf(nm0, c0.x, acc[0]) * s0, fmaf(nm0, c0.y, acc[1]) * s0);
    a[1] = pack_bf16(fmaf(nm1, c0.x, acc[2]) * s1, fmaf(nm1, c0.y, acc[3]) * s1);
    a[2] = pack_bf16(fmaf(nm0, c1.x, acc[4]) * s0, fmaf(nm0, c1.y, acc[5]) * s0);
    a[3] = pack_bf16(fmaf(nm1, c1.x, acc[6]) * s1, fmaf(nm1, c1.y, acc[7]) * s1);
}

template <int UP>
__device__ __forceinline__ uint32_t hh_pair(const float* ag, float4 cs, float nmean) {
    const float g0 = fmaf(nmean, cs.x, ag[0]), g1 = fmaf(nmean, cs.y, ag[1]);
    const float u0 = fmaf(nmean, cs.z, ag[UP]), u1 = fmaf(nmean, cs.w, ag[UP + 1]);
    return pack_bf16(g0 * u0, g1 * u1);
}
template <int UP, int NTP>
__device__ __forceinline__ void hh_stage(const float* acc, uint32_t cs3, float nm0, float nm1, uint32_t stg, int lane) {
#pragma unroll
    for (int tp = 0; tp < NTP; tp++) {
        const float4 c0 = lds_f4(cs3 + tp * 128), c1 = lds_f4(cs3 + tp * 128 + 64);
        stsm4(stg + (lane & 15) * 128 + (((2 * tp + (lane >> 4)) ^ (lane & 7)) << 4), hh_pair<UP>(acc + 8 * tp, c0, nm0),
              hh_pair<UP>(acc + 8 * tp + 2, c0, nm1), hh_pair<UP>(acc + 8 * tp + 4, c1, nm0), hh_pair<UP>(acc + 8 * tp + 6, c1, nm1));
    }
    fence_async_smem();
    __syncwarp();
}

struct Ring {
    int slot; uint32_t phase;
    __device__ __forceinline__ void adv() { if (++slot == NB) { slot = 0; phase ^= 1; } }
};

__global__ void __launch_bounds__(NTHREADS, 1) fused_kernel(const __grid_constant__ Params P) {
    extern __shared__ __align__(1024) uint8_t smem_raw[];
    const uint32_t sb = smem_u32(smem_raw);
    const int tid = threadIdx.x, lane = tid & 31;
    const int warp = __shfl_sync(0xffffffffu, tid >> 5, 0);
    unsigned role = blockIdx.x;
    if (P.use_smid) asm volatile("mov.u32 %0, %%smid;" : "=r"(role));
    role = P.role[role];
    const int m = role >> 3, j = role & 7;
    const bool helper = role >= 128;

    TL(0, tid == 0); TLG(0, tid == 0);
    float* const acc_j = g_acc + j * ACC_SIZE;
    unsigned* const cnt_j = g_cnt + j * 32;

    if (__builtin_expect(warp >= 8, 1)) {
        asm volatile("setmaxnreg.dec.sync.aligned.u32 72;");
        if (elect_one()) {
            if (warp == 8) {
                if (!helper) {
#pragma unroll
                    for (int i = 0; i < NB; i++) mbar_init(sb + BAR_FULLB + 8 * i, 1);
#pragma unroll
                    for (int i = 0; i < 2; i++) {
                        mbar_expect_tx(sb + BAR_FULLB + 8 * i, SLOT);
                        tma3d(sb + OFF_B + i * SLOT, &P.twkv, sb + BAR_FULLB + 8 * i, 64 * j, 64 * i, 1);
                    }
                }
            } else if (warp == 9) {
#pragma unroll
                for (int i = 0; i < 8; i++) mbar_init(sb + BAR_FULLA + 8 * i, 1);
#pragma unroll
                for (int i = 0; i < 2; i++) {
                    mbar_expect_tx(sb + BAR_FULLA + 8 * i, SLOT);
                    tma2d(sb + OFF_A + i * SLOT, helper ? &P.twq : &P.tx, sb + BAR_FULLA + 8 * i, helper ? DM + 128 * j : 64 * i, 128 * (helper ? i : m));
                }
            } else if (warp == 10) {
#pragma unroll
                for (int i = 0; i < 7; i++) mbar_init(sb + BAR_CS1 + 8 * i, i == 0 ? 64 : (i == 1 ? 96 : (i < 4 ? 32 : 8)));
                trap_if_gt(sb & 1023, 0);
            } else {
#pragma unroll
                for (int i = 0; i < 14; i++) mbar_init(sb + (i < 8 ? BAR_EMPTYA : BAR_EMPTYB - 64) + 8 * i, 8);
            }
        }
        __syncwarp();
        const unsigned epoch = ld_relaxed(&g_epoch);
        bar_sync(0, NTHREADS);
        if (helper) {
            if (warp == 8) {
                if (elect_one()) {
#pragma unroll 1
                    for (int i = 2; i < 72; i++) {
                        const uint32_t full = sb + BAR_FULLA + 8 * (i & 7), dst = sb + OFF_A + (i & 7) * SLOT;
                        mbar_wait(sb + BAR_EMPTYA + 8 * (i & 7), ((i >> 3) & 1) ^ 1);
                        mbar_expect_tx(full, SLOT);
                        if (i < 24) {
                            tma2d(dst, &P.twq, full, (i < 16 ? DM + 64 * (i & 8) : 0) + 128 * j + 16 * (i & 4), 128 * (i & 3));
                        } else {
                            const int u = (i >> 3) - 3, c0 = 176 * (2 * j + (u & 1)) + 64 * (u >> 1);
                            tma2d(dst, &P.twg, full, c0, 64 * (i & 7));
                            tma2d(dst + 8192, &P.twu, full, c0, 64 * (i & 7));
                        }
                    }
                    prefetch_l2(P.wd + (size_t)j * 176128, 352256);
                }
            } else if (warp == 9) {
                wait_count_warp(g_cnt + (lane & 7) * 32, epoch * 64);
            }
            return;
        }
        if (warp == 8) {
            if (elect_one()) {
                if (m >= 3 && m < 8)
                    asm volatile("cp.async.bulk.prefetch.tensor.3d.L2.global [%0, {%1, %2, %3}];" ::"l"(&P.twkv), "r"(64 * j), "r"(64 * m), "r"(1) : "memory");
                if (j >= 3)
                    asm volatile("cp.async.bulk.prefetch.tensor.2d.L2.global [%0, {%1, %2}];" ::"l"(&P.tx), "r"(64 * j), "r"(128 * m) : "memory");
                Ring r{2, 0};
#pragma unroll 1
                for (int i = 2; i < 56; i++) {
                    const uint32_t full = sb + BAR_FULLB + 8 * r.slot, dst = sb + OFF_B + r.slot * SLOT;
                    mbar_wait(sb + BAR_EMPTYB + 8 * r.slot, r.phase ^ 1);
                    if (i >= 10 && i < 14) {
                        mbar_arrive(full);
                    } else {
                        if (i >= AHEAD && i < 6) mbar_wait(full - 8 * AHEAD, 0);
                        mbar_expect_tx(full, SLOT);
                        if (i < 8) {
                            tma3d(dst, &P.twkv, full, 64 * j, 64 * i, 1);
                        } else if (i < 20) {
                            tma2d(dst, i < 16 ? &P.twq : &P.two, full, 64 * j, 128 * (i & 3));
                        } else if (i < 36) {
                            tma3d(dst, &P.twg2, full, 176 * j, 32 * (i - 20), 0);
                            tma3d(dst + 8192, &P.twu2, full, 176 * j, 32 * (i - 20), 0);
                        } else if (i < 44) {
                            tma2d(dst, &P.twg, full, 176 * j + 128, 64 * (i - 36));
                            tma2d(dst + 8192, &P.twu, full, 176 * j + 128, 64 * (i - 36));
                        } else {
                            const int c = (i - 44) >> 2, jj = (i & 3) * 2;
                            tma2d(dst, &P.twd, full, 64 * j, 176 * jj + 64 * c);
                            tma2d(dst + 8192, &P.twd, full, 64 * j, 176 * (jj + 1) + 64 * c);
                        }
                    }
                    r.adv();
                }
            }
            return;
        }
        if (warp == 9) {
            if (elect_one()) {
#pragma unroll 1
                for (int i = 2; i < 8; i++) {
                    if (i >= AHEAD + 1) mbar_wait(sb + BAR_FULLA + 8 * (i - AHEAD - 1), 0);
                    mbar_expect_tx(sb + BAR_FULLA + 8 * i, SLOT);
                    tma2d(sb + OFF_A + i * SLOT, &P.tx, sb + BAR_FULLA + 8 * i, 64 * i, 128 * m);
                }
#pragma unroll 1
                for (int i = 1; i < 12; i++) prefetch_tmap(&P.tx + i);
#pragma unroll 1
                for (int r = 1; r < 6; r++) {
                    const CUtensorMap* tm = &P.tx + min(r, 3);
                    const int cstep = r < 3 ? 64 : 192, cbase = r < 3 ? 0 : 64 * (r - 3), skip = r < 3 ? j : 8;
                    wait_count(g_flag + (m * 5 + r - 1) * 32, epoch * (r < 3 ? 64 : 8));
                    TL(64 + r, true);
#pragma unroll 1
                    for (int t = 0; t < 8; t++) {
                        if (t == skip) continue;
                        mbar_wait(sb + BAR_EMPTYA + 8 * t, (r - 1) & 1);
                        mbar_expect_tx(sb + BAR_FULLA + 8 * t, SLOT);
                        tma2d(sb + OFF_A + t * SLOT, tm, sb + BAR_FULLA + 8 * t, cbase + cstep * t, 128 * m);
                    }
                }
            }
            return;
        }
        const int a = warp - 10;
        {
            const int row = 16 * j + 8 * a + (lane >> 2);
            const uint32_t ra = sb + OFF_A + row * 128;
            float sh = 0.f, s0 = 0.f, s1 = 0.f, q0 = 0.f, q1 = 0.f;
#pragma unroll 1
            for (int kt = 0; kt < 8; kt++) {
                mbar_wait(sb + BAR_FULLA + 8 * kt, 0);
                if (kt == 0) sh = bf_lo(lds128(ra + ((row & 7) << 4)).x);
#pragma unroll
                for (int i = 0; i < 2; i++) {
                    const uint4 v = lds128(ra + kt * SLOT + (((2 * (lane & 3) + i) ^ (row & 7)) << 4));
                    const uint32_t ww[4] = {v.x, v.y, v.z, v.w};
#pragma unroll
                    for (int e = 0; e < 4; e++) {
                        const float d0 = bf_lo(ww[e]) - sh, d1 = bf_hi(ww[e]) - sh;
                        s0 += d0; q0 = fmaf(d0, d0, q0);
                        s1 += d1; q1 = fmaf(d1, d1, q1);
                    }
                }
            }
            s0 += s1; q0 += q1;
#pragma unroll
            for (int o = 1; o <= 2; o <<= 1) { s0 += __shfl_xor_sync(0xffffffffu, s0, o); q0 += __shfl_xor_sync(0xffffffffu, q0, o); }
            const float md = s0 * (1.f / DM);
            const float rs = rsqrtf(fmaxf(q0 * (1.f / DM) - md * md, 0.f) + 1e-5f);
            st_tagged_if(g_xstat + 2 * (128 * m + row), rs, -(sh + md), epoch, (lane & 3) == 0);
        }
        const unsigned long long* cs = g_cs + j * 768 + 2 * lane;
#pragma unroll 1
        for (int c = 0; c < (a ? 4 : 9); c++) {
            if (c == 3 && !a) {
                uint32_t it = 0;
                while (__any_sync(0xffffffffu, (int)(ld_acquire(g_flag + (m * 5 + 1) * 32) - epoch * 64) < 0)) {
                    __nanosleep(500);
                    trap_if_gt(++it, 1u << 22);
                }
            }
            const unsigned long long* src = c == 0 ? cs + 128 * a : (c < 3 ? g_xstat + 2 * (128 * m + 64 * a + 32 * (c - 1) + lane) : cs + (a ? 256 : 192 + 64 * c));
            const uint32_t dst = c == 0 ? OFF_CS1 + 256 * (a + 1) + 8 * lane : (c < 3 ? OFF_XST + (64 * a + 32 * (c - 1) + lane) * 8
                                        : (a ? OFF_CS1 + 8 * lane : OFF_CS3 + (32 * ((c - 3) >> 1) + lane) * 16 + 8 * ((c - 3) & 1)));
            uint4 v;
            uint32_t it = 0;
            while (true) {
                v = ld_tagged(src);
                if (!__any_sync(0xffffffffu, v.y != epoch || v.w != epoch)) break;
                __nanosleep(60);
                trap_if_gt(++it, 1u << 22);
            }
            sts64(sb + dst, v.x, v.z);
            if (c == 2 || c == (a ? 3 : 8)) mbar_arrive(sb + (c == 2 ? BAR_CS1 : (a ? BAR_CSQ : BAR_CS3)));
        }
        if (a) {
            uint32_t it = 0;
            while (__any_sync(0xffffffffu, (int)(ld_acquire(g_flag + (m * 5 + 1) * 32) - epoch * 64) < 0)) {
                __nanosleep(500);
                trap_if_gt(++it, 1u << 22);
            }
        }
#pragma unroll 1
        for (int rr = 0; rr < 2; rr++) {
            const int row = 64 * rr + 32 * a + lane;
            const float* sp = g_hstat + (1024 * m + row) * 2;
            float2 v[8];
#pragma unroll
            for (int i = 0; i < 8; i++) v[i] = ld_l2_f2(sp + 256 * i);
            float mean = 0.f;
#pragma unroll
            for (int i = 0; i < 8; i++) mean += v[i].x;
            mean *= 0.125f;
            float m2 = 0.f, dv = 0.f;
#pragma unroll
            for (int i = 0; i < 8; i++) { m2 += v[i].y; dv = fmaf(v[i].x - mean, v[i].x - mean, dv); }
            sts_f2(sb + OFF_CS1 + row * 8, -mean, __fdividef(1.f, fmaf(dv, 64.f, m2) * (1.f / DM) + 1e-5f));
        }
        mbar_arrive(sb + BAR_CS3);
#pragma unroll 1
        for (int c = a; c < 3; c += 2) {
            const int slot = c == 2 ? 1 : 4 + c;
            mbar_wait(sb + BAR_STG + 8 * c, 0);
            if (elect_one()) {
                tma_store2d(&P.thh, sb + OFF_B + slot * SLOT, 192 * j + 64 * c, 128 * m);
                asm volatile("cp.async.bulk.wait_group.read 0;" ::: "memory");
                mbar_arrive_n_if(sb + BAR_EMPTYB + 8 * slot, 8, true);
                asm volatile("cp.async.bulk.wait_group 0;" ::: "memory");
            }
            __syncwarp();
            TL(60 + c, lane == 0);
            uint32_t ack = 0;
#pragma unroll
            for (int i = 0; i < 4; i++) ack |= readback(g_hh + (size_t)(128 * m + 32 * i + lane) * FFP + 192 * j + 64 * c);
            signal_after(g_flag + (m * 5 + 2 + c) * 32, ack, P.zero, lane == 0);
            TL(54 + c, lane == 0);
        }
        return;
    }
    const unsigned epoch = ld_relaxed(&g_epoch);
    uint32_t wraw[16];
    if (!helper) {
        const uint32_t* wp = reinterpret_cast<const uint32_t*>(P.wphi) + (4 * j) * 128 + (lane & 3) * 16 + (lane >> 2);
#pragma unroll
        for (int i = 0; i < 16; i++)
            asm volatile("ld.global.nc.u32 %0, [%1];" : "=r"(wraw[i]) : "l"(wp + (i >> 2) * 128 + ((i >> 1) & 1) * 64 + (i & 1) * 8));
    }
    asm volatile("setmaxnreg.inc.sync.aligned.u32 216;");
    bar_sync(0, NTHREADS);
    if (helper) {
        if (warp < 4) {
            sts128(sb + OFF_B + 16 * tid, 0x3f803f80u, 0x3f803f80u, 0x3f803f80u, 0x3f803f80u);
            for (int i = tid; i < 2 * ACC_SIZE / 4; i += 128) stg128(g_acc + 2 * j * ACC_SIZE + 4 * i, 0, 0, 0, 0);
            fence_async_smem();
            fence_gpu();
            bar_sync(1, 128);
            float acc[8];
            int i = 0;
#pragma unroll 1
            for (int job = 0; job < 12; job++) {
                const int n = job < 6 ? 4 : 8;
#pragma unroll 1
                for (int t = 0; t < n; t++, i++) {
                    mbar_wait(sb + BAR_FULLA + 8 * (i & 7), (i >> 3) & 1);
                    wg_fence();
#pragma unroll
                    for (int k = 0; k < 8; k++)
                        wgmma_n8_tt(acc + (k & 4), desc_lo(sb + OFF_A) + (i & 7) * (SLOT >> 4) + 128 * k, desc_lo(sb + OFF_B), (t | (k & 3)) != 0);
                    wg_commit();
                    wg_wait<1>();
                    mbar_arrive_n_if(sb + BAR_EMPTYA + 8 * ((i + 7) & 7), 2, lane == 0 && i > 0);
                }
                wg_wait<0>();
                fence_acc<8>(acc);
                const int q = lane & 3;
                const float lo = (q & 1) ? acc[2] : acc[0], hi = (q & 1) ? acc[6] : acc[4];
                const float v = job < 6 ? lo + hi : ((q & 2) ? hi : lo);
                unsigned long long* dst = g_cs + ((2 * j + (job & 1)) * 6 + (job >> 1)) * 128 + (q >> 1) * 64 + 16 * warp + 8 * (q & 1) + (lane >> 2);
                asm volatile("st.relaxed.gpu.global.b64 [%0], %1;" ::"l"(dst), "l"(((unsigned long long)epoch << 32) | __float_as_uint(v)) : "memory");
            }
        }
        return;
    }
    {
        const int w = warp >> 2, wv = warp & 3, g = lane >> 2, q = lane & 3;
        const int row_w = 128 * m + 16 * warp;
        const uint32_t sa = sb + OFF_A + w * 8192;
        const desc_t dA = desc_lo(sa), dB = desc_lo(sb + OFF_B);
        unsigned* const flag_m = g_flag + m * 160;
        const bool l0 = lane == 0;
        Ring rg{0, 0};
        int prev = 0;

        uint32_t wb[16];
        constexpr float L2E = 1.4426950408889634f;
        const int ch = lane >> 4, sw = lane & 7;
        const uint32_t lrow = (lane & 15) * 128;
        {
            float acc[64];
#pragma unroll 1
            for (int kt = 0; kt < 8; kt++) {
                mbar_waitc(sb + BAR_FULLA + 8 * kt, 0);
                mbar_waitc(sb + BAR_FULLB + 8 * rg.slot, rg.phase);
                const desc_t da = dA + kt * (SLOT >> 4), db = dB + rg.slot * (SLOT >> 4);
                wg_fence();
#pragma unroll
                for (int k = 0; k < 4; k++) wgmma_n128(acc, da + 2 * k, db + 128 * k, (kt | k) != 0);
                wg_commit();
                wg_wait<1>();
                mbar_arrive_if(sb + BAR_EMPTYB + 8 * prev, l0 && kt > 0);
                prev = rg.slot; rg.adv();
            }
#pragma unroll
            for (int i = 0; i < 8; i++) {
                wb[(i >> 1) * 4 + (i & 1)] = __byte_perm(wraw[2 * i], wraw[2 * i + 1], 0x5410);
                wb[(i >> 1) * 4 + 2 + (i & 1)] = __byte_perm(wraw[2 * i], wraw[2 * i + 1], 0x7632);
            }
            TL(17, tid == 0);
            mbar_waitc(sb + BAR_CS1, 0);
            const float2 s0 = lds_f2(sb + OFF_XST + (16 * warp + g) * 8), s1 = lds_f2(sb + OFF_XST + (16 * warp + g + 8) * 8);
            wg_wait<0>();
            fence_acc<64>(acc);
            mbar_arrive_if(sb + BAR_EMPTYB + 8 * prev, l0);
            TL(2, tid == 0);
            mbar_waitc(sb + BAR_FULLB + 8 * 4, 1); mbar_waitc(sb + BAR_FULLB + 8 * 5, 1);
            mbar_waitc(sb + BAR_FULLB + 8 * 0, 0); mbar_waitc(sb + BAR_FULLB + 8 * 1, 0);
            const uint32_t st = sb + OFF_B + warp * 2048 + lrow;
#pragma unroll
            for (int hh = 0; hh < 4; hh++) {
                uint32_t a[4];
                ln_frag<false>(acc + 8 * hh, sb + OFF_CS1 + (64 + 16 * hh + 2 * q) * 4, 0.f, s0.y, 0.f, s1.y, a);
                stsm4(st + 4 * SLOT + (((2 * hh + ch) ^ sw) << 4), a[0], a[1], a[2], a[3]);
                ln_frag<true>(acc + 32 + 8 * hh, sb + OFF_CS1 + (128 + 16 * hh + 2 * q) * 4, s0.x, s0.y, s1.x, s1.y, a);
                stsm4(st + (hh >> 1) * SLOT + (((2 * (hh & 1) + ch) ^ sw) << 4), a[0], a[1], a[2], a[3]);
            }
            stsm4(st + ch * SLOT + ((4 ^ sw) << 4), 0x3f803f80u, 0x3f803f80u, 0x3f803f80u, 0x3f803f80u);
        }
        uint32_t res_lo[8], res_hi[8];
        const uint32_t own_rows = sb + OFF_A + j * SLOT + warp * 2048;
#pragma unroll
        for (int b = 0; b < 4; b++)
            ldsm4(own_rows + lrow + (((2 * b + ch) ^ sw) << 4), res_lo[2 * b], res_hi[2 * b], res_lo[2 * b + 1], res_hi[2 * b + 1]);
        const uint32_t pq = sb + OFF_A + ((j + 1) & 7) * SLOT, pq2 = sb + OFF_A + ((j + 2) & 7) * SLOT;
        if (w == 1) {
            fence_async_smem();
            bar_arrive(2, 256);
            float acc0[32], acc1[32];
            const desc_t dA0 = desc_lo(sb + OFF_A);
#pragma unroll 1
            for (int b = 0; b < 8; b++) {
                const int slot = 2 + ((b >> 1) & 1);
                mbar_waitc(sb + BAR_FULLB + 8 * slot, (b >> 2) ^ 1);
                const desc_t da = dA0 + b * (SLOT >> 4), db = dB + slot * (SLOT >> 4) + (b & 1) * 512;
                wg_fence();
#pragma unroll
                for (int k = 0; k < 4; k++) {
                    wgmma_n64(acc0, da + 2 * k, db + 128 * k, (b | k) != 0);
                    wgmma_n64(acc1, da + 512 + 2 * k, db + 128 * k, (b | k) != 0);
                }
                wg_commit();
                wg_wait<0>();
                mbar_arrive_n_if(sb + BAR_EMPTYB + 8 * slot, 2, l0 && (b & 1));
            }
            fence_acc<32>(acc0); fence_acc<32>(acc1);
            TL(4, tid == 128);
            mbar_waitc(sb + BAR_CSQ, 0);
            bar_sync(3, 128);
#pragma unroll
            for (int mt = 0; mt < 2; mt++) {
                const float n0 = lds_f2(sb + OFF_XST + (64 * mt + 16 * wv + g) * 8).y, n1 = lds_f2(sb + OFF_XST + (64 * mt + 16 * wv + g + 8) * 8).y;
#pragma unroll
                for (int hh = 0; hh < 4; hh++) {
                    uint32_t a[4];
                    ln_frag<false>((mt ? acc1 : acc0) + 8 * hh, sb + OFF_CS1 + (16 * hh + 2 * q) * 4, 0.f, n0, 0.f, n1, a);
                    stsm4(pq + mt * 8192 + wv * 2048 + lrow + (((2 * hh + ch) ^ sw) << 4), a[0], a[1], a[2], a[3]);
                }
            }
        }
        __syncwarp();
#pragma unroll 1
        for (int mt = 0; mt < 2; mt++) {
            if (mt == 1 && w == 0) bar_sync(2, 256);
            const uint32_t ro = mt * 8192 + wv * 2048 + lrow;
            const uint32_t t0 = (w ? pq : sb + OFF_B + 4 * SLOT) + ro, t1 = (w ? pq2 : sb + OFF_B + 5 * SLOT) + ro;
            const float c0 = lds_f2(sb + OFF_XST + (64 * mt + 16 * wv + g) * 8).x * L2E, c1 = lds_f2(sb + OFF_XST + (64 * mt + 16 * wv + g + 8) * 8).x * L2E;
            uint32_t a[16], fp[16], fm[16];
#pragma unroll
            for (int hh = 0; hh < 4; hh++) ldsm4(t0 + (((2 * hh + ch) ^ sw) << 4), a[4 * hh], a[4 * hh + 1], a[4 * hh + 2], a[4 * hh + 3]);
#pragma unroll
            for (int hh = 0; hh < 4; hh++) feature_map(a + 4 * hh, wb + 4 * hh, c0, c1, fp + 4 * hh, fm + 4 * hh);
#pragma unroll
            for (int hh = 0; hh < 4; hh++) {
                stsm4(((hh >> 1) ? t1 : t0) + (((4 * (hh & 1) + ch) ^ sw) << 4), fp[4 * hh], fp[4 * hh + 1], fp[4 * hh + 2], fp[4 * hh + 3]);
                stsm4(((hh >> 1) ? t1 : t0) + (((4 * (hh & 1) + 2 + ch) ^ sw) << 4), fm[4 * hh], fm[4 * hh + 1], fm[4 * hh + 2], fm[4 * hh + 3]);
            }
        }
        TL(5, tid == 128);
        const uint32_t kvs = sb + OFF_B;
        if (w == 0) {
            fence_async_smem();
            bar_sync(4, 128);
            float kvd[40];
            wg_fence();
#pragma unroll
            for (int k = 0; k < 16; k++)
                wgmma_n40_tt(kvd + 20 * (k & 1), dB + (4 + (k & 1)) * (SLOT >> 4) + 128 * (k >> 1), dB + (k & 1) * (SLOT >> 4) + 128 * (k >> 1), k > 1);
            wg_commit();
            wg_wait<0>();
            fence_acc<40>(kvd);
            const bool h1 = wv >= 2;
            uint32_t ack = 0;
#pragma unroll
            for (int u = 0; u < 2; u++) {
                const float* d = kvd + 20 * u;
                const int f = 64 * u + 16 * wv + g;
                float* kvp = acc_j + ACC_KV + f * 16 + 2 * q;
                ack |= atom_f32x2(kvp, h1 ? d[8] : d[0], h1 ? d[9] : d[1]);
                ack |= atom_f32x2(kvp + 128, h1 ? d[10] : d[2], h1 ? d[11] : d[3]);
                ack |= atom_f32x2(kvp + 8, h1 ? d[12] : d[4], h1 ? d[13] : d[5]);
                ack |= atom_f32x2(kvp + 136, h1 ? d[14] : d[6], h1 ? d[15] : d[7]);
            }
            ack |= atom_f32_if(acc_j + ACC_Z + 64 * (q >> 1) + 16 * wv + g + 8 * (q & 1),
                               (q & 2) ? ((q & 1) ? kvd[38] : kvd[36]) : ((q & 1) ? kvd[18] : kvd[16]), true);
            TL(3, tid == 0);
            mbar_arrive_n_if(sb + BAR_EMPTYB + 8 * (lane == 2 ? 1 : 4 + lane), 2, lane < 3);
            signal_after(cnt_j, ack, P.zero, l0);
            TL(19, tid == 0);
            while (__any_sync(0xffffffffu, (int)(ld_acquire(cnt_j) - epoch * 64) < 0)) {}
            TL(6, tid == 0);
            float4 a[4];
#pragma unroll
            for (int i = 0; i < 4; i++) a[i] = ld_l2_f4(acc_j + ACC_KV + 4 * (tid + 128 * i));
            const float zz = ld_l2_f(acc_j + ACC_Z + tid);
#pragma unroll
            for (int i = 0; i < 4; i++)
                sts64(kvs + ((tid >> 2) + 32 * i) * 48 + (tid & 3) * 8, pack_bf16(a[i].x, a[i].y), pack_bf16(a[i].z, a[i].w));
            const uint32_t z2 = pack_bf16(zz, zz);
            sts128(kvs + tid * 48 + 32, z2, z2, z2, z2);
        }
        mbar_arrive_if(sb + BAR_EMPTYA + 8 * ((j + lane) & 7), lane >= 3 && lane < 8);
        bar_sync(1, 256);
        TL(12, tid == 0);
        {
            uint32_t o_lo[8], o_hi[8];
#pragma unroll
            for (int hh = 0; hh < 4; hh++) {
                uint32_t b[8], zb[4], fp[4], fm[4];
                const uint32_t base = kvs + hh * 32 * 48, t = ((hh >> 1) ? pq2 : pq) + warp * 2048 + lrow;
                ldsm4(t + (((4 * (hh & 1) + ch) ^ sw) << 4), fp[0], fp[1], fp[2], fp[3]);
                ldsm4(t + (((4 * (hh & 1) + 2 + ch) ^ sw) << 4), fm[0], fm[1], fm[2], fm[3]);
                ldsm4t(base + (lane & 15) * 48 + (lane >> 4) * 16, b[0], b[1], b[2], b[3]);
                ldsm4t(base + (16 + (lane & 15)) * 48 + (lane >> 4) * 16, b[4], b[5], b[6], b[7]);
                ldsm4t(base + lane * 48 + 32, zb[0], zb[1], zb[2], zb[3]);
                float n0[4], n1[4], dn[4];
                mma16816_z(n0, fp, b[0], b[1]); mma16816_z(n1, fp, b[2], b[3]); mma16816_z(dn, fp, zb[0], zb[1]);
                mma16816(n0, fm, b[4], b[5]); mma16816(n1, fm, b[6], b[7]); mma16816(dn, fm, zb[2], zb[3]);
                const float i0 = rcp(dn[0] + 1e-6f), i1 = rcp(dn[2] + 1e-6f);
                o_lo[2 * hh] = pack_bf16(n0[0] * i0, n0[1] * i0); o_hi[2 * hh] = pack_bf16(n0[2] * i1, n0[3] * i1);
                o_lo[2 * hh + 1] = pack_bf16(n1[0] * i0, n1[1] * i0); o_hi[2 * hh + 1] = pack_bf16(n1[2] * i1, n1[3] * i1);
            }
            __syncwarp();
            mbar_arrive_if(sb + (lane ? BAR_EMPTYA + 8 * ((j + lane) & 7) : BAR_EMPTYB), lane < 3);
            rg.slot = 4; rg.phase = 0;
            const uint32_t ack = store_tile<true>(own_rows, g_o + (size_t)row_w * DM + 64 * j, o_lo, o_hi, lane);
            fence_async_smem();
            signal_after(flag_m, ack, P.zero, l0);
            TL(7, tid == 0);
        }
        {
            float acc[32];
#pragma unroll
            for (int t = 0; t < 8; t++) {
                acc[4 * t] = bf_lo(res_lo[t]); acc[4 * t + 1] = bf_hi(res_lo[t]);
                acc[4 * t + 2] = bf_lo(res_hi[t]); acc[4 * t + 3] = bf_hi(res_hi[t]);
            }
            fence_acc<32>(acc);
#pragma unroll 1
            for (int kp = 0; kp < 4; kp++) {
                mbar_waitc(sb + BAR_FULLB + 8 * rg.slot, rg.phase);
#pragma unroll
                for (int hf = 0; hf < 2; hf++) {
                    const int kt = 2 * kp + hf;
                    mbar_waitc(sb + BAR_FULLA + 8 * kt, kt != j);
                    TL(8, kt == 0 && tid == 0);
                    const desc_t da = dA + kp * (2 * SLOT >> 4), db = dB + rg.slot * (SLOT >> 4);
                    wg_fence();
#pragma unroll
                    for (int k = 0; k < 4; k++) wgmma_n64(acc, da + hf * (SLOT >> 4) + 2 * k, db + (hf * 4 + k) * 128, 1);
                    wg_commit();
                    wg_wait<1>();
                    mbar_arrive_if(sb + BAR_EMPTYA + 8 * ((kt + 7) & 7), l0 && kt > 0 && kt - 1 != j);
                    if (hf == 0) mbar_arrive_if(sb + BAR_EMPTYB + 8 * prev, l0 && kt > 0);
                }
                prev = rg.slot; rg.adv();
            }
            wg_wait<0>();
            fence_acc<32>(acc);
            mbar_arrive_if(sb + BAR_EMPTYA + 8 * 7, l0 && j != 7);
            mbar_arrive_if(sb + BAR_EMPTYB + 8 * prev, l0);
            TL(9, tid == 0);
            float s0 = 0.f, s1 = 0.f;
#pragma unroll
            for (int t = 0; t < 8; t++) {
                res_lo[t] = pack_bf16(acc[4 * t], acc[4 * t + 1]);
                res_hi[t] = pack_bf16(acc[4 * t + 2], acc[4 * t + 3]);
                s0 += acc[4 * t] + acc[4 * t + 1];
                s1 += acc[4 * t + 2] + acc[4 * t + 3];
            }
            uint32_t ack = store_tile<true>(own_rows, g_h + (size_t)row_w * DM + 64 * j, res_lo, res_hi, lane);
            s0 += __shfl_xor_sync(0xffffffffu, s0, 1); s1 += __shfl_xor_sync(0xffffffffu, s1, 1);
            s0 += __shfl_xor_sync(0xffffffffu, s0, 2); s1 += __shfl_xor_sync(0xffffffffu, s1, 2);
            const float mu0 = s0 * (1.f / 64), mu1 = s1 * (1.f / 64);
            float q0 = 0.f, q1 = 0.f;
#pragma unroll
            for (int t = 0; t < 8; t++) {
                float d;
                d = acc[4 * t] - mu0; q0 = fmaf(d, d, q0);
                d = acc[4 * t + 1] - mu0; q0 = fmaf(d, d, q0);
                d = acc[4 * t + 2] - mu1; q1 = fmaf(d, d, q1);
                d = acc[4 * t + 3] - mu1; q1 = fmaf(d, d, q1);
            }
            q0 += __shfl_xor_sync(0xffffffffu, q0, 1); q1 += __shfl_xor_sync(0xffffffffu, q1, 1);
            q0 += __shfl_xor_sync(0xffffffffu, q0, 2); q1 += __shfl_xor_sync(0xffffffffu, q1, 2);
            stg_f2_if(g_hstat + (role * 128 + 16 * warp + g + 8 * (q & 1)) * 2, q ? mu1 : mu0, q ? q1 : q0, q < 2);
            ack |= readback(g_hstat + (role * 128 + 16 * warp + g + 8 * (q & 1)) * 2);
            fence_async_smem();
            signal_after(flag_m + 32, ack, P.zero, l0);
            TL(10, tid == 0);
        }
        {
            const uint32_t cs3 = sb + OFF_CS3 + q * 16;
            float nm0, nm1;
            {
                float acc[128];
                const desc_t dB4 = dB - (256ull << 16);
#pragma unroll 1
                for (int i = 0; i < 16; i++) {
                    mbar_waitc(sb + BAR_FULLA + 8 * (i >> 1), 0);
                    mbar_waitc(sb + BAR_FULLB + 8 * rg.slot, rg.phase);
                    TL(44, tid == 0 && i == 2);
                    const desc_t da = dA + (i >> 1) * (SLOT >> 4) + (i & 1) * 4, db = dB4 + rg.slot * (SLOT >> 4);
                    wg_fence();
                    wgmma_n256(acc, da, db, i != 0);
                    wgmma_n256(acc, da + 2, db + 128, 1);
                    wg_commit();
                    wg_wait<1>();
                    mbar_arrive_if(sb + BAR_EMPTYB + 8 * prev, l0 && i > 0 && i < 15);
                    prev = rg.slot; rg.adv();
                }
                mbar_waitc(sb + BAR_CS3, 0);
                nm0 = lds_f2(sb + OFF_CS1 + (16 * warp + g) * 8).x; nm1 = lds_f2(sb + OFF_CS1 + (16 * warp + g + 8) * 8).x;
                wg_wait<0>();
                fence_acc<128>(acc);
                TL(11, tid == 0);
                bar_sync(1, 256);
                hh_stage<64, 4>(acc, cs3, nm0, nm1, sb + OFF_B + 4 * SLOT + warp * 2048, lane);
                mbar_arrive_if(sb + BAR_STG, l0);
                hh_stage<64, 4>(acc + 32, cs3 + 512, nm0, nm1, sb + OFF_B + 5 * SLOT + warp * 2048, lane);
                mbar_arrive_if(sb + BAR_STG + 8, l0);
                TL(50, tid == 0);
            }
            {
                float acc[56];
#pragma unroll 1
                for (int kt = 0; kt < 8; kt++) {
                    mbar_waitc(sb + BAR_FULLB + 8 * rg.slot, rg.phase);
                    const desc_t da = dA + kt * (SLOT >> 4), db = dB + rg.slot * (SLOT >> 4);
                    wg_fence();
#pragma unroll
                    for (int k = 0; k < 4; k++) wgmma_n112(acc, da + 2 * k, db + 128 * k, (kt | k) != 0);
                    wg_commit();
                    wg_wait<1>();
                    mbar_arrive_if(sb + BAR_EMPTYB + 8 * prev, l0 && kt > 0);
                    mbar_arrive_if(sb + BAR_EMPTYA + 8 * ((kt + 7) & 7), l0 && kt > 0);
                    prev = rg.slot; rg.adv();
                }
                wg_wait<0>();
                fence_acc<56>(acc);
                mbar_arrive_if(sb + BAR_EMPTYA + 8 * 7, l0);
                TL(13, tid == 0);
                bar_sync(1, 256);
                hh_stage<32, 3>(acc, cs3 + 1024, nm0, nm1, sb + OFF_B + 1 * SLOT + warp * 2048, lane);
                mbar_arrive_if(sb + BAR_STG + 16, l0);
                TL(52, tid == 0);
            }
        }
        {
            float acc[64];
            const desc_t dA0 = desc_lo(sb + OFF_A);
#define KT_P4(I, NK)                                                                                        \
    do {                                                                                                    \
        const int s_ = (2 * (I) + w) & 7;                                                                   \
        mbar_waitc(sb + BAR_FULLB + 8 * rg.slot, rg.phase);                                                 \
        mbar_waitc(sb + BAR_FULLA + 8 * s_, (((I) >> 2) + 1) & 1);                                          \
        TL(30 + (I), tid == 0);                                                                             \
        const desc_t dh_ = dA0 + s_ * (SLOT >> 4), dw_ = dB + rg.slot * (SLOT >> 4) + w * 512;              \
        wg_fence();                                                                                         \
        _Pragma("unroll") for (int k = 0; k < (NK); k++) wgmma_n128_tn(acc, dw_ + 128 * k, dh_ + 2 * k, ((I) | k) != 0); \
        wg_commit();                                                                                        \
        wg_wait<1>();                                                                                       \
        mbar_arrive_n_if(sb + BAR_EMPTYA + 8 * ((s_ + 6) & 7), 2, l0 && (I) > 0);                           \
        mbar_arrive_if(sb + BAR_EMPTYB + 8 * prev, l0 && (I) > 0);                                          \
        prev = rg.slot; rg.adv();                                                                           \
    } while (0)
#pragma unroll 1
            for (int i = 0; i < 8; i++) KT_P4(i, 4);
#pragma unroll 1
            for (int i = 8; i < 12; i++) KT_P4(i, 3);
            const uint32_t tile = sb + OFF_A + w * SLOT;
#pragma unroll
            for (int b = 0; b < 4; b++)
                stsm4(tile + (16 * wv + (lane & 15)) * 128 + (((2 * b + (lane >> 4)) ^ (lane & 7)) << 4),
                      res_lo[2 * b], res_hi[2 * b], res_lo[2 * b + 1], res_hi[2 * b + 1]);
            wg_wait<0>();
            fence_acc<64>(acc);
            TL(15, tid == 0);
            const uint32_t xch = sb + OFF_A + 2 * SLOT + (tid & 127) * 16;
            if (w) {
#pragma unroll
                for (int t = 0; t < 8; t++) {
                    sts128(xch + SLOT + t * 2048, __float_as_uint(acc[4 * t]), __float_as_uint(acc[4 * t + 1]),
                           __float_as_uint(acc[4 * t + 2]), __float_as_uint(acc[4 * t + 3]));
                }
#pragma unroll
                for (int t = 0; t < 32; t++) acc[t] = acc[32 + t];
            } else {
#pragma unroll
                for (int t = 0; t < 8; t++)
                    sts128(xch + t * 2048, __float_as_uint(acc[32 + 4 * t]), __float_as_uint(acc[33 + 4 * t]),
                           __float_as_uint(acc[34 + 4 * t]), __float_as_uint(acc[35 + 4 * t]));
            }
            bar_sync(1, 256);
            const uint32_t blk = tile + ((lane & 7) + (lane >> 4) * 8) * 128 + (((2 * wv + ((lane >> 3) & 1)) ^ (lane & 7)) << 4);
#pragma unroll
            for (int tp = 0; tp < 4; tp++) {
                uint32_t hr[4];
                ldsm4t(blk + tp * 2048, hr[0], hr[1], hr[2], hr[3]);
#pragma unroll
                for (int u = 0; u < 2; u++) {
                    const int t = 2 * tp + u;
                    const float4 o = lds_f4(xch + (w ^ 1) * SLOT + t * 2048);
                    const float4 st = lds_f4(sb + OFF_CS1 + (64 * w + 8 * t + 2 * q) * 8);
                    hr[2 * u] = pack_bf16(fmaf(acc[4 * t] + o.x, st.y, bf_lo(hr[2 * u])), fmaf(acc[4 * t + 1] + o.y, st.w, bf_hi(hr[2 * u])));
                    hr[2 * u + 1] = pack_bf16(fmaf(acc[4 * t + 2] + o.z, st.y, bf_lo(hr[2 * u + 1])), fmaf(acc[4 * t + 3] + o.w, st.w, bf_hi(hr[2 * u + 1])));
                }
                stsm4t(blk + tp * 2048, hr[0], hr[1], hr[2], hr[3]);
            }
            bar_sync(2 + w, 128);
#pragma unroll
            for (int i = 0; i < 4; i++) {
                const int rr = 16 * wv + 4 * i + (lane >> 3);
                const uint4 v = lds128(tile + rr * 128 + (((lane & 7) ^ (rr & 7)) << 4));
                stg128(P.out + (size_t)(128 * m + 64 * w + rr) * DM + 64 * j + (lane & 7) * 8, v.x, v.y, v.z, v.w);
            }
            if (tid == 0 && role == 0) g_epoch = epoch + 1;
            TL(16, tid == 0); TLG(1, tid == 0);
        }
    }
}

typedef CUresult (*EncodeFn)(CUtensorMap*, CUtensorMapDataType, cuuint32_t, void*, const cuuint64_t*, const cuuint64_t*,
                             const cuuint32_t*, const cuuint32_t*, CUtensorMapInterleave, CUtensorMapSwizzle,
                             CUtensorMapL2promotion, CUtensorMapFloatOOBfill);

static void make_map2d(EncodeFn enc, CUtensorMap* tm, const void* base, uint64_t cols, uint64_t rows, uint64_t pitch_elems,
                       uint32_t box_rows) {
    cuuint64_t gd[2] = {cols, rows};
    cuuint64_t gs[1] = {pitch_elems * 2};
    cuuint32_t bd[2] = {64, box_rows};
    cuuint32_t es[2] = {1, 1};
    enc(tm, CU_TENSOR_MAP_DATA_TYPE_BFLOAT16, 2, const_cast<void*>(base), gd, gs, bd, es, CU_TENSOR_MAP_INTERLEAVE_NONE,
        CU_TENSOR_MAP_SWIZZLE_128B, CU_TENSOR_MAP_L2_PROMOTION_L2_256B, CU_TENSOR_MAP_FLOAT_OOB_FILL_NONE);
}

}

extern "C" void kernel_launch(void* const* d_in, const int* in_sizes, int n_in, void* d_out, int out_size) {
    using namespace hk;
    (void)in_sizes; (void)n_in; (void)out_size;
    static EncodeFn enc = nullptr;
    static void *po = nullptr, *ph = nullptr, *phh = nullptr;
    static int std_layout = 0;
    if (!enc) {
        void* fn = nullptr;
        cudaDriverEntryPointQueryResult qr;
        cudaGetDriverEntryPoint("cuTensorMapEncodeTiled", &fn, cudaEnableDefault, &qr);
        enc = (EncodeFn)fn;
        cudaGetSymbolAddress(&po, g_o);
        cudaGetSymbolAddress(&ph, g_h);
        cudaGetSymbolAddress(&phh, g_hh);
        cudaFuncSetAttribute(fused_kernel, cudaFuncAttributeMaxDynamicSharedMemorySize, SMEM_BYTES);
        int dev = 0, sms = 0;
        cudaGetDevice(&dev);
        cudaDeviceGetAttribute(&sms, cudaDevAttrMultiProcessorCount, dev);
        cudaFuncSetAttribute(fused_kernel, cudaFuncAttributeNonPortableClusterSizeAllowed, 1);
        const int sizes[3] = {8, 9, 16}, want[3] = {15, 9, 7};
        bool ok = sms == NCTA;
        for (int i = 0; i < 3 && ok; i++) {
            cudaLaunchConfig_t cfg = {};
            cfg.gridDim = dim3(sizes[i] * 8); cfg.blockDim = dim3(NTHREADS); cfg.dynamicSmemBytes = SMEM_BYTES;
            cudaLaunchAttribute at;
            at.id = cudaLaunchAttributeClusterDimension;
            at.val.clusterDim.x = sizes[i]; at.val.clusterDim.y = 1; at.val.clusterDim.z = 1;
            cfg.attrs = &at; cfg.numAttrs = 1;
            int n = 0;
            ok = cudaOccupancyMaxActiveClusters(&n, fused_kernel, &cfg) == cudaSuccess && n == want[i];
        }
        (void)cudaGetLastError();
        std_layout = ok ? 1 : 0;
    }
    Params P;
    const __nv_bfloat16* x = (const __nv_bfloat16*)d_in[0];
    P.x = x;
    P.wqkv = (const __nv_bfloat16*)d_in[1];
    P.wphi = (const __nv_bfloat16*)d_in[2];
    P.wo = (const __nv_bfloat16*)d_in[3];
    P.wg = (const __nv_bfloat16*)d_in[5];
    P.wu = (const __nv_bfloat16*)d_in[6];
    P.wd = (const __nv_bfloat16*)d_in[7];
    P.out = (__nv_bfloat16*)d_out;
    P.use_smid = std_layout;
    P.zero = 0;
    for (int i = 0; i < NCTA; i++) {
        int role = i < 4 ? 128 + i : i - 4;
        if (std_layout) {
            const int tpc = i >> 1, odd = i & 1;
            if (tpc < 32) role = (tpc & 7) * 8 + (tpc >> 3) * 2 + odd;
            else if (tpc < 60) role = (8 + (tpc - 32) % 7) * 8 + ((tpc - 32) / 7) * 2 + odd;
            else if (tpc < 62) role = 128 + (tpc - 60) * 2 + odd;
            else role = 15 * 8 + (tpc - 62) * 2 + odd;
        }
        P.role[i] = (unsigned char)role;
    }
    make_map2d(enc, &P.tx, x, DM, SEQ, DM, 128);
    make_map2d(enc, &P.to, po, DM, SEQ, DM, 128);
    make_map2d(enc, &P.th, ph, DM, SEQ, DM, 128);
    make_map2d(enc, &P.thh, phh, FFP, SEQ, FFP, 128);
    make_map2d(enc, &P.twq, P.wqkv, 3 * DM, DM, 3 * DM, 128);
    make_map2d(enc, &P.two, P.wo, DM, DM, DM, 128);
    make_map2d(enc, &P.twg, P.wg, FF, DM, FF, 64);
    make_map2d(enc, &P.twu, P.wu, FF, DM, FF, 64);
    make_map2d(enc, &P.twd, P.wd, DM, FF, DM, 64);
    {
        cuuint64_t gd[3] = {(cuuint64_t)DM, (cuuint64_t)DM, 3};
        cuuint64_t gs[2] = {(cuuint64_t)3 * DM * 2, (cuuint64_t)DM * 2};
        cuuint32_t bd[3] = {64, 64, 2};
        cuuint32_t es[3] = {1, 1, 1};
        enc(&P.twkv, CU_TENSOR_MAP_DATA_TYPE_BFLOAT16, 3, const_cast<__nv_bfloat16*>(P.wqkv), gd, gs, bd, es,
            CU_TENSOR_MAP_INTERLEAVE_NONE, CU_TENSOR_MAP_SWIZZLE_128B, CU_TENSOR_MAP_L2_PROMOTION_L2_256B,
            CU_TENSOR_MAP_FLOAT_OOB_FILL_NONE);
    }
    for (int i = 0; i < 2; i++) {
        cuuint64_t gd[3] = {(cuuint64_t)FF - 64, (cuuint64_t)DM, 2};
        cuuint64_t gs[2] = {(cuuint64_t)FF * 2, 128};
        cuuint32_t bd[3] = {64, 32, 2};
        cuuint32_t es[3] = {1, 1, 1};
        enc(i ? &P.twu2 : &P.twg2, CU_TENSOR_MAP_DATA_TYPE_BFLOAT16, 3, const_cast<__nv_bfloat16*>(i ? P.wu : P.wg), gd, gs, bd, es,
            CU_TENSOR_MAP_INTERLEAVE_NONE, CU_TENSOR_MAP_SWIZZLE_128B, CU_TENSOR_MAP_L2_PROMOTION_L2_256B,
            CU_TENSOR_MAP_FLOAT_OOB_FILL_NONE);
    }
    fused_kernel<<<NCTA, NTHREADS, SMEM_BYTES>>>(P);
}
```

```cpp
#include <cuda_runtime.h>
#include <cuda_bf16.h>
#include <cuda.h>
#include <stdint.h>

namespace hk {

constexpr int SEQ = 2048, DM = 512, FF = 1376, FFP = 1536;
constexpr int NCTA = 132;
constexpr int NTHREADS = 384;
constexpr uint32_t SLOT = 16384;
constexpr uint32_t OFF_A = 0, OFF_B = 8 * SLOT, OFF_MISC = 14 * SLOT;
constexpr uint32_t BAR_FULLA = OFF_MISC + 0, BAR_EMPTYA = OFF_MISC + 64, BAR_FULLB = OFF_MISC + 128,
                   BAR_EMPTYB = OFF_MISC + 176, BAR_CS1 = OFF_MISC + 224, BAR_CS3 = OFF_MISC + 232,
                   BAR_CSQ = OFF_MISC + 240, BAR_CSV = OFF_MISC + 248,
                   BAR_STG = OFF_MISC + 256,
                   BAR_KVW = OFF_MISC + 280, BAR_KVR = OFF_MISC + 288;
constexpr uint32_t OFF_CS1 = OFF_MISC + 384;
constexpr uint32_t OFF_CS3 = OFF_CS1 + 1024;
constexpr uint32_t OFF_XST = OFF_CS3;
constexpr uint32_t SMEM_BYTES = OFF_CS3 + 1536;
#define KVS(j) ((j) == 3 ? 2 : 3)
constexpr int NB = 6;
constexpr int AHEAD = 3;

constexpr int ACC_KV = 0, ACC_Z = 2048, ACC_SIZE = 2176;

__device__ __align__(1024) __nv_bfloat16 g_o[SEQ * DM];
__device__ __align__(1024) __nv_bfloat16 g_h[SEQ * DM];
__device__ __align__(1024) __nv_bfloat16 g_hh[SEQ * FFP];
__device__ __align__(128) float g_hstat[SEQ * 16];
__device__ __align__(128) unsigned long long g_xstat[SEQ * 2];
__device__ __align__(128) float g_acc[8 * ACC_SIZE];
__device__ __align__(128) unsigned g_cnt[8 * 32];
__device__ __align__(128) unsigned long long g_cs[8 * 6 * 128];
__device__ __align__(128) unsigned g_flag[16 * 5 * 32];
__device__ unsigned g_epoch = 1;

#define TL(i, pred) do {} while (0)
#define TLG(i, pred) do {} while (0)

struct Params {
    CUtensorMap tx, to, th, thh, twkv, twq, two, twg, twu, twd, twg2, twu2;
    const __nv_bfloat16 *x, *wqkv, *wphi, *wo, *wg, *wu, *wd;
    __nv_bfloat16* out;
    int use_smid;
    unsigned zero;
    unsigned char role[NCTA];
};

__device__ __forceinline__ uint32_t smem_u32(const void* p) { return (uint32_t)__cvta_generic_to_shared(p); }
__device__ __forceinline__ void mbar_init(uint32_t bar, uint32_t cnt) {
    asm volatile("mbarrier.init.shared::cta.b64 [%0], %1;" ::"r"(bar), "r"(cnt) : "memory");
}
__device__ __forceinline__ void mbar_expect_tx(uint32_t bar, uint32_t bytes) {
    asm volatile("mbarrier.arrive.expect_tx.shared::cta.b64 _, [%0], %1;" ::"r"(bar), "r"(bytes) : "memory");
}
__device__ __forceinline__ void mbar_arrive(uint32_t bar) {
    asm volatile("mbarrier.arrive.shared::cta.b64 _, [%0];" ::"r"(bar) : "memory");
}
__device__ __forceinline__ void mbar_arrive_if(uint32_t bar, bool pred) {
    asm volatile("{.reg .pred p; setp.ne.u32 p, %1, 0; @p mbarrier.arrive.shared::cta.b64 _, [%0];}" ::"r"(bar), "r"((uint32_t)pred) : "memory");
}
__device__ __forceinline__ bool mbar_try(uint32_t bar, uint32_t parity) {
    uint32_t ok;
    asm volatile("{.reg .pred p; mbarrier.try_wait.parity.shared::cta.b64 p, [%1], %2; selp.u32 %0,1,0,p;}"
                 : "=r"(ok) : "r"(bar), "r"(parity) : "memory");
    return ok;
}
__device__ __forceinline__ bool mbar_test(uint32_t bar, uint32_t parity) {
    uint32_t ok;
    asm volatile("{.reg .pred p; mbarrier.test_wait.parity.shared::cta.b64 p, [%1], %2; selp.u32 %0,1,0,p;}"
                 : "=r"(ok) : "r"(bar), "r"(parity) : "memory");
    return ok;
}
__device__ __forceinline__ void trap_if_gt(uint32_t v, uint32_t lim) {
    asm volatile("{.reg .pred p; setp.gt.u32 p, %0, %1; @p trap;}" ::"r"(v), "r"(lim));
}
__device__ __forceinline__ void mbar_wait(uint32_t bar, uint32_t parity) {
    asm volatile("{\n"
                 ".reg .pred P1, P2;\n"
                 ".reg .u32 c;\n"
                 "mov.u32 c, 0;\n"
                 "LAB_WAIT:\n"
                 "mbarrier.try_wait.parity.shared::cta.b64 P1, [%0], %1;\n"
                 "@P1 bra LAB_DONE;\n"
                 "add.u32 c, c, 1;\n"
                 "setp.gt.u32 P2, c, 4194304;\n"
                 "@P2 trap;\n"
                 "bra LAB_WAIT;\n"
                 "LAB_DONE:\n"
                 "}" ::"r"(bar), "r"(parity) : "memory");
}
__device__ __forceinline__ void mbar_waitc(uint32_t bar, uint32_t parity) {
    asm volatile("{\n"
                 ".reg .pred P1;\n"
                 "LAB_WAIT:\n"
                 "mbarrier.try_wait.parity.shared::cta.b64 P1, [%0], %1;\n"
                 "@!P1 bra LAB_WAIT;\n"
                 "}" ::"r"(bar), "r"(parity) : "memory");
}
__device__ __forceinline__ void tma2d(uint32_t dst, const CUtensorMap* tm, uint32_t bar, int c0, int c1) {
    asm volatile("cp.async.bulk.tensor.2d.shared::cluster.global.mbarrier::complete_tx::bytes [%0], [%1, {%3, %4}], [%2];"
                 ::"r"(dst), "l"(tm), "r"(bar), "r"(c0), "r"(c1) : "memory");
}
__device__ __forceinline__ void tma3d(uint32_t dst, const CUtensorMap* tm, uint32_t bar, int c0, int c1, int c2) {
    asm volatile("cp.async.bulk.tensor.3d.shared::cluster.global.mbarrier::complete_tx::bytes [%0], [%1, {%3, %4, %5}], [%2];"
                 ::"r"(dst), "l"(tm), "r"(bar), "r"(c0), "r"(c1), "r"(c2) : "memory");
}
__device__ __forceinline__ bool elect_one() {
    uint32_t ok;
    asm volatile("{.reg .pred p; elect.sync _|p, 0xffffffff; selp.u32 %0, 1, 0, p;}" : "=r"(ok));
    return ok;
}
__device__ __forceinline__ void prefetch_tmap(const CUtensorMap* tm) {
    asm volatile("prefetch.tensormap [%0];" ::"l"(tm) : "memory");
}
__device__ __forceinline__ void prefetch_l2(const void* p, uint32_t bytes) {
    asm volatile("cp.async.bulk.prefetch.L2.global [%0], %1;" ::"l"(p), "r"(bytes) : "memory");
}
__device__ __forceinline__ unsigned ld_acquire(const unsigned* p) {
    unsigned v; asm volatile("ld.acquire.gpu.global.u32 %0, [%1];" : "=r"(v) : "l"(p) : "memory"); return v;
}
__device__ __forceinline__ uint4 ld_acquire4(const unsigned* p) {
    uint4 v;
    asm volatile("ld.acquire.gpu.global.v4.u32 {%0,%1,%2,%3}, [%4];" : "=r"(v.x), "=r"(v.y), "=r"(v.z), "=r"(v.w) : "l"(p) : "memory");
    return v;
}
__device__ __forceinline__ unsigned ld_relaxed(const unsigned* p) {
    unsigned v; asm volatile("ld.relaxed.gpu.global.u32 %0, [%1];" : "=r"(v) : "l"(p)); return v;
}
__device__ __forceinline__ void st_relaxed(unsigned* p, unsigned v) {
    asm volatile("st.relaxed.gpu.global.u32 [%0], %1;" ::"l"(p), "r"(v) : "memory");
}
__device__ __forceinline__ void red_relaxed(unsigned* p, unsigned v) {
    asm volatile("red.relaxed.gpu.global.add.u32 [%0], %1;" ::"l"(p), "r"(v) : "memory");
}
__device__ __forceinline__ void fence_gpu() { asm volatile("fence.acq_rel.gpu;" ::: "memory"); }
__device__ __forceinline__ void fence_async_smem() { asm volatile("fence.proxy.async.shared::cta;" ::: "memory"); }
__device__ __forceinline__ void fence_async_global() { asm volatile("fence.proxy.async.global;" ::: "memory"); }
__device__ __forceinline__ void wait_count(const unsigned* p, unsigned target) {
    uint32_t it = 0;
    while ((int)(ld_acquire(p) - target) < 0) trap_if_gt(++it, 1u << 22);
}
__device__ __forceinline__ void wait_count_warp(const unsigned* p, unsigned target) {
    uint32_t it = 0;
    while (__any_sync(0xffffffffu, (int)(ld_acquire(p) - target) < 0)) trap_if_gt(++it, 1u << 22);
}
__device__ __forceinline__ void red_f32(float* p, float a) {
    asm volatile("red.relaxed.gpu.global.add.f32 [%0], %1;" ::"l"(p), "f"(a) : "memory");
}
__device__ __forceinline__ void red_f32x2(float* p, float a, float b) {
    asm volatile("red.relaxed.gpu.global.add.v2.f32 [%0], {%1, %2};" ::"l"(p), "f"(a), "f"(b) : "memory");
}
__device__ __forceinline__ void red_f32x4(float* p, float a, float b, float c, float d) {
    asm volatile("red.relaxed.gpu.global.add.v4.f32 [%0], {%1, %2, %3, %4};" ::"l"(p), "f"(a), "f"(b), "f"(c), "f"(d) : "memory");
}
__device__ __forceinline__ float4 ld_l2_f4(const float* p) {
    float4 v;
    asm volatile("ld.relaxed.gpu.global.v4.f32 {%0,%1,%2,%3}, [%4];" : "=f"(v.x), "=f"(v.y), "=f"(v.z), "=f"(v.w) : "l"(p) : "memory");
    return v;
}
__device__ __forceinline__ float2 ld_l2_f2(const float* p) {
    float2 v;
    asm volatile("ld.relaxed.gpu.global.v2.f32 {%0,%1}, [%2];" : "=f"(v.x), "=f"(v.y) : "l"(p) : "memory");
    return v;
}
__device__ __forceinline__ float ld_l2_f(const float* p) {
    float v;
    asm volatile("ld.relaxed.gpu.global.f32 %0, [%1];" : "=f"(v) : "l"(p) : "memory");
    return v;
}
__device__ __forceinline__ uint4 ldg_nc(const void* p) {
    uint4 v;
    asm volatile("ld.global.nc.L1::no_allocate.v4.u32 {%0,%1,%2,%3}, [%4];" : "=r"(v.x), "=r"(v.y), "=r"(v.z), "=r"(v.w) : "l"(p));
    return v;
}
__device__ __forceinline__ void stg128(void* p, uint32_t a, uint32_t b, uint32_t c, uint32_t d) {
    asm volatile("st.global.v4.u32 [%0], {%1,%2,%3,%4};" ::"l"(p), "r"(a), "r"(b), "r"(c), "r"(d) : "memory");
}
__device__ __forceinline__ uint4 lds128(uint32_t a) {
    uint4 v;
    asm volatile("ld.shared.v4.u32 {%0,%1,%2,%3}, [%4];" : "=r"(v.x), "=r"(v.y), "=r"(v.z), "=r"(v.w) : "r"(a) : "memory");
    return v;
}
__device__ __forceinline__ float2 lds_f2(uint32_t a) {
    float2 v;
    asm volatile("ld.shared.v2.f32 {%0,%1}, [%2];" : "=f"(v.x), "=f"(v.y) : "r"(a) : "memory");
    return v;
}
__device__ __forceinline__ void sts_f2(uint32_t a, float x, float y) {
    asm volatile("st.shared.v2.f32 [%0], {%1,%2};" ::"r"(a), "f"(x), "f"(y) : "memory");
}
__device__ __forceinline__ void sts64(uint32_t a, uint32_t x, uint32_t y) {
    asm volatile("st.shared.v2.u32 [%0], {%1,%2};" ::"r"(a), "r"(x), "r"(y) : "memory");
}
__device__ __forceinline__ void sts128(uint32_t a, uint32_t x, uint32_t y, uint32_t z, uint32_t w) {
    asm volatile("st.shared.v4.u32 [%0], {%1,%2,%3,%4};" ::"r"(a), "r"(x), "r"(y), "r"(z), "r"(w) : "memory");
}
__device__ __forceinline__ void stsm4(uint32_t a, uint32_t r0, uint32_t r1, uint32_t r2, uint32_t r3) {
    asm volatile("stmatrix.sync.aligned.m8n8.x4.shared.b16 [%0], {%1,%2,%3,%4};" ::"r"(a), "r"(r0), "r"(r1), "r"(r2), "r"(r3) : "memory");
}
__device__ __forceinline__ void stsm4t(uint32_t a, uint32_t r0, uint32_t r1, uint32_t r2, uint32_t r3) {
    asm volatile("stmatrix.sync.aligned.m8n8.x4.trans.shared.b16 [%0], {%1,%2,%3,%4};" ::"r"(a), "r"(r0), "r"(r1), "r"(r2), "r"(r3) : "memory");
}
__device__ __forceinline__ void tma_store2d(const CUtensorMap* tm, uint32_t src, int c0, int c1) {
    asm volatile("cp.async.bulk.tensor.2d.global.shared::cta.bulk_group [%0, {%2, %3}], [%1];" ::"l"(tm), "r"(src), "r"(c0), "r"(c1) : "memory");
    asm volatile("cp.async.bulk.commit_group;" ::: "memory");
}
__device__ __forceinline__ void ldsm4(uint32_t a, uint32_t& r0, uint32_t& r1, uint32_t& r2, uint32_t& r3) {
    asm volatile("ldmatrix.sync.aligned.m8n8.x4.shared.b16 {%0,%1,%2,%3}, [%4];" : "=r"(r0), "=r"(r1), "=r"(r2), "=r"(r3) : "r"(a) : "memory");
}
__device__ __forceinline__ void ldsm4t(uint32_t a, uint32_t& r0, uint32_t& r1, uint32_t& r2, uint32_t& r3) {
    asm volatile("ldmatrix.sync.aligned.m8n8.x4.trans.shared.b16 {%0,%1,%2,%3}, [%4];" : "=r"(r0), "=r"(r1), "=r"(r2), "=r"(r3) : "r"(a) : "memory");
}
__device__ __forceinline__ void mma16816(float* c, const uint32_t* a, uint32_t b0, uint32_t b1) {
    asm("mma.sync.aligned.m16n8k16.row.col.f32.bf16.bf16.f32 {%0,%1,%2,%3}, {%4,%5,%6,%7}, {%8,%9}, {%0,%1,%2,%3};"
                 : "+f"(c[0]), "+f"(c[1]), "+f"(c[2]), "+f"(c[3])
                 : "r"(a[0]), "r"(a[1]), "r"(a[2]), "r"(a[3]), "r"(b0), "r"(b1));
}
__device__ __forceinline__ uint32_t pack_bf16(float lo, float hi) {
    uint32_t r; asm("cvt.rn.bf16x2.f32 %0, %1, %2;" : "=r"(r) : "f"(hi), "f"(lo)); return r;
}
__device__ __forceinline__ float bf_lo(uint32_t w) { return __uint_as_float(w << 16); }
__device__ __forceinline__ float bf_hi(uint32_t w) { return __uint_as_float(w & 0xffff0000u); }
__device__ __forceinline__ float ex2(float x) { float r; asm("ex2.approx.ftz.f32 %0, %1;" : "=f"(r) : "f"(x)); return r; }
__device__ __forceinline__ float rcp(float x) { float r; asm("rcp.approx.ftz.f32 %0, %1;" : "=f"(r) : "f"(x)); return r; }
__device__ __forceinline__ void bar_sync(int id, int n) { asm volatile("bar.sync %0, %1;" ::"r"(id), "r"(n) : "memory"); }

typedef unsigned long long desc_t;
__device__ __forceinline__ desc_t desc_lo(uint32_t addr) { return (desc_t)(((addr & 0x3FFFF) >> 4) | (512u << 16)) | (0x40000040ull << 32); }
__device__ __forceinline__ void wg_fence() { asm volatile("wgmma.fence.sync.aligned;" ::: "memory"); }
__device__ __forceinline__ void wg_commit() { asm volatile("wgmma.commit_group.sync.aligned;" ::: "memory"); }
template <int N> __device__ __forceinline__ void wg_wait() { asm volatile("wgmma.wait_group.sync.aligned %0;" ::"n"(N) : "memory"); }
template <int N> __device__ __forceinline__ void fence_acc(float* d) {
#pragma unroll
    for (int i = 0; i < N; i++) asm volatile("" : "+f"(d[i])::"memory");
}
#define R4(o) "+f"(d[o + 0]), "+f"(d[o + 1]), "+f"(d[o + 2]), "+f"(d[o + 3])
#define R8(o) R4(o), R4(o + 4)
__device__ __forceinline__ void wgmma_n128(float* d, desc_t da, desc_t db, int sc) {
    asm volatile("{.reg .pred p; setp.ne.b32 p, %66, 0;\n"
                 "wgmma.mma_async.sync.aligned.m64n128k16.f32.bf16.bf16 {%0,%1,%2,%3,%4,%5,%6,%7,%8,%9,%10,%11,%12,%13,%14,%15,%16,%17,%18,%19,%20,%21,%22,%23,%24,%25,%26,%27,%28,%29,%30,%31,"
                 "%32,%33,%34,%35,%36,%37,%38,%39,%40,%41,%42,%43,%44,%45,%46,%47,%48,%49,%50,%51,%52,%53,%54,%55,%56,%57,%58,%59,%60,%61,%62,%63}, %64, %65, p, 1, 1, 0, 1;}"
                 : R8(0), R8(8), R8(16), R8(24), R8(32), R8(40), R8(48), R8(56)
                 : "l"(da), "l"(db), "r"(sc));
}
__device__ __forceinline__ void wgmma_n256(float* d, desc_t da, desc_t db, int sc) {
    asm volatile("{.reg .pred p; setp.ne.b32 p, %130, 0;\n"
                 "wgmma.mma_async.sync.aligned.m64n256k16.f32.bf16.bf16 {%0,%1,%2,%3,%4,%5,%6,%7,%8,%9,%10,%11,%12,%13,%14,%15,%16,%17,%18,%19,%20,%21,%22,%23,%24,%25,%26,%27,%28,%29,%30,%31,%32,%33,%34,%35,%36,%37,%38,%39,%40,%41,%42,%43,%44,%45,%46,%47,%48,%49,%50,%51,%52,%53,%54,%55,%56,%57,%58,%59,%60,%61,%62,%63,%64,%65,%66,%67,%68,%69,%70,%71,%72,%73,%74,%75,%76,%77,%78,%79,%80,%81,%82,%83,%84,%85,%86,%87,%88,%89,%90,%91,%92,%93,%94,%95,%96,%97,%98,%99,%100,%101,%102,%103,%104,%105,%106,%107,%108,%109,%110,%111,%112,%113,%114,%115,%116,%117,%118,%119,%120,%121,%122,%123,%124,%125,%126,%127}, %128, %129, p, 1, 1, 0, 1;}"
                 : R8(0), R8(8), R8(16), R8(24), R8(32), R8(40), R8(48), R8(56), R8(64), R8(72), R8(80), R8(88), R8(96), R8(104), R8(112), R8(120)
                 : "l"(da), "l"(db), "r"(sc));
}
__device__ __forceinline__ void wgmma_n112(float* d, desc_t da, desc_t db, int sc) {
    asm volatile("{.reg .pred p; setp.ne.b32 p, %58, 0;\n"
                 "wgmma.mma_async.sync.aligned.m64n112k16.f32.bf16.bf16 {%0,%1,%2,%3,%4,%5,%6,%7,%8,%9,%10,%11,%12,%13,%14,%15,%16,%17,%18,%19,%20,%21,%22,%23,%24,%25,%26,%27,%28,%29,%30,%31,%32,%33,%34,%35,%36,%37,%38,%39,%40,%41,%42,%43,%44,%45,%46,%47,%48,%49,%50,%51,%52,%53,%54,%55}, %56, %57, p, 1, 1, 0, 1;}"
                 : R8(0), R8(8), R8(16), R8(24), R8(32), R8(40), R8(48)
                 : "l"(da), "l"(db), "r"(sc));
}
__device__ __forceinline__ void wgmma_n128_tn(float* d, desc_t da, desc_t db, int sc) {
    asm volatile("{.reg .pred p; setp.ne.b32 p, %66, 0;\n"
                 "wgmma.mma_async.sync.aligned.m64n128k16.f32.bf16.bf16 {%0,%1,%2,%3,%4,%5,%6,%7,%8,%9,%10,%11,%12,%13,%14,%15,%16,%17,%18,%19,%20,%21,%22,%23,%24,%25,%26,%27,%28,%29,%30,%31,%32,%33,%34,%35,%36,%37,%38,%39,%40,%41,%42,%43,%44,%45,%46,%47,%48,%49,%50,%51,%52,%53,%54,%55,%56,%57,%58,%59,%60,%61,%62,%63}, %64, %65, p, 1, 1, 1, 0;}"
                 : R8(0), R8(8), R8(16), R8(24), R8(32), R8(40), R8(48), R8(56)
                 : "l"(da), "l"(db), "r"(sc));
}
__device__ __forceinline__ void wgmma_n64(float* d, desc_t da, desc_t db, int sc) {
    asm volatile("{.reg .pred p; setp.ne.b32 p, %34, 0;\n"
                 "wgmma.mma_async.sync.aligned.m64n64k16.f32.bf16.bf16 {%0,%1,%2,%3,%4,%5,%6,%7,%8,%9,%10,%11,%12,%13,%14,%15,%16,%17,%18,%19,%20,%21,%22,%23,%24,%25,%26,%27,%28,%29,%30,%31}, %32, %33, p, 1, 1, 0, 1;}"
                 : R8(0), R8(8), R8(16), R8(24)
                 : "l"(da), "l"(db), "r"(sc));
}
__device__ __forceinline__ void wgmma_n40_tt(float* d, desc_t da, desc_t db, int sc) {
    asm volatile("{.reg .pred p; setp.ne.b32 p, %22, 0;\n"
                 "wgmma.mma_async.sync.aligned.m64n40k16.f32.bf16.bf16 {%0,%1,%2,%3,%4,%5,%6,%7,%8,%9,%10,%11,%12,%13,%14,%15,%16,%17,%18,%19}, %20, %21, p, 1, 1, 1, 1;}"
                 : R8(0), R8(8), R4(16)
                 : "l"(da), "l"(db), "r"(sc));
}

__device__ __forceinline__ void wgmma_n8_tt(float* d, desc_t da, desc_t db, int sc) {
    asm volatile("{.reg .pred p; setp.ne.b32 p, %6, 0;\n"
                 "wgmma.mma_async.sync.aligned.m64n8k16.f32.bf16.bf16 {%0,%1,%2,%3}, %4, %5, p, 1, 1, 1, 1;}"
                 : R4(0)
                 : "l"(da), "l"(db), "r"(sc));
}

__device__ __forceinline__ uint32_t readback(const void* p) {
    uint32_t v; asm volatile("ld.relaxed.gpu.global.u32 %0, [%1];" : "=r"(v) : "l"(p) : "memory"); return v;
}
__device__ __forceinline__ uint32_t atom_f32x2(float* p, float a, float b) {
    float x, y;
    asm volatile("atom.relaxed.gpu.global.add.v2.f32 {%0,%1}, [%2], {%3,%4};" : "=f"(x), "=f"(y) : "l"(p), "f"(a), "f"(b) : "memory");
    return __float_as_uint(x);
}
__device__ __forceinline__ uint32_t atom_f32_if(float* p, float a, bool pred) {
    float x = 0.f;
    asm volatile("{.reg .pred p; setp.ne.u32 p, %3, 0; @p atom.relaxed.gpu.global.add.f32 %0, [%1], %2;}" : "+f"(x) : "l"(p), "f"(a), "r"((uint32_t)pred) : "memory");
    return __float_as_uint(x);
}
__device__ __forceinline__ void signal_after(unsigned* cnt, uint32_t ack, uint32_t zero, bool pred) {
    asm volatile("{.reg .pred p; setp.ne.u32 p, %2, 0; @p red.relaxed.gpu.global.add.u32 [%0], %1;}"
                 ::"l"(cnt), "r"((ack & zero) + 1), "r"((uint32_t)pred) : "memory");
}
__device__ __forceinline__ void signal_late(unsigned* cnt, const uint32_t* a, uint32_t zero, bool pred) {
    uint32_t v;
    asm volatile("{.reg .b32 t; lop3.b32 t, %1, %2, %3, 0xfe; lop3.b32 t, t, %4, %5, 0xfe; lop3.b32 t, t, %6, %7, 0xfe; or.b32 %0, t, %8;}"
                 : "=r"(v) : "r"(a[0]), "r"(a[1]), "r"(a[2]), "r"(a[3]), "r"(a[4]), "r"(a[5]), "r"(a[6]), "r"(a[7]));
    signal_after(cnt, v, zero, pred);
}
__device__ __forceinline__ void red_f32_if(float* p, float a, bool pred) {
    asm volatile("{.reg .pred p; setp.ne.u32 p, %2, 0; @p red.relaxed.gpu.global.add.f32 [%0], %1;}" ::"l"(p), "f"(a), "r"((uint32_t)pred) : "memory");
}
__device__ __forceinline__ void stg_f2_if(float* p, float a, float b, bool pred) {
    asm volatile("{.reg .pred p; setp.ne.u32 p, %3, 0; @p st.global.v2.f32 [%0], {%1,%2};}" ::"l"(p), "f"(a), "f"(b), "r"((uint32_t)pred) : "memory");
}
__device__ __forceinline__ void stg64(void* p, uint32_t a, uint32_t b) {
    asm volatile("st.global.v2.u32 [%0], {%1,%2};" ::"l"(p), "r"(a), "r"(b) : "memory");
}
__device__ __forceinline__ void mma16816_z(float* c, const uint32_t* a, uint32_t b0, uint32_t b1) {
    asm("mma.sync.aligned.m16n8k16.row.col.f32.bf16.bf16.f32 {%0,%1,%2,%3}, {%4,%5,%6,%7}, {%8,%9}, {%10,%10,%10,%10};"
                 : "=f"(c[0]), "=f"(c[1]), "=f"(c[2]), "=f"(c[3])
                 : "r"(a[0]), "r"(a[1]), "r"(a[2]), "r"(a[3]), "r"(b0), "r"(b1), "f"(0.f));
}
__device__ __forceinline__ uint32_t max2(uint32_t a, uint32_t b) { uint32_t r; asm("max.bf16x2 %0, %1, %2;" : "=r"(r) : "r"(a), "r"(b)); return r; }
__device__ __forceinline__ uint32_t min2(uint32_t a, uint32_t b) { uint32_t r; asm("min.bf16x2 %0, %1, %2;" : "=r"(r) : "r"(a), "r"(b)); return r; }
__device__ __forceinline__ void bar_arrive(int id, int n) { asm volatile("bar.arrive %0, %1;" ::"r"(id), "r"(n) : "memory"); }
__device__ __forceinline__ void mbar_arrive_n_if(uint32_t bar, uint32_t n, bool pred) {
    asm volatile("{.reg .pred p; setp.ne.u32 p, %1, 0; @p mbarrier.arrive.shared::cta.b64 _, [%0], %2;}" ::"r"(bar), "r"((uint32_t)pred), "r"(n) : "memory");
}
__device__ __forceinline__ float4 lds_f4(uint32_t a) {
    float4 v;
    asm volatile("ld.shared.v4.f32 {%0,%1,%2,%3}, [%4];" : "=f"(v.x), "=f"(v.y), "=f"(v.z), "=f"(v.w) : "r"(a) : "memory");
    return v;
}
__device__ __forceinline__ uint4 ld_tagged(const unsigned long long* p) {
    unsigned long long a, b;
    asm volatile("ld.acquire.gpu.global.v2.b64 {%0,%1}, [%2];" : "=l"(a), "=l"(b) : "l"(p) : "memory");
    return make_uint4((unsigned)a, (unsigned)(a >> 32), (unsigned)b, (unsigned)(b >> 32));
}
__device__ __forceinline__ uint4 ld_tagged_rlx(const unsigned long long* p) {
    unsigned long long a, b;
    asm volatile("ld.relaxed.gpu.global.v2.b64 {%0,%1}, [%2];" : "=l"(a), "=l"(b) : "l"(p) : "memory");
    return make_uint4((unsigned)a, (unsigned)(a >> 32), (unsigned)b, (unsigned)(b >> 32));
}
__device__ __forceinline__ void st_tagged_if(unsigned long long* p, float a, float b, unsigned tag, bool pred) {
    const unsigned long long t = (unsigned long long)tag << 32;
    asm volatile("{.reg .pred p; setp.ne.u32 p, %3, 0; @p st.relaxed.gpu.global.v2.b64 [%0], {%1,%2};}"
                 ::"l"(p), "l"(t | __float_as_uint(a)), "l"(t | __float_as_uint(b)), "r"((uint32_t)pred) : "memory");
}

template <bool ACK>
__device__ __forceinline__ uint32_t store_tile(uint32_t tile_rows, __nv_bfloat16* gdst, const uint32_t* lo, const uint32_t* hi, int lane) {
    const int r = lane & 15;
#pragma unroll
    for (int b = 0; b < 4; b++)
        stsm4(tile_rows + r * 128 + (((2 * b + (lane >> 4)) ^ (r & 7)) << 4), lo[2 * b], hi[2 * b], lo[2 * b + 1], hi[2 * b + 1]);
    __syncwarp();
    uint32_t ack = 0;
#pragma unroll
    for (int i = 0; i < 4; i++) {
        const int rr = 4 * i + (lane >> 3);
        const uint4 v = lds128(tile_rows + rr * 128 + (((lane & 7) ^ (rr & 7)) << 4));
        stg128(gdst + rr * DM + (lane & 7) * 8, v.x, v.y, v.z, v.w);
    }
    if (ACK) {
#pragma unroll
        for (int i = 0; i < 4; i++) ack |= readback(gdst + (4 * i + (lane >> 3)) * DM + (lane & 7) * 8);
    }
    return ack;
}

__device__ __forceinline__ void feature_map(const uint32_t* a, const uint32_t* wb, float c0, float c1, uint32_t* plus, uint32_t* minus) {
    float p[8];
    mma16816_z(p, a, wb[0], wb[1]);
    mma16816_z(p + 4, a, wb[2], wb[3]);
    const uint32_t P0 = pack_bf16(p[0], p[2]), P1 = pack_bf16(p[1], p[3]), P2 = pack_bf16(p[4], p[6]), P3 = pack_bf16(p[5], p[7]);
    uint32_t mx = max2(max2(P0, P1), max2(P2, P3)), mn = min2(min2(P0, P1), min2(P2, P3));
#pragma unroll
    for (int s = 1; s <= 2; s <<= 1) {
        mx = max2(mx, __shfl_xor_sync(0xffffffffu, mx, s));
        mn = min2(mn, __shfl_xor_sync(0xffffffffu, mn, s));
    }
    const float mx0 = bf_lo(mx) * c0, mx1 = bf_hi(mx) * c1, mn0 = bf_lo(mn) * c0, mn1 = bf_hi(mn) * c1;
    p[0] = bf_lo(P0); p[2] = bf_hi(P0); p[1] = bf_lo(P1); p[3] = bf_hi(P1);
    p[4] = bf_lo(P2); p[6] = bf_hi(P2); p[5] = bf_lo(P3); p[7] = bf_hi(P3);
    float ep[8], em[8];
#pragma unroll
    for (int i = 0; i < 8; i++) {
        const bool r1 = (i & 2);
        ep[i] = ex2(fmaf(p[i], r1 ? c1 : c0, r1 ? -mx1 : -mx0));
        em[i] = ex2(fmaf(p[i], r1 ? -c1 : -c0, r1 ? mn1 : mn0));
    }
    float sp[4], sm[4];
#pragma unroll
    for (int i = 0; i < 4; i++) { plus[i] = pack_bf16(ep[2 * i], ep[2 * i + 1]); minus[i] = pack_bf16(em[2 * i], em[2 * i + 1]); }
    mma16816_z(sp, plus, 0x3f803f80u, 0x3f803f80u);
    mma16816_z(sm, minus, 0x3f803f80u, 0x3f803f80u);
    const float rs[4] = {rcp(sp[0]), rcp(sp[2]), rcp(sm[0]), rcp(sm[2])};
#pragma unroll
    for (int i = 0; i < 4; i++) {
        plus[i] = pack_bf16(ep[2 * i] * rs[i & 1], ep[2 * i + 1] * rs[i & 1]);
        minus[i] = pack_bf16(em[2 * i] * rs[2 + (i & 1)], em[2 * i + 1] * rs[2 + (i & 1)]);
    }
}

template <bool SCALE>
__device__ __forceinline__ void ln_frag(const float* acc, uint32_t cs_addr, float rs0, float nm0, float rs1, float nm1, uint32_t* a) {
    const float2 c0 = lds_f2(cs_addr), c1 = lds_f2(cs_addr + 32);
    const float s0 = SCALE ? rs0 : 1.f, s1 = SCALE ? rs1 : 1.f;
    a[0] = pack_bf16(fmaf(nm0, c0.x, acc[0]) * s0, fmaf(nm0, c0.y, acc[1]) * s0);
    a[1] = pack_bf16(fmaf(nm1, c0.x, acc[2]) * s1, fmaf(nm1, c0.y, acc[3]) * s1);
    a[2] = pack_bf16(fmaf(nm0, c1.x, acc[4]) * s0, fmaf(nm0, c1.y, acc[5]) * s0);
    a[3] = pack_bf16(fmaf(nm1, c1.x, acc[6]) * s1, fmaf(nm1, c1.y, acc[7]) * s1);
}

template <int UP>
__device__ __forceinline__ uint32_t hh_pair(const float* ag, float4 cs, float nmean) {
    const float g0 = fmaf(nmean, cs.x, ag[0]), g1 = fmaf(nmean, cs.y, ag[1]);
    const float u0 = fmaf(nmean, cs.z, ag[UP]), u1 = fmaf(nmean, cs.w, ag[UP + 1]);
    return pack_bf16(g0 * u0, g1 * u1);
}
template <int UP, int NTP>
__device__ __forceinline__ void hh_stage(const float* acc, uint32_t cs3, float nm0, float nm1, uint32_t stg, int lane) {
#pragma unroll
    for (int tp = 0; tp < NTP; tp++) {
        const float4 c0 = lds_f4(cs3 + tp * 128), c1 = lds_f4(cs3 + tp * 128 + 64);
        stsm4(stg + (lane & 15) * 128 + (((2 * tp + (lane >> 4)) ^ (lane & 7)) << 4), hh_pair<UP>(acc + 8 * tp, c0, nm0),
              hh_pair<UP>(acc + 8 * tp + 2, c0, nm1), hh_pair<UP>(acc + 8 * tp + 4, c1, nm0), hh_pair<UP>(acc + 8 * tp + 6, c1, nm1));
    }
    fence_async_smem();
    __syncwarp();
}

struct Ring {
    int slot; uint32_t phase;
    __device__ __forceinline__ void adv() { if (++slot == NB) { slot = 0; phase ^= 1; } }
};

__global__ void __launch_bounds__(NTHREADS, 1) fused_kernel(const __grid_constant__ Params P) {
    extern __shared__ __align__(1024) uint8_t smem_raw[];
    const uint32_t sb = smem_u32(smem_raw);
    const int tid = threadIdx.x, lane = tid & 31;
    const int warp = __shfl_sync(0xffffffffu, tid >> 5, 0);
    unsigned role = blockIdx.x;
    if (P.use_smid) asm volatile("mov.u32 %0, %%smid;" : "=r"(role));
    role = P.role[role];
    const int m = role >> 3, j = role & 7;
    const bool helper = role >= 128;

    TL(0, tid == 0); TLG(0, tid == 0);
    float* const acc_j = g_acc + j * ACC_SIZE;
    unsigned* const cnt_j = g_cnt + j * 32;

    if (__builtin_expect(warp >= 8, 1)) {
        asm volatile("setmaxnreg.dec.sync.aligned.u32 72;");
        if (elect_one()) {
            if (warp == 8) {
                if (!helper) {
#pragma unroll
                    for (int i = 0; i < NB; i++) mbar_init(sb + BAR_FULLB + 8 * i, 1);
#pragma unroll
                    for (int i = 0; i < 2; i++) {
                        mbar_expect_tx(sb + BAR_FULLB + 8 * i, SLOT);
                        tma3d(sb + OFF_B + i * SLOT, &P.twkv, sb + BAR_FULLB + 8 * i, 64 * j, 64 * i, 1);
                    }
                }
            } else if (warp == 9) {
#pragma unroll
                for (int i = 0; i < 8; i++) mbar_init(sb + BAR_FULLA + 8 * i, 1);
#pragma unroll
                for (int i = 0; i < 2; i++) {
                    mbar_expect_tx(sb + BAR_FULLA + 8 * i, SLOT);
                    tma2d(sb + OFF_A + i * SLOT, helper ? &P.twq : &P.tx, sb + BAR_FULLA + 8 * i, helper ? DM + 128 * j : 64 * i, 128 * (helper ? i : m));
                }
            } else if (warp == 10) {
#pragma unroll
                for (int i = 0; i < 9; i++) mbar_init(sb + BAR_CS1 + 8 * i, i == 0 || i == 8 ? 64 : (i == 1 ? 96 : (i < 4 ? 32 : 8)));
                trap_if_gt(sb & 1023, 0);
            } else {
#pragma unroll
                for (int i = 0; i < 14; i++) mbar_init(sb + (i < 8 ? BAR_EMPTYA : BAR_EMPTYB - 64) + 8 * i, 8);
            }
        }
        __syncwarp();
        const unsigned epoch = ld_relaxed(&g_epoch);
        bar_sync(0, NTHREADS);
        if (helper) {
            if (warp == 8) {
                if (elect_one()) {
#pragma unroll 1
                    for (int i = 2; i < 72; i++) {
                        const uint32_t full = sb + BAR_FULLA + 8 * (i & 7), dst = sb + OFF_A + (i & 7) * SLOT;
                        mbar_wait(sb + BAR_EMPTYA + 8 * (i & 7), ((i >> 3) & 1) ^ 1);
                        mbar_expect_tx(full, SLOT);
                        if (i < 24) {
                            tma2d(dst, &P.twq, full, (i < 16 ? DM + 64 * (i & 8) : 0) + 128 * j + 16 * (i & 4), 128 * (i & 3));
                        } else {
                            const int u = (i >> 3) - 3, c0 = 176 * (2 * j + (u & 1)) + 64 * (u >> 1);
                            tma2d(dst, &P.twg, full, c0, 64 * (i & 7));
                            tma2d(dst + 8192, &P.twu, full, c0, 64 * (i & 7));
                        }
                    }
                    prefetch_l2(P.wd + (size_t)j * 176128, 352256);
                }
            } else if (warp == 9) {
                wait_count_warp(g_cnt + (lane & 7) * 32, epoch * 32);
            }
            return;
        }
        if (warp == 8) {
            if (elect_one()) {
                if (m >= 3 && m < 8)
                    asm volatile("cp.async.bulk.prefetch.tensor.3d.L2.global [%0, {%1, %2, %3}];" ::"l"(&P.twkv), "r"(64 * j), "r"(64 * m), "r"(1) : "memory");
                if (j >= 3)
                    asm volatile("cp.async.bulk.prefetch.tensor.2d.L2.global [%0, {%1, %2}];" ::"l"(&P.tx), "r"(64 * j), "r"(128 * m) : "memory");
                Ring r{2, 0};
#pragma unroll 1
                for (int i = 2; i < 56; i++) {
                    const uint32_t full = sb + BAR_FULLB + 8 * r.slot, dst = sb + OFF_B + r.slot * SLOT;
                    mbar_wait(sb + BAR_EMPTYB + 8 * r.slot, r.phase ^ 1);
                    if (i >= 10 && i < 14) {
                        mbar_arrive(full);
                    } else {
                        if (i >= AHEAD && i < 6) mbar_wait(full - 8 * AHEAD, 0);
                        mbar_expect_tx(full, SLOT);
                        if (i < 8) {
                            tma3d(dst, &P.twkv, full, 64 * j, 64 * i, 1);
                        } else if (i < 20) {
                            tma2d(dst, i < 16 ? &P.twq : &P.two, full, 64 * j, 128 * (i & 3));
                        } else if (i < 36) {
                            tma3d(dst, &P.twg2, full, 176 * j, 32 * (i - 20), 0);
                            tma3d(dst + 8192, &P.twu2, full, 176 * j, 32 * (i - 20), 0);
                        } else if (i < 44) {
                            tma2d(dst, &P.twg, full, 176 * j + 128, 64 * (i - 36));
                            tma2d(dst + 8192, &P.twu, full, 176 * j + 128, 64 * (i - 36));
                        } else {
                            const int c = (i - 44) >> 2, jj = (i & 3) * 2;
                            tma2d(dst, &P.twd, full, 64 * j, 176 * jj + 64 * c);
                            tma2d(dst + 8192, &P.twd, full, 64 * j, 176 * (jj + 1) + 64 * c);
                        }
                    }
                    r.adv();
                }
            }
            return;
        }
        if (warp == 9) {
            if (elect_one()) {
#pragma unroll 1
                for (int i = 2; i < 8; i++) {
                    if (i >= AHEAD + 1) mbar_wait(sb + BAR_FULLA + 8 * (i - AHEAD - 1), 0);
                    mbar_expect_tx(sb + BAR_FULLA + 8 * i, SLOT);
                    tma2d(sb + OFF_A + i * SLOT, &P.tx, sb + BAR_FULLA + 8 * i, 64 * i, 128 * m);
                }
#pragma unroll 1
                for (int i = 1; i < 12; i++) prefetch_tmap(&P.tx + i);
#pragma unroll 1
                for (int r = 1; r < 6; r++) {
                    const CUtensorMap* tm = &P.tx + min(r, 3);
                    const int cstep = r < 3 ? 64 : 192, cbase = r < 3 ? 0 : 64 * (r - 3), skip = r < 3 ? j : 8;
                    wait_count(g_flag + (m * 5 + r - 1) * 32, epoch * (r < 3 ? 64 : 8));
                    TL(64 + r, true);
#pragma unroll 1
                    for (int t = 0; t < 8; t++) {
                        if (t == skip) continue;
                        mbar_wait(sb + BAR_EMPTYA + 8 * t, (r - 1) & 1);
                        mbar_expect_tx(sb + BAR_FULLA + 8 * t, SLOT);
                        tma2d(sb + OFF_A + t * SLOT, tm, sb + BAR_FULLA + 8 * t, cbase + cstep * t, 128 * m);
                    }
                }
            }
            return;
        }
        const int a = warp - 10;
        {
            const int row = 16 * j + 8 * a + (lane >> 2);
            const uint32_t ra = sb + OFF_A + row * 128;
            float sh = 0.f, s0 = 0.f, s1 = 0.f, q0 = 0.f, q1 = 0.f;
#pragma unroll 1
            for (int kt = 0; kt < 8; kt++) {
                mbar_wait(sb + BAR_FULLA + 8 * kt, 0);
                if (kt == 0) sh = bf_lo(lds128(ra + ((row & 7) << 4)).x);
#pragma unroll
                for (int i = 0; i < 2; i++) {
                    const uint4 v = lds128(ra + kt * SLOT + (((2 * (lane & 3) + i) ^ (row & 7)) << 4));
                    const uint32_t ww[4] = {v.x, v.y, v.z, v.w};
#pragma unroll
                    for (int e = 0; e < 4; e++) {
                        const float d0 = bf_lo(ww[e]) - sh, d1 = bf_hi(ww[e]) - sh;
                        s0 += d0; q0 = fmaf(d0, d0, q0);
                        s1 += d1; q1 = fmaf(d1, d1, q1);
                    }
                }
            }
            s0 += s1; q0 += q1;
#pragma unroll
            for (int o = 1; o <= 2; o <<= 1) { s0 += __shfl_xor_sync(0xffffffffu, s0, o); q0 += __shfl_xor_sync(0xffffffffu, q0, o); }
            const float md = s0 * (1.f / DM);
            const float rs = rsqrtf(fmaxf(q0 * (1.f / DM) - md * md, 0.f) + 1e-5f);
            st_tagged_if(g_xstat + 2 * (128 * m + row), rs, -(sh + md), epoch, (lane & 3) == 0);
        }
        const unsigned long long* cs = g_cs + j * 768 + 2 * lane;
#pragma unroll 1
        for (int c = 0; c < (a ? 5 : 10); c++) {
            if (c == 4) {
                const int t = 32 * a + lane;
                const uint32_t kvs = sb + OFF_A + KVS(j) * SLOT;
                mbar_wait(sb + BAR_KVW, 0);
#pragma unroll 1
                for (int pass = 0; pass < 2; pass++) {
                    float4 v[8];
#pragma unroll
                    for (int i = 0; i < 8; i++) v[i] = ld_l2_f4(acc_j + ACC_KV + 4 * (t + 64 * i));
                    const float2 zz = ld_l2_f2(acc_j + ACC_Z + 2 * t);
#pragma unroll
                    for (int i = 0; i < 8; i++)
                        sts64(kvs + ((t >> 2) + 16 * i) * 48 + (t & 3) * 8, pack_bf16(v[i].x, v[i].y), pack_bf16(v[i].z, v[i].w));
                    const uint32_t z0 = pack_bf16(zz.x, zz.x), z1 = pack_bf16(zz.y, zz.y);
                    sts128(kvs + t * 96 + 32, z0, z0, z0, z0);
                    sts128(kvs + t * 96 + 80, z1, z1, z1, z1);
                    if (pass == 0) {
                        __syncwarp();
                        if (lane == 0) red_relaxed(cnt_j, 1);
                        TL(19, t == 0);
                        wait_count_warp(cnt_j, epoch * 32);
                        TL(12, t == 0);
                    }
                }
                mbar_arrive(sb + BAR_KVR);
                uint32_t it = 0;
                while (__any_sync(0xffffffffu, (int)(ld_acquire(g_flag + (m * 5 + 1) * 32) - epoch * 64) < 0)) {
                    __nanosleep(500);
                    trap_if_gt(++it, 1u << 22);
                }
                if (a) break;
            }
            if (c == 3 && !a) continue;
            const unsigned long long* src = c < 2 ? g_xstat + 2 * (128 * m + 64 * a + 32 * c + lane) : cs + (c < 4 ? 128 * (a + c - 2) : 128 + 64 * c);
            const uint32_t dst = c < 2 ? OFF_XST + (64 * a + 32 * c + lane) * 8
                                       : (c < 4 ? OFF_CS1 + (c == 2 ? 256 * (a + 1) : 0) + 8 * lane : OFF_CS3 + (32 * ((c - 4) >> 1) + lane) * 16 + 8 * (c & 1));
            uint4 v;
            uint32_t it = 0;
            while (true) {
                v = ld_tagged(src);
                if (!__any_sync(0xffffffffu, v.y != epoch || v.w != epoch)) break;
                __nanosleep(60);
                trap_if_gt(++it, 1u << 22);
            }
            sts64(sb + dst, v.x, v.z);
            if (c == 2 - a || (a && c > 1) || c == 9) mbar_arrive(sb + (c == 9 ? BAR_CS3 : (c == 2 - a ? BAR_CS1 : (c == 2 ? BAR_CSV : BAR_CSQ))));
        }
#pragma unroll 1
        for (int rr = 0; rr < 2; rr++) {
            const int row = 64 * rr + 32 * a + lane;
            const float* sp = g_hstat + (1024 * m + row) * 2;
            float2 v[8];
#pragma unroll
            for (int i = 0; i < 8; i++) v[i] = ld_l2_f2(sp + 256 * i);
            float mean = 0.f;
#pragma unroll
            for (int i = 0; i < 8; i++) mean += v[i].x;
            mean *= 0.125f;
            float m2 = 0.f, dv = 0.f;
#pragma unroll
            for (int i = 0; i < 8; i++) { m2 += v[i].y; dv = fmaf(v[i].x - mean, v[i].x - mean, dv); }
            sts_f2(sb + OFF_CS1 + row * 8, -mean, __fdividef(1.f, fmaf(dv, 64.f, m2) * (1.f / DM) + 1e-5f));
        }
        mbar_arrive(sb + BAR_CS3);
#pragma unroll 1
        for (int c = a; c < 3; c += 2) {
            const int slot = c == 2 ? 1 : 4 + c;
            mbar_wait(sb + BAR_STG + 8 * c, 0);
            if (elect_one()) {
                tma_store2d(&P.thh, sb + OFF_B + slot * SLOT, 192 * j + 64 * c, 128 * m);
                asm volatile("cp.async.bulk.wait_group.read 0;" ::: "memory");
                mbar_arrive_n_if(sb + BAR_EMPTYB + 8 * slot, 8, true);
                asm volatile("cp.async.bulk.wait_group 0;" ::: "memory");
            }
            __syncwarp();
            TL(60 + c, lane == 0);
            uint32_t ack = 0;
#pragma unroll
            for (int i = 0; i < 4; i++) ack |= readback(g_hh + (size_t)(128 * m + 32 * i + lane) * FFP + 192 * j + 64 * c);
            signal_after(g_flag + (m * 5 + 2 + c) * 32, ack, P.zero, lane == 0);
            TL(54 + c, lane == 0);
        }
        return;
    }
    const unsigned epoch = ld_relaxed(&g_epoch);
    uint32_t wraw[16];
    if (!helper) {
        const uint32_t* wp = reinterpret_cast<const uint32_t*>(P.wphi) + (4 * j) * 128 + (lane & 3) * 16 + (lane >> 2);
#pragma unroll
        for (int i = 0; i < 16; i++)
            asm volatile("ld.global.nc.u32 %0, [%1];" : "=r"(wraw[i]) : "l"(wp + (i >> 2) * 128 + ((i >> 1) & 1) * 64 + (i & 1) * 8));
    }
    asm volatile("setmaxnreg.inc.sync.aligned.u32 216;");
    bar_sync(0, NTHREADS);
    if (helper) {
        if (warp < 4) {
            sts128(sb + OFF_B + 16 * tid, 0x3f803f80u, 0x3f803f80u, 0x3f803f80u, 0x3f803f80u);
            for (int i = tid; i < 2 * ACC_SIZE / 4; i += 128) stg128(g_acc + 2 * j * ACC_SIZE + 4 * i, 0, 0, 0, 0);
            fence_async_smem();
            fence_gpu();
            bar_sync(1, 128);
            float acc[8];
            int i = 0;
#pragma unroll 1
            for (int job = 0; job < 12; job++) {
                const int n = job < 6 ? 4 : 8;
#pragma unroll 1
                for (int t = 0; t < n; t++, i++) {
                    mbar_wait(sb + BAR_FULLA + 8 * (i & 7), (i >> 3) & 1);
                    wg_fence();
#pragma unroll
                    for (int k = 0; k < 8; k++)
                        wgmma_n8_tt(acc + (k & 4), desc_lo(sb + OFF_A) + (i & 7) * (SLOT >> 4) + 128 * k, desc_lo(sb + OFF_B), (t | (k & 3)) != 0);
                    wg_commit();
                    wg_wait<1>();
                    mbar_arrive_n_if(sb + BAR_EMPTYA + 8 * ((i + 7) & 7), 2, lane == 0 && i > 0);
                }
                wg_wait<0>();
                fence_acc<8>(acc);
                const int q = lane & 3;
                const float lo = (q & 1) ? acc[2] : acc[0], hi = (q & 1) ? acc[6] : acc[4];
                const float v = job < 6 ? lo + hi : ((q & 2) ? hi : lo);
                unsigned long long* dst = g_cs + ((2 * j + (job & 1)) * 6 + (job >> 1)) * 128 + (q >> 1) * 64 + 16 * warp + 8 * (q & 1) + (lane >> 2);
                asm volatile("st.relaxed.gpu.global.b64 [%0], %1;" ::"l"(dst), "l"(((unsigned long long)epoch << 32) | __float_as_uint(v)) : "memory");
            }
        }
        return;
    }
    {
        const int w = warp >> 2, wv = warp & 3, g = lane >> 2, q = lane & 3;
        const int row_w = 128 * m + 16 * warp;
        const uint32_t sa = sb + OFF_A + w * 8192;
        const desc_t dA = desc_lo(sa), dB = desc_lo(sb + OFF_B);
        unsigned* const flag_m = g_flag + m * 160;
        const bool l0 = lane == 0;
        Ring rg{0, 0};
        int prev = 0;

        uint32_t wb[16];
        constexpr float L2E = 1.4426950408889634f;
        const int ch = lane >> 4, sw = lane & 7;
        const uint32_t lrow = (lane & 15) * 128;
        uint32_t fp[16], fm[16];
        {
            float acc[64], accq[32];
#pragma unroll 1
            for (int kt = 0; kt < 8; kt++) {
                mbar_waitc(sb + BAR_FULLA + 8 * kt, 0);
                mbar_waitc(sb + BAR_FULLB + 8 * rg.slot, rg.phase);
                const desc_t da = dA + kt * (SLOT >> 4), db = dB + rg.slot * (SLOT >> 4);
                wg_fence();
#pragma unroll
                for (int k = 0; k < 4; k++) wgmma_n128(acc, da + 2 * k, db + 128 * k, (kt | k) != 0);
                wg_commit();
                wg_wait<1>();
                mbar_arrive_if(sb + BAR_EMPTYB + 8 * prev, l0 && kt > 0);
                prev = rg.slot; rg.adv();
            }
#pragma unroll
            for (int i = 0; i < 8; i++) {
                wb[(i >> 1) * 4 + (i & 1)] = __byte_perm(wraw[2 * i], wraw[2 * i + 1], 0x5410);
                wb[(i >> 1) * 4 + 2 + (i & 1)] = __byte_perm(wraw[2 * i], wraw[2 * i + 1], 0x7632);
            }
            float2 s0, s1;
            uint32_t a[16];
            wg_wait<0>();
            fence_acc<64>(acc);
            mbar_arrive_if(sb + BAR_EMPTYB + 8 * prev, l0);
#pragma unroll 1
            for (int it = 0; it < 2; it++) {
                mbar_waitc(sb + BAR_FULLB + 8 * 2, it ^ 1); mbar_waitc(sb + BAR_FULLB + 8 * 3, it ^ 1);
                const desc_t da = dA + it * (4 * SLOT >> 4);
                wg_fence();
#pragma unroll
                for (int k = 0; k < 16; k++) wgmma_n64(accq, da + (k >> 2) * (SLOT >> 4) + (k & 3) * 2, dB + 2 * (SLOT >> 4) + 128 * k, (it | k) != 0);
                wg_commit();
                TL(17 + it, tid == 0);
                mbar_waitc(sb + BAR_CS1 + 16 * it, 0);
                s0 = lds_f2(sb + OFF_XST + (16 * warp + g) * 8); s1 = lds_f2(sb + OFF_XST + (16 * warp + g + 8) * 8);
                wg_wait<0>();
                fence_acc<32>(accq);
                mbar_arrive_if(sb + BAR_EMPTYB + 8 * (2 + lane), lane < 2);
                TL(2 + 2 * it, tid == 0);
                if (it == 0) {
#pragma unroll
                    for (int hh = 0; hh < 4; hh++)
                        ln_frag<false>(acc + 8 * hh, sb + OFF_CS1 + (64 + 16 * hh + 2 * q) * 4, 0.f, s0.y, 0.f, s1.y, a + 4 * hh);
                } else {
#pragma unroll
                    for (int hh = 0; hh < 4; hh++)
                        ln_frag<false>(accq + 8 * hh, sb + OFF_CS1 + (16 * hh + 2 * q) * 4, 0.f, s0.y, 0.f, s1.y, a + 4 * hh);
                }
#pragma unroll
                for (int hh = 0; hh < 4; hh++) feature_map(a + 4 * hh, wb + 4 * hh, s0.x * L2E, s1.x * L2E, fp + 4 * hh, fm + 4 * hh);
                if (it == 0) {
                    mbar_waitc(sb + BAR_FULLB + 8 * 4, 1); mbar_waitc(sb + BAR_FULLB + 8 * 5, 1);
                    mbar_waitc(sb + BAR_FULLB + 8 * 0, 0); mbar_waitc(sb + BAR_FULLB + 8 * 1, 0);
                    mbar_waitc(sb + BAR_CSV, 0);
                    const uint32_t st = sb + OFF_B + warp * 2048 + lrow;
#pragma unroll
                    for (int hh = 0; hh < 4; hh++) {
                        stsm4(st + (4 + (hh >> 1)) * SLOT + (((4 * (hh & 1) + ch) ^ sw) << 4), fp[4 * hh], fp[4 * hh + 1], fp[4 * hh + 2], fp[4 * hh + 3]);
                        stsm4(st + (4 + (hh >> 1)) * SLOT + (((4 * (hh & 1) + 2 + ch) ^ sw) << 4), fm[4 * hh], fm[4 * hh + 1], fm[4 * hh + 2], fm[4 * hh + 3]);
                        ln_frag<true>(acc + 32 + 8 * hh, sb + OFF_CS1 + (128 + 16 * hh + 2 * q) * 4, s0.x, s0.y, s1.x, s1.y, a);
                        stsm4(st + (hh >> 1) * SLOT + (((2 * (hh & 1) + ch) ^ sw) << 4), a[0], a[1], a[2], a[3]);
                    }
                    stsm4(st + ch * SLOT + ((4 ^ sw) << 4), 0x3f803f80u, 0x3f803f80u, 0x3f803f80u, 0x3f803f80u);
                    fence_async_smem();
                    bar_sync(1, 256);
                    float kvd[20];
                    wg_fence();
#pragma unroll
                    for (int k = 0; k < 8; k++)
                        wgmma_n40_tt(kvd, dB + (4 + w) * (SLOT >> 4) + 128 * k, dB + w * (SLOT >> 4) + 128 * k, k != 0);
                    wg_commit();
                    wg_wait<0>();
                    fence_acc<20>(kvd);
                    const bool h1 = wv >= 2;
                    const int f = 16 * warp + g;
                    float* kvp = acc_j + ACC_KV + f * 16 + 2 * q;
                    red_f32x2(kvp, h1 ? kvd[8] : kvd[0], h1 ? kvd[9] : kvd[1]);
                    red_f32x2(kvp + 128, h1 ? kvd[10] : kvd[2], h1 ? kvd[11] : kvd[3]);
                    red_f32x2(kvp + 8, h1 ? kvd[12] : kvd[4], h1 ? kvd[13] : kvd[5]);
                    red_f32x2(kvp + 136, h1 ? kvd[14] : kvd[6], h1 ? kvd[15] : kvd[7]);
                    red_f32_if(acc_j + ACC_Z + f + 8 * (q & 1), q ? kvd[18] : kvd[16], q < 2);
                    __syncwarp();
                    mbar_arrive_if(sb + (lane == 4 ? BAR_KVW : BAR_EMPTYB + 8 * ((4 + lane) % 6)), lane < 5);
                    TL(3, tid == 0);
                }
            }
        }
        uint32_t res_lo[8], res_hi[8];
        const uint32_t own_rows = sb + OFF_A + j * SLOT + warp * 2048;
#pragma unroll
        for (int b = 0; b < 4; b++)
            ldsm4(own_rows + lrow + (((2 * b + ch) ^ sw) << 4), res_lo[2 * b], res_hi[2 * b], res_lo[2 * b + 1], res_hi[2 * b + 1]);
        mbar_arrive_if(sb + BAR_EMPTYA + 8 * lane, lane < 8 && lane != j && lane != KVS(j));
        TL(5, tid == 0);
        mbar_waitc(sb + BAR_KVR, 0);
        TL(6, tid == 0);
        {
            const uint32_t kvs = sb + OFF_A + KVS(j) * SLOT;
            uint32_t o_lo[8], o_hi[8];
#pragma unroll
            for (int hh = 0; hh < 4; hh++) {
                uint32_t b[8], zb[4];
                const uint32_t base = kvs + hh * 32 * 48;
                ldsm4t(base + (lane & 15) * 48 + (lane >> 4) * 16, b[0], b[1], b[2], b[3]);
                ldsm4t(base + (16 + (lane & 15)) * 48 + (lane >> 4) * 16, b[4], b[5], b[6], b[7]);
                ldsm4t(base + lane * 48 + 32, zb[0], zb[1], zb[2], zb[3]);
                float n0[4], n1[4], dn[4];
                mma16816_z(n0, fp + 4 * hh, b[0], b[1]); mma16816_z(n1, fp + 4 * hh, b[2], b[3]); mma16816_z(dn, fp + 4 * hh, zb[0], zb[1]);
                mma16816(n0, fm + 4 * hh, b[4], b[5]); mma16816(n1, fm + 4 * hh, b[6], b[7]); mma16816(dn, fm + 4 * hh, zb[2], zb[3]);
                const float i0 = rcp(dn[0] + 1e-6f), i1 = rcp(dn[2] + 1e-6f);
                o_lo[2 * hh] = pack_bf16(n0[0] * i0, n0[1] * i0); o_hi[2 * hh] = pack_bf16(n0[2] * i1, n0[3] * i1);
                o_lo[2 * hh + 1] = pack_bf16(n1[0] * i0, n1[1] * i0); o_hi[2 * hh + 1] = pack_bf16(n1[2] * i1, n1[3] * i1);
            }
            __syncwarp();
            mbar_arrive_if(sb + BAR_EMPTYA + 8 * KVS(j), l0);
            rg.slot = 4; rg.phase = 0;
            const uint32_t ack = store_tile<true>(own_rows, g_o + (size_t)row_w * DM + 64 * j, o_lo, o_hi, lane);
            fence_async_smem();
            signal_after(flag_m, ack, P.zero, l0);
            TL(7, tid == 0);
        }
        {
            float acc[32];
#pragma unroll
            for (int t = 0; t < 8; t++) {
                acc[4 * t] = bf_lo(res_lo[t]); acc[4 * t + 1] = bf_hi(res_lo[t]);
                acc[4 * t + 2] = bf_lo(res_hi[t]); acc[4 * t + 3] = bf_hi(res_hi[t]);
            }
            fence_acc<32>(acc);
#pragma unroll 1
            for (int kp = 0; kp < 4; kp++) {
                mbar_waitc(sb + BAR_FULLB + 8 * rg.slot, rg.phase);
#pragma unroll
                for (int hf = 0; hf < 2; hf++) {
                    const int kt = 2 * kp + hf;
                    mbar_waitc(sb + BAR_FULLA + 8 * kt, kt != j);
                    TL(8, kt == 0 && tid == 0);
                    const desc_t da = dA + kp * (2 * SLOT >> 4), db = dB + rg.slot * (SLOT >> 4);
                    wg_fence();
#pragma unroll
                    for (int k = 0; k < 4; k++) wgmma_n64(acc, da + hf * (SLOT >> 4) + 2 * k, db + (hf * 4 + k) * 128, 1);
                    wg_commit();
                    wg_wait<1>();
                    mbar_arrive_if(sb + BAR_EMPTYA + 8 * ((kt + 7) & 7), l0 && kt > 0 && kt - 1 != j);
                    if (hf == 0) mbar_arrive_if(sb + BAR_EMPTYB + 8 * prev, l0 && kt > 0);
                }
                prev = rg.slot; rg.adv();
            }
            wg_wait<0>();
            fence_acc<32>(acc);
            mbar_arrive_if(sb + BAR_EMPTYA + 8 * 7, l0 && j != 7);
            mbar_arrive_if(sb + BAR_EMPTYB + 8 * prev, l0);
            TL(9, tid == 0);
            float s0 = 0.f, s1 = 0.f;
#pragma unroll
            for (int t = 0; t < 8; t++) {
                res_lo[t] = pack_bf16(acc[4 * t], acc[4 * t + 1]);
                res_hi[t] = pack_bf16(acc[4 * t + 2], acc[4 * t + 3]);
                s0 += acc[4 * t] + acc[4 * t + 1];
                s1 += acc[4 * t + 2] + acc[4 * t + 3];
            }
            uint32_t ack = store_tile<true>(own_rows, g_h + (size_t)row_w * DM + 64 * j, res_lo, res_hi, lane);
            s0 += __shfl_xor_sync(0xffffffffu, s0, 1); s1 += __shfl_xor_sync(0xffffffffu, s1, 1);
            s0 += __shfl_xor_sync(0xffffffffu, s0, 2); s1 += __shfl_xor_sync(0xffffffffu, s1, 2);
            const float mu0 = s0 * (1.f / 64), mu1 = s1 * (1.f / 64);
            float q0 = 0.f, q1 = 0.f;
#pragma unroll
            for (int t = 0; t < 8; t++) {
                float d;
                d = acc[4 * t] - mu0; q0 = fmaf(d, d, q0);
                d = acc[4 * t + 1] - mu0; q0 = fmaf(d, d, q0);
                d = acc[4 * t + 2] - mu1; q1 = fmaf(d, d, q1);
                d = acc[4 * t + 3] - mu1; q1 = fmaf(d, d, q1);
            }
            q0 += __shfl_xor_sync(0xffffffffu, q0, 1); q1 += __shfl_xor_sync(0xffffffffu, q1, 1);
            q0 += __shfl_xor_sync(0xffffffffu, q0, 2); q1 += __shfl_xor_sync(0xffffffffu, q1, 2);
            stg_f2_if(g_hstat + (role * 128 + 16 * warp + g + 8 * (q & 1)) * 2, q ? mu1 : mu0, q ? q1 : q0, q < 2);
            ack |= readback(g_hstat + (role * 128 + 16 * warp + g + 8 * (q & 1)) * 2);
            fence_async_smem();
            signal_after(flag_m + 32, ack, P.zero, l0);
            TL(10, tid == 0);
        }
        {
            const uint32_t cs3 = sb + OFF_CS3 + q * 16;
            float nm0, nm1;
            {
                float acc[128];
                const desc_t dB4 = dB - (256ull << 16);
#pragma unroll 1
                for (int i = 0; i < 16; i++) {
                    mbar_waitc(sb + BAR_FULLA + 8 * (i >> 1), 0);
                    mbar_waitc(sb + BAR_FULLB + 8 * rg.slot, rg.phase);
                    TL(44, tid == 0 && i == 2);
                    const desc_t da = dA + (i >> 1) * (SLOT >> 4) + (i & 1) * 4, db = dB4 + rg.slot * (SLOT >> 4);
                    wg_fence();
                    wgmma_n256(acc, da, db, i != 0);
                    wgmma_n256(acc, da + 2, db + 128, 1);
                    wg_commit();
                    wg_wait<1>();
                    mbar_arrive_if(sb + BAR_EMPTYB + 8 * prev, l0 && i > 0 && i < 15);
                    prev = rg.slot; rg.adv();
                }
                mbar_waitc(sb + BAR_CS3, 0);
                nm0 = lds_f2(sb + OFF_CS1 + (16 * warp + g) * 8).x; nm1 = lds_f2(sb + OFF_CS1 + (16 * warp + g + 8) * 8).x;
                wg_wait<0>();
                fence_acc<128>(acc);
                TL(11, tid == 0);
                bar_sync(1, 256);
                hh_stage<64, 4>(acc, cs3, nm0, nm1, sb + OFF_B + 4 * SLOT + warp * 2048, lane);
                mbar_arrive_if(sb + BAR_STG, l0);
                hh_stage<64, 4>(acc + 32, cs3 + 512, nm0, nm1, sb + OFF_B + 5 * SLOT + warp * 2048, lane);
                mbar_arrive_if(sb + BAR_STG + 8, l0);
                TL(50, tid == 0);
            }
            {
                float acc[56];
#pragma unroll 1
                for (int kt = 0; kt < 8; kt++) {
                    mbar_waitc(sb + BAR_FULLB + 8 * rg.slot, rg.phase);
                    const desc_t da = dA + kt * (SLOT >> 4), db = dB + rg.slot * (SLOT >> 4);
                    wg_fence();
#pragma unroll
                    for (int k = 0; k < 4; k++) wgmma_n112(acc, da + 2 * k, db + 128 * k, (kt | k) != 0);
                    wg_commit();
                    wg_wait<1>();
                    mbar_arrive_if(sb + BAR_EMPTYB + 8 * prev, l0 && kt > 0);
                    mbar_arrive_if(sb + BAR_EMPTYA + 8 * ((kt + 7) & 7), l0 && kt > 0);
                    prev = rg.slot; rg.adv();
                }
                wg_wait<0>();
                fence_acc<56>(acc);
                mbar_arrive_if(sb + BAR_EMPTYA + 8 * 7, l0);
                TL(13, tid == 0);
                bar_sync(1, 256);
                hh_stage<32, 3>(acc, cs3 + 1024, nm0, nm1, sb + OFF_B + 1 * SLOT + warp * 2048, lane);
                mbar_arrive_if(sb + BAR_STG + 16, l0);
                TL(52, tid == 0);
            }
        }
        {
            float acc[64];
            const desc_t dA0 = desc_lo(sb + OFF_A);
#define KT_P4(I, NK)                                                                                        \
    do {                                                                                                    \
        const int s_ = (2 * (I) + w) & 7;                                                                   \
        mbar_waitc(sb + BAR_FULLB + 8 * rg.slot, rg.phase);                                                 \
        mbar_waitc(sb + BAR_FULLA + 8 * s_, (((I) >> 2) + 1) & 1);                                          \
        TL(30 + (I), tid == 0);                                                                             \
        const desc_t dh_ = dA0 + s_ * (SLOT >> 4), dw_ = dB + rg.slot * (SLOT >> 4) + w * 512;              \
        wg_fence();                                                                                         \
        _Pragma("unroll") for (int k = 0; k < (NK); k++) wgmma_n128_tn(acc, dw_ + 128 * k, dh_ + 2 * k, ((I) | k) != 0); \
        wg_commit();                                                                                        \
        wg_wait<1>();                                                                                       \
        mbar_arrive_n_if(sb + BAR_EMPTYA + 8 * ((s_ + 6) & 7), 2, l0 && (I) > 0);                           \
        mbar_arrive_if(sb + BAR_EMPTYB + 8 * prev, l0 && (I) > 0);                                          \
        prev = rg.slot; rg.adv();                                                                           \
    } while (0)
#pragma unroll 1
            for (int i = 0; i < 8; i++) KT_P4(i, 4);
#pragma unroll 1
            for (int i = 8; i < 12; i++) KT_P4(i, 3);
            const uint32_t tile = sb + OFF_A + w * SLOT;
#pragma unroll
            for (int b = 0; b < 4; b++)
                stsm4(tile + (16 * wv + (lane & 15)) * 128 + (((2 * b + (lane >> 4)) ^ (lane & 7)) << 4),
                      res_lo[2 * b], res_hi[2 * b], res_lo[2 * b + 1], res_hi[2 * b + 1]);
            wg_wait<0>();
            fence_acc<64>(acc);
            TL(15, tid == 0);
            const uint32_t xch = sb + OFF_A + 2 * SLOT + (tid & 127) * 16;
            if (w) {
#pragma unroll
                for (int t = 0; t < 8; t++) {
                    sts128(xch + SLOT + t * 2048, __float_as_uint(acc[4 * t]), __float_as_uint(acc[4 * t + 1]),
                           __float_as_uint(acc[4 * t + 2]), __float_as_uint(acc[4 * t + 3]));
                }
#pragma unroll
                for (int t = 0; t < 32; t++) acc[t] = acc[32 + t];
            } else {
#pragma unroll
                for (int t = 0; t < 8; t++)
                    sts128(xch + t * 2048, __float_as_uint(acc[32 + 4 * t]), __float_as_uint(acc[33 + 4 * t]),
                           __float_as_uint(acc[34 + 4 * t]), __float_as_uint(acc[35 + 4 * t]));
            }
            bar_sync(1, 256);
            const uint32_t blk = tile + ((lane & 7) + (lane >> 4) * 8) * 128 + (((2 * wv + ((lane >> 3) & 1)) ^ (lane & 7)) << 4);
#pragma unroll
            for (int tp = 0; tp < 4; tp++) {
                uint32_t hr[4];
                ldsm4t(blk + tp * 2048, hr[0], hr[1], hr[2], hr[3]);
#pragma unroll
                for (int u = 0; u < 2; u++) {
                    const int t = 2 * tp + u;
                    const float4 o = lds_f4(xch + (w ^ 1) * SLOT + t * 2048);
                    const float4 st = lds_f4(sb + OFF_CS1 + (64 * w + 8 * t + 2 * q) * 8);
                    hr[2 * u] = pack_bf16(fmaf(acc[4 * t] + o.x, st.y, bf_lo(hr[2 * u])), fmaf(acc[4 * t + 1] + o.y, st.w, bf_hi(hr[2 * u])));
                    hr[2 * u + 1] = pack_bf16(fmaf(acc[4 * t + 2] + o.z, st.y, bf_lo(hr[2 * u + 1])), fmaf(acc[4 * t + 3] + o.w, st.w, bf_hi(hr[2 * u + 1])));
                }
                stsm4t(blk + tp * 2048, hr[0], hr[1], hr[2], hr[3]);
            }
            bar_sync(2 + w, 128);
#pragma unroll
            for (int i = 0; i < 4; i++) {
                const int rr = 16 * wv + 4 * i + (lane >> 3);
                const uint4 v = lds128(tile + rr * 128 + (((lane & 7) ^ (rr & 7)) << 4));
                stg128(P.out + (size_t)(128 * m + 64 * w + rr) * DM + 64 * j + (lane & 7) * 8, v.x, v.y, v.z, v.w);
            }
            if (tid == 0 && role == 0) g_epoch = epoch + 1;
            TL(16, tid == 0); TLG(1, tid == 0);
        }
    }
}

typedef CUresult (*EncodeFn)(CUtensorMap*, CUtensorMapDataType, cuuint32_t, void*, const cuuint64_t*, const cuuint64_t*,
                             const cuuint32_t*, const cuuint32_t*, CUtensorMapInterleave, CUtensorMapSwizzle,
                             CUtensorMapL2promotion, CUtensorMapFloatOOBfill);

static void make_map2d(EncodeFn enc, CUtensorMap* tm, const void* base, uint64_t cols, uint64_t rows, uint64_t pitch_elems,
                       uint32_t box_rows) {
    cuuint64_t gd[2] = {cols, rows};
    cuuint64_t gs[1] = {pitch_elems * 2};
    cuuint32_t bd[2] = {64, box_rows};
    cuuint32_t es[2] = {1, 1};
    enc(tm, CU_TENSOR_MAP_DATA_TYPE_BFLOAT16, 2, const_cast<void*>(base), gd, gs, bd, es, CU_TENSOR_MAP_INTERLEAVE_NONE,
        CU_TENSOR_MAP_SWIZZLE_128B, CU_TENSOR_MAP_L2_PROMOTION_L2_256B, CU_TENSOR_MAP_FLOAT_OOB_FILL_NONE);
}

}

extern "C" void kernel_launch(void* const* d_in, const int* in_sizes, int n_in, void* d_out, int out_size) {
    using namespace hk;
    (void)in_sizes; (void)n_in; (void)out_size;
    static EncodeFn enc = nullptr;
    static void *po = nullptr, *ph = nullptr, *phh = nullptr;
    static int std_layout = 0;
    if (!enc) {
        void* fn = nullptr;
        cudaDriverEntryPointQueryResult qr;
        cudaGetDriverEntryPoint("cuTensorMapEncodeTiled", &fn, cudaEnableDefault, &qr);
        enc = (EncodeFn)fn;
        cudaGetSymbolAddress(&po, g_o);
        cudaGetSymbolAddress(&ph, g_h);
        cudaGetSymbolAddress(&phh, g_hh);
        cudaFuncSetAttribute(fused_kernel, cudaFuncAttributeMaxDynamicSharedMemorySize, SMEM_BYTES);
        int dev = 0, sms = 0;
        cudaGetDevice(&dev);
        cudaDeviceGetAttribute(&sms, cudaDevAttrMultiProcessorCount, dev);
        cudaFuncSetAttribute(fused_kernel, cudaFuncAttributeNonPortableClusterSizeAllowed, 1);
        const int sizes[3] = {8, 9, 16}, want[3] = {15, 9, 7};
        bool ok = sms == NCTA;
        for (int i = 0; i < 3 && ok; i++) {
            cudaLaunchConfig_t cfg = {};
            cfg.gridDim = dim3(sizes[i] * 8); cfg.blockDim = dim3(NTHREADS); cfg.dynamicSmemBytes = SMEM_BYTES;
            cudaLaunchAttribute at;
            at.id = cudaLaunchAttributeClusterDimension;
            at.val.clusterDim.x = sizes[i]; at.val.clusterDim.y = 1; at.val.clusterDim.z = 1;
            cfg.attrs = &at; cfg.numAttrs = 1;
            int n = 0;
            ok = cudaOccupancyMaxActiveClusters(&n, fused_kernel, &cfg) == cudaSuccess && n == want[i];
        }
        (void)cudaGetLastError();
        std_layout = ok ? 1 : 0;
    }
    Params P;
    const __nv_bfloat16* x = (const __nv_bfloat16*)d_in[0];
    P.x = x;
    P.wqkv = (const __nv_bfloat16*)d_in[1];
    P.wphi = (const __nv_bfloat16*)d_in[2];
    P.wo = (const __nv_bfloat16*)d_in[3];
    P.wg = (const __nv_bfloat16*)d_in[5];
    P.wu = (const __nv_bfloat16*)d_in[6];
    P.wd = (const __nv_bfloat16*)d_in[7];
    P.out = (__nv_bfloat16*)d_out;
    P.use_smid = std_layout;
    P.zero = 0;
    for (int i = 0; i < NCTA; i++) {
        int role = i < 4 ? 128 + i : i - 4;
        if (std_layout) {
            const int tpc = i >> 1, odd = i & 1;
            if (tpc < 32) role = (tpc & 7) * 8 + (tpc >> 3) * 2 + odd;
            else if (tpc < 60) role = (8 + (tpc - 32) % 7) * 8 + ((tpc - 32) / 7) * 2 + odd;
            else if (tpc < 62) role = 128 + (tpc - 60) * 2 + odd;
            else role = 15 * 8 + (tpc - 62) * 2 + odd;
        }
        P.role[i] = (unsigned char)role;
    }
    make_map2d(enc, &P.tx, x, DM, SEQ, DM, 128);
    make_map2d(enc, &P.to, po, DM, SEQ, DM, 128);
    make_map2d(enc, &P.th, ph, DM, SEQ, DM, 128);
    make_map2d(enc, &P.thh, phh, FFP, SEQ, FFP, 128);
    make_map2d(enc, &P.twq, P.wqkv, 3 * DM, DM, 3 * DM, 128);
    make_map2d(enc, &P.two, P.wo, DM, DM, DM, 128);
    make_map2d(enc, &P.twg, P.wg, FF, DM, FF, 64);
    make_map2d(enc, &P.twu, P.wu, FF, DM, FF, 64);
    make_map2d(enc, &P.twd, P.wd, DM, FF, DM, 64);
    {
        cuuint64_t gd[3] = {(cuuint64_t)DM, (cuuint64_t)DM, 3};
        cuuint64_t gs[2] = {(cuuint64_t)3 * DM * 2, (cuuint64_t)DM * 2};
        cuuint32_t bd[3] = {64, 64, 2};
        cuuint32_t es[3] = {1, 1, 1};
        enc(&P.twkv, CU_TENSOR_MAP_DATA_TYPE_BFLOAT16, 3, const_cast<__nv_bfloat16*>(P.wqkv), gd, gs, bd, es,
            CU_TENSOR_MAP_INTERLEAVE_NONE, CU_TENSOR_MAP_SWIZZLE_128B, CU_TENSOR_MAP_L2_PROMOTION_L2_256B,
            CU_TENSOR_MAP_FLOAT_OOB_FILL_NONE);
    }
    for (int i = 0; i < 2; i++) {
        cuuint64_t gd[3] = {(cuuint64_t)FF - 64, (cuuint64_t)DM, 2};
        cuuint64_t gs[2] = {(cuuint64_t)FF * 2, 128};
        cuuint32_t bd[3] = {64, 32, 2};
        cuuint32_t es[3] = {1, 1, 1};
        enc(i ? &P.twu2 : &P.twg2, CU_TENSOR_MAP_DATA_TYPE_BFLOAT16, 3, const_cast<__nv_bfloat16*>(i ? P.wu : P.wg), gd, gs, bd, es,
            CU_TENSOR_MAP_INTERLEAVE_NONE, CU_TENSOR_MAP_SWIZZLE_128B, CU_TENSOR_MAP_L2_PROMOTION_L2_256B,
            CU_TENSOR_MAP_FLOAT_OOB_FILL_NONE);
    }
    fused_kernel<<<NCTA, NTHREADS, SMEM_BYTES>>>(P);
}
```

```cpp
#include <cuda_runtime.h>
#include <cuda_bf16.h>
#include <cuda.h>
#include <stdint.h>

namespace hk {

constexpr int SEQ = 2048, DM = 512, FF = 1376, FFP = 1536;
constexpr int NCTA = 132;
constexpr int NTHREADS = 384;
constexpr uint32_t SLOT = 16384;
constexpr uint32_t OFF_A = 0, OFF_B = 8 * SLOT, OFF_MISC = 14 * SLOT;
constexpr uint32_t BAR_FULLA = OFF_MISC + 0, BAR_EMPTYA = OFF_MISC + 64, BAR_FULLB = OFF_MISC + 128,
                   BAR_EMPTYB = OFF_MISC + 176, BAR_CS1 = OFF_MISC + 224, BAR_CS3 = OFF_MISC + 232,
                   BAR_CSQ = OFF_MISC + 240, BAR_CSV = OFF_MISC + 248,
                   BAR_STG = OFF_MISC + 256,
                   BAR_KVW = OFF_MISC + 280, BAR_KVR = OFF_MISC + 288;
constexpr uint32_t OFF_CS1 = OFF_MISC + 384;
constexpr uint32_t OFF_CS3 = OFF_CS1 + 1024;
constexpr uint32_t OFF_XST = OFF_CS3;
constexpr uint32_t SMEM_BYTES = OFF_CS3 + 1536;
#define KVS(j) ((j) == 3 ? 2 : 3)
#define KORD(i, j) ((i) == 0 ? (j) : (i) - ((i) <= (j)))
constexpr int NB = 6;
constexpr int AHEAD = 3;

constexpr int ACC_KV = 0, ACC_Z = 2048, ACC_SIZE = 2176;

__device__ __align__(1024) __nv_bfloat16 g_o[SEQ * DM];
__device__ __align__(1024) __nv_bfloat16 g_h[SEQ * DM];
__device__ __align__(1024) __nv_bfloat16 g_hh[SEQ * FFP];
__device__ __align__(128) float g_hstat[SEQ * 16];
__device__ __align__(128) unsigned long long g_xstat[SEQ * 2];
__device__ __align__(128) float g_acc[8 * ACC_SIZE];
__device__ __align__(128) unsigned g_cnt[8 * 32];
__device__ __align__(128) unsigned long long g_cs[8 * 6 * 128];
__device__ __align__(128) unsigned g_flag[16 * 5 * 32];
__device__ unsigned g_epoch = 1;

#define TL(i, pred) do {} while (0)
#define TLG(i, pred) do {} while (0)

struct Params {
    CUtensorMap tx, to, th, thh, twkv, twq, two, twg, twu, twd, twg2, twu2;
    const __nv_bfloat16 *x, *wqkv, *wphi, *wo, *wg, *wu, *wd;
    __nv_bfloat16* out;
    int use_smid;
    unsigned zero;
    unsigned char role[NCTA];
};

__device__ __forceinline__ uint32_t smem_u32(const void* p) { return (uint32_t)__cvta_generic_to_shared(p); }
__device__ __forceinline__ void mbar_init(uint32_t bar, uint32_t cnt) {
    asm volatile("mbarrier.init.shared::cta.b64 [%0], %1;" ::"r"(bar), "r"(cnt) : "memory");
}
__device__ __forceinline__ void mbar_expect_tx(uint32_t bar, uint32_t bytes) {
    asm volatile("mbarrier.arrive.expect_tx.shared::cta.b64 _, [%0], %1;" ::"r"(bar), "r"(bytes) : "memory");
}
__device__ __forceinline__ void mbar_arrive(uint32_t bar) {
    asm volatile("mbarrier.arrive.shared::cta.b64 _, [%0];" ::"r"(bar) : "memory");
}
__device__ __forceinline__ void mbar_arrive_if(uint32_t bar, bool pred) {
    asm volatile("{.reg .pred p; setp.ne.u32 p, %1, 0; @p mbarrier.arrive.shared::cta.b64 _, [%0];}" ::"r"(bar), "r"((uint32_t)pred) : "memory");
}
__device__ __forceinline__ bool mbar_try(uint32_t bar, uint32_t parity) {
    uint32_t ok;
    asm volatile("{.reg .pred p; mbarrier.try_wait.parity.shared::cta.b64 p, [%1], %2; selp.u32 %0,1,0,p;}"
                 : "=r"(ok) : "r"(bar), "r"(parity) : "memory");
    return ok;
}
__device__ __forceinline__ bool mbar_test(uint32_t bar, uint32_t parity) {
    uint32_t ok;
    asm volatile("{.reg .pred p; mbarrier.test_wait.parity.shared::cta.b64 p, [%1], %2; selp.u32 %0,1,0,p;}"
                 : "=r"(ok) : "r"(bar), "r"(parity) : "memory");
    return ok;
}
__device__ __forceinline__ void trap_if_gt(uint32_t v, uint32_t lim) {
    asm volatile("{.reg .pred p; setp.gt.u32 p, %0, %1; @p trap;}" ::"r"(v), "r"(lim));
}
__device__ __forceinline__ void mbar_wait(uint32_t bar, uint32_t parity) {
    asm volatile("{\n"
                 ".reg .pred P1, P2;\n"
                 ".reg .u32 c;\n"
                 "mov.u32 c, 0;\n"
                 "LAB_WAIT:\n"
                 "mbarrier.try_wait.parity.shared::cta.b64 P1, [%0], %1;\n"
                 "@P1 bra LAB_DONE;\n"
                 "add.u32 c, c, 1;\n"
                 "setp.gt.u32 P2, c, 4194304;\n"
                 "@P2 trap;\n"
                 "bra LAB_WAIT;\n"
                 "LAB_DONE:\n"
                 "}" ::"r"(bar), "r"(parity) : "memory");
}
__device__ __forceinline__ void mbar_waitc(uint32_t bar, uint32_t parity) {
    asm volatile("{\n"
                 ".reg .pred P1;\n"
                 "LAB_WAIT:\n"
                 "mbarrier.try_wait.parity.shared::cta.b64 P1, [%0], %1;\n"
                 "@!P1 bra LAB_WAIT;\n"
                 "}" ::"r"(bar), "r"(parity) : "memory");
}
__device__ __forceinline__ void tma2d(uint32_t dst, const CUtensorMap* tm, uint32_t bar, int c0, int c1) {
    asm volatile("cp.async.bulk.tensor.2d.shared::cluster.global.mbarrier::complete_tx::bytes [%0], [%1, {%3, %4}], [%2];"
                 ::"r"(dst), "l"(tm), "r"(bar), "r"(c0), "r"(c1) : "memory");
}
__device__ __forceinline__ void tma3d(uint32_t dst, const CUtensorMap* tm, uint32_t bar, int c0, int c1, int c2) {
    asm volatile("cp.async.bulk.tensor.3d.shared::cluster.global.mbarrier::complete_tx::bytes [%0], [%1, {%3, %4, %5}], [%2];"
                 ::"r"(dst), "l"(tm), "r"(bar), "r"(c0), "r"(c1), "r"(c2) : "memory");
}
__device__ __forceinline__ bool elect_one() {
    uint32_t ok;
    asm volatile("{.reg .pred p; elect.sync _|p, 0xffffffff; selp.u32 %0, 1, 0, p;}" : "=r"(ok));
    return ok;
}
__device__ __forceinline__ void prefetch_tmap(const CUtensorMap* tm) {
    asm volatile("prefetch.tensormap [%0];" ::"l"(tm) : "memory");
}
__device__ __forceinline__ void prefetch_l2(const void* p, uint32_t bytes) {
    asm volatile("cp.async.bulk.prefetch.L2.global [%0], %1;" ::"l"(p), "r"(bytes) : "memory");
}
__device__ __forceinline__ unsigned ld_acquire(const unsigned* p) {
    unsigned v; asm volatile("ld.acquire.gpu.global.u32 %0, [%1];" : "=r"(v) : "l"(p) : "memory"); return v;
}
__device__ __forceinline__ uint4 ld_acquire4(const unsigned* p) {
    uint4 v;
    asm volatile("ld.acquire.gpu.global.v4.u32 {%0,%1,%2,%3}, [%4];" : "=r"(v.x), "=r"(v.y), "=r"(v.z), "=r"(v.w) : "l"(p) : "memory");
    return v;
}
__device__ __forceinline__ unsigned ld_relaxed(const unsigned* p) {
    unsigned v; asm volatile("ld.relaxed.gpu.global.u32 %0, [%1];" : "=r"(v) : "l"(p)); return v;
}
__device__ __forceinline__ void st_relaxed(unsigned* p, unsigned v) {
    asm volatile("st.relaxed.gpu.global.u32 [%0], %1;" ::"l"(p), "r"(v) : "memory");
}
__device__ __forceinline__ void red_relaxed(unsigned* p, unsigned v) {
    asm volatile("red.relaxed.gpu.global.add.u32 [%0], %1;" ::"l"(p), "r"(v) : "memory");
}
__device__ __forceinline__ void fence_gpu() { asm volatile("fence.acq_rel.gpu;" ::: "memory"); }
__device__ __forceinline__ void fence_async_smem() { asm volatile("fence.proxy.async.shared::cta;" ::: "memory"); }
__device__ __forceinline__ void fence_async_global() { asm volatile("fence.proxy.async.global;" ::: "memory"); }
__device__ __forceinline__ void wait_count(const unsigned* p, unsigned target) {
    uint32_t it = 0;
    while ((int)(ld_acquire(p) - target) < 0) trap_if_gt(++it, 1u << 22);
}
__device__ __forceinline__ void wait_count_warp(const unsigned* p, unsigned target) {
    uint32_t it = 0;
    while (__any_sync(0xffffffffu, (int)(ld_acquire(p) - target) < 0)) trap_if_gt(++it, 1u << 22);
}
__device__ __forceinline__ void red_f32(float* p, float a) {
    asm volatile("red.relaxed.gpu.global.add.f32 [%0], %1;" ::"l"(p), "f"(a) : "memory");
}
__device__ __forceinline__ void red_f32x2(float* p, float a, float b) {
    asm volatile("red.relaxed.gpu.global.add.v2.f32 [%0], {%1, %2};" ::"l"(p), "f"(a), "f"(b) : "memory");
}
__device__ __forceinline__ void red_f32x4(float* p, float a, float b, float c, float d) {
    asm volatile("red.relaxed.gpu.global.add.v4.f32 [%0], {%1, %2, %3, %4};" ::"l"(p), "f"(a), "f"(b), "f"(c), "f"(d) : "memory");
}
__device__ __forceinline__ float4 ld_l2_f4(const float* p) {
    float4 v;
    asm volatile("ld.relaxed.gpu.global.v4.f32 {%0,%1,%2,%3}, [%4];" : "=f"(v.x), "=f"(v.y), "=f"(v.z), "=f"(v.w) : "l"(p) : "memory");
    return v;
}
__device__ __forceinline__ float2 ld_l2_f2(const float* p) {
    float2 v;
    asm volatile("ld.relaxed.gpu.global.v2.f32 {%0,%1}, [%2];" : "=f"(v.x), "=f"(v.y) : "l"(p) : "memory");
    return v;
}
__device__ __forceinline__ float ld_l2_f(const float* p) {
    float v;
    asm volatile("ld.relaxed.gpu.global.f32 %0, [%1];" : "=f"(v) : "l"(p) : "memory");
    return v;
}
__device__ __forceinline__ uint4 ldg_nc(const void* p) {
    uint4 v;
    asm volatile("ld.global.nc.L1::no_allocate.v4.u32 {%0,%1,%2,%3}, [%4];" : "=r"(v.x), "=r"(v.y), "=r"(v.z), "=r"(v.w) : "l"(p));
    return v;
}
__device__ __forceinline__ void stg128(void* p, uint32_t a, uint32_t b, uint32_t c, uint32_t d) {
    asm volatile("st.global.v4.u32 [%0], {%1,%2,%3,%4};" ::"l"(p), "r"(a), "r"(b), "r"(c), "r"(d) : "memory");
}
__device__ __forceinline__ uint4 lds128(uint32_t a) {
    uint4 v;
    asm volatile("ld.shared.v4.u32 {%0,%1,%2,%3}, [%4];" : "=r"(v.x), "=r"(v.y), "=r"(v.z), "=r"(v.w) : "r"(a) : "memory");
    return v;
}
__device__ __forceinline__ float2 lds_f2(uint32_t a) {
    float2 v;
    asm volatile("ld.shared.v2.f32 {%0,%1}, [%2];" : "=f"(v.x), "=f"(v.y) : "r"(a) : "memory");
    return v;
}
__device__ __forceinline__ void sts_f2(uint32_t a, float x, float y) {
    asm volatile("st.shared.v2.f32 [%0], {%1,%2};" ::"r"(a), "f"(x), "f"(y) : "memory");
}
__device__ __forceinline__ void sts64(uint32_t a, uint32_t x, uint32_t y) {
    asm volatile("st.shared.v2.u32 [%0], {%1,%2};" ::"r"(a), "r"(x), "r"(y) : "memory");
}
__device__ __forceinline__ void sts128(uint32_t a, uint32_t x, uint32_t y, uint32_t z, uint32_t w) {
    asm volatile("st.shared.v4.u32 [%0], {%1,%2,%3,%4};" ::"r"(a), "r"(x), "r"(y), "r"(z), "r"(w) : "memory");
}
__device__ __forceinline__ void stsm4(uint32_t a, uint32_t r0, uint32_t r1, uint32_t r2, uint32_t r3) {
    asm volatile("stmatrix.sync.aligned.m8n8.x4.shared.b16 [%0], {%1,%2,%3,%4};" ::"r"(a), "r"(r0), "r"(r1), "r"(r2), "r"(r3) : "memory");
}
__device__ __forceinline__ void stsm4t(uint32_t a, uint32_t r0, uint32_t r1, uint32_t r2, uint32_t r3) {
    asm volatile("stmatrix.sync.aligned.m8n8.x4.trans.shared.b16 [%0], {%1,%2,%3,%4};" ::"r"(a), "r"(r0), "r"(r1), "r"(r2), "r"(r3) : "memory");
}
__device__ __forceinline__ void tma_store2d(const CUtensorMap* tm, uint32_t src, int c0, int c1) {
    asm volatile("cp.async.bulk.tensor.2d.global.shared::cta.bulk_group [%0, {%2, %3}], [%1];" ::"l"(tm), "r"(src), "r"(c0), "r"(c1) : "memory");
    asm volatile("cp.async.bulk.commit_group;" ::: "memory");
}
__device__ __forceinline__ void ldsm4(uint32_t a, uint32_t& r0, uint32_t& r1, uint32_t& r2, uint32_t& r3) {
    asm volatile("ldmatrix.sync.aligned.m8n8.x4.shared.b16 {%0,%1,%2,%3}, [%4];" : "=r"(r0), "=r"(r1), "=r"(r2), "=r"(r3) : "r"(a) : "memory");
}
__device__ __forceinline__ void ldsm4t(uint32_t a, uint32_t& r0, uint32_t& r1, uint32_t& r2, uint32_t& r3) {
    asm volatile("ldmatrix.sync.aligned.m8n8.x4.trans.shared.b16 {%0,%1,%2,%3}, [%4];" : "=r"(r0), "=r"(r1), "=r"(r2), "=r"(r3) : "r"(a) : "memory");
}
__device__ __forceinline__ void mma16816(float* c, const uint32_t* a, uint32_t b0, uint32_t b1) {
    asm("mma.sync.aligned.m16n8k16.row.col.f32.bf16.bf16.f32 {%0,%1,%2,%3}, {%4,%5,%6,%7}, {%8,%9}, {%0,%1,%2,%3};"
                 : "+f"(c[0]), "+f"(c[1]), "+f"(c[2]), "+f"(c[3])
                 : "r"(a[0]), "r"(a[1]), "r"(a[2]), "r"(a[3]), "r"(b0), "r"(b1));
}
__device__ __forceinline__ uint32_t pack_bf16(float lo, float hi) {
    uint32_t r; asm("cvt.rn.bf16x2.f32 %0, %1, %2;" : "=r"(r) : "f"(hi), "f"(lo)); return r;
}
__device__ __forceinline__ float bf_lo(uint32_t w) { return __uint_as_float(w << 16); }
__device__ __forceinline__ float bf_hi(uint32_t w) { return __uint_as_float(w & 0xffff0000u); }
__device__ __forceinline__ float ex2(float x) { float r; asm("ex2.approx.ftz.f32 %0, %1;" : "=f"(r) : "f"(x)); return r; }
__device__ __forceinline__ float rcp(float x) { float r; asm("rcp.approx.ftz.f32 %0, %1;" : "=f"(r) : "f"(x)); return r; }
__device__ __forceinline__ void bar_sync(int id, int n) { asm volatile("bar.sync %0, %1;" ::"r"(id), "r"(n) : "memory"); }

typedef unsigned long long desc_t;
__device__ __forceinline__ desc_t desc_lo(uint32_t addr) { return (desc_t)(((addr & 0x3FFFF) >> 4) | (512u << 16)) | (0x40000040ull << 32); }
__device__ __forceinline__ void wg_fence() { asm volatile("wgmma.fence.sync.aligned;" ::: "memory"); }
__device__ __forceinline__ void wg_commit() { asm volatile("wgmma.commit_group.sync.aligned;" ::: "memory"); }
template <int N> __device__ __forceinline__ void wg_wait() { asm volatile("wgmma.wait_group.sync.aligned %0;" ::"n"(N) : "memory"); }
template <int N> __device__ __forceinline__ void fence_acc(float* d) {
#pragma unroll
    for (int i = 0; i < N; i++) asm volatile("" : "+f"(d[i])::"memory");
}
#define R4(o) "+f"(d[o + 0]), "+f"(d[o + 1]), "+f"(d[o + 2]), "+f"(d[o + 3])
#define R8(o) R4(o), R4(o + 4)
__device__ __forceinline__ void wgmma_n128(float* d, desc_t da, desc_t db, int sc) {
    asm volatile("{.reg .pred p; setp.ne.b32 p, %66, 0;\n"
                 "wgmma.mma_async.sync.aligned.m64n128k16.f32.bf16.bf16 {%0,%1,%2,%3,%4,%5,%6,%7,%8,%9,%10,%11,%12,%13,%14,%15,%16,%17,%18,%19,%20,%21,%22,%23,%24,%25,%26,%27,%28,%29,%30,%31,"
                 "%32,%33,%34,%35,%36,%37,%38,%39,%40,%41,%42,%43,%44,%45,%46,%47,%48,%49,%50,%51,%52,%53,%54,%55,%56,%57,%58,%59,%60,%61,%62,%63}, %64, %65, p, 1, 1, 0, 1;}"
                 : R8(0), R8(8), R8(16), R8(24), R8(32), R8(40), R8(48), R8(56)
                 : "l"(da), "l"(db), "r"(sc));
}
__device__ __forceinline__ void wgmma_n256(float* d, desc_t da, desc_t db, int sc) {
    asm volatile("{.reg .pred p; setp.ne.b32 p, %130, 0;\n"
                 "wgmma.mma_async.sync.aligned.m64n256k16.f32.bf16.bf16 {%0,%1,%2,%3,%4,%5,%6,%7,%8,%9,%10,%11,%12,%13,%14,%15,%16,%17,%18,%19,%20,%21,%22,%23,%24,%25,%26,%27,%28,%29,%30,%31,%32,%33,%34,%35,%36,%37,%38,%39,%40,%41,%42,%43,%44,%45,%46,%47,%48,%49,%50,%51,%52,%53,%54,%55,%56,%57,%58,%59,%60,%61,%62,%63,%64,%65,%66,%67,%68,%69,%70,%71,%72,%73,%74,%75,%76,%77,%78,%79,%80,%81,%82,%83,%84,%85,%86,%87,%88,%89,%90,%91,%92,%93,%94,%95,%96,%97,%98,%99,%100,%101,%102,%103,%104,%105,%106,%107,%108,%109,%110,%111,%112,%113,%114,%115,%116,%117,%118,%119,%120,%121,%122,%123,%124,%125,%126,%127}, %128, %129, p, 1, 1, 0, 1;}"
                 : R8(0), R8(8), R8(16), R8(24), R8(32), R8(40), R8(48), R8(56), R8(64), R8(72), R8(80), R8(88), R8(96), R8(104), R8(112), R8(120)
                 : "l"(da), "l"(db), "r"(sc));
}
__device__ __forceinline__ void wgmma_n112(float* d, desc_t da, desc_t db, int sc) {
    asm volatile("{.reg .pred p; setp.ne.b32 p, %58, 0;\n"
                 "wgmma.mma_async.sync.aligned.m64n112k16.f32.bf16.bf16 {%0,%1,%2,%3,%4,%5,%6,%7,%8,%9,%10,%11,%12,%13,%14,%15,%16,%17,%18,%19,%20,%21,%22,%23,%24,%25,%26,%27,%28,%29,%30,%31,%32,%33,%34,%35,%36,%37,%38,%39,%40,%41,%42,%43,%44,%45,%46,%47,%48,%49,%50,%51,%52,%53,%54,%55}, %56, %57, p, 1, 1, 0, 1;}"
                 : R8(0), R8(8), R8(16), R8(24), R8(32), R8(40), R8(48)
                 : "l"(da), "l"(db), "r"(sc));
}
__device__ __forceinline__ void wgmma_n128_tn(float* d, desc_t da, desc_t db, int sc) {
    asm volatile("{.reg .pred p; setp.ne.b32 p, %66, 0;\n"
                 "wgmma.mma_async.sync.aligned.m64n128k16.f32.bf16.bf16 {%0,%1,%2,%3,%4,%5,%6,%7,%8,%9,%10,%11,%12,%13,%14,%15,%16,%17,%18,%19,%20,%21,%22,%23,%24,%25,%26,%27,%28,%29,%30,%31,%32,%33,%34,%35,%36,%37,%38,%39,%40,%41,%42,%43,%44,%45,%46,%47,%48,%49,%50,%51,%52,%53,%54,%55,%56,%57,%58,%59,%60,%61,%62,%63}, %64, %65, p, 1, 1, 1, 0;}"
                 : R8(0), R8(8), R8(16), R8(24), R8(32), R8(40), R8(48), R8(56)
                 : "l"(da), "l"(db), "r"(sc));
}
__device__ __forceinline__ void wgmma_n64(float* d, desc_t da, desc_t db, int sc) {
    asm volatile("{.reg .pred p; setp.ne.b32 p, %34, 0;\n"
                 "wgmma.mma_async.sync.aligned.m64n64k16.f32.bf16.bf16 {%0,%1,%2,%3,%4,%5,%6,%7,%8,%9,%10,%11,%12,%13,%14,%15,%16,%17,%18,%19,%20,%21,%22,%23,%24,%25,%26,%27,%28,%29,%30,%31}, %32, %33, p, 1, 1, 0, 1;}"
                 : R8(0), R8(8), R8(16), R8(24)
                 : "l"(da), "l"(db), "r"(sc));
}
__device__ __forceinline__ void wgmma_n40_tt(float* d, desc_t da, desc_t db, int sc) {
    asm volatile("{.reg .pred p; setp.ne.b32 p, %22, 0;\n"
                 "wgmma.mma_async.sync.aligned.m64n40k16.f32.bf16.bf16 {%0,%1,%2,%3,%4,%5,%6,%7,%8,%9,%10,%11,%12,%13,%14,%15,%16,%17,%18,%19}, %20, %21, p, 1, 1, 1, 1;}"
                 : R8(0), R8(8), R4(16)
                 : "l"(da), "l"(db), "r"(sc));
}

__device__ __forceinline__ void wgmma_n8_tt(float* d, desc_t da, desc_t db, int sc) {
    asm volatile("{.reg .pred p; setp.ne.b32 p, %6, 0;\n"
                 "wgmma.mma_async.sync.aligned.m64n8k16.f32.bf16.bf16 {%0,%1,%2,%3}, %4, %5, p, 1, 1, 1, 1;}"
                 : R4(0)
                 : "l"(da), "l"(db), "r"(sc));
}

__device__ __forceinline__ uint32_t readback(const void* p) {
    uint32_t v; asm volatile("ld.relaxed.gpu.global.u32 %0, [%1];" : "=r"(v) : "l"(p) : "memory"); return v;
}
__device__ __forceinline__ uint32_t atom_f32x2(float* p, float a, float b) {
    float x, y;
    asm volatile("atom.relaxed.gpu.global.add.v2.f32 {%0,%1}, [%2], {%3,%4};" : "=f"(x), "=f"(y) : "l"(p), "f"(a), "f"(b) : "memory");
    return __float_as_uint(x);
}
__device__ __forceinline__ uint32_t atom_f32_if(float* p, float a, bool pred) {
    float x = 0.f;
    asm volatile("{.reg .pred p; setp.ne.u32 p, %3, 0; @p atom.relaxed.gpu.global.add.f32 %0, [%1], %2;}" : "+f"(x) : "l"(p), "f"(a), "r"((uint32_t)pred) : "memory");
    return __float_as_uint(x);
}
__device__ __forceinline__ void signal_after(unsigned* cnt, uint32_t ack, uint32_t zero, bool pred) {
    asm volatile("{.reg .pred p; setp.ne.u32 p, %2, 0; @p red.relaxed.gpu.global.add.u32 [%0], %1;}"
                 ::"l"(cnt), "r"((ack & zero) + 1), "r"((uint32_t)pred) : "memory");
}
__device__ __forceinline__ void signal_late(unsigned* cnt, const uint32_t* a, uint32_t zero, bool pred) {
    uint32_t v;
    asm volatile("{.reg .b32 t; lop3.b32 t, %1, %2, %3, 0xfe; lop3.b32 %0, t, %4, %5, 0xfe;}"
                 : "=r"(v) : "r"(a[0]), "r"(a[1]), "r"(a[2]), "r"(a[3]), "r"(a[4]));
    signal_after(cnt, v, zero, pred);
}
__device__ __forceinline__ void red_f32_if(float* p, float a, bool pred) {
    asm volatile("{.reg .pred p; setp.ne.u32 p, %2, 0; @p red.relaxed.gpu.global.add.f32 [%0], %1;}" ::"l"(p), "f"(a), "r"((uint32_t)pred) : "memory");
}
__device__ __forceinline__ void stg_f2_if(float* p, float a, float b, bool pred) {
    asm volatile("{.reg .pred p; setp.ne.u32 p, %3, 0; @p st.global.v2.f32 [%0], {%1,%2};}" ::"l"(p), "f"(a), "f"(b), "r"((uint32_t)pred) : "memory");
}
__device__ __forceinline__ void stg64(void* p, uint32_t a, uint32_t b) {
    asm volatile("st.global.v2.u32 [%0], {%1,%2};" ::"l"(p), "r"(a), "r"(b) : "memory");
}
__device__ __forceinline__ void mma16816_z(float* c, const uint32_t* a, uint32_t b0, uint32_t b1) {
    asm("mma.sync.aligned.m16n8k16.row.col.f32.bf16.bf16.f32 {%0,%1,%2,%3}, {%4,%5,%6,%7}, {%8,%9}, {%10,%10,%10,%10};"
                 : "=f"(c[0]), "=f"(c[1]), "=f"(c[2]), "=f"(c[3])
                 : "r"(a[0]), "r"(a[1]), "r"(a[2]), "r"(a[3]), "r"(b0), "r"(b1), "f"(0.f));
}
__device__ __forceinline__ uint32_t max2(uint32_t a, uint32_t b) { uint32_t r; asm("max.bf16x2 %0, %1, %2;" : "=r"(r) : "r"(a), "r"(b)); return r; }
__device__ __forceinline__ uint32_t min2(uint32_t a, uint32_t b) { uint32_t r; asm("min.bf16x2 %0, %1, %2;" : "=r"(r) : "r"(a), "r"(b)); return r; }
__device__ __forceinline__ void bar_arrive(int id, int n) { asm volatile("bar.arrive %0, %1;" ::"r"(id), "r"(n) : "memory"); }
__device__ __forceinline__ void mbar_arrive_n_if(uint32_t bar, uint32_t n, bool pred) {
    asm volatile("{.reg .pred p; setp.ne.u32 p, %1, 0; @p mbarrier.arrive.shared::cta.b64 _, [%0], %2;}" ::"r"(bar), "r"((uint32_t)pred), "r"(n) : "memory");
}
__device__ __forceinline__ float4 lds_f4(uint32_t a) {
    float4 v;
    asm volatile("ld.shared.v4.f32 {%0,%1,%2,%3}, [%4];" : "=f"(v.x), "=f"(v.y), "=f"(v.z), "=f"(v.w) : "r"(a) : "memory");
    return v;
}
__device__ __forceinline__ uint4 ld_tagged(const unsigned long long* p) {
    unsigned long long a, b;
    asm volatile("ld.acquire.gpu.global.v2.b64 {%0,%1}, [%2];" : "=l"(a), "=l"(b) : "l"(p) : "memory");
    return make_uint4((unsigned)a, (unsigned)(a >> 32), (unsigned)b, (unsigned)(b >> 32));
}
__device__ __forceinline__ uint4 ld_tagged_rlx(const unsigned long long* p) {
    unsigned long long a, b;
    asm volatile("ld.relaxed.gpu.global.v2.b64 {%0,%1}, [%2];" : "=l"(a), "=l"(b) : "l"(p) : "memory");
    return make_uint4((unsigned)a, (unsigned)(a >> 32), (unsigned)b, (unsigned)(b >> 32));
}
__device__ __forceinline__ void st_tagged_if(unsigned long long* p, float a, float b, unsigned tag, bool pred) {
    const unsigned long long t = (unsigned long long)tag << 32;
    asm volatile("{.reg .pred p; setp.ne.u32 p, %3, 0; @p st.relaxed.gpu.global.v2.b64 [%0], {%1,%2};}"
                 ::"l"(p), "l"(t | __float_as_uint(a)), "l"(t | __float_as_uint(b)), "r"((uint32_t)pred) : "memory");
}

__device__ __forceinline__ void store_tile(uint32_t tile_rows, __nv_bfloat16* gdst, const uint32_t* lo, const uint32_t* hi, int lane, uint32_t* ack) {
    const int r = lane & 15;
#pragma unroll
    for (int b = 0; b < 4; b++)
        stsm4(tile_rows + r * 128 + (((2 * b + (lane >> 4)) ^ (r & 7)) << 4), lo[2 * b], hi[2 * b], lo[2 * b + 1], hi[2 * b + 1]);
    fence_async_smem();
    __syncwarp();
#pragma unroll
    for (int i = 0; i < 4; i++) {
        const int rr = 4 * i + (lane >> 3);
        const uint4 v = lds128(tile_rows + rr * 128 + (((lane & 7) ^ (rr & 7)) << 4));
        stg128(gdst + rr * DM + (lane & 7) * 8, v.x, v.y, v.z, v.w);
    }
#pragma unroll
    for (int i = 0; i < 4; i++) ack[i] = readback(gdst + (4 * i + (lane >> 3)) * DM + (lane & 7) * 8);
}

__device__ __forceinline__ void feature_maps(const uint32_t* a, const uint32_t* wb, float c0, float c1, uint32_t* plus, uint32_t* minus) {
    uint32_t P[16], mx[4], mn[4];
#pragma unroll
    for (int h = 0; h < 4; h++) {
        float p[8];
        mma16816_z(p, a + 4 * h, wb[4 * h], wb[4 * h + 1]);
        mma16816_z(p + 4, a + 4 * h, wb[4 * h + 2], wb[4 * h + 3]);
        P[4 * h] = pack_bf16(p[0], p[2]); P[4 * h + 1] = pack_bf16(p[1], p[3]);
        P[4 * h + 2] = pack_bf16(p[4], p[6]); P[4 * h + 3] = pack_bf16(p[5], p[7]);
        mx[h] = max2(max2(P[4 * h], P[4 * h + 1]), max2(P[4 * h + 2], P[4 * h + 3]));
        mn[h] = min2(min2(P[4 * h], P[4 * h + 1]), min2(P[4 * h + 2], P[4 * h + 3]));
    }
#pragma unroll
    for (int s = 1; s <= 2; s <<= 1) {
        uint32_t tx[4], tn[4];
#pragma unroll
        for (int h = 0; h < 4; h++) { tx[h] = __shfl_xor_sync(0xffffffffu, mx[h], s); tn[h] = __shfl_xor_sync(0xffffffffu, mn[h], s); }
#pragma unroll
        for (int h = 0; h < 4; h++) { mx[h] = max2(mx[h], tx[h]); mn[h] = min2(mn[h], tn[h]); }
    }
#pragma unroll
    for (int h = 0; h < 4; h++) {
        const float mx0 = bf_lo(mx[h]) * c0, mx1 = bf_hi(mx[h]) * c1, mn0 = bf_lo(mn[h]) * c0, mn1 = bf_hi(mn[h]) * c1;
        float ep[8], em[8];
#pragma unroll
        for (int i = 0; i < 8; i++) {
            const bool r1 = (i & 2);
            const uint32_t w = P[4 * h + (i >> 2) * 2 + (i & 1)];
            const float p = r1 ? bf_hi(w) : bf_lo(w);
            ep[i] = ex2(fmaf(p, r1 ? c1 : c0, r1 ? -mx1 : -mx0));
            em[i] = ex2(fmaf(p, r1 ? -c1 : -c0, r1 ? mn1 : mn0));
        }
        float sp[4], sm[4];
        uint32_t tp[4], tm[4];
#pragma unroll
        for (int i = 0; i < 4; i++) { tp[i] = pack_bf16(ep[2 * i], ep[2 * i + 1]); tm[i] = pack_bf16(em[2 * i], em[2 * i + 1]); }
        mma16816_z(sp, tp, 0x3f803f80u, 0x3f803f80u);
        mma16816_z(sm, tm, 0x3f803f80u, 0x3f803f80u);
        const float r0 = rcp(sp[0] * sm[0]), r1 = rcp(sp[2] * sm[2]);
        const float rs[4] = {r0 * sm[0], r1 * sm[2], r0 * sp[0], r1 * sp[2]};
#pragma unroll
        for (int i = 0; i < 4; i++) {
            plus[4 * h + i] = pack_bf16(ep[2 * i] * rs[i & 1], ep[2 * i + 1] * rs[i & 1]);
            minus[4 * h + i] = pack_bf16(em[2 * i] * rs[2 + (i & 1)], em[2 * i + 1] * rs[2 + (i & 1)]);
        }
    }
}

template <bool SCALE>
__device__ __forceinline__ void ln_frag(const float* acc, uint32_t cs_addr, float rs0, float nm0, float rs1, float nm1, uint32_t* a) {
    const float2 c0 = lds_f2(cs_addr), c1 = lds_f2(cs_addr + 32);
    const float s0 = SCALE ? rs0 : 1.f, s1 = SCALE ? rs1 : 1.f;
    a[0] = pack_bf16(fmaf(nm0, c0.x, acc[0]) * s0, fmaf(nm0, c0.y, acc[1]) * s0);
    a[1] = pack_bf16(fmaf(nm1, c0.x, acc[2]) * s1, fmaf(nm1, c0.y, acc[3]) * s1);
    a[2] = pack_bf16(fmaf(nm0, c1.x, acc[4]) * s0, fmaf(nm0, c1.y, acc[5]) * s0);
    a[3] = pack_bf16(fmaf(nm1, c1.x, acc[6]) * s1, fmaf(nm1, c1.y, acc[7]) * s1);
}

template <int UP>
__device__ __forceinline__ uint32_t hh_pair(const float* ag, float4 cs, float nmean) {
    const float g0 = fmaf(nmean, cs.x, ag[0]), g1 = fmaf(nmean, cs.y, ag[1]);
    const float u0 = fmaf(nmean, cs.z, ag[UP]), u1 = fmaf(nmean, cs.w, ag[UP + 1]);
    return pack_bf16(g0 * u0, g1 * u1);
}
template <int UP, int NTP>
__device__ __forceinline__ void hh_stage(const float* acc, uint32_t cs3, float nm0, float nm1, uint32_t stg, int lane) {
#pragma unroll
    for (int tp = 0; tp < NTP; tp++) {
        const float4 c0 = lds_f4(cs3 + tp * 128), c1 = lds_f4(cs3 + tp * 128 + 64);
        stsm4(stg + (lane & 15) * 128 + (((2 * tp + (lane >> 4)) ^ (lane & 7)) << 4), hh_pair<UP>(acc + 8 * tp, c0, nm0),
              hh_pair<UP>(acc + 8 * tp + 2, c0, nm1), hh_pair<UP>(acc + 8 * tp + 4, c1, nm0), hh_pair<UP>(acc + 8 * tp + 6, c1, nm1));
    }
    fence_async_smem();
    __syncwarp();
}

struct Ring {
    int slot; uint32_t phase;
    __device__ __forceinline__ void adv() { if (++slot == NB) { slot = 0; phase ^= 1; } }
};

__global__ void __launch_bounds__(NTHREADS, 1) fused_kernel(const __grid_constant__ Params P) {
    extern __shared__ __align__(1024) uint8_t smem_raw[];
    const uint32_t sb = smem_u32(smem_raw);
    const int tid = threadIdx.x, lane = tid & 31;
    const int warp = __shfl_sync(0xffffffffu, tid >> 5, 0);
    unsigned role = blockIdx.x;
    if (P.use_smid) asm volatile("mov.u32 %0, %%smid;" : "=r"(role));
    role = P.role[role];
    const int m = role >> 3, j = role & 7;
    const bool helper = role >= 128;

    TL(0, tid == 0); TLG(0, tid == 0);
    float* const acc_j = g_acc + j * ACC_SIZE;
    unsigned* const cnt_j = g_cnt + j * 32;

    if (__builtin_expect(warp >= 8, 1)) {
        asm volatile("setmaxnreg.dec.sync.aligned.u32 72;");
        if (elect_one()) {
            if (warp == 8) {
                if (!helper) {
#pragma unroll
                    for (int i = 0; i < NB; i++) mbar_init(sb + BAR_FULLB + 8 * i, 1);
#pragma unroll
                    for (int i = 0; i < 2; i++) {
                        mbar_expect_tx(sb + BAR_FULLB + 8 * i, SLOT);
                        tma3d(sb + OFF_B + i * SLOT, &P.twkv, sb + BAR_FULLB + 8 * i, 64 * j, 64 * i, 1);
                    }
                }
            } else if (warp == 9) {
#pragma unroll
                for (int i = 0; i < 8; i++) mbar_init(sb + BAR_FULLA + 8 * i, 1);
#pragma unroll
                for (int i = 0; i < 2; i++) {
                    mbar_expect_tx(sb + BAR_FULLA + 8 * i, SLOT);
                    tma2d(sb + OFF_A + i * SLOT, helper ? &P.twq : &P.tx, sb + BAR_FULLA + 8 * i, helper ? DM + 128 * j : 64 * i, 128 * (helper ? i : m));
                }
            } else if (warp == 10) {
#pragma unroll
                for (int i = 0; i < 9; i++) mbar_init(sb + BAR_CS1 + 8 * i, i == 0 || i == 8 ? 64 : (i == 1 ? 96 : (i < 4 ? 32 : 8)));
                trap_if_gt(sb & 1023, 0);
            } else {
#pragma unroll
                for (int i = 0; i < 14; i++) mbar_init(sb + (i < 8 ? BAR_EMPTYA : BAR_EMPTYB - 64) + 8 * i, 8);
            }
        }
        __syncwarp();
        const unsigned epoch = ld_relaxed(&g_epoch);
        bar_sync(0, NTHREADS);
        if (helper) {
            if (warp == 8) {
                if (elect_one()) {
#pragma unroll 1
                    for (int i = 2; i < 72; i++) {
                        const uint32_t full = sb + BAR_FULLA + 8 * (i & 7), dst = sb + OFF_A + (i & 7) * SLOT;
                        mbar_wait(sb + BAR_EMPTYA + 8 * (i & 7), ((i >> 3) & 1) ^ 1);
                        mbar_expect_tx(full, SLOT);
                        if (i < 24) {
                            tma2d(dst, &P.twq, full, (i < 16 ? DM + 64 * (i & 8) : 0) + 128 * j + 16 * (i & 4), 128 * (i & 3));
                        } else {
                            const int u = (i >> 3) - 3, c0 = 176 * (2 * j + (u & 1)) + 64 * (u >> 1);
                            tma2d(dst, &P.twg, full, c0, 64 * (i & 7));
                            tma2d(dst + 8192, &P.twu, full, c0, 64 * (i & 7));
                        }
                    }
                    prefetch_l2(P.wd + (size_t)j * 176128, 352256);
                }
            } else if (warp == 9) {
                wait_count_warp(g_cnt + (lane & 7) * 32, epoch * 32);
            }
            return;
        }
        if (warp == 8) {
            if (elect_one()) {
                if (m >= 3 && m < 8)
                    asm volatile("cp.async.bulk.prefetch.tensor.3d.L2.global [%0, {%1, %2, %3}];" ::"l"(&P.twkv), "r"(64 * j), "r"(64 * m), "r"(1) : "memory");
                if (j >= 3)
                    asm volatile("cp.async.bulk.prefetch.tensor.2d.L2.global [%0, {%1, %2}];" ::"l"(&P.tx), "r"(64 * j), "r"(128 * m) : "memory");
                Ring r{2, 0};
#pragma unroll 1
                for (int i = 2; i < 56; i++) {
                    const uint32_t full = sb + BAR_FULLB + 8 * r.slot, dst = sb + OFF_B + r.slot * SLOT;
                    mbar_wait(sb + BAR_EMPTYB + 8 * r.slot, r.phase ^ 1);
                    if (i >= 10 && i < 14) {
                        mbar_arrive(full);
                    } else {
                        if (i >= AHEAD && i < 6) mbar_wait(full - 8 * AHEAD, 0);
                        mbar_expect_tx(full, SLOT);
                        if (i < 8) {
                            tma3d(dst, &P.twkv, full, 64 * j, 64 * i, 1);
                        } else if (i < 16) {
                            tma2d(dst, &P.twq, full, 64 * j, 128 * (i & 3));
                        } else if (i >= 20 && i < 36) {
                            const int k0 = 64 * KORD((i - 20) >> 1, j) + 32 * (i & 1);
                            tma3d(dst, &P.twg2, full, 176 * j, k0, 0);
                            tma3d(dst + 8192, &P.twu2, full, 176 * j, k0, 0);
                        } else {
                            const int e = 2 * (i & 3);
                            const bool wo = i < 20, gu = !wo && i < 44;
                            const int c0 = gu ? 176 * j + 128 : 64 * j;
                            const int r0 = wo ? 64 * KORD(e, j) : (gu ? 64 * (i - 36) : 176 * e + 64 * ((i - 44) >> 2));
                            const int r1 = wo ? 64 * KORD(e + 1, j) : (gu ? r0 : r0 + 176);
                            tma2d(dst, wo ? &P.two : (gu ? &P.twg : &P.twd), full, c0, r0);
                            tma2d(dst + 8192, wo ? &P.two : (gu ? &P.twu : &P.twd), full, c0, r1);
                        }
                    }
                    r.adv();
                }
            }
            return;
        }
        if (warp == 9) {
            if (elect_one()) {
#pragma unroll 1
                for (int i = 2; i < 8; i++) {
                    if (i >= AHEAD + 1) mbar_wait(sb + BAR_FULLA + 8 * (i - AHEAD - 1), 0);
                    mbar_expect_tx(sb + BAR_FULLA + 8 * i, SLOT);
                    tma2d(sb + OFF_A + i * SLOT, &P.tx, sb + BAR_FULLA + 8 * i, 64 * i, 128 * m);
                }
#pragma unroll 1
                for (int i = 1; i < 12; i++) prefetch_tmap(&P.tx + i);
#pragma unroll 1
                for (int r = 1; r < 6; r++) {
                    const CUtensorMap* tm = &P.tx + min(r, 3);
                    const int cstep = r < 3 ? 64 : 192, cbase = r < 3 ? 0 : 64 * (r - 3), skip = r < 3 ? j : 8;
                    wait_count(g_flag + (m * 5 + r - 1) * 32, epoch * (r < 3 ? 64 : 8));
                    TL(64 + r, true);
#pragma unroll 1
                    for (int t = 0; t < 8; t++) {
                        if (t == skip) continue;
                        mbar_wait(sb + BAR_EMPTYA + 8 * t, (r - 1) & 1);
                        mbar_expect_tx(sb + BAR_FULLA + 8 * t, SLOT);
                        tma2d(sb + OFF_A + t * SLOT, tm, sb + BAR_FULLA + 8 * t, cbase + cstep * t, 128 * m);
                    }
                }
            }
            return;
        }
        const int a = warp - 10;
        {
            const int row = 16 * j + 8 * a + (lane >> 2);
            const uint32_t ra = sb + OFF_A + row * 128;
            float sh = 0.f, s0 = 0.f, s1 = 0.f, q0 = 0.f, q1 = 0.f;
#pragma unroll 1
            for (int kt = 0; kt < 8; kt++) {
                mbar_wait(sb + BAR_FULLA + 8 * kt, 0);
                if (kt == 0) sh = bf_lo(lds128(ra + ((row & 7) << 4)).x);
#pragma unroll
                for (int i = 0; i < 2; i++) {
                    const uint4 v = lds128(ra + kt * SLOT + (((2 * (lane & 3) + i) ^ (row & 7)) << 4));
                    const uint32_t ww[4] = {v.x, v.y, v.z, v.w};
#pragma unroll
                    for (int e = 0; e < 4; e++) {
                        const float d0 = bf_lo(ww[e]) - sh, d1 = bf_hi(ww[e]) - sh;
                        s0 += d0; q0 = fmaf(d0, d0, q0);
                        s1 += d1; q1 = fmaf(d1, d1, q1);
                    }
                }
            }
            s0 += s1; q0 += q1;
#pragma unroll
            for (int o = 1; o <= 2; o <<= 1) { s0 += __shfl_xor_sync(0xffffffffu, s0, o); q0 += __shfl_xor_sync(0xffffffffu, q0, o); }
            const float md = s0 * (1.f / DM);
            const float rs = rsqrtf(fmaxf(q0 * (1.f / DM) - md * md, 0.f) + 1e-5f);
            st_tagged_if(g_xstat + 2 * (128 * m + row), rs, -(sh + md), epoch, (lane & 3) == 0);
        }
        const unsigned long long* cs = g_cs + j * 768 + 2 * lane;
#pragma unroll 1
        for (int c = 0; c < (a ? 5 : 10); c++) {
            if (c == 4) {
                const int t = 32 * a + lane;
                const uint32_t kvs = sb + OFF_A + KVS(j) * SLOT;
                mbar_wait(sb + BAR_KVW, 0);
#pragma unroll 1
                for (int pass = 0; pass < 2; pass++) {
                    float4 v[8];
#pragma unroll
                    for (int i = 0; i < 8; i++) v[i] = ld_l2_f4(acc_j + ACC_KV + 4 * (t + 64 * i));
                    const float2 zz = ld_l2_f2(acc_j + ACC_Z + 2 * t);
#pragma unroll
                    for (int i = 0; i < 8; i++)
                        sts64(kvs + ((t >> 2) + 16 * i) * 48 + (t & 3) * 8, pack_bf16(v[i].x, v[i].y), pack_bf16(v[i].z, v[i].w));
                    const uint32_t z0 = pack_bf16(zz.x, zz.x), z1 = pack_bf16(zz.y, zz.y);
                    sts128(kvs + t * 96 + 32, z0, z0, z0, z0);
                    sts128(kvs + t * 96 + 80, z1, z1, z1, z1);
                    if (pass == 0) {
                        __syncwarp();
                        if (lane == 0) red_relaxed(cnt_j, 1);
                        TL(19, t == 0);
                        wait_count_warp(cnt_j, epoch * 32);
                        TL(12, t == 0);
                    }
                }
                mbar_arrive(sb + BAR_KVR);
                uint32_t it = 0;
                while (__any_sync(0xffffffffu, (int)(ld_acquire(g_flag + (m * 5 + 1) * 32) - epoch * 64) < 0)) {
                    __nanosleep(500);
                    trap_if_gt(++it, 1u << 22);
                }
                if (a) break;
            }
            if (c == 3 && !a) continue;
            const unsigned long long* src = c < 2 ? g_xstat + 2 * (128 * m + 64 * a + 32 * c + lane) : cs + (c < 4 ? 128 * (a + c - 2) : 128 + 64 * c);
            const uint32_t dst = c < 2 ? OFF_XST + (64 * a + 32 * c + lane) * 8
                                       : (c < 4 ? OFF_CS1 + (c == 2 ? 256 * (a + 1) : 0) + 8 * lane : OFF_CS3 + (32 * ((c - 4) >> 1) + lane) * 16 + 8 * (c & 1));
            uint4 v;
            uint32_t it = 0;
            while (true) {
                v = ld_tagged(src);
                if (!__any_sync(0xffffffffu, v.y != epoch || v.w != epoch)) break;
                __nanosleep(60);
                trap_if_gt(++it, 1u << 22);
            }
            sts64(sb + dst, v.x, v.z);
            if (c == 2 - a || (a && c > 1) || c == 9) mbar_arrive(sb + (c == 9 ? BAR_CS3 : (c == 2 - a ? BAR_CS1 : (c == 2 ? BAR_CSV : BAR_CSQ))));
        }
#pragma unroll 1
        for (int rr = 0; rr < 2; rr++) {
            const int row = 64 * rr + 32 * a + lane;
            const float* sp = g_hstat + (1024 * m + row) * 2;
            float2 v[8];
#pragma unroll
            for (int i = 0; i < 8; i++) v[i] = ld_l2_f2(sp + 256 * i);
            float mean = 0.f;
#pragma unroll
            for (int i = 0; i < 8; i++) mean += v[i].x;
            mean *= 0.125f;
            float m2 = 0.f, dv = 0.f;
#pragma unroll
            for (int i = 0; i < 8; i++) { m2 += v[i].y; dv = fmaf(v[i].x - mean, v[i].x - mean, dv); }
            sts_f2(sb + OFF_CS1 + row * 8, -mean, __fdividef(1.f, fmaf(dv, 64.f, m2) * (1.f / DM) + 1e-5f));
        }
        mbar_arrive(sb + BAR_CS3);
#pragma unroll 1
        for (int c = a; c < 3; c += 2) {
            const int slot = c == 2 ? 1 : 4 + c;
            mbar_wait(sb + BAR_STG + 8 * c, 0);
            if (elect_one()) {
                tma_store2d(&P.thh, sb + OFF_B + slot * SLOT, 192 * j + 64 * c, 128 * m);
                asm volatile("cp.async.bulk.wait_group.read 0;" ::: "memory");
                mbar_arrive_n_if(sb + BAR_EMPTYB + 8 * slot, 8, true);
                asm volatile("cp.async.bulk.wait_group 0;" ::: "memory");
            }
            __syncwarp();
            TL(60 + c, lane == 0);
            uint32_t ack = 0;
#pragma unroll
            for (int i = 0; i < 4; i++) ack |= readback(g_hh + (size_t)(128 * m + 32 * i + lane) * FFP + 192 * j + 64 * c);
            signal_after(g_flag + (m * 5 + 2 + c) * 32, ack, P.zero, lane == 0);
            TL(54 + c, lane == 0);
        }
        return;
    }
    const unsigned epoch = ld_relaxed(&g_epoch);
    uint32_t wraw[16];
    if (!helper) {
        const uint32_t* wp = reinterpret_cast<const uint32_t*>(P.wphi) + (4 * j) * 128 + (lane & 3) * 16 + (lane >> 2);
#pragma unroll
        for (int i = 0; i < 16; i++)
            asm volatile("ld.global.nc.u32 %0, [%1];" : "=r"(wraw[i]) : "l"(wp + (i >> 2) * 128 + ((i >> 1) & 1) * 64 + (i & 1) * 8));
    }
    asm volatile("setmaxnreg.inc.sync.aligned.u32 216;");
    bar_sync(0, NTHREADS);
    if (helper) {
        if (warp < 4) {
            sts128(sb + OFF_B + 16 * tid, 0x3f803f80u, 0x3f803f80u, 0x3f803f80u, 0x3f803f80u);
            for (int i = tid; i < 2 * ACC_SIZE / 4; i += 128) stg128(g_acc + 2 * j * ACC_SIZE + 4 * i, 0, 0, 0, 0);
            fence_async_smem();
            fence_gpu();
            bar_sync(1, 128);
            float acc[8];
            int i = 0;
#pragma unroll 1
            for (int job = 0; job < 12; job++) {
                const int n = job < 6 ? 4 : 8;
#pragma unroll 1
                for (int t = 0; t < n; t++, i++) {
                    mbar_wait(sb + BAR_FULLA + 8 * (i & 7), (i >> 3) & 1);
                    wg_fence();
#pragma unroll
                    for (int k = 0; k < 8; k++)
                        wgmma_n8_tt(acc + (k & 4), desc_lo(sb + OFF_A) + (i & 7) * (SLOT >> 4) + 128 * k, desc_lo(sb + OFF_B), (t | (k & 3)) != 0);
                    wg_commit();
                    wg_wait<1>();
                    mbar_arrive_n_if(sb + BAR_EMPTYA + 8 * ((i + 7) & 7), 2, lane == 0 && i > 0);
                }
                wg_wait<0>();
                fence_acc<8>(acc);
                const int q = lane & 3;
                const float lo = (q & 1) ? acc[2] : acc[0], hi = (q & 1) ? acc[6] : acc[4];
                const float v = job < 6 ? lo + hi : ((q & 2) ? hi : lo);
                unsigned long long* dst = g_cs + ((2 * j + (job & 1)) * 6 + (job >> 1)) * 128 + (q >> 1) * 64 + 16 * warp + 8 * (q & 1) + (lane >> 2);
                asm volatile("st.relaxed.gpu.global.b64 [%0], %1;" ::"l"(dst), "l"(((unsigned long long)epoch << 32) | __float_as_uint(v)) : "memory");
            }
        }
        return;
    }
    {
        const int w = warp >> 2, wv = warp & 3, g = lane >> 2, q = lane & 3;
        const int row_w = 128 * m + 16 * warp;
        const uint32_t sa = sb + OFF_A + w * 8192;
        const desc_t dA = desc_lo(sa), dB = desc_lo(sb + OFF_B);
        unsigned* const flag_m = g_flag + m * 160;
        const bool l0 = lane == 0;
        Ring rg{0, 0};
        int prev = 0;

        uint32_t wb[16];
        constexpr float L2E = 1.4426950408889634f;
        const int ch = lane >> 4, sw = lane & 7;
        const uint32_t lrow = (lane & 15) * 128;
        uint32_t fp[16], fm[16];
        {
            float acc[64], accq[32];
#pragma unroll 1
            for (int kt = 0; kt < 8; kt++) {
                mbar_waitc(sb + BAR_FULLA + 8 * kt, 0);
                mbar_waitc(sb + BAR_FULLB + 8 * rg.slot, rg.phase);
                const desc_t da = dA + kt * (SLOT >> 4), db = dB + rg.slot * (SLOT >> 4);
                wg_fence();
#pragma unroll
                for (int k = 0; k < 4; k++) wgmma_n128(acc, da + 2 * k, db + 128 * k, (kt | k) != 0);
                wg_commit();
                wg_wait<1>();
                mbar_arrive_if(sb + BAR_EMPTYB + 8 * prev, l0 && kt > 0);
                prev = rg.slot; rg.adv();
            }
#pragma unroll
            for (int i = 0; i < 8; i++) {
                wb[(i >> 1) * 4 + (i & 1)] = __byte_perm(wraw[2 * i], wraw[2 * i + 1], 0x5410);
                wb[(i >> 1) * 4 + 2 + (i & 1)] = __byte_perm(wraw[2 * i], wraw[2 * i + 1], 0x7632);
            }
            float2 s0, s1;
            uint32_t a[16];
            wg_wait<0>();
            fence_acc<64>(acc);
            mbar_arrive_if(sb + BAR_EMPTYB + 8 * prev, l0);
#pragma unroll 1
            for (int it = 0; it < 2; it++) {
                mbar_waitc(sb + BAR_FULLB + 8 * 2, it ^ 1); mbar_waitc(sb + BAR_FULLB + 8 * 3, it ^ 1);
                const desc_t da = dA + it * (4 * SLOT >> 4);
                wg_fence();
#pragma unroll
                for (int k = 0; k < 16; k++) wgmma_n64(accq, da + (k >> 2) * (SLOT >> 4) + (k & 3) * 2, dB + 2 * (SLOT >> 4) + 128 * k, (it | k) != 0);
                wg_commit();
                TL(17 + it, tid == 0);
                mbar_waitc(sb + BAR_CS1 + 16 * it, 0);
                s0 = lds_f2(sb + OFF_XST + (16 * warp + g) * 8); s1 = lds_f2(sb + OFF_XST + (16 * warp + g + 8) * 8);
                wg_wait<0>();
                fence_acc<32>(accq);
                mbar_arrive_if(sb + BAR_EMPTYB + 8 * (2 + lane), lane < 2);
                TL(2 + 2 * it, tid == 0);
                if (it == 0) {
#pragma unroll
                    for (int hh = 0; hh < 4; hh++)
                        ln_frag<false>(acc + 8 * hh, sb + OFF_CS1 + (64 + 16 * hh + 2 * q) * 4, 0.f, s0.y, 0.f, s1.y, a + 4 * hh);
                } else {
#pragma unroll
                    for (int hh = 0; hh < 4; hh++)
                        ln_frag<false>(accq + 8 * hh, sb + OFF_CS1 + (16 * hh + 2 * q) * 4, 0.f, s0.y, 0.f, s1.y, a + 4 * hh);
                }
                feature_maps(a, wb, s0.x * L2E, s1.x * L2E, fp, fm);
                if (it == 0) {
                    mbar_waitc(sb + BAR_FULLB + 8 * 4, 1); mbar_waitc(sb + BAR_FULLB + 8 * 5, 1);
                    mbar_waitc(sb + BAR_FULLB + 8 * 0, 0); mbar_waitc(sb + BAR_FULLB + 8 * 1, 0);
                    mbar_waitc(sb + BAR_CSV, 0);
                    const uint32_t st = sb + OFF_B + warp * 2048 + lrow;
#pragma unroll
                    for (int hh = 0; hh < 4; hh++) {
                        stsm4(st + (4 + (hh >> 1)) * SLOT + (((4 * (hh & 1) + ch) ^ sw) << 4), fp[4 * hh], fp[4 * hh + 1], fp[4 * hh + 2], fp[4 * hh + 3]);
                        stsm4(st + (4 + (hh >> 1)) * SLOT + (((4 * (hh & 1) + 2 + ch) ^ sw) << 4), fm[4 * hh], fm[4 * hh + 1], fm[4 * hh + 2], fm[4 * hh + 3]);
                        ln_frag<true>(acc + 32 + 8 * hh, sb + OFF_CS1 + (128 + 16 * hh + 2 * q) * 4, s0.x, s0.y, s1.x, s1.y, a);
                        stsm4(st + (hh >> 1) * SLOT + (((2 * (hh & 1) + ch) ^ sw) << 4), a[0], a[1], a[2], a[3]);
                    }
                    stsm4(st + ch * SLOT + ((4 ^ sw) << 4), 0x3f803f80u, 0x3f803f80u, 0x3f803f80u, 0x3f803f80u);
                    fence_async_smem();
                    bar_sync(1, 256);
                    float kvd[20];
                    wg_fence();
#pragma unroll
                    for (int k = 0; k < 8; k++)
                        wgmma_n40_tt(kvd, dB + (4 + w) * (SLOT >> 4) + 128 * k, dB + w * (SLOT >> 4) + 128 * k, k != 0);
                    wg_commit();
                    wg_wait<0>();
                    fence_acc<20>(kvd);
                    const bool h1 = wv >= 2;
                    const int f = 16 * warp + g;
                    float* kvp = acc_j + ACC_KV + f * 16 + 2 * q;
                    red_f32x2(kvp, h1 ? kvd[8] : kvd[0], h1 ? kvd[9] : kvd[1]);
                    red_f32x2(kvp + 128, h1 ? kvd[10] : kvd[2], h1 ? kvd[11] : kvd[3]);
                    red_f32x2(kvp + 8, h1 ? kvd[12] : kvd[4], h1 ? kvd[13] : kvd[5]);
                    red_f32x2(kvp + 136, h1 ? kvd[14] : kvd[6], h1 ? kvd[15] : kvd[7]);
                    red_f32_if(acc_j + ACC_Z + f + 8 * (q & 1), q ? kvd[18] : kvd[16], q < 2);
                    __syncwarp();
                    mbar_arrive_if(sb + (lane == 4 ? BAR_KVW : BAR_EMPTYB + 8 * ((4 + lane) % 6)), lane < 5);
                    TL(3, tid == 0);
                }
            }
        }
        uint32_t res_lo[8], res_hi[8], ack[5];
        const uint32_t own_rows = sb + OFF_A + j * SLOT + warp * 2048;
#pragma unroll
        for (int b = 0; b < 4; b++)
            ldsm4(own_rows + lrow + (((2 * b + ch) ^ sw) << 4), res_lo[2 * b], res_hi[2 * b], res_lo[2 * b + 1], res_hi[2 * b + 1]);
        mbar_arrive_if(sb + BAR_EMPTYA + 8 * lane, lane < 8 && lane != j && lane != KVS(j));
        TL(5, tid == 0);
        mbar_waitc(sb + BAR_KVR, 0);
        TL(6, tid == 0);
        {
            const uint32_t kvs = sb + OFF_A + KVS(j) * SLOT;
            uint32_t o_lo[8], o_hi[8];
#pragma unroll
            for (int hh = 0; hh < 4; hh++) {
                uint32_t b[8], zb[4];
                const uint32_t base = kvs + hh * 32 * 48;
                ldsm4t(base + (lane & 15) * 48 + (lane >> 4) * 16, b[0], b[1], b[2], b[3]);
                ldsm4t(base + (16 + (lane & 15)) * 48 + (lane >> 4) * 16, b[4], b[5], b[6], b[7]);
                ldsm4t(base + lane * 48 + 32, zb[0], zb[1], zb[2], zb[3]);
                float n0[4], n1[4], dn[4];
                mma16816_z(n0, fp + 4 * hh, b[0], b[1]); mma16816_z(n1, fp + 4 * hh, b[2], b[3]); mma16816_z(dn, fp + 4 * hh, zb[0], zb[1]);
                mma16816(n0, fm + 4 * hh, b[4], b[5]); mma16816(n1, fm + 4 * hh, b[6], b[7]); mma16816(dn, fm + 4 * hh, zb[2], zb[3]);
                const float i0 = rcp(dn[0] + 1e-6f), i1 = rcp(dn[2] + 1e-6f);
                o_lo[2 * hh] = pack_bf16(n0[0] * i0, n0[1] * i0); o_hi[2 * hh] = pack_bf16(n0[2] * i1, n0[3] * i1);
                o_lo[2 * hh + 1] = pack_bf16(n1[0] * i0, n1[1] * i0); o_hi[2 * hh + 1] = pack_bf16(n1[2] * i1, n1[3] * i1);
            }
            __syncwarp();
            mbar_arrive_if(sb + BAR_EMPTYA + 8 * KVS(j), l0);
            rg.slot = 4; rg.phase = 0;
            store_tile(own_rows, g_o + (size_t)row_w * DM + 64 * j, o_lo, o_hi, lane, ack);
            ack[4] = 0;
            TL(7, tid == 0);
        }
        {
            float acc[32];
#pragma unroll
            for (int t = 0; t < 8; t++) {
                acc[4 * t] = bf_lo(res_lo[t]); acc[4 * t + 1] = bf_hi(res_lo[t]);
                acc[4 * t + 2] = bf_lo(res_hi[t]); acc[4 * t + 3] = bf_hi(res_hi[t]);
            }
            fence_acc<32>(acc);
            int pa = 0;
#pragma unroll 1
            for (int kp = 0; kp < 4; kp++) {
                mbar_waitc(sb + BAR_FULLB + 8 * rg.slot, rg.phase);
#pragma unroll
                for (int hf = 0; hf < 2; hf++) {
                    const int i = 2 * kp + hf, kt = KORD(i, j);
                    mbar_waitc(sb + BAR_FULLA + 8 * kt, i != 0);
                    TL(8, i == 1 && tid == 0);
                    const desc_t da = dA + kt * (SLOT >> 4), db = dB + rg.slot * (SLOT >> 4);
                    wg_fence();
#pragma unroll
                    for (int k = 0; k < 4; k++) wgmma_n64(acc, da + 2 * k, db + (hf * 4 + k) * 128, 1);
                    wg_commit();
                    wg_wait<1>();
                    mbar_arrive_if(sb + BAR_EMPTYA + 8 * pa, l0 && i > 1);
                    if (hf == 0) {
                        mbar_arrive_if(sb + BAR_EMPTYB + 8 * prev, l0 && i > 0);
                        if (i == 0) { signal_late(flag_m, ack, P.zero, l0); TL(20, tid == 0); }
                    }
                    pa = kt;
                }
                prev = rg.slot; rg.adv();
            }
            wg_wait<0>();
            fence_acc<32>(acc);
            mbar_arrive_if(sb + BAR_EMPTYA + 8 * pa, l0);
            mbar_arrive_if(sb + BAR_EMPTYB + 8 * prev, l0);
            TL(9, tid == 0);
            float s0 = 0.f, s1 = 0.f;
#pragma unroll
            for (int t = 0; t < 8; t++) {
                res_lo[t] = pack_bf16(acc[4 * t], acc[4 * t + 1]);
                res_hi[t] = pack_bf16(acc[4 * t + 2], acc[4 * t + 3]);
                s0 += acc[4 * t] + acc[4 * t + 1];
                s1 += acc[4 * t + 2] + acc[4 * t + 3];
            }
            store_tile(own_rows, g_h + (size_t)row_w * DM + 64 * j, res_lo, res_hi, lane, ack);
            s0 += __shfl_xor_sync(0xffffffffu, s0, 1); s1 += __shfl_xor_sync(0xffffffffu, s1, 1);
            s0 += __shfl_xor_sync(0xffffffffu, s0, 2); s1 += __shfl_xor_sync(0xffffffffu, s1, 2);
            const float mu0 = s0 * (1.f / 64), mu1 = s1 * (1.f / 64);
            float q0 = 0.f, q1 = 0.f;
#pragma unroll
            for (int t = 0; t < 8; t++) {
                float d;
                d = acc[4 * t] - mu0; q0 = fmaf(d, d, q0);
                d = acc[4 * t + 1] - mu0; q0 = fmaf(d, d, q0);
                d = acc[4 * t + 2] - mu1; q1 = fmaf(d, d, q1);
                d = acc[4 * t + 3] - mu1; q1 = fmaf(d, d, q1);
            }
            q0 += __shfl_xor_sync(0xffffffffu, q0, 1); q1 += __shfl_xor_sync(0xffffffffu, q1, 1);
            q0 += __shfl_xor_sync(0xffffffffu, q0, 2); q1 += __shfl_xor_sync(0xffffffffu, q1, 2);
            stg_f2_if(g_hstat + (role * 128 + 16 * warp + g + 8 * (q & 1)) * 2, q ? mu1 : mu0, q ? q1 : q0, q < 2);
            ack[4] = readback(g_hstat + (role * 128 + 16 * warp + g + 8 * (q & 1)) * 2);
            TL(10, tid == 0);
        }
        {
            const uint32_t cs3 = sb + OFF_CS3 + q * 16;
            float nm0, nm1;
            {
                float acc[128];
                const desc_t dB4 = dB - (256ull << 16);
#pragma unroll 1
                for (int i = 0; i < 16; i++) {
                    const int kt = KORD(i >> 1, j);
                    mbar_waitc(sb + BAR_FULLA + 8 * kt, 0);
                    mbar_waitc(sb + BAR_FULLB + 8 * rg.slot, rg.phase);
                    TL(44, tid == 0 && i == 2);
                    const desc_t da = dA + kt * (SLOT >> 4) + (i & 1) * 4, db = dB4 + rg.slot * (SLOT >> 4);
                    wg_fence();
                    wgmma_n256(acc, da, db, i != 0);
                    wgmma_n256(acc, da + 2, db + 128, 1);
                    wg_commit();
                    wg_wait<1>();
                    mbar_arrive_if(sb + BAR_EMPTYB + 8 * prev, l0 && i > 0 && i < 15);
                    if (i == 1) { signal_late(flag_m + 32, ack, P.zero, l0); TL(21, tid == 0); }
                    prev = rg.slot; rg.adv();
                }
                mbar_waitc(sb + BAR_CS3, 0);
                nm0 = lds_f2(sb + OFF_CS1 + (16 * warp + g) * 8).x; nm1 = lds_f2(sb + OFF_CS1 + (16 * warp + g + 8) * 8).x;
                wg_wait<0>();
                fence_acc<128>(acc);
                TL(11, tid == 0);
                bar_sync(1, 256);
                hh_stage<64, 4>(acc, cs3, nm0, nm1, sb + OFF_B + 4 * SLOT + warp * 2048, lane);
                mbar_arrive_if(sb + BAR_STG, l0);
                hh_stage<64, 4>(acc + 32, cs3 + 512, nm0, nm1, sb + OFF_B + 5 * SLOT + warp * 2048, lane);
                mbar_arrive_if(sb + BAR_STG + 8, l0);
                TL(50, tid == 0);
            }
            {
                float acc[56];
#pragma unroll 1
                for (int kt = 0; kt < 8; kt++) {
                    mbar_waitc(sb + BAR_FULLB + 8 * rg.slot, rg.phase);
                    const desc_t da = dA + kt * (SLOT >> 4), db = dB + rg.slot * (SLOT >> 4);
                    wg_fence();
#pragma unroll
                    for (int k = 0; k < 4; k++) wgmma_n112(acc, da + 2 * k, db + 128 * k, (kt | k) != 0);
                    wg_commit();
                    wg_wait<1>();
                    mbar_arrive_if(sb + BAR_EMPTYB + 8 * prev, l0 && kt > 0);
                    mbar_arrive_if(sb + BAR_EMPTYA + 8 * ((kt + 7) & 7), l0 && kt > 0);
                    prev = rg.slot; rg.adv();
                }
                wg_wait<0>();
                fence_acc<56>(acc);
                mbar_arrive_if(sb + BAR_EMPTYA + 8 * 7, l0);
                TL(13, tid == 0);
                bar_sync(1, 256);
                hh_stage<32, 3>(acc, cs3 + 1024, nm0, nm1, sb + OFF_B + 1 * SLOT + warp * 2048, lane);
                mbar_arrive_if(sb + BAR_STG + 16, l0);
                TL(52, tid == 0);
            }
        }
        {
            float acc[64];
            const desc_t dA0 = desc_lo(sb + OFF_A);
#define KT_P4(I, NK)                                                                                        \
    do {                                                                                                    \
        const int s_ = (2 * (I) + w) & 7;                                                                   \
        mbar_waitc(sb + BAR_FULLB + 8 * rg.slot, rg.phase);                                                 \
        mbar_waitc(sb + BAR_FULLA + 8 * s_, (((I) >> 2) + 1) & 1);                                          \
        TL(30 + (I), tid == 0);                                                                             \
        const desc_t dh_ = dA0 + s_ * (SLOT >> 4), dw_ = dB + rg.slot * (SLOT >> 4) + w * 512;              \
        wg_fence();                                                                                         \
        _Pragma("unroll") for (int k = 0; k < (NK); k++) wgmma_n128_tn(acc, dw_ + 128 * k, dh_ + 2 * k, ((I) | k) != 0); \
        wg_commit();                                                                                        \
        wg_wait<1>();                                                                                       \
        mbar_arrive_n_if(sb + BAR_EMPTYA + 8 * ((s_ + 6) & 7), 2, l0 && (I) > 0);                           \
        mbar_arrive_if(sb + BAR_EMPTYB + 8 * prev, l0 && (I) > 0);                                          \
        prev = rg.slot; rg.adv();                                                                           \
    } while (0)
#pragma unroll 1
            for (int i = 0; i < 8; i++) KT_P4(i, 4);
#pragma unroll 1
            for (int i = 8; i < 12; i++) KT_P4(i, 3);
            const uint32_t tile = sb + OFF_A + w * SLOT;
#pragma unroll
            for (int b = 0; b < 4; b++)
                stsm4(tile + (16 * wv + (lane & 15)) * 128 + (((2 * b + (lane >> 4)) ^ (lane & 7)) << 4),
                      res_lo[2 * b], res_hi[2 * b], res_lo[2 * b + 1], res_hi[2 * b + 1]);
            wg_wait<0>();
            fence_acc<64>(acc);
            TL(15, tid == 0);
            const uint32_t xch = sb + OFF_A + 2 * SLOT + (tid & 127) * 16;
            if (w) {
#pragma unroll
                for (int t = 0; t < 8; t++) {
                    sts128(xch + SLOT + t * 2048, __float_as_uint(acc[4 * t]), __float_as_uint(acc[4 * t + 1]),
                           __float_as_uint(acc[4 * t + 2]), __float_as_uint(acc[4 * t + 3]));
                }
#pragma unroll
                for (int t = 0; t < 32; t++) acc[t] = acc[32 + t];
            } else {
#pragma unroll
                for (int t = 0; t < 8; t++)
                    sts128(xch + t * 2048, __float_as_uint(acc[32 + 4 * t]), __float_as_uint(acc[33 + 4 * t]),
                           __float_as_uint(acc[34 + 4 * t]), __float_as_uint(acc[35 + 4 * t]));
            }
            bar_sync(1, 256);
            const uint32_t blk = tile + ((lane & 7) + (lane >> 4) * 8) * 128 + (((2 * wv + ((lane >> 3) & 1)) ^ (lane & 7)) << 4);
#pragma unroll
            for (int tp = 0; tp < 4; tp++) {
                uint32_t hr[4];
                ldsm4t(blk + tp * 2048, hr[0], hr[1], hr[2], hr[3]);
#pragma unroll
                for (int u = 0; u < 2; u++) {
                    const int t = 2 * tp + u;
                    const float4 o = lds_f4(xch + (w ^ 1) * SLOT + t * 2048);
                    const float4 st = lds_f4(sb + OFF_CS1 + (64 * w + 8 * t + 2 * q) * 8);
                    hr[2 * u] = pack_bf16(fmaf(acc[4 * t] + o.x, st.y, bf_lo(hr[2 * u])), fmaf(acc[4 * t + 1] + o.y, st.w, bf_hi(hr[2 * u])));
                    hr[2 * u + 1] = pack_bf16(fmaf(acc[4 * t + 2] + o.z, st.y, bf_lo(hr[2 * u + 1])), fmaf(acc[4 * t + 3] + o.w, st.w, bf_hi(hr[2 * u + 1])));
                }
                stsm4t(blk + tp * 2048, hr[0], hr[1], hr[2], hr[3]);
            }
            bar_sync(2 + w, 128);
#pragma unroll
            for (int i = 0; i < 4; i++) {
                const int rr = 16 * wv + 4 * i + (lane >> 3);
                const uint4 v = lds128(tile + rr * 128 + (((lane & 7) ^ (rr & 7)) << 4));
                stg128(P.out + (size_t)(128 * m + 64 * w + rr) * DM + 64 * j + (lane & 7) * 8, v.x, v.y, v.z, v.w);
            }
            if (tid == 0 && role == 0) g_epoch = epoch + 1;
            TL(16, tid == 0); TLG(1, tid == 0);
        }
    }
}

typedef CUresult (*EncodeFn)(CUtensorMap*, CUtensorMapDataType, cuuint32_t, void*, const cuuint64_t*, const cuuint64_t*,
                             const cuuint32_t*, const cuuint32_t*, CUtensorMapInterleave, CUtensorMapSwizzle,
                             CUtensorMapL2promotion, CUtensorMapFloatOOBfill);

static void make_map2d(EncodeFn enc, CUtensorMap* tm, const void* base, uint64_t cols, uint64_t rows, uint64_t pitch_elems,
                       uint32_t box_rows) {
    cuuint64_t gd[2] = {cols, rows};
    cuuint64_t gs[1] = {pitch_elems * 2};
    cuuint32_t bd[2] = {64, box_rows};
    cuuint32_t es[2] = {1, 1};
    enc(tm, CU_TENSOR_MAP_DATA_TYPE_BFLOAT16, 2, const_cast<void*>(base), gd, gs, bd, es, CU_TENSOR_MAP_INTERLEAVE_NONE,
        CU_TENSOR_MAP_SWIZZLE_128B, CU_TENSOR_MAP_L2_PROMOTION_L2_256B, CU_TENSOR_MAP_FLOAT_OOB_FILL_NONE);
}

}

extern "C" void kernel_launch(void* const* d_in, const int* in_sizes, int n_in, void* d_out, int out_size) {
    using namespace hk;
    (void)in_sizes; (void)n_in; (void)out_size;
    static EncodeFn enc = nullptr;
    static void *po = nullptr, *ph = nullptr, *phh = nullptr;
    static int std_layout = 0;
    if (!enc) {
        void* fn = nullptr;
        cudaDriverEntryPointQueryResult qr;
        cudaGetDriverEntryPoint("cuTensorMapEncodeTiled", &fn, cudaEnableDefault, &qr);
        enc = (EncodeFn)fn;
        cudaGetSymbolAddress(&po, g_o);
        cudaGetSymbolAddress(&ph, g_h);
        cudaGetSymbolAddress(&phh, g_hh);
        cudaFuncSetAttribute(fused_kernel, cudaFuncAttributeMaxDynamicSharedMemorySize, SMEM_BYTES);
        int dev = 0, sms = 0;
        cudaGetDevice(&dev);
        cudaDeviceGetAttribute(&sms, cudaDevAttrMultiProcessorCount, dev);
        cudaFuncSetAttribute(fused_kernel, cudaFuncAttributeNonPortableClusterSizeAllowed, 1);
        const int sizes[3] = {8, 9, 16}, want[3] = {15, 9, 7};
        bool ok = sms == NCTA;
        for (int i = 0; i < 3 && ok; i++) {
            cudaLaunchConfig_t cfg = {};
            cfg.gridDim = dim3(sizes[i] * 8); cfg.blockDim = dim3(NTHREADS); cfg.dynamicSmemBytes = SMEM_BYTES;
            cudaLaunchAttribute at;
            at.id = cudaLaunchAttributeClusterDimension;
            at.val.clusterDim.x = sizes[i]; at.val.clusterDim.y = 1; at.val.clusterDim.z = 1;
            cfg.attrs = &at; cfg.numAttrs = 1;
            int n = 0;
            ok = cudaOccupancyMaxActiveClusters(&n, fused_kernel, &cfg) == cudaSuccess && n == want[i];
        }
        (void)cudaGetLastError();
        std_layout = ok ? 1 : 0;
    }
    Params P;
    const __nv_bfloat16* x = (const __nv_bfloat16*)d_in[0];
    P.x = x;
    P.wqkv = (const __nv_bfloat16*)d_in[1];
    P.wphi = (const __nv_bfloat16*)d_in[2];
    P.wo = (const __nv_bfloat16*)d_in[3];
    P.wg = (const __nv_bfloat16*)d_in[5];
    P.wu = (const __nv_bfloat16*)d_in[6];
    P.wd = (const __nv_bfloat16*)d_in[7];
    P.out = (__nv_bfloat16*)d_out;
    P.use_smid = std_layout;
    P.zero = 0;
    for (int i = 0; i < NCTA; i++) {
        int role = i < 4 ? 128 + i : i - 4;
        if (std_layout) {
            const int tpc = i >> 1, odd = i & 1;
            if (tpc < 32) role = (tpc & 7) * 8 + (tpc >> 3) * 2 + odd;
            else if (tpc < 60) role = (8 + (tpc - 32) % 7) * 8 + ((tpc - 32) / 7) * 2 + odd;
            else if (tpc < 62) role = 128 + (tpc - 60) * 2 + odd;
            else role = 15 * 8 + (tpc - 62) * 2 + odd;
        }
        P.role[i] = (unsigned char)role;
    }
    make_map2d(enc, &P.tx, x, DM, SEQ, DM, 128);
    make_map2d(enc, &P.to, po, DM, SEQ, DM, 128);
    make_map2d(enc, &P.th, ph, DM, SEQ, DM, 128);
    make_map2d(enc, &P.thh, phh, FFP, SEQ, FFP, 128);
    make_map2d(enc, &P.twq, P.wqkv, 3 * DM, DM, 3 * DM, 128);
    make_map2d(enc, &P.two, P.wo, DM, DM, DM, 64);
    make_map2d(enc, &P.twg, P.wg, FF, DM, FF, 64);
    make_map2d(enc, &P.twu, P.wu, FF, DM, FF, 64);
    make_map2d(enc, &P.twd, P.wd, DM, FF, DM, 64);
    {
        cuuint64_t gd[3] = {(cuuint64_t)DM, (cuuint64_t)DM, 3};
        cuuint64_t gs[2] = {(cuuint64_t)3 * DM * 2, (cuuint64_t)DM * 2};
        cuuint32_t bd[3] = {64, 64, 2};
        cuuint32_t es[3] = {1, 1, 1};
        enc(&P.twkv, CU_TENSOR_MAP_DATA_TYPE_BFLOAT16, 3, const_cast<__nv_bfloat16*>(P.wqkv), gd, gs, bd, es,
            CU_TENSOR_MAP_INTERLEAVE_NONE, CU_TENSOR_MAP_SWIZZLE_128B, CU_TENSOR_MAP_L2_PROMOTION_L2_256B,
            CU_TENSOR_MAP_FLOAT_OOB_FILL_NONE);
    }
    for (int i = 0; i < 2; i++) {
        cuuint64_t gd[3] = {(cuuint64_t)FF - 64, (cuuint64_t)DM, 2};
        cuuint64_t gs[2] = {(cuuint64_t)FF * 2, 128};
        cuuint32_t bd[3] = {64, 32, 2};
        cuuint32_t es[3] = {1, 1, 1};
        enc(i ? &P.twu2 : &P.twg2, CU_TENSOR_MAP_DATA_TYPE_BFLOAT16, 3, const_cast<__nv_bfloat16*>(i ? P.wu : P.wg), gd, gs, bd, es,
            CU_TENSOR_MAP_INTERLEAVE_NONE, CU_TENSOR_MAP_SWIZZLE_128B, CU_TENSOR_MAP_L2_PROMOTION_L2_256B,
            CU_TENSOR_MAP_FLOAT_OOB_FILL_NONE);
    }
    fused_kernel<<<NCTA, NTHREADS, SMEM_BYTES>>>(P);
}
```

```cpp
#include <cuda_runtime.h>
#include <cuda_bf16.h>
#include <cuda.h>
#include <stdint.h>

namespace hk {

constexpr int SEQ = 2048, DM = 512, FF = 1376, FFP = 1536;
constexpr int NCTA = 132;
constexpr int NTHREADS = 384;
constexpr uint32_t SLOT = 16384;
constexpr uint32_t OFF_A = 0, OFF_B = 8 * SLOT, OFF_MISC = 14 * SLOT;
constexpr uint32_t BAR_FULLA = OFF_MISC + 0, BAR_EMPTYA = OFF_MISC + 64, BAR_FULLB = OFF_MISC + 128,
                   BAR_EMPTYB = OFF_MISC + 176, BAR_CS1 = OFF_MISC + 224, BAR_CS3 = OFF_MISC + 232,
                   BAR_CSQ = OFF_MISC + 240, BAR_CSV = OFF_MISC + 248,
                   BAR_STG = OFF_MISC + 256,
                   BAR_KVW = OFF_MISC + 280, BAR_KVR = OFF_MISC + 288;
constexpr uint32_t OFF_CS1 = OFF_MISC + 384;
constexpr uint32_t OFF_CS3 = OFF_CS1 + 1024;
constexpr uint32_t OFF_XST = OFF_CS3;
constexpr uint32_t SMEM_BYTES = OFF_CS3 + 1536;
#define KVS(j) ((j) == 3 ? 2 : 3)
#define KORD(i, j) ((i) == 0 ? (j) : (i) - ((i) <= (j)))
constexpr int NB = 6;
constexpr int AHEAD = 3;

constexpr int ACC_KV = 0, ACC_Z = 2048, ACC_SIZE = 2176;

__device__ __align__(1024) __nv_bfloat16 g_o[SEQ * DM];
__device__ __align__(1024) __nv_bfloat16 g_h[SEQ * DM];
__device__ __align__(1024) __nv_bfloat16 g_hh[SEQ * FFP];
__device__ __align__(128) float g_hstat[SEQ * 16];
__device__ __align__(128) unsigned long long g_xstat[SEQ * 2];
__device__ __align__(128) float g_acc[8 * ACC_SIZE];
__device__ __align__(128) unsigned g_cnt[8 * 32];
__device__ __align__(128) unsigned long long g_cs[8 * 6 * 128];
__device__ __align__(128) unsigned g_flag[16 * 5 * 32];
__device__ unsigned g_epoch = 1;

#define TL(i, pred) do {} while (0)
#define TLG(i, pred) do {} while (0)

struct Params {
    CUtensorMap tx, to, th, thh, twkv, twq, two, twg, twu, twd;
    const __nv_bfloat16 *x, *wqkv, *wphi, *wo, *wg, *wu, *wd;
    __nv_bfloat16* out;
    int use_smid;
    unsigned zero;
    unsigned char role[NCTA];
};

__device__ __forceinline__ uint32_t smem_u32(const void* p) { return (uint32_t)__cvta_generic_to_shared(p); }
__device__ __forceinline__ void mbar_init(uint32_t bar, uint32_t cnt) {
    asm volatile("mbarrier.init.shared::cta.b64 [%0], %1;" ::"r"(bar), "r"(cnt) : "memory");
}
__device__ __forceinline__ void mbar_expect_tx(uint32_t bar, uint32_t bytes) {
    asm volatile("mbarrier.arrive.expect_tx.shared::cta.b64 _, [%0], %1;" ::"r"(bar), "r"(bytes) : "memory");
}
__device__ __forceinline__ void mbar_arrive(uint32_t bar) {
    asm volatile("mbarrier.arrive.shared::cta.b64 _, [%0];" ::"r"(bar) : "memory");
}
__device__ __forceinline__ void mbar_arrive_if(uint32_t bar, bool pred) {
    asm volatile("{.reg .pred p; setp.ne.u32 p, %1, 0; @p mbarrier.arrive.shared::cta.b64 _, [%0];}" ::"r"(bar), "r"((uint32_t)pred) : "memory");
}
__device__ __forceinline__ bool mbar_try(uint32_t bar, uint32_t parity) {
    uint32_t ok;
    asm volatile("{.reg .pred p; mbarrier.try_wait.parity.shared::cta.b64 p, [%1], %2; selp.u32 %0,1,0,p;}"
                 : "=r"(ok) : "r"(bar), "r"(parity) : "memory");
    return ok;
}
__device__ __forceinline__ bool mbar_test(uint32_t bar, uint32_t parity) {
    uint32_t ok;
    asm volatile("{.reg .pred p; mbarrier.test_wait.parity.shared::cta.b64 p, [%1], %2; selp.u32 %0,1,0,p;}"
                 : "=r"(ok) : "r"(bar), "r"(parity) : "memory");
    return ok;
}
__device__ __forceinline__ void trap_if_gt(uint32_t v, uint32_t lim) {
    asm volatile("{.reg .pred p; setp.gt.u32 p, %0, %1; @p trap;}" ::"r"(v), "r"(lim));
}
__device__ __forceinline__ void mbar_wait(uint32_t bar, uint32_t parity) {
    asm volatile("{\n"
                 ".reg .pred P1, P2;\n"
                 ".reg .u32 c;\n"
                 "mov.u32 c, 0;\n"
                 "LAB_WAIT:\n"
                 "mbarrier.try_wait.parity.shared::cta.b64 P1, [%0], %1;\n"
                 "@P1 bra LAB_DONE;\n"
                 "add.u32 c, c, 1;\n"
                 "setp.gt.u32 P2, c, 4194304;\n"
                 "@P2 trap;\n"
                 "bra LAB_WAIT;\n"
                 "LAB_DONE:\n"
                 "}" ::"r"(bar), "r"(parity) : "memory");
}
__device__ __forceinline__ void mbar_waitc(uint32_t bar, uint32_t parity) {
    asm volatile("{\n"
                 ".reg .pred P1;\n"
                 "LAB_WAIT:\n"
                 "mbarrier.try_wait.parity.shared::cta.b64 P1, [%0], %1;\n"
                 "@!P1 bra LAB_WAIT;\n"
                 "}" ::"r"(bar), "r"(parity) : "memory");
}
__device__ __forceinline__ void tma2d(uint32_t dst, const CUtensorMap* tm, uint32_t bar, int c0, int c1) {
    asm volatile("cp.async.bulk.tensor.2d.shared::cluster.global.mbarrier::complete_tx::bytes [%0], [%1, {%3, %4}], [%2];"
                 ::"r"(dst), "l"(tm), "r"(bar), "r"(c0), "r"(c1) : "memory");
}
__device__ __forceinline__ void tma3d(uint32_t dst, const CUtensorMap* tm, uint32_t bar, int c0, int c1, int c2) {
    asm volatile("cp.async.bulk.tensor.3d.shared::cluster.global.mbarrier::complete_tx::bytes [%0], [%1, {%3, %4, %5}], [%2];"
                 ::"r"(dst), "l"(tm), "r"(bar), "r"(c0), "r"(c1), "r"(c2) : "memory");
}
__device__ __forceinline__ bool elect_one() {
    uint32_t ok;
    asm volatile("{.reg .pred p; elect.sync _|p, 0xffffffff; selp.u32 %0, 1, 0, p;}" : "=r"(ok));
    return ok;
}
__device__ __forceinline__ void prefetch_tmap(const CUtensorMap* tm) {
    asm volatile("prefetch.tensormap [%0];" ::"l"(tm) : "memory");
}
__device__ __forceinline__ void prefetch_l2(const void* p, uint32_t bytes) {
    asm volatile("cp.async.bulk.prefetch.L2.global [%0], %1;" ::"l"(p), "r"(bytes) : "memory");
}
__device__ __forceinline__ unsigned ld_acquire(const unsigned* p) {
    unsigned v; asm volatile("ld.acquire.gpu.global.u32 %0, [%1];" : "=r"(v) : "l"(p) : "memory"); return v;
}
__device__ __forceinline__ uint4 ld_acquire4(const unsigned* p) {
    uint4 v;
    asm volatile("ld.acquire.gpu.global.v4.u32 {%0,%1,%2,%3}, [%4];" : "=r"(v.x), "=r"(v.y), "=r"(v.z), "=r"(v.w) : "l"(p) : "memory");
    return v;
}
__device__ __forceinline__ unsigned ld_relaxed(const unsigned* p) {
    unsigned v; asm volatile("ld.relaxed.gpu.global.u32 %0, [%1];" : "=r"(v) : "l"(p)); return v;
}
__device__ __forceinline__ void st_relaxed(unsigned* p, unsigned v) {
    asm volatile("st.relaxed.gpu.global.u32 [%0], %1;" ::"l"(p), "r"(v) : "memory");
}
__device__ __forceinline__ void red_relaxed(unsigned* p, unsigned v) {
    asm volatile("red.relaxed.gpu.global.add.u32 [%0], %1;" ::"l"(p), "r"(v) : "memory");
}
__device__ __forceinline__ void fence_gpu() { asm volatile("fence.acq_rel.gpu;" ::: "memory"); }
__device__ __forceinline__ void fence_async_smem() { asm volatile("fence.proxy.async.shared::cta;" ::: "memory"); }
__device__ __forceinline__ void fence_async_global() { asm volatile("fence.proxy.async.global;" ::: "memory"); }
__device__ __forceinline__ uint32_t readback(const void* p) {
    uint32_t v; asm volatile("ld.relaxed.gpu.global.u32 %0, [%1];" : "=r"(v) : "l"(p) : "memory"); return v;
}
__device__ __forceinline__ void wait_count(const unsigned* p, unsigned target) {
    uint32_t it = 0;
    while ((int)(readback(p) - target) < 0) trap_if_gt(++it, 1u << 22);
}
__device__ __forceinline__ void wait_count_warp(const unsigned* p, unsigned target) {
    uint32_t it = 0;
    while (__any_sync(0xffffffffu, (int)(readback(p) - target) < 0)) trap_if_gt(++it, 1u << 22);
}
__device__ __forceinline__ void red_f32(float* p, float a) {
    asm volatile("red.relaxed.gpu.global.add.f32 [%0], %1;" ::"l"(p), "f"(a) : "memory");
}
__device__ __forceinline__ void red_f32x2(float* p, float a, float b) {
    asm volatile("red.relaxed.gpu.global.add.v2.f32 [%0], {%1, %2};" ::"l"(p), "f"(a), "f"(b) : "memory");
}
__device__ __forceinline__ void red_f32x4(float* p, float a, float b, float c, float d) {
    asm volatile("red.relaxed.gpu.global.add.v4.f32 [%0], {%1, %2, %3, %4};" ::"l"(p), "f"(a), "f"(b), "f"(c), "f"(d) : "memory");
}
__device__ __forceinline__ float4 ld_l2_f4(const float* p) {
    float4 v;
    asm volatile("ld.relaxed.gpu.global.v4.f32 {%0,%1,%2,%3}, [%4];" : "=f"(v.x), "=f"(v.y), "=f"(v.z), "=f"(v.w) : "l"(p) : "memory");
    return v;
}
__device__ __forceinline__ float2 ld_l2_f2(const float* p) {
    float2 v;
    asm volatile("ld.relaxed.gpu.global.v2.f32 {%0,%1}, [%2];" : "=f"(v.x), "=f"(v.y) : "l"(p) : "memory");
    return v;
}
__device__ __forceinline__ float ld_l2_f(const float* p) {
    float v;
    asm volatile("ld.relaxed.gpu.global.f32 %0, [%1];" : "=f"(v) : "l"(p) : "memory");
    return v;
}
__device__ __forceinline__ uint4 ldg_nc(const void* p) {
    uint4 v;
    asm volatile("ld.global.nc.L1::no_allocate.v4.u32 {%0,%1,%2,%3}, [%4];" : "=r"(v.x), "=r"(v.y), "=r"(v.z), "=r"(v.w) : "l"(p));
    return v;
}
__device__ __forceinline__ void stg128(void* p, uint32_t a, uint32_t b, uint32_t c, uint32_t d) {
    asm volatile("st.global.v4.u32 [%0], {%1,%2,%3,%4};" ::"l"(p), "r"(a), "r"(b), "r"(c), "r"(d) : "memory");
}
__device__ __forceinline__ uint4 lds128(uint32_t a) {
    uint4 v;
    asm volatile("ld.shared.v4.u32 {%0,%1,%2,%3}, [%4];" : "=r"(v.x), "=r"(v.y), "=r"(v.z), "=r"(v.w) : "r"(a) : "memory");
    return v;
}
__device__ __forceinline__ float2 lds_f2(uint32_t a) {
    float2 v;
    asm volatile("ld.shared.v2.f32 {%0,%1}, [%2];" : "=f"(v.x), "=f"(v.y) : "r"(a) : "memory");
    return v;
}
__device__ __forceinline__ void sts_f2(uint32_t a, float x, float y) {
    asm volatile("st.shared.v2.f32 [%0], {%1,%2};" ::"r"(a), "f"(x), "f"(y) : "memory");
}
__device__ __forceinline__ void sts64(uint32_t a, uint32_t x, uint32_t y) {
    asm volatile("st.shared.v2.u32 [%0], {%1,%2};" ::"r"(a), "r"(x), "r"(y) : "memory");
}
__device__ __forceinline__ void sts128(uint32_t a, uint32_t x, uint32_t y, uint32_t z, uint32_t w) {
    asm volatile("st.shared.v4.u32 [%0], {%1,%2,%3,%4};" ::"r"(a), "r"(x), "r"(y), "r"(z), "r"(w) : "memory");
}
__device__ __forceinline__ void stsm4(uint32_t a, uint32_t r0, uint32_t r1, uint32_t r2, uint32_t r3) {
    asm volatile("stmatrix.sync.aligned.m8n8.x4.shared.b16 [%0], {%1,%2,%3,%4};" ::"r"(a), "r"(r0), "r"(r1), "r"(r2), "r"(r3) : "memory");
}
__device__ __forceinline__ void stsm4t(uint32_t a, uint32_t r0, uint32_t r1, uint32_t r2, uint32_t r3) {
    asm volatile("stmatrix.sync.aligned.m8n8.x4.trans.shared.b16 [%0], {%1,%2,%3,%4};" ::"r"(a), "r"(r0), "r"(r1), "r"(r2), "r"(r3) : "memory");
}
__device__ __forceinline__ void tma_store2d(const CUtensorMap* tm, uint32_t src, int c0, int c1) {
    asm volatile("cp.async.bulk.tensor.2d.global.shared::cta.bulk_group [%0, {%2, %3}], [%1];" ::"l"(tm), "r"(src), "r"(c0), "r"(c1) : "memory");
    asm volatile("cp.async.bulk.commit_group;" ::: "memory");
}
__device__ __forceinline__ void ldsm4(uint32_t a, uint32_t& r0, uint32_t& r1, uint32_t& r2, uint32_t& r3) {
    asm volatile("ldmatrix.sync.aligned.m8n8.x4.shared.b16 {%0,%1,%2,%3}, [%4];" : "=r"(r0), "=r"(r1), "=r"(r2), "=r"(r3) : "r"(a) : "memory");
}
__device__ __forceinline__ void ldsm4t(uint32_t a, uint32_t& r0, uint32_t& r1, uint32_t& r2, uint32_t& r3) {
    asm volatile("ldmatrix.sync.aligned.m8n8.x4.trans.shared.b16 {%0,%1,%2,%3}, [%4];" : "=r"(r0), "=r"(r1), "=r"(r2), "=r"(r3) : "r"(a) : "memory");
}
__device__ __forceinline__ void mma16816(float* c, const uint32_t* a, uint32_t b0, uint32_t b1) {
    asm("mma.sync.aligned.m16n8k16.row.col.f32.bf16.bf16.f32 {%0,%1,%2,%3}, {%4,%5,%6,%7}, {%8,%9}, {%0,%1,%2,%3};"
                 : "+f"(c[0]), "+f"(c[1]), "+f"(c[2]), "+f"(c[3])
                 : "r"(a[0]), "r"(a[1]), "r"(a[2]), "r"(a[3]), "r"(b0), "r"(b1));
}
__device__ __forceinline__ uint32_t pack_bf16(float lo, float hi) {
    uint32_t r; asm("cvt.rn.bf16x2.f32 %0, %1, %2;" : "=r"(r) : "f"(hi), "f"(lo)); return r;
}
__device__ __forceinline__ float bf_lo(uint32_t w) { return __uint_as_float(w << 16); }
__device__ __forceinline__ float bf_hi(uint32_t w) { return __uint_as_float(w & 0xffff0000u); }
__device__ __forceinline__ float ex2(float x) { float r; asm("ex2.approx.ftz.f32 %0, %1;" : "=f"(r) : "f"(x)); return r; }
__device__ __forceinline__ float rcp(float x) { float r; asm("rcp.approx.ftz.f32 %0, %1;" : "=f"(r) : "f"(x)); return r; }
__device__ __forceinline__ void bar_sync(int id, int n) { asm volatile("bar.sync %0, %1;" ::"r"(id), "r"(n) : "memory"); }

typedef unsigned long long desc_t;
__device__ __forceinline__ desc_t desc_lo(uint32_t addr) { return (desc_t)(((addr & 0x3FFFF) >> 4) | (512u << 16)) | (0x40000040ull << 32); }
__device__ __forceinline__ void wg_fence() { asm volatile("wgmma.fence.sync.aligned;" ::: "memory"); }
__device__ __forceinline__ void wg_commit() { asm volatile("wgmma.commit_group.sync.aligned;" ::: "memory"); }
template <int N> __device__ __forceinline__ void wg_wait() { asm volatile("wgmma.wait_group.sync.aligned %0;" ::"n"(N) : "memory"); }
template <int N> __device__ __forceinline__ void fence_acc(float* d) {
#pragma unroll
    for (int i = 0; i < N; i++) asm volatile("" : "+f"(d[i])::"memory");
}
#define R4(o) "+f"(d[o + 0]), "+f"(d[o + 1]), "+f"(d[o + 2]), "+f"(d[o + 3])
#define R8(o) R4(o), R4(o + 4)
__device__ __forceinline__ void wgmma_n128(float* d, desc_t da, desc_t db, int sc) {
    asm volatile("{.reg .pred p; setp.ne.b32 p, %66, 0;\n"
                 "wgmma.mma_async.sync.aligned.m64n128k16.f32.bf16.bf16 {%0,%1,%2,%3,%4,%5,%6,%7,%8,%9,%10,%11,%12,%13,%14,%15,%16,%17,%18,%19,%20,%21,%22,%23,%24,%25,%26,%27,%28,%29,%30,%31,"
                 "%32,%33,%34,%35,%36,%37,%38,%39,%40,%41,%42,%43,%44,%45,%46,%47,%48,%49,%50,%51,%52,%53,%54,%55,%56,%57,%58,%59,%60,%61,%62,%63}, %64, %65, p, 1, 1, 0, 1;}"
                 : R8(0), R8(8), R8(16), R8(24), R8(32), R8(40), R8(48), R8(56)
                 : "l"(da), "l"(db), "r"(sc));
}
__device__ __forceinline__ void wgmma_n112(float* d, desc_t da, desc_t db, int sc) {
    asm volatile("{.reg .pred p; setp.ne.b32 p, %58, 0;\n"
                 "wgmma.mma_async.sync.aligned.m64n112k16.f32.bf16.bf16 {%0,%1,%2,%3,%4,%5,%6,%7,%8,%9,%10,%11,%12,%13,%14,%15,%16,%17,%18,%19,%20,%21,%22,%23,%24,%25,%26,%27,%28,%29,%30,%31,%32,%33,%34,%35,%36,%37,%38,%39,%40,%41,%42,%43,%44,%45,%46,%47,%48,%49,%50,%51,%52,%53,%54,%55}, %56, %57, p, 1, 1, 0, 1;}"
                 : R8(0), R8(8), R8(16), R8(24), R8(32), R8(40), R8(48)
                 : "l"(da), "l"(db), "r"(sc));
}
__device__ __forceinline__ void wgmma_n128_tn(float* d, desc_t da, desc_t db, int sc) {
    asm volatile("{.reg .pred p; setp.ne.b32 p, %66, 0;\n"
                 "wgmma.mma_async.sync.aligned.m64n128k16.f32.bf16.bf16 {%0,%1,%2,%3,%4,%5,%6,%7,%8,%9,%10,%11,%12,%13,%14,%15,%16,%17,%18,%19,%20,%21,%22,%23,%24,%25,%26,%27,%28,%29,%30,%31,%32,%33,%34,%35,%36,%37,%38,%39,%40,%41,%42,%43,%44,%45,%46,%47,%48,%49,%50,%51,%52,%53,%54,%55,%56,%57,%58,%59,%60,%61,%62,%63}, %64, %65, p, 1, 1, 1, 0;}"
                 : R8(0), R8(8), R8(16), R8(24), R8(32), R8(40), R8(48), R8(56)
                 : "l"(da), "l"(db), "r"(sc));
}
__device__ __forceinline__ void wgmma_n64(float* d, desc_t da, desc_t db, int sc) {
    asm volatile("{.reg .pred p; setp.ne.b32 p, %34, 0;\n"
                 "wgmma.mma_async.sync.aligned.m64n64k16.f32.bf16.bf16 {%0,%1,%2,%3,%4,%5,%6,%7,%8,%9,%10,%11,%12,%13,%14,%15,%16,%17,%18,%19,%20,%21,%22,%23,%24,%25,%26,%27,%28,%29,%30,%31}, %32, %33, p, 1, 1, 0, 1;}"
                 : R8(0), R8(8), R8(16), R8(24)
                 : "l"(da), "l"(db), "r"(sc));
}
__device__ __forceinline__ void wgmma_n40_tt(float* d, desc_t da, desc_t db, int sc) {
    asm volatile("{.reg .pred p; setp.ne.b32 p, %22, 0;\n"
                 "wgmma.mma_async.sync.aligned.m64n40k16.f32.bf16.bf16 {%0,%1,%2,%3,%4,%5,%6,%7,%8,%9,%10,%11,%12,%13,%14,%15,%16,%17,%18,%19}, %20, %21, p, 1, 1, 1, 1;}"
                 : R8(0), R8(8), R4(16)
                 : "l"(da), "l"(db), "r"(sc));
}

__device__ __forceinline__ void wgmma_n8_tt(float* d, desc_t da, desc_t db, int sc) {
    asm volatile("{.reg .pred p; setp.ne.b32 p, %6, 0;\n"
                 "wgmma.mma_async.sync.aligned.m64n8k16.f32.bf16.bf16 {%0,%1,%2,%3}, %4, %5, p, 1, 1, 1, 1;}"
                 : R4(0)
                 : "l"(da), "l"(db), "r"(sc));
}

__device__ __forceinline__ uint32_t atom_f32x2(float* p, float a, float b) {
    float x, y;
    asm volatile("atom.relaxed.gpu.global.add.v2.f32 {%0,%1}, [%2], {%3,%4};" : "=f"(x), "=f"(y) : "l"(p), "f"(a), "f"(b) : "memory");
    return __float_as_uint(x);
}
__device__ __forceinline__ uint32_t atom_f32_if(float* p, float a, bool pred) {
    float x = 0.f;
    asm volatile("{.reg .pred p; setp.ne.u32 p, %3, 0; @p atom.relaxed.gpu.global.add.f32 %0, [%1], %2;}" : "+f"(x) : "l"(p), "f"(a), "r"((uint32_t)pred) : "memory");
    return __float_as_uint(x);
}
__device__ __forceinline__ void signal_after(unsigned* cnt, uint32_t ack, uint32_t zero, bool pred) {
    asm volatile("{.reg .pred p; setp.ne.u32 p, %2, 0; @p red.relaxed.gpu.global.add.u32 [%0], %1;}"
                 ::"l"(cnt), "r"((ack & zero) + 1), "r"((uint32_t)pred) : "memory");
}
__device__ __forceinline__ void signal_late(unsigned* cnt, const uint32_t* a, uint32_t zero, bool pred) {
    uint32_t v;
    asm volatile("{.reg .b32 t; lop3.b32 t, %1, %2, %3, 0xfe; lop3.b32 %0, t, %4, %5, 0xfe;}"
                 : "=r"(v) : "r"(a[0]), "r"(a[1]), "r"(a[2]), "r"(a[3]), "r"(a[4]));
    signal_after(cnt, v, zero, pred);
}
__device__ __forceinline__ void red_f32_if(float* p, float a, bool pred) {
    asm volatile("{.reg .pred p; setp.ne.u32 p, %2, 0; @p red.relaxed.gpu.global.add.f32 [%0], %1;}" ::"l"(p), "f"(a), "r"((uint32_t)pred) : "memory");
}
__device__ __forceinline__ void stg_f2_if(float* p, float a, float b, bool pred) {
    asm volatile("{.reg .pred p; setp.ne.u32 p, %3, 0; @p st.global.v2.f32 [%0], {%1,%2};}" ::"l"(p), "f"(a), "f"(b), "r"((uint32_t)pred) : "memory");
}
__device__ __forceinline__ void stg64(void* p, uint32_t a, uint32_t b) {
    asm volatile("st.global.v2.u32 [%0], {%1,%2};" ::"l"(p), "r"(a), "r"(b) : "memory");
}
__device__ __forceinline__ void mma16816_z(float* c, const uint32_t* a, uint32_t b0, uint32_t b1) {
    asm("mma.sync.aligned.m16n8k16.row.col.f32.bf16.bf16.f32 {%0,%1,%2,%3}, {%4,%5,%6,%7}, {%8,%9}, {%10,%10,%10,%10};"
                 : "=f"(c[0]), "=f"(c[1]), "=f"(c[2]), "=f"(c[3])
                 : "r"(a[0]), "r"(a[1]), "r"(a[2]), "r"(a[3]), "r"(b0), "r"(b1), "f"(0.f));
}
__device__ __forceinline__ uint32_t max2(uint32_t a, uint32_t b) { uint32_t r; asm("max.bf16x2 %0, %1, %2;" : "=r"(r) : "r"(a), "r"(b)); return r; }
__device__ __forceinline__ uint32_t min2(uint32_t a, uint32_t b) { uint32_t r; asm("min.bf16x2 %0, %1, %2;" : "=r"(r) : "r"(a), "r"(b)); return r; }
__device__ __forceinline__ void bar_arrive(int id, int n) { asm volatile("bar.arrive %0, %1;" ::"r"(id), "r"(n) : "memory"); }
__device__ __forceinline__ void mbar_arrive_n_if(uint32_t bar, uint32_t n, bool pred) {
    asm volatile("{.reg .pred p; setp.ne.u32 p, %1, 0; @p mbarrier.arrive.shared::cta.b64 _, [%0], %2;}" ::"r"(bar), "r"((uint32_t)pred), "r"(n) : "memory");
}
__device__ __forceinline__ float4 lds_f4(uint32_t a) {
    float4 v;
    asm volatile("ld.shared.v4.f32 {%0,%1,%2,%3}, [%4];" : "=f"(v.x), "=f"(v.y), "=f"(v.z), "=f"(v.w) : "r"(a) : "memory");
    return v;
}
__device__ __forceinline__ uint4 ld_tagged(const unsigned long long* p) {
    unsigned long long a, b;
    asm volatile("ld.acquire.gpu.global.v2.b64 {%0,%1}, [%2];" : "=l"(a), "=l"(b) : "l"(p) : "memory");
    return make_uint4((unsigned)a, (unsigned)(a >> 32), (unsigned)b, (unsigned)(b >> 32));
}
__device__ __forceinline__ uint4 ld_tagged_rlx(const unsigned long long* p) {
    unsigned long long a, b;
    asm volatile("ld.relaxed.gpu.global.v2.b64 {%0,%1}, [%2];" : "=l"(a), "=l"(b) : "l"(p) : "memory");
    return make_uint4((unsigned)a, (unsigned)(a >> 32), (unsigned)b, (unsigned)(b >> 32));
}
__device__ __forceinline__ void st_tagged_if(unsigned long long* p, float a, float b, unsigned tag, bool pred) {
    const unsigned long long t = (unsigned long long)tag << 32;
    asm volatile("{.reg .pred p; setp.ne.u32 p, %3, 0; @p st.relaxed.gpu.global.v2.b64 [%0], {%1,%2};}"
                 ::"l"(p), "l"(t | __float_as_uint(a)), "l"(t | __float_as_uint(b)), "r"((uint32_t)pred) : "memory");
}

__device__ __forceinline__ void store_tile(uint32_t tile_rows, __nv_bfloat16* gdst, const uint32_t* lo, const uint32_t* hi, int lane, uint32_t* ack) {
    const int r = lane & 15;
#pragma unroll
    for (int b = 0; b < 4; b++)
        stsm4(tile_rows + r * 128 + (((2 * b + (lane >> 4)) ^ (r & 7)) << 4), lo[2 * b], hi[2 * b], lo[2 * b + 1], hi[2 * b + 1]);
    fence_async_smem();
    __syncwarp();
#pragma unroll
    for (int i = 0; i < 4; i++) {
        const int rr = 4 * i + (lane >> 3);
        const uint4 v = lds128(tile_rows + rr * 128 + (((lane & 7) ^ (rr & 7)) << 4));
        stg128(gdst + rr * DM + (lane & 7) * 8, v.x, v.y, v.z, v.w);
    }
#pragma unroll
    for (int i = 0; i < 4; i++) ack[i] = readback(gdst + (4 * i + (lane >> 3)) * DM + (lane & 7) * 8);
}

__device__ __forceinline__ void feature_maps(const uint32_t* a, const uint32_t* wb, float c0, float c1, uint32_t* plus, uint32_t* minus) {
    uint32_t P[16], mx[4], mn[4];
#pragma unroll
    for (int h = 0; h < 4; h++) {
        float p[8];
        mma16816_z(p, a + 4 * h, wb[4 * h], wb[4 * h + 1]);
        mma16816_z(p + 4, a + 4 * h, wb[4 * h + 2], wb[4 * h + 3]);
        P[4 * h] = pack_bf16(p[0], p[2]); P[4 * h + 1] = pack_bf16(p[1], p[3]);
        P[4 * h + 2] = pack_bf16(p[4], p[6]); P[4 * h + 3] = pack_bf16(p[5], p[7]);
        mx[h] = max2(max2(P[4 * h], P[4 * h + 1]), max2(P[4 * h + 2], P[4 * h + 3]));
        mn[h] = min2(min2(P[4 * h], P[4 * h + 1]), min2(P[4 * h + 2], P[4 * h + 3]));
    }
#pragma unroll
    for (int s = 1; s <= 2; s <<= 1) {
        uint32_t tx[4], tn[4];
#pragma unroll
        for (int h = 0; h < 4; h++) { tx[h] = __shfl_xor_sync(0xffffffffu, mx[h], s); tn[h] = __shfl_xor_sync(0xffffffffu, mn[h], s); }
#pragma unroll
        for (int h = 0; h < 4; h++) { mx[h] = max2(mx[h], tx[h]); mn[h] = min2(mn[h], tn[h]); }
    }
#pragma unroll
    for (int h = 0; h < 4; h++) {
        const float mx0 = bf_lo(mx[h]) * c0, mx1 = bf_hi(mx[h]) * c1, mn0 = bf_lo(mn[h]) * c0, mn1 = bf_hi(mn[h]) * c1;
        float ep[8], em[8];
#pragma unroll
        for (int i = 0; i < 8; i++) {
            const bool r1 = (i & 2);
            const uint32_t w = P[4 * h + (i >> 2) * 2 + (i & 1)];
            const float p = r1 ? bf_hi(w) : bf_lo(w);
            ep[i] = ex2(fmaf(p, r1 ? c1 : c0, r1 ? -mx1 : -mx0));
            em[i] = ex2(fmaf(p, r1 ? -c1 : -c0, r1 ? mn1 : mn0));
        }
        float sp[4], sm[4];
        uint32_t tp[4], tm[4];
#pragma unroll
        for (int i = 0; i < 4; i++) { tp[i] = pack_bf16(ep[2 * i], ep[2 * i + 1]); tm[i] = pack_bf16(em[2 * i], em[2 * i + 1]); }
        mma16816_z(sp, tp, 0x3f803f80u, 0x3f803f80u);
        mma16816_z(sm, tm, 0x3f803f80u, 0x3f803f80u);
        const float r0 = rcp(sp[0] * sm[0]), r1 = rcp(sp[2] * sm[2]);
        const float rs[4] = {r0 * sm[0], r1 * sm[2], r0 * sp[0], r1 * sp[2]};
#pragma unroll
        for (int i = 0; i < 4; i++) {
            plus[4 * h + i] = pack_bf16(ep[2 * i] * rs[i & 1], ep[2 * i + 1] * rs[i & 1]);
            minus[4 * h + i] = pack_bf16(em[2 * i] * rs[2 + (i & 1)], em[2 * i + 1] * rs[2 + (i & 1)]);
        }
    }
}

template <bool SCALE>
__device__ __forceinline__ void ln_frag(const float* acc, uint32_t cs_addr, float rs0, float nm0, float rs1, float nm1, uint32_t* a) {
    const float2 c0 = lds_f2(cs_addr), c1 = lds_f2(cs_addr + 32);
    const float s0 = SCALE ? rs0 : 1.f, s1 = SCALE ? rs1 : 1.f;
    a[0] = pack_bf16(fmaf(nm0, c0.x, acc[0]) * s0, fmaf(nm0, c0.y, acc[1]) * s0);
    a[1] = pack_bf16(fmaf(nm1, c0.x, acc[2]) * s1, fmaf(nm1, c0.y, acc[3]) * s1);
    a[2] = pack_bf16(fmaf(nm0, c1.x, acc[4]) * s0, fmaf(nm0, c1.y, acc[5]) * s0);
    a[3] = pack_bf16(fmaf(nm1, c1.x, acc[6]) * s1, fmaf(nm1, c1.y, acc[7]) * s1);
}

template <int UP>
__device__ __forceinline__ uint32_t hh_pair(const float* ag, float4 cs, float nmean) {
    const float g0 = fmaf(nmean, cs.x, ag[0]), g1 = fmaf(nmean, cs.y, ag[1]);
    const float u0 = fmaf(nmean, cs.z, ag[UP]), u1 = fmaf(nmean, cs.w, ag[UP + 1]);
    return pack_bf16(g0 * u0, g1 * u1);
}
template <int UP, int NTP>
__device__ __forceinline__ void hh_stage(const float* acc, uint32_t cs3, float nm0, float nm1, uint32_t stg, int lane) {
#pragma unroll
    for (int tp = 0; tp < NTP; tp++) {
        const float4 c0 = lds_f4(cs3 + tp * 128), c1 = lds_f4(cs3 + tp * 128 + 64);
        stsm4(stg + (lane & 15) * 128 + (((2 * tp + (lane >> 4)) ^ (lane & 7)) << 4), hh_pair<UP>(acc + 8 * tp, c0, nm0),
              hh_pair<UP>(acc + 8 * tp + 2, c0, nm1), hh_pair<UP>(acc + 8 * tp + 4, c1, nm0), hh_pair<UP>(acc + 8 * tp + 6, c1, nm1));
    }
    fence_async_smem();
    __syncwarp();
}

struct Ring {
    int slot; uint32_t phase;
    __device__ __forceinline__ void adv() { if (++slot == NB) { slot = 0; phase ^= 1; } }
};

__global__ void __launch_bounds__(NTHREADS, 1) fused_kernel(const __grid_constant__ Params P) {
    extern __shared__ __align__(1024) uint8_t smem_raw[];
    const uint32_t sb = smem_u32(smem_raw);
    const int tid = threadIdx.x, lane = tid & 31;
    const int warp = __shfl_sync(0xffffffffu, tid >> 5, 0);
    unsigned role = blockIdx.x;
    if (P.use_smid) asm volatile("mov.u32 %0, %%smid;" : "=r"(role));
    role = P.role[role];
    const int m = role >> 3, j = role & 7;
    const bool helper = role >= 128;

    TL(0, tid == 0); TLG(0, tid == 0);
    float* const acc_j = g_acc + j * ACC_SIZE;
    unsigned* const cnt_j = g_cnt + j * 32;

    if (__builtin_expect(warp >= 8, 1)) {
        asm volatile("setmaxnreg.dec.sync.aligned.u32 72;");
        if (elect_one()) {
            if (warp == 8) {
                if (!helper) {
#pragma unroll
                    for (int i = 0; i < NB; i++) mbar_init(sb + BAR_FULLB + 8 * i, 1);
#pragma unroll
                    for (int i = 0; i < 2; i++) {
                        mbar_expect_tx(sb + BAR_FULLB + 8 * i, SLOT);
                        tma3d(sb + OFF_B + i * SLOT, &P.twkv, sb + BAR_FULLB + 8 * i, 64 * j, 64 * i, 1);
                    }
                }
            } else if (warp == 9) {
#pragma unroll
                for (int i = 0; i < 8; i++) mbar_init(sb + BAR_FULLA + 8 * i, 1);
#pragma unroll
                for (int i = 0; i < 2; i++) {
                    mbar_expect_tx(sb + BAR_FULLA + 8 * i, SLOT);
                    tma2d(sb + OFF_A + i * SLOT, helper ? &P.twq : &P.tx, sb + BAR_FULLA + 8 * i, helper ? DM + 128 * j : 64 * i, 128 * (helper ? i : m));
                }
            } else if (warp == 10) {
#pragma unroll
                for (int i = 0; i < 9; i++) mbar_init(sb + BAR_CS1 + 8 * i, i == 0 || i == 8 ? 64 : (i == 1 ? 96 : (i < 4 ? 32 : 8)));
                trap_if_gt(sb & 1023, 0);
            } else {
#pragma unroll
                for (int i = 0; i < 14; i++) mbar_init(sb + (i < 8 ? BAR_EMPTYA : BAR_EMPTYB - 64) + 8 * i, 8);
            }
        }
        __syncwarp();
        const unsigned epoch = ld_relaxed(&g_epoch);
        bar_sync(0, NTHREADS);
        if (helper) {
            if (warp == 8) {
                if (elect_one()) {
#pragma unroll 1
                    for (int i = 2; i < 72; i++) {
                        const uint32_t full = sb + BAR_FULLA + 8 * (i & 7), dst = sb + OFF_A + (i & 7) * SLOT;
                        mbar_wait(sb + BAR_EMPTYA + 8 * (i & 7), ((i >> 3) & 1) ^ 1);
                        mbar_expect_tx(full, SLOT);
                        if (i < 24) {
                            tma2d(dst, &P.twq, full, (i < 16 ? DM + 64 * (i & 8) : 0) + 128 * j + 16 * (i & 4), 128 * (i & 3));
                        } else {
                            const int u = (i >> 3) - 3, c0 = 176 * (2 * j + (u & 1)) + 64 * (u >> 1);
                            tma2d(dst, &P.twg, full, c0, 64 * (i & 7));
                            tma2d(dst + 8192, &P.twu, full, c0, 64 * (i & 7));
                        }
                    }
                    prefetch_l2(P.wd + (size_t)j * 176128, 352256);
                }
            } else if (warp == 9) {
                wait_count_warp(g_cnt + (lane & 7) * 32, epoch * 32);
            }
            return;
        }
        if (warp == 8) {
            if (elect_one()) {
                if (m >= 3 && m < 8)
                    asm volatile("cp.async.bulk.prefetch.tensor.3d.L2.global [%0, {%1, %2, %3}];" ::"l"(&P.twkv), "r"(64 * j), "r"(64 * m), "r"(1) : "memory");
                if (j >= 3)
                    asm volatile("cp.async.bulk.prefetch.tensor.2d.L2.global [%0, {%1, %2}];" ::"l"(&P.tx), "r"(64 * j), "r"(128 * m) : "memory");
                Ring r{2, 0};
#pragma unroll 1
                for (int i = 2; i < 56; i++) {
                    const uint32_t full = sb + BAR_FULLB + 8 * r.slot, dst = sb + OFF_B + r.slot * SLOT;
                    mbar_wait(sb + BAR_EMPTYB + 8 * r.slot, r.phase ^ 1);
                    if (i >= 10 && i < 14) {
                        mbar_arrive(full);
                    } else {
                        if (i >= AHEAD && i < 6) mbar_wait(full - 8 * AHEAD, 0);
                        mbar_expect_tx(full, SLOT);
                        if (i < 8) {
                            tma3d(dst, &P.twkv, full, 64 * j, 64 * i, 1);
                        } else if (i < 16) {
                            tma2d(dst, &P.twq, full, 64 * j, 128 * (i & 3));
                        } else {
                            const int e = 2 * (i & 3), g8 = i - 20;
                            const bool wo = i < 20, gu = !wo && i < 44;
                            const int c0 = gu ? 176 * j + 8 * (g8 & ~7) : 64 * j;
                            const int r0 = wo ? 64 * KORD(e, j) : (gu ? 64 * (g8 < 8 ? KORD(g8, j) : g8 & 7) : 176 * e + 64 * ((i - 44) >> 2));
                            const int r1 = wo ? 64 * KORD(e + 1, j) : (gu ? r0 : r0 + 176);
                            tma2d(dst, wo ? &P.two : (gu ? &P.twg : &P.twd), full, c0, r0);
                            tma2d(dst + 8192, wo ? &P.two : (gu ? &P.twu : &P.twd), full, c0, r1);
                        }
                    }
                    r.adv();
                }
            }
            return;
        }
        if (warp == 9) {
            if (elect_one()) {
#pragma unroll 1
                for (int i = 2; i < 8; i++) {
                    if (i >= AHEAD + 1) mbar_wait(sb + BAR_FULLA + 8 * (i - AHEAD - 1), 0);
                    mbar_expect_tx(sb + BAR_FULLA + 8 * i, SLOT);
                    tma2d(sb + OFF_A + i * SLOT, &P.tx, sb + BAR_FULLA + 8 * i, 64 * i, 128 * m);
                }
#pragma unroll 1
                for (int i = 1; i < 10; i++) prefetch_tmap(&P.tx + i);
#pragma unroll 1
                for (int r = 1; r < 6; r++) {
                    const CUtensorMap* tm = &P.tx + min(r, 3);
                    const int cstep = r < 3 ? 64 : 192, cbase = r < 3 ? 0 : 64 * (r - 3), skip = r < 3 ? j : 8;
                    mbar_wait(sb + BAR_EMPTYA + 8 * (skip == 0), (r - 1) & 1);
                    wait_count(g_flag + (m * 5 + r - 1) * 32, epoch * (r < 3 ? 64 : 8));
                    TL(64 + r, true);
#pragma unroll 1
                    for (int t = 0; t < 8; t++) {
                        if (t == skip) continue;
                        mbar_wait(sb + BAR_EMPTYA + 8 * t, (r - 1) & 1);
                        mbar_expect_tx(sb + BAR_FULLA + 8 * t, SLOT);
                        tma2d(sb + OFF_A + t * SLOT, tm, sb + BAR_FULLA + 8 * t, cbase + cstep * t, 128 * m);
                    }
                }
            }
            return;
        }
        const int a = warp - 10;
        {
            const int row = 16 * j + 8 * a + (lane >> 2);
            const uint32_t ra = sb + OFF_A + row * 128;
            float sh = 0.f, s0 = 0.f, s1 = 0.f, q0 = 0.f, q1 = 0.f;
#pragma unroll 1
            for (int kt = 0; kt < 8; kt++) {
                mbar_wait(sb + BAR_FULLA + 8 * kt, 0);
                if (kt == 0) sh = bf_lo(lds128(ra + ((row & 7) << 4)).x);
#pragma unroll
                for (int i = 0; i < 2; i++) {
                    const uint4 v = lds128(ra + kt * SLOT + (((2 * (lane & 3) + i) ^ (row & 7)) << 4));
                    const uint32_t ww[4] = {v.x, v.y, v.z, v.w};
#pragma unroll
                    for (int e = 0; e < 4; e++) {
                        const float d0 = bf_lo(ww[e]) - sh, d1 = bf_hi(ww[e]) - sh;
                        s0 += d0; q0 = fmaf(d0, d0, q0);
                        s1 += d1; q1 = fmaf(d1, d1, q1);
                    }
                }
            }
            s0 += s1; q0 += q1;
#pragma unroll
            for (int o = 1; o <= 2; o <<= 1) { s0 += __shfl_xor_sync(0xffffffffu, s0, o); q0 += __shfl_xor_sync(0xffffffffu, q0, o); }
            const float md = s0 * (1.f / DM);
            const float rs = rsqrtf(fmaxf(q0 * (1.f / DM) - md * md, 0.f) + 1e-5f);
            st_tagged_if(g_xstat + 2 * (128 * m + row), rs, -(sh + md), epoch, (lane & 3) == 0);
        }
        const unsigned long long* cs = g_cs + j * 768 + 2 * lane;
#pragma unroll 1
        for (int c = 0; c < (a ? 5 : 10); c++) {
            if (c == 4) {
                const int t = 32 * a + lane;
                const uint32_t kvs = sb + OFF_A + KVS(j) * SLOT;
                mbar_wait(sb + BAR_KVW, 0);
#pragma unroll 1
                for (int pass = 0; pass < 2; pass++) {
                    float4 v[8];
#pragma unroll
                    for (int i = 0; i < 8; i++) v[i] = ld_l2_f4(acc_j + ACC_KV + 4 * (t + 64 * i));
                    const float2 zz = ld_l2_f2(acc_j + ACC_Z + 2 * t);
#pragma unroll
                    for (int i = 0; i < 8; i++)
                        sts64(kvs + ((t >> 2) + 16 * i) * 48 + (t & 3) * 8, pack_bf16(v[i].x, v[i].y), pack_bf16(v[i].z, v[i].w));
                    const uint32_t z0 = pack_bf16(zz.x, zz.x), z1 = pack_bf16(zz.y, zz.y);
                    sts128(kvs + t * 96 + 32, z0, z0, z0, z0);
                    sts128(kvs + t * 96 + 80, z1, z1, z1, z1);
                    if (pass == 0) {
                        __syncwarp();
                        if (lane == 0) red_relaxed(cnt_j, 1);
                        TL(19, t == 0);
                        wait_count_warp(cnt_j, epoch * 32);
                        TL(14, t == 0);
                    }
                }
                mbar_arrive(sb + BAR_KVR);
                uint32_t it = 0;
                while (__any_sync(0xffffffffu, (int)(readback(g_flag + (m * 5 + 1) * 32) - epoch * 64) < 0)) {
                    __nanosleep(500);
                    trap_if_gt(++it, 1u << 22);
                }
                if (a) break;
            }
            if (c == 3 && !a) continue;
            const unsigned long long* src = c < 2 ? g_xstat + 2 * (128 * m + 64 * a + 32 * c + lane) : cs + (c < 4 ? 128 * (a + c - 2) : 128 + 64 * c);
            const uint32_t dst = c < 2 ? OFF_XST + (64 * a + 32 * c + lane) * 8
                                       : (c < 4 ? OFF_CS1 + (c == 2 ? 256 * (a + 1) : 0) + 8 * lane : OFF_CS3 + (32 * ((c - 4) >> 1) + lane) * 16 + 8 * (c & 1));
            uint4 v;
            uint32_t it = 0;
            while (true) {
                v = ld_tagged_rlx(src);
                if (!__any_sync(0xffffffffu, v.y != epoch || v.w != epoch)) break;
                __nanosleep(60);
                trap_if_gt(++it, 1u << 22);
            }
            sts64(sb + dst, v.x, v.z);
            if (c == 2 - a || (a && c > 1) || c == 9) mbar_arrive(sb + (c == 9 ? BAR_CS3 : (c == 2 - a ? BAR_CS1 : (c == 2 ? BAR_CSV : BAR_CSQ))));
        }
#pragma unroll 1
        for (int rr = 0; rr < 2; rr++) {
            const int row = 64 * rr + 32 * a + lane;
            const float* sp = g_hstat + (1024 * m + row) * 2;
            float2 v[8];
#pragma unroll
            for (int i = 0; i < 8; i++) v[i] = ld_l2_f2(sp + 256 * i);
            float mean = 0.f;
#pragma unroll
            for (int i = 0; i < 8; i++) mean += v[i].x;
            mean *= 0.125f;
            float m2 = 0.f, dv = 0.f;
#pragma unroll
            for (int i = 0; i < 8; i++) { m2 += v[i].y; dv = fmaf(v[i].x - mean, v[i].x - mean, dv); }
            sts_f2(sb + OFF_CS1 + row * 8, -mean, __fdividef(1.f, fmaf(dv, 64.f, m2) * (1.f / DM) + 1e-5f));
        }
        mbar_arrive(sb + BAR_CS3);
#pragma unroll 1
        for (int c = a; c < 3; c += 2) {
            const int slot = c == 2 ? 1 : 3 + 2 * c;
            mbar_wait(sb + BAR_STG + 8 * c, 0);
            if (elect_one()) {
                tma_store2d(&P.thh, sb + OFF_B + slot * SLOT, 192 * j + 64 * c, 128 * m);
                asm volatile("cp.async.bulk.wait_group.read 0;" ::: "memory");
                mbar_arrive_n_if(sb + BAR_EMPTYB + 8 * slot, 8, true);
                asm volatile("cp.async.bulk.wait_group 0;" ::: "memory");
            }
            __syncwarp();
            TL(60 + c, lane == 0);
            uint32_t ack = 0;
#pragma unroll
            for (int i = 0; i < 4; i++) ack |= readback(g_hh + (size_t)(128 * m + 32 * i + lane) * FFP + 192 * j + 64 * c);
            signal_after(g_flag + (m * 5 + 2 + c) * 32, ack, P.zero, lane == 0);
            TL(54 + c, lane == 0);
        }
        return;
    }
    const unsigned epoch = ld_relaxed(&g_epoch);
    uint32_t wraw[16];
    if (!helper) {
        const uint32_t* wp = reinterpret_cast<const uint32_t*>(P.wphi) + (4 * j) * 128 + (lane & 3) * 16 + (lane >> 2);
#pragma unroll
        for (int i = 0; i < 16; i++)
            asm volatile("ld.global.nc.u32 %0, [%1];" : "=r"(wraw[i]) : "l"(wp + (i >> 2) * 128 + ((i >> 1) & 1) * 64 + (i & 1) * 8));
    }
    asm volatile("setmaxnreg.inc.sync.aligned.u32 216;");
    bar_sync(0, NTHREADS);
    if (helper) {
        if (warp < 4) {
            sts128(sb + OFF_B + 16 * tid, 0x3f803f80u, 0x3f803f80u, 0x3f803f80u, 0x3f803f80u);
            for (int i = tid; i < 2 * ACC_SIZE / 4; i += 128) stg128(g_acc + 2 * j * ACC_SIZE + 4 * i, 0, 0, 0, 0);
            fence_async_smem();
            fence_gpu();
            bar_sync(1, 128);
            float acc[8];
            int i = 0;
#pragma unroll 1
            for (int job = 0; job < 12; job++) {
                const int n = job < 6 ? 4 : 8;
#pragma unroll 1
                for (int t = 0; t < n; t++, i++) {
                    mbar_wait(sb + BAR_FULLA + 8 * (i & 7), (i >> 3) & 1);
                    wg_fence();
#pragma unroll
                    for (int k = 0; k < 8; k++)
                        wgmma_n8_tt(acc + (k & 4), desc_lo(sb + OFF_A) + (i & 7) * (SLOT >> 4) + 128 * k, desc_lo(sb + OFF_B), (t | (k & 3)) != 0);
                    wg_commit();
                    wg_wait<1>();
                    mbar_arrive_n_if(sb + BAR_EMPTYA + 8 * ((i + 7) & 7), 2, lane == 0 && i > 0);
                }
                wg_wait<0>();
                fence_acc<8>(acc);
                const int q = lane & 3;
                const float lo = (q & 1) ? acc[2] : acc[0], hi = (q & 1) ? acc[6] : acc[4];
                const float v = job < 6 ? lo + hi : ((q & 2) ? hi : lo);
                unsigned long long* dst = g_cs + ((2 * j + (job & 1)) * 6 + (job >> 1)) * 128 + (q >> 1) * 64 + 16 * warp + 8 * (q & 1) + (lane >> 2);
                asm volatile("st.relaxed.gpu.global.b64 [%0], %1;" ::"l"(dst), "l"(((unsigned long long)epoch << 32) | __float_as_uint(v)) : "memory");
            }
        }
        return;
    }
    {
        const int w = warp >> 2, wv = warp & 3, g = lane >> 2, q = lane & 3;
        const int row_w = 128 * m + 16 * warp;
        const uint32_t sa = sb + OFF_A + w * 8192;
        const desc_t dA = desc_lo(sa), dB = desc_lo(sb + OFF_B);
        unsigned* const flag_m = g_flag + m * 160;
        const bool l0 = lane == 0;
        Ring rg{0, 0};
        int prev = 0;

        uint32_t wb[16];
        constexpr float L2E = 1.4426950408889634f;
        const int ch = lane >> 4, sw = lane & 7;
        const uint32_t lrow = (lane & 15) * 128;
        uint32_t fp[16], fm[16];
        {
            float acc[64], accq[32];
#pragma unroll 1
            for (int kt = 0; kt < 8; kt++) {
                mbar_waitc(sb + BAR_FULLA + 8 * kt, 0);
                mbar_waitc(sb + BAR_FULLB + 8 * rg.slot, rg.phase);
                const desc_t da = dA + kt * (SLOT >> 4), db = dB + rg.slot * (SLOT >> 4);
                wg_fence();
#pragma unroll
                for (int k = 0; k < 4; k++) wgmma_n128(acc, da + 2 * k, db + 128 * k, (kt | k) != 0);
                wg_commit();
                wg_wait<1>();
                mbar_arrive_if(sb + BAR_EMPTYB + 8 * prev, l0 && kt > 0);
                prev = rg.slot; rg.adv();
            }
#pragma unroll
            for (int i = 0; i < 8; i++) {
                wb[(i >> 1) * 4 + (i & 1)] = __byte_perm(wraw[2 * i], wraw[2 * i + 1], 0x5410);
                wb[(i >> 1) * 4 + 2 + (i & 1)] = __byte_perm(wraw[2 * i], wraw[2 * i + 1], 0x7632);
            }
            float2 s0, s1;
            uint32_t a[16];
            wg_wait<0>();
            fence_acc<64>(acc);
            mbar_arrive_if(sb + BAR_EMPTYB + 8 * prev, l0);
#pragma unroll 1
            for (int it = 0; it < 2; it++) {
                mbar_waitc(sb + BAR_FULLB + 8 * 2, it ^ 1); mbar_waitc(sb + BAR_FULLB + 8 * 3, it ^ 1);
                const desc_t da = dA + it * (4 * SLOT >> 4);
                wg_fence();
#pragma unroll
                for (int k = 0; k < 16; k++) wgmma_n64(accq, da + (k >> 2) * (SLOT >> 4) + (k & 3) * 2, dB + 2 * (SLOT >> 4) + 128 * k, (it | k) != 0);
                wg_commit();
                TL(17 + it, tid == 0);
                mbar_waitc(sb + BAR_CS1 + 16 * it, 0);
                s0 = lds_f2(sb + OFF_XST + (16 * warp + g) * 8); s1 = lds_f2(sb + OFF_XST + (16 * warp + g + 8) * 8);
                wg_wait<0>();
                fence_acc<32>(accq);
                mbar_arrive_if(sb + BAR_EMPTYB + 8 * (2 + lane), lane < 2);
                TL(2 + 2 * it, tid == 0);
                if (it == 0) {
#pragma unroll
                    for (int hh = 0; hh < 4; hh++)
                        ln_frag<false>(acc + 8 * hh, sb + OFF_CS1 + (64 + 16 * hh + 2 * q) * 4, 0.f, s0.y, 0.f, s1.y, a + 4 * hh);
                } else {
#pragma unroll
                    for (int hh = 0; hh < 4; hh++)
                        ln_frag<false>(accq + 8 * hh, sb + OFF_CS1 + (16 * hh + 2 * q) * 4, 0.f, s0.y, 0.f, s1.y, a + 4 * hh);
                }
                feature_maps(a, wb, s0.x * L2E, s1.x * L2E, fp, fm);
                if (it == 0) {
                    mbar_waitc(sb + BAR_FULLB + 8 * 4, 1); mbar_waitc(sb + BAR_FULLB + 8 * 5, 1);
                    mbar_waitc(sb + BAR_FULLB + 8 * 0, 0); mbar_waitc(sb + BAR_FULLB + 8 * 1, 0);
                    mbar_waitc(sb + BAR_CSV, 0);
                    const uint32_t st = sb + OFF_B + warp * 2048 + lrow;
#pragma unroll
                    for (int hh = 0; hh < 4; hh++) {
                        stsm4(st + (4 + (hh >> 1)) * SLOT + (((4 * (hh & 1) + ch) ^ sw) << 4), fp[4 * hh], fp[4 * hh + 1], fp[4 * hh + 2], fp[4 * hh + 3]);
                        stsm4(st + (4 + (hh >> 1)) * SLOT + (((4 * (hh & 1) + 2 + ch) ^ sw) << 4), fm[4 * hh], fm[4 * hh + 1], fm[4 * hh + 2], fm[4 * hh + 3]);
                        ln_frag<true>(acc + 32 + 8 * hh, sb + OFF_CS1 + (128 + 16 * hh + 2 * q) * 4, s0.x, s0.y, s1.x, s1.y, a);
                        stsm4(st + (hh >> 1) * SLOT + (((2 * (hh & 1) + ch) ^ sw) << 4), a[0], a[1], a[2], a[3]);
                    }
                    stsm4(st + ch * SLOT + ((4 ^ sw) << 4), 0x3f803f80u, 0x3f803f80u, 0x3f803f80u, 0x3f803f80u);
                    fence_async_smem();
                    bar_sync(1, 256);
                    float kvd[20];
                    wg_fence();
#pragma unroll
                    for (int k = 0; k < 8; k++)
                        wgmma_n40_tt(kvd, dB + (4 + w) * (SLOT >> 4) + 128 * k, dB + w * (SLOT >> 4) + 128 * k, k != 0);
                    wg_commit();
                    wg_wait<0>();
                    fence_acc<20>(kvd);
                    const bool h1 = wv >= 2;
                    const int f = 16 * warp + g;
                    float* kvp = acc_j + ACC_KV + f * 16 + 2 * q;
                    red_f32x2(kvp, h1 ? kvd[8] : kvd[0], h1 ? kvd[9] : kvd[1]);
                    red_f32x2(kvp + 128, h1 ? kvd[10] : kvd[2], h1 ? kvd[11] : kvd[3]);
                    red_f32x2(kvp + 8, h1 ? kvd[12] : kvd[4], h1 ? kvd[13] : kvd[5]);
                    red_f32x2(kvp + 136, h1 ? kvd[14] : kvd[6], h1 ? kvd[15] : kvd[7]);
                    red_f32_if(acc_j + ACC_Z + f + 8 * (q & 1), q ? kvd[18] : kvd[16], q < 2);
                    __syncwarp();
                    mbar_arrive_if(sb + (lane == 4 ? BAR_KVW : BAR_EMPTYB + 8 * ((4 + lane) % 6)), lane < 5);
                    TL(3, tid == 0);
                }
            }
        }
        uint32_t res_lo[8], res_hi[8], ack[5];
        const uint32_t own_rows = sb + OFF_A + j * SLOT + warp * 2048;
#pragma unroll
        for (int b = 0; b < 4; b++)
            ldsm4(own_rows + lrow + (((2 * b + ch) ^ sw) << 4), res_lo[2 * b], res_hi[2 * b], res_lo[2 * b + 1], res_hi[2 * b + 1]);
        mbar_arrive_if(sb + BAR_EMPTYA + 8 * lane, lane < 8 && lane != j && lane != KVS(j));
        TL(5, tid == 0);
        mbar_waitc(sb + BAR_KVR, 0);
        TL(6, tid == 0);
        {
            const uint32_t kvs = sb + OFF_A + KVS(j) * SLOT;
            uint32_t o_lo[8], o_hi[8];
#pragma unroll
            for (int hh = 0; hh < 4; hh++) {
                uint32_t b[8], zb[4];
                const uint32_t base = kvs + hh * 32 * 48;
                ldsm4t(base + (lane & 15) * 48 + (lane >> 4) * 16, b[0], b[1], b[2], b[3]);
                ldsm4t(base + (16 + (lane & 15)) * 48 + (lane >> 4) * 16, b[4], b[5], b[6], b[7]);
                ldsm4t(base + lane * 48 + 32, zb[0], zb[1], zb[2], zb[3]);
                float n0[4], n1[4], dn[4];
                mma16816_z(n0, fp + 4 * hh, b[0], b[1]); mma16816_z(n1, fp + 4 * hh, b[2], b[3]); mma16816_z(dn, fp + 4 * hh, zb[0], zb[1]);
                mma16816(n0, fm + 4 * hh, b[4], b[5]); mma16816(n1, fm + 4 * hh, b[6], b[7]); mma16816(dn, fm + 4 * hh, zb[2], zb[3]);
                const float i0 = rcp(dn[0] + 1e-6f), i1 = rcp(dn[2] + 1e-6f);
                o_lo[2 * hh] = pack_bf16(n0[0] * i0, n0[1] * i0); o_hi[2 * hh] = pack_bf16(n0[2] * i1, n0[3] * i1);
                o_lo[2 * hh + 1] = pack_bf16(n1[0] * i0, n1[1] * i0); o_hi[2 * hh + 1] = pack_bf16(n1[2] * i1, n1[3] * i1);
            }
            __syncwarp();
            mbar_arrive_if(sb + BAR_EMPTYA + 8 * KVS(j), l0);
            rg.slot = 4; rg.phase = 0;
            store_tile(own_rows, g_o + (size_t)row_w * DM + 64 * j, o_lo, o_hi, lane, ack);
            ack[4] = 0;
            TL(7, tid == 0);
        }
        {
            float acc[32];
#pragma unroll
            for (int t = 0; t < 8; t++) {
                acc[4 * t] = bf_lo(res_lo[t]); acc[4 * t + 1] = bf_hi(res_lo[t]);
                acc[4 * t + 2] = bf_lo(res_hi[t]); acc[4 * t + 3] = bf_hi(res_hi[t]);
            }
            fence_acc<32>(acc);
            int pa = 0;
#pragma unroll 1
            for (int kp = 0; kp < 4; kp++) {
                mbar_waitc(sb + BAR_FULLB + 8 * rg.slot, rg.phase);
#pragma unroll
                for (int hf = 0; hf < 2; hf++) {
                    const int i = 2 * kp + hf, kt = KORD(i, j);
                    mbar_waitc(sb + BAR_FULLA + 8 * kt, i != 0);
                    TL(8, i == 1 && tid == 0);
                    const desc_t da = dA + kt * (SLOT >> 4), db = dB + rg.slot * (SLOT >> 4);
                    wg_fence();
#pragma unroll
                    for (int k = 0; k < 4; k++) wgmma_n64(acc, da + 2 * k, db + (hf * 4 + k) * 128, 1);
                    wg_commit();
                    wg_wait<1>();
                    mbar_arrive_if(sb + BAR_EMPTYA + 8 * pa, l0 && i > 1);
                    if (hf == 0) {
                        mbar_arrive_if(sb + BAR_EMPTYB + 8 * prev, l0 && i > 0);
                        if (i == 0) { signal_late(flag_m, ack, P.zero, l0); TL(20, tid == 0); }
                    }
                    pa = kt;
                }
                prev = rg.slot; rg.adv();
            }
            wg_wait<0>();
            fence_acc<32>(acc);
            mbar_arrive_if(sb + BAR_EMPTYA + 8 * pa, l0);
            mbar_arrive_if(sb + BAR_EMPTYB + 8 * prev, l0);
            TL(9, tid == 0);
            float s0 = 0.f, s1 = 0.f;
#pragma unroll
            for (int t = 0; t < 8; t++) {
                res_lo[t] = pack_bf16(acc[4 * t], acc[4 * t + 1]);
                res_hi[t] = pack_bf16(acc[4 * t + 2], acc[4 * t + 3]);
                s0 += acc[4 * t] + acc[4 * t + 1];
                s1 += acc[4 * t + 2] + acc[4 * t + 3];
            }
            store_tile(own_rows, g_h + (size_t)row_w * DM + 64 * j, res_lo, res_hi, lane, ack);
            s0 += __shfl_xor_sync(0xffffffffu, s0, 1); s1 += __shfl_xor_sync(0xffffffffu, s1, 1);
            s0 += __shfl_xor_sync(0xffffffffu, s0, 2); s1 += __shfl_xor_sync(0xffffffffu, s1, 2);
            const float mu0 = s0 * (1.f / 64), mu1 = s1 * (1.f / 64);
            float q0 = 0.f, q1 = 0.f;
#pragma unroll
            for (int t = 0; t < 8; t++) {
                float d;
                d = acc[4 * t] - mu0; q0 = fmaf(d, d, q0);
                d = acc[4 * t + 1] - mu0; q0 = fmaf(d, d, q0);
                d = acc[4 * t + 2] - mu1; q1 = fmaf(d, d, q1);
                d = acc[4 * t + 3] - mu1; q1 = fmaf(d, d, q1);
            }
            q0 += __shfl_xor_sync(0xffffffffu, q0, 1); q1 += __shfl_xor_sync(0xffffffffu, q1, 1);
            q0 += __shfl_xor_sync(0xffffffffu, q0, 2); q1 += __shfl_xor_sync(0xffffffffu, q1, 2);
            stg_f2_if(g_hstat + (role * 128 + 16 * warp + g + 8 * (q & 1)) * 2, q ? mu1 : mu0, q ? q1 : q0, q < 2);
            ack[4] = readback(g_hstat + (role * 128 + 16 * warp + g + 8 * (q & 1)) * 2);
            TL(10, tid == 0);
        }
        {
            float acc[64];
#pragma unroll 1
            for (int c = 0; c < 3; c++) {
#define KT_P3(MMA)                                                                                          \
    _Pragma("unroll 1") for (int i = 0; i < 8; i++) {                                                       \
        const int kt = c ? i : KORD(i, j);                                                                  \
        mbar_waitc(sb + BAR_FULLA + 8 * kt, 0);                                                             \
        mbar_waitc(sb + BAR_FULLB + 8 * rg.slot, rg.phase);                                                 \
        TL(44, tid == 0 && i == 1 && c == 0);                                                               \
        const desc_t da = dA + kt * (SLOT >> 4), db = dB + rg.slot * (SLOT >> 4);                           \
        wg_fence();                                                                                         \
        _Pragma("unroll") for (int k = 0; k < 4; k++) MMA(acc, da + 2 * k, db + 128 * k, (i | k) != 0);     \
        wg_commit();                                                                                        \
        wg_wait<1>();                                                                                       \
        mbar_arrive_if(sb + BAR_EMPTYB + 8 * prev, l0 && i > 0);                                            \
        mbar_arrive_if(sb + BAR_EMPTYA + 8 * ((i + 7) & 7), l0 && i > 0 && c == 2);                         \
        if ((i | c) == 0) { signal_late(flag_m + 32, ack, P.zero, l0); TL(21, tid == 0); }                  \
        prev = rg.slot; rg.adv();                                                                           \
    }
                if (c < 2) { KT_P3(wgmma_n128) } else { KT_P3(wgmma_n112) }
                mbar_waitc(sb + BAR_CS3, 0);
                const float nm0 = lds_f2(sb + OFF_CS1 + (16 * warp + g) * 8).x, nm1 = lds_f2(sb + OFF_CS1 + (16 * warp + g + 8) * 8).x;
                wg_wait<0>();
                fence_acc<64>(acc);
                mbar_arrive_if(sb + BAR_EMPTYA + 8 * 7, l0 && c == 2);
                TL(11 + c, tid == 0);
                bar_sync(1, 256);
                hh_stage<32, 4>(acc, sb + OFF_CS3 + q * 16 + 512 * c, nm0, nm1, sb + OFF_B + prev * SLOT + warp * 2048, lane);
                mbar_arrive_if(sb + BAR_STG + 8 * c, l0);
                TL(50 + c, tid == 0);
            }
        }
        {
            float acc[64];
            const desc_t dA0 = desc_lo(sb + OFF_A);
#define KT_P4(I, NK)                                                                                        \
    do {                                                                                                    \
        const int s_ = (2 * (I) + w) & 7;                                                                   \
        mbar_waitc(sb + BAR_FULLB + 8 * rg.slot, rg.phase);                                                 \
        mbar_waitc(sb + BAR_FULLA + 8 * s_, (((I) >> 2) + 1) & 1);                                          \
        TL(30 + (I), tid == 0);                                                                             \
        const desc_t dh_ = dA0 + s_ * (SLOT >> 4), dw_ = dB + rg.slot * (SLOT >> 4) + w * 512;              \
        wg_fence();                                                                                         \
        _Pragma("unroll") for (int k = 0; k < (NK); k++) wgmma_n128_tn(acc, dw_ + 128 * k, dh_ + 2 * k, ((I) | k) != 0); \
        wg_commit();                                                                                        \
        wg_wait<1>();                                                                                       \
        mbar_arrive_n_if(sb + BAR_EMPTYA + 8 * ((s_ + 6) & 7), 2, l0 && (I) > 0);                           \
        mbar_arrive_if(sb + BAR_EMPTYB + 8 * prev, l0 && (I) > 0);                                          \
        prev = rg.slot; rg.adv();                                                                           \
    } while (0)
#pragma unroll 1
            for (int i = 0; i < 8; i++) KT_P4(i, 4);
#pragma unroll 1
            for (int i = 8; i < 12; i++) KT_P4(i, 3);
            const uint32_t tile = sb + OFF_A + w * SLOT;
#pragma unroll
            for (int b = 0; b < 4; b++)
                stsm4(tile + (16 * wv + (lane & 15)) * 128 + (((2 * b + (lane >> 4)) ^ (lane & 7)) << 4),
                      res_lo[2 * b], res_hi[2 * b], res_lo[2 * b + 1], res_hi[2 * b + 1]);
            wg_wait<0>();
            fence_acc<64>(acc);
            TL(15, tid == 0);
            const uint32_t xch = sb + OFF_A + 2 * SLOT + (tid & 127) * 16;
            if (w) {
#pragma unroll
                for (int t = 0; t < 8; t++) {
                    sts128(xch + SLOT + t * 2048, __float_as_uint(acc[4 * t]), __float_as_uint(acc[4 * t + 1]),
                           __float_as_uint(acc[4 * t + 2]), __float_as_uint(acc[4 * t + 3]));
                }
#pragma unroll
                for (int t = 0; t < 32; t++) acc[t] = acc[32 + t];
            } else {
#pragma unroll
                for (int t = 0; t < 8; t++)
                    sts128(xch + t * 2048, __float_as_uint(acc[32 + 4 * t]), __float_as_uint(acc[33 + 4 * t]),
                           __float_as_uint(acc[34 + 4 * t]), __float_as_uint(acc[35 + 4 * t]));
            }
            bar_sync(1, 256);
            const uint32_t blk = tile + ((lane & 7) + (lane >> 4) * 8) * 128 + (((2 * wv + ((lane >> 3) & 1)) ^ (lane & 7)) << 4);
#pragma unroll
            for (int tp = 0; tp < 4; tp++) {
                uint32_t hr[4];
                ldsm4t(blk + tp * 2048, hr[0], hr[1], hr[2], hr[3]);
#pragma unroll
                for (int u = 0; u < 2; u++) {
                    const int t = 2 * tp + u;
                    const float4 o = lds_f4(xch + (w ^ 1) * SLOT + t * 2048);
                    const float4 st = lds_f4(sb + OFF_CS1 + (64 * w + 8 * t + 2 * q) * 8);
                    hr[2 * u] = pack_bf16(fmaf(acc[4 * t] + o.x, st.y, bf_lo(hr[2 * u])), fmaf(acc[4 * t + 1] + o.y, st.w, bf_hi(hr[2 * u])));
                    hr[2 * u + 1] = pack_bf16(fmaf(acc[4 * t + 2] + o.z, st.y, bf_lo(hr[2 * u + 1])), fmaf(acc[4 * t + 3] + o.w, st.w, bf_hi(hr[2 * u + 1])));
                }
                stsm4t(blk + tp * 2048, hr[0], hr[1], hr[2], hr[3]);
            }
            bar_sync(2 + w, 128);
#pragma unroll
            for (int i = 0; i < 4; i++) {
                const int rr = 16 * wv + 4 * i + (lane >> 3);
                const uint4 v = lds128(tile + rr * 128 + (((lane & 7) ^ (rr & 7)) << 4));
                stg128(P.out + (size_t)(128 * m + 64 * w + rr) * DM + 64 * j + (lane & 7) * 8, v.x, v.y, v.z, v.w);
            }
            if (tid == 0 && role == 0) g_epoch = epoch + 1;
            TL(16, tid == 0); TLG(1, tid == 0);
        }
    }
}

typedef CUresult (*EncodeFn)(CUtensorMap*, CUtensorMapDataType, cuuint32_t, void*, const cuuint64_t*, const cuuint64_t*,
                             const cuuint32_t*, const cuuint32_t*, CUtensorMapInterleave, CUtensorMapSwizzle,
                             CUtensorMapL2promotion, CUtensorMapFloatOOBfill);

static void make_map2d(EncodeFn enc, CUtensorMap* tm, const void* base, uint64_t cols, uint64_t rows, uint64_t pitch_elems,
                       uint32_t box_rows) {
    cuuint64_t gd[2] = {cols, rows};
    cuuint64_t gs[1] = {pitch_elems * 2};
    cuuint32_t bd[2] = {64, box_rows};
    cuuint32_t es[2] = {1, 1};
    enc(tm, CU_TENSOR_MAP_DATA_TYPE_BFLOAT16, 2, const_cast<void*>(base), gd, gs, bd, es, CU_TENSOR_MAP_INTERLEAVE_NONE,
        CU_TENSOR_MAP_SWIZZLE_128B, CU_TENSOR_MAP_L2_PROMOTION_L2_256B, CU_TENSOR_MAP_FLOAT_OOB_FILL_NONE);
}

}

extern "C" void kernel_launch(void* const* d_in, const int* in_sizes, int n_in, void* d_out, int out_size) {
    using namespace hk;
    (void)in_sizes; (void)n_in; (void)out_size;
    static EncodeFn enc = nullptr;
    static void *po = nullptr, *ph = nullptr, *phh = nullptr;
    static int std_layout = 0;
    if (!enc) {
        void* fn = nullptr;
        cudaDriverEntryPointQueryResult qr;
        cudaGetDriverEntryPoint("cuTensorMapEncodeTiled", &fn, cudaEnableDefault, &qr);
        enc = (EncodeFn)fn;
        cudaGetSymbolAddress(&po, g_o);
        cudaGetSymbolAddress(&ph, g_h);
        cudaGetSymbolAddress(&phh, g_hh);
        cudaFuncSetAttribute(fused_kernel, cudaFuncAttributeMaxDynamicSharedMemorySize, SMEM_BYTES);
        int dev = 0, sms = 0;
        cudaGetDevice(&dev);
        cudaDeviceGetAttribute(&sms, cudaDevAttrMultiProcessorCount, dev);
        cudaFuncSetAttribute(fused_kernel, cudaFuncAttributeNonPortableClusterSizeAllowed, 1);
        const int sizes[3] = {8, 9, 16}, want[3] = {15, 9, 7};
        bool ok = sms == NCTA;
        for (int i = 0; i < 3 && ok; i++) {
            cudaLaunchConfig_t cfg = {};
            cfg.gridDim = dim3(sizes[i] * 8); cfg.blockDim = dim3(NTHREADS); cfg.dynamicSmemBytes = SMEM_BYTES;
            cudaLaunchAttribute at;
            at.id = cudaLaunchAttributeClusterDimension;
            at.val.clusterDim.x = sizes[i]; at.val.clusterDim.y = 1; at.val.clusterDim.z = 1;
            cfg.attrs = &at; cfg.numAttrs = 1;
            int n = 0;
            ok = cudaOccupancyMaxActiveClusters(&n, fused_kernel, &cfg) == cudaSuccess && n == want[i];
        }
        (void)cudaGetLastError();
        std_layout = ok ? 1 : 0;
    }
    Params P;
    const __nv_bfloat16* x = (const __nv_bfloat16*)d_in[0];
    P.x = x;
    P.wqkv = (const __nv_bfloat16*)d_in[1];
    P.wphi = (const __nv_bfloat16*)d_in[2];
    P.wo = (const __nv_bfloat16*)d_in[3];
    P.wg = (const __nv_bfloat16*)d_in[5];
    P.wu = (const __nv_bfloat16*)d_in[6];
    P.wd = (const __nv_bfloat16*)d_in[7];
    P.out = (__nv_bfloat16*)d_out;
    P.use_smid = std_layout;
    P.zero = 0;
    for (int i = 0; i < NCTA; i++) {
        int role = i < 4 ? 128 + i : i - 4;
        if (std_layout) {
            const int tpc = i >> 1, odd = i & 1;
            if (tpc < 32) role = (tpc & 7) * 8 + (tpc >> 3) * 2 + odd;
            else if (tpc < 60) role = (8 + (tpc - 32) % 7) * 8 + ((tpc - 32) / 7) * 2 + odd;
            else if (tpc < 62) role = 128 + (tpc - 60) * 2 + odd;
            else role = 15 * 8 + (tpc - 62) * 2 + odd;
        }
        P.role[i] = (unsigned char)role;
    }
    make_map2d(enc, &P.tx, x, DM, SEQ, DM, 128);
    make_map2d(enc, &P.to, po, DM, SEQ, DM, 128);
    make_map2d(enc, &P.th, ph, DM, SEQ, DM, 128);
    make_map2d(enc, &P.thh, phh, FFP, SEQ, FFP, 128);
    make_map2d(enc, &P.twq, P.wqkv, 3 * DM, DM, 3 * DM, 128);
    make_map2d(enc, &P.two, P.wo, DM, DM, DM, 64);
    make_map2d(enc, &P.twg, P.wg, FF, DM, FF, 64);
    make_map2d(enc, &P.twu, P.wu, FF, DM, FF, 64);
    make_map2d(enc, &P.twd, P.wd, DM, FF, DM, 64);
    {
        cuuint64_t gd[3] = {(cuuint64_t)DM, (cuuint64_t)DM, 3};
        cuuint64_t gs[2] = {(cuuint64_t)3 * DM * 2, (cuuint64_t)DM * 2};
        cuuint32_t bd[3] = {64, 64, 2};
        cuuint32_t es[3] = {1, 1, 1};
        enc(&P.twkv, CU_TENSOR_MAP_DATA_TYPE_BFLOAT16, 3, const_cast<__nv_bfloat16*>(P.wqkv), gd, gs, bd, es,
            CU_TENSOR_MAP_INTERLEAVE_NONE, CU_TENSOR_MAP_SWIZZLE_128B, CU_TENSOR_MAP_L2_PROMOTION_L2_256B,
            CU_TENSOR_MAP_FLOAT_OOB_FILL_NONE);
    }
    fused_kernel<<<NCTA, NTHREADS, SMEM_BYTES>>>(P);
}
```

```cpp
#include <cuda_runtime.h>
#include <cuda_bf16.h>
#include <cuda.h>
#include <stdint.h>

namespace hk {

constexpr int SEQ = 2048, DM = 512, FF = 1376, FFP = 1536;
constexpr int NCTA = 132;
constexpr int NTHREADS = 384;
constexpr uint32_t SLOT = 16384;
constexpr uint32_t OFF_A = 0, OFF_B = 8 * SLOT, OFF_MISC = 14 * SLOT;
constexpr uint32_t BAR_FULLA = OFF_MISC + 0, BAR_EMPTYA = OFF_MISC + 64, BAR_FULLB = OFF_MISC + 128,
                   BAR_EMPTYB = OFF_MISC + 176, BAR_CS1 = OFF_MISC + 224, BAR_CS3 = OFF_MISC + 232,
                   BAR_CSQ = OFF_MISC + 240, BAR_CSV = OFF_MISC + 248,
                   BAR_STG = OFF_MISC + 256,
                   BAR_KVW = OFF_MISC + 280, BAR_KVR = OFF_MISC + 288;
constexpr uint32_t OFF_CS1 = OFF_MISC + 384;
constexpr uint32_t OFF_CS3 = OFF_CS1 + 1024;
constexpr uint32_t OFF_XST = OFF_CS3;
constexpr uint32_t SMEM_BYTES = OFF_CS3 + 1536;
#define KVS(j) ((j) == 3 ? 2 : 3)
#define KORD(i, j) ((i) == 0 ? (j) : (i) - ((i) <= (j)))
constexpr int NB = 6;
constexpr int AHEAD = 3;

constexpr int ACC_KV = 0, ACC_Z = 2048, ACC_SIZE = 2176;

__device__ __align__(1024) __nv_bfloat16 g_o[SEQ * DM];
__device__ __align__(1024) __nv_bfloat16 g_h[SEQ * DM];
__device__ __align__(1024) __nv_bfloat16 g_hh[SEQ * FFP];
__device__ __align__(128) float g_hstat[SEQ * 16];
__device__ __align__(128) unsigned long long g_xstat[SEQ * 2];
__device__ __align__(128) float g_acc[8 * ACC_SIZE];
__device__ __align__(128) unsigned g_cnt[8 * 32];
__device__ __align__(128) unsigned long long g_cs[8 * 6 * 128];
__device__ __align__(128) unsigned g_flag[16 * 5 * 32];
__device__ unsigned g_epoch = 1;

#define TL(i, pred) do {} while (0)
#define TLG(i, pred) do {} while (0)

struct Params {
    CUtensorMap tx, to, th, thh, twkv, twq, two, twg, twu, twd;
    const __nv_bfloat16 *x, *wqkv, *wphi, *wo, *wg, *wu, *wd;
    __nv_bfloat16* out;
    int use_smid;
    unsigned zero;
    unsigned char role[NCTA];
};

__device__ __forceinline__ uint32_t smem_u32(const void* p) { return (uint32_t)__cvta_generic_to_shared(p); }
__device__ __forceinline__ void mbar_init(uint32_t bar, uint32_t cnt) {
    asm volatile("mbarrier.init.shared::cta.b64 [%0], %1;" ::"r"(bar), "r"(cnt) : "memory");
}
__device__ __forceinline__ void mbar_expect_tx(uint32_t bar, uint32_t bytes) {
    asm volatile("mbarrier.arrive.expect_tx.shared::cta.b64 _, [%0], %1;" ::"r"(bar), "r"(bytes) : "memory");
}
__device__ __forceinline__ void mbar_arrive(uint32_t bar) {
    asm volatile("mbarrier.arrive.shared::cta.b64 _, [%0];" ::"r"(bar) : "memory");
}
__device__ __forceinline__ void mbar_arrive_if(uint32_t bar, bool pred) {
    asm volatile("{.reg .pred p; setp.ne.u32 p, %1, 0; @p mbarrier.arrive.shared::cta.b64 _, [%0];}" ::"r"(bar), "r"((uint32_t)pred) : "memory");
}
__device__ __forceinline__ bool mbar_try(uint32_t bar, uint32_t parity) {
    uint32_t ok;
    asm volatile("{.reg .pred p; mbarrier.try_wait.parity.shared::cta.b64 p, [%1], %2; selp.u32 %0,1,0,p;}"
                 : "=r"(ok) : "r"(bar), "r"(parity) : "memory");
    return ok;
}
__device__ __forceinline__ bool mbar_test(uint32_t bar, uint32_t parity) {
    uint32_t ok;
    asm volatile("{.reg .pred p; mbarrier.test_wait.parity.shared::cta.b64 p, [%1], %2; selp.u32 %0,1,0,p;}"
                 : "=r"(ok) : "r"(bar), "r"(parity) : "memory");
    return ok;
}
__device__ __forceinline__ void trap_if_gt(uint32_t v, uint32_t lim) {
    asm volatile("{.reg .pred p; setp.gt.u32 p, %0, %1; @p trap;}" ::"r"(v), "r"(lim));
}
__device__ __forceinline__ void mbar_wait(uint32_t bar, uint32_t parity) {
    asm volatile("{\n"
                 ".reg .pred P1, P2;\n"
                 ".reg .u32 c;\n"
                 "mov.u32 c, 0;\n"
                 "LAB_WAIT:\n"
                 "mbarrier.try_wait.parity.shared::cta.b64 P1, [%0], %1;\n"
                 "@P1 bra LAB_DONE;\n"
                 "add.u32 c, c, 1;\n"
                 "setp.gt.u32 P2, c, 4194304;\n"
                 "@P2 trap;\n"
                 "bra LAB_WAIT;\n"
                 "LAB_DONE:\n"
                 "}" ::"r"(bar), "r"(parity) : "memory");
}
__device__ __forceinline__ void mbar_waitc(uint32_t bar, uint32_t parity) {
    asm volatile("{\n"
                 ".reg .pred P1;\n"
                 "LAB_WAIT:\n"
                 "mbarrier.try_wait.parity.shared::cta.b64 P1, [%0], %1;\n"
                 "@!P1 bra LAB_WAIT;\n"
                 "}" ::"r"(bar), "r"(parity) : "memory");
}
__device__ __forceinline__ void tma2d(uint32_t dst, const CUtensorMap* tm, uint32_t bar, int c0, int c1) {
    asm volatile("cp.async.bulk.tensor.2d.shared::cluster.global.mbarrier::complete_tx::bytes [%0], [%1, {%3, %4}], [%2];"
                 ::"r"(dst), "l"(tm), "r"(bar), "r"(c0), "r"(c1) : "memory");
}
__device__ __forceinline__ void tma3d(uint32_t dst, const CUtensorMap* tm, uint32_t bar, int c0, int c1, int c2) {
    asm volatile("cp.async.bulk.tensor.3d.shared::cluster.global.mbarrier::complete_tx::bytes [%0], [%1, {%3, %4, %5}], [%2];"
                 ::"r"(dst), "l"(tm), "r"(bar), "r"(c0), "r"(c1), "r"(c2) : "memory");
}
__device__ __forceinline__ bool elect_one() {
    uint32_t ok;
    asm volatile("{.reg .pred p; elect.sync _|p, 0xffffffff; selp.u32 %0, 1, 0, p;}" : "=r"(ok));
    return ok;
}
__device__ __forceinline__ void prefetch_tmap(const CUtensorMap* tm) {
    asm volatile("prefetch.tensormap [%0];" ::"l"(tm) : "memory");
}
__device__ __forceinline__ void prefetch_l2(const void* p, uint32_t bytes) {
    asm volatile("cp.async.bulk.prefetch.L2.global [%0], %1;" ::"l"(p), "r"(bytes) : "memory");
}
__device__ __forceinline__ unsigned ld_acquire(const unsigned* p) {
    unsigned v; asm volatile("ld.acquire.gpu.global.u32 %0, [%1];" : "=r"(v) : "l"(p) : "memory"); return v;
}
__device__ __forceinline__ uint4 ld_acquire4(const unsigned* p) {
    uint4 v;
    asm volatile("ld.acquire.gpu.global.v4.u32 {%0,%1,%2,%3}, [%4];" : "=r"(v.x), "=r"(v.y), "=r"(v.z), "=r"(v.w) : "l"(p) : "memory");
    return v;
}
__device__ __forceinline__ unsigned ld_relaxed(const unsigned* p) {
    unsigned v; asm volatile("ld.relaxed.gpu.global.u32 %0, [%1];" : "=r"(v) : "l"(p)); return v;
}
__device__ __forceinline__ void st_relaxed(unsigned* p, unsigned v) {
    asm volatile("st.relaxed.gpu.global.u32 [%0], %1;" ::"l"(p), "r"(v) : "memory");
}
__device__ __forceinline__ void red_relaxed(unsigned* p, unsigned v) {
    asm volatile("red.relaxed.gpu.global.add.u32 [%0], %1;" ::"l"(p), "r"(v) : "memory");
}
__device__ __forceinline__ void fence_gpu() { asm volatile("fence.acq_rel.gpu;" ::: "memory"); }
__device__ __forceinline__ void fence_async_smem() { asm volatile("fence.proxy.async.shared::cta;" ::: "memory"); }
__device__ __forceinline__ void fence_async_global() { asm volatile("fence.proxy.async.global;" ::: "memory"); }
__device__ __forceinline__ uint32_t readback(const void* p) {
    uint32_t v; asm volatile("ld.relaxed.gpu.global.u32 %0, [%1];" : "=r"(v) : "l"(p) : "memory"); return v;
}
__device__ __forceinline__ void wait_count(const unsigned* p, unsigned target) {
    uint32_t it = 0;
    while ((int)(readback(p) - target) < 0) trap_if_gt(++it, 1u << 22);
}
__device__ __forceinline__ void wait_count_warp(const unsigned* p, unsigned target) {
    uint32_t it = 0;
    while (__any_sync(0xffffffffu, (int)(readback(p) - target) < 0)) trap_if_gt(++it, 1u << 22);
}
__device__ __forceinline__ void red_f32(float* p, float a) {
    asm volatile("red.relaxed.gpu.global.add.f32 [%0], %1;" ::"l"(p), "f"(a) : "memory");
}
__device__ __forceinline__ void red_f32x2(float* p, float a, float b) {
    asm volatile("red.relaxed.gpu.global.add.v2.f32 [%0], {%1, %2};" ::"l"(p), "f"(a), "f"(b) : "memory");
}
__device__ __forceinline__ void red_f32x4(float* p, float a, float b, float c, float d) {
    asm volatile("red.relaxed.gpu.global.add.v4.f32 [%0], {%1, %2, %3, %4};" ::"l"(p), "f"(a), "f"(b), "f"(c), "f"(d) : "memory");
}
__device__ __forceinline__ float4 ld_l2_f4(const float* p) {
    float4 v;
    asm volatile("ld.relaxed.gpu.global.v4.f32 {%0,%1,%2,%3}, [%4];" : "=f"(v.x), "=f"(v.y), "=f"(v.z), "=f"(v.w) : "l"(p) : "memory");
    return v;
}
__device__ __forceinline__ float2 ld_l2_f2(const float* p) {
    float2 v;
    asm volatile("ld.relaxed.gpu.global.v2.f32 {%0,%1}, [%2];" : "=f"(v.x), "=f"(v.y) : "l"(p) : "memory");
    return v;
}
__device__ __forceinline__ float ld_l2_f(const float* p) {
    float v;
    asm volatile("ld.relaxed.gpu.global.f32 %0, [%1];" : "=f"(v) : "l"(p) : "memory");
    return v;
}
__device__ __forceinline__ uint4 ldg_nc(const void* p) {
    uint4 v;
    asm volatile("ld.global.nc.L1::no_allocate.v4.u32 {%0,%1,%2,%3}, [%4];" : "=r"(v.x), "=r"(v.y), "=r"(v.z), "=r"(v.w) : "l"(p));
    return v;
}
__device__ __forceinline__ void stg128(void* p, uint32_t a, uint32_t b, uint32_t c, uint32_t d) {
    asm volatile("st.global.v4.u32 [%0], {%1,%2,%3,%4};" ::"l"(p), "r"(a), "r"(b), "r"(c), "r"(d) : "memory");
}
__device__ __forceinline__ uint4 lds128(uint32_t a) {
    uint4 v;
    asm volatile("ld.shared.v4.u32 {%0,%1,%2,%3}, [%4];" : "=r"(v.x), "=r"(v.y), "=r"(v.z), "=r"(v.w) : "r"(a) : "memory");
    return v;
}
__device__ __forceinline__ float2 lds_f2(uint32_t a) {
    float2 v;
    asm volatile("ld.shared.v2.f32 {%0,%1}, [%2];" : "=f"(v.x), "=f"(v.y) : "r"(a) : "memory");
    return v;
}
__device__ __forceinline__ void sts_f2(uint32_t a, float x, float y) {
    asm volatile("st.shared.v2.f32 [%0], {%1,%2};" ::"r"(a), "f"(x), "f"(y) : "memory");
}
__device__ __forceinline__ void sts64(uint32_t a, uint32_t x, uint32_t y) {
    asm volatile("st.shared.v2.u32 [%0], {%1,%2};" ::"r"(a), "r"(x), "r"(y) : "memory");
}
__device__ __forceinline__ void sts128(uint32_t a, uint32_t x, uint32_t y, uint32_t z, uint32_t w) {
    asm volatile("st.shared.v4.u32 [%0], {%1,%2,%3,%4};" ::"r"(a), "r"(x), "r"(y), "r"(z), "r"(w) : "memory");
}
__device__ __forceinline__ void stsm4(uint32_t a, uint32_t r0, uint32_t r1, uint32_t r2, uint32_t r3) {
    asm volatile("stmatrix.sync.aligned.m8n8.x4.shared.b16 [%0], {%1,%2,%3,%4};" ::"r"(a), "r"(r0), "r"(r1), "r"(r2), "r"(r3) : "memory");
}
__device__ __forceinline__ void stsm4t(uint32_t a, uint32_t r0, uint32_t r1, uint32_t r2, uint32_t r3) {
    asm volatile("stmatrix.sync.aligned.m8n8.x4.trans.shared.b16 [%0], {%1,%2,%3,%4};" ::"r"(a), "r"(r0), "r"(r1), "r"(r2), "r"(r3) : "memory");
}
__device__ __forceinline__ void tma_store2d(const CUtensorMap* tm, uint32_t src, int c0, int c1) {
    asm volatile("cp.async.bulk.tensor.2d.global.shared::cta.bulk_group [%0, {%2, %3}], [%1];" ::"l"(tm), "r"(src), "r"(c0), "r"(c1) : "memory");
    asm volatile("cp.async.bulk.commit_group;" ::: "memory");
}
__device__ __forceinline__ void ldsm4(uint32_t a, uint32_t& r0, uint32_t& r1, uint32_t& r2, uint32_t& r3) {
    asm volatile("ldmatrix.sync.aligned.m8n8.x4.shared.b16 {%0,%1,%2,%3}, [%4];" : "=r"(r0), "=r"(r1), "=r"(r2), "=r"(r3) : "r"(a) : "memory");
}
__device__ __forceinline__ void ldsm4t(uint32_t a, uint32_t& r0, uint32_t& r1, uint32_t& r2, uint32_t& r3) {
    asm volatile("ldmatrix.sync.aligned.m8n8.x4.trans.shared.b16 {%0,%1,%2,%3}, [%4];" : "=r"(r0), "=r"(r1), "=r"(r2), "=r"(r3) : "r"(a) : "memory");
}
__device__ __forceinline__ void mma16816(float* c, const uint32_t* a, uint32_t b0, uint32_t b1) {
    asm("mma.sync.aligned.m16n8k16.row.col.f32.bf16.bf16.f32 {%0,%1,%2,%3}, {%4,%5,%6,%7}, {%8,%9}, {%0,%1,%2,%3};"
                 : "+f"(c[0]), "+f"(c[1]), "+f"(c[2]), "+f"(c[3])
                 : "r"(a[0]), "r"(a[1]), "r"(a[2]), "r"(a[3]), "r"(b0), "r"(b1));
}
__device__ __forceinline__ uint32_t pack_bf16(float lo, float hi) {
    uint32_t r; asm("cvt.rn.bf16x2.f32 %0, %1, %2;" : "=r"(r) : "f"(hi), "f"(lo)); return r;
}
__device__ __forceinline__ float bf_lo(uint32_t w) { return __uint_as_float(w << 16); }
__device__ __forceinline__ float bf_hi(uint32_t w) { return __uint_as_float(w & 0xffff0000u); }
__device__ __forceinline__ float ex2(float x) { float r; asm("ex2.approx.ftz.f32 %0, %1;" : "=f"(r) : "f"(x)); return r; }
__device__ __forceinline__ float rcp(float x) { float r; asm("rcp.approx.ftz.f32 %0, %1;" : "=f"(r) : "f"(x)); return r; }
__device__ __forceinline__ void bar_sync(int id, int n) { asm volatile("bar.sync %0, %1;" ::"r"(id), "r"(n) : "memory"); }

typedef unsigned long long desc_t;
__device__ __forceinline__ desc_t desc_lo(uint32_t addr) { return (desc_t)(((addr & 0x3FFFF) >> 4) | (512u << 16)) | (0x40000040ull << 32); }
__device__ __forceinline__ void wg_fence() { asm volatile("wgmma.fence.sync.aligned;" ::: "memory"); }
__device__ __forceinline__ void wg_commit() { asm volatile("wgmma.commit_group.sync.aligned;" ::: "memory"); }
template <int N> __device__ __forceinline__ void wg_wait() { asm volatile("wgmma.wait_group.sync.aligned %0;" ::"n"(N) : "memory"); }
template <int N> __device__ __forceinline__ void fence_acc(float* d) {
#pragma unroll
    for (int i = 0; i < N; i++) asm volatile("" : "+f"(d[i])::"memory");
}
#define R4(o) "+f"(d[o + 0]), "+f"(d[o + 1]), "+f"(d[o + 2]), "+f"(d[o + 3])
#define R8(o) R4(o), R4(o + 4)
__device__ __forceinline__ void wgmma_n128(float* d, desc_t da, desc_t db, int sc) {
    asm volatile("{.reg .pred p; setp.ne.b32 p, %66, 0;\n"
                 "wgmma.mma_async.sync.aligned.m64n128k16.f32.bf16.bf16 {%0,%1,%2,%3,%4,%5,%6,%7,%8,%9,%10,%11,%12,%13,%14,%15,%16,%17,%18,%19,%20,%21,%22,%23,%24,%25,%26,%27,%28,%29,%30,%31,"
                 "%32,%33,%34,%35,%36,%37,%38,%39,%40,%41,%42,%43,%44,%45,%46,%47,%48,%49,%50,%51,%52,%53,%54,%55,%56,%57,%58,%59,%60,%61,%62,%63}, %64, %65, p, 1, 1, 0, 1;}"
                 : R8(0), R8(8), R8(16), R8(24), R8(32), R8(40), R8(48), R8(56)
                 : "l"(da), "l"(db), "r"(sc));
}
__device__ __forceinline__ void wgmma_n112(float* d, desc_t da, desc_t db, int sc) {
    asm volatile("{.reg .pred p; setp.ne.b32 p, %58, 0;\n"
                 "wgmma.mma_async.sync.aligned.m64n112k16.f32.bf16.bf16 {%0,%1,%2,%3,%4,%5,%6,%7,%8,%9,%10,%11,%12,%13,%14,%15,%16,%17,%18,%19,%20,%21,%22,%23,%24,%25,%26,%27,%28,%29,%30,%31,%32,%33,%34,%35,%36,%37,%38,%39,%40,%41,%42,%43,%44,%45,%46,%47,%48,%49,%50,%51,%52,%53,%54,%55}, %56, %57, p, 1, 1, 0, 1;}"
                 : R8(0), R8(8), R8(16), R8(24), R8(32), R8(40), R8(48)
                 : "l"(da), "l"(db), "r"(sc));
}
__device__ __forceinline__ void wgmma_n128_tn(float* d, desc_t da, desc_t db, int sc) {
    asm volatile("{.reg .pred p; setp.ne.b32 p, %66, 0;\n"
                 "wgmma.mma_async.sync.aligned.m64n128k16.f32.bf16.bf16 {%0,%1,%2,%3,%4,%5,%6,%7,%8,%9,%10,%11,%12,%13,%14,%15,%16,%17,%18,%19,%20,%21,%22,%23,%24,%25,%26,%27,%28,%29,%30,%31,%32,%33,%34,%35,%36,%37,%38,%39,%40,%41,%42,%43,%44,%45,%46,%47,%48,%49,%50,%51,%52,%53,%54,%55,%56,%57,%58,%59,%60,%61,%62,%63}, %64, %65, p, 1, 1, 1, 0;}"
                 : R8(0), R8(8), R8(16), R8(24), R8(32), R8(40), R8(48), R8(56)
                 : "l"(da), "l"(db), "r"(sc));
}
__device__ __forceinline__ void wgmma_n64(float* d, desc_t da, desc_t db, int sc) {
    asm volatile("{.reg .pred p; setp.ne.b32 p, %34, 0;\n"
                 "wgmma.mma_async.sync.aligned.m64n64k16.f32.bf16.bf16 {%0,%1,%2,%3,%4,%5,%6,%7,%8,%9,%10,%11,%12,%13,%14,%15,%16,%17,%18,%19,%20,%21,%22,%23,%24,%25,%26,%27,%28,%29,%30,%31}, %32, %33, p, 1, 1, 0, 1;}"
                 : R8(0), R8(8), R8(16), R8(24)
                 : "l"(da), "l"(db), "r"(sc));
}
__device__ __forceinline__ void wgmma_n40_tt(float* d, desc_t da, desc_t db, int sc) {
    asm volatile("{.reg .pred p; setp.ne.b32 p, %22, 0;\n"
                 "wgmma.mma_async.sync.aligned.m64n40k16.f32.bf16.bf16 {%0,%1,%2,%3,%4,%5,%6,%7,%8,%9,%10,%11,%12,%13,%14,%15,%16,%17,%18,%19}, %20, %21, p, 1, 1, 1, 1;}"
                 : R8(0), R8(8), R4(16)
                 : "l"(da), "l"(db), "r"(sc));
}

__device__ __forceinline__ void wgmma_n8_tt(float* d, desc_t da, desc_t db, int sc) {
    asm volatile("{.reg .pred p; setp.ne.b32 p, %6, 0;\n"
                 "wgmma.mma_async.sync.aligned.m64n8k16.f32.bf16.bf16 {%0,%1,%2,%3}, %4, %5, p, 1, 1, 1, 1;}"
                 : R4(0)
                 : "l"(da), "l"(db), "r"(sc));
}

__device__ __forceinline__ uint32_t atom_f32x2(float* p, float a, float b) {
    float x, y;
    asm volatile("atom.relaxed.gpu.global.add.v2.f32 {%0,%1}, [%2], {%3,%4};" : "=f"(x), "=f"(y) : "l"(p), "f"(a), "f"(b) : "memory");
    return __float_as_uint(x);
}
__device__ __forceinline__ uint32_t atom_f32_if(float* p, float a, bool pred) {
    float x = 0.f;
    asm volatile("{.reg .pred p; setp.ne.u32 p, %3, 0; @p atom.relaxed.gpu.global.add.f32 %0, [%1], %2;}" : "+f"(x) : "l"(p), "f"(a), "r"((uint32_t)pred) : "memory");
    return __float_as_uint(x);
}
__device__ __forceinline__ void signal_after(unsigned* cnt, uint32_t ack, uint32_t zero, bool pred) {
    asm volatile("{.reg .pred p; setp.ne.u32 p, %2, 0; @p red.relaxed.gpu.global.add.u32 [%0], %1;}"
                 ::"l"(cnt), "r"((ack & zero) + 1), "r"((uint32_t)pred) : "memory");
}
__device__ __forceinline__ void signal_late(unsigned* cnt, const uint32_t* a, uint32_t zero, bool pred) {
    uint32_t v;
    asm volatile("{.reg .b32 t; lop3.b32 t, %1, %2, %3, 0xfe; lop3.b32 %0, t, %4, %5, 0xfe;}"
                 : "=r"(v) : "r"(a[0]), "r"(a[1]), "r"(a[2]), "r"(a[3]), "r"(a[4]));
    signal_after(cnt, v, zero, pred);
}
__device__ __forceinline__ void red_f32_if(float* p, float a, bool pred) {
    asm volatile("{.reg .pred p; setp.ne.u32 p, %2, 0; @p red.relaxed.gpu.global.add.f32 [%0], %1;}" ::"l"(p), "f"(a), "r"((uint32_t)pred) : "memory");
}
__device__ __forceinline__ void stg_f2_if(float* p, float a, float b, bool pred) {
    asm volatile("{.reg .pred p; setp.ne.u32 p, %3, 0; @p st.global.v2.f32 [%0], {%1,%2};}" ::"l"(p), "f"(a), "f"(b), "r"((uint32_t)pred) : "memory");
}
__device__ __forceinline__ void stg64(void* p, uint32_t a, uint32_t b) {
    asm volatile("st.global.v2.u32 [%0], {%1,%2};" ::"l"(p), "r"(a), "r"(b) : "memory");
}
__device__ __forceinline__ void mma16816_z(float* c, const uint32_t* a, uint32_t b0, uint32_t b1) {
    asm("mma.sync.aligned.m16n8k16.row.col.f32.bf16.bf16.f32 {%0,%1,%2,%3}, {%4,%5,%6,%7}, {%8,%9}, {%10,%10,%10,%10};"
                 : "=f"(c[0]), "=f"(c[1]), "=f"(c[2]), "=f"(c[3])
                 : "r"(a[0]), "r"(a[1]), "r"(a[2]), "r"(a[3]), "r"(b0), "r"(b1), "f"(0.f));
}
__device__ __forceinline__ uint32_t max2(uint32_t a, uint32_t b) { uint32_t r; asm("max.bf16x2 %0, %1, %2;" : "=r"(r) : "r"(a), "r"(b)); return r; }
__device__ __forceinline__ uint32_t min2(uint32_t a, uint32_t b) { uint32_t r; asm("min.bf16x2 %0, %1, %2;" : "=r"(r) : "r"(a), "r"(b)); return r; }
__device__ __forceinline__ void bar_arrive(int id, int n) { asm volatile("bar.arrive %0, %1;" ::"r"(id), "r"(n) : "memory"); }
__device__ __forceinline__ void mbar_arrive_n_if(uint32_t bar, uint32_t n, bool pred) {
    asm volatile("{.reg .pred p; setp.ne.u32 p, %1, 0; @p mbarrier.arrive.shared::cta.b64 _, [%0], %2;}" ::"r"(bar), "r"((uint32_t)pred), "r"(n) : "memory");
}
__device__ __forceinline__ float4 lds_f4(uint32_t a) {
    float4 v;
    asm volatile("ld.shared.v4.f32 {%0,%1,%2,%3}, [%4];" : "=f"(v.x), "=f"(v.y), "=f"(v.z), "=f"(v.w) : "r"(a) : "memory");
    return v;
}
__device__ __forceinline__ uint4 ld_tagged(const unsigned long long* p) {
    unsigned long long a, b;
    asm volatile("ld.acquire.gpu.global.v2.b64 {%0,%1}, [%2];" : "=l"(a), "=l"(b) : "l"(p) : "memory");
    return make_uint4((unsigned)a, (unsigned)(a >> 32), (unsigned)b, (unsigned)(b >> 32));
}
__device__ __forceinline__ uint4 ld_tagged_rlx(const unsigned long long* p) {
    unsigned long long a, b;
    asm volatile("ld.relaxed.gpu.global.v2.b64 {%0,%1}, [%2];" : "=l"(a), "=l"(b) : "l"(p) : "memory");
    return make_uint4((unsigned)a, (unsigned)(a >> 32), (unsigned)b, (unsigned)(b >> 32));
}
__device__ __forceinline__ void st_tagged_if(unsigned long long* p, float a, float b, unsigned tag, bool pred) {
    const unsigned long long t = (unsigned long long)tag << 32;
    asm volatile("{.reg .pred p; setp.ne.u32 p, %3, 0; @p st.relaxed.gpu.global.v2.b64 [%0], {%1,%2};}"
                 ::"l"(p), "l"(t | __float_as_uint(a)), "l"(t | __float_as_uint(b)), "r"((uint32_t)pred) : "memory");
}

__device__ __forceinline__ void store_tile(uint32_t tile_rows, __nv_bfloat16* gdst, const uint32_t* lo, const uint32_t* hi, int lane, uint32_t* ack) {
    const int r = lane & 15;
#pragma unroll
    for (int b = 0; b < 4; b++)
        stsm4(tile_rows + r * 128 + (((2 * b + (lane >> 4)) ^ (r & 7)) << 4), lo[2 * b], hi[2 * b], lo[2 * b + 1], hi[2 * b + 1]);
    fence_async_smem();
    __syncwarp();
#pragma unroll
    for (int i = 0; i < 4; i++) {
        const int rr = 4 * i + (lane >> 3);
        const uint4 v = lds128(tile_rows + rr * 128 + (((lane & 7) ^ (rr & 7)) << 4));
        stg128(gdst + rr * DM + (lane & 7) * 8, v.x, v.y, v.z, v.w);
    }
#pragma unroll
    for (int i = 0; i < 4; i++) ack[i] = readback(gdst + (4 * i + (lane >> 3)) * DM + (lane & 7) * 8);
}

__device__ __forceinline__ void feature_maps(const uint32_t* a, const uint32_t* wb, float c0, float c1, uint32_t* plus, uint32_t* minus) {
    uint32_t P[16], mx[4], mn[4];
#pragma unroll
    for (int h = 0; h < 4; h++) {
        float p[8];
        mma16816_z(p, a + 4 * h, wb[4 * h], wb[4 * h + 1]);
        mma16816_z(p + 4, a + 4 * h, wb[4 * h + 2], wb[4 * h + 3]);
        P[4 * h] = pack_bf16(p[0], p[2]); P[4 * h + 1] = pack_bf16(p[1], p[3]);
        P[4 * h + 2] = pack_bf16(p[4], p[6]); P[4 * h + 3] = pack_bf16(p[5], p[7]);
        mx[h] = max2(max2(P[4 * h], P[4 * h + 1]), max2(P[4 * h + 2], P[4 * h + 3]));
        mn[h] = min2(min2(P[4 * h], P[4 * h + 1]), min2(P[4 * h + 2], P[4 * h + 3]));
    }
#pragma unroll
    for (int s = 1; s <= 2; s <<= 1) {
        uint32_t tx[4], tn[4];
#pragma unroll
        for (int h = 0; h < 4; h++) { tx[h] = __shfl_xor_sync(0xffffffffu, mx[h], s); tn[h] = __shfl_xor_sync(0xffffffffu, mn[h], s); }
#pragma unroll
        for (int h = 0; h < 4; h++) { mx[h] = max2(mx[h], tx[h]); mn[h] = min2(mn[h], tn[h]); }
    }
#pragma unroll
    for (int h = 0; h < 4; h++) {
        const float mx0 = bf_lo(mx[h]) * c0, mx1 = bf_hi(mx[h]) * c1, mn0 = bf_lo(mn[h]) * c0, mn1 = bf_hi(mn[h]) * c1;
        float ep[8], em[8];
#pragma unroll
        for (int i = 0; i < 8; i++) {
            const bool r1 = (i & 2);
            const uint32_t w = P[4 * h + (i >> 2) * 2 + (i & 1)];
            const float p = r1 ? bf_hi(w) : bf_lo(w);
            ep[i] = ex2(fmaf(p, r1 ? c1 : c0, r1 ? -mx1 : -mx0));
            em[i] = ex2(fmaf(p, r1 ? -c1 : -c0, r1 ? mn1 : mn0));
        }
        float sp[4], sm[4];
        uint32_t tp[4], tm[4];
#pragma unroll
        for (int i = 0; i < 4; i++) { tp[i] = pack_bf16(ep[2 * i], ep[2 * i + 1]); tm[i] = pack_bf16(em[2 * i], em[2 * i + 1]); }
        mma16816_z(sp, tp, 0x3f803f80u, 0x3f803f80u);
        mma16816_z(sm, tm, 0x3f803f80u, 0x3f803f80u);
        const float r0 = rcp(sp[0] * sm[0]), r1 = rcp(sp[2] * sm[2]);
        const float rs[4] = {r0 * sm[0], r1 * sm[2], r0 * sp[0], r1 * sp[2]};
#pragma unroll
        for (int i = 0; i < 4; i++) {
            plus[4 * h + i] = pack_bf16(ep[2 * i] * rs[i & 1], ep[2 * i + 1] * rs[i & 1]);
            minus[4 * h + i] = pack_bf16(em[2 * i] * rs[2 + (i & 1)], em[2 * i + 1] * rs[2 + (i & 1)]);
        }
    }
}

template <bool SCALE>
__device__ __forceinline__ void ln_frag(const float* acc, uint32_t cs_addr, float rs0, float nm0, float rs1, float nm1, uint32_t* a) {
    const float2 c0 = lds_f2(cs_addr), c1 = lds_f2(cs_addr + 32);
    const float s0 = SCALE ? rs0 : 1.f, s1 = SCALE ? rs1 : 1.f;
    a[0] = pack_bf16(fmaf(nm0, c0.x, acc[0]) * s0, fmaf(nm0, c0.y, acc[1]) * s0);
    a[1] = pack_bf16(fmaf(nm1, c0.x, acc[2]) * s1, fmaf(nm1, c0.y, acc[3]) * s1);
    a[2] = pack_bf16(fmaf(nm0, c1.x, acc[4]) * s0, fmaf(nm0, c1.y, acc[5]) * s0);
    a[3] = pack_bf16(fmaf(nm1, c1.x, acc[6]) * s1, fmaf(nm1, c1.y, acc[7]) * s1);
}

template <int UP>
__device__ __forceinline__ uint32_t hh_pair(const float* ag, float4 cs, float nmean) {
    const float g0 = fmaf(nmean, cs.x, ag[0]), g1 = fmaf(nmean, cs.y, ag[1]);
    const float u0 = fmaf(nmean, cs.z, ag[UP]), u1 = fmaf(nmean, cs.w, ag[UP + 1]);
    return pack_bf16(g0 * u0, g1 * u1);
}
template <int UP, int NTP>
__device__ __forceinline__ void hh_stage(const float* acc, uint32_t cs3, float nm0, float nm1, uint32_t stg, int lane) {
#pragma unroll
    for (int tp = 0; tp < NTP; tp++) {
        const float4 c0 = lds_f4(cs3 + tp * 128), c1 = lds_f4(cs3 + tp * 128 + 64);
        stsm4(stg + (lane & 15) * 128 + (((2 * tp + (lane >> 4)) ^ (lane & 7)) << 4), hh_pair<UP>(acc + 8 * tp, c0, nm0),
              hh_pair<UP>(acc + 8 * tp + 2, c0, nm1), hh_pair<UP>(acc + 8 * tp + 4, c1, nm0), hh_pair<UP>(acc + 8 * tp + 6, c1, nm1));
    }
    fence_async_smem();
    __syncwarp();
}

struct Ring {
    int slot; uint32_t phase;
    __device__ __forceinline__ void adv() { if (++slot == NB) { slot = 0; phase ^= 1; } }
};

__global__ void __launch_bounds__(NTHREADS, 1) fused_kernel(const __grid_constant__ Params P) {
    extern __shared__ __align__(1024) uint8_t smem_raw[];
    const uint32_t sb = smem_u32(smem_raw);
    const int tid = threadIdx.x, lane = tid & 31;
    const int warp = __shfl_sync(0xffffffffu, tid >> 5, 0);
    unsigned role = blockIdx.x;
    if (P.use_smid) asm volatile("mov.u32 %0, %%smid;" : "=r"(role));
    role = P.role[role];
    const int m = role >> 3, j = role & 7;
    const bool helper = role >= 128;

    TL(0, tid == 0); TLG(0, tid == 0);
    float* const acc_j = g_acc + j * ACC_SIZE;
    unsigned* const cnt_j = g_cnt + j * 32;

    if (__builtin_expect(warp >= 8, 1)) {
        asm volatile("setmaxnreg.dec.sync.aligned.u32 72;");
        if (elect_one()) {
            if (warp == 8) {
                if (!helper) {
#pragma unroll
                    for (int i = 0; i < NB; i++) mbar_init(sb + BAR_FULLB + 8 * i, 1);
#pragma unroll
                    for (int i = 0; i < 2; i++) {
                        mbar_expect_tx(sb + BAR_FULLB + 8 * i, SLOT);
                        tma3d(sb + OFF_B + i * SLOT, &P.twkv, sb + BAR_FULLB + 8 * i, 64 * j, 64 * i, 1);
                    }
                }
            } else if (warp == 9) {
#pragma unroll
                for (int i = 0; i < 8; i++) mbar_init(sb + BAR_FULLA + 8 * i, 1);
#pragma unroll
                for (int i = 0; i < 2; i++) {
                    mbar_expect_tx(sb + BAR_FULLA + 8 * i, SLOT);
                    tma2d(sb + OFF_A + i * SLOT, helper ? &P.twq : &P.tx, sb + BAR_FULLA + 8 * i, helper ? DM + 128 * j : 64 * i, 128 * (helper ? i : m));
                }
            } else if (warp == 10) {
#pragma unroll
                for (int i = 0; i < 9; i++) mbar_init(sb + BAR_CS1 + 8 * i, i == 0 || i == 8 ? 64 : (i == 1 ? 96 : (i < 4 ? 32 : 8)));
                trap_if_gt(sb & 1023, 0);
            } else {
#pragma unroll
                for (int i = 0; i < 14; i++) mbar_init(sb + (i < 8 ? BAR_EMPTYA : BAR_EMPTYB - 64) + 8 * i, 8);
            }
        }
        __syncwarp();
        const unsigned epoch = ld_relaxed(&g_epoch);
        bar_sync(0, NTHREADS);
        if (helper) {
            if (warp == 8) {
                if (elect_one()) {
#pragma unroll 1
                    for (int i = 2; i < 72; i++) {
                        const uint32_t full = sb + BAR_FULLA + 8 * (i & 7), dst = sb + OFF_A + (i & 7) * SLOT;
                        mbar_wait(sb + BAR_EMPTYA + 8 * (i & 7), ((i >> 3) & 1) ^ 1);
                        mbar_expect_tx(full, SLOT);
                        if (i < 24) {
                            tma2d(dst, &P.twq, full, (i < 16 ? DM + 64 * (i & 8) : 0) + 128 * j + 16 * (i & 4), 128 * (i & 3));
                        } else {
                            const int u = (i >> 3) - 3, c0 = 176 * (2 * j + (u & 1)) + 64 * (u >> 1);
                            tma2d(dst, &P.twg, full, c0, 64 * (i & 7));
                            tma2d(dst + 8192, &P.twu, full, c0, 64 * (i & 7));
                        }
                    }
                    prefetch_l2(P.wd + (size_t)j * 176128, 352256);
                }
            } else if (warp == 9) {
                wait_count_warp(g_cnt + (lane & 7) * 32, epoch * 32);
            }
            return;
        }
        if (warp == 8) {
            if (elect_one()) {
                if (m >= 3 && m < 8)
                    asm volatile("cp.async.bulk.prefetch.tensor.3d.L2.global [%0, {%1, %2, %3}];" ::"l"(&P.twkv), "r"(64 * j), "r"(64 * m), "r"(1) : "memory");
                if (j >= 3)
                    asm volatile("cp.async.bulk.prefetch.tensor.2d.L2.global [%0, {%1, %2}];" ::"l"(&P.tx), "r"(64 * j), "r"(128 * m) : "memory");
                Ring r{2, 0};
#pragma unroll 1
                for (int i = 2; i < 59; i++) {
                    const uint32_t full = sb + BAR_FULLB + 8 * r.slot, dst = sb + OFF_B + r.slot * SLOT;
                    mbar_wait(sb + BAR_EMPTYB + 8 * r.slot, r.phase ^ 1);
                    if ((i >= 10 && i < 14) || i == 28 || i == 37 || i == 46) {
                        mbar_arrive(full);
                    } else {
                        if (i >= AHEAD && i < 6) mbar_wait(full - 8 * AHEAD, 0);
                        mbar_expect_tx(full, SLOT);
                        if (i < 8) {
                            tma3d(dst, &P.twkv, full, 64 * j, 64 * i, 1);
                        } else if (i < 16) {
                            tma2d(dst, &P.twq, full, 64 * j, 128 * (i & 3));
                        } else {
                            const bool wo = i < 20, gu = !wo && i < 46;
                            const int e = 2 * ((wo ? i : i + 1) & 3), g8 = i - 20 - (i > 28) - (i > 37);
                            const int c0 = gu ? 176 * j + 8 * (g8 & ~7) : 64 * j;
                            const int r0 = wo ? 64 * KORD(e, j) : (gu ? 64 * (g8 < 8 ? KORD(g8, j) : g8 & 7) : 176 * e + 64 * ((i - 47) >> 2));
                            const int r1 = wo ? 64 * KORD(e + 1, j) : (gu ? r0 : r0 + 176);
                            tma2d(dst, wo ? &P.two : (gu ? &P.twg : &P.twd), full, c0, r0);
                            tma2d(dst + 8192, wo ? &P.two : (gu ? &P.twu : &P.twd), full, c0, r1);
                        }
                    }
                    r.adv();
                }
            }
            return;
        }
        if (warp == 9) {
            if (elect_one()) {
#pragma unroll 1
                for (int i = 2; i < 8; i++) {
                    if (i >= AHEAD + 1) mbar_wait(sb + BAR_FULLA + 8 * (i - AHEAD - 1), 0);
                    mbar_expect_tx(sb + BAR_FULLA + 8 * i, SLOT);
                    tma2d(sb + OFF_A + i * SLOT, &P.tx, sb + BAR_FULLA + 8 * i, 64 * i, 128 * m);
                }
#pragma unroll 1
                for (int i = 1; i < 10; i++) prefetch_tmap(&P.tx + i);
#pragma unroll 1
                for (int r = 1; r < 6; r++) {
                    const CUtensorMap* tm = &P.tx + min(r, 3);
                    const int cstep = r < 3 ? 64 : 192, cbase = r < 3 ? 0 : 64 * (r - 3), skip = r < 3 ? j : 8;
                    mbar_wait(sb + BAR_EMPTYA + 8 * (skip == 0), (r - 1) & 1);
                    wait_count(g_flag + (m * 5 + r - 1) * 32, epoch * (r < 3 ? 64 : 8));
                    TL(64 + r, true);
#pragma unroll 1
                    for (int t = 0; t < 8; t++) {
                        if (t == skip) continue;
                        mbar_wait(sb + BAR_EMPTYA + 8 * t, (r - 1) & 1);
                        mbar_expect_tx(sb + BAR_FULLA + 8 * t, SLOT);
                        tma2d(sb + OFF_A + t * SLOT, tm, sb + BAR_FULLA + 8 * t, cbase + cstep * t, 128 * m);
                    }
                }
            }
            return;
        }
        const int a = warp - 10;
        {
            const int row = 16 * j + 8 * a + (lane >> 2);
            const uint32_t ra = sb + OFF_A + row * 128;
            float sh = 0.f, s0 = 0.f, s1 = 0.f, q0 = 0.f, q1 = 0.f;
#pragma unroll 1
            for (int kt = 0; kt < 8; kt++) {
                mbar_wait(sb + BAR_FULLA + 8 * kt, 0);
                if (kt == 0) sh = bf_lo(lds128(ra + ((row & 7) << 4)).x);
#pragma unroll
                for (int i = 0; i < 2; i++) {
                    const uint4 v = lds128(ra + kt * SLOT + (((2 * (lane & 3) + i) ^ (row & 7)) << 4));
                    const uint32_t ww[4] = {v.x, v.y, v.z, v.w};
#pragma unroll
                    for (int e = 0; e < 4; e++) {
                        const float d0 = bf_lo(ww[e]) - sh, d1 = bf_hi(ww[e]) - sh;
                        s0 += d0; q0 = fmaf(d0, d0, q0);
                        s1 += d1; q1 = fmaf(d1, d1, q1);
                    }
                }
            }
            s0 += s1; q0 += q1;
#pragma unroll
            for (int o = 1; o <= 2; o <<= 1) { s0 += __shfl_xor_sync(0xffffffffu, s0, o); q0 += __shfl_xor_sync(0xffffffffu, q0, o); }
            const float md = s0 * (1.f / DM);
            const float rs = rsqrtf(fmaxf(q0 * (1.f / DM) - md * md, 0.f) + 1e-5f);
            st_tagged_if(g_xstat + 2 * (128 * m + row), rs, -(sh + md), epoch, (lane & 3) == 0);
        }
        const unsigned long long* cs = g_cs + j * 768 + 2 * lane;
#pragma unroll 1
        for (int c = 0; c < (a ? 5 : 10); c++) {
            if (c == 4) {
                const int t = 32 * a + lane;
                const uint32_t kvs = sb + OFF_A + KVS(j) * SLOT;
                mbar_wait(sb + BAR_KVW, 0);
#pragma unroll 1
                for (int pass = 0; pass < 2; pass++) {
                    float4 v[8];
#pragma unroll
                    for (int i = 0; i < 8; i++) v[i] = ld_l2_f4(acc_j + ACC_KV + 4 * (t + 64 * i));
                    const float2 zz = ld_l2_f2(acc_j + ACC_Z + 2 * t);
#pragma unroll
                    for (int i = 0; i < 8; i++)
                        sts64(kvs + ((t >> 2) + 16 * i) * 48 + (t & 3) * 8, pack_bf16(v[i].x, v[i].y), pack_bf16(v[i].z, v[i].w));
                    const uint32_t z0 = pack_bf16(zz.x, zz.x), z1 = pack_bf16(zz.y, zz.y);
                    sts128(kvs + t * 96 + 32, z0, z0, z0, z0);
                    sts128(kvs + t * 96 + 80, z1, z1, z1, z1);
                    if (pass == 0) {
                        __syncwarp();
                        if (lane == 0) red_relaxed(cnt_j, 1);
                        TL(19, t == 0);
                        wait_count_warp(cnt_j, epoch * 32);
                        TL(14, t == 0);
                    }
                }
                mbar_arrive(sb + BAR_KVR);
                if (a) break;
            }
            if (c == 3 && !a) continue;
            const unsigned long long* src = c < 2 ? g_xstat + 2 * (128 * m + 64 * a + 32 * c + lane) : cs + (c < 4 ? 128 * (a + c - 2) : 128 + 64 * c);
            const uint32_t dst = c < 2 ? OFF_XST + (64 * a + 32 * c + lane) * 8
                                       : (c < 4 ? OFF_CS1 + (c == 2 ? 256 * (a + 1) : 0) + 8 * lane : OFF_CS3 + (32 * ((c - 4) >> 1) + lane) * 16 + 8 * (c & 1));
            uint4 v;
            uint32_t it = 0;
            while (true) {
                v = ld_tagged_rlx(src);
                if (!__any_sync(0xffffffffu, v.y != epoch || v.w != epoch)) break;
                __nanosleep(60);
                trap_if_gt(++it, 1u << 22);
            }
            sts64(sb + dst, v.x, v.z);
            if (c == 2 - a || (a && c > 1) || c == 9) mbar_arrive(sb + (c == 9 ? BAR_CS3 : (c == 2 - a ? BAR_CS1 : (c == 2 ? BAR_CSV : BAR_CSQ))));
        }
        {
            uint32_t it = 0;
            while (__any_sync(0xffffffffu, (int)(readback(g_flag + (m * 5 + 1) * 32) - epoch * 64) < 0)) {
                __nanosleep(200);
                trap_if_gt(++it, 1u << 22);
            }
            const int row = 2 * (32 * a + lane);
            const float* sp = g_hstat + (1024 * m + row) * 2;
            float4 v[8];
#pragma unroll
            for (int i = 0; i < 8; i++) v[i] = ld_l2_f4(sp + 256 * i);
            float ma = 0.f, mb = 0.f;
#pragma unroll
            for (int i = 0; i < 8; i++) { ma += v[i].x; mb += v[i].z; }
            ma *= 0.125f; mb *= 0.125f;
            float sa = 0.f, sb2 = 0.f, da = 0.f, db = 0.f;
#pragma unroll
            for (int i = 0; i < 8; i++) {
                sa += v[i].y; da = fmaf(v[i].x - ma, v[i].x - ma, da);
                sb2 += v[i].w; db = fmaf(v[i].z - mb, v[i].z - mb, db);
            }
            sts128(sb + OFF_CS1 + row * 8, __float_as_uint(-ma), __float_as_uint(rcp(fmaf(da, 64.f, sa) * (1.f / DM) + 1e-5f)),
                   __float_as_uint(-mb), __float_as_uint(rcp(fmaf(db, 64.f, sb2) * (1.f / DM) + 1e-5f)));
        }
        mbar_arrive(sb + BAR_CS3);
#pragma unroll 1
        for (int c = a; c < 3; c += 2) {
            const int slot = c == 1 ? 1 : 4;
            mbar_wait(sb + BAR_STG + 8 * c, 0);
            if (elect_one()) {
                tma_store2d(&P.thh, sb + OFF_B + slot * SLOT, 192 * j + 64 * c, 128 * m);
                asm volatile("cp.async.bulk.wait_group.read 0;" ::: "memory");
                mbar_arrive_n_if(sb + BAR_EMPTYB + 8 * slot, 8, true);
                asm volatile("cp.async.bulk.wait_group 0;" ::: "memory");
            }
            __syncwarp();
            TL(60 + c, lane == 0);
            uint32_t ack = 0;
#pragma unroll
            for (int i = 0; i < 4; i++) ack |= readback(g_hh + (size_t)(128 * m + 32 * i + lane) * FFP + 192 * j + 64 * c);
            signal_after(g_flag + (m * 5 + 2 + c) * 32, ack, P.zero, lane == 0);
            TL(54 + c, lane == 0);
        }
        return;
    }
    const unsigned epoch = ld_relaxed(&g_epoch);
    uint32_t wraw[16];
    if (!helper) {
        const uint32_t* wp = reinterpret_cast<const uint32_t*>(P.wphi) + (4 * j) * 128 + (lane & 3) * 16 + (lane >> 2);
#pragma unroll
        for (int i = 0; i < 16; i++)
            asm volatile("ld.global.nc.u32 %0, [%1];" : "=r"(wraw[i]) : "l"(wp + (i >> 2) * 128 + ((i >> 1) & 1) * 64 + (i & 1) * 8));
    }
    asm volatile("setmaxnreg.inc.sync.aligned.u32 216;");
    bar_sync(0, NTHREADS);
    if (helper) {
        if (warp < 4) {
            sts128(sb + OFF_B + 16 * tid, 0x3f803f80u, 0x3f803f80u, 0x3f803f80u, 0x3f803f80u);
            for (int i = tid; i < 2 * ACC_SIZE / 4; i += 128) stg128(g_acc + 2 * j * ACC_SIZE + 4 * i, 0, 0, 0, 0);
            fence_async_smem();
            fence_gpu();
            bar_sync(1, 128);
            float acc[8];
            int i = 0;
#pragma unroll 1
            for (int job = 0; job < 12; job++) {
                const int n = job < 6 ? 4 : 8;
#pragma unroll 1
                for (int t = 0; t < n; t++, i++) {
                    mbar_wait(sb + BAR_FULLA + 8 * (i & 7), (i >> 3) & 1);
                    wg_fence();
#pragma unroll
                    for (int k = 0; k < 8; k++)
                        wgmma_n8_tt(acc + (k & 4), desc_lo(sb + OFF_A) + (i & 7) * (SLOT >> 4) + 128 * k, desc_lo(sb + OFF_B), (t | (k & 3)) != 0);
                    wg_commit();
                    wg_wait<1>();
                    mbar_arrive_n_if(sb + BAR_EMPTYA + 8 * ((i + 7) & 7), 2, lane == 0 && i > 0);
                }
                wg_wait<0>();
                fence_acc<8>(acc);
                const int q = lane & 3;
                const float lo = (q & 1) ? acc[2] : acc[0], hi = (q & 1) ? acc[6] : acc[4];
                const float v = job < 6 ? lo + hi : ((q & 2) ? hi : lo);
                unsigned long long* dst = g_cs + ((2 * j + (job & 1)) * 6 + (job >> 1)) * 128 + (q >> 1) * 64 + 16 * warp + 8 * (q & 1) + (lane >> 2);
                asm volatile("st.relaxed.gpu.global.b64 [%0], %1;" ::"l"(dst), "l"(((unsigned long long)epoch << 32) | __float_as_uint(v)) : "memory");
            }
        }
        return;
    }
    {
        const int w = warp >> 2, wv = warp & 3, g = lane >> 2, q = lane & 3;
        const int row_w = 128 * m + 16 * warp;
        const uint32_t sa = sb + OFF_A + w * 8192;
        const desc_t dA = desc_lo(sa), dB = desc_lo(sb + OFF_B);
        unsigned* const flag_m = g_flag + m * 160;
        const bool l0 = lane == 0;
        Ring rg{0, 0};
        int prev = 0;

        uint32_t wb[16];
        constexpr float L2E = 1.4426950408889634f;
        const int ch = lane >> 4, sw = lane & 7;
        const uint32_t lrow = (lane & 15) * 128;
        uint32_t fp[16], fm[16];
        {
            float acc[64], accq[32];
#pragma unroll 1
            for (int kt = 0; kt < 8; kt++) {
                mbar_waitc(sb + BAR_FULLA + 8 * kt, 0);
                mbar_waitc(sb + BAR_FULLB + 8 * rg.slot, rg.phase);
                const desc_t da = dA + kt * (SLOT >> 4), db = dB + rg.slot * (SLOT >> 4);
                wg_fence();
#pragma unroll
                for (int k = 0; k < 4; k++) wgmma_n128(acc, da + 2 * k, db + 128 * k, (kt | k) != 0);
                wg_commit();
                wg_wait<1>();
                mbar_arrive_if(sb + BAR_EMPTYB + 8 * prev, l0 && kt > 0);
                prev = rg.slot; rg.adv();
            }
#pragma unroll
            for (int i = 0; i < 8; i++) {
                wb[(i >> 1) * 4 + (i & 1)] = __byte_perm(wraw[2 * i], wraw[2 * i + 1], 0x5410);
                wb[(i >> 1) * 4 + 2 + (i & 1)] = __byte_perm(wraw[2 * i], wraw[2 * i + 1], 0x7632);
            }
            float2 s0, s1;
            uint32_t a[16];
            wg_wait<0>();
            fence_acc<64>(acc);
            mbar_arrive_if(sb + BAR_EMPTYB + 8 * prev, l0);
#pragma unroll 1
            for (int it = 0; it < 2; it++) {
                mbar_waitc(sb + BAR_FULLB + 8 * 2, it ^ 1); mbar_waitc(sb + BAR_FULLB + 8 * 3, it ^ 1);
                const desc_t da = dA + it * (4 * SLOT >> 4);
                wg_fence();
#pragma unroll
                for (int k = 0; k < 16; k++) wgmma_n64(accq, da + (k >> 2) * (SLOT >> 4) + (k & 3) * 2, dB + 2 * (SLOT >> 4) + 128 * k, (it | k) != 0);
                wg_commit();
                TL(17 + it, tid == 0);
                mbar_waitc(sb + BAR_CS1 + 16 * it, 0);
                wg_wait<0>();
                fence_acc<32>(accq);
                mbar_arrive_if(sb + BAR_EMPTYB + 8 * (2 + lane), lane < 2);
                TL(2 + 2 * it, tid == 0);
                if (it == 0) {
                    s0 = lds_f2(sb + OFF_XST + (16 * warp + g) * 8); s1 = lds_f2(sb + OFF_XST + (16 * warp + g + 8) * 8);
#pragma unroll
                    for (int hh = 0; hh < 4; hh++)
                        ln_frag<false>(acc + 8 * hh, sb + OFF_CS1 + (64 + 16 * hh + 2 * q) * 4, 0.f, s0.y, 0.f, s1.y, a + 4 * hh);
                } else {
#pragma unroll
                    for (int hh = 0; hh < 4; hh++)
                        ln_frag<false>(accq + 8 * hh, sb + OFF_CS1 + (16 * hh + 2 * q) * 4, 0.f, s0.y, 0.f, s1.y, a + 4 * hh);
                }
                feature_maps(a, wb, s0.x * L2E, s1.x * L2E, fp, fm);
                if (it == 0) {
                    mbar_waitc(sb + BAR_FULLB + 8 * 4, 1); mbar_waitc(sb + BAR_FULLB + 8 * 5, 1);
                    mbar_waitc(sb + BAR_FULLB + 8 * 0, 0); mbar_waitc(sb + BAR_FULLB + 8 * 1, 0);
                    mbar_waitc(sb + BAR_CSV, 0);
                    const uint32_t st = sb + OFF_B + warp * 2048 + lrow;
#pragma unroll
                    for (int hh = 0; hh < 4; hh++) {
                        stsm4(st + (4 + (hh >> 1)) * SLOT + (((4 * (hh & 1) + ch) ^ sw) << 4), fp[4 * hh], fp[4 * hh + 1], fp[4 * hh + 2], fp[4 * hh + 3]);
                        stsm4(st + (4 + (hh >> 1)) * SLOT + (((4 * (hh & 1) + 2 + ch) ^ sw) << 4), fm[4 * hh], fm[4 * hh + 1], fm[4 * hh + 2], fm[4 * hh + 3]);
                        ln_frag<true>(acc + 32 + 8 * hh, sb + OFF_CS1 + (128 + 16 * hh + 2 * q) * 4, s0.x, s0.y, s1.x, s1.y, a);
                        stsm4(st + (hh >> 1) * SLOT + (((2 * (hh & 1) + ch) ^ sw) << 4), a[0], a[1], a[2], a[3]);
                    }
                    stsm4(st + ch * SLOT + ((4 ^ sw) << 4), 0x3f803f80u, 0x3f803f80u, 0x3f803f80u, 0x3f803f80u);
                    fence_async_smem();
                    bar_sync(1, 256);
                    float kvd[20];
                    wg_fence();
#pragma unroll
                    for (int k = 0; k < 8; k++)
                        wgmma_n40_tt(kvd, dB + (4 + w) * (SLOT >> 4) + 128 * k, dB + w * (SLOT >> 4) + 128 * k, k != 0);
                    wg_commit();
                    wg_wait<0>();
                    fence_acc<20>(kvd);
                    const bool h1 = wv >= 2;
                    const int f = 16 * warp + g;
                    float* kvp = acc_j + ACC_KV + f * 16 + 2 * q;
                    red_f32x2(kvp, h1 ? kvd[8] : kvd[0], h1 ? kvd[9] : kvd[1]);
                    red_f32x2(kvp + 128, h1 ? kvd[10] : kvd[2], h1 ? kvd[11] : kvd[3]);
                    red_f32x2(kvp + 8, h1 ? kvd[12] : kvd[4], h1 ? kvd[13] : kvd[5]);
                    red_f32x2(kvp + 136, h1 ? kvd[14] : kvd[6], h1 ? kvd[15] : kvd[7]);
                    red_f32_if(acc_j + ACC_Z + f + 8 * (q & 1), q ? kvd[18] : kvd[16], q < 2);
                    __syncwarp();
                    mbar_arrive_if(sb + (lane == 4 ? BAR_KVW : BAR_EMPTYB + 8 * ((4 + lane) % 6)), lane < 5);
                    TL(3, tid == 0);
                }
            }
        }
        uint32_t res_lo[8], res_hi[8], ack[5];
        const uint32_t own_rows = sb + OFF_A + j * SLOT + warp * 2048;
#pragma unroll
        for (int b = 0; b < 4; b++)
            ldsm4(own_rows + lrow + (((2 * b + ch) ^ sw) << 4), res_lo[2 * b], res_hi[2 * b], res_lo[2 * b + 1], res_hi[2 * b + 1]);
        mbar_arrive_if(sb + BAR_EMPTYA + 8 * lane, lane < 8 && lane != j && lane != KVS(j));
        TL(5, tid == 0);
        mbar_waitc(sb + BAR_KVR, 0);
        TL(6, tid == 0);
        {
            const uint32_t kvs = sb + OFF_A + KVS(j) * SLOT;
            uint32_t o_lo[8], o_hi[8];
#pragma unroll
            for (int hh = 0; hh < 4; hh++) {
                uint32_t b[8], zb[4];
                const uint32_t base = kvs + hh * 32 * 48;
                ldsm4t(base + (lane & 15) * 48 + (lane >> 4) * 16, b[0], b[1], b[2], b[3]);
                ldsm4t(base + (16 + (lane & 15)) * 48 + (lane >> 4) * 16, b[4], b[5], b[6], b[7]);
                ldsm4t(base + lane * 48 + 32, zb[0], zb[1], zb[2], zb[3]);
                float n0[4], n1[4], dn[4];
                mma16816_z(n0, fp + 4 * hh, b[0], b[1]); mma16816_z(n1, fp + 4 * hh, b[2], b[3]); mma16816_z(dn, fp + 4 * hh, zb[0], zb[1]);
                mma16816(n0, fm + 4 * hh, b[4], b[5]); mma16816(n1, fm + 4 * hh, b[6], b[7]); mma16816(dn, fm + 4 * hh, zb[2], zb[3]);
                const float i0 = rcp(dn[0] + 1e-6f), i1 = rcp(dn[2] + 1e-6f);
                o_lo[2 * hh] = pack_bf16(n0[0] * i0, n0[1] * i0); o_hi[2 * hh] = pack_bf16(n0[2] * i1, n0[3] * i1);
                o_lo[2 * hh + 1] = pack_bf16(n1[0] * i0, n1[1] * i0); o_hi[2 * hh + 1] = pack_bf16(n1[2] * i1, n1[3] * i1);
            }
            __syncwarp();
            mbar_arrive_if(sb + BAR_EMPTYA + 8 * KVS(j), l0);
            rg.slot = 4; rg.phase = 0;
            store_tile(own_rows, g_o + (size_t)row_w * DM + 64 * j, o_lo, o_hi, lane, ack);
            ack[4] = 0;
            TL(7, tid == 0);
        }
        {
            float acc[32];
#pragma unroll
            for (int t = 0; t < 8; t++) {
                acc[4 * t] = bf_lo(res_lo[t]); acc[4 * t + 1] = bf_hi(res_lo[t]);
                acc[4 * t + 2] = bf_lo(res_hi[t]); acc[4 * t + 3] = bf_hi(res_hi[t]);
            }
            fence_acc<32>(acc);
            int pa = 0;
#pragma unroll 1
            for (int kp = 0; kp < 4; kp++) {
                mbar_waitc(sb + BAR_FULLB + 8 * rg.slot, rg.phase);
#pragma unroll
                for (int hf = 0; hf < 2; hf++) {
                    const int i = 2 * kp + hf, kt = KORD(i, j);
                    mbar_waitc(sb + BAR_FULLA + 8 * kt, i != 0);
                    TL(8, i == 1 && tid == 0);
                    const desc_t da = dA + kt * (SLOT >> 4), db = dB + rg.slot * (SLOT >> 4);
                    wg_fence();
#pragma unroll
                    for (int k = 0; k < 4; k++) wgmma_n64(acc, da + 2 * k, db + (hf * 4 + k) * 128, 1);
                    wg_commit();
                    wg_wait<1>();
                    mbar_arrive_if(sb + BAR_EMPTYA + 8 * pa, l0 && i > 1);
                    if (hf == 0) {
                        mbar_arrive_if(sb + BAR_EMPTYB + 8 * prev, l0 && i > 0);
                        if (i == 0) { signal_late(flag_m, ack, P.zero, l0); TL(20, tid == 0); }
                    }
                    pa = kt;
                }
                prev = rg.slot; rg.adv();
            }
            wg_wait<0>();
            fence_acc<32>(acc);
            mbar_arrive_if(sb + BAR_EMPTYA + 8 * pa, l0);
            mbar_arrive_if(sb + BAR_EMPTYB + 8 * prev, l0);
            TL(9, tid == 0);
            float s0 = 0.f, s1 = 0.f;
#pragma unroll
            for (int t = 0; t < 8; t++) {
                res_lo[t] = pack_bf16(acc[4 * t], acc[4 * t + 1]);
                res_hi[t] = pack_bf16(acc[4 * t + 2], acc[4 * t + 3]);
                s0 += acc[4 * t] + acc[4 * t + 1];
                s1 += acc[4 * t + 2] + acc[4 * t + 3];
            }
            store_tile(own_rows, g_h + (size_t)row_w * DM + 64 * j, res_lo, res_hi, lane, ack);
            s0 += __shfl_xor_sync(0xffffffffu, s0, 1); s1 += __shfl_xor_sync(0xffffffffu, s1, 1);
            s0 += __shfl_xor_sync(0xffffffffu, s0, 2); s1 += __shfl_xor_sync(0xffffffffu, s1, 2);
            const float mu0 = s0 * (1.f / 64), mu1 = s1 * (1.f / 64);
            float q0 = 0.f, q1 = 0.f;
#pragma unroll
            for (int t = 0; t < 8; t++) {
                float d;
                d = acc[4 * t] - mu0; q0 = fmaf(d, d, q0);
                d = acc[4 * t + 1] - mu0; q0 = fmaf(d, d, q0);
                d = acc[4 * t + 2] - mu1; q1 = fmaf(d, d, q1);
                d = acc[4 * t + 3] - mu1; q1 = fmaf(d, d, q1);
            }
            q0 += __shfl_xor_sync(0xffffffffu, q0, 1); q1 += __shfl_xor_sync(0xffffffffu, q1, 1);
            q0 += __shfl_xor_sync(0xffffffffu, q0, 2); q1 += __shfl_xor_sync(0xffffffffu, q1, 2);
            stg_f2_if(g_hstat + (role * 128 + 16 * warp + g + 8 * (q & 1)) * 2, q ? mu1 : mu0, q ? q1 : q0, q < 2);
            ack[4] = readback(g_hstat + (role * 128 + 16 * warp + g + 8 * (q & 1)) * 2);
            TL(10, tid == 0);
        }
        {
            float acc[64];
#pragma unroll 1
            for (int c = 0; c < 3; c++) {
#define KT_P3(MMA)                                                                                          \
    _Pragma("unroll 1") for (int i = 0; i < 8; i++) {                                                       \
        const int kt = c ? i : KORD(i, j);                                                                  \
        mbar_waitc(sb + BAR_FULLA + 8 * kt, 0);                                                             \
        mbar_waitc(sb + BAR_FULLB + 8 * rg.slot, rg.phase);                                                 \
        TL(44, tid == 0 && i == 1 && c == 0);                                                               \
        const desc_t da = dA + kt * (SLOT >> 4), db = dB + rg.slot * (SLOT >> 4);                           \
        wg_fence();                                                                                         \
        _Pragma("unroll") for (int k = 0; k < 4; k++) MMA(acc, da + 2 * k, db + 128 * k, (i | k) != 0);     \
        wg_commit();                                                                                        \
        wg_wait<1>();                                                                                       \
        mbar_arrive_if(sb + BAR_EMPTYB + 8 * prev, l0 && i > 0);                                            \
        mbar_arrive_if(sb + BAR_EMPTYA + 8 * ((i + 7) & 7), l0 && i > 0 && c == 2);                         \
        if ((i | c) == 0) { signal_late(flag_m + 32, ack, P.zero, l0); TL(21, tid == 0); }                  \
        prev = rg.slot; rg.adv();                                                                           \
    }
                if (c < 2) { KT_P3(wgmma_n128) } else { KT_P3(wgmma_n112) }
                mbar_waitc(sb + BAR_CS3, 0);
                const float nm0 = lds_f2(sb + OFF_CS1 + (16 * warp + g) * 8).x, nm1 = lds_f2(sb + OFF_CS1 + (16 * warp + g + 8) * 8).x;
                wg_wait<0>();
                fence_acc<64>(acc);
                mbar_arrive_if(sb + BAR_EMPTYA + 8 * 7, l0 && c == 2);
                mbar_arrive_if(sb + BAR_EMPTYB + 8 * prev, l0);
                TL(11 + c, tid == 0);
                mbar_waitc(sb + BAR_FULLB + 8 * rg.slot, rg.phase);
                hh_stage<32, 4>(acc, sb + OFF_CS3 + q * 16 + 512 * c, nm0, nm1, sb + OFF_B + rg.slot * SLOT + warp * 2048, lane);
                rg.adv();
                mbar_arrive_if(sb + BAR_STG + 8 * c, l0);
                TL(50 + c, tid == 0);
            }
        }
        {
            float acc[64];
            const desc_t dA0 = desc_lo(sb + OFF_A);
#define KT_P4(I, NK)                                                                                        \
    do {                                                                                                    \
        const int s_ = (2 * (I) + w) & 7;                                                                   \
        mbar_waitc(sb + BAR_FULLB + 8 * rg.slot, rg.phase);                                                 \
        mbar_waitc(sb + BAR_FULLA + 8 * s_, (((I) >> 2) + 1) & 1);                                          \
        TL(30 + (I), tid == 0);                                                                             \
        const desc_t dh_ = dA0 + s_ * (SLOT >> 4), dw_ = dB + rg.slot * (SLOT >> 4) + w * 512;              \
        wg_fence();                                                                                         \
        _Pragma("unroll") for (int k = 0; k < (NK); k++) wgmma_n128_tn(acc, dw_ + 128 * k, dh_ + 2 * k, ((I) | k) != 0); \
        wg_commit();                                                                                        \
        wg_wait<1>();                                                                                       \
        mbar_arrive_n_if(sb + BAR_EMPTYA + 8 * ((s_ + 6) & 7), 2, l0 && (I) > 0);                           \
        mbar_arrive_if(sb + BAR_EMPTYB + 8 * prev, l0 && (I) > 0);                                          \
        prev = rg.slot; rg.adv();                                                                           \
    } while (0)
#pragma unroll 1
            for (int i = 0; i < 8; i++) KT_P4(i, 4);
#pragma unroll 1
            for (int i = 8; i < 12; i++) KT_P4(i, 3);
            const uint32_t tile = sb + OFF_A + w * SLOT;
#pragma unroll
            for (int b = 0; b < 4; b++)
                stsm4(tile + (16 * wv + (lane & 15)) * 128 + (((2 * b + (lane >> 4)) ^ (lane & 7)) << 4),
                      res_lo[2 * b], res_hi[2 * b], res_lo[2 * b + 1], res_hi[2 * b + 1]);
            wg_wait<0>();
            fence_acc<64>(acc);
            TL(15, tid == 0);
            const uint32_t xch = sb + OFF_A + 2 * SLOT + (tid & 127) * 16;
            if (w) {
#pragma unroll
                for (int t = 0; t < 8; t++) {
                    sts128(xch + SLOT + t * 2048, __float_as_uint(acc[4 * t]), __float_as_uint(acc[4 * t + 1]),
                           __float_as_uint(acc[4 * t + 2]), __float_as_uint(acc[4 * t + 3]));
                }
#pragma unroll
                for (int t = 0; t < 32; t++) acc[t] = acc[32 + t];
            } else {
#pragma unroll
                for (int t = 0; t < 8; t++)
                    sts128(xch + t * 2048, __float_as_uint(acc[32 + 4 * t]), __float_as_uint(acc[33 + 4 * t]),
                           __float_as_uint(acc[34 + 4 * t]), __float_as_uint(acc[35 + 4 * t]));
            }
            bar_sync(1, 256);
            const uint32_t blk = tile + ((lane & 7) + (lane >> 4) * 8) * 128 + (((2 * wv + ((lane >> 3) & 1)) ^ (lane & 7)) << 4);
#pragma unroll
            for (int tp = 0; tp < 4; tp++) {
                uint32_t hr[4];
                ldsm4t(blk + tp * 2048, hr[0], hr[1], hr[2], hr[3]);
#pragma unroll
                for (int u = 0; u < 2; u++) {
                    const int t = 2 * tp + u;
                    const float4 o = lds_f4(xch + (w ^ 1) * SLOT + t * 2048);
                    const float4 st = lds_f4(sb + OFF_CS1 + (64 * w + 8 * t + 2 * q) * 8);
                    hr[2 * u] = pack_bf16(fmaf(acc[4 * t] + o.x, st.y, bf_lo(hr[2 * u])), fmaf(acc[4 * t + 1] + o.y, st.w, bf_hi(hr[2 * u])));
                    hr[2 * u + 1] = pack_bf16(fmaf(acc[4 * t + 2] + o.z, st.y, bf_lo(hr[2 * u + 1])), fmaf(acc[4 * t + 3] + o.w, st.w, bf_hi(hr[2 * u + 1])));
                }
                stsm4t(blk + tp * 2048, hr[0], hr[1], hr[2], hr[3]);
            }
            bar_sync(2 + w, 128);
#pragma unroll
            for (int i = 0; i < 4; i++) {
                const int rr = 16 * wv + 4 * i + (lane >> 3);
                const uint4 v = lds128(tile + rr * 128 + (((lane & 7) ^ (rr & 7)) << 4));
                stg128(P.out + (size_t)(128 * m + 64 * w + rr) * DM + 64 * j + (lane & 7) * 8, v.x, v.y, v.z, v.w);
            }
            if (tid == 0 && role == 0) g_epoch = epoch + 1;
            TL(16, tid == 0); TLG(1, tid == 0);
        }
    }
}

typedef CUresult (*EncodeFn)(CUtensorMap*, CUtensorMapDataType, cuuint32_t, void*, const cuuint64_t*, const cuuint64_t*,
                             const cuuint32_t*, const cuuint32_t*, CUtensorMapInterleave, CUtensorMapSwizzle,
                             CUtensorMapL2promotion, CUtensorMapFloatOOBfill);

static void make_map2d(EncodeFn enc, CUtensorMap* tm, const void* base, uint64_t cols, uint64_t rows, uint64_t pitch_elems,
                       uint32_t box_rows) {
    cuuint64_t gd[2] = {cols, rows};
    cuuint64_t gs[1] = {pitch_elems * 2};
    cuuint32_t bd[2] = {64, box_rows};
    cuuint32_t es[2] = {1, 1};
    enc(tm, CU_TENSOR_MAP_DATA_TYPE_BFLOAT16, 2, const_cast<void*>(base), gd, gs, bd, es, CU_TENSOR_MAP_INTERLEAVE_NONE,
        CU_TENSOR_MAP_SWIZZLE_128B, CU_TENSOR_MAP_L2_PROMOTION_L2_256B, CU_TENSOR_MAP_FLOAT_OOB_FILL_NONE);
}

}

extern "C" void kernel_launch(void* const* d_in, const int* in_sizes, int n_in, void* d_out, int out_size) {
    using namespace hk;
    (void)in_sizes; (void)n_in; (void)out_size;
    static EncodeFn enc = nullptr;
    static void *po = nullptr, *ph = nullptr, *phh = nullptr;
    static int std_layout = 0;
    if (!enc) {
        void* fn = nullptr;
        cudaDriverEntryPointQueryResult qr;
        cudaGetDriverEntryPoint("cuTensorMapEncodeTiled", &fn, cudaEnableDefault, &qr);
        enc = (EncodeFn)fn;
        cudaGetSymbolAddress(&po, g_o);
        cudaGetSymbolAddress(&ph, g_h);
        cudaGetSymbolAddress(&phh, g_hh);
        cudaFuncSetAttribute(fused_kernel, cudaFuncAttributeMaxDynamicSharedMemorySize, SMEM_BYTES);
        int dev = 0, sms = 0;
        cudaGetDevice(&dev);
        cudaDeviceGetAttribute(&sms, cudaDevAttrMultiProcessorCount, dev);
        cudaFuncSetAttribute(fused_kernel, cudaFuncAttributeNonPortableClusterSizeAllowed, 1);
        const int sizes[3] = {8, 9, 16}, want[3] = {15, 9, 7};
        bool ok = sms == NCTA;
        for (int i = 0; i < 3 && ok; i++) {
            cudaLaunchConfig_t cfg = {};
            cfg.gridDim = dim3(sizes[i] * 8); cfg.blockDim = dim3(NTHREADS); cfg.dynamicSmemBytes = SMEM_BYTES;
            cudaLaunchAttribute at;
            at.id = cudaLaunchAttributeClusterDimension;
            at.val.clusterDim.x = sizes[i]; at.val.clusterDim.y = 1; at.val.clusterDim.z = 1;
            cfg.attrs = &at; cfg.numAttrs = 1;
            int n = 0;
            ok = cudaOccupancyMaxActiveClusters(&n, fused_kernel, &cfg) == cudaSuccess && n == want[i];
        }
        (void)cudaGetLastError();
        std_layout = ok ? 1 : 0;
    }
    Params P;
    const __nv_bfloat16* x = (const __nv_bfloat16*)d_in[0];
    P.x = x;
    P.wqkv = (const __nv_bfloat16*)d_in[1];
    P.wphi = (const __nv_bfloat16*)d_in[2];
    P.wo = (const __nv_bfloat16*)d_in[3];
    P.wg = (const __nv_bfloat16*)d_in[5];
    P.wu = (const __nv_bfloat16*)d_in[6];
    P.wd = (const __nv_bfloat16*)d_in[7];
    P.out = (__nv_bfloat16*)d_out;
    P.use_smid = std_layout;
    P.zero = 0;
    for (int i = 0; i < NCTA; i++) {
        int role = i < 4 ? 128 + i : i - 4;
        if (std_layout) {
            const int tpc = i >> 1, odd = i & 1;
            if (tpc < 32) role = (tpc & 7) * 8 + (tpc >> 3) * 2 + odd;
            else if (tpc < 60) role = (8 + (tpc - 32) % 7) * 8 + ((tpc - 32) / 7) * 2 + odd;
            else if (tpc < 62) role = 128 + (tpc - 60) * 2 + odd;
            else role = 15 * 8 + (tpc - 62) * 2 + odd;
        }
        P.role[i] = (unsigned char)role;
    }
    make_map2d(enc, &P.tx, x, DM, SEQ, DM, 128);
    make_map2d(enc, &P.to, po, DM, SEQ, DM, 128);
    make_map2d(enc, &P.th, ph, DM, SEQ, DM, 128);
    make_map2d(enc, &P.thh, phh, FFP, SEQ, FFP, 128);
    make_map2d(enc, &P.twq, P.wqkv, 3 * DM, DM, 3 * DM, 128);
    make_map2d(enc, &P.two, P.wo, DM, DM, DM, 64);
    make_map2d(enc, &P.twg, P.wg, FF, DM, FF, 64);
    make_map2d(enc, &P.twu, P.wu, FF, DM, FF, 64);
    make_map2d(enc, &P.twd, P.wd, DM, FF, DM, 64);
    {
        cuuint64_t gd[3] = {(cuuint64_t)DM, (cuuint64_t)DM, 3};
        cuuint64_t gs[2] = {(cuuint64_t)3 * DM * 2, (cuuint64_t)DM * 2};
        cuuint32_t bd[3] = {64, 64, 2};
        cuuint32_t es[3] = {1, 1, 1};
        enc(&P.twkv, CU_TENSOR_MAP_DATA_TYPE_BFLOAT16, 3, const_cast<__nv_bfloat16*>(P.wqkv), gd, gs, bd, es,
            CU_TENSOR_MAP_INTERLEAVE_NONE, CU_TENSOR_MAP_SWIZZLE_128B, CU_TENSOR_MAP_L2_PROMOTION_L2_256B,
            CU_TENSOR_MAP_FLOAT_OOB_FILL_NONE);
    }
    fused_kernel<<<NCTA, NTHREADS, SMEM_BYTES>>>(P);
}
```

```cpp
#include <cuda_runtime.h>
#include <cuda_bf16.h>
#include <cuda.h>
#include <stdint.h>

namespace hk {

constexpr int SEQ = 2048, DM = 512, FF = 1376, FFP = 1536;
constexpr int NCTA = 132;
constexpr int NTHREADS = 384;
constexpr uint32_t SLOT = 16384;
constexpr uint32_t OFF_A = 0, OFF_B = 8 * SLOT, OFF_MISC = 14 * SLOT;
constexpr uint32_t BAR_FULLA = OFF_MISC + 0, BAR_EMPTYA = OFF_MISC + 64, BAR_FULLB = OFF_MISC + 128,
                   BAR_EMPTYB = OFF_MISC + 176, BAR_CS1 = OFF_MISC + 224, BAR_CS3 = OFF_MISC + 232,
                   BAR_CSQ = OFF_MISC + 240, BAR_CSV = OFF_MISC + 248,
                   BAR_STG = OFF_MISC + 256,
                   BAR_KVW = OFF_MISC + 280, BAR_KVR = OFF_MISC + 288;
constexpr uint32_t OFF_CS1 = OFF_MISC + 384;
constexpr uint32_t OFF_CS3 = OFF_CS1 + 1024;
constexpr uint32_t OFF_XST = OFF_CS3;
constexpr uint32_t SMEM_BYTES = OFF_CS3 + 1536;
#define KVS(j) ((j) == 3 ? 2 : 3)
#define KORD(i, j) ((i) == 0 ? (j) : (i) - ((i) <= (j)))
constexpr int NB = 6;
#define STAGGER 0
constexpr int AHEAD = 3;

constexpr int ACC_KV = 0, ACC_Z = 2048, ACC_SIZE = 2176;

__device__ __align__(1024) __nv_bfloat16 g_o[SEQ * DM];
__device__ __align__(1024) __nv_bfloat16 g_h[SEQ * DM];
__device__ __align__(1024) __nv_bfloat16 g_hh[SEQ * FFP];
__device__ __align__(128) float g_hstat[SEQ * 16];
__device__ __align__(128) unsigned long long g_xstat[SEQ * 2];
__device__ __align__(128) float g_acc[8 * ACC_SIZE];
__device__ __align__(128) unsigned g_cnt[8 * 32];
__device__ __align__(128) unsigned long long g_cs[8 * 6 * 128];
__device__ __align__(128) unsigned g_flag[16 * 5 * 32];
__device__ unsigned g_epoch = 1;

#define TL(i, pred) do {} while (0)
#define TLG(i, pred) do {} while (0)

struct Params {
    CUtensorMap tx, to, th, thh, twq, two, twg, twu, twd;
    const __nv_bfloat16 *x, *wqkv, *wphi, *wo, *wg, *wu, *wd;
    __nv_bfloat16* out;
    unsigned zero;
    unsigned char role[NCTA];
};

__device__ __forceinline__ uint32_t smem_u32(const void* p) { return (uint32_t)__cvta_generic_to_shared(p); }
__device__ __forceinline__ void mbar_init(uint32_t bar, uint32_t cnt) {
    asm volatile("mbarrier.init.shared::cta.b64 [%0], %1;" ::"r"(bar), "r"(cnt) : "memory");
}
__device__ __forceinline__ void mbar_expect_tx(uint32_t bar, uint32_t bytes) {
    asm volatile("mbarrier.arrive.expect_tx.shared::cta.b64 _, [%0], %1;" ::"r"(bar), "r"(bytes) : "memory");
}
__device__ __forceinline__ void mbar_arrive(uint32_t bar) {
    asm volatile("mbarrier.arrive.shared::cta.b64 _, [%0];" ::"r"(bar) : "memory");
}
__device__ __forceinline__ void mbar_arrive_if(uint32_t bar, bool pred) {
    asm volatile("{.reg .pred p; setp.ne.u32 p, %1, 0; @p mbarrier.arrive.shared::cta.b64 _, [%0];}" ::"r"(bar), "r"((uint32_t)pred) : "memory");
}
__device__ __forceinline__ bool mbar_try(uint32_t bar, uint32_t parity) {
    uint32_t ok;
    asm volatile("{.reg .pred p; mbarrier.try_wait.parity.shared::cta.b64 p, [%1], %2; selp.u32 %0,1,0,p;}"
                 : "=r"(ok) : "r"(bar), "r"(parity) : "memory");
    return ok;
}
__device__ __forceinline__ bool mbar_test(uint32_t bar, uint32_t parity) {
    uint32_t ok;
    asm volatile("{.reg .pred p; mbarrier.test_wait.parity.shared::cta.b64 p, [%1], %2; selp.u32 %0,1,0,p;}"
                 : "=r"(ok) : "r"(bar), "r"(parity) : "memory");
    return ok;
}
__device__ __forceinline__ void trap_if_gt(uint32_t v, uint32_t lim) {
    asm volatile("{.reg .pred p; setp.gt.u32 p, %0, %1; @p trap;}" ::"r"(v), "r"(lim));
}
__device__ __forceinline__ void mbar_wait(uint32_t bar, uint32_t parity) {
    asm volatile("{\n"
                 ".reg .pred P1, P2;\n"
                 ".reg .u32 c;\n"
                 "mov.u32 c, 0;\n"
                 "LAB_WAIT:\n"
                 "mbarrier.try_wait.parity.shared::cta.b64 P1, [%0], %1;\n"
                 "@P1 bra LAB_DONE;\n"
                 "add.u32 c, c, 1;\n"
                 "setp.gt.u32 P2, c, 4194304;\n"
                 "@P2 trap;\n"
                 "bra LAB_WAIT;\n"
                 "LAB_DONE:\n"
                 "}" ::"r"(bar), "r"(parity) : "memory");
}
__device__ __forceinline__ void mbar_waitc(uint32_t bar, uint32_t parity) {
    asm volatile("{\n"
                 ".reg .pred P1;\n"
                 "LAB_WAIT:\n"
                 "mbarrier.try_wait.parity.shared::cta.b64 P1, [%0], %1;\n"
                 "@!P1 bra LAB_WAIT;\n"
                 "}" ::"r"(bar), "r"(parity) : "memory");
}
__device__ __forceinline__ void tma2d(uint32_t dst, const CUtensorMap* tm, uint32_t bar, int c0, int c1) {
    asm volatile("cp.async.bulk.tensor.2d.shared::cluster.global.mbarrier::complete_tx::bytes [%0], [%1, {%3, %4}], [%2];"
                 ::"r"(dst), "l"(tm), "r"(bar), "r"(c0), "r"(c1) : "memory");
}
__device__ __forceinline__ void tma2d_mc(uint32_t dst, const CUtensorMap* tm, uint32_t bar, int c0, int c1) {
    asm volatile("cp.async.bulk.tensor.2d.shared::cluster.global.mbarrier::complete_tx::bytes.multicast::cluster [%0], [%1, {%3, %4}], [%2], %5;"
                 ::"r"(dst), "l"(tm), "r"(bar), "r"(c0), "r"(c1), "h"((uint16_t)3) : "memory");
}
__device__ __forceinline__ uint32_t mapa(uint32_t addr, uint32_t rank) {
    uint32_t r; asm("mapa.shared::cluster.u32 %0, %1, %2;" : "=r"(r) : "r"(addr), "r"(rank)); return r;
}
__device__ __forceinline__ void mbar_arrive_cl_if(uint32_t cbar, bool pred) {
    asm volatile("{.reg .pred p; setp.ne.u32 p, %1, 0; @p mbarrier.arrive.shared::cluster.b64 _, [%0];}" ::"r"(cbar), "r"((uint32_t)pred) : "memory");
}
__device__ __forceinline__ bool elect_one() {
    uint32_t ok;
    asm volatile("{.reg .pred p; elect.sync _|p, 0xffffffff; selp.u32 %0, 1, 0, p;}" : "=r"(ok));
    return ok;
}
__device__ __forceinline__ void prefetch_tmap(const CUtensorMap* tm) {
    asm volatile("prefetch.tensormap [%0];" ::"l"(tm) : "memory");
}
__device__ __forceinline__ void prefetch_l2(const void* p, uint32_t bytes) {
    asm volatile("cp.async.bulk.prefetch.L2.global [%0], %1;" ::"l"(p), "r"(bytes) : "memory");
}
__device__ __forceinline__ unsigned ld_acquire(const unsigned* p) {
    unsigned v; asm volatile("ld.acquire.gpu.global.u32 %0, [%1];" : "=r"(v) : "l"(p) : "memory"); return v;
}
__device__ __forceinline__ uint4 ld_acquire4(const unsigned* p) {
    uint4 v;
    asm volatile("ld.acquire.gpu.global.v4.u32 {%0,%1,%2,%3}, [%4];" : "=r"(v.x), "=r"(v.y), "=r"(v.z), "=r"(v.w) : "l"(p) : "memory");
    return v;
}
__device__ __forceinline__ unsigned ld_relaxed(const unsigned* p) {
    unsigned v; asm volatile("ld.relaxed.gpu.global.u32 %0, [%1];" : "=r"(v) : "l"(p)); return v;
}
__device__ __forceinline__ void st_relaxed(unsigned* p, unsigned v) {
    asm volatile("st.relaxed.gpu.global.u32 [%0], %1;" ::"l"(p), "r"(v) : "memory");
}
__device__ __forceinline__ void red_relaxed(unsigned* p, unsigned v) {
    asm volatile("red.relaxed.gpu.global.add.u32 [%0], %1;" ::"l"(p), "r"(v) : "memory");
}
__device__ __forceinline__ void fence_gpu() { asm volatile("fence.acq_rel.gpu;" ::: "memory"); }
__device__ __forceinline__ void fence_async_smem() { asm volatile("fence.proxy.async.shared::cta;" ::: "memory"); }
__device__ __forceinline__ void fence_async_global() { asm volatile("fence.proxy.async.global;" ::: "memory"); }
__device__ __forceinline__ uint32_t readback(const void* p) {
    uint32_t v; asm volatile("ld.relaxed.gpu.global.u32 %0, [%1];" : "=r"(v) : "l"(p) : "memory"); return v;
}
__device__ __forceinline__ void wait_count(const unsigned* p, unsigned target) {
    uint32_t it = 0;
    while ((int)(readback(p) - target) < 0) trap_if_gt(++it, 1u << 22);
}
__device__ __forceinline__ void wait_count_warp(const unsigned* p, unsigned target) {
    uint32_t it = 0;
    while (__any_sync(0xffffffffu, (int)(readback(p) - target) < 0)) trap_if_gt(++it, 1u << 22);
}
__device__ __forceinline__ void red_f32(float* p, float a) {
    asm volatile("red.relaxed.gpu.global.add.f32 [%0], %1;" ::"l"(p), "f"(a) : "memory");
}
__device__ __forceinline__ void red_f32x2(float* p, float a, float b) {
    asm volatile("red.relaxed.gpu.global.add.v2.f32 [%0], {%1, %2};" ::"l"(p), "f"(a), "f"(b) : "memory");
}
__device__ __forceinline__ void red_f32x4(float* p, float a, float b, float c, float d) {
    asm volatile("red.relaxed.gpu.global.add.v4.f32 [%0], {%1, %2, %3, %4};" ::"l"(p), "f"(a), "f"(b), "f"(c), "f"(d) : "memory");
}
__device__ __forceinline__ float4 ld_l2_f4(const float* p) {
    float4 v;
    asm volatile("ld.relaxed.gpu.global.v4.f32 {%0,%1,%2,%3}, [%4];" : "=f"(v.x), "=f"(v.y), "=f"(v.z), "=f"(v.w) : "l"(p) : "memory");
    return v;
}
__device__ __forceinline__ float2 ld_l2_f2(const float* p) {
    float2 v;
    asm volatile("ld.relaxed.gpu.global.v2.f32 {%0,%1}, [%2];" : "=f"(v.x), "=f"(v.y) : "l"(p) : "memory");
    return v;
}
__device__ __forceinline__ float ld_l2_f(const float* p) {
    float v;
    asm volatile("ld.relaxed.gpu.global.f32 %0, [%1];" : "=f"(v) : "l"(p) : "memory");
    return v;
}
__device__ __forceinline__ uint4 ldg_nc(const void* p) {
    uint4 v;
    asm volatile("ld.global.nc.L1::no_allocate.v4.u32 {%0,%1,%2,%3}, [%4];" : "=r"(v.x), "=r"(v.y), "=r"(v.z), "=r"(v.w) : "l"(p));
    return v;
}
__device__ __forceinline__ void stg128(void* p, uint32_t a, uint32_t b, uint32_t c, uint32_t d) {
    asm volatile("st.global.v4.u32 [%0], {%1,%2,%3,%4};" ::"l"(p), "r"(a), "r"(b), "r"(c), "r"(d) : "memory");
}
__device__ __forceinline__ uint4 lds128(uint32_t a) {
    uint4 v;
    asm volatile("ld.shared.v4.u32 {%0,%1,%2,%3}, [%4];" : "=r"(v.x), "=r"(v.y), "=r"(v.z), "=r"(v.w) : "r"(a) : "memory");
    return v;
}
__device__ __forceinline__ float2 lds_f2(uint32_t a) {
    float2 v;
    asm volatile("ld.shared.v2.f32 {%0,%1}, [%2];" : "=f"(v.x), "=f"(v.y) : "r"(a) : "memory");
    return v;
}
__device__ __forceinline__ void sts_f2(uint32_t a, float x, float y) {
    asm volatile("st.shared.v2.f32 [%0], {%1,%2};" ::"r"(a), "f"(x), "f"(y) : "memory");
}
__device__ __forceinline__ void sts64(uint32_t a, uint32_t x, uint32_t y) {
    asm volatile("st.shared.v2.u32 [%0], {%1,%2};" ::"r"(a), "r"(x), "r"(y) : "memory");
}
__device__ __forceinline__ void sts128(uint32_t a, uint32_t x, uint32_t y, uint32_t z, uint32_t w) {
    asm volatile("st.shared.v4.u32 [%0], {%1,%2,%3,%4};" ::"r"(a), "r"(x), "r"(y), "r"(z), "r"(w) : "memory");
}
__device__ __forceinline__ void stsm4(uint32_t a, uint32_t r0, uint32_t r1, uint32_t r2, uint32_t r3) {
    asm volatile("stmatrix.sync.aligned.m8n8.x4.shared.b16 [%0], {%1,%2,%3,%4};" ::"r"(a), "r"(r0), "r"(r1), "r"(r2), "r"(r3) : "memory");
}
__device__ __forceinline__ void stsm4t(uint32_t a, uint32_t r0, uint32_t r1, uint32_t r2, uint32_t r3) {
    asm volatile("stmatrix.sync.aligned.m8n8.x4.trans.shared.b16 [%0], {%1,%2,%3,%4};" ::"r"(a), "r"(r0), "r"(r1), "r"(r2), "r"(r3) : "memory");
}
__device__ __forceinline__ void tma_store2d(const CUtensorMap* tm, uint32_t src, int c0, int c1) {
    asm volatile("cp.async.bulk.tensor.2d.global.shared::cta.bulk_group [%0, {%2, %3}], [%1];" ::"l"(tm), "r"(src), "r"(c0), "r"(c1) : "memory");
    asm volatile("cp.async.bulk.commit_group;" ::: "memory");
}
__device__ __forceinline__ void ldsm4(uint32_t a, uint32_t& r0, uint32_t& r1, uint32_t& r2, uint32_t& r3) {
    asm volatile("ldmatrix.sync.aligned.m8n8.x4.shared.b16 {%0,%1,%2,%3}, [%4];" : "=r"(r0), "=r"(r1), "=r"(r2), "=r"(r3) : "r"(a) : "memory");
}
__device__ __forceinline__ void ldsm4t(uint32_t a, uint32_t& r0, uint32_t& r1, uint32_t& r2, uint32_t& r3) {
    asm volatile("ldmatrix.sync.aligned.m8n8.x4.trans.shared.b16 {%0,%1,%2,%3}, [%4];" : "=r"(r0), "=r"(r1), "=r"(r2), "=r"(r3) : "r"(a) : "memory");
}
__device__ __forceinline__ void mma16816(float* c, const uint32_t* a, uint32_t b0, uint32_t b1) {
    asm("mma.sync.aligned.m16n8k16.row.col.f32.bf16.bf16.f32 {%0,%1,%2,%3}, {%4,%5,%6,%7}, {%8,%9}, {%0,%1,%2,%3};"
                 : "+f"(c[0]), "+f"(c[1]), "+f"(c[2]), "+f"(c[3])
                 : "r"(a[0]), "r"(a[1]), "r"(a[2]), "r"(a[3]), "r"(b0), "r"(b1));
}
__device__ __forceinline__ uint32_t pack_bf16(float lo, float hi) {
    uint32_t r; asm("cvt.rn.bf16x2.f32 %0, %1, %2;" : "=r"(r) : "f"(hi), "f"(lo)); return r;
}
__device__ __forceinline__ float bf_lo(uint32_t w) { return __uint_as_float(w << 16); }
__device__ __forceinline__ float bf_hi(uint32_t w) { return __uint_as_float(w & 0xffff0000u); }
__device__ __forceinline__ float ex2(float x) { float r; asm("ex2.approx.ftz.f32 %0, %1;" : "=f"(r) : "f"(x)); return r; }
__device__ __forceinline__ float rcp(float x) { float r; asm("rcp.approx.ftz.f32 %0, %1;" : "=f"(r) : "f"(x)); return r; }
__device__ __forceinline__ void bar_sync(int id, int n) { asm volatile("bar.sync %0, %1;" ::"r"(id), "r"(n) : "memory"); }

typedef unsigned long long desc_t;
__device__ __forceinline__ desc_t desc_lo(uint32_t addr) { return (desc_t)(((addr & 0x3FFFF) >> 4) | (512u << 16)) | (0x40000040ull << 32); }
__device__ __forceinline__ void wg_fence() { asm volatile("wgmma.fence.sync.aligned;" ::: "memory"); }
__device__ __forceinline__ void wg_commit() { asm volatile("wgmma.commit_group.sync.aligned;" ::: "memory"); }
template <int N> __device__ __forceinline__ void wg_wait() { asm volatile("wgmma.wait_group.sync.aligned %0;" ::"n"(N) : "memory"); }
template <int N> __device__ __forceinline__ void fence_acc(float* d) {
#pragma unroll
    for (int i = 0; i < N; i++) asm volatile("" : "+f"(d[i])::"memory");
}
#define R4(o) "+f"(d[o + 0]), "+f"(d[o + 1]), "+f"(d[o + 2]), "+f"(d[o + 3])
#define R8(o) R4(o), R4(o + 4)
__device__ __forceinline__ void wgmma_n128(float* d, desc_t da, desc_t db, int sc) {
    asm volatile("{.reg .pred p; setp.ne.b32 p, %66, 0;\n"
                 "wgmma.mma_async.sync.aligned.m64n128k16.f32.bf16.bf16 {%0,%1,%2,%3,%4,%5,%6,%7,%8,%9,%10,%11,%12,%13,%14,%15,%16,%17,%18,%19,%20,%21,%22,%23,%24,%25,%26,%27,%28,%29,%30,%31,"
                 "%32,%33,%34,%35,%36,%37,%38,%39,%40,%41,%42,%43,%44,%45,%46,%47,%48,%49,%50,%51,%52,%53,%54,%55,%56,%57,%58,%59,%60,%61,%62,%63}, %64, %65, p, 1, 1, 0, 1;}"
                 : R8(0), R8(8), R8(16), R8(24), R8(32), R8(40), R8(48), R8(56)
                 : "l"(da), "l"(db), "r"(sc));
}
__device__ __forceinline__ void wgmma_n112(float* d, desc_t da, desc_t db, int sc) {
    asm volatile("{.reg .pred p; setp.ne.b32 p, %58, 0;\n"
                 "wgmma.mma_async.sync.aligned.m64n112k16.f32.bf16.bf16 {%0,%1,%2,%3,%4,%5,%6,%7,%8,%9,%10,%11,%12,%13,%14,%15,%16,%17,%18,%19,%20,%21,%22,%23,%24,%25,%26,%27,%28,%29,%30,%31,%32,%33,%34,%35,%36,%37,%38,%39,%40,%41,%42,%43,%44,%45,%46,%47,%48,%49,%50,%51,%52,%53,%54,%55}, %56, %57, p, 1, 1, 0, 1;}"
                 : R8(0), R8(8), R8(16), R8(24), R8(32), R8(40), R8(48)
                 : "l"(da), "l"(db), "r"(sc));
}
__device__ __forceinline__ void wgmma_n128_tn(float* d, desc_t da, desc_t db, int sc) {
    asm volatile("{.reg .pred p; setp.ne.b32 p, %66, 0;\n"
                 "wgmma.mma_async.sync.aligned.m64n128k16.f32.bf16.bf16 {%0,%1,%2,%3,%4,%5,%6,%7,%8,%9,%10,%11,%12,%13,%14,%15,%16,%17,%18,%19,%20,%21,%22,%23,%24,%25,%26,%27,%28,%29,%30,%31,%32,%33,%34,%35,%36,%37,%38,%39,%40,%41,%42,%43,%44,%45,%46,%47,%48,%49,%50,%51,%52,%53,%54,%55,%56,%57,%58,%59,%60,%61,%62,%63}, %64, %65, p, 1, 1, 1, 0;}"
                 : R8(0), R8(8), R8(16), R8(24), R8(32), R8(40), R8(48), R8(56)
                 : "l"(da), "l"(db), "r"(sc));
}
__device__ __forceinline__ void wgmma_n64(float* d, desc_t da, desc_t db, int sc) {
    asm volatile("{.reg .pred p; setp.ne.b32 p, %34, 0;\n"
                 "wgmma.mma_async.sync.aligned.m64n64k16.f32.bf16.bf16 {%0,%1,%2,%3,%4,%5,%6,%7,%8,%9,%10,%11,%12,%13,%14,%15,%16,%17,%18,%19,%20,%21,%22,%23,%24,%25,%26,%27,%28,%29,%30,%31}, %32, %33, p, 1, 1, 0, 1;}"
                 : R8(0), R8(8), R8(16), R8(24)
                 : "l"(da), "l"(db), "r"(sc));
}
__device__ __forceinline__ void wgmma_n40_tt(float* d, desc_t da, desc_t db, int sc) {
    asm volatile("{.reg .pred p; setp.ne.b32 p, %22, 0;\n"
                 "wgmma.mma_async.sync.aligned.m64n40k16.f32.bf16.bf16 {%0,%1,%2,%3,%4,%5,%6,%7,%8,%9,%10,%11,%12,%13,%14,%15,%16,%17,%18,%19}, %20, %21, p, 1, 1, 1, 1;}"
                 : R8(0), R8(8), R4(16)
                 : "l"(da), "l"(db), "r"(sc));
}

__device__ __forceinline__ void wgmma_n8_tt(float* d, desc_t da, desc_t db, int sc) {
    asm volatile("{.reg .pred p; setp.ne.b32 p, %6, 0;\n"
                 "wgmma.mma_async.sync.aligned.m64n8k16.f32.bf16.bf16 {%0,%1,%2,%3}, %4, %5, p, 1, 1, 1, 1;}"
                 : R4(0)
                 : "l"(da), "l"(db), "r"(sc));
}

__device__ __forceinline__ uint32_t atom_f32x2(float* p, float a, float b) {
    float x, y;
    asm volatile("atom.relaxed.gpu.global.add.v2.f32 {%0,%1}, [%2], {%3,%4};" : "=f"(x), "=f"(y) : "l"(p), "f"(a), "f"(b) : "memory");
    return __float_as_uint(x);
}
__device__ __forceinline__ uint32_t atom_f32_if(float* p, float a, bool pred) {
    float x = 0.f;
    asm volatile("{.reg .pred p; setp.ne.u32 p, %3, 0; @p atom.relaxed.gpu.global.add.f32 %0, [%1], %2;}" : "+f"(x) : "l"(p), "f"(a), "r"((uint32_t)pred) : "memory");
    return __float_as_uint(x);
}
__device__ __forceinline__ void signal_after(unsigned* cnt, uint32_t ack, uint32_t zero, bool pred) {
    asm volatile("{.reg .pred p; setp.ne.u32 p, %2, 0; @p red.relaxed.gpu.global.add.u32 [%0], %1;}"
                 ::"l"(cnt), "r"((ack & zero) + 1), "r"((uint32_t)pred) : "memory");
}
__device__ __forceinline__ void signal_late(unsigned* cnt, const uint32_t* a, uint32_t zero, bool pred) {
    uint32_t v;
    asm volatile("{.reg .b32 t; lop3.b32 t, %1, %2, %3, 0xfe; lop3.b32 %0, t, %4, %5, 0xfe;}"
                 : "=r"(v) : "r"(a[0]), "r"(a[1]), "r"(a[2]), "r"(a[3]), "r"(a[4]));
    signal_after(cnt, v, zero, pred);
}
__device__ __forceinline__ void red_f32_if(float* p, float a, bool pred) {
    asm volatile("{.reg .pred p; setp.ne.u32 p, %2, 0; @p red.relaxed.gpu.global.add.f32 [%0], %1;}" ::"l"(p), "f"(a), "r"((uint32_t)pred) : "memory");
}
__device__ __forceinline__ void stg_f2_if(float* p, float a, float b, bool pred) {
    asm volatile("{.reg .pred p; setp.ne.u32 p, %3, 0; @p st.global.v2.f32 [%0], {%1,%2};}" ::"l"(p), "f"(a), "f"(b), "r"((uint32_t)pred) : "memory");
}
__device__ __forceinline__ void stg64(void* p, uint32_t a, uint32_t b) {
    asm volatile("st.global.v2.u32 [%0], {%1,%2};" ::"l"(p), "r"(a), "r"(b) : "memory");
}
__device__ __forceinline__ void mma16816_z(float* c, const uint32_t* a, uint32_t b0, uint32_t b1) {
    asm("mma.sync.aligned.m16n8k16.row.col.f32.bf16.bf16.f32 {%0,%1,%2,%3}, {%4,%5,%6,%7}, {%8,%9}, {%10,%10,%10,%10};"
                 : "=f"(c[0]), "=f"(c[1]), "=f"(c[2]), "=f"(c[3])
                 : "r"(a[0]), "r"(a[1]), "r"(a[2]), "r"(a[3]), "r"(b0), "r"(b1), "f"(0.f));
}
__device__ __forceinline__ uint32_t max2(uint32_t a, uint32_t b) { uint32_t r; asm("max.bf16x2 %0, %1, %2;" : "=r"(r) : "r"(a), "r"(b)); return r; }
__device__ __forceinline__ uint32_t min2(uint32_t a, uint32_t b) { uint32_t r; asm("min.bf16x2 %0, %1, %2;" : "=r"(r) : "r"(a), "r"(b)); return r; }
__device__ __forceinline__ void bar_arrive(int id, int n) { asm volatile("bar.arrive %0, %1;" ::"r"(id), "r"(n) : "memory"); }
__device__ __forceinline__ void mbar_arrive_n_if(uint32_t bar, uint32_t n, bool pred) {
    asm volatile("{.reg .pred p; setp.ne.u32 p, %1, 0; @p mbarrier.arrive.shared::cta.b64 _, [%0], %2;}" ::"r"(bar), "r"((uint32_t)pred), "r"(n) : "memory");
}
__device__ __forceinline__ float4 lds_f4(uint32_t a) {
    float4 v;
    asm volatile("ld.shared.v4.f32 {%0,%1,%2,%3}, [%4];" : "=f"(v.x), "=f"(v.y), "=f"(v.z), "=f"(v.w) : "r"(a) : "memory");
    return v;
}
__device__ __forceinline__ uint4 ld_tagged(const unsigned long long* p) {
    unsigned long long a, b;
    asm volatile("ld.acquire.gpu.global.v2.b64 {%0,%1}, [%2];" : "=l"(a), "=l"(b) : "l"(p) : "memory");
    return make_uint4((unsigned)a, (unsigned)(a >> 32), (unsigned)b, (unsigned)(b >> 32));
}
__device__ __forceinline__ uint4 ld_tagged_rlx(const unsigned long long* p) {
    unsigned long long a, b;
    asm volatile("ld.relaxed.gpu.global.v2.b64 {%0,%1}, [%2];" : "=l"(a), "=l"(b) : "l"(p) : "memory");
    return make_uint4((unsigned)a, (unsigned)(a >> 32), (unsigned)b, (unsigned)(b >> 32));
}
__device__ __forceinline__ void st_tagged_if(unsigned long long* p, float a, float b, unsigned tag, bool pred) {
    const unsigned long long t = (unsigned long long)tag << 32;
    asm volatile("{.reg .pred p; setp.ne.u32 p, %3, 0; @p st.relaxed.gpu.global.v2.b64 [%0], {%1,%2};}"
                 ::"l"(p), "l"(t | __float_as_uint(a)), "l"(t | __float_as_uint(b)), "r"((uint32_t)pred) : "memory");
}

__device__ __forceinline__ void store_tile(uint32_t tile_rows, __nv_bfloat16* gdst, const uint32_t* lo, const uint32_t* hi, int lane, uint32_t* ack) {
    const int r = lane & 15;
#pragma unroll
    for (int b = 0; b < 4; b++)
        stsm4(tile_rows + r * 128 + (((2 * b + (lane >> 4)) ^ (r & 7)) << 4), lo[2 * b], hi[2 * b], lo[2 * b + 1], hi[2 * b + 1]);
    fence_async_smem();
    __syncwarp();
#pragma unroll
    for (int i = 0; i < 4; i++) {
        const int rr = 4 * i + (lane >> 3);
        const uint4 v = lds128(tile_rows + rr * 128 + (((lane & 7) ^ (rr & 7)) << 4));
        stg128(gdst + rr * DM + (lane & 7) * 8, v.x, v.y, v.z, v.w);
    }
#pragma unroll
    for (int i = 0; i < 4; i++) ack[i] = readback(gdst + (4 * i + (lane >> 3)) * DM + (lane & 7) * 8);
}

__device__ __forceinline__ void feature_maps(const uint32_t* a, const uint32_t* wb, float c0, float c1, uint32_t* plus, uint32_t* minus) {
    uint32_t P[16], mx[4], mn[4];
#pragma unroll
    for (int h = 0; h < 4; h++) {
        float p[8];
        mma16816_z(p, a + 4 * h, wb[4 * h], wb[4 * h + 1]);
        mma16816_z(p + 4, a + 4 * h, wb[4 * h + 2], wb[4 * h + 3]);
        P[4 * h] = pack_bf16(p[0], p[2]); P[4 * h + 1] = pack_bf16(p[1], p[3]);
        P[4 * h + 2] = pack_bf16(p[4], p[6]); P[4 * h + 3] = pack_bf16(p[5], p[7]);
        mx[h] = max2(max2(P[4 * h], P[4 * h + 1]), max2(P[4 * h + 2], P[4 * h + 3]));
        mn[h] = min2(min2(P[4 * h], P[4 * h + 1]), min2(P[4 * h + 2], P[4 * h + 3]));
    }
#pragma unroll
    for (int s = 1; s <= 2; s <<= 1) {
        uint32_t tx[4], tn[4];
#pragma unroll
        for (int h = 0; h < 4; h++) { tx[h] = __shfl_xor_sync(0xffffffffu, mx[h], s); tn[h] = __shfl_xor_sync(0xffffffffu, mn[h], s); }
#pragma unroll
        for (int h = 0; h < 4; h++) { mx[h] = max2(mx[h], tx[h]); mn[h] = min2(mn[h], tn[h]); }
    }
#pragma unroll
    for (int h = 0; h < 4; h++) {
        const float mx0 = bf_lo(mx[h]) * c0, mx1 = bf_hi(mx[h]) * c1, mn0 = bf_lo(mn[h]) * c0, mn1 = bf_hi(mn[h]) * c1;
        float ep[8], em[8];
#pragma unroll
        for (int i = 0; i < 8; i++) {
            const bool r1 = (i & 2);
            const uint32_t w = P[4 * h + (i >> 2) * 2 + (i & 1)];
            const float p = r1 ? bf_hi(w) : bf_lo(w);
            ep[i] = ex2(fmaf(p, r1 ? c1 : c0, r1 ? -mx1 : -mx0));
            em[i] = ex2(fmaf(p, r1 ? -c1 : -c0, r1 ? mn1 : mn0));
        }
        float sp[4], sm[4];
        uint32_t tp[4], tm[4];
#pragma unroll
        for (int i = 0; i < 4; i++) { tp[i] = pack_bf16(ep[2 * i], ep[2 * i + 1]); tm[i] = pack_bf16(em[2 * i], em[2 * i + 1]); }
        mma16816_z(sp, tp, 0x3f803f80u, 0x3f803f80u);
        mma16816_z(sm, tm, 0x3f803f80u, 0x3f803f80u);
        const float r0 = rcp(sp[0] * sm[0]), r1 = rcp(sp[2] * sm[2]);
        const float rs[4] = {r0 * sm[0], r1 * sm[2], r0 * sp[0], r1 * sp[2]};
#pragma unroll
        for (int i = 0; i < 4; i++) {
            plus[4 * h + i] = pack_bf16(ep[2 * i] * rs[i & 1], ep[2 * i + 1] * rs[i & 1]);
            minus[4 * h + i] = pack_bf16(em[2 * i] * rs[2 + (i & 1)], em[2 * i + 1] * rs[2 + (i & 1)]);
        }
    }
}

template <bool SCALE>
__device__ __forceinline__ void ln_frag(const float* acc, uint32_t cs_addr, float rs0, float nm0, float rs1, float nm1, uint32_t* a) {
    const float2 c0 = lds_f2(cs_addr), c1 = lds_f2(cs_addr + 32);
    const float s0 = SCALE ? rs0 : 1.f, s1 = SCALE ? rs1 : 1.f;
    a[0] = pack_bf16(fmaf(nm0, c0.x, acc[0]) * s0, fmaf(nm0, c0.y, acc[1]) * s0);
    a[1] = pack_bf16(fmaf(nm1, c0.x, acc[2]) * s1, fmaf(nm1, c0.y, acc[3]) * s1);
    a[2] = pack_bf16(fmaf(nm0, c1.x, acc[4]) * s0, fmaf(nm0, c1.y, acc[5]) * s0);
    a[3] = pack_bf16(fmaf(nm1, c1.x, acc[6]) * s1, fmaf(nm1, c1.y, acc[7]) * s1);
}

template <int UP>
__device__ __forceinline__ uint32_t hh_pair(const float* ag, float4 cs, float nmean) {
    const float g0 = fmaf(nmean, cs.x, ag[0]), g1 = fmaf(nmean, cs.y, ag[1]);
    const float u0 = fmaf(nmean, cs.z, ag[UP]), u1 = fmaf(nmean, cs.w, ag[UP + 1]);
    return pack_bf16(g0 * u0, g1 * u1);
}
__device__ __forceinline__ void hh_stage(const float* acc, const float4* cs, float nm0, float nm1, uint32_t stg, int lane) {
#pragma unroll
    for (int tp = 0; tp < 4; tp++)
        stsm4(stg + (lane & 15) * 128 + (((2 * tp + (lane >> 4)) ^ (lane & 7)) << 4), hh_pair<32>(acc + 8 * tp, cs[2 * tp], nm0),
              hh_pair<32>(acc + 8 * tp + 2, cs[2 * tp], nm1), hh_pair<32>(acc + 8 * tp + 4, cs[2 * tp + 1], nm0),
              hh_pair<32>(acc + 8 * tp + 6, cs[2 * tp + 1], nm1));
    fence_async_smem();
    __syncwarp();
}

struct Ring {
    int slot; uint32_t phase;
    __device__ __forceinline__ void adv() { if (++slot == NB) { slot = 0; phase ^= 1; } }
};

__global__ void __cluster_dims__(2, 1, 1) __launch_bounds__(NTHREADS, 1) fused_kernel(const __grid_constant__ Params P) {
    extern __shared__ __align__(1024) uint8_t smem_raw[];
    const uint32_t sb = smem_u32(smem_raw);
    const int tid = threadIdx.x, lane = tid & 31;
    const int warp = __shfl_sync(0xffffffffu, tid >> 5, 0);
    const unsigned role = P.role[blockIdx.x], rank = blockIdx.x & 1;
    const int m = role >> 3, j = role & 7;
    const bool helper = role >= 128;

    TL(0, tid == 0); TLG(0, tid == 0);
    float* const acc_j = g_acc + j * ACC_SIZE;
    unsigned* const cnt_j = g_cnt + j * 32;

    if (__builtin_expect(warp >= 8, 1)) {
        asm volatile("setmaxnreg.dec.sync.aligned.u32 72;");
        if (elect_one()) {
            if (warp == 8) {
                if (!helper) {
#pragma unroll
                    for (int i = 0; i < NB; i++) mbar_init(sb + BAR_FULLB + 8 * i, 1);
#pragma unroll
                    for (int i = 0; i < 2; i++) {
                        mbar_expect_tx(sb + BAR_FULLB + 8 * i, SLOT);
                        tma2d(sb + OFF_B + i * SLOT, &P.twq, sb + BAR_FULLB + 8 * i, DM + 64 * j, 64 * i);
                        tma2d(sb + OFF_B + i * SLOT + 8192, &P.twq, sb + BAR_FULLB + 8 * i, 2 * DM + 64 * j, 64 * i);
                    }
                }
            } else if (warp == 9) {
#pragma unroll
                for (int i = 0; i < 8; i++) mbar_init(sb + BAR_FULLA + 8 * i, 1);
                if (!helper) {
#pragma unroll
                    for (int i = 0; i < 2; i++) {
                        mbar_expect_tx(sb + BAR_FULLA + 8 * i, SLOT);
                        tma2d(sb + OFF_A + i * SLOT, &P.tx, sb + BAR_FULLA + 8 * i, 64 * i, 128 * m);
                    }
                }
            } else if (warp == 10) {
#pragma unroll
                for (int i = 0; i < 9; i++) mbar_init(sb + BAR_CS1 + 8 * i, i == 0 || i == 8 ? 64 : (i == 1 ? 96 : (i < 4 ? 32 : 8)));
                trap_if_gt(sb & 1023, 0);
            } else {
#pragma unroll
                for (int i = 0; i < 14; i++) mbar_init(sb + (i < 8 ? BAR_EMPTYA : BAR_EMPTYB - 64) + 8 * i, i < 8 ? 8 : 16);
            }
            asm volatile("fence.mbarrier_init.release.cluster;" ::: "memory");
        }
        __syncwarp();
        asm volatile("barrier.cluster.arrive.relaxed.aligned;" ::: "memory");
        const unsigned epoch = ld_relaxed(&g_epoch);
        bar_sync(0, NTHREADS);
        if (helper) {
            if (warp == 8) {
                if (elect_one()) {
#pragma unroll 1
                    for (int i = 0; i < 72; i++) {
                        const uint32_t full = sb + BAR_FULLA + 8 * (i & 7), dst = sb + OFF_A + (i & 7) * SLOT;
                        mbar_wait(sb + BAR_EMPTYA + 8 * (i & 7), ((i >> 3) & 1) ^ 1);
                        mbar_expect_tx(full, SLOT);
                        const bool qkv = i < 24;
                        const int u = (i >> 3) - 3;
                        const int c0 = qkv ? (i < 16 ? DM + 64 * (i & 8) : 0) + 128 * j + 16 * (i & 4) : 176 * (2 * j + (u & 1)) + 64 * (u >> 1);
                        const int r0 = qkv ? 128 * (i & 3) : 64 * (i & 7);
                        tma2d(dst, qkv ? &P.twq : &P.twg, full, c0, r0);
                        tma2d(dst + 8192, qkv ? &P.twq : &P.twu, full, c0, qkv ? r0 + 64 : r0);
                    }
                    prefetch_l2(P.wd + (size_t)j * 176128, 352256);
                }
            }
            return;
        }
        if (warp == 8) {
            asm volatile("barrier.cluster.wait.aligned;" ::: "memory");
            if (elect_one()) {
                if (m >= 6)
                    asm volatile("cp.async.bulk.prefetch.tensor.2d.L2.global [%0, {%1, %2}];" ::"l"(&P.twq), "r"(DM + DM * (m & 1) + 64 * j), "r"(64 * (m >> 1)) : "memory");
                if (j >= 3)
                    asm volatile("cp.async.bulk.prefetch.tensor.2d.L2.global [%0, {%1, %2}];" ::"l"(&P.tx), "r"(64 * j), "r"(128 * m) : "memory");
                Ring r{2, 0};
#pragma unroll 1
                for (int i = 2; i < 59; i++) {
                    const uint32_t full = sb + BAR_FULLB + 8 * r.slot;
                    mbar_wait(sb + BAR_EMPTYB + 8 * r.slot, r.phase ^ 1);
                    if ((i >= 10 && i < 14) || i == 28 || i == 37 || i == 46) {
                        mbar_arrive(full);
                    } else {
                        if (i >= AHEAD && i < 6) mbar_wait(full - 8 * AHEAD, 0);
                        mbar_expect_tx(full, SLOT);
                        const int e = 2 * ((i < 20 ? i : i + 1) & 3) + rank, g8 = i - 20 - (i > 28) - (i > 37);
                        const CUtensorMap* tm = i < 16 ? &P.twq : (i < 20 ? &P.two : (i < 46 ? &P.twg + rank : &P.twd));
                        const int c0 = i < 8 ? DM + DM * rank + 64 * j : ((i >= 20 && i < 46) ? 176 * j + 8 * (g8 & ~7) : 64 * j);
                        const int r0 = i < 8 ? 64 * i : (i < 16 ? 64 * e : (i < 20 ? 64 * KORD(e, j)
                                             : (i < 46 ? 64 * (g8 < 8 ? KORD(g8, j) : g8 & 7) : 176 * e + 64 * ((i - 47) >> 2))));
                        tma2d_mc(sb + OFF_B + r.slot * SLOT + rank * 8192, tm, full, c0, r0);
                    }
                    r.adv();
                }
            }
            return;
        }
        if (warp == 9) {
            if (elect_one()) {
#pragma unroll 1
                for (int i = 2; i < 8; i++) {
                    if (i >= AHEAD + 1) mbar_wait(sb + BAR_FULLA + 8 * (i - AHEAD - 1), 0);
                    mbar_expect_tx(sb + BAR_FULLA + 8 * i, SLOT);
                    tma2d(sb + OFF_A + i * SLOT, &P.tx, sb + BAR_FULLA + 8 * i, 64 * i, 128 * m);
                }
#pragma unroll 1
                for (int i = 1; i < 9; i++) prefetch_tmap(&P.tx + i);
#pragma unroll 1
                for (int r = 1; r < 6; r++) {
                    const CUtensorMap* tm = &P.tx + min(r, 3);
                    const int cstep = r < 3 ? 64 : 192, cbase = r < 3 ? 0 : 64 * (r - 3), skip = r < 3 ? j : 8;
                    mbar_wait(sb + BAR_EMPTYA + 8 * (skip == 0), (r - 1) & 1);
                    wait_count(g_flag + (m * 5 + r - 1) * 32, epoch * (r < 3 ? 64 : 8));
                    TL(64 + r, true);
#pragma unroll 1
                    for (int t = 0; t < 8; t++) {
                        if (t == skip) continue;
                        mbar_wait(sb + BAR_EMPTYA + 8 * t, (r - 1) & 1);
                        mbar_expect_tx(sb + BAR_FULLA + 8 * t, SLOT);
                        tma2d(sb + OFF_A + t * SLOT, tm, sb + BAR_FULLA + 8 * t, cbase + cstep * t, 128 * m);
                    }
                }
            }
            return;
        }
        const int a = warp - 10;
        {
            const int row = 16 * j + 8 * a + (lane >> 2);
            const uint32_t ra = sb + OFF_A + row * 128;
            float sh = 0.f, s0 = 0.f, s1 = 0.f, q0 = 0.f, q1 = 0.f;
#pragma unroll 1
            for (int kt = 0; kt < 8; kt++) {
                mbar_wait(sb + BAR_FULLA + 8 * kt, 0);
                if (kt == 0) sh = bf_lo(lds128(ra + ((row & 7) << 4)).x);
#pragma unroll
                for (int i = 0; i < 2; i++) {
                    const uint4 v = lds128(ra + kt * SLOT + (((2 * (lane & 3) + i) ^ (row & 7)) << 4));
                    const uint32_t ww[4] = {v.x, v.y, v.z, v.w};
#pragma unroll
                    for (int e = 0; e < 4; e++) {
                        const float d0 = bf_lo(ww[e]) - sh, d1 = bf_hi(ww[e]) - sh;
                        s0 += d0; q0 = fmaf(d0, d0, q0);
                        s1 += d1; q1 = fmaf(d1, d1, q1);
                    }
                }
            }
            s0 += s1; q0 += q1;
#pragma unroll
            for (int o = 1; o <= 2; o <<= 1) { s0 += __shfl_xor_sync(0xffffffffu, s0, o); q0 += __shfl_xor_sync(0xffffffffu, q0, o); }
            const float md = s0 * (1.f / DM);
            const float rs = rsqrtf(fmaxf(q0 * (1.f / DM) - md * md, 0.f) + 1e-5f);
            st_tagged_if(g_xstat + 2 * (128 * m + row), rs, -(sh + md), epoch, (lane & 3) == 0);
        }
        const unsigned long long* cs = g_cs + j * 768 + 2 * lane;
#pragma unroll 1
        for (int c = 0; c < (a ? 5 : 10); c++) {
            if (c == 4) {
                const int t = 32 * a + lane;
                const uint32_t kvs = sb + OFF_A + KVS(j) * SLOT;
                mbar_wait(sb + BAR_KVW, 0);
#pragma unroll 1
                for (int pass = 0; pass < 2; pass++) {
                    float4 v[8];
#pragma unroll
                    for (int i = 0; i < 8; i++) v[i] = ld_l2_f4(acc_j + ACC_KV + 4 * (t + 64 * i));
                    const float2 zz = ld_l2_f2(acc_j + ACC_Z + 2 * t);
#pragma unroll
                    for (int i = 0; i < 8; i++)
                        sts64(kvs + ((t >> 2) + 16 * i) * 48 + (t & 3) * 8, pack_bf16(v[i].x, v[i].y), pack_bf16(v[i].z, v[i].w));
                    const uint32_t z0 = pack_bf16(zz.x, zz.x), z1 = pack_bf16(zz.y, zz.y);
                    sts128(kvs + t * 96 + 32, z0, z0, z0, z0);
                    sts128(kvs + t * 96 + 80, z1, z1, z1, z1);
                    if (pass == 0) {
                        __syncwarp();
                        if (lane == 0) red_relaxed(cnt_j, 1);
                        TL(19, t == 0);
                        wait_count_warp(cnt_j, epoch * 32);
                        TL(14, t == 0);
                    }
                }
                mbar_arrive(sb + BAR_KVR);
                if (a) break;
            }
            if (c == 3 && !a) continue;
            const unsigned long long* src = c < 2 ? g_xstat + 2 * (128 * m + 64 * a + 32 * c + lane) : cs + (c < 4 ? 128 * (a + c - 2) : 128 + 64 * c);
            const uint32_t dst = c < 2 ? OFF_XST + (64 * a + 32 * c + lane) * 8
                                       : (c < 4 ? OFF_CS1 + (c == 2 ? 256 * (a + 1) : 0) + 8 * lane : OFF_CS3 + (32 * ((c - 4) >> 1) + lane) * 16 + 8 * (c & 1));
            uint4 v;
            uint32_t it = 0;
            while (true) {
                v = ld_tagged_rlx(src);
                if (!__any_sync(0xffffffffu, v.y != epoch || v.w != epoch)) break;
                __nanosleep(60);
                trap_if_gt(++it, 1u << 22);
            }
            sts64(sb + dst, v.x, v.z);
            if (c == 2 - a || (a && c > 1) || c == 9) mbar_arrive(sb + (c == 9 ? BAR_CS3 : (c == 2 - a ? BAR_CS1 : (c == 2 ? BAR_CSV : BAR_CSQ))));
        }
        {
            uint32_t it = 0;
            while (__any_sync(0xffffffffu, (int)(readback(g_flag + (m * 5 + 1) * 32) - epoch * 64) < 0)) {
                __nanosleep(200);
                trap_if_gt(++it, 1u << 22);
            }
            const int row = 2 * (32 * a + lane);
            const float* sp = g_hstat + (1024 * m + row) * 2;
            float4 v[8];
#pragma unroll
            for (int i = 0; i < 8; i++) v[i] = ld_l2_f4(sp + 256 * i);
            float ma = 0.f, mb = 0.f;
#pragma unroll
            for (int i = 0; i < 8; i++) { ma += v[i].x; mb += v[i].z; }
            ma *= 0.125f; mb *= 0.125f;
            float sa = 0.f, sb2 = 0.f, da = 0.f, db = 0.f;
#pragma unroll
            for (int i = 0; i < 8; i++) {
                sa += v[i].y; da = fmaf(v[i].x - ma, v[i].x - ma, da);
                sb2 += v[i].w; db = fmaf(v[i].z - mb, v[i].z - mb, db);
            }
            sts128(sb + OFF_CS1 + row * 8, __float_as_uint(-ma), __float_as_uint(rcp(fmaf(da, 64.f, sa) * (1.f / DM) + 1e-5f)),
                   __float_as_uint(-mb), __float_as_uint(rcp(fmaf(db, 64.f, sb2) * (1.f / DM) + 1e-5f)));
        }
        mbar_arrive(sb + BAR_CS3);
#pragma unroll 1
        for (int c = a; c < 3; c += 2) {
            const int slot = c == 1 ? 1 : 4;
            mbar_wait(sb + BAR_STG + 8 * c, 0);
            if (elect_one()) {
                tma_store2d(&P.thh, sb + OFF_B + slot * SLOT, 192 * j + 64 * c, 128 * m);
                asm volatile("cp.async.bulk.wait_group.read 0;" ::: "memory");
                mbar_arrive_n_if(sb + BAR_EMPTYB + 8 * slot, 8, true);
                asm volatile("mbarrier.arrive.shared::cluster.b64 _, [%0], 8;" ::"r"(mapa(sb + BAR_EMPTYB + 8 * slot, rank ^ 1)) : "memory");
                asm volatile("cp.async.bulk.wait_group 0;" ::: "memory");
            }
            __syncwarp();
            TL(60 + c, lane == 0);
            uint32_t ack = 0;
#pragma unroll
            for (int i = 0; i < 4; i++) ack |= readback(g_hh + (size_t)(128 * m + 32 * i + lane) * FFP + 192 * j + 64 * c);
            signal_after(g_flag + (m * 5 + 2 + c) * 32, ack, P.zero, lane == 0);
            TL(54 + c, lane == 0);
        }
        return;
    }
    const unsigned epoch = ld_relaxed(&g_epoch);
    uint32_t wraw[16];
    if (!helper) {
        const uint32_t* wp = reinterpret_cast<const uint32_t*>(P.wphi) + (4 * j) * 128 + (lane & 3) * 16 + (lane >> 2);
#pragma unroll
        for (int i = 0; i < 16; i++)
            asm volatile("ld.global.nc.u32 %0, [%1];" : "=r"(wraw[i]) : "l"(wp + (i >> 2) * 128 + ((i >> 1) & 1) * 64 + (i & 1) * 8));
    }
    asm volatile("barrier.cluster.arrive.relaxed.aligned;" ::: "memory");
    asm volatile("setmaxnreg.inc.sync.aligned.u32 216;");
    bar_sync(0, NTHREADS);
    if (helper) {
        if (warp < 4) {
            sts128(sb + OFF_B + 16 * tid, 0x3f803f80u, 0x3f803f80u, 0x3f803f80u, 0x3f803f80u);
            for (int i = tid; i < 2 * ACC_SIZE / 4; i += 128) stg128(g_acc + 2 * j * ACC_SIZE + 4 * i, 0, 0, 0, 0);
            fence_async_smem();
            fence_gpu();
            bar_sync(1, 128);
            float acc[8];
            int i = 0;
#pragma unroll 1
            for (int job = 0; job < 12; job++) {
                const int n = job < 6 ? 4 : 8;
#pragma unroll 1
                for (int t = 0; t < n; t++, i++) {
                    mbar_wait(sb + BAR_FULLA + 8 * (i & 7), (i >> 3) & 1);
                    wg_fence();
#pragma unroll
                    for (int k = 0; k < 8; k++)
                        wgmma_n8_tt(acc + (k & 4), desc_lo(sb + OFF_A) + (i & 7) * (SLOT >> 4) + 128 * k, desc_lo(sb + OFF_B), (t | (k & 3)) != 0);
                    wg_commit();
                    wg_wait<1>();
                    mbar_arrive_n_if(sb + BAR_EMPTYA + 8 * ((i + 7) & 7), 2, lane == 0 && i > 0);
                }
                wg_wait<0>();
                fence_acc<8>(acc);
                const int q = lane & 3;
                const float lo = (q & 1) ? acc[2] : acc[0], hi = (q & 1) ? acc[6] : acc[4];
                const float v = job < 6 ? lo + hi : ((q & 2) ? hi : lo);
                unsigned long long* dst = g_cs + ((2 * j + (job & 1)) * 6 + (job >> 1)) * 128 + (q >> 1) * 64 + 16 * warp + 8 * (q & 1) + (lane >> 2);
                asm volatile("st.relaxed.gpu.global.b64 [%0], %1;" ::"l"(dst), "l"(((unsigned long long)epoch << 32) | __float_as_uint(v)) : "memory");
            }
        }
        return;
    }
    {
        const int w = warp >> 2, wv = warp & 3, g = lane >> 2, q = lane & 3;
        const int row_w = 128 * m + 16 * warp;
        const uint32_t sa = sb + OFF_A + w * 8192;
        const desc_t dA = desc_lo(sa), dB = desc_lo(sb + OFF_B);
        unsigned* const flag_m = g_flag + m * 160;
        const bool l0 = lane == 0, l2 = lane < 2;
        const uint32_t eb = mapa(sb + BAR_EMPTYB, lane & 1);
        asm volatile("barrier.cluster.wait.aligned;" ::: "memory");
        Ring rg{0, 0};
        int prev = 0;

        uint32_t wb[16];
        constexpr float L2E = 1.4426950408889634f;
        const int ch = lane >> 4, sw = lane & 7;
        const uint32_t lrow = (lane & 15) * 128;
        uint32_t fp[16], fm[16];
        {
            float acc[64], accq[32];
#pragma unroll 1
            for (int kt = 0; kt < 8; kt++) {
                mbar_waitc(sb + BAR_FULLA + 8 * kt, 0);
                mbar_waitc(sb + BAR_FULLB + 8 * rg.slot, rg.phase);
                const desc_t da = dA + kt * (SLOT >> 4), db = dB + rg.slot * (SLOT >> 4);
                wg_fence();
#pragma unroll
                for (int k = 0; k < 4; k++) wgmma_n128(acc, da + 2 * k, db + 128 * k, (kt | k) != 0);
                wg_commit();
                wg_wait<1>();
                mbar_arrive_cl_if(eb + 8 * prev, l2 && kt > 0);
                prev = rg.slot; rg.adv();
            }
#pragma unroll
            for (int i = 0; i < 8; i++) {
                wb[(i >> 1) * 4 + (i & 1)] = __byte_perm(wraw[2 * i], wraw[2 * i + 1], 0x5410);
                wb[(i >> 1) * 4 + 2 + (i & 1)] = __byte_perm(wraw[2 * i], wraw[2 * i + 1], 0x7632);
            }
            float2 s0, s1;
            uint32_t a[16];
            wg_wait<0>();
            fence_acc<64>(acc);
            mbar_arrive_cl_if(eb + 8 * prev, l2);
#pragma unroll 1
            for (int it = 0; it < 2; it++) {
                mbar_waitc(sb + BAR_FULLB + 8 * 2, it ^ 1); mbar_waitc(sb + BAR_FULLB + 8 * 3, it ^ 1);
                const desc_t da = dA + it * (4 * SLOT >> 4);
                wg_fence();
#pragma unroll
                for (int k = 0; k < 16; k++) wgmma_n64(accq, da + (k >> 2) * (SLOT >> 4) + (k & 3) * 2, dB + 2 * (SLOT >> 4) + 128 * k, (it | k) != 0);
                wg_commit();
                TL(17 + it, tid == 0);
                mbar_waitc(sb + BAR_CS1 + 16 * it, 0);
                wg_wait<0>();
                fence_acc<32>(accq);
                mbar_arrive_cl_if(eb + 8 * (2 + (lane >> 1)), lane < 4);
                TL(2 + 2 * it, tid == 0);
                if (it == 0) {
                    s0 = lds_f2(sb + OFF_XST + (16 * warp + g) * 8); s1 = lds_f2(sb + OFF_XST + (16 * warp + g + 8) * 8);
#pragma unroll
                    for (int hh = 0; hh < 4; hh++)
                        ln_frag<false>(acc + 8 * hh, sb + OFF_CS1 + (64 + 16 * hh + 2 * q) * 4, 0.f, s0.y, 0.f, s1.y, a + 4 * hh);
                } else {
#pragma unroll
                    for (int hh = 0; hh < 4; hh++)
                        ln_frag<false>(accq + 8 * hh, sb + OFF_CS1 + (16 * hh + 2 * q) * 4, 0.f, s0.y, 0.f, s1.y, a + 4 * hh);
                }
                feature_maps(a, wb, s0.x * L2E, s1.x * L2E, fp, fm);
                if (it == 0) {
                    mbar_waitc(sb + BAR_FULLB + 8 * 4, 1); mbar_waitc(sb + BAR_FULLB + 8 * 5, 1);
                    mbar_waitc(sb + BAR_FULLB + 8 * 0, 0); mbar_waitc(sb + BAR_FULLB + 8 * 1, 0);
                    mbar_waitc(sb + BAR_CSV, 0);
                    const uint32_t st = sb + OFF_B + warp * 2048 + lrow;
#pragma unroll
                    for (int hh = 0; hh < 4; hh++) {
                        stsm4(st + (4 + (hh >> 1)) * SLOT + (((4 * (hh & 1) + ch) ^ sw) << 4), fp[4 * hh], fp[4 * hh + 1], fp[4 * hh + 2], fp[4 * hh + 3]);
                        stsm4(st + (4 + (hh >> 1)) * SLOT + (((4 * (hh & 1) + 2 + ch) ^ sw) << 4), fm[4 * hh], fm[4 * hh + 1], fm[4 * hh + 2], fm[4 * hh + 3]);
                        ln_frag<true>(acc + 32 + 8 * hh, sb + OFF_CS1 + (128 + 16 * hh + 2 * q) * 4, s0.x, s0.y, s1.x, s1.y, a);
                        stsm4(st + (hh >> 1) * SLOT + (((2 * (hh & 1) + ch) ^ sw) << 4), a[0], a[1], a[2], a[3]);
                    }
                    stsm4(st + ch * SLOT + ((4 ^ sw) << 4), 0x3f803f80u, 0x3f803f80u, 0x3f803f80u, 0x3f803f80u);
                    fence_async_smem();
                    bar_sync(1, 256);
                    float kvd[20];
                    wg_fence();
#pragma unroll
                    for (int k = 0; k < 8; k++)
                        wgmma_n40_tt(kvd, dB + (4 + w) * (SLOT >> 4) + 128 * k, dB + w * (SLOT >> 4) + 128 * k, k != 0);
                    wg_commit();
                    wg_wait<0>();
                    fence_acc<20>(kvd);
                    const bool h1 = wv >= 2;
                    const int f = 16 * warp + g;
                    float* kvp = acc_j + ACC_KV + f * 16 + 2 * q;
                    red_f32x2(kvp, h1 ? kvd[8] : kvd[0], h1 ? kvd[9] : kvd[1]);
                    red_f32x2(kvp + 128, h1 ? kvd[10] : kvd[2], h1 ? kvd[11] : kvd[3]);
                    red_f32x2(kvp + 8, h1 ? kvd[12] : kvd[4], h1 ? kvd[13] : kvd[5]);
                    red_f32x2(kvp + 136, h1 ? kvd[14] : kvd[6], h1 ? kvd[15] : kvd[7]);
                    red_f32_if(acc_j + ACC_Z + f + 8 * (q & 1), q ? kvd[18] : kvd[16], q < 2);
                    __syncwarp();
                    mbar_arrive_if(sb + BAR_KVW, l0);
                    mbar_arrive_cl_if(eb + 8 * ((4 + (lane >> 1)) % 6), lane < 8);
                    TL(3, tid == 0);
                }
            }
        }
        uint32_t res_lo[8], res_hi[8], ack[5];
        const uint32_t own_rows = sb + OFF_A + j * SLOT + warp * 2048;
#pragma unroll
        for (int b = 0; b < 4; b++)
            ldsm4(own_rows + lrow + (((2 * b + ch) ^ sw) << 4), res_lo[2 * b], res_hi[2 * b], res_lo[2 * b + 1], res_hi[2 * b + 1]);
        mbar_arrive_if(sb + BAR_EMPTYA + 8 * lane, lane < 8 && lane != j && lane != KVS(j));
        TL(5, tid == 0);
        mbar_waitc(sb + BAR_KVR, 0);
        TL(6, tid == 0);
        {
            const uint32_t kvs = sb + OFF_A + KVS(j) * SLOT;
            uint32_t o_lo[8], o_hi[8];
#pragma unroll
            for (int hh = 0; hh < 4; hh++) {
                uint32_t b[8], zb[4];
                const uint32_t base = kvs + hh * 32 * 48;
                ldsm4t(base + (lane & 15) * 48 + (lane >> 4) * 16, b[0], b[1], b[2], b[3]);
                ldsm4t(base + (16 + (lane & 15)) * 48 + (lane >> 4) * 16, b[4], b[5], b[6], b[7]);
                ldsm4t(base + lane * 48 + 32, zb[0], zb[1], zb[2], zb[3]);
                float n0[4], n1[4], dn[4];
                mma16816_z(n0, fp + 4 * hh, b[0], b[1]); mma16816_z(n1, fp + 4 * hh, b[2], b[3]); mma16816_z(dn, fp + 4 * hh, zb[0], zb[1]);
                mma16816(n0, fm + 4 * hh, b[4], b[5]); mma16816(n1, fm + 4 * hh, b[6], b[7]); mma16816(dn, fm + 4 * hh, zb[2], zb[3]);
                const float i0 = rcp(dn[0] + 1e-6f), i1 = rcp(dn[2] + 1e-6f);
                o_lo[2 * hh] = pack_bf16(n0[0] * i0, n0[1] * i0); o_hi[2 * hh] = pack_bf16(n0[2] * i1, n0[3] * i1);
                o_lo[2 * hh + 1] = pack_bf16(n1[0] * i0, n1[1] * i0); o_hi[2 * hh + 1] = pack_bf16(n1[2] * i1, n1[3] * i1);
            }
            __syncwarp();
            mbar_arrive_if(sb + BAR_EMPTYA + 8 * KVS(j), l0);
            rg.slot = 4; rg.phase = 0;
            store_tile(own_rows, g_o + (size_t)row_w * DM + 64 * j, o_lo, o_hi, lane, ack);
            ack[4] = 0;
            TL(7, tid == 0);
        }
        {
            float acc[32];
#pragma unroll
            for (int t = 0; t < 8; t++) {
                acc[4 * t] = bf_lo(res_lo[t]); acc[4 * t + 1] = bf_hi(res_lo[t]);
                acc[4 * t + 2] = bf_lo(res_hi[t]); acc[4 * t + 3] = bf_hi(res_hi[t]);
            }
            fence_acc<32>(acc);
            int pa = 0;
#pragma unroll 1
            for (int kp = 0; kp < 4; kp++) {
                mbar_waitc(sb + BAR_FULLB + 8 * rg.slot, rg.phase);
#pragma unroll
                for (int hf = 0; hf < 2; hf++) {
                    const int i = 2 * kp + hf, kt = KORD(i, j);
                    mbar_waitc(sb + BAR_FULLA + 8 * kt, i != 0);
                    TL(8, i == 1 && tid == 0);
                    const desc_t da = dA + kt * (SLOT >> 4), db = dB + rg.slot * (SLOT >> 4);
                    wg_fence();
#pragma unroll
                    for (int k = 0; k < 4; k++) wgmma_n64(acc, da + 2 * k, db + (hf * 4 + k) * 128, 1);
                    wg_commit();
                    wg_wait<1>();
                    mbar_arrive_if(sb + BAR_EMPTYA + 8 * pa, l0 && i > 1);
                    if (hf == 0) {
                        mbar_arrive_cl_if(eb + 8 * prev, l2 && i > 0);
                        if (i == 0) { signal_late(flag_m, ack, P.zero, l0); TL(20, tid == 0); }
                    }
                    pa = kt;
                }
                prev = rg.slot; rg.adv();
            }
            wg_wait<0>();
            fence_acc<32>(acc);
            mbar_arrive_if(sb + BAR_EMPTYA + 8 * pa, l0);
            mbar_arrive_cl_if(eb + 8 * prev, l2);
            TL(9, tid == 0);
            float s0 = 0.f, s1 = 0.f;
#pragma unroll
            for (int t = 0; t < 8; t++) {
                res_lo[t] = pack_bf16(acc[4 * t], acc[4 * t + 1]);
                res_hi[t] = pack_bf16(acc[4 * t + 2], acc[4 * t + 3]);
                s0 += acc[4 * t] + acc[4 * t + 1];
                s1 += acc[4 * t + 2] + acc[4 * t + 3];
            }
            store_tile(own_rows, g_h + (size_t)row_w * DM + 64 * j, res_lo, res_hi, lane, ack);
            s0 += __shfl_xor_sync(0xffffffffu, s0, 1); s1 += __shfl_xor_sync(0xffffffffu, s1, 1);
            s0 += __shfl_xor_sync(0xffffffffu, s0, 2); s1 += __shfl_xor_sync(0xffffffffu, s1, 2);
            const float mu0 = s0 * (1.f / 64), mu1 = s1 * (1.f / 64);
            float q0 = 0.f, q1 = 0.f;
#pragma unroll
            for (int t = 0; t < 8; t++) {
                float d;
                d = acc[4 * t] - mu0; q0 = fmaf(d, d, q0);
                d = acc[4 * t + 1] - mu0; q0 = fmaf(d, d, q0);
                d = acc[4 * t + 2] - mu1; q1 = fmaf(d, d, q1);
                d = acc[4 * t + 3] - mu1; q1 = fmaf(d, d, q1);
            }
            q0 += __shfl_xor_sync(0xffffffffu, q0, 1); q1 += __shfl_xor_sync(0xffffffffu, q1, 1);
            q0 += __shfl_xor_sync(0xffffffffu, q0, 2); q1 += __shfl_xor_sync(0xffffffffu, q1, 2);
            stg_f2_if(g_hstat + (role * 128 + 16 * warp + g + 8 * (q & 1)) * 2, q ? mu1 : mu0, q ? q1 : q0, q < 2);
            ack[4] = readback(g_hstat + (role * 128 + 16 * warp + g + 8 * (q & 1)) * 2);
            TL(10, tid == 0);
        }
        {
            float acc[64];
#pragma unroll 1
            for (int c = 0; c < 3; c++) {
#define KT_P3(MMA)                                                                                          \
    _Pragma("unroll 1") for (int i = 0; i < 8; i++) {                                                       \
        const int kt = c ? i : KORD(i, j);                                                                  \
        mbar_waitc(sb + BAR_FULLA + 8 * kt, 0);                                                             \
        mbar_waitc(sb + BAR_FULLB + 8 * rg.slot, rg.phase);                                                 \
        TL(44, tid == 0 && i == 1 && c == 0);                                                               \
        const desc_t da = dA + kt * (SLOT >> 4), db = dB + rg.slot * (SLOT >> 4);                           \
        wg_fence();                                                                                         \
        _Pragma("unroll") for (int k = 0; k < 4; k++) MMA(acc, da + 2 * k, db + 128 * k, (i | k) != 0);     \
        wg_commit();                                                                                        \
        wg_wait<1>();                                                                                       \
        mbar_arrive_cl_if(eb + 8 * prev, l2 && i > 0);                                            \
        mbar_arrive_if(sb + BAR_EMPTYA + 8 * ((i + 7) & 7), l0 && i > 0 && c == 2);                         \
        if ((i | c) == 0) { signal_late(flag_m + 32, ack, P.zero, l0); TL(21, tid == 0); }                  \
        if (STAGGER && c == 0 && i == (w ? 0 : STAGGER)) { if (w) bar_sync(2, 256); else bar_arrive(2, 256); } \
        prev = rg.slot; rg.adv();                                                                           \
    }
                if (c < 2) { KT_P3(wgmma_n128) } else { KT_P3(wgmma_n112) }
                mbar_waitc(sb + BAR_CS3, 0);
                mbar_waitc(sb + BAR_FULLB + 8 * rg.slot, rg.phase);
                const float nm0 = lds_f2(sb + OFF_CS1 + (16 * warp + g) * 8).x, nm1 = lds_f2(sb + OFF_CS1 + (16 * warp + g + 8) * 8).x;
                float4 cs[8];
#pragma unroll
                for (int t = 0; t < 8; t++) cs[t] = lds_f4(sb + OFF_CS3 + q * 16 + 512 * c + 64 * t);
                wg_wait<0>();
                fence_acc<64>(acc);
                mbar_arrive_if(sb + BAR_EMPTYA + 8 * 7, l0 && c == 2);
                mbar_arrive_cl_if(eb + 8 * prev, l2);
                TL(11 + c, tid == 0);
                hh_stage(acc, cs, nm0, nm1, sb + OFF_B + rg.slot * SLOT + warp * 2048, lane);
                rg.adv();
                mbar_arrive_if(sb + BAR_STG + 8 * c, l0);
                TL(50 + c, tid == 0);
            }
        }
        {
            float acc[64];
            const desc_t dA0 = desc_lo(sb + OFF_A);
#define KT_P4(I, NK)                                                                                        \
    do {                                                                                                    \
        const int s_ = (2 * (I) + w) & 7;                                                                   \
        mbar_waitc(sb + BAR_FULLB + 8 * rg.slot, rg.phase);                                                 \
        mbar_waitc(sb + BAR_FULLA + 8 * s_, (((I) >> 2) + 1) & 1);                                          \
        TL(30 + (I), tid == 0);                                                                             \
        const desc_t dh_ = dA0 + s_ * (SLOT >> 4), dw_ = dB + rg.slot * (SLOT >> 4) + w * 512;              \
        wg_fence();                                                                                         \
        _Pragma("unroll") for (int k = 0; k < (NK); k++) wgmma_n128_tn(acc, dw_ + 128 * k, dh_ + 2 * k, ((I) | k) != 0); \
        wg_commit();                                                                                        \
        wg_wait<1>();                                                                                       \
        mbar_arrive_n_if(sb + BAR_EMPTYA + 8 * ((s_ + 6) & 7), 2, l0 && (I) > 0);                           \
        mbar_arrive_cl_if(eb + 8 * prev, l2 && (I) > 0 && (I) < 7);                                          \
        prev = rg.slot; rg.adv();                                                                           \
    } while (0)
#pragma unroll 1
            for (int i = 0; i < 8; i++) KT_P4(i, 4);
#pragma unroll 1
            for (int i = 8; i < 12; i++) KT_P4(i, 3);
            const uint32_t tile = sb + OFF_A + w * SLOT;
#pragma unroll
            for (int b = 0; b < 4; b++)
                stsm4(tile + (16 * wv + (lane & 15)) * 128 + (((2 * b + (lane >> 4)) ^ (lane & 7)) << 4),
                      res_lo[2 * b], res_hi[2 * b], res_lo[2 * b + 1], res_hi[2 * b + 1]);
            wg_wait<0>();
            fence_acc<64>(acc);
            TL(15, tid == 0);
            const uint32_t xch = sb + OFF_A + 2 * SLOT + (tid & 127) * 16;
            if (w) {
#pragma unroll
                for (int t = 0; t < 8; t++) {
                    sts128(xch + SLOT + t * 2048, __float_as_uint(acc[4 * t]), __float_as_uint(acc[4 * t + 1]),
                           __float_as_uint(acc[4 * t + 2]), __float_as_uint(acc[4 * t + 3]));
                }
#pragma unroll
                for (int t = 0; t < 32; t++) acc[t] = acc[32 + t];
            } else {
#pragma unroll
                for (int t = 0; t < 8; t++)
                    sts128(xch + t * 2048, __float_as_uint(acc[32 + 4 * t]), __float_as_uint(acc[33 + 4 * t]),
                           __float_as_uint(acc[34 + 4 * t]), __float_as_uint(acc[35 + 4 * t]));
            }
            bar_sync(1, 256);
            const uint32_t blk = tile + ((lane & 7) + (lane >> 4) * 8) * 128 + (((2 * wv + ((lane >> 3) & 1)) ^ (lane & 7)) << 4);
#pragma unroll
            for (int tp = 0; tp < 4; tp++) {
                uint32_t hr[4];
                ldsm4t(blk + tp * 2048, hr[0], hr[1], hr[2], hr[3]);
#pragma unroll
                for (int u = 0; u < 2; u++) {
                    const int t = 2 * tp + u;
                    const float4 o = lds_f4(xch + (w ^ 1) * SLOT + t * 2048);
                    const float4 st = lds_f4(sb + OFF_CS1 + (64 * w + 8 * t + 2 * q) * 8);
                    hr[2 * u] = pack_bf16(fmaf(acc[4 * t] + o.x, st.y, bf_lo(hr[2 * u])), fmaf(acc[4 * t + 1] + o.y, st.w, bf_hi(hr[2 * u])));
                    hr[2 * u + 1] = pack_bf16(fmaf(acc[4 * t + 2] + o.z, st.y, bf_lo(hr[2 * u + 1])), fmaf(acc[4 * t + 3] + o.w, st.w, bf_hi(hr[2 * u + 1])));
                }
                stsm4t(blk + tp * 2048, hr[0], hr[1], hr[2], hr[3]);
            }
            bar_sync(2 + w, 128);
#pragma unroll
            for (int i = 0; i < 4; i++) {
                const int rr = 16 * wv + 4 * i + (lane >> 3);
                const uint4 v = lds128(tile + rr * 128 + (((lane & 7) ^ (rr & 7)) << 4));
                stg128(P.out + (size_t)(128 * m + 64 * w + rr) * DM + 64 * j + (lane & 7) * 8, v.x, v.y, v.z, v.w);
            }
            if (tid == 0 && role == 0) g_epoch = epoch + 1;
            TL(16, tid == 0); TLG(1, tid == 0);
        }
    }
}

__global__ void probe_kernel() {}

typedef CUresult (*EncodeFn)(CUtensorMap*, CUtensorMapDataType, cuuint32_t, void*, const cuuint64_t*, const cuuint64_t*,
                             const cuuint32_t*, const cuuint32_t*, CUtensorMapInterleave, CUtensorMapSwizzle,
                             CUtensorMapL2promotion, CUtensorMapFloatOOBfill);

static void make_map2d(EncodeFn enc, CUtensorMap* tm, const void* base, uint64_t cols, uint64_t rows, uint64_t pitch_elems,
                       uint32_t box_rows) {
    cuuint64_t gd[2] = {cols, rows};
    cuuint64_t gs[1] = {pitch_elems * 2};
    cuuint32_t bd[2] = {64, box_rows};
    cuuint32_t es[2] = {1, 1};
    enc(tm, CU_TENSOR_MAP_DATA_TYPE_BFLOAT16, 2, const_cast<void*>(base), gd, gs, bd, es, CU_TENSOR_MAP_INTERLEAVE_NONE,
        CU_TENSOR_MAP_SWIZZLE_128B, CU_TENSOR_MAP_L2_PROMOTION_L2_256B, CU_TENSOR_MAP_FLOAT_OOB_FILL_NONE);
}

}

extern "C" void kernel_launch(void* const* d_in, const int* in_sizes, int n_in, void* d_out, int out_size) {
    using namespace hk;
    (void)in_sizes; (void)n_in; (void)out_size;
    static EncodeFn enc = nullptr;
    static void *po = nullptr, *ph = nullptr, *phh = nullptr;
    static int std_layout = 0;
    if (!enc) {
        void* fn = nullptr;
        cudaDriverEntryPointQueryResult qr;
        cudaGetDriverEntryPoint("cuTensorMapEncodeTiled", &fn, cudaEnableDefault, &qr);
        enc = (EncodeFn)fn;
        cudaGetSymbolAddress(&po, g_o);
        cudaGetSymbolAddress(&ph, g_h);
        cudaGetSymbolAddress(&phh, g_hh);
        cudaFuncSetAttribute(fused_kernel, cudaFuncAttributeMaxDynamicSharedMemorySize, SMEM_BYTES);
        int dev = 0, sms = 0;
        cudaGetDevice(&dev);
        cudaDeviceGetAttribute(&sms, cudaDevAttrMultiProcessorCount, dev);
        cudaFuncSetAttribute(probe_kernel, cudaFuncAttributeNonPortableClusterSizeAllowed, 1);
        cudaFuncSetAttribute(probe_kernel, cudaFuncAttributeMaxDynamicSharedMemorySize, SMEM_BYTES);
        const int sizes[3] = {8, 9, 16}, want[3] = {15, 9, 7};
        bool ok = sms == NCTA;
        for (int i = 0; i < 3 && ok; i++) {
            cudaLaunchConfig_t cfg = {};
            cfg.gridDim = dim3(sizes[i] * 8); cfg.blockDim = dim3(NTHREADS); cfg.dynamicSmemBytes = SMEM_BYTES;
            cudaLaunchAttribute at;
            at.id = cudaLaunchAttributeClusterDimension;
            at.val.clusterDim.x = sizes[i]; at.val.clusterDim.y = 1; at.val.clusterDim.z = 1;
            cfg.attrs = &at; cfg.numAttrs = 1;
            int n = 0;
            ok = cudaOccupancyMaxActiveClusters(&n, probe_kernel, &cfg) == cudaSuccess && n == want[i];
        }
        (void)cudaGetLastError();
        std_layout = ok ? 1 : 0;
    }
    Params P;
    const __nv_bfloat16* x = (const __nv_bfloat16*)d_in[0];
    P.x = x;
    P.wqkv = (const __nv_bfloat16*)d_in[1];
    P.wphi = (const __nv_bfloat16*)d_in[2];
    P.wo = (const __nv_bfloat16*)d_in[3];
    P.wg = (const __nv_bfloat16*)d_in[5];
    P.wu = (const __nv_bfloat16*)d_in[6];
    P.wd = (const __nv_bfloat16*)d_in[7];
    P.out = (__nv_bfloat16*)d_out;
    P.zero = 0;
    for (int i = 0; i < NCTA; i++) {
        const int odd = i & 1;
        int role = i < 4 ? 128 + i : (((i - 4) >> 4) * 2 + odd) * 8 + (((i - 4) >> 1) & 7);
        if (std_layout) {
            const int tpc = i < 8 ? 62 + (i >> 1) : (i - 8) >> 1;
            if (tpc < 32) role = (tpc & 7) ? (2 * ((tpc & 7) - 1) + odd) * 8 + (tpc >> 3) : (14 + odd) * 8 + (tpc >> 3);
            else if (tpc < 60) role = (2 * ((tpc - 32) % 7) + odd) * 8 + 4 + (tpc - 32) / 7;
            else if (tpc < 62) role = 128 + (tpc - 60) * 2 + odd;
            else role = (14 + odd) * 8 + 4 + (tpc - 62);
        }
        P.role[i] = (unsigned char)role;
    }
    make_map2d(enc, &P.tx, x, DM, SEQ, DM, 128);
    make_map2d(enc, &P.to, po, DM, SEQ, DM, 128);
    make_map2d(enc, &P.th, ph, DM, SEQ, DM, 128);
    make_map2d(enc, &P.thh, phh, FFP, SEQ, FFP, 128);
    make_map2d(enc, &P.twq, P.wqkv, 3 * DM, DM, 3 * DM, 64);
    make_map2d(enc, &P.two, P.wo, DM, DM, DM, 64);
    make_map2d(enc, &P.twg, P.wg, FF, DM, FF, 64);
    make_map2d(enc, &P.twu, P.wu, FF, DM, FF, 64);
    make_map2d(enc, &P.twd, P.wd, DM, FF, DM, 64);
    fused_kernel<<<NCTA, NTHREADS, SMEM_BYTES>>>(P);
}
```

```cpp
#include <cuda_runtime.h>
#include <cuda_bf16.h>
#include <cuda.h>
#include <stdint.h>

namespace hk {

constexpr int SEQ = 2048, DM = 512, FF = 1376, FFP = 1536;
constexpr int NCTA = 132;
constexpr int NTHREADS = 384;
constexpr uint32_t SLOT = 16384;
constexpr uint32_t OFF_A = 0, OFF_B = 8 * SLOT, OFF_MISC = 14 * SLOT;
constexpr uint32_t BAR_FULLA = OFF_MISC + 0, BAR_EMPTYA = OFF_MISC + 64, BAR_FULLB = OFF_MISC + 128,
                   BAR_EMPTYB = OFF_MISC + 176, BAR_CS1 = OFF_MISC + 224, BAR_CS3 = OFF_MISC + 232,
                   BAR_CSQ = OFF_MISC + 240, BAR_CSV = OFF_MISC + 248,
                   BAR_STG = OFF_MISC + 256,
                   BAR_KVW = OFF_MISC + 280, BAR_KVR = OFF_MISC + 288;
constexpr uint32_t OFF_CS1 = OFF_MISC + 384;
constexpr uint32_t OFF_CS3 = OFF_CS1 + 1024;
constexpr uint32_t OFF_XST = OFF_CS3;
constexpr uint32_t SMEM_BYTES = OFF_CS3 + 1536;
#define KVS(j) ((j) == 3 ? 2 : 3)
#define KORD(i, j) ((i) == 0 ? (j) : (i) - ((i) <= (j)))
constexpr int NB = 6;
constexpr int AHEAD = 3;

constexpr int ACC_KV = 0, ACC_Z = 2048, ACC_SIZE = 2176;

__device__ __align__(1024) __nv_bfloat16 g_o[SEQ * DM];
__device__ __align__(1024) __nv_bfloat16 g_h[SEQ * DM];
__device__ __align__(1024) __nv_bfloat16 g_hh[SEQ * FFP];
__device__ __align__(128) unsigned long long g_hstat[SEQ * 16];
__device__ __align__(128) unsigned long long g_xstat[SEQ * 2];
__device__ __align__(128) float g_acc[8 * ACC_SIZE];
__device__ __align__(128) unsigned g_cnt[8 * 32];
__device__ __align__(128) unsigned long long g_cs[8 * 6 * 128];
__device__ __align__(128) unsigned g_flag[16 * 5 * 32];
__device__ unsigned g_epoch = 1;

#define TL(i, pred) do {} while (0)
#define TLG(i, pred) do {} while (0)

struct Params {
    CUtensorMap tx, to, th, thh, twq, two, twg, twu, twd, tout;
    const __nv_bfloat16 *x, *wqkv, *wphi, *wo, *wg, *wu, *wd;
    __nv_bfloat16* out;
    unsigned zero;
    unsigned char role[NCTA];
};

__device__ __forceinline__ uint32_t smem_u32(const void* p) { return (uint32_t)__cvta_generic_to_shared(p); }
__device__ __forceinline__ void mbar_init(uint32_t bar, uint32_t cnt) {
    asm volatile("mbarrier.init.shared::cta.b64 [%0], %1;" ::"r"(bar), "r"(cnt) : "memory");
}
__device__ __forceinline__ void mbar_expect_tx(uint32_t bar, uint32_t bytes) {
    asm volatile("mbarrier.arrive.expect_tx.shared::cta.b64 _, [%0], %1;" ::"r"(bar), "r"(bytes) : "memory");
}
__device__ __forceinline__ void mbar_arrive(uint32_t bar) {
    asm volatile("mbarrier.arrive.shared::cta.b64 _, [%0];" ::"r"(bar) : "memory");
}
__device__ __forceinline__ void mbar_arrive_if(uint32_t bar, bool pred) {
    asm volatile("{.reg .pred p; setp.ne.u32 p, %1, 0; @p mbarrier.arrive.shared::cta.b64 _, [%0];}" ::"r"(bar), "r"((uint32_t)pred) : "memory");
}
__device__ __forceinline__ bool mbar_try(uint32_t bar, uint32_t parity) {
    uint32_t ok;
    asm volatile("{.reg .pred p; mbarrier.try_wait.parity.shared::cta.b64 p, [%1], %2; selp.u32 %0,1,0,p;}"
                 : "=r"(ok) : "r"(bar), "r"(parity) : "memory");
    return ok;
}
__device__ __forceinline__ bool mbar_test(uint32_t bar, uint32_t parity) {
    uint32_t ok;
    asm volatile("{.reg .pred p; mbarrier.test_wait.parity.shared::cta.b64 p, [%1], %2; selp.u32 %0,1,0,p;}"
                 : "=r"(ok) : "r"(bar), "r"(parity) : "memory");
    return ok;
}
__device__ __forceinline__ void trap_if_gt(uint32_t v, uint32_t lim) {
    asm volatile("{.reg .pred p; setp.gt.u32 p, %0, %1; @p trap;}" ::"r"(v), "r"(lim));
}
__device__ __forceinline__ void mbar_wait(uint32_t bar, uint32_t parity) {
    asm volatile("{\n"
                 ".reg .pred P1, P2;\n"
                 ".reg .u32 c;\n"
                 "mov.u32 c, 0;\n"
                 "LAB_WAIT:\n"
                 "mbarrier.try_wait.parity.shared::cta.b64 P1, [%0], %1;\n"
                 "@P1 bra LAB_DONE;\n"
                 "add.u32 c, c, 1;\n"
                 "setp.gt.u32 P2, c, 4194304;\n"
                 "@P2 trap;\n"
                 "bra LAB_WAIT;\n"
                 "LAB_DONE:\n"
                 "}" ::"r"(bar), "r"(parity) : "memory");
}
__device__ __forceinline__ void mbar_waitc(uint32_t bar, uint32_t parity) {
    asm volatile("{\n"
                 ".reg .pred P1;\n"
                 "LAB_WAIT:\n"
                 "mbarrier.try_wait.parity.shared::cta.b64 P1, [%0], %1;\n"
                 "@!P1 bra LAB_WAIT;\n"
                 "}" ::"r"(bar), "r"(parity) : "memory");
}
__device__ __forceinline__ void tma2d(uint32_t dst, const CUtensorMap* tm, uint32_t bar, int c0, int c1) {
    asm volatile("cp.async.bulk.tensor.2d.shared::cluster.global.mbarrier::complete_tx::bytes [%0], [%1, {%3, %4}], [%2];"
                 ::"r"(dst), "l"(tm), "r"(bar), "r"(c0), "r"(c1) : "memory");
}
__device__ __forceinline__ void tma2d_mc(uint32_t dst, const CUtensorMap* tm, uint32_t bar, int c0, int c1) {
    asm volatile("cp.async.bulk.tensor.2d.shared::cluster.global.mbarrier::complete_tx::bytes.multicast::cluster [%0], [%1, {%3, %4}], [%2], %5;"
                 ::"r"(dst), "l"(tm), "r"(bar), "r"(c0), "r"(c1), "h"((uint16_t)3) : "memory");
}
__device__ __forceinline__ uint32_t mapa(uint32_t addr, uint32_t rank) {
    uint32_t r; asm("mapa.shared::cluster.u32 %0, %1, %2;" : "=r"(r) : "r"(addr), "r"(rank)); return r;
}
__device__ __forceinline__ void mbar_arrive_cl_if(uint32_t cbar, bool pred) {
    asm volatile("{.reg .pred p; setp.ne.u32 p, %1, 0; @p mbarrier.arrive.shared::cluster.b64 _, [%0];}" ::"r"(cbar), "r"((uint32_t)pred) : "memory");
}
__device__ __forceinline__ bool elect_one() {
    uint32_t ok;
    asm volatile("{.reg .pred p; elect.sync _|p, 0xffffffff; selp.u32 %0, 1, 0, p;}" : "=r"(ok));
    return ok;
}
__device__ __forceinline__ void prefetch_tmap(const CUtensorMap* tm) {
    asm volatile("prefetch.tensormap [%0];" ::"l"(tm) : "memory");
}
__device__ __forceinline__ void prefetch_l2(const void* p, uint32_t bytes) {
    asm volatile("cp.async.bulk.prefetch.L2.global [%0], %1;" ::"l"(p), "r"(bytes) : "memory");
}
__device__ __forceinline__ unsigned ld_acquire(const unsigned* p) {
    unsigned v; asm volatile("ld.acquire.gpu.global.u32 %0, [%1];" : "=r"(v) : "l"(p) : "memory"); return v;
}
__device__ __forceinline__ uint4 ld_acquire4(const unsigned* p) {
    uint4 v;
    asm volatile("ld.acquire.gpu.global.v4.u32 {%0,%1,%2,%3}, [%4];" : "=r"(v.x), "=r"(v.y), "=r"(v.z), "=r"(v.w) : "l"(p) : "memory");
    return v;
}
__device__ __forceinline__ unsigned ld_relaxed(const unsigned* p) {
    unsigned v; asm volatile("ld.relaxed.gpu.global.u32 %0, [%1];" : "=r"(v) : "l"(p)); return v;
}
__device__ __forceinline__ void st_relaxed(unsigned* p, unsigned v) {
    asm volatile("st.relaxed.gpu.global.u32 [%0], %1;" ::"l"(p), "r"(v) : "memory");
}
__device__ __forceinline__ void red_relaxed(unsigned* p, unsigned v) {
    asm volatile("red.relaxed.gpu.global.add.u32 [%0], %1;" ::"l"(p), "r"(v) : "memory");
}
__device__ __forceinline__ void fence_gpu() { asm volatile("fence.acq_rel.gpu;" ::: "memory"); }
__device__ __forceinline__ void fence_async_smem() { asm volatile("fence.proxy.async.shared::cta;" ::: "memory"); }
__device__ __forceinline__ void fence_async_global() { asm volatile("fence.proxy.async.global;" ::: "memory"); }
__device__ __forceinline__ uint32_t readback(const void* p) {
    uint32_t v; asm volatile("ld.relaxed.gpu.global.u32 %0, [%1];" : "=r"(v) : "l"(p) : "memory"); return v;
}
__device__ __forceinline__ void wait_count(const unsigned* p, unsigned target) {
    uint32_t it = 0;
    while ((int)(readback(p) - target) < 0) trap_if_gt(++it, 1u << 22);
}
__device__ __forceinline__ void wait_count_warp(const unsigned* p, unsigned target) {
    uint32_t it = 0;
    while (__any_sync(0xffffffffu, (int)(readback(p) - target) < 0)) trap_if_gt(++it, 1u << 22);
}
__device__ __forceinline__ void red_f32(float* p, float a) {
    asm volatile("red.relaxed.gpu.global.add.f32 [%0], %1;" ::"l"(p), "f"(a) : "memory");
}
__device__ __forceinline__ void red_f32x2(float* p, float a, float b) {
    asm volatile("red.relaxed.gpu.global.add.v2.f32 [%0], {%1, %2};" ::"l"(p), "f"(a), "f"(b) : "memory");
}
__device__ __forceinline__ void red_f32x4(float* p, float a, float b, float c, float d) {
    asm volatile("red.relaxed.gpu.global.add.v4.f32 [%0], {%1, %2, %3, %4};" ::"l"(p), "f"(a), "f"(b), "f"(c), "f"(d) : "memory");
}
__device__ __forceinline__ float4 ld_l2_f4(const float* p) {
    float4 v;
    asm volatile("ld.relaxed.gpu.global.v4.f32 {%0,%1,%2,%3}, [%4];" : "=f"(v.x), "=f"(v.y), "=f"(v.z), "=f"(v.w) : "l"(p) : "memory");
    return v;
}
__device__ __forceinline__ float2 ld_l2_f2(const float* p) {
    float2 v;
    asm volatile("ld.relaxed.gpu.global.v2.f32 {%0,%1}, [%2];" : "=f"(v.x), "=f"(v.y) : "l"(p) : "memory");
    return v;
}
__device__ __forceinline__ float ld_l2_f(const float* p) {
    float v;
    asm volatile("ld.relaxed.gpu.global.f32 %0, [%1];" : "=f"(v) : "l"(p) : "memory");
    return v;
}
__device__ __forceinline__ uint4 ldg_nc(const void* p) {
    uint4 v;
    asm volatile("ld.global.nc.L1::no_allocate.v4.u32 {%0,%1,%2,%3}, [%4];" : "=r"(v.x), "=r"(v.y), "=r"(v.z), "=r"(v.w) : "l"(p));
    return v;
}
__device__ __forceinline__ void stg128(void* p, uint32_t a, uint32_t b, uint32_t c, uint32_t d) {
    asm volatile("st.global.v4.u32 [%0], {%1,%2,%3,%4};" ::"l"(p), "r"(a), "r"(b), "r"(c), "r"(d) : "memory");
}
__device__ __forceinline__ uint4 lds128(uint32_t a) {
    uint4 v;
    asm volatile("ld.shared.v4.u32 {%0,%1,%2,%3}, [%4];" : "=r"(v.x), "=r"(v.y), "=r"(v.z), "=r"(v.w) : "r"(a) : "memory");
    return v;
}
__device__ __forceinline__ float2 lds_f2(uint32_t a) {
    float2 v;
    asm volatile("ld.shared.v2.f32 {%0,%1}, [%2];" : "=f"(v.x), "=f"(v.y) : "r"(a) : "memory");
    return v;
}
__device__ __forceinline__ void sts_f2(uint32_t a, float x, float y) {
    asm volatile("st.shared.v2.f32 [%0], {%1,%2};" ::"r"(a), "f"(x), "f"(y) : "memory");
}
__device__ __forceinline__ void sts64(uint32_t a, uint32_t x, uint32_t y) {
    asm volatile("st.shared.v2.u32 [%0], {%1,%2};" ::"r"(a), "r"(x), "r"(y) : "memory");
}
__device__ __forceinline__ void sts128(uint32_t a, uint32_t x, uint32_t y, uint32_t z, uint32_t w) {
    asm volatile("st.shared.v4.u32 [%0], {%1,%2,%3,%4};" ::"r"(a), "r"(x), "r"(y), "r"(z), "r"(w) : "memory");
}
__device__ __forceinline__ void stsm4(uint32_t a, uint32_t r0, uint32_t r1, uint32_t r2, uint32_t r3) {
    asm volatile("stmatrix.sync.aligned.m8n8.x4.shared.b16 [%0], {%1,%2,%3,%4};" ::"r"(a), "r"(r0), "r"(r1), "r"(r2), "r"(r3) : "memory");
}
__device__ __forceinline__ void stsm4t(uint32_t a, uint32_t r0, uint32_t r1, uint32_t r2, uint32_t r3) {
    asm volatile("stmatrix.sync.aligned.m8n8.x4.trans.shared.b16 [%0], {%1,%2,%3,%4};" ::"r"(a), "r"(r0), "r"(r1), "r"(r2), "r"(r3) : "memory");
}
__device__ __forceinline__ void tma_store2d(const CUtensorMap* tm, uint32_t src, int c0, int c1) {
    asm volatile("cp.async.bulk.tensor.2d.global.shared::cta.bulk_group [%0, {%2, %3}], [%1];" ::"l"(tm), "r"(src), "r"(c0), "r"(c1) : "memory");
    asm volatile("cp.async.bulk.commit_group;" ::: "memory");
}
__device__ __forceinline__ void ldsm4(uint32_t a, uint32_t& r0, uint32_t& r1, uint32_t& r2, uint32_t& r3) {
    asm volatile("ldmatrix.sync.aligned.m8n8.x4.shared.b16 {%0,%1,%2,%3}, [%4];" : "=r"(r0), "=r"(r1), "=r"(r2), "=r"(r3) : "r"(a) : "memory");
}
__device__ __forceinline__ void ldsm4t(uint32_t a, uint32_t& r0, uint32_t& r1, uint32_t& r2, uint32_t& r3) {
    asm volatile("ldmatrix.sync.aligned.m8n8.x4.trans.shared.b16 {%0,%1,%2,%3}, [%4];" : "=r"(r0), "=r"(r1), "=r"(r2), "=r"(r3) : "r"(a) : "memory");
}
__device__ __forceinline__ void mma16816(float* c, const uint32_t* a, uint32_t b0, uint32_t b1) {
    asm("mma.sync.aligned.m16n8k16.row.col.f32.bf16.bf16.f32 {%0,%1,%2,%3}, {%4,%5,%6,%7}, {%8,%9}, {%0,%1,%2,%3};"
                 : "+f"(c[0]), "+f"(c[1]), "+f"(c[2]), "+f"(c[3])
                 : "r"(a[0]), "r"(a[1]), "r"(a[2]), "r"(a[3]), "r"(b0), "r"(b1));
}
__device__ __forceinline__ uint32_t pack_bf16(float lo, float hi) {
    uint32_t r; asm("cvt.rn.bf16x2.f32 %0, %1, %2;" : "=r"(r) : "f"(hi), "f"(lo)); return r;
}
__device__ __forceinline__ float bf_lo(uint32_t w) { return __uint_as_float(w << 16); }
__device__ __forceinline__ float bf_hi(uint32_t w) { return __uint_as_float(w & 0xffff0000u); }
__device__ __forceinline__ float ex2(float x) { float r; asm("ex2.approx.ftz.f32 %0, %1;" : "=f"(r) : "f"(x)); return r; }
__device__ __forceinline__ float rcp(float x) { float r; asm("rcp.approx.ftz.f32 %0, %1;" : "=f"(r) : "f"(x)); return r; }
__device__ __forceinline__ void bar_sync(int id, int n) { asm volatile("bar.sync %0, %1;" ::"r"(id), "r"(n) : "memory"); }

typedef unsigned long long desc_t;
__device__ __forceinline__ desc_t desc_lo(uint32_t addr) { return (desc_t)(((addr & 0x3FFFF) >> 4) | (512u << 16)) | (0x40000040ull << 32); }
__device__ __forceinline__ void wg_fence() { asm volatile("wgmma.fence.sync.aligned;" ::: "memory"); }
__device__ __forceinline__ void wg_commit() { asm volatile("wgmma.commit_group.sync.aligned;" ::: "memory"); }
template <int N> __device__ __forceinline__ void wg_wait() { asm volatile("wgmma.wait_group.sync.aligned %0;" ::"n"(N) : "memory"); }
template <int N> __device__ __forceinline__ void fence_acc(float* d) {
#pragma unroll
    for (int i = 0; i < N; i++) asm volatile("" : "+f"(d[i])::"memory");
}
#define R4(o) "+f"(d[o + 0]), "+f"(d[o + 1]), "+f"(d[o + 2]), "+f"(d[o + 3])
#define R8(o) R4(o), R4(o + 4)
__device__ __forceinline__ void wgmma_n128(float* d, desc_t da, desc_t db, int sc) {
    asm volatile("{.reg .pred p; setp.ne.b32 p, %66, 0;\n"
                 "wgmma.mma_async.sync.aligned.m64n128k16.f32.bf16.bf16 {%0,%1,%2,%3,%4,%5,%6,%7,%8,%9,%10,%11,%12,%13,%14,%15,%16,%17,%18,%19,%20,%21,%22,%23,%24,%25,%26,%27,%28,%29,%30,%31,"
                 "%32,%33,%34,%35,%36,%37,%38,%39,%40,%41,%42,%43,%44,%45,%46,%47,%48,%49,%50,%51,%52,%53,%54,%55,%56,%57,%58,%59,%60,%61,%62,%63}, %64, %65, p, 1, 1, 0, 1;}"
                 : R8(0), R8(8), R8(16), R8(24), R8(32), R8(40), R8(48), R8(56)
                 : "l"(da), "l"(db), "r"(sc));
}
__device__ __forceinline__ void wgmma_n112(float* d, desc_t da, desc_t db, int sc) {
    asm volatile("{.reg .pred p; setp.ne.b32 p, %58, 0;\n"
                 "wgmma.mma_async.sync.aligned.m64n112k16.f32.bf16.bf16 {%0,%1,%2,%3,%4,%5,%6,%7,%8,%9,%10,%11,%12,%13,%14,%15,%16,%17,%18,%19,%20,%21,%22,%23,%24,%25,%26,%27,%28,%29,%30,%31,%32,%33,%34,%35,%36,%37,%38,%39,%40,%41,%42,%43,%44,%45,%46,%47,%48,%49,%50,%51,%52,%53,%54,%55}, %56, %57, p, 1, 1, 0, 1;}"
                 : R8(0), R8(8), R8(16), R8(24), R8(32), R8(40), R8(48)
                 : "l"(da), "l"(db), "r"(sc));
}
__device__ __forceinline__ void wgmma_n128_tn(float* d, desc_t da, desc_t db, int sc) {
    asm volatile("{.reg .pred p; setp.ne.b32 p, %66, 0;\n"
                 "wgmma.mma_async.sync.aligned.m64n128k16.f32.bf16.bf16 {%0,%1,%2,%3,%4,%5,%6,%7,%8,%9,%10,%11,%12,%13,%14,%15,%16,%17,%18,%19,%20,%21,%22,%23,%24,%25,%26,%27,%28,%29,%30,%31,%32,%33,%34,%35,%36,%37,%38,%39,%40,%41,%42,%43,%44,%45,%46,%47,%48,%49,%50,%51,%52,%53,%54,%55,%56,%57,%58,%59,%60,%61,%62,%63}, %64, %65, p, 1, 1, 1, 0;}"
                 : R8(0), R8(8), R8(16), R8(24), R8(32), R8(40), R8(48), R8(56)
                 : "l"(da), "l"(db), "r"(sc));
}
__device__ __forceinline__ void wgmma_n64(float* d, desc_t da, desc_t db, int sc) {
    asm volatile("{.reg .pred p; setp.ne.b32 p, %34, 0;\n"
                 "wgmma.mma_async.sync.aligned.m64n64k16.f32.bf16.bf16 {%0,%1,%2,%3,%4,%5,%6,%7,%8,%9,%10,%11,%12,%13,%14,%15,%16,%17,%18,%19,%20,%21,%22,%23,%24,%25,%26,%27,%28,%29,%30,%31}, %32, %33, p, 1, 1, 0, 1;}"
                 : R8(0), R8(8), R8(16), R8(24)
                 : "l"(da), "l"(db), "r"(sc));
}
__device__ __forceinline__ void wgmma_n40_tt(float* d, desc_t da, desc_t db, int sc) {
    asm volatile("{.reg .pred p; setp.ne.b32 p, %22, 0;\n"
                 "wgmma.mma_async.sync.aligned.m64n40k16.f32.bf16.bf16 {%0,%1,%2,%3,%4,%5,%6,%7,%8,%9,%10,%11,%12,%13,%14,%15,%16,%17,%18,%19}, %20, %21, p, 1, 1, 1, 1;}"
                 : R8(0), R8(8), R4(16)
                 : "l"(da), "l"(db), "r"(sc));
}

__device__ __forceinline__ void wgmma_n8_tt(float* d, desc_t da, desc_t db, int sc) {
    asm volatile("{.reg .pred p; setp.ne.b32 p, %6, 0;\n"
                 "wgmma.mma_async.sync.aligned.m64n8k16.f32.bf16.bf16 {%0,%1,%2,%3}, %4, %5, p, 1, 1, 1, 1;}"
                 : R4(0)
                 : "l"(da), "l"(db), "r"(sc));
}

__device__ __forceinline__ uint32_t atom_f32x2(float* p, float a, float b) {
    float x, y;
    asm volatile("atom.relaxed.gpu.global.add.v2.f32 {%0,%1}, [%2], {%3,%4};" : "=f"(x), "=f"(y) : "l"(p), "f"(a), "f"(b) : "memory");
    return __float_as_uint(x);
}
__device__ __forceinline__ uint32_t atom_f32_if(float* p, float a, bool pred) {
    float x = 0.f;
    asm volatile("{.reg .pred p; setp.ne.u32 p, %3, 0; @p atom.relaxed.gpu.global.add.f32 %0, [%1], %2;}" : "+f"(x) : "l"(p), "f"(a), "r"((uint32_t)pred) : "memory");
    return __float_as_uint(x);
}
__device__ __forceinline__ void signal_after(unsigned* cnt, uint32_t ack, uint32_t zero, bool pred) {
    asm volatile("{.reg .pred p; setp.ne.u32 p, %2, 0; @p red.relaxed.gpu.global.add.u32 [%0], %1;}"
                 ::"l"(cnt), "r"((ack & zero) + 1), "r"((uint32_t)pred) : "memory");
}
__device__ __forceinline__ void signal_late(unsigned* cnt, const uint32_t* a, uint32_t zero, bool pred) {
    uint32_t v;
    asm volatile("{.reg .b32 t; lop3.b32 t, %1, %2, %3, 0xfe; or.b32 %0, t, %4;}"
                 : "=r"(v) : "r"(a[0]), "r"(a[1]), "r"(a[2]), "r"(a[3]));
    signal_after(cnt, v, zero, pred);
}
__device__ __forceinline__ void red_f32_if(float* p, float a, bool pred) {
    asm volatile("{.reg .pred p; setp.ne.u32 p, %2, 0; @p red.relaxed.gpu.global.add.f32 [%0], %1;}" ::"l"(p), "f"(a), "r"((uint32_t)pred) : "memory");
}
__device__ __forceinline__ void stg_f2_if(float* p, float a, float b, bool pred) {
    asm volatile("{.reg .pred p; setp.ne.u32 p, %3, 0; @p st.global.v2.f32 [%0], {%1,%2};}" ::"l"(p), "f"(a), "f"(b), "r"((uint32_t)pred) : "memory");
}
__device__ __forceinline__ void stg64(void* p, uint32_t a, uint32_t b) {
    asm volatile("st.global.v2.u32 [%0], {%1,%2};" ::"l"(p), "r"(a), "r"(b) : "memory");
}
__device__ __forceinline__ void mma16816_z(float* c, const uint32_t* a, uint32_t b0, uint32_t b1) {
    asm("mma.sync.aligned.m16n8k16.row.col.f32.bf16.bf16.f32 {%0,%1,%2,%3}, {%4,%5,%6,%7}, {%8,%9}, {%10,%10,%10,%10};"
                 : "=f"(c[0]), "=f"(c[1]), "=f"(c[2]), "=f"(c[3])
                 : "r"(a[0]), "r"(a[1]), "r"(a[2]), "r"(a[3]), "r"(b0), "r"(b1), "f"(0.f));
}
__device__ __forceinline__ uint32_t max2(uint32_t a, uint32_t b) { uint32_t r; asm("max.bf16x2 %0, %1, %2;" : "=r"(r) : "r"(a), "r"(b)); return r; }
__device__ __forceinline__ uint32_t min2(uint32_t a, uint32_t b) { uint32_t r; asm("min.bf16x2 %0, %1, %2;" : "=r"(r) : "r"(a), "r"(b)); return r; }
__device__ __forceinline__ void bar_arrive(int id, int n) { asm volatile("bar.arrive %0, %1;" ::"r"(id), "r"(n) : "memory"); }
__device__ __forceinline__ void mbar_arrive_n_if(uint32_t bar, uint32_t n, bool pred) {
    asm volatile("{.reg .pred p; setp.ne.u32 p, %1, 0; @p mbarrier.arrive.shared::cta.b64 _, [%0], %2;}" ::"r"(bar), "r"((uint32_t)pred), "r"(n) : "memory");
}
__device__ __forceinline__ float4 lds_f4(uint32_t a) {
    float4 v;
    asm volatile("ld.shared.v4.f32 {%0,%1,%2,%3}, [%4];" : "=f"(v.x), "=f"(v.y), "=f"(v.z), "=f"(v.w) : "r"(a) : "memory");
    return v;
}
__device__ __forceinline__ uint4 ld_tagged(const unsigned long long* p) {
    unsigned long long a, b;
    asm volatile("ld.acquire.gpu.global.v2.b64 {%0,%1}, [%2];" : "=l"(a), "=l"(b) : "l"(p) : "memory");
    return make_uint4((unsigned)a, (unsigned)(a >> 32), (unsigned)b, (unsigned)(b >> 32));
}
__device__ __forceinline__ uint4 ld_tagged_rlx(const unsigned long long* p) {
    unsigned long long a, b;
    asm volatile("ld.relaxed.gpu.global.v2.b64 {%0,%1}, [%2];" : "=l"(a), "=l"(b) : "l"(p) : "memory");
    return make_uint4((unsigned)a, (unsigned)(a >> 32), (unsigned)b, (unsigned)(b >> 32));
}
__device__ __forceinline__ void st_tagged_if(unsigned long long* p, float a, float b, unsigned tag, bool pred) {
    const unsigned long long t = (unsigned long long)tag << 32;
    asm volatile("{.reg .pred p; setp.ne.u32 p, %3, 0; @p st.relaxed.gpu.global.v2.b64 [%0], {%1,%2};}"
                 ::"l"(p), "l"(t | __float_as_uint(a)), "l"(t | __float_as_uint(b)), "r"((uint32_t)pred) : "memory");
}

__device__ __forceinline__ void store_tile(uint32_t tile_rows, __nv_bfloat16* gdst, const uint32_t* lo, const uint32_t* hi, int lane, uint32_t* ack) {
    const int r = lane & 15;
#pragma unroll
    for (int b = 0; b < 4; b++)
        stsm4(tile_rows + r * 128 + (((2 * b + (lane >> 4)) ^ (r & 7)) << 4), lo[2 * b], hi[2 * b], lo[2 * b + 1], hi[2 * b + 1]);
    fence_async_smem();
    __syncwarp();
#pragma unroll
    for (int i = 0; i < 4; i++) {
        const int rr = 4 * i + (lane >> 3);
        const uint4 v = lds128(tile_rows + rr * 128 + (((lane & 7) ^ (rr & 7)) << 4));
        stg128(gdst + rr * DM + (lane & 7) * 8, v.x, v.y, v.z, v.w);
    }
#pragma unroll
    for (int i = 0; i < 4; i++) ack[i] = readback(gdst + (4 * i + (lane >> 3)) * DM + (lane & 7) * 8);
}

__device__ __forceinline__ void feature_maps(const uint32_t* a, const uint32_t* wb, float c0, float c1, uint32_t* plus, uint32_t* minus) {
    uint32_t P[16], mx[4], mn[4];
#pragma unroll
    for (int h = 0; h < 4; h++) {
        float p[8];
        mma16816_z(p, a + 4 * h, wb[4 * h], wb[4 * h + 1]);
        mma16816_z(p + 4, a + 4 * h, wb[4 * h + 2], wb[4 * h + 3]);
        P[4 * h] = pack_bf16(p[0], p[2]); P[4 * h + 1] = pack_bf16(p[1], p[3]);
        P[4 * h + 2] = pack_bf16(p[4], p[6]); P[4 * h + 3] = pack_bf16(p[5], p[7]);
        mx[h] = max2(max2(P[4 * h], P[4 * h + 1]), max2(P[4 * h + 2], P[4 * h + 3]));
        mn[h] = min2(min2(P[4 * h], P[4 * h + 1]), min2(P[4 * h + 2], P[4 * h + 3]));
    }
#pragma unroll
    for (int s = 1; s <= 2; s <<= 1) {
        uint32_t tx[4], tn[4];
#pragma unroll
        for (int h = 0; h < 4; h++) { tx[h] = __shfl_xor_sync(0xffffffffu, mx[h], s); tn[h] = __shfl_xor_sync(0xffffffffu, mn[h], s); }
#pragma unroll
        for (int h = 0; h < 4; h++) { mx[h] = max2(mx[h], tx[h]); mn[h] = min2(mn[h], tn[h]); }
    }
#pragma unroll
    for (int h = 0; h < 4; h++) {
        const float mx0 = bf_lo(mx[h]) * c0, mx1 = bf_hi(mx[h]) * c1, mn0 = bf_lo(mn[h]) * c0, mn1 = bf_hi(mn[h]) * c1;
        float ep[8], em[8];
#pragma unroll
        for (int i = 0; i < 8; i++) {
            const bool r1 = (i & 2);
            const uint32_t w = P[4 * h + (i >> 2) * 2 + (i & 1)];
            const float p = r1 ? bf_hi(w) : bf_lo(w);
            ep[i] = ex2(fmaf(p, r1 ? c1 : c0, r1 ? -mx1 : -mx0));
            em[i] = ex2(fmaf(p, r1 ? -c1 : -c0, r1 ? mn1 : mn0));
        }
        float sp[4], sm[4];
        uint32_t tp[4], tm[4];
#pragma unroll
        for (int i = 0; i < 4; i++) { tp[i] = pack_bf16(ep[2 * i], ep[2 * i + 1]); tm[i] = pack_bf16(em[2 * i], em[2 * i + 1]); }
        mma16816_z(sp, tp, 0x3f803f80u, 0x3f803f80u);
        mma16816_z(sm, tm, 0x3f803f80u, 0x3f803f80u);
        const float r0 = rcp(sp[0] * sm[0]), r1 = rcp(sp[2] * sm[2]);
        const float rs[4] = {r0 * sm[0], r1 * sm[2], r0 * sp[0], r1 * sp[2]};
#pragma unroll
        for (int i = 0; i < 4; i++) {
            plus[4 * h + i] = pack_bf16(ep[2 * i] * rs[i & 1], ep[2 * i + 1] * rs[i & 1]);
            minus[4 * h + i] = pack_bf16(em[2 * i] * rs[2 + (i & 1)], em[2 * i + 1] * rs[2 + (i & 1)]);
        }
    }
}

template <bool SCALE>
__device__ __forceinline__ void ln_frag(const float* acc, uint32_t cs_addr, float rs0, float nm0, float rs1, float nm1, uint32_t* a) {
    const float2 c0 = lds_f2(cs_addr), c1 = lds_f2(cs_addr + 32);
    const float s0 = SCALE ? rs0 : 1.f, s1 = SCALE ? rs1 : 1.f;
    a[0] = pack_bf16(fmaf(nm0, c0.x, acc[0]) * s0, fmaf(nm0, c0.y, acc[1]) * s0);
    a[1] = pack_bf16(fmaf(nm1, c0.x, acc[2]) * s1, fmaf(nm1, c0.y, acc[3]) * s1);
    a[2] = pack_bf16(fmaf(nm0, c1.x, acc[4]) * s0, fmaf(nm0, c1.y, acc[5]) * s0);
    a[3] = pack_bf16(fmaf(nm1, c1.x, acc[6]) * s1, fmaf(nm1, c1.y, acc[7]) * s1);
}

template <int UP>
__device__ __forceinline__ uint32_t hh_pair(const float* ag, float4 cs, float nmean) {
    const float g0 = fmaf(nmean, cs.x, ag[0]), g1 = fmaf(nmean, cs.y, ag[1]);
    const float u0 = fmaf(nmean, cs.z, ag[UP]), u1 = fmaf(nmean, cs.w, ag[UP + 1]);
    return pack_bf16(g0 * u0, g1 * u1);
}
template <int NTP>
__device__ __forceinline__ void hh_stage(const float* acc, const float4* cs, float nm0, float nm1, uint32_t stg, int lane) {
#pragma unroll
    for (int tp = 0; tp < NTP; tp++)
        stsm4(stg + (lane & 15) * 128 + (((2 * tp + (lane >> 4)) ^ (lane & 7)) << 4), hh_pair<32>(acc + 8 * tp, cs[2 * tp], nm0),
              hh_pair<32>(acc + 8 * tp + 2, cs[2 * tp], nm1), hh_pair<32>(acc + 8 * tp + 4, cs[2 * tp + 1], nm0),
              hh_pair<32>(acc + 8 * tp + 6, cs[2 * tp + 1], nm1));
    fence_async_smem();
    __syncwarp();
}

struct Ring {
    int slot; uint32_t phase;
    __device__ __forceinline__ void adv() { if (++slot == NB) { slot = 0; phase ^= 1; } }
};

__global__ void __cluster_dims__(2, 1, 1) __launch_bounds__(NTHREADS, 1) fused_kernel(const __grid_constant__ Params P) {
    extern __shared__ __align__(1024) uint8_t smem_raw[];
    const uint32_t sb = smem_u32(smem_raw);
    const int tid = threadIdx.x, lane = tid & 31;
    const int warp = __shfl_sync(0xffffffffu, tid >> 5, 0);
    const unsigned role = P.role[blockIdx.x], rank = blockIdx.x & 1;
    const int m = role >> 3, j = role & 7;
    const bool helper = role >= 128;

    TL(0, tid == 0); TLG(0, tid == 0);
    float* const acc_j = g_acc + j * ACC_SIZE;
    unsigned* const cnt_j = g_cnt + j * 32;

    if (__builtin_expect(warp >= 8, 1)) {
        asm volatile("setmaxnreg.dec.sync.aligned.u32 72;");
        if (elect_one()) {
            if (warp == 8) {
                if (!helper) {
#pragma unroll
                    for (int i = 0; i < NB; i++) mbar_init(sb + BAR_FULLB + 8 * i, 1);
#pragma unroll
                    for (int i = 0; i < 2; i++) {
                        mbar_expect_tx(sb + BAR_FULLB + 8 * i, SLOT);
                        tma2d(sb + OFF_B + i * SLOT, &P.twq, sb + BAR_FULLB + 8 * i, DM + 64 * j, 64 * i);
                        tma2d(sb + OFF_B + i * SLOT + 8192, &P.twq, sb + BAR_FULLB + 8 * i, 2 * DM + 64 * j, 64 * i);
                    }
                }
            } else if (warp == 9) {
#pragma unroll
                for (int i = 0; i < 8; i++) mbar_init(sb + BAR_FULLA + 8 * i, 1);
                if (!helper) {
#pragma unroll
                    for (int i = 0; i < 2; i++) {
                        mbar_expect_tx(sb + BAR_FULLA + 8 * i, SLOT);
                        tma2d(sb + OFF_A + i * SLOT, &P.tx, sb + BAR_FULLA + 8 * i, 64 * i, 128 * m);
                    }
                }
            } else if (warp == 10) {
#pragma unroll
                for (int i = 0; i < 9; i++) mbar_init(sb + BAR_CS1 + 8 * i, i == 0 || i == 8 ? 64 : (i == 1 ? 96 : (i < 4 ? 32 : 8)));
                trap_if_gt(sb & 1023, 0);
            } else {
#pragma unroll
                for (int i = 0; i < 14; i++) mbar_init(sb + (i < 8 ? BAR_EMPTYA : BAR_EMPTYB - 64) + 8 * i, i < 8 ? 8 : 16);
            }
            asm volatile("fence.mbarrier_init.release.cluster;" ::: "memory");
        }
        __syncwarp();
        asm volatile("barrier.cluster.arrive.relaxed.aligned;" ::: "memory");
        const unsigned epoch = ld_relaxed(&g_epoch);
        bar_sync(0, NTHREADS);
        if (helper) {
            if (warp == 8) {
                if (elect_one()) {
#pragma unroll 1
                    for (int i = 0; i < 72; i++) {
                        const uint32_t full = sb + BAR_FULLA + 8 * (i & 7), dst = sb + OFF_A + (i & 7) * SLOT;
                        mbar_wait(sb + BAR_EMPTYA + 8 * (i & 7), ((i >> 3) & 1) ^ 1);
                        mbar_expect_tx(full, SLOT);
                        const bool qkv = i < 24;
                        const int u = (i >> 3) - 3;
                        const int c0 = qkv ? (i < 16 ? DM + 64 * (i & 8) : 0) + 128 * j + 16 * (i & 4) : 176 * (2 * j + (u & 1)) + 64 * (u >> 1);
                        const int r0 = qkv ? 128 * (i & 3) : 64 * (i & 7);
                        tma2d(dst, qkv ? &P.twq : &P.twg, full, c0, r0);
                        tma2d(dst + 8192, qkv ? &P.twq : &P.twu, full, c0, qkv ? r0 + 64 : r0);
                    }
                    prefetch_l2(P.wd + (size_t)j * 176128, 352256);
                }
            }
            return;
        }
        if (warp == 8) {
            asm volatile("barrier.cluster.wait.aligned;" ::: "memory");
            if (elect_one()) {
                if (m >= 6)
                    asm volatile("cp.async.bulk.prefetch.tensor.2d.L2.global [%0, {%1, %2}];" ::"l"(&P.twq), "r"(DM + DM * (m & 1) + 64 * j), "r"(64 * (m >> 1)) : "memory");
                if (j >= 3)
                    asm volatile("cp.async.bulk.prefetch.tensor.2d.L2.global [%0, {%1, %2}];" ::"l"(&P.tx), "r"(64 * j), "r"(128 * m) : "memory");
                Ring r{2, 0};
#pragma unroll 1
                for (int i = 2; i < 59; i++) {
                    const uint32_t full = sb + BAR_FULLB + 8 * r.slot;
                    mbar_wait(sb + BAR_EMPTYB + 8 * r.slot, r.phase ^ 1);
                    if ((i >= 10 && i < 14) || i == 28 || i == 37 || i == 46) {
                        mbar_arrive(full);
                    } else {
                        if (i >= AHEAD && i < 6) mbar_wait(full - 8 * AHEAD, 0);
                        mbar_expect_tx(full, SLOT);
                        const int e = 2 * ((i < 20 ? i : i + 1) & 3) + rank, g8 = i - 20 - (i > 28) - (i > 37);
                        const CUtensorMap* tm = i < 16 ? &P.twq : (i < 20 ? &P.two : (i < 46 ? &P.twg + rank : &P.twd));
                        const int c0 = i < 8 ? DM + DM * rank + 64 * j : ((i >= 20 && i < 46) ? 176 * j + 8 * (g8 & ~7) : 64 * j);
                        const int r0 = i < 8 ? 64 * i : (i < 16 ? 64 * e : (i < 20 ? 64 * KORD(e, j)
                                             : (i < 46 ? 64 * (g8 < 8 ? KORD(g8, j) : g8 & 7) : 176 * e + 64 * ((i - 47) >> 2))));
                        tma2d_mc(sb + OFF_B + r.slot * SLOT + rank * 8192, tm, full, c0, r0);
                    }
                    r.adv();
                }
            }
            return;
        }
        if (warp == 9) {
            if (elect_one()) {
#pragma unroll 1
                for (int i = 2; i < 8; i++) {
                    if (i >= AHEAD + 1) mbar_wait(sb + BAR_FULLA + 8 * (i - AHEAD - 1), 0);
                    mbar_expect_tx(sb + BAR_FULLA + 8 * i, SLOT);
                    tma2d(sb + OFF_A + i * SLOT, &P.tx, sb + BAR_FULLA + 8 * i, 64 * i, 128 * m);
                }
#pragma unroll 1
                for (int i = 1; i < 10; i++) prefetch_tmap(&P.tx + i);
#pragma unroll 1
                for (int r = 1; r < 6; r++) {
                    const CUtensorMap* tm = &P.tx + min(r, 3);
                    const int cstep = r < 3 ? 64 : 192, cbase = r < 3 ? 0 : 64 * (r - 3), skip = r < 3 ? j : 8;
                    if (r < 4) mbar_wait(sb + BAR_EMPTYA + 8 * (skip == 0), (r - 1) & 1);
                    wait_count(g_flag + (m * 5 + r - 1) * 32, epoch * (r < 3 ? 64 : 8));
                    TL(64 + r, true);
#pragma unroll 1
                    for (int t = 0; t < 8; t++) {
                        if (t == skip) continue;
                        mbar_wait(sb + BAR_EMPTYA + 8 * t, (r - 1) & 1);
                        mbar_expect_tx(sb + BAR_FULLA + 8 * t, SLOT);
                        tma2d(sb + OFF_A + t * SLOT, tm, sb + BAR_FULLA + 8 * t, cbase + cstep * t, 128 * m);
                    }
                }
            }
            return;
        }
        const int a = warp - 10;
        {
            const int row = 16 * j + 8 * a + (lane >> 2);
            const uint32_t ra = sb + OFF_A + row * 128;
            float sh = 0.f, s0 = 0.f, s1 = 0.f, q0 = 0.f, q1 = 0.f;
#pragma unroll 1
            for (int kt = 0; kt < 8; kt++) {
                mbar_wait(sb + BAR_FULLA + 8 * kt, 0);
                if (kt == 0) sh = bf_lo(lds128(ra + ((row & 7) << 4)).x);
#pragma unroll
                for (int i = 0; i < 2; i++) {
                    const uint4 v = lds128(ra + kt * SLOT + (((2 * (lane & 3) + i) ^ (row & 7)) << 4));
                    const uint32_t ww[4] = {v.x, v.y, v.z, v.w};
#pragma unroll
                    for (int e = 0; e < 4; e++) {
                        const float d0 = bf_lo(ww[e]) - sh, d1 = bf_hi(ww[e]) - sh;
                        s0 += d0; q0 = fmaf(d0, d0, q0);
                        s1 += d1; q1 = fmaf(d1, d1, q1);
                    }
                }
            }
            s0 += s1; q0 += q1;
#pragma unroll
            for (int o = 1; o <= 2; o <<= 1) { s0 += __shfl_xor_sync(0xffffffffu, s0, o); q0 += __shfl_xor_sync(0xffffffffu, q0, o); }
            const float md = s0 * (1.f / DM);
            const float rs = rsqrtf(fmaxf(q0 * (1.f / DM) - md * md, 0.f) + 1e-5f);
            st_tagged_if(g_xstat + 2 * (128 * m + row), rs, -(sh + md), epoch, (lane & 3) == 0);
        }
        const unsigned long long* cs = g_cs + j * 768 + 2 * lane;
#pragma unroll 1
        for (int c = 0; c < (a ? 5 : 10); c++) {
            if (c == 4) {
                const int t = 32 * a + lane;
                const uint32_t kvs = sb + OFF_A + KVS(j) * SLOT;
                mbar_wait(sb + BAR_KVW, 0);
#pragma unroll 1
                for (int pass = 0; pass < 2; pass++) {
                    float4 v[8];
#pragma unroll
                    for (int i = 0; i < 8; i++) v[i] = ld_l2_f4(acc_j + ACC_KV + 4 * (t + 64 * i));
                    const float2 zz = ld_l2_f2(acc_j + ACC_Z + 2 * t);
#pragma unroll
                    for (int i = 0; i < 8; i++)
                        sts64(kvs + ((t >> 2) + 16 * i) * 48 + (t & 3) * 8, pack_bf16(v[i].x, v[i].y), pack_bf16(v[i].z, v[i].w));
                    const uint32_t z0 = pack_bf16(zz.x, zz.x), z1 = pack_bf16(zz.y, zz.y);
                    sts128(kvs + t * 96 + 32, z0, z0, z0, z0);
                    sts128(kvs + t * 96 + 80, z1, z1, z1, z1);
                    if (pass == 0) {
                        __syncwarp();
                        if (lane == 0) red_relaxed(cnt_j, 1);
                        TL(19, t == 0);
                        wait_count_warp(cnt_j, epoch * 32);
                        TL(14, t == 0);
                    }
                }
                mbar_arrive(sb + BAR_KVR);
                if (a) break;
            }
            if (c == 3 && !a) continue;
            const unsigned long long* src = c < 2 ? g_xstat + 2 * (128 * m + 64 * a + 32 * c + lane) : cs + (c < 4 ? 128 * (a + c - 2) : 128 + 64 * c);
            const uint32_t dst = c < 2 ? OFF_XST + (64 * a + 32 * c + lane) * 8
                                       : (c < 4 ? OFF_CS1 + (c == 2 ? 256 * (a + 1) : 0) + 8 * lane : OFF_CS3 + (32 * ((c - 4) >> 1) + lane) * 16 + 8 * (c & 1));
            uint4 v;
            uint32_t it = 0;
            while (true) {
                v = ld_tagged_rlx(src);
                if (!__any_sync(0xffffffffu, v.y != epoch || v.w != epoch)) break;
                __nanosleep(60);
                trap_if_gt(++it, 1u << 22);
            }
            sts64(sb + dst, v.x, v.z);
            if (c == 2 - a || (a && c > 1) || c == 9) mbar_arrive(sb + (c == 9 ? BAR_CS3 : (c == 2 - a ? BAR_CS1 : (c == 2 ? BAR_CSV : BAR_CSQ))));
        }
        {
            uint32_t it = 0;
            while (__any_sync(0xffffffffu, (int)(readback(g_flag + (m * 5 + 1) * 32) - epoch * 64) < 0)) {
                __nanosleep(200);
                trap_if_gt(++it, 1u << 22);
            }
#pragma unroll 1
            for (int rr = 0; rr < 2; rr++) {
                const int row = 64 * rr + 32 * a + lane;
                uint4 v[8];
                bool bad;
                do {
                    bad = false;
#pragma unroll
                    for (int i = 0; i < 8; i++) v[i] = ld_tagged_rlx(g_hstat + (1024 * m + 128 * i + row) * 2);
#pragma unroll
                    for (int i = 0; i < 8; i++) bad |= v[i].y != epoch || v[i].w != epoch;
                    trap_if_gt(++it, 1u << 22);
                } while (__any_sync(0xffffffffu, bad));
                float mean = 0.f;
#pragma unroll
                for (int i = 0; i < 8; i++) mean += __uint_as_float(v[i].x);
                mean *= 0.125f;
                float m2 = 0.f, dv = 0.f;
#pragma unroll
                for (int i = 0; i < 8; i++) { const float d = __uint_as_float(v[i].x) - mean; m2 += __uint_as_float(v[i].z); dv = fmaf(d, d, dv); }
                sts_f2(sb + OFF_CS1 + row * 8, -mean, rcp(fmaf(dv, 64.f, m2) * (1.f / DM) + 1e-5f));
            }
        }
        mbar_arrive(sb + BAR_CS3);
#pragma unroll 1
        for (int c = a; c < 3; c += 2) {
            const int slot = c == 1 ? 1 : 4;
            mbar_wait(sb + BAR_STG + 8 * c, 0);
            if (elect_one()) {
                tma_store2d(&P.thh, sb + OFF_B + slot * SLOT, 192 * j + 64 * c, 128 * m);
                asm volatile("cp.async.bulk.wait_group.read 0;" ::: "memory");
                mbar_arrive_n_if(sb + BAR_EMPTYB + 8 * slot, 8, true);
                asm volatile("mbarrier.arrive.shared::cluster.b64 _, [%0], 8;" ::"r"(mapa(sb + BAR_EMPTYB + 8 * slot, rank ^ 1)) : "memory");
                asm volatile("cp.async.bulk.wait_group 0;" ::: "memory");
            }
            __syncwarp();
            TL(60 + c, lane == 0);
            uint32_t ack = 0;
#pragma unroll
            for (int i = 0; i < 4; i++) ack |= readback(g_hh + (size_t)(128 * m + 32 * i + lane) * FFP + 192 * j + 64 * c);
            signal_after(g_flag + (m * 5 + 2 + c) * 32, ack, P.zero, lane == 0);
            TL(54 + c, lane == 0);
        }
        return;
    }
    const unsigned epoch = ld_relaxed(&g_epoch);
    uint32_t wraw[16];
    if (!helper) {
        const uint32_t* wp = reinterpret_cast<const uint32_t*>(P.wphi) + (4 * j) * 128 + (lane & 3) * 16 + (lane >> 2);
#pragma unroll
        for (int i = 0; i < 16; i++)
            asm volatile("ld.global.nc.u32 %0, [%1];" : "=r"(wraw[i]) : "l"(wp + (i >> 2) * 128 + ((i >> 1) & 1) * 64 + (i & 1) * 8));
    }
    asm volatile("barrier.cluster.arrive.relaxed.aligned;" ::: "memory");
    asm volatile("setmaxnreg.inc.sync.aligned.u32 216;");
    bar_sync(0, NTHREADS);
    if (helper) {
        if (warp < 4) {
            sts128(sb + OFF_B + 16 * tid, 0x3f803f80u, 0x3f803f80u, 0x3f803f80u, 0x3f803f80u);
            for (int i = tid; i < 2 * ACC_SIZE / 4; i += 128) stg128(g_acc + 2 * j * ACC_SIZE + 4 * i, 0, 0, 0, 0);
            fence_async_smem();
            fence_gpu();
            bar_sync(1, 128);
            float acc[8];
            int i = 0;
#pragma unroll 1
            for (int job = 0; job < 12; job++) {
                const int n = job < 6 ? 4 : 8;
#pragma unroll 1
                for (int t = 0; t < n; t++, i++) {
                    mbar_wait(sb + BAR_FULLA + 8 * (i & 7), (i >> 3) & 1);
                    wg_fence();
#pragma unroll
                    for (int k = 0; k < 8; k++)
                        wgmma_n8_tt(acc + (k & 4), desc_lo(sb + OFF_A) + (i & 7) * (SLOT >> 4) + 128 * k, desc_lo(sb + OFF_B), (t | (k & 3)) != 0);
                    wg_commit();
                    wg_wait<1>();
                    mbar_arrive_n_if(sb + BAR_EMPTYA + 8 * ((i + 7) & 7), 2, lane == 0 && i > 0);
                }
                wg_wait<0>();
                fence_acc<8>(acc);
                const int q = lane & 3;
                const float lo = (q & 1) ? acc[2] : acc[0], hi = (q & 1) ? acc[6] : acc[4];
                const float v = job < 6 ? lo + hi : ((q & 2) ? hi : lo);
                unsigned long long* dst = g_cs + ((2 * j + (job & 1)) * 6 + (job >> 1)) * 128 + (q >> 1) * 64 + 16 * warp + 8 * (q & 1) + (lane >> 2);
                asm volatile("st.relaxed.gpu.global.b64 [%0], %1;" ::"l"(dst), "l"(((unsigned long long)epoch << 32) | __float_as_uint(v)) : "memory");
            }
        }
        return;
    }
    {
        const int w = warp >> 2, wv = warp & 3, g = lane >> 2, q = lane & 3;
        const int row_w = 128 * m + 16 * warp;
        const uint32_t sa = sb + OFF_A + w * 8192;
        const desc_t dA = desc_lo(sa), dB = desc_lo(sb + OFF_B);
        unsigned* const flag_m = g_flag + m * 160;
        const bool l0 = lane == 0, l2 = lane < 2;
        const uint32_t eb = mapa(sb + BAR_EMPTYB, lane & 1);
        asm volatile("barrier.cluster.wait.aligned;" ::: "memory");
        Ring rg{0, 0};
        int prev = 0;

        uint32_t wb[16];
        constexpr float L2E = 1.4426950408889634f;
        const int ch = lane >> 4, sw = lane & 7;
        const uint32_t lrow = (lane & 15) * 128;
        uint32_t fp[16], fm[16];
        {
            float acc[64], accq[32];
#pragma unroll 1
            for (int kt = 0; kt < 8; kt++) {
                mbar_waitc(sb + BAR_FULLA + 8 * kt, 0);
                mbar_waitc(sb + BAR_FULLB + 8 * rg.slot, rg.phase);
                const desc_t da = dA + kt * (SLOT >> 4), db = dB + rg.slot * (SLOT >> 4);
                wg_fence();
#pragma unroll
                for (int k = 0; k < 4; k++) wgmma_n128(acc, da + 2 * k, db + 128 * k, (kt | k) != 0);
                wg_commit();
                wg_wait<1>();
                mbar_arrive_cl_if(eb + 8 * prev, l2 && kt > 0);
                prev = rg.slot; rg.adv();
            }
#pragma unroll
            for (int i = 0; i < 8; i++) {
                wb[(i >> 1) * 4 + (i & 1)] = __byte_perm(wraw[2 * i], wraw[2 * i + 1], 0x5410);
                wb[(i >> 1) * 4 + 2 + (i & 1)] = __byte_perm(wraw[2 * i], wraw[2 * i + 1], 0x7632);
            }
            float2 s0, s1;
            uint32_t a[16];
            wg_wait<0>();
            fence_acc<64>(acc);
            mbar_arrive_cl_if(eb + 8 * prev, l2);
#pragma unroll 1
            for (int it = 0; it < 2; it++) {
                mbar_waitc(sb + BAR_FULLB + 8 * 2, it ^ 1); mbar_waitc(sb + BAR_FULLB + 8 * 3, it ^ 1);
                const desc_t da = dA + it * (4 * SLOT >> 4);
                wg_fence();
#pragma unroll
                for (int k = 0; k < 16; k++) wgmma_n64(accq, da + (k >> 2) * (SLOT >> 4) + (k & 3) * 2, dB + 2 * (SLOT >> 4) + 128 * k, (it | k) != 0);
                wg_commit();
                TL(17 + it, tid == 0);
                mbar_waitc(sb + BAR_CS1 + 16 * it, 0);
                wg_wait<0>();
                fence_acc<32>(accq);
                mbar_arrive_cl_if(eb + 8 * (2 + (lane >> 1)), lane < 4);
                TL(2 + 2 * it, tid == 0);
                if (it == 0) {
                    s0 = lds_f2(sb + OFF_XST + (16 * warp + g) * 8); s1 = lds_f2(sb + OFF_XST + (16 * warp + g + 8) * 8);
#pragma unroll
                    for (int hh = 0; hh < 4; hh++)
                        ln_frag<false>(acc + 8 * hh, sb + OFF_CS1 + (64 + 16 * hh + 2 * q) * 4, 0.f, s0.y, 0.f, s1.y, a + 4 * hh);
                } else {
#pragma unroll
                    for (int hh = 0; hh < 4; hh++)
                        ln_frag<false>(accq + 8 * hh, sb + OFF_CS1 + (16 * hh + 2 * q) * 4, 0.f, s0.y, 0.f, s1.y, a + 4 * hh);
                }
                feature_maps(a, wb, s0.x * L2E, s1.x * L2E, fp, fm);
                if (it == 0) {
                    mbar_waitc(sb + BAR_FULLB + 8 * 4, 1); mbar_waitc(sb + BAR_FULLB + 8 * 5, 1);
                    mbar_waitc(sb + BAR_FULLB + 8 * 0, 0); mbar_waitc(sb + BAR_FULLB + 8 * 1, 0);
                    mbar_waitc(sb + BAR_CSV, 0);
                    const uint32_t st = sb + OFF_B + warp * 2048 + lrow;
#pragma unroll
                    for (int hh = 0; hh < 4; hh++) {
                        stsm4(st + (4 + (hh >> 1)) * SLOT + (((4 * (hh & 1) + ch) ^ sw) << 4), fp[4 * hh], fp[4 * hh + 1], fp[4 * hh + 2], fp[4 * hh + 3]);
                        stsm4(st + (4 + (hh >> 1)) * SLOT + (((4 * (hh & 1) + 2 + ch) ^ sw) << 4), fm[4 * hh], fm[4 * hh + 1], fm[4 * hh + 2], fm[4 * hh + 3]);
                        ln_frag<true>(acc + 32 + 8 * hh, sb + OFF_CS1 + (128 + 16 * hh + 2 * q) * 4, s0.x, s0.y, s1.x, s1.y, a);
                        stsm4(st + (hh >> 1) * SLOT + (((2 * (hh & 1) + ch) ^ sw) << 4), a[0], a[1], a[2], a[3]);
                    }
                    stsm4(st + ch * SLOT + ((4 ^ sw) << 4), 0x3f803f80u, 0x3f803f80u, 0x3f803f80u, 0x3f803f80u);
                    fence_async_smem();
                    bar_sync(1, 256);
                    float kvd[20];
                    wg_fence();
#pragma unroll
                    for (int k = 0; k < 8; k++)
                        wgmma_n40_tt(kvd, dB + (4 + w) * (SLOT >> 4) + 128 * k, dB + w * (SLOT >> 4) + 128 * k, k != 0);
                    wg_commit();
                    wg_wait<0>();
                    fence_acc<20>(kvd);
                    const bool h1 = wv >= 2;
                    const int f = 16 * warp + g;
                    float* kvp = acc_j + ACC_KV + f * 16 + 2 * q;
                    red_f32x2(kvp, h1 ? kvd[8] : kvd[0], h1 ? kvd[9] : kvd[1]);
                    red_f32x2(kvp + 128, h1 ? kvd[10] : kvd[2], h1 ? kvd[11] : kvd[3]);
                    red_f32x2(kvp + 8, h1 ? kvd[12] : kvd[4], h1 ? kvd[13] : kvd[5]);
                    red_f32x2(kvp + 136, h1 ? kvd[14] : kvd[6], h1 ? kvd[15] : kvd[7]);
                    red_f32_if(acc_j + ACC_Z + f + 8 * (q & 1), q ? kvd[18] : kvd[16], q < 2);
                    __syncwarp();
                    mbar_arrive_if(sb + BAR_KVW, l0);
                    mbar_arrive_cl_if(eb + 8 * ((4 + (lane >> 1)) % 6), lane < 8);
                    TL(3, tid == 0);
                }
            }
        }
        uint32_t res_lo[8], res_hi[8], ack[4];
        const uint32_t own_rows = sb + OFF_A + j * SLOT + warp * 2048;
#pragma unroll
        for (int b = 0; b < 4; b++)
            ldsm4(own_rows + lrow + (((2 * b + ch) ^ sw) << 4), res_lo[2 * b], res_hi[2 * b], res_lo[2 * b + 1], res_hi[2 * b + 1]);
        mbar_arrive_if(sb + BAR_EMPTYA + 8 * lane, lane < 8 && lane != j && lane != KVS(j));
        TL(5, tid == 0);
        mbar_waitc(sb + BAR_KVR, 0);
        TL(6, tid == 0);
        {
            const uint32_t kvs = sb + OFF_A + KVS(j) * SLOT;
            uint32_t o_lo[8], o_hi[8];
#pragma unroll
            for (int hh = 0; hh < 4; hh++) {
                uint32_t b[8], zb[4];
                const uint32_t base = kvs + hh * 32 * 48;
                ldsm4t(base + (lane & 15) * 48 + (lane >> 4) * 16, b[0], b[1], b[2], b[3]);
                ldsm4t(base + (16 + (lane & 15)) * 48 + (lane >> 4) * 16, b[4], b[5], b[6], b[7]);
                ldsm4t(base + lane * 48 + 32, zb[0], zb[1], zb[2], zb[3]);
                float n0[4], n1[4], dn[4];
                mma16816_z(n0, fp + 4 * hh, b[0], b[1]); mma16816_z(n1, fp + 4 * hh, b[2], b[3]); mma16816_z(dn, fp + 4 * hh, zb[0], zb[1]);
                mma16816(n0, fm + 4 * hh, b[4], b[5]); mma16816(n1, fm + 4 * hh, b[6], b[7]); mma16816(dn, fm + 4 * hh, zb[2], zb[3]);
                const float i0 = rcp(dn[0] + 1e-6f), i1 = rcp(dn[2] + 1e-6f);
                o_lo[2 * hh] = pack_bf16(n0[0] * i0, n0[1] * i0); o_hi[2 * hh] = pack_bf16(n0[2] * i1, n0[3] * i1);
                o_lo[2 * hh + 1] = pack_bf16(n1[0] * i0, n1[1] * i0); o_hi[2 * hh + 1] = pack_bf16(n1[2] * i1, n1[3] * i1);
            }
            __syncwarp();
            mbar_arrive_if(sb + BAR_EMPTYA + 8 * KVS(j), l0);
            rg.slot = 4; rg.phase = 0;
            store_tile(own_rows, g_o + (size_t)row_w * DM + 64 * j, o_lo, o_hi, lane, ack);
            TL(7, tid == 0);
        }
        {
            float acc[32];
#pragma unroll
            for (int t = 0; t < 8; t++) {
                acc[4 * t] = bf_lo(res_lo[t]); acc[4 * t + 1] = bf_hi(res_lo[t]);
                acc[4 * t + 2] = bf_lo(res_hi[t]); acc[4 * t + 3] = bf_hi(res_hi[t]);
            }
            fence_acc<32>(acc);
            int pa = 0;
#pragma unroll 1
            for (int kp = 0; kp < 4; kp++) {
                mbar_waitc(sb + BAR_FULLB + 8 * rg.slot, rg.phase);
#pragma unroll
                for (int hf = 0; hf < 2; hf++) {
                    const int i = 2 * kp + hf, kt = KORD(i, j);
                    mbar_waitc(sb + BAR_FULLA + 8 * kt, i != 0);
                    TL(8, i == 1 && tid == 0);
                    const desc_t da = dA + kt * (SLOT >> 4), db = dB + rg.slot * (SLOT >> 4);
                    wg_fence();
#pragma unroll
                    for (int k = 0; k < 4; k++) wgmma_n64(acc, da + 2 * k, db + (hf * 4 + k) * 128, 1);
                    wg_commit();
                    wg_wait<1>();
                    mbar_arrive_if(sb + BAR_EMPTYA + 8 * pa, l0 && i > 1);
                    if (hf == 0) {
                        mbar_arrive_cl_if(eb + 8 * prev, l2 && i > 0);
                        if (i == 0) { signal_late(flag_m, ack, P.zero, l0); TL(20, tid == 0); }
                    }
                    pa = kt;
                }
                prev = rg.slot; rg.adv();
            }
            wg_wait<0>();
            fence_acc<32>(acc);
            mbar_arrive_if(sb + BAR_EMPTYA + 8 * pa, l0);
            mbar_arrive_cl_if(eb + 8 * prev, l2);
            TL(9, tid == 0);
            float s0 = 0.f, s1 = 0.f;
#pragma unroll
            for (int t = 0; t < 8; t++) {
                res_lo[t] = pack_bf16(acc[4 * t], acc[4 * t + 1]);
                res_hi[t] = pack_bf16(acc[4 * t + 2], acc[4 * t + 3]);
                s0 += acc[4 * t] + acc[4 * t + 1];
                s1 += acc[4 * t + 2] + acc[4 * t + 3];
            }
            store_tile(own_rows, g_h + (size_t)row_w * DM + 64 * j, res_lo, res_hi, lane, ack);
            s0 += __shfl_xor_sync(0xffffffffu, s0, 1); s1 += __shfl_xor_sync(0xffffffffu, s1, 1);
            s0 += __shfl_xor_sync(0xffffffffu, s0, 2); s1 += __shfl_xor_sync(0xffffffffu, s1, 2);
            const float mu0 = s0 * (1.f / 64), mu1 = s1 * (1.f / 64);
            float q0 = 0.f, q1 = 0.f;
#pragma unroll
            for (int t = 0; t < 8; t++) {
                float d;
                d = acc[4 * t] - mu0; q0 = fmaf(d, d, q0);
                d = acc[4 * t + 1] - mu0; q0 = fmaf(d, d, q0);
                d = acc[4 * t + 2] - mu1; q1 = fmaf(d, d, q1);
                d = acc[4 * t + 3] - mu1; q1 = fmaf(d, d, q1);
            }
            q0 += __shfl_xor_sync(0xffffffffu, q0, 1); q1 += __shfl_xor_sync(0xffffffffu, q1, 1);
            q0 += __shfl_xor_sync(0xffffffffu, q0, 2); q1 += __shfl_xor_sync(0xffffffffu, q1, 2);
            st_tagged_if(g_hstat + (role * 128 + 16 * warp + g + 8 * (q & 1)) * 2, q ? mu1 : mu0, q ? q1 : q0, epoch, q < 2);
            TL(10, tid == 0);
        }
        float acc0[64], acc1[64], acc2[56], nm0, nm1;
        float4 cs[8];
        int stg_slot;
        uint32_t hr[16];
#define P3_GROUP(MMA, ACC, KT)                                                                              \
        mbar_waitc(sb + BAR_FULLB + 8 * rg.slot, rg.phase);                                                 \
        {                                                                                                   \
            const desc_t da = dA + (KT) * (SLOT >> 4), db = dB + rg.slot * (SLOT >> 4);                     \
            wg_fence();                                                                                     \
            _Pragma("unroll") for (int k = 0; k < 4; k++) MMA(ACC, da + 2 * k, db + 128 * k, (i | k) != 0); \
            wg_commit();                                                                                    \
        }
#define P3_PRE(C, NT)                                             \
        mbar_waitc(sb + BAR_FULLB + 8 * rg.slot, rg.phase);                                                 \
        stg_slot = rg.slot; rg.adv();                                                                       \
        _Pragma("unroll") for (int t = 0; t < (NT); t++) cs[t] = lds_f4(sb + OFF_CS3 + q * 16 + 512 * (C) + 64 * t);
#define P3_EPI(C, ACC, N, NTP)                                                                              \
        fence_acc<N>(ACC);                                                                                  \
        TL(11 + (C), tid == 0);                                                                             \
        hh_stage<NTP>(ACC, cs, nm0, nm1, sb + OFF_B + stg_slot * SLOT + warp * 2048, lane);                 \
        mbar_arrive_if(sb + BAR_STG + 8 * (C), l0);                                                         \
        TL(50 + (C), tid == 0);
#pragma unroll 1
        for (int i = 0; i < 8; i++) {
            const int kt = KORD(i, j);
            mbar_waitc(sb + BAR_FULLA + 8 * kt, 0);
            TL(44, tid == 0 && i == 1);
            P3_GROUP(wgmma_n128, acc0, kt)
            wg_wait<1>();
            mbar_arrive_cl_if(eb + 8 * prev, l2 && i > 0);
            if (i == 0) { signal_late(flag_m + 32, ack, P.zero, l0); TL(21, tid == 0); }
            prev = rg.slot; rg.adv();
        }
        mbar_waitc(sb + BAR_CS3, 0);
        nm0 = lds_f2(sb + OFF_CS1 + (16 * warp + g) * 8).x; nm1 = lds_f2(sb + OFF_CS1 + (16 * warp + g + 8) * 8).x;
        P3_PRE(0, 8)
#pragma unroll 1
        for (int i = 0; i < 8; i++) {
            P3_GROUP(wgmma_n128, acc1, i)
            wg_wait<1>();
            mbar_arrive_cl_if(eb + 8 * prev, l2);
            if (i == 0) { P3_EPI(0, acc0, 64, 4) }
            prev = rg.slot; rg.adv();
        }
        const uint32_t blk = ((lane & 7) + (lane >> 4) * 8) * 128 + (((2 * wv + ((lane >> 3) & 1)) ^ (lane & 7)) << 4);
#pragma unroll
        for (int tp = 0; tp < 4; tp++) ldsm4t(sa + j * SLOT + blk + tp * 2048, hr[4 * tp], hr[4 * tp + 1], hr[4 * tp + 2], hr[4 * tp + 3]);
        P3_PRE(1, 8)
#pragma unroll 1
        for (int i = 0; i < 8; i++) {
            P3_GROUP(wgmma_n112, acc2, i)
            wg_wait<1>();
            mbar_arrive_cl_if(eb + 8 * prev, l2);
            mbar_arrive_if(sb + BAR_EMPTYA + 8 * ((i + 7) & 7), l0 && i > 0);
            if (i == 0) { P3_EPI(1, acc1, 64, 4) }
            prev = rg.slot; rg.adv();
        }
        P3_PRE(2, 6)
        {
            float acc[64];
            const desc_t dA0 = desc_lo(sb + OFF_A);
#define KT_P4(I, NK)                                                                                        \
        const int s_ = (2 * (I) + w) & 7;                                                                   \
        mbar_waitc(sb + BAR_FULLB + 8 * rg.slot, rg.phase);                                                 \
        mbar_waitc(sb + BAR_FULLA + 8 * s_, (((I) >> 2) + 1) & 1);                                          \
        TL(30 + (I), tid == 0);                                                                             \
        const desc_t dh_ = dA0 + s_ * (SLOT >> 4), dw_ = dB + rg.slot * (SLOT >> 4) + w * 512;              \
        wg_fence();                                                                                         \
        _Pragma("unroll") for (int k = 0; k < (NK); k++) wgmma_n128_tn(acc, dw_ + 128 * k, dh_ + 2 * k, ((I) | k) != 0); \
        wg_commit();                                                                                        \
        wg_wait<1>();
#pragma unroll 1
            for (int i = 0; i < 8; i++) {
                KT_P4(i, 4)
                mbar_arrive_n_if(sb + BAR_EMPTYA + 8 * (i ? (s_ + 6) & 7 : 7), i ? 2 : 1, l0);
                mbar_arrive_cl_if(eb + 8 * prev, l2 && i < 7);
                if (i == 0) { P3_EPI(2, acc2, 56, 3) }
                prev = rg.slot; rg.adv();
            }
#pragma unroll 1
            for (int i = 8; i < 12; i++) {
                KT_P4(i, 3)
                mbar_arrive_n_if(sb + BAR_EMPTYA + 8 * ((s_ + 6) & 7), 2, l0);
                rg.adv();
            }
            float r2[16];
#pragma unroll
            for (int t = 0; t < 8; t++) {
                const float4 st = lds_f4(sb + OFF_CS1 + (64 * w + 8 * t + 2 * q) * 8);
                r2[2 * t] = st.y; r2[2 * t + 1] = st.w;
            }
            wg_wait<0>();
            fence_acc<64>(acc);
            TL(15, tid == 0);
            const uint32_t xch = sb + OFF_A + 2 * SLOT + (tid & 127) * 16;
            if (w) {
#pragma unroll
                for (int t = 0; t < 8; t++) {
                    sts128(xch + SLOT + t * 2048, __float_as_uint(acc[4 * t]), __float_as_uint(acc[4 * t + 1]),
                           __float_as_uint(acc[4 * t + 2]), __float_as_uint(acc[4 * t + 3]));
                }
#pragma unroll
                for (int t = 0; t < 32; t++) acc[t] = acc[32 + t];
            } else {
#pragma unroll
                for (int t = 0; t < 8; t++)
                    sts128(xch + t * 2048, __float_as_uint(acc[32 + 4 * t]), __float_as_uint(acc[33 + 4 * t]),
                           __float_as_uint(acc[34 + 4 * t]), __float_as_uint(acc[35 + 4 * t]));
            }
            bar_sync(1, 256);
            float4 o[8];
#pragma unroll
            for (int t = 0; t < 8; t++) o[t] = lds_f4(xch + (w ^ 1) * SLOT + t * 2048);
            const uint32_t tile = sb + OFF_A + w * SLOT;
#pragma unroll
            for (int t = 0; t < 8; t++) {
                hr[2 * t] = pack_bf16(fmaf(acc[4 * t] + o[t].x, r2[2 * t], bf_lo(hr[2 * t])), fmaf(acc[4 * t + 1] + o[t].y, r2[2 * t + 1], bf_hi(hr[2 * t])));
                hr[2 * t + 1] = pack_bf16(fmaf(acc[4 * t + 2] + o[t].z, r2[2 * t], bf_lo(hr[2 * t + 1])), fmaf(acc[4 * t + 3] + o[t].w, r2[2 * t + 1], bf_hi(hr[2 * t + 1])));
            }
#pragma unroll
            for (int tp = 0; tp < 4; tp++) stsm4t(tile + blk + tp * 2048, hr[4 * tp], hr[4 * tp + 1], hr[4 * tp + 2], hr[4 * tp + 3]);
            fence_async_smem();
            bar_sync(2 + w, 128);
            if ((tid & 127) == 0) {
                tma_store2d(&P.tout, tile, 64 * j, 128 * m + 64 * w);
                asm volatile("cp.async.bulk.wait_group.read 0;" ::: "memory");
            }
            if (tid == 0 && role == 0) g_epoch = epoch + 1;
            TL(16, tid == 0); TLG(1, tid == 0);
        }
    }
}

__global__ void probe_kernel() {}

typedef CUresult (*EncodeFn)(CUtensorMap*, CUtensorMapDataType, cuuint32_t, void*, const cuuint64_t*, const cuuint64_t*,
                             const cuuint32_t*, const cuuint32_t*, CUtensorMapInterleave, CUtensorMapSwizzle,
                             CUtensorMapL2promotion, CUtensorMapFloatOOBfill);

static void make_map2d(EncodeFn enc, CUtensorMap* tm, const void* base, uint64_t cols, uint64_t rows, uint64_t pitch_elems,
                       uint32_t box_rows) {
    cuuint64_t gd[2] = {cols, rows};
    cuuint64_t gs[1] = {pitch_elems * 2};
    cuuint32_t bd[2] = {64, box_rows};
    cuuint32_t es[2] = {1, 1};
    enc(tm, CU_TENSOR_MAP_DATA_TYPE_BFLOAT16, 2, const_cast<void*>(base), gd, gs, bd, es, CU_TENSOR_MAP_INTERLEAVE_NONE,
        CU_TENSOR_MAP_SWIZZLE_128B, CU_TENSOR_MAP_L2_PROMOTION_L2_256B, CU_TENSOR_MAP_FLOAT_OOB_FILL_NONE);
}

}

extern "C" void kernel_launch(void* const* d_in, const int* in_sizes, int n_in, void* d_out, int out_size) {
    using namespace hk;
    (void)in_sizes; (void)n_in; (void)out_size;
    static EncodeFn enc = nullptr;
    static void *po = nullptr, *ph = nullptr, *phh = nullptr;
    static int std_layout = 0;
    if (!enc) {
        void* fn = nullptr;
        cudaDriverEntryPointQueryResult qr;
        cudaGetDriverEntryPoint("cuTensorMapEncodeTiled", &fn, cudaEnableDefault, &qr);
        enc = (EncodeFn)fn;
        cudaGetSymbolAddress(&po, g_o);
        cudaGetSymbolAddress(&ph, g_h);
        cudaGetSymbolAddress(&phh, g_hh);
        cudaFuncSetAttribute(fused_kernel, cudaFuncAttributeMaxDynamicSharedMemorySize, SMEM_BYTES);
        int dev = 0, sms = 0;
        cudaGetDevice(&dev);
        cudaDeviceGetAttribute(&sms, cudaDevAttrMultiProcessorCount, dev);
        cudaFuncSetAttribute(probe_kernel, cudaFuncAttributeNonPortableClusterSizeAllowed, 1);
        cudaFuncSetAttribute(probe_kernel, cudaFuncAttributeMaxDynamicSharedMemorySize, SMEM_BYTES);
        const int sizes[3] = {8, 9, 16}, want[3] = {15, 9, 7};
        bool ok = sms == NCTA;
        for (int i = 0; i < 3 && ok; i++) {
            cudaLaunchConfig_t cfg = {};
            cfg.gridDim = dim3(sizes[i] * 8); cfg.blockDim = dim3(NTHREADS); cfg.dynamicSmemBytes = SMEM_BYTES;
            cudaLaunchAttribute at;
            at.id = cudaLaunchAttributeClusterDimension;
            at.val.clusterDim.x = sizes[i]; at.val.clusterDim.y = 1; at.val.clusterDim.z = 1;
            cfg.attrs = &at; cfg.numAttrs = 1;
            int n = 0;
            ok = cudaOccupancyMaxActiveClusters(&n, probe_kernel, &cfg) == cudaSuccess && n == want[i];
        }
        (void)cudaGetLastError();
        std_layout = ok ? 1 : 0;
    }
    Params P;
    const __nv_bfloat16* x = (const __nv_bfloat16*)d_in[0];
    P.x = x;
    P.wqkv = (const __nv_bfloat16*)d_in[1];
    P.wphi = (const __nv_bfloat16*)d_in[2];
    P.wo = (const __nv_bfloat16*)d_in[3];
    P.wg = (const __nv_bfloat16*)d_in[5];
    P.wu = (const __nv_bfloat16*)d_in[6];
    P.wd = (const __nv_bfloat16*)d_in[7];
    P.out = (__nv_bfloat16*)d_out;
    P.zero = 0;
    for (int i = 0; i < NCTA; i++) {
        const int odd = i & 1;
        int role = i < 4 ? 128 + i : (((i - 4) >> 4) * 2 + odd) * 8 + (((i - 4) >> 1) & 7);
        if (std_layout) {
            const int tpc = i < 8 ? 62 + (i >> 1) : (i - 8) >> 1;
            if (tpc < 32) role = (tpc & 7) ? (2 * ((tpc & 7) - 1) + odd) * 8 + (tpc >> 3) : (14 + odd) * 8 + (tpc >> 3);
            else if (tpc < 60) role = (2 * ((tpc - 32) % 7) + odd) * 8 + 4 + (tpc - 32) / 7;
            else if (tpc < 62) role = 128 + (tpc - 60) * 2 + odd;
            else role = (14 + odd) * 8 + 4 + (tpc - 62);
        }
        P.role[i] = (unsigned char)role;
    }
    make_map2d(enc, &P.tx, x, DM, SEQ, DM, 128);
    make_map2d(enc, &P.to, po, DM, SEQ, DM, 128);
    make_map2d(enc, &P.th, ph, DM, SEQ, DM, 128);
    make_map2d(enc, &P.thh, phh, FFP, SEQ, FFP, 128);
    make_map2d(enc, &P.twq, P.wqkv, 3 * DM, DM, 3 * DM, 64);
    make_map2d(enc, &P.two, P.wo, DM, DM, DM, 64);
    make_map2d(enc, &P.twg, P.wg, FF, DM, FF, 64);
    make_map2d(enc, &P.twu, P.wu, FF, DM, FF, 64);
    make_map2d(enc, &P.twd, P.wd, DM, FF, DM, 64);
    make_map2d(enc, &P.tout, d_out, DM, SEQ, DM, 64);
    fused_kernel<<<NCTA, NTHREADS, SMEM_BYTES>>>(P);
}
```

```cpp
#include <cuda_runtime.h>
#include <cuda_bf16.h>
#include <cuda.h>
#include <stdint.h>

namespace hk {

constexpr int SEQ = 2048, DM = 512, FF = 1376, FFP = 1536;
constexpr int NCTA = 132;
constexpr int NTHREADS = 384;
constexpr uint32_t SLOT = 16384;
constexpr uint32_t OFF_A = 0, OFF_B = 8 * SLOT, OFF_MISC = 14 * SLOT;
constexpr uint32_t BAR_FULLA = OFF_MISC + 0, BAR_EMPTYA = OFF_MISC + 64, BAR_FULLB = OFF_MISC + 128,
                   BAR_EMPTYB = OFF_MISC + 176, BAR_CS1 = OFF_MISC + 224, BAR_CS3 = OFF_MISC + 232,
                   BAR_CSQ = OFF_MISC + 240, BAR_CSV = OFF_MISC + 248,
                   BAR_STG = OFF_MISC + 256,
                   BAR_KVW = OFF_MISC + 280, BAR_KVR = OFF_MISC + 288;
constexpr uint32_t OFF_CS1 = OFF_MISC + 384;
constexpr uint32_t OFF_CS3 = OFF_CS1 + 1024;
constexpr uint32_t OFF_XST = OFF_CS3;
constexpr uint32_t SMEM_BYTES = OFF_CS3 + 1536;
#define KVS(j) ((j) == 3 ? 2 : 3)
#define KORD(i, j) ((i) == 0 ? (j) : (i) - ((i) <= (j)))
constexpr int NB = 6;
constexpr int AHEAD = 3;

constexpr int ACC_KV = 0, ACC_Z = 2048, ACC_SIZE = 2176;

__device__ __align__(1024) __nv_bfloat16 g_o[SEQ * DM];
__device__ __align__(1024) __nv_bfloat16 g_h[SEQ * DM];
__device__ __align__(1024) __nv_bfloat16 g_hh[SEQ * FFP];
__device__ __align__(128) unsigned long long g_hstat[SEQ * 16];
__device__ __align__(128) unsigned long long g_xstat[SEQ * 2];
__device__ __align__(128) float g_acc[8 * ACC_SIZE];
__device__ __align__(128) unsigned g_cnt[8 * 32];
__device__ __align__(128) unsigned long long g_cs[8 * 6 * 128];
__device__ __align__(128) unsigned g_flag[16 * 5 * 32];
__device__ unsigned g_epoch = 1;

#define TL(i, pred) do {} while (0)
#define TLG(i, pred) do {} while (0)

struct Params {
    CUtensorMap tx, to, th, thh, twq, two, twg, twu, twd, tout;
    const __nv_bfloat16 *x, *wqkv, *wphi, *wo, *wg, *wu, *wd;
    __nv_bfloat16* out;
    unsigned zero;
    unsigned char role[NCTA];
};

__device__ __forceinline__ uint32_t smem_u32(const void* p) { return (uint32_t)__cvta_generic_to_shared(p); }
__device__ __forceinline__ void mbar_init(uint32_t bar, uint32_t cnt) {
    asm volatile("mbarrier.init.shared::cta.b64 [%0], %1;" ::"r"(bar), "r"(cnt) : "memory");
}
__device__ __forceinline__ void mbar_expect_tx(uint32_t bar, uint32_t bytes) {
    asm volatile("mbarrier.arrive.expect_tx.shared::cta.b64 _, [%0], %1;" ::"r"(bar), "r"(bytes) : "memory");
}
__device__ __forceinline__ void mbar_arrive(uint32_t bar) {
    asm volatile("mbarrier.arrive.shared::cta.b64 _, [%0];" ::"r"(bar) : "memory");
}
__device__ __forceinline__ void mbar_arrive_if(uint32_t bar, bool pred) {
    asm volatile("{.reg .pred p; setp.ne.u32 p, %1, 0; @p mbarrier.arrive.shared::cta.b64 _, [%0];}" ::"r"(bar), "r"((uint32_t)pred) : "memory");
}
__device__ __forceinline__ bool mbar_try(uint32_t bar, uint32_t parity) {
    uint32_t ok;
    asm volatile("{.reg .pred p; mbarrier.try_wait.parity.shared::cta.b64 p, [%1], %2; selp.u32 %0,1,0,p;}"
                 : "=r"(ok) : "r"(bar), "r"(parity) : "memory");
    return ok;
}
__device__ __forceinline__ bool mbar_test(uint32_t bar, uint32_t parity) {
    uint32_t ok;
    asm volatile("{.reg .pred p; mbarrier.test_wait.parity.shared::cta.b64 p, [%1], %2; selp.u32 %0,1,0,p;}"
                 : "=r"(ok) : "r"(bar), "r"(parity) : "memory");
    return ok;
}
__device__ __forceinline__ void trap_if_gt(uint32_t v, uint32_t lim) {
    asm volatile("{.reg .pred p; setp.gt.u32 p, %0, %1; @p trap;}" ::"r"(v), "r"(lim));
}
__device__ __forceinline__ void mbar_wait(uint32_t bar, uint32_t parity) {
    asm volatile("{\n"
                 ".reg .pred P1, P2;\n"
                 ".reg .u32 c;\n"
                 "mov.u32 c, 0;\n"
                 "LAB_WAIT:\n"
                 "mbarrier.try_wait.parity.shared::cta.b64 P1, [%0], %1;\n"
                 "@P1 bra LAB_DONE;\n"
                 "add.u32 c, c, 1;\n"
                 "setp.gt.u32 P2, c, 4194304;\n"
                 "@P2 trap;\n"
                 "bra LAB_WAIT;\n"
                 "LAB_DONE:\n"
                 "}" ::"r"(bar), "r"(parity) : "memory");
}
__device__ __forceinline__ void mbar_waitc(uint32_t bar, uint32_t parity) {
    asm volatile("{\n"
                 ".reg .pred P1;\n"
                 "LAB_WAIT:\n"
                 "mbarrier.try_wait.parity.shared::cta.b64 P1, [%0], %1;\n"
                 "@!P1 bra LAB_WAIT;\n"
                 "}" ::"r"(bar), "r"(parity) : "memory");
}
__device__ __forceinline__ void tma2d(uint32_t dst, const CUtensorMap* tm, uint32_t bar, int c0, int c1) {
    asm volatile("cp.async.bulk.tensor.2d.shared::cluster.global.mbarrier::complete_tx::bytes [%0], [%1, {%3, %4}], [%2];"
                 ::"r"(dst), "l"(tm), "r"(bar), "r"(c0), "r"(c1) : "memory");
}
__device__ __forceinline__ void tma2d_mc(uint32_t dst, const CUtensorMap* tm, uint32_t bar, int c0, int c1) {
    asm volatile("cp.async.bulk.tensor.2d.shared::cluster.global.mbarrier::complete_tx::bytes.multicast::cluster [%0], [%1, {%3, %4}], [%2], %5;"
                 ::"r"(dst), "l"(tm), "r"(bar), "r"(c0), "r"(c1), "h"((uint16_t)3) : "memory");
}
__device__ __forceinline__ uint32_t mapa(uint32_t addr, uint32_t rank) {
    uint32_t r; asm("mapa.shared::cluster.u32 %0, %1, %2;" : "=r"(r) : "r"(addr), "r"(rank)); return r;
}
__device__ __forceinline__ void mbar_arrive_cl_if(uint32_t cbar, bool pred) {
    asm volatile("{.reg .pred p; setp.ne.u32 p, %1, 0; @p mbarrier.arrive.shared::cluster.b64 _, [%0];}" ::"r"(cbar), "r"((uint32_t)pred) : "memory");
}
__device__ __forceinline__ bool elect_one() {
    uint32_t ok;
    asm volatile("{.reg .pred p; elect.sync _|p, 0xffffffff; selp.u32 %0, 1, 0, p;}" : "=r"(ok));
    return ok;
}
__device__ __forceinline__ void prefetch_tmap(const CUtensorMap* tm) {
    asm volatile("prefetch.tensormap [%0];" ::"l"(tm) : "memory");
}
__device__ __forceinline__ void prefetch_l2(const void* p, uint32_t bytes) {
    asm volatile("cp.async.bulk.prefetch.L2.global [%0], %1;" ::"l"(p), "r"(bytes) : "memory");
}
__device__ __forceinline__ unsigned ld_acquire(const unsigned* p) {
    unsigned v; asm volatile("ld.acquire.gpu.global.u32 %0, [%1];" : "=r"(v) : "l"(p) : "memory"); return v;
}
__device__ __forceinline__ uint4 ld_acquire4(const unsigned* p) {
    uint4 v;
    asm volatile("ld.acquire.gpu.global.v4.u32 {%0,%1,%2,%3}, [%4];" : "=r"(v.x), "=r"(v.y), "=r"(v.z), "=r"(v.w) : "l"(p) : "memory");
    return v;
}
__device__ __forceinline__ unsigned ld_relaxed(const unsigned* p) {
    unsigned v; asm volatile("ld.relaxed.gpu.global.u32 %0, [%1];" : "=r"(v) : "l"(p)); return v;
}
__device__ __forceinline__ void st_relaxed(unsigned* p, unsigned v) {
    asm volatile("st.relaxed.gpu.global.u32 [%0], %1;" ::"l"(p), "r"(v) : "memory");
}
__device__ __forceinline__ void red_relaxed(unsigned* p, unsigned v) {
    asm volatile("red.relaxed.gpu.global.add.u32 [%0], %1;" ::"l"(p), "r"(v) : "memory");
}
__device__ __forceinline__ void fence_gpu() { asm volatile("fence.acq_rel.gpu;" ::: "memory"); }
__device__ __forceinline__ void fence_async_smem() { asm volatile("fence.proxy.async.shared::cta;" ::: "memory"); }
__device__ __forceinline__ void fence_async_global() { asm volatile("fence.proxy.async.global;" ::: "memory"); }
__device__ __forceinline__ uint32_t readback(const void* p) {
    uint32_t v; asm volatile("ld.relaxed.gpu.global.u32 %0, [%1];" : "=r"(v) : "l"(p) : "memory"); return v;
}
__device__ __forceinline__ void wait_count(const unsigned* p, unsigned target) {
    uint32_t it = 0;
    while ((int)(readback(p) - target) < 0) trap_if_gt(++it, 1u << 22);
}
__device__ __forceinline__ void wait_count_warp(const unsigned* p, unsigned target) {
    uint32_t it = 0;
    while (__any_sync(0xffffffffu, (int)(readback(p) - target) < 0)) trap_if_gt(++it, 1u << 22);
}
__device__ __forceinline__ void red_f32(float* p, float a) {
    asm volatile("red.relaxed.gpu.global.add.f32 [%0], %1;" ::"l"(p), "f"(a) : "memory");
}
__device__ __forceinline__ void red_f32x2(float* p, float a, float b) {
    asm volatile("red.relaxed.gpu.global.add.v2.f32 [%0], {%1, %2};" ::"l"(p), "f"(a), "f"(b) : "memory");
}
__device__ __forceinline__ void red_f32x4(float* p, float a, float b, float c, float d) {
    asm volatile("red.relaxed.gpu.global.add.v4.f32 [%0], {%1, %2, %3, %4};" ::"l"(p), "f"(a), "f"(b), "f"(c), "f"(d) : "memory");
}
__device__ __forceinline__ float4 ld_l2_f4(const float* p) {
    float4 v;
    asm volatile("ld.relaxed.gpu.global.v4.f32 {%0,%1,%2,%3}, [%4];" : "=f"(v.x), "=f"(v.y), "=f"(v.z), "=f"(v.w) : "l"(p) : "memory");
    return v;
}
__device__ __forceinline__ float2 ld_l2_f2(const float* p) {
    float2 v;
    asm volatile("ld.relaxed.gpu.global.v2.f32 {%0,%1}, [%2];" : "=f"(v.x), "=f"(v.y) : "l"(p) : "memory");
    return v;
}
__device__ __forceinline__ float ld_l2_f(const float* p) {
    float v;
    asm volatile("ld.relaxed.gpu.global.f32 %0, [%1];" : "=f"(v) : "l"(p) : "memory");
    return v;
}
__device__ __forceinline__ uint4 ldg_nc(const void* p) {
    uint4 v;
    asm volatile("ld.global.nc.L1::no_allocate.v4.u32 {%0,%1,%2,%3}, [%4];" : "=r"(v.x), "=r"(v.y), "=r"(v.z), "=r"(v.w) : "l"(p));
    return v;
}
__device__ __forceinline__ void stg128(void* p, uint32_t a, uint32_t b, uint32_t c, uint32_t d) {
    asm volatile("st.global.v4.u32 [%0], {%1,%2,%3,%4};" ::"l"(p), "r"(a), "r"(b), "r"(c), "r"(d) : "memory");
}
__device__ __forceinline__ uint4 lds128(uint32_t a) {
    uint4 v;
    asm volatile("ld.shared.v4.u32 {%0,%1,%2,%3}, [%4];" : "=r"(v.x), "=r"(v.y), "=r"(v.z), "=r"(v.w) : "r"(a) : "memory");
    return v;
}
__device__ __forceinline__ float2 lds_f2(uint32_t a) {
    float2 v;
    asm volatile("ld.shared.v2.f32 {%0,%1}, [%2];" : "=f"(v.x), "=f"(v.y) : "r"(a) : "memory");
    return v;
}
__device__ __forceinline__ void sts_f2(uint32_t a, float x, float y) {
    asm volatile("st.shared.v2.f32 [%0], {%1,%2};" ::"r"(a), "f"(x), "f"(y) : "memory");
}
__device__ __forceinline__ void sts64(uint32_t a, uint32_t x, uint32_t y) {
    asm volatile("st.shared.v2.u32 [%0], {%1,%2};" ::"r"(a), "r"(x), "r"(y) : "memory");
}
__device__ __forceinline__ void sts128(uint32_t a, uint32_t x, uint32_t y, uint32_t z, uint32_t w) {
    asm volatile("st.shared.v4.u32 [%0], {%1,%2,%3,%4};" ::"r"(a), "r"(x), "r"(y), "r"(z), "r"(w) : "memory");
}
__device__ __forceinline__ void stsm4(uint32_t a, uint32_t r0, uint32_t r1, uint32_t r2, uint32_t r3) {
    asm volatile("stmatrix.sync.aligned.m8n8.x4.shared.b16 [%0], {%1,%2,%3,%4};" ::"r"(a), "r"(r0), "r"(r1), "r"(r2), "r"(r3) : "memory");
}
__device__ __forceinline__ void stsm4t(uint32_t a, uint32_t r0, uint32_t r1, uint32_t r2, uint32_t r3) {
    asm volatile("stmatrix.sync.aligned.m8n8.x4.trans.shared.b16 [%0], {%1,%2,%3,%4};" ::"r"(a), "r"(r0), "r"(r1), "r"(r2), "r"(r3) : "memory");
}
__device__ __forceinline__ void tma_store2d(const CUtensorMap* tm, uint32_t src, int c0, int c1) {
    asm volatile("cp.async.bulk.tensor.2d.global.shared::cta.bulk_group [%0, {%2, %3}], [%1];" ::"l"(tm), "r"(src), "r"(c0), "r"(c1) : "memory");
    asm volatile("cp.async.bulk.commit_group;" ::: "memory");
}
__device__ __forceinline__ void ldsm4(uint32_t a, uint32_t& r0, uint32_t& r1, uint32_t& r2, uint32_t& r3) {
    asm volatile("ldmatrix.sync.aligned.m8n8.x4.shared.b16 {%0,%1,%2,%3}, [%4];" : "=r"(r0), "=r"(r1), "=r"(r2), "=r"(r3) : "r"(a) : "memory");
}
__device__ __forceinline__ void ldsm4t(uint32_t a, uint32_t& r0, uint32_t& r1, uint32_t& r2, uint32_t& r3) {
    asm volatile("ldmatrix.sync.aligned.m8n8.x4.trans.shared.b16 {%0,%1,%2,%3}, [%4];" : "=r"(r0), "=r"(r1), "=r"(r2), "=r"(r3) : "r"(a) : "memory");
}
__device__ __forceinline__ void mma16816(float* c, const uint32_t* a, uint32_t b0, uint32_t b1) {
    asm("mma.sync.aligned.m16n8k16.row.col.f32.bf16.bf16.f32 {%0,%1,%2,%3}, {%4,%5,%6,%7}, {%8,%9}, {%0,%1,%2,%3};"
                 : "+f"(c[0]), "+f"(c[1]), "+f"(c[2]), "+f"(c[3])
                 : "r"(a[0]), "r"(a[1]), "r"(a[2]), "r"(a[3]), "r"(b0), "r"(b1));
}
__device__ __forceinline__ uint32_t pack_bf16(float lo, float hi) {
    uint32_t r; asm("cvt.rn.bf16x2.f32 %0, %1, %2;" : "=r"(r) : "f"(hi), "f"(lo)); return r;
}
__device__ __forceinline__ float bf_lo(uint32_t w) { return __uint_as_float(w << 16); }
__device__ __forceinline__ float bf_hi(uint32_t w) { return __uint_as_float(w & 0xffff0000u); }
__device__ __forceinline__ float ex2(float x) { float r; asm("ex2.approx.ftz.f32 %0, %1;" : "=f"(r) : "f"(x)); return r; }
__device__ __forceinline__ float rcp(float x) { float r; asm("rcp.approx.ftz.f32 %0, %1;" : "=f"(r) : "f"(x)); return r; }
__device__ __forceinline__ void bar_sync(int id, int n) { asm volatile("bar.sync %0, %1;" ::"r"(id), "r"(n) : "memory"); }

typedef unsigned long long desc_t;
__device__ __forceinline__ desc_t desc_lo(uint32_t addr) { return (desc_t)(((addr & 0x3FFFF) >> 4) | (512u << 16)) | (0x40000040ull << 32); }
__device__ __forceinline__ void wg_fence() { asm volatile("wgmma.fence.sync.aligned;" ::: "memory"); }
__device__ __forceinline__ void wg_commit() { asm volatile("wgmma.commit_group.sync.aligned;" ::: "memory"); }
template <int N> __device__ __forceinline__ void wg_wait() { asm volatile("wgmma.wait_group.sync.aligned %0;" ::"n"(N) : "memory"); }
template <int N> __device__ __forceinline__ void fence_acc(float* d) {
#pragma unroll
    for (int i = 0; i < N; i++) asm volatile("" : "+f"(d[i])::"memory");
}
#define R4(o) "+f"(d[o + 0]), "+f"(d[o + 1]), "+f"(d[o + 2]), "+f"(d[o + 3])
#define R8(o) R4(o), R4(o + 4)
__device__ __forceinline__ void wgmma_n128(float* d, desc_t da, desc_t db, int sc) {
    asm volatile("{.reg .pred p; setp.ne.b32 p, %66, 0;\n"
                 "wgmma.mma_async.sync.aligned.m64n128k16.f32.bf16.bf16 {%0,%1,%2,%3,%4,%5,%6,%7,%8,%9,%10,%11,%12,%13,%14,%15,%16,%17,%18,%19,%20,%21,%22,%23,%24,%25,%26,%27,%28,%29,%30,%31,"
                 "%32,%33,%34,%35,%36,%37,%38,%39,%40,%41,%42,%43,%44,%45,%46,%47,%48,%49,%50,%51,%52,%53,%54,%55,%56,%57,%58,%59,%60,%61,%62,%63}, %64, %65, p, 1, 1, 0, 1;}"
                 : R8(0), R8(8), R8(16), R8(24), R8(32), R8(40), R8(48), R8(56)
                 : "l"(da), "l"(db), "r"(sc));
}
__device__ __forceinline__ void wgmma_n112(float* d, desc_t da, desc_t db, int sc) {
    asm volatile("{.reg .pred p; setp.ne.b32 p, %58, 0;\n"
                 "wgmma.mma_async.sync.aligned.m64n112k16.f32.bf16.bf16 {%0,%1,%2,%3,%4,%5,%6,%7,%8,%9,%10,%11,%12,%13,%14,%15,%16,%17,%18,%19,%20,%21,%22,%23,%24,%25,%26,%27,%28,%29,%30,%31,%32,%33,%34,%35,%36,%37,%38,%39,%40,%41,%42,%43,%44,%45,%46,%47,%48,%49,%50,%51,%52,%53,%54,%55}, %56, %57, p, 1, 1, 0, 1;}"
                 : R8(0), R8(8), R8(16), R8(24), R8(32), R8(40), R8(48)
                 : "l"(da), "l"(db), "r"(sc));
}
__device__ __forceinline__ void wgmma_n128_tn(float* d, desc_t da, desc_t db, int sc) {
    asm volatile("{.reg .pred p; setp.ne.b32 p, %66, 0;\n"
                 "wgmma.mma_async.sync.aligned.m64n128k16.f32.bf16.bf16 {%0,%1,%2,%3,%4,%5,%6,%7,%8,%9,%10,%11,%12,%13,%14,%15,%16,%17,%18,%19,%20,%21,%22,%23,%24,%25,%26,%27,%28,%29,%30,%31,%32,%33,%34,%35,%36,%37,%38,%39,%40,%41,%42,%43,%44,%45,%46,%47,%48,%49,%50,%51,%52,%53,%54,%55,%56,%57,%58,%59,%60,%61,%62,%63}, %64, %65, p, 1, 1, 1, 0;}"
                 : R8(0), R8(8), R8(16), R8(24), R8(32), R8(40), R8(48), R8(56)
                 : "l"(da), "l"(db), "r"(sc));
}
__device__ __forceinline__ void wgmma_n64(float* d, desc_t da, desc_t db, int sc) {
    asm volatile("{.reg .pred p; setp.ne.b32 p, %34, 0;\n"
                 "wgmma.mma_async.sync.aligned.m64n64k16.f32.bf16.bf16 {%0,%1,%2,%3,%4,%5,%6,%7,%8,%9,%10,%11,%12,%13,%14,%15,%16,%17,%18,%19,%20,%21,%22,%23,%24,%25,%26,%27,%28,%29,%30,%31}, %32, %33, p, 1, 1, 0, 1;}"
                 : R8(0), R8(8), R8(16), R8(24)
                 : "l"(da), "l"(db), "r"(sc));
}
__device__ __forceinline__ void wgmma_n40_tt(float* d, desc_t da, desc_t db, int sc) {
    asm volatile("{.reg .pred p; setp.ne.b32 p, %22, 0;\n"
                 "wgmma.mma_async.sync.aligned.m64n40k16.f32.bf16.bf16 {%0,%1,%2,%3,%4,%5,%6,%7,%8,%9,%10,%11,%12,%13,%14,%15,%16,%17,%18,%19}, %20, %21, p, 1, 1, 1, 1;}"
                 : R8(0), R8(8), R4(16)
                 : "l"(da), "l"(db), "r"(sc));
}

__device__ __forceinline__ void wgmma_n8_tt(float* d, desc_t da, desc_t db, int sc) {
    asm volatile("{.reg .pred p; setp.ne.b32 p, %6, 0;\n"
                 "wgmma.mma_async.sync.aligned.m64n8k16.f32.bf16.bf16 {%0,%1,%2,%3}, %4, %5, p, 1, 1, 1, 1;}"
                 : R4(0)
                 : "l"(da), "l"(db), "r"(sc));
}

__device__ __forceinline__ uint32_t atom_f32x2(float* p, float a, float b) {
    float x, y;
    asm volatile("atom.relaxed.gpu.global.add.v2.f32 {%0,%1}, [%2], {%3,%4};" : "=f"(x), "=f"(y) : "l"(p), "f"(a), "f"(b) : "memory");
    return __float_as_uint(x);
}
__device__ __forceinline__ uint32_t atom_f32_if(float* p, float a, bool pred) {
    float x = 0.f;
    asm volatile("{.reg .pred p; setp.ne.u32 p, %3, 0; @p atom.relaxed.gpu.global.add.f32 %0, [%1], %2;}" : "+f"(x) : "l"(p), "f"(a), "r"((uint32_t)pred) : "memory");
    return __float_as_uint(x);
}
__device__ __forceinline__ void signal_after(unsigned* cnt, uint32_t ack, uint32_t zero, bool pred) {
    asm volatile("{.reg .pred p; setp.ne.u32 p, %2, 0; @p red.relaxed.gpu.global.add.u32 [%0], %1;}"
                 ::"l"(cnt), "r"((ack & zero) + 1), "r"((uint32_t)pred) : "memory");
}
__device__ __forceinline__ void signal_late(unsigned* cnt, const uint32_t* a, uint32_t zero, bool pred) {
    uint32_t v;
    asm volatile("{.reg .b32 t; lop3.b32 t, %1, %2, %3, 0xfe; or.b32 %0, t, %4;}"
                 : "=r"(v) : "r"(a[0]), "r"(a[1]), "r"(a[2]), "r"(a[3]));
    signal_after(cnt, v, zero, pred);
}
__device__ __forceinline__ void red_f32_if(float* p, float a, bool pred) {
    asm volatile("{.reg .pred p; setp.ne.u32 p, %2, 0; @p red.relaxed.gpu.global.add.f32 [%0], %1;}" ::"l"(p), "f"(a), "r"((uint32_t)pred) : "memory");
}
__device__ __forceinline__ void stg_f2_if(float* p, float a, float b, bool pred) {
    asm volatile("{.reg .pred p; setp.ne.u32 p, %3, 0; @p st.global.v2.f32 [%0], {%1,%2};}" ::"l"(p), "f"(a), "f"(b), "r"((uint32_t)pred) : "memory");
}
__device__ __forceinline__ void stg64(void* p, uint32_t a, uint32_t b) {
    asm volatile("st.global.v2.u32 [%0], {%1,%2};" ::"l"(p), "r"(a), "r"(b) : "memory");
}
__device__ __forceinline__ void mma16816_z(float* c, const uint32_t* a, uint32_t b0, uint32_t b1) {
    asm("mma.sync.aligned.m16n8k16.row.col.f32.bf16.bf16.f32 {%0,%1,%2,%3}, {%4,%5,%6,%7}, {%8,%9}, {%10,%10,%10,%10};"
                 : "=f"(c[0]), "=f"(c[1]), "=f"(c[2]), "=f"(c[3])
                 : "r"(a[0]), "r"(a[1]), "r"(a[2]), "r"(a[3]), "r"(b0), "r"(b1), "f"(0.f));
}
__device__ __forceinline__ uint32_t max2(uint32_t a, uint32_t b) { uint32_t r; asm("max.bf16x2 %0, %1, %2;" : "=r"(r) : "r"(a), "r"(b)); return r; }
__device__ __forceinline__ uint32_t min2(uint32_t a, uint32_t b) { uint32_t r; asm("min.bf16x2 %0, %1, %2;" : "=r"(r) : "r"(a), "r"(b)); return r; }
__device__ __forceinline__ void bar_arrive(int id, int n) { asm volatile("bar.arrive %0, %1;" ::"r"(id), "r"(n) : "memory"); }
__device__ __forceinline__ void mbar_arrive_n_if(uint32_t bar, uint32_t n, bool pred) {
    asm volatile("{.reg .pred p; setp.ne.u32 p, %1, 0; @p mbarrier.arrive.shared::cta.b64 _, [%0], %2;}" ::"r"(bar), "r"((uint32_t)pred), "r"(n) : "memory");
}
__device__ __forceinline__ float4 lds_f4(uint32_t a) {
    float4 v;
    asm volatile("ld.shared.v4.f32 {%0,%1,%2,%3}, [%4];" : "=f"(v.x), "=f"(v.y), "=f"(v.z), "=f"(v.w) : "r"(a) : "memory");
    return v;
}
__device__ __forceinline__ uint4 ld_tagged(const unsigned long long* p) {
    unsigned long long a, b;
    asm volatile("ld.acquire.gpu.global.v2.b64 {%0,%1}, [%2];" : "=l"(a), "=l"(b) : "l"(p) : "memory");
    return make_uint4((unsigned)a, (unsigned)(a >> 32), (unsigned)b, (unsigned)(b >> 32));
}
__device__ __forceinline__ uint4 ld_tagged_rlx(const unsigned long long* p) {
    unsigned long long a, b;
    asm volatile("ld.relaxed.gpu.global.v2.b64 {%0,%1}, [%2];" : "=l"(a), "=l"(b) : "l"(p) : "memory");
    return make_uint4((unsigned)a, (unsigned)(a >> 32), (unsigned)b, (unsigned)(b >> 32));
}
__device__ __forceinline__ void st_tagged_if(unsigned long long* p, float a, float b, unsigned tag, bool pred) {
    const unsigned long long t = (unsigned long long)tag << 32;
    asm volatile("{.reg .pred p; setp.ne.u32 p, %3, 0; @p st.relaxed.gpu.global.v2.b64 [%0], {%1,%2};}"
                 ::"l"(p), "l"(t | __float_as_uint(a)), "l"(t | __float_as_uint(b)), "r"((uint32_t)pred) : "memory");
}

__device__ __forceinline__ void store_tile(uint32_t tile_rows, __nv_bfloat16* gdst, const uint32_t* lo, const uint32_t* hi, int lane, uint32_t* ack) {
    const int r = lane & 15;
#pragma unroll
    for (int b = 0; b < 4; b++)
        stsm4(tile_rows + r * 128 + (((2 * b + (lane >> 4)) ^ (r & 7)) << 4), lo[2 * b], hi[2 * b], lo[2 * b + 1], hi[2 * b + 1]);
    fence_async_smem();
    __syncwarp();
#pragma unroll
    for (int i = 0; i < 4; i++) {
        const int rr = 4 * i + (lane >> 3);
        const uint4 v = lds128(tile_rows + rr * 128 + (((lane & 7) ^ (rr & 7)) << 4));
        stg128(gdst + rr * DM + (lane & 7) * 8, v.x, v.y, v.z, v.w);
    }
#pragma unroll
    for (int i = 0; i < 4; i++) ack[i] = readback(gdst + (4 * i + (lane >> 3)) * DM + (lane & 7) * 8);
}

__device__ __forceinline__ void feature_maps(const uint32_t* a, const uint32_t* wb, float c0, float c1, uint32_t* plus, uint32_t* minus) {
    uint32_t P[16], mx[4], mn[4];
#pragma unroll
    for (int h = 0; h < 4; h++) {
        float p[8];
        mma16816_z(p, a + 4 * h, wb[4 * h], wb[4 * h + 1]);
        mma16816_z(p + 4, a + 4 * h, wb[4 * h + 2], wb[4 * h + 3]);
        P[4 * h] = pack_bf16(p[0], p[2]); P[4 * h + 1] = pack_bf16(p[1], p[3]);
        P[4 * h + 2] = pack_bf16(p[4], p[6]); P[4 * h + 3] = pack_bf16(p[5], p[7]);
        mx[h] = max2(max2(P[4 * h], P[4 * h + 1]), max2(P[4 * h + 2], P[4 * h + 3]));
        mn[h] = min2(min2(P[4 * h], P[4 * h + 1]), min2(P[4 * h + 2], P[4 * h + 3]));
    }
#pragma unroll
    for (int s = 1; s <= 2; s <<= 1) {
        uint32_t tx[4], tn[4];
#pragma unroll
        for (int h = 0; h < 4; h++) { tx[h] = __shfl_xor_sync(0xffffffffu, mx[h], s); tn[h] = __shfl_xor_sync(0xffffffffu, mn[h], s); }
#pragma unroll
        for (int h = 0; h < 4; h++) { mx[h] = max2(mx[h], tx[h]); mn[h] = min2(mn[h], tn[h]); }
    }
#pragma unroll
    for (int h = 0; h < 4; h++) {
        const float mx0 = bf_lo(mx[h]) * c0, mx1 = bf_hi(mx[h]) * c1, mn0 = bf_lo(mn[h]) * c0, mn1 = bf_hi(mn[h]) * c1;
        float ep[8], em[8];
#pragma unroll
        for (int i = 0; i < 8; i++) {
            const bool r1 = (i & 2);
            const uint32_t w = P[4 * h + (i >> 2) * 2 + (i & 1)];
            const float p = r1 ? bf_hi(w) : bf_lo(w);
            ep[i] = ex2(fmaf(p, r1 ? c1 : c0, r1 ? -mx1 : -mx0));
            em[i] = ex2(fmaf(p, r1 ? -c1 : -c0, r1 ? mn1 : mn0));
        }
        float sp[4], sm[4];
        uint32_t tp[4], tm[4];
#pragma unroll
        for (int i = 0; i < 4; i++) { tp[i] = pack_bf16(ep[2 * i], ep[2 * i + 1]); tm[i] = pack_bf16(em[2 * i], em[2 * i + 1]); }
        mma16816_z(sp, tp, 0x3f803f80u, 0x3f803f80u);
        mma16816_z(sm, tm, 0x3f803f80u, 0x3f803f80u);
        const float r0 = rcp(sp[0] * sm[0]), r1 = rcp(sp[2] * sm[2]);
        const float rs[4] = {r0 * sm[0], r1 * sm[2], r0 * sp[0], r1 * sp[2]};
#pragma unroll
        for (int i = 0; i < 4; i++) {
            plus[4 * h + i] = pack_bf16(ep[2 * i] * rs[i & 1], ep[2 * i + 1] * rs[i & 1]);
            minus[4 * h + i] = pack_bf16(em[2 * i] * rs[2 + (i & 1)], em[2 * i + 1] * rs[2 + (i & 1)]);
        }
    }
}

template <bool SCALE>
__device__ __forceinline__ void ln_frag(const float* acc, uint32_t cs_addr, float rs0, float nm0, float rs1, float nm1, uint32_t* a) {
    const float2 c0 = lds_f2(cs_addr), c1 = lds_f2(cs_addr + 32);
    const float s0 = SCALE ? rs0 : 1.f, s1 = SCALE ? rs1 : 1.f;
    a[0] = pack_bf16(fmaf(nm0, c0.x, acc[0]) * s0, fmaf(nm0, c0.y, acc[1]) * s0);
    a[1] = pack_bf16(fmaf(nm1, c0.x, acc[2]) * s1, fmaf(nm1, c0.y, acc[3]) * s1);
    a[2] = pack_bf16(fmaf(nm0, c1.x, acc[4]) * s0, fmaf(nm0, c1.y, acc[5]) * s0);
    a[3] = pack_bf16(fmaf(nm1, c1.x, acc[6]) * s1, fmaf(nm1, c1.y, acc[7]) * s1);
}

template <int UP>
__device__ __forceinline__ uint32_t hh_pair(const float* ag, float4 cs, float nmean) {
    const float g0 = fmaf(nmean, cs.x, ag[0]), g1 = fmaf(nmean, cs.y, ag[1]);
    const float u0 = fmaf(nmean, cs.z, ag[UP]), u1 = fmaf(nmean, cs.w, ag[UP + 1]);
    return pack_bf16(g0 * u0, g1 * u1);
}
template <int NTP>
__device__ __forceinline__ void hh_stage(const float* acc, const float4* cs, float nm0, float nm1, uint32_t stg, int lane) {
#pragma unroll
    for (int tp = 0; tp < NTP; tp++)
        stsm4(stg + (lane & 15) * 128 + (((2 * tp + (lane >> 4)) ^ (lane & 7)) << 4), hh_pair<32>(acc + 8 * tp, cs[2 * tp], nm0),
              hh_pair<32>(acc + 8 * tp + 2, cs[2 * tp], nm1), hh_pair<32>(acc + 8 * tp + 4, cs[2 * tp + 1], nm0),
              hh_pair<32>(acc + 8 * tp + 6, cs[2 * tp + 1], nm1));
    fence_async_smem();
    __syncwarp();
}

struct Ring {
    int slot; uint32_t phase;
    __device__ __forceinline__ void adv() { if (++slot == NB) { slot = 0; phase ^= 1; } }
    __device__ __forceinline__ void adv5() { slot += slot == 3; adv(); }
};

__global__ void __cluster_dims__(2, 1, 1) __launch_bounds__(NTHREADS, 1) fused_kernel(const __grid_constant__ Params P) {
    extern __shared__ __align__(1024) uint8_t smem_raw[];
    const uint32_t sb = smem_u32(smem_raw);
    const int tid = threadIdx.x, lane = tid & 31;
    const int warp = __shfl_sync(0xffffffffu, tid >> 5, 0);
    const unsigned role = P.role[blockIdx.x], rank = blockIdx.x & 1;
    const int m = role >> 3, j = role & 7;
    const bool helper = role >= 128;

    TL(0, tid == 0); TLG(0, tid == 0);
    float* const acc_j = g_acc + j * ACC_SIZE;
    unsigned* const cnt_j = g_cnt + j * 32;

    if (__builtin_expect(warp >= 8, 1)) {
        asm volatile("setmaxnreg.dec.sync.aligned.u32 72;");
        if (elect_one()) {
            if (warp == 8) {
                if (!helper) {
#pragma unroll
                    for (int i = 0; i < NB; i++) mbar_init(sb + BAR_FULLB + 8 * i, 1);
#pragma unroll
                    for (int i = 0; i < 2; i++) {
                        mbar_expect_tx(sb + BAR_FULLB + 8 * i, SLOT);
                        tma2d(sb + OFF_B + i * SLOT, &P.twq, sb + BAR_FULLB + 8 * i, DM + 64 * j, 64 * i);
                        tma2d(sb + OFF_B + i * SLOT + 8192, &P.twq, sb + BAR_FULLB + 8 * i, 2 * DM + 64 * j, 64 * i);
                    }
                }
            } else if (warp == 9) {
#pragma unroll
                for (int i = 0; i < 8; i++) mbar_init(sb + BAR_FULLA + 8 * i, 1);
                if (!helper) {
#pragma unroll
                    for (int i = 0; i < 2; i++) {
                        mbar_expect_tx(sb + BAR_FULLA + 8 * i, SLOT);
                        tma2d(sb + OFF_A + i * SLOT, &P.tx, sb + BAR_FULLA + 8 * i, 64 * i, 128 * m);
                    }
                }
            } else if (warp == 10) {
#pragma unroll
                for (int i = 0; i < 9; i++) mbar_init(sb + BAR_CS1 + 8 * i, i == 0 || i == 8 ? 64 : (i == 1 ? 96 : (i < 4 ? 32 : 8)));
                trap_if_gt(sb & 1023, 0);
            } else {
#pragma unroll
                for (int i = 0; i < 14; i++) mbar_init(sb + (i < 8 ? BAR_EMPTYA : BAR_EMPTYB - 64) + 8 * i, i < 8 ? 8 : 16);
            }
            asm volatile("fence.mbarrier_init.release.cluster;" ::: "memory");
        }
        __syncwarp();
        asm volatile("barrier.cluster.arrive.relaxed.aligned;" ::: "memory");
        const unsigned epoch = ld_relaxed(&g_epoch);
        bar_sync(0, NTHREADS);
        if (helper) {
            if (warp == 8) {
                if (elect_one()) {
#pragma unroll 1
                    for (int i = 0; i < 72; i++) {
                        const uint32_t full = sb + BAR_FULLA + 8 * (i & 7), dst = sb + OFF_A + (i & 7) * SLOT;
                        mbar_wait(sb + BAR_EMPTYA + 8 * (i & 7), ((i >> 3) & 1) ^ 1);
                        mbar_expect_tx(full, SLOT);
                        const bool qkv = i < 24;
                        const int u = (i >> 3) - 3;
                        const int c0 = qkv ? (i < 16 ? DM + 64 * (i & 8) : 0) + 128 * j + 16 * (i & 4) : 176 * (2 * j + (u & 1)) + 64 * (u >> 1);
                        const int r0 = qkv ? 128 * (i & 3) : 64 * (i & 7);
                        tma2d(dst, qkv ? &P.twq : &P.twg, full, c0, r0);
                        tma2d(dst + 8192, qkv ? &P.twq : &P.twu, full, c0, qkv ? r0 + 64 : r0);
                    }
                    prefetch_l2(P.wd + (size_t)j * 176128, 352256);
                }
            }
            return;
        }
        if (warp == 8) {
            asm volatile("barrier.cluster.wait.aligned;" ::: "memory");
            if (elect_one()) {
                if (m >= 6)
                    asm volatile("cp.async.bulk.prefetch.tensor.2d.L2.global [%0, {%1, %2}];" ::"l"(&P.twq), "r"(DM + DM * (m & 1) + 64 * j), "r"(64 * (m >> 1)) : "memory");
                if (j >= 3)
                    asm volatile("cp.async.bulk.prefetch.tensor.2d.L2.global [%0, {%1, %2}];" ::"l"(&P.tx), "r"(64 * j), "r"(128 * m) : "memory");
                Ring r{2, 0};
#pragma unroll 1
                for (int i = 2; i < 56; i++) {
                    const uint32_t full = sb + BAR_FULLB + 8 * r.slot;
                    mbar_wait(sb + BAR_EMPTYB + 8 * r.slot, r.phase ^ 1);
                    if (i >= 10 && i < 14) {
                        mbar_arrive(full);
                    } else {
                        if (i >= AHEAD && i < 6) mbar_wait(full - 8 * AHEAD, 0);
                        mbar_expect_tx(full, SLOT);
                        const int e = 2 * (i & 3) + rank, g8 = i - 20;
                        const CUtensorMap* tm = i < 16 ? &P.twq : (i < 20 ? &P.two : (i < 44 ? &P.twg + rank : &P.twd));
                        const int c0 = i < 8 ? DM + DM * rank + 64 * j : ((i >= 20 && i < 44) ? 176 * j + 8 * (g8 & ~7) : 64 * j);
                        const int r0 = i < 8 ? 64 * i : (i < 16 ? 64 * e : (i < 20 ? 64 * KORD(e, j)
                                             : (i < 44 ? 64 * (g8 < 8 ? KORD(g8, j) : g8 & 7) : 176 * e + 64 * ((i - 44) >> 2))));
                        tma2d_mc(sb + OFF_B + r.slot * SLOT + rank * 8192, tm, full, c0, r0);
                    }
                    r.slot += i >= 20 && r.slot == 3;
                    r.adv();
                }
            }
            return;
        }
        if (warp == 9) {
            if (elect_one()) {
#pragma unroll 1
                for (int i = 2; i < 8; i++) {
                    if (i >= AHEAD + 1) mbar_wait(sb + BAR_FULLA + 8 * (i - AHEAD - 1), 0);
                    mbar_expect_tx(sb + BAR_FULLA + 8 * i, SLOT);
                    tma2d(sb + OFF_A + i * SLOT, &P.tx, sb + BAR_FULLA + 8 * i, 64 * i, 128 * m);
                }
#pragma unroll 1
                for (int i = 1; i < 10; i++) prefetch_tmap(&P.tx + i);
#pragma unroll 1
                for (int r = 1; r < 6; r++) {
                    const CUtensorMap* tm = &P.tx + min(r, 3);
                    const int cstep = r < 3 ? 64 : 192, cbase = r < 3 ? 0 : 64 * (r - 3), skip = r < 3 ? j : 8;
                    if (r < 4) mbar_wait(sb + BAR_EMPTYA + 8 * (skip == 0), (r - 1) & 1);
                    wait_count(g_flag + (m * 5 + r - 1) * 32, epoch * (r < 3 ? 64 : 8));
                    TL(64 + r, true);
#pragma unroll 1
                    for (int t = 0; t < 8; t++) {
                        if (t == skip) continue;
                        mbar_wait(sb + BAR_EMPTYA + 8 * t, (r - 1) & 1);
                        mbar_expect_tx(sb + BAR_FULLA + 8 * t, SLOT);
                        tma2d(sb + OFF_A + t * SLOT, tm, sb + BAR_FULLA + 8 * t, cbase + cstep * t, 128 * m);
                    }
                }
            }
            return;
        }
        const int a = warp - 10;
        {
            const int row = 16 * j + 8 * a + (lane >> 2);
            const uint32_t ra = sb + OFF_A + row * 128;
            float sh = 0.f, s0 = 0.f, s1 = 0.f, q0 = 0.f, q1 = 0.f;
#pragma unroll 1
            for (int kt = 0; kt < 8; kt++) {
                mbar_wait(sb + BAR_FULLA + 8 * kt, 0);
                if (kt == 0) sh = bf_lo(lds128(ra + ((row & 7) << 4)).x);
#pragma unroll
                for (int i = 0; i < 2; i++) {
                    const uint4 v = lds128(ra + kt * SLOT + (((2 * (lane & 3) + i) ^ (row & 7)) << 4));
                    const uint32_t ww[4] = {v.x, v.y, v.z, v.w};
#pragma unroll
                    for (int e = 0; e < 4; e++) {
                        const float d0 = bf_lo(ww[e]) - sh, d1 = bf_hi(ww[e]) - sh;
                        s0 += d0; q0 = fmaf(d0, d0, q0);
                        s1 += d1; q1 = fmaf(d1, d1, q1);
                    }
                }
            }
            s0 += s1; q0 += q1;
#pragma unroll
            for (int o = 1; o <= 2; o <<= 1) { s0 += __shfl_xor_sync(0xffffffffu, s0, o); q0 += __shfl_xor_sync(0xffffffffu, q0, o); }
            const float md = s0 * (1.f / DM);
            const float rs = rsqrtf(fmaxf(q0 * (1.f / DM) - md * md, 0.f) + 1e-5f);
            st_tagged_if(g_xstat + 2 * (128 * m + row), rs, -(sh + md), epoch, (lane & 3) == 0);
        }
        const unsigned long long* cs = g_cs + j * 768 + 2 * lane;
#pragma unroll 1
        for (int c = 0; c < (a ? 5 : 10); c++) {
            if (c == 4) {
                const int t = 32 * a + lane;
                const uint32_t kvs = sb + OFF_A + KVS(j) * SLOT;
                mbar_wait(sb + BAR_KVW, 0);
#pragma unroll 1
                for (int pass = 0; pass < 2; pass++) {
                    float4 v[8];
#pragma unroll
                    for (int i = 0; i < 8; i++) v[i] = ld_l2_f4(acc_j + ACC_KV + 4 * (t + 64 * i));
                    const float2 zz = ld_l2_f2(acc_j + ACC_Z + 2 * t);
#pragma unroll
                    for (int i = 0; i < 8; i++)
                        sts64(kvs + ((t >> 2) + 16 * i) * 48 + (t & 3) * 8, pack_bf16(v[i].x, v[i].y), pack_bf16(v[i].z, v[i].w));
                    const uint32_t z0 = pack_bf16(zz.x, zz.x), z1 = pack_bf16(zz.y, zz.y);
                    sts128(kvs + t * 96 + 32, z0, z0, z0, z0);
                    sts128(kvs + t * 96 + 80, z1, z1, z1, z1);
                    if (pass == 0) {
                        __syncwarp();
                        if (lane == 0) red_relaxed(cnt_j, 1);
                        TL(19, t == 0);
                        wait_count_warp(cnt_j, epoch * 32);
                        TL(14, t == 0);
                    }
                }
                mbar_arrive(sb + BAR_KVR);
                if (a) break;
            }
            if (c == 3 && !a) continue;
            const unsigned long long* src = c < 2 ? g_xstat + 2 * (128 * m + 64 * a + 32 * c + lane) : cs + (c < 4 ? 128 * (a + c - 2) : 128 + 64 * c);
            const uint32_t dst = c < 2 ? OFF_XST + (64 * a + 32 * c + lane) * 8
                                       : (c < 4 ? OFF_CS1 + (c == 2 ? 256 * (a + 1) : 0) + 8 * lane : OFF_CS3 + (32 * ((c - 4) >> 1) + lane) * 16 + 8 * (c & 1));
            uint4 v;
            uint32_t it = 0;
            while (true) {
                v = ld_tagged_rlx(src);
                if (!__any_sync(0xffffffffu, v.y != epoch || v.w != epoch)) break;
                __nanosleep(60);
                trap_if_gt(++it, 1u << 22);
            }
            sts64(sb + dst, v.x, v.z);
            if (c == 2 - a || (a && c > 1) || c == 9) mbar_arrive(sb + (c == 9 ? BAR_CS3 : (c == 2 - a ? BAR_CS1 : (c == 2 ? BAR_CSV : BAR_CSQ))));
        }
        {
            uint32_t it = 0;
            while (__any_sync(0xffffffffu, (int)(readback(g_flag + (m * 5 + 1) * 32) - epoch * 64) < 0)) {
                __nanosleep(200);
                trap_if_gt(++it, 1u << 22);
            }
#pragma unroll 1
            for (int rr = 0; rr < 2; rr++) {
                const int row = 64 * rr + 32 * a + lane;
                uint4 v[8];
                bool bad;
                do {
                    bad = false;
#pragma unroll
                    for (int i = 0; i < 8; i++) v[i] = ld_tagged_rlx(g_hstat + (1024 * m + 128 * i + row) * 2);
#pragma unroll
                    for (int i = 0; i < 8; i++) bad |= v[i].y != epoch || v[i].w != epoch;
                    trap_if_gt(++it, 1u << 22);
                } while (__any_sync(0xffffffffu, bad));
                float mean = 0.f;
#pragma unroll
                for (int i = 0; i < 8; i++) mean += __uint_as_float(v[i].x);
                mean *= 0.125f;
                float m2 = 0.f, dv = 0.f;
#pragma unroll
                for (int i = 0; i < 8; i++) { const float d = __uint_as_float(v[i].x) - mean; m2 += __uint_as_float(v[i].z); dv = fmaf(d, d, dv); }
                sts_f2(sb + OFF_CS1 + row * 8, -mean, rcp(fmaf(dv, 64.f, m2) * (1.f / DM) + 1e-5f));
            }
        }
        mbar_arrive(sb + BAR_CS3);
#pragma unroll 1
        for (int c = a; c < 3; c += 2) {
            mbar_wait(sb + BAR_STG + 8 * c, 0);
            if (elect_one()) {
                tma_store2d(&P.thh, sb + OFF_B + 4 * SLOT, 192 * j + 64 * c, 128 * m);
                asm volatile("cp.async.bulk.wait_group.read 0;" ::: "memory");
                mbar_arrive(sb + BAR_FULLB + 8 * 4);
                asm volatile("cp.async.bulk.wait_group 0;" ::: "memory");
            }
            __syncwarp();
            TL(60 + c, lane == 0);
            uint32_t ack = 0;
#pragma unroll
            for (int i = 0; i < 4; i++) ack |= readback(g_hh + (size_t)(128 * m + 32 * i + lane) * FFP + 192 * j + 64 * c);
            signal_after(g_flag + (m * 5 + 2 + c) * 32, ack, P.zero, lane == 0);
            TL(54 + c, lane == 0);
        }
        return;
    }
    const unsigned epoch = ld_relaxed(&g_epoch);
    uint32_t wraw[16];
    if (!helper) {
        const uint32_t* wp = reinterpret_cast<const uint32_t*>(P.wphi) + (4 * j) * 128 + (lane & 3) * 16 + (lane >> 2);
#pragma unroll
        for (int i = 0; i < 16; i++)
            asm volatile("ld.global.nc.u32 %0, [%1];" : "=r"(wraw[i]) : "l"(wp + (i >> 2) * 128 + ((i >> 1) & 1) * 64 + (i & 1) * 8));
    }
    asm volatile("barrier.cluster.arrive.relaxed.aligned;" ::: "memory");
    asm volatile("setmaxnreg.inc.sync.aligned.u32 216;");
    bar_sync(0, NTHREADS);
    if (helper) {
        if (warp < 4) {
            sts128(sb + OFF_B + 16 * tid, 0x3f803f80u, 0x3f803f80u, 0x3f803f80u, 0x3f803f80u);
            for (int i = tid; i < 2 * ACC_SIZE / 4; i += 128) stg128(g_acc + 2 * j * ACC_SIZE + 4 * i, 0, 0, 0, 0);
            fence_async_smem();
            fence_gpu();
            bar_sync(1, 128);
            float acc[8];
            int i = 0;
#pragma unroll 1
            for (int job = 0; job < 12; job++) {
                const int n = job < 6 ? 4 : 8;
#pragma unroll 1
                for (int t = 0; t < n; t++, i++) {
                    mbar_wait(sb + BAR_FULLA + 8 * (i & 7), (i >> 3) & 1);
                    wg_fence();
#pragma unroll
                    for (int k = 0; k < 8; k++)
                        wgmma_n8_tt(acc + (k & 4), desc_lo(sb + OFF_A) + (i & 7) * (SLOT >> 4) + 128 * k, desc_lo(sb + OFF_B), (t | (k & 3)) != 0);
                    wg_commit();
                    wg_wait<1>();
                    mbar_arrive_n_if(sb + BAR_EMPTYA + 8 * ((i + 7) & 7), 2, lane == 0 && i > 0);
                }
                wg_wait<0>();
                fence_acc<8>(acc);
                const int q = lane & 3;
                const float lo = (q & 1) ? acc[2] : acc[0], hi = (q & 1) ? acc[6] : acc[4];
                const float v = job < 6 ? lo + hi : ((q & 2) ? hi : lo);
                unsigned long long* dst = g_cs + ((2 * j + (job & 1)) * 6 + (job >> 1)) * 128 + (q >> 1) * 64 + 16 * warp + 8 * (q & 1) + (lane >> 2);
                asm volatile("st.relaxed.gpu.global.b64 [%0], %1;" ::"l"(dst), "l"(((unsigned long long)epoch << 32) | __float_as_uint(v)) : "memory");
            }
        }
        return;
    }
    {
        const int w = warp >> 2, wv = warp & 3, g = lane >> 2, q = lane & 3;
        const int row_w = 128 * m + 16 * warp;
        const uint32_t sa = sb + OFF_A + w * 8192;
        const desc_t dA = desc_lo(sa), dB = desc_lo(sb + OFF_B);
        unsigned* const flag_m = g_flag + m * 160;
        const bool l0 = lane == 0, l2 = lane < 2;
        const uint32_t eb = mapa(sb + BAR_EMPTYB, lane & 1);
        asm volatile("barrier.cluster.wait.aligned;" ::: "memory");
        Ring rg{0, 0};
        int prev = 0;

        uint32_t wb[16];
        constexpr float L2E = 1.4426950408889634f;
        const int ch = lane >> 4, sw = lane & 7;
        const uint32_t lrow = (lane & 15) * 128;
        uint32_t fp[16], fm[16];
        {
            float acc[64], accq[32];
#pragma unroll 1
            for (int kt = 0; kt < 8; kt++) {
                mbar_waitc(sb + BAR_FULLA + 8 * kt, 0);
                mbar_waitc(sb + BAR_FULLB + 8 * rg.slot, rg.phase);
                const desc_t da = dA + kt * (SLOT >> 4), db = dB + rg.slot * (SLOT >> 4);
                wg_fence();
#pragma unroll
                for (int k = 0; k < 4; k++) wgmma_n128(acc, da + 2 * k, db + 128 * k, (kt | k) != 0);
                wg_commit();
                wg_wait<1>();
                mbar_arrive_cl_if(eb + 8 * prev, l2 && kt > 0);
                prev = rg.slot; rg.adv();
            }
#pragma unroll
            for (int i = 0; i < 8; i++) {
                wb[(i >> 1) * 4 + (i & 1)] = __byte_perm(wraw[2 * i], wraw[2 * i + 1], 0x5410);
                wb[(i >> 1) * 4 + 2 + (i & 1)] = __byte_perm(wraw[2 * i], wraw[2 * i + 1], 0x7632);
            }
            float2 s0, s1;
            uint32_t a[16];
            wg_wait<0>();
            fence_acc<64>(acc);
            mbar_arrive_cl_if(eb + 8 * prev, l2);
#pragma unroll 1
            for (int it = 0; it < 2; it++) {
                mbar_waitc(sb + BAR_FULLB + 8 * 2, it ^ 1); mbar_waitc(sb + BAR_FULLB + 8 * 3, it ^ 1);
                const desc_t da = dA + it * (4 * SLOT >> 4);
                wg_fence();
#pragma unroll
                for (int k = 0; k < 16; k++) wgmma_n64(accq, da + (k >> 2) * (SLOT >> 4) + (k & 3) * 2, dB + 2 * (SLOT >> 4) + 128 * k, (it | k) != 0);
                wg_commit();
                TL(17 + it, tid == 0);
                mbar_waitc(sb + BAR_CS1 + 16 * it, 0);
                wg_wait<0>();
                fence_acc<32>(accq);
                mbar_arrive_cl_if(eb + 8 * (2 + (lane >> 1)), lane < 4);
                TL(2 + 2 * it, tid == 0);
                if (it == 0) {
                    s0 = lds_f2(sb + OFF_XST + (16 * warp + g) * 8); s1 = lds_f2(sb + OFF_XST + (16 * warp + g + 8) * 8);
#pragma unroll
                    for (int hh = 0; hh < 4; hh++)
                        ln_frag<false>(acc + 8 * hh, sb + OFF_CS1 + (64 + 16 * hh + 2 * q) * 4, 0.f, s0.y, 0.f, s1.y, a + 4 * hh);
                } else {
#pragma unroll
                    for (int hh = 0; hh < 4; hh++)
                        ln_frag<false>(accq + 8 * hh, sb + OFF_CS1 + (16 * hh + 2 * q) * 4, 0.f, s0.y, 0.f, s1.y, a + 4 * hh);
                }
                feature_maps(a, wb, s0.x * L2E, s1.x * L2E, fp, fm);
                if (it == 0) {
                    mbar_waitc(sb + BAR_FULLB + 8 * 4, 1); mbar_waitc(sb + BAR_FULLB + 8 * 5, 1);
                    mbar_waitc(sb + BAR_FULLB + 8 * 0, 0); mbar_waitc(sb + BAR_FULLB + 8 * 1, 0);
                    mbar_waitc(sb + BAR_CSV, 0);
                    const uint32_t st = sb + OFF_B + warp * 2048 + lrow;
#pragma unroll
                    for (int hh = 0; hh < 4; hh++) {
                        stsm4(st + (4 + (hh >> 1)) * SLOT + (((4 * (hh & 1) + ch) ^ sw) << 4), fp[4 * hh], fp[4 * hh + 1], fp[4 * hh + 2], fp[4 * hh + 3]);
                        stsm4(st + (4 + (hh >> 1)) * SLOT + (((4 * (hh & 1) + 2 + ch) ^ sw) << 4), fm[4 * hh], fm[4 * hh + 1], fm[4 * hh + 2], fm[4 * hh + 3]);
                        ln_frag<true>(acc + 32 + 8 * hh, sb + OFF_CS1 + (128 + 16 * hh + 2 * q) * 4, s0.x, s0.y, s1.x, s1.y, a);
                        stsm4(st + (hh >> 1) * SLOT + (((2 * (hh & 1) + ch) ^ sw) << 4), a[0], a[1], a[2], a[3]);
                    }
                    stsm4(st + ch * SLOT + ((4 ^ sw) << 4), 0x3f803f80u, 0x3f803f80u, 0x3f803f80u, 0x3f803f80u);
                    fence_async_smem();
                    bar_sync(1, 256);
                    float kvd[20];
                    wg_fence();
#pragma unroll
                    for (int k = 0; k < 8; k++)
                        wgmma_n40_tt(kvd, dB + (4 + w) * (SLOT >> 4) + 128 * k, dB + w * (SLOT >> 4) + 128 * k, k != 0);
                    wg_commit();
                    wg_wait<0>();
                    fence_acc<20>(kvd);
                    const bool h1 = wv >= 2;
                    const int f = 16 * warp + g;
                    float* kvp = acc_j + ACC_KV + f * 16 + 2 * q;
                    red_f32x2(kvp, h1 ? kvd[8] : kvd[0], h1 ? kvd[9] : kvd[1]);
                    red_f32x2(kvp + 128, h1 ? kvd[10] : kvd[2], h1 ? kvd[11] : kvd[3]);
                    red_f32x2(kvp + 8, h1 ? kvd[12] : kvd[4], h1 ? kvd[13] : kvd[5]);
                    red_f32x2(kvp + 136, h1 ? kvd[14] : kvd[6], h1 ? kvd[15] : kvd[7]);
                    red_f32_if(acc_j + ACC_Z + f + 8 * (q & 1), q ? kvd[18] : kvd[16], q < 2);
                    __syncwarp();
                    mbar_arrive_if(sb + BAR_KVW, l0);
                    mbar_arrive_cl_if(eb + 8 * ((4 + (lane >> 1)) % 6), lane < 8);
                    TL(3, tid == 0);
                }
            }
        }
        uint32_t res_lo[8], res_hi[8], ack[4];
        const uint32_t own_rows = sb + OFF_A + j * SLOT + warp * 2048;
#pragma unroll
        for (int b = 0; b < 4; b++)
            ldsm4(own_rows + lrow + (((2 * b + ch) ^ sw) << 4), res_lo[2 * b], res_hi[2 * b], res_lo[2 * b + 1], res_hi[2 * b + 1]);
        mbar_arrive_if(sb + BAR_EMPTYA + 8 * lane, lane < 8 && lane != j && lane != KVS(j));
        TL(5, tid == 0);
        mbar_waitc(sb + BAR_KVR, 0);
        TL(6, tid == 0);
        {
            const uint32_t kvs = sb + OFF_A + KVS(j) * SLOT;
            uint32_t o_lo[8], o_hi[8];
#pragma unroll
            for (int hh = 0; hh < 4; hh++) {
                uint32_t b[8], zb[4];
                const uint32_t base = kvs + hh * 32 * 48;
                ldsm4t(base + (lane & 15) * 48 + (lane >> 4) * 16, b[0], b[1], b[2], b[3]);
                ldsm4t(base + (16 + (lane & 15)) * 48 + (lane >> 4) * 16, b[4], b[5], b[6], b[7]);
                ldsm4t(base + lane * 48 + 32, zb[0], zb[1], zb[2], zb[3]);
                float n0[4], n1[4], dn[4];
                mma16816_z(n0, fp + 4 * hh, b[0], b[1]); mma16816_z(n1, fp + 4 * hh, b[2], b[3]); mma16816_z(dn, fp + 4 * hh, zb[0], zb[1]);
                mma16816(n0, fm + 4 * hh, b[4], b[5]); mma16816(n1, fm + 4 * hh, b[6], b[7]); mma16816(dn, fm + 4 * hh, zb[2], zb[3]);
                const float i0 = rcp(dn[0] + 1e-6f), i1 = rcp(dn[2] + 1e-6f);
                o_lo[2 * hh] = pack_bf16(n0[0] * i0, n0[1] * i0); o_hi[2 * hh] = pack_bf16(n0[2] * i1, n0[3] * i1);
                o_lo[2 * hh + 1] = pack_bf16(n1[0] * i0, n1[1] * i0); o_hi[2 * hh + 1] = pack_bf16(n1[2] * i1, n1[3] * i1);
            }
            __syncwarp();
            mbar_arrive_if(sb + BAR_EMPTYA + 8 * KVS(j), l0);
            rg.slot = 4; rg.phase = 0;
            store_tile(own_rows, g_o + (size_t)row_w * DM + 64 * j, o_lo, o_hi, lane, ack);
            TL(7, tid == 0);
        }
        {
            float acc[32];
#pragma unroll
            for (int t = 0; t < 8; t++) {
                acc[4 * t] = bf_lo(res_lo[t]); acc[4 * t + 1] = bf_hi(res_lo[t]);
                acc[4 * t + 2] = bf_lo(res_hi[t]); acc[4 * t + 3] = bf_hi(res_hi[t]);
            }
            fence_acc<32>(acc);
            int pa = 0;
#pragma unroll 1
            for (int kp = 0; kp < 4; kp++) {
                mbar_waitc(sb + BAR_FULLB + 8 * rg.slot, rg.phase);
#pragma unroll
                for (int hf = 0; hf < 2; hf++) {
                    const int i = 2 * kp + hf, kt = KORD(i, j);
                    mbar_waitc(sb + BAR_FULLA + 8 * kt, i != 0);
                    TL(8, i == 1 && tid == 0);
                    const desc_t da = dA + kt * (SLOT >> 4), db = dB + rg.slot * (SLOT >> 4);
                    wg_fence();
#pragma unroll
                    for (int k = 0; k < 4; k++) wgmma_n64(acc, da + 2 * k, db + (hf * 4 + k) * 128, 1);
                    wg_commit();
                    wg_wait<1>();
                    mbar_arrive_if(sb + BAR_EMPTYA + 8 * pa, l0 && i > 1);
                    if (hf == 0) {
                        mbar_arrive_cl_if(eb + 8 * prev, l2 && i > 0);
                        if (i == 0) { signal_late(flag_m, ack, P.zero, l0); TL(20, tid == 0); }
                    }
                    pa = kt;
                }
                prev = rg.slot; rg.adv();
            }
            wg_wait<0>();
            fence_acc<32>(acc);
            mbar_arrive_if(sb + BAR_EMPTYA + 8 * pa, l0);
            mbar_arrive_cl_if(eb + 8 * prev, l2);
            TL(9, tid == 0);
            float s0 = 0.f, s1 = 0.f;
#pragma unroll
            for (int t = 0; t < 8; t++) {
                res_lo[t] = pack_bf16(acc[4 * t], acc[4 * t + 1]);
                res_hi[t] = pack_bf16(acc[4 * t + 2], acc[4 * t + 3]);
                s0 += acc[4 * t] + acc[4 * t + 1];
                s1 += acc[4 * t + 2] + acc[4 * t + 3];
            }
            store_tile(own_rows, g_h + (size_t)row_w * DM + 64 * j, res_lo, res_hi, lane, ack);
            s0 += __shfl_xor_sync(0xffffffffu, s0, 1); s1 += __shfl_xor_sync(0xffffffffu, s1, 1);
            s0 += __shfl_xor_sync(0xffffffffu, s0, 2); s1 += __shfl_xor_sync(0xffffffffu, s1, 2);
            const float mu0 = s0 * (1.f / 64), mu1 = s1 * (1.f / 64);
            float q0 = 0.f, q1 = 0.f;
#pragma unroll
            for (int t = 0; t < 8; t++) {
                float d;
                d = acc[4 * t] - mu0; q0 = fmaf(d, d, q0);
                d = acc[4 * t + 1] - mu0; q0 = fmaf(d, d, q0);
                d = acc[4 * t + 2] - mu1; q1 = fmaf(d, d, q1);
                d = acc[4 * t + 3] - mu1; q1 = fmaf(d, d, q1);
            }
            q0 += __shfl_xor_sync(0xffffffffu, q0, 1); q1 += __shfl_xor_sync(0xffffffffu, q1, 1);
            q0 += __shfl_xor_sync(0xffffffffu, q0, 2); q1 += __shfl_xor_sync(0xffffffffu, q1, 2);
            st_tagged_if(g_hstat + (role * 128 + 16 * warp + g + 8 * (q & 1)) * 2, q ? mu1 : mu0, q ? q1 : q0, epoch, q < 2);
            TL(10, tid == 0);
        }
        float acc0[64], acc1[64], acc2[56], nm0, nm1;
        float4 cs[8];
        uint32_t hr[16];
#define P3_GROUP(MMA, ACC, KT)                                                                              \
        mbar_waitc(sb + BAR_FULLB + 8 * rg.slot, rg.phase);                                                 \
        {                                                                                                   \
            const desc_t da = dA + (KT) * (SLOT >> 4), db = dB + rg.slot * (SLOT >> 4);                     \
            wg_fence();                                                                                     \
            _Pragma("unroll") for (int k = 0; k < 4; k++) MMA(ACC, da + 2 * k, db + 128 * k, (i | k) != 0); \
            wg_commit();                                                                                    \
        }
#define P3_PRE(C, NT)                                           \
        if (C) mbar_waitc(sb + BAR_FULLB + 8 * 4, (C) & 1);                                                 \
        _Pragma("unroll") for (int t = 0; t < (NT); t++) cs[t] = lds_f4(sb + OFF_CS3 + q * 16 + 512 * (C) + 64 * t);
#define P3_EPI(C, ACC, N, NTP)                                                                              \
        fence_acc<N>(ACC);                                                                                  \
        TL(11 + (C), tid == 0);                                                                             \
        hh_stage<NTP>(ACC, cs, nm0, nm1, sb + OFF_B + 4 * SLOT + warp * 2048, lane);                 \
        mbar_arrive_if(sb + BAR_STG + 8 * (C), l0);                                                         \
        TL(50 + (C), tid == 0);
#pragma unroll 1
        for (int i = 0; i < 8; i++) {
            const int kt = KORD(i, j);
            mbar_waitc(sb + BAR_FULLA + 8 * kt, 0);
            TL(44, tid == 0 && i == 1);
            P3_GROUP(wgmma_n128, acc0, kt)
            wg_wait<1>();
            mbar_arrive_cl_if(eb + 8 * prev, l2 && i > 0);
            if (i == 0) { signal_late(flag_m + 32, ack, P.zero, l0); TL(21, tid == 0); }
            prev = rg.slot; rg.adv5();
        }
        mbar_waitc(sb + BAR_CS3, 0);
        nm0 = lds_f2(sb + OFF_CS1 + (16 * warp + g) * 8).x; nm1 = lds_f2(sb + OFF_CS1 + (16 * warp + g + 8) * 8).x;
        P3_PRE(0, 8)
#pragma unroll 1
        for (int i = 0; i < 8; i++) {
            P3_GROUP(wgmma_n128, acc1, i)
            wg_wait<1>();
            mbar_arrive_cl_if(eb + 8 * prev, l2);
            if (i == 0) { P3_EPI(0, acc0, 64, 4) }
            prev = rg.slot; rg.adv5();
        }
        const uint32_t blk = ((lane & 7) + (lane >> 4) * 8) * 128 + (((2 * wv + ((lane >> 3) & 1)) ^ (lane & 7)) << 4);
#pragma unroll
        for (int tp = 0; tp < 4; tp++) ldsm4t(sa + j * SLOT + blk + tp * 2048, hr[4 * tp], hr[4 * tp + 1], hr[4 * tp + 2], hr[4 * tp + 3]);
        P3_PRE(1, 8)
#pragma unroll 1
        for (int i = 0; i < 8; i++) {
            P3_GROUP(wgmma_n112, acc2, i)
            wg_wait<1>();
            mbar_arrive_cl_if(eb + 8 * prev, l2);
            mbar_arrive_if(sb + BAR_EMPTYA + 8 * ((i + 7) & 7), l0 && i > 0);
            if (i == 0) { P3_EPI(1, acc1, 64, 4) }
            prev = rg.slot; rg.adv5();
        }
        P3_PRE(2, 6)
        {
            float acc[64];
            const desc_t dA0 = desc_lo(sb + OFF_A);
#define KT_P4(I, NK)                                                                                        \
        const int s_ = (2 * (I) + w) & 7;                                                                   \
        mbar_waitc(sb + BAR_FULLB + 8 * rg.slot, rg.phase);                                                 \
        mbar_waitc(sb + BAR_FULLA + 8 * s_, (((I) >> 2) + 1) & 1);                                          \
        TL(30 + (I), tid == 0);                                                                             \
        const desc_t dh_ = dA0 + s_ * (SLOT >> 4), dw_ = dB + rg.slot * (SLOT >> 4) + w * 512;              \
        wg_fence();                                                                                         \
        _Pragma("unroll") for (int k = 0; k < (NK); k++) wgmma_n128_tn(acc, dw_ + 128 * k, dh_ + 2 * k, ((I) | k) != 0); \
        wg_commit();                                                                                        \
        wg_wait<1>();
#pragma unroll 1
            for (int i = 0; i < 8; i++) {
                KT_P4(i, 4)
                mbar_arrive_n_if(sb + BAR_EMPTYA + 8 * (i ? (s_ + 6) & 7 : 7), i ? 2 : 1, l0);
                mbar_arrive_cl_if(eb + 8 * prev, l2);
                if (i == 0) { P3_EPI(2, acc2, 56, 3) }
                prev = rg.slot; rg.adv5();
            }
#pragma unroll 1
            for (int i = 8; i < 12; i++) {
                KT_P4(i, 3)
                mbar_arrive_n_if(sb + BAR_EMPTYA + 8 * ((s_ + 6) & 7), 2, l0);
                rg.adv5();
            }
            float r2[16];
#pragma unroll
            for (int t = 0; t < 8; t++) {
                const float4 st = lds_f4(sb + OFF_CS1 + (64 * w + 8 * t + 2 * q) * 8);
                r2[2 * t] = st.y; r2[2 * t + 1] = st.w;
            }
            wg_wait<0>();
            fence_acc<64>(acc);
            TL(15, tid == 0);
            const uint32_t xch = sb + OFF_A + 2 * SLOT + (tid & 127) * 16;
            if (w) {
#pragma unroll
                for (int t = 0; t < 8; t++) {
                    sts128(xch + SLOT + t * 2048, __float_as_uint(acc[4 * t]), __float_as_uint(acc[4 * t + 1]),
                           __float_as_uint(acc[4 * t + 2]), __float_as_uint(acc[4 * t + 3]));
                }
#pragma unroll
                for (int t = 0; t < 32; t++) acc[t] = acc[32 + t];
            } else {
#pragma unroll
                for (int t = 0; t < 8; t++)
                    sts128(xch + t * 2048, __float_as_uint(acc[32 + 4 * t]), __float_as_uint(acc[33 + 4 * t]),
                           __float_as_uint(acc[34 + 4 * t]), __float_as_uint(acc[35 + 4 * t]));
            }
            bar_sync(1, 256);
            float4 o[8];
#pragma unroll
            for (int t = 0; t < 8; t++) o[t] = lds_f4(xch + (w ^ 1) * SLOT + t * 2048);
            const uint32_t tile = sb + OFF_A + w * SLOT;
#pragma unroll
            for (int t = 0; t < 8; t++) {
                hr[2 * t] = pack_bf16(fmaf(acc[4 * t] + o[t].x, r2[2 * t], bf_lo(hr[2 * t])), fmaf(acc[4 * t + 1] + o[t].y, r2[2 * t + 1], bf_hi(hr[2 * t])));
                hr[2 * t + 1] = pack_bf16(fmaf(acc[4 * t + 2] + o[t].z, r2[2 * t], bf_lo(hr[2 * t + 1])), fmaf(acc[4 * t + 3] + o[t].w, r2[2 * t + 1], bf_hi(hr[2 * t + 1])));
            }
#pragma unroll
            for (int tp = 0; tp < 4; tp++) stsm4t(tile + blk + tp * 2048, hr[4 * tp], hr[4 * tp + 1], hr[4 * tp + 2], hr[4 * tp + 3]);
            fence_async_smem();
            bar_sync(2 + w, 128);
            if ((tid & 127) == 0) {
                tma_store2d(&P.tout, tile, 64 * j, 128 * m + 64 * w);
                asm volatile("cp.async.bulk.wait_group.read 0;" ::: "memory");
            }
            if (tid == 0 && role == 0) g_epoch = epoch + 1;
            TL(16, tid == 0); TLG(1, tid == 0);
        }
    }
}

__global__ void probe_kernel() {}

typedef CUresult (*EncodeFn)(CUtensorMap*, CUtensorMapDataType, cuuint32_t, void*, const cuuint64_t*, const cuuint64_t*,
                             const cuuint32_t*, const cuuint32_t*, CUtensorMapInterleave, CUtensorMapSwizzle,
                             CUtensorMapL2promotion, CUtensorMapFloatOOBfill);

static void make_map2d(EncodeFn enc, CUtensorMap* tm, const void* base, uint64_t cols, uint64_t rows, uint64_t pitch_elems,
                       uint32_t box_rows) {
    cuuint64_t gd[2] = {cols, rows};
    cuuint64_t gs[1] = {pitch_elems * 2};
    cuuint32_t bd[2] = {64, box_rows};
    cuuint32_t es[2] = {1, 1};
    enc(tm, CU_TENSOR_MAP_DATA_TYPE_BFLOAT16, 2, const_cast<void*>(base), gd, gs, bd, es, CU_TENSOR_MAP_INTERLEAVE_NONE,
        CU_TENSOR_MAP_SWIZZLE_128B, CU_TENSOR_MAP_L2_PROMOTION_L2_256B, CU_TENSOR_MAP_FLOAT_OOB_FILL_NONE);
}

}

extern "C" void kernel_launch(void* const* d_in, const int* in_sizes, int n_in, void* d_out, int out_size) {
    using namespace hk;
    (void)in_sizes; (void)n_in; (void)out_size;
    static EncodeFn enc = nullptr;
    static void *po = nullptr, *ph = nullptr, *phh = nullptr;
    static int std_layout = 0;
    if (!enc) {
        void* fn = nullptr;
        cudaDriverEntryPointQueryResult qr;
        cudaGetDriverEntryPoint("cuTensorMapEncodeTiled", &fn, cudaEnableDefault, &qr);
        enc = (EncodeFn)fn;
        cudaGetSymbolAddress(&po, g_o);
        cudaGetSymbolAddress(&ph, g_h);
        cudaGetSymbolAddress(&phh, g_hh);
        cudaFuncSetAttribute(fused_kernel, cudaFuncAttributeMaxDynamicSharedMemorySize, SMEM_BYTES);
        int dev = 0, sms = 0;
        cudaGetDevice(&dev);
        cudaDeviceGetAttribute(&sms, cudaDevAttrMultiProcessorCount, dev);
        cudaFuncSetAttribute(probe_kernel, cudaFuncAttributeNonPortableClusterSizeAllowed, 1);
        cudaFuncSetAttribute(probe_kernel, cudaFuncAttributeMaxDynamicSharedMemorySize, SMEM_BYTES);
        const int sizes[3] = {8, 9, 16}, want[3] = {15, 9, 7};
        bool ok = sms == NCTA;
        for (int i = 0; i < 3 && ok; i++) {
            cudaLaunchConfig_t cfg = {};
            cfg.gridDim = dim3(sizes[i] * 8); cfg.blockDim = dim3(NTHREADS); cfg.dynamicSmemBytes = SMEM_BYTES;
            cudaLaunchAttribute at;
            at.id = cudaLaunchAttributeClusterDimension;
            at.val.clusterDim.x = sizes[i]; at.val.clusterDim.y = 1; at.val.clusterDim.z = 1;
            cfg.attrs = &at; cfg.numAttrs = 1;
            int n = 0;
            ok = cudaOccupancyMaxActiveClusters(&n, probe_kernel, &cfg) == cudaSuccess && n == want[i];
        }
        (void)cudaGetLastError();
        std_layout = ok ? 1 : 0;
    }
    Params P;
    const __nv_bfloat16* x = (const __nv_bfloat16*)d_in[0];
    P.x = x;
    P.wqkv = (const __nv_bfloat16*)d_in[1];
    P.wphi = (const __nv_bfloat16*)d_in[2];
    P.wo = (const __nv_bfloat16*)d_in[3];
    P.wg = (const __nv_bfloat16*)d_in[5];
    P.wu = (const __nv_bfloat16*)d_in[6];
    P.wd = (const __nv_bfloat16*)d_in[7];
    P.out = (__nv_bfloat16*)d_out;
    P.zero = 0;
    for (int i = 0; i < NCTA; i++) {
        const int odd = i & 1;
        int role = i < 4 ? 128 + i : (((i - 4) >> 4) * 2 + odd) * 8 + (((i - 4) >> 1) & 7);
        if (std_layout) {
            const int tpc = i < 8 ? 62 + (i >> 1) : (i - 8) >> 1;
            if (tpc < 32) role = (tpc & 7) ? (2 * ((tpc & 7) - 1) + odd) * 8 + (tpc >> 3) : (14 + odd) * 8 + (tpc >> 3);
            else if (tpc < 60) role = (2 * ((tpc - 32) % 7) + odd) * 8 + 4 + (tpc - 32) / 7;
            else if (tpc < 62) role = 128 + (tpc - 60) * 2 + odd;
            else role = (14 + odd) * 8 + 4 + (tpc - 62);
        }
        P.role[i] = (unsigned char)role;
    }
    make_map2d(enc, &P.tx, x, DM, SEQ, DM, 128);
    make_map2d(enc, &P.to, po, DM, SEQ, DM, 128);
    make_map2d(enc, &P.th, ph, DM, SEQ, DM, 128);
    make_map2d(enc, &P.thh, phh, FFP, SEQ, FFP, 128);
    make_map2d(enc, &P.twq, P.wqkv, 3 * DM, DM, 3 * DM, 64);
    make_map2d(enc, &P.two, P.wo, DM, DM, DM, 64);
    make_map2d(enc, &P.twg, P.wg, FF, DM, FF, 64);
    make_map2d(enc, &P.twu, P.wu, FF, DM, FF, 64);
    make_map2d(enc, &P.twd, P.wd, DM, FF, DM, 64);
    make_map2d(enc, &P.tout, d_out, DM, SEQ, DM, 64);
    fused_kernel<<<NCTA, NTHREADS, SMEM_BYTES>>>(P);
}
```

```cpp
#include <cuda_runtime.h>
#include <cuda_bf16.h>
#include <cuda.h>
#include <stdint.h>

namespace hk {

constexpr int SEQ = 2048, DM = 512, FF = 1376, FFP = 1536;
constexpr int NCTA = 132;
constexpr int NTHREADS = 384;
constexpr uint32_t SLOT = 16384;
constexpr uint32_t OFF_A = 0, OFF_B = 8 * SLOT, OFF_MISC = 14 * SLOT;
constexpr uint32_t BAR_FULLA = OFF_MISC + 0, BAR_EMPTYA = OFF_MISC + 64, BAR_FULLB = OFF_MISC + 128,
                   BAR_EMPTYB = OFF_MISC + 176, BAR_CS1 = OFF_MISC + 224, BAR_CS3 = OFF_MISC + 232,
                   BAR_CSQ = OFF_MISC + 240, BAR_CSV = OFF_MISC + 248,
                   BAR_STG = OFF_MISC + 256,
                   BAR_KVW = OFF_MISC + 280, BAR_KVR = OFF_MISC + 288;
constexpr uint32_t OFF_CS1 = OFF_MISC + 384;
constexpr uint32_t OFF_CS3 = OFF_CS1 + 1024;
constexpr uint32_t OFF_XST = OFF_CS3;
constexpr uint32_t SMEM_BYTES = OFF_CS3 + 1536;
#define KVS(j) ((j) == 3 ? 2 : 3)
#define KORD(i, j) ((i) == 0 ? (j) : (i) - ((i) <= (j)))
constexpr int NB = 6;
constexpr int AHEAD = 3;

constexpr int ACC_KV = 0, ACC_Z = 2048, ACC_SIZE = 2176;

__device__ __align__(1024) __nv_bfloat16 g_o[SEQ * DM];
__device__ __align__(1024) __nv_bfloat16 g_h[SEQ * DM];
__device__ __align__(1024) __nv_bfloat16 g_hh[SEQ * FFP];
__device__ __align__(128) unsigned long long g_hstat[SEQ * 16];
__device__ __align__(128) unsigned long long g_xstat[SEQ * 2];
__device__ __align__(128) float g_acc[8 * ACC_SIZE];
__device__ __align__(128) unsigned g_cnt[8 * 32];
__device__ __align__(128) unsigned long long g_cs[8 * 6 * 128];
__device__ __align__(128) unsigned g_flag[16 * 5 * 32];
__device__ unsigned g_epoch = 1;

#define TL(i, pred) do {} while (0)
#define TLG(i, pred) do {} while (0)

struct Params {
    CUtensorMap tx, to, th, thh, twq, two, twg, twu, twd, tout;
    const __nv_bfloat16 *x, *wqkv, *wphi, *wo, *wg, *wu, *wd;
    __nv_bfloat16* out;
    unsigned zero;
    unsigned char role[NCTA];
};

__device__ __forceinline__ uint32_t smem_u32(const void* p) { return (uint32_t)__cvta_generic_to_shared(p); }
__device__ __forceinline__ void mbar_init(uint32_t bar, uint32_t cnt) {
    asm volatile("mbarrier.init.shared::cta.b64 [%0], %1;" ::"r"(bar), "r"(cnt) : "memory");
}
__device__ __forceinline__ void mbar_expect_tx(uint32_t bar, uint32_t bytes) {
    asm volatile("mbarrier.arrive.expect_tx.shared::cta.b64 _, [%0], %1;" ::"r"(bar), "r"(bytes) : "memory");
}
__device__ __forceinline__ void mbar_arrive(uint32_t bar) {
    asm volatile("mbarrier.arrive.shared::cta.b64 _, [%0];" ::"r"(bar) : "memory");
}
__device__ __forceinline__ void mbar_arrive_if(uint32_t bar, bool pred) {
    asm volatile("{.reg .pred p; setp.ne.u32 p, %1, 0; @p mbarrier.arrive.shared::cta.b64 _, [%0];}" ::"r"(bar), "r"((uint32_t)pred) : "memory");
}
__device__ __forceinline__ bool mbar_try(uint32_t bar, uint32_t parity) {
    uint32_t ok;
    asm volatile("{.reg .pred p; mbarrier.try_wait.parity.shared::cta.b64 p, [%1], %2; selp.u32 %0,1,0,p;}"
                 : "=r"(ok) : "r"(bar), "r"(parity) : "memory");
    return ok;
}
__device__ __forceinline__ bool mbar_test(uint32_t bar, uint32_t parity) {
    uint32_t ok;
    asm volatile("{.reg .pred p; mbarrier.test_wait.parity.shared::cta.b64 p, [%1], %2; selp.u32 %0,1,0,p;}"
                 : "=r"(ok) : "r"(bar), "r"(parity) : "memory");
    return ok;
}
__device__ __forceinline__ void trap_if_gt(uint32_t v, uint32_t lim) {
    asm volatile("{.reg .pred p; setp.gt.u32 p, %0, %1; @p trap;}" ::"r"(v), "r"(lim));
}
__device__ __forceinline__ void mbar_wait(uint32_t bar, uint32_t parity) {
    asm volatile("{\n"
                 ".reg .pred P1, P2;\n"
                 ".reg .u32 c;\n"
                 "mov.u32 c, 0;\n"
                 "LAB_WAIT:\n"
                 "mbarrier.try_wait.parity.shared::cta.b64 P1, [%0], %1;\n"
                 "@P1 bra LAB_DONE;\n"
                 "add.u32 c, c, 1;\n"
                 "setp.gt.u32 P2, c, 4194304;\n"
                 "@P2 trap;\n"
                 "bra LAB_WAIT;\n"
                 "LAB_DONE:\n"
                 "}" ::"r"(bar), "r"(parity) : "memory");
}
__device__ __forceinline__ void mbar_waitc(uint32_t bar, uint32_t parity) {
    asm volatile("{\n"
                 ".reg .pred P1;\n"
                 "LAB_WAIT:\n"
                 "mbarrier.try_wait.parity.shared::cta.b64 P1, [%0], %1;\n"
                 "@!P1 bra LAB_WAIT;\n"
                 "}" ::"r"(bar), "r"(parity) : "memory");
}
__device__ __forceinline__ void tma2d(uint32_t dst, const CUtensorMap* tm, uint32_t bar, int c0, int c1) {
    asm volatile("cp.async.bulk.tensor.2d.shared::cluster.global.mbarrier::complete_tx::bytes [%0], [%1, {%3, %4}], [%2];"
                 ::"r"(dst), "l"(tm), "r"(bar), "r"(c0), "r"(c1) : "memory");
}
__device__ __forceinline__ void tma2d_mc(uint32_t dst, const CUtensorMap* tm, uint32_t bar, int c0, int c1) {
    asm volatile("cp.async.bulk.tensor.2d.shared::cluster.global.mbarrier::complete_tx::bytes.multicast::cluster [%0], [%1, {%3, %4}], [%2], %5;"
                 ::"r"(dst), "l"(tm), "r"(bar), "r"(c0), "r"(c1), "h"((uint16_t)3) : "memory");
}
__device__ __forceinline__ uint32_t mapa(uint32_t addr, uint32_t rank) {
    uint32_t r; asm("mapa.shared::cluster.u32 %0, %1, %2;" : "=r"(r) : "r"(addr), "r"(rank)); return r;
}
__device__ __forceinline__ void mbar_arrive_cl_if(uint32_t cbar, bool pred) {
    asm volatile("{.reg .pred p; setp.ne.u32 p, %1, 0; @p mbarrier.arrive.shared::cluster.b64 _, [%0];}" ::"r"(cbar), "r"((uint32_t)pred) : "memory");
}
__device__ __forceinline__ bool elect_one() {
    uint32_t ok;
    asm volatile("{.reg .pred p; elect.sync _|p, 0xffffffff; selp.u32 %0, 1, 0, p;}" : "=r"(ok));
    return ok;
}
__device__ __forceinline__ void prefetch_tmap(const CUtensorMap* tm) {
    asm volatile("prefetch.tensormap [%0];" ::"l"(tm) : "memory");
}
__device__ __forceinline__ void prefetch_l2(const void* p, uint32_t bytes) {
    asm volatile("cp.async.bulk.prefetch.L2.global [%0], %1;" ::"l"(p), "r"(bytes) : "memory");
}
__device__ __forceinline__ unsigned ld_acquire(const unsigned* p) {
    unsigned v; asm volatile("ld.acquire.gpu.global.u32 %0, [%1];" : "=r"(v) : "l"(p) : "memory"); return v;
}
__device__ __forceinline__ uint4 ld_acquire4(const unsigned* p) {
    uint4 v;
    asm volatile("ld.acquire.gpu.global.v4.u32 {%0,%1,%2,%3}, [%4];" : "=r"(v.x), "=r"(v.y), "=r"(v.z), "=r"(v.w) : "l"(p) : "memory");
    return v;
}
__device__ __forceinline__ unsigned ld_relaxed(const unsigned* p) {
    unsigned v; asm volatile("ld.relaxed.gpu.global.u32 %0, [%1];" : "=r"(v) : "l"(p)); return v;
}
__device__ __forceinline__ void st_relaxed(unsigned* p, unsigned v) {
    asm volatile("st.relaxed.gpu.global.u32 [%0], %1;" ::"l"(p), "r"(v) : "memory");
}
__device__ __forceinline__ void red_relaxed(unsigned* p, unsigned v) {
    asm volatile("red.relaxed.gpu.global.add.u32 [%0], %1;" ::"l"(p), "r"(v) : "memory");
}
__device__ __forceinline__ void fence_gpu() { asm volatile("fence.acq_rel.gpu;" ::: "memory"); }
__device__ __forceinline__ void fence_async_smem() { asm volatile("fence.proxy.async.shared::cta;" ::: "memory"); }
__device__ __forceinline__ void fence_async_global() { asm volatile("fence.proxy.async.global;" ::: "memory"); }
__device__ __forceinline__ uint32_t readback(const void* p) {
    uint32_t v; asm volatile("ld.relaxed.gpu.global.u32 %0, [%1];" : "=r"(v) : "l"(p) : "memory"); return v;
}
__device__ __forceinline__ void wait_count(const unsigned* p, unsigned target) {
    uint32_t it = 0;
    while ((int)(readback(p) - target) < 0) trap_if_gt(++it, 1u << 22);
}
__device__ __forceinline__ void wait_count_warp(const unsigned* p, unsigned target) {
    uint32_t it = 0;
    while (__any_sync(0xffffffffu, (int)(readback(p) - target) < 0)) trap_if_gt(++it, 1u << 22);
}
__device__ __forceinline__ void red_f32(float* p, float a) {
    asm volatile("red.relaxed.gpu.global.add.f32 [%0], %1;" ::"l"(p), "f"(a) : "memory");
}
__device__ __forceinline__ void red_f32x2(float* p, float a, float b) {
    asm volatile("red.relaxed.gpu.global.add.v2.f32 [%0], {%1, %2};" ::"l"(p), "f"(a), "f"(b) : "memory");
}
__device__ __forceinline__ void red_f32x4(float* p, float a, float b, float c, float d) {
    asm volatile("red.relaxed.gpu.global.add.v4.f32 [%0], {%1, %2, %3, %4};" ::"l"(p), "f"(a), "f"(b), "f"(c), "f"(d) : "memory");
}
__device__ __forceinline__ float4 ld_l2_f4(const float* p) {
    float4 v;
    asm volatile("ld.relaxed.gpu.global.v4.f32 {%0,%1,%2,%3}, [%4];" : "=f"(v.x), "=f"(v.y), "=f"(v.z), "=f"(v.w) : "l"(p) : "memory");
    return v;
}
__device__ __forceinline__ float2 ld_l2_f2(const float* p) {
    float2 v;
    asm volatile("ld.relaxed.gpu.global.v2.f32 {%0,%1}, [%2];" : "=f"(v.x), "=f"(v.y) : "l"(p) : "memory");
    return v;
}
__device__ __forceinline__ float ld_l2_f(const float* p) {
    float v;
    asm volatile("ld.relaxed.gpu.global.f32 %0, [%1];" : "=f"(v) : "l"(p) : "memory");
    return v;
}
__device__ __forceinline__ uint4 ldg_nc(const void* p) {
    uint4 v;
    asm volatile("ld.global.nc.L1::no_allocate.v4.u32 {%0,%1,%2,%3}, [%4];" : "=r"(v.x), "=r"(v.y), "=r"(v.z), "=r"(v.w) : "l"(p));
    return v;
}
__device__ __forceinline__ void stg128(void* p, uint32_t a, uint32_t b, uint32_t c, uint32_t d) {
    asm volatile("st.global.v4.u32 [%0], {%1,%2,%3,%4};" ::"l"(p), "r"(a), "r"(b), "r"(c), "r"(d) : "memory");
}
__device__ __forceinline__ uint4 lds128(uint32_t a) {
    uint4 v;
    asm volatile("ld.shared.v4.u32 {%0,%1,%2,%3}, [%4];" : "=r"(v.x), "=r"(v.y), "=r"(v.z), "=r"(v.w) : "r"(a) : "memory");
    return v;
}
__device__ __forceinline__ float2 lds_f2(uint32_t a) {
    float2 v;
    asm volatile("ld.shared.v2.f32 {%0,%1}, [%2];" : "=f"(v.x), "=f"(v.y) : "r"(a) : "memory");
    return v;
}
__device__ __forceinline__ void sts_f2(uint32_t a, float x, float y) {
    asm volatile("st.shared.v2.f32 [%0], {%1,%2};" ::"r"(a), "f"(x), "f"(y) : "memory");
}
__device__ __forceinline__ void sts64(uint32_t a, uint32_t x, uint32_t y) {
    asm volatile("st.shared.v2.u32 [%0], {%1,%2};" ::"r"(a), "r"(x), "r"(y) : "memory");
}
__device__ __forceinline__ void sts128(uint32_t a, uint32_t x, uint32_t y, uint32_t z, uint32_t w) {
    asm volatile("st.shared.v4.u32 [%0], {%1,%2,%3,%4};" ::"r"(a), "r"(x), "r"(y), "r"(z), "r"(w) : "memory");
}
__device__ __forceinline__ void stsm4(uint32_t a, uint32_t r0, uint32_t r1, uint32_t r2, uint32_t r3) {
    asm volatile("stmatrix.sync.aligned.m8n8.x4.shared.b16 [%0], {%1,%2,%3,%4};" ::"r"(a), "r"(r0), "r"(r1), "r"(r2), "r"(r3) : "memory");
}
__device__ __forceinline__ void stsm4t(uint32_t a, uint32_t r0, uint32_t r1, uint32_t r2, uint32_t r3) {
    asm volatile("stmatrix.sync.aligned.m8n8.x4.trans.shared.b16 [%0], {%1,%2,%3,%4};" ::"r"(a), "r"(r0), "r"(r1), "r"(r2), "r"(r3) : "memory");
}
__device__ __forceinline__ void tma_store2d(const CUtensorMap* tm, uint32_t src, int c0, int c1) {
    asm volatile("cp.async.bulk.tensor.2d.global.shared::cta.bulk_group [%0, {%2, %3}], [%1];" ::"l"(tm), "r"(src), "r"(c0), "r"(c1) : "memory");
    asm volatile("cp.async.bulk.commit_group;" ::: "memory");
}
__device__ __forceinline__ void ldsm4(uint32_t a, uint32_t& r0, uint32_t& r1, uint32_t& r2, uint32_t& r3) {
    asm volatile("ldmatrix.sync.aligned.m8n8.x4.shared.b16 {%0,%1,%2,%3}, [%4];" : "=r"(r0), "=r"(r1), "=r"(r2), "=r"(r3) : "r"(a) : "memory");
}
__device__ __forceinline__ void ldsm4t(uint32_t a, uint32_t& r0, uint32_t& r1, uint32_t& r2, uint32_t& r3) {
    asm volatile("ldmatrix.sync.aligned.m8n8.x4.trans.shared.b16 {%0,%1,%2,%3}, [%4];" : "=r"(r0), "=r"(r1), "=r"(r2), "=r"(r3) : "r"(a) : "memory");
}
__device__ __forceinline__ void mma16816(float* c, const uint32_t* a, uint32_t b0, uint32_t b1) {
    asm("mma.sync.aligned.m16n8k16.row.col.f32.bf16.bf16.f32 {%0,%1,%2,%3}, {%4,%5,%6,%7}, {%8,%9}, {%0,%1,%2,%3};"
                 : "+f"(c[0]), "+f"(c[1]), "+f"(c[2]), "+f"(c[3])
                 : "r"(a[0]), "r"(a[1]), "r"(a[2]), "r"(a[3]), "r"(b0), "r"(b1));
}
__device__ __forceinline__ uint32_t pack_bf16(float lo, float hi) {
    uint32_t r; asm("cvt.rn.bf16x2.f32 %0, %1, %2;" : "=r"(r) : "f"(hi), "f"(lo)); return r;
}
__device__ __forceinline__ float bf_lo(uint32_t w) { return __uint_as_float(w << 16); }
__device__ __forceinline__ float bf_hi(uint32_t w) { return __uint_as_float(w & 0xffff0000u); }
__device__ __forceinline__ float ex2(float x) { float r; asm("ex2.approx.ftz.f32 %0, %1;" : "=f"(r) : "f"(x)); return r; }
__device__ __forceinline__ float rcp(float x) { float r; asm("rcp.approx.ftz.f32 %0, %1;" : "=f"(r) : "f"(x)); return r; }
__device__ __forceinline__ void bar_sync(int id, int n) { asm volatile("bar.sync %0, %1;" ::"r"(id), "r"(n) : "memory"); }

typedef unsigned long long desc_t;
__device__ __forceinline__ desc_t desc_lo(uint32_t addr) { return (desc_t)(((addr & 0x3FFFF) >> 4) | (512u << 16)) | (0x40000040ull << 32); }
__device__ __forceinline__ void wg_fence() { asm volatile("wgmma.fence.sync.aligned;" ::: "memory"); }
__device__ __forceinline__ void wg_commit() { asm volatile("wgmma.commit_group.sync.aligned;" ::: "memory"); }
template <int N> __device__ __forceinline__ void wg_wait() { asm volatile("wgmma.wait_group.sync.aligned %0;" ::"n"(N) : "memory"); }
template <int N> __device__ __forceinline__ void fence_acc(float* d) {
#pragma unroll
    for (int i = 0; i < N; i++) asm volatile("" : "+f"(d[i])::"memory");
}
#define R4(o) "+f"(d[o + 0]), "+f"(d[o + 1]), "+f"(d[o + 2]), "+f"(d[o + 3])
#define R8(o) R4(o), R4(o + 4)
__device__ __forceinline__ void wgmma_n128(float* d, desc_t da, desc_t db, int sc) {
    asm volatile("{.reg .pred p; setp.ne.b32 p, %66, 0;\n"
                 "wgmma.mma_async.sync.aligned.m64n128k16.f32.bf16.bf16 {%0,%1,%2,%3,%4,%5,%6,%7,%8,%9,%10,%11,%12,%13,%14,%15,%16,%17,%18,%19,%20,%21,%22,%23,%24,%25,%26,%27,%28,%29,%30,%31,"
                 "%32,%33,%34,%35,%36,%37,%38,%39,%40,%41,%42,%43,%44,%45,%46,%47,%48,%49,%50,%51,%52,%53,%54,%55,%56,%57,%58,%59,%60,%61,%62,%63}, %64, %65, p, 1, 1, 0, 1;}"
                 : R8(0), R8(8), R8(16), R8(24), R8(32), R8(40), R8(48), R8(56)
                 : "l"(da), "l"(db), "r"(sc));
}
__device__ __forceinline__ void wgmma_n112(float* d, desc_t da, desc_t db, int sc) {
    asm volatile("{.reg .pred p; setp.ne.b32 p, %58, 0;\n"
                 "wgmma.mma_async.sync.aligned.m64n112k16.f32.bf16.bf16 {%0,%1,%2,%3,%4,%5,%6,%7,%8,%9,%10,%11,%12,%13,%14,%15,%16,%17,%18,%19,%20,%21,%22,%23,%24,%25,%26,%27,%28,%29,%30,%31,%32,%33,%34,%35,%36,%37,%38,%39,%40,%41,%42,%43,%44,%45,%46,%47,%48,%49,%50,%51,%52,%53,%54,%55}, %56, %57, p, 1, 1, 0, 1;}"
                 : R8(0), R8(8), R8(16), R8(24), R8(32), R8(40), R8(48)
                 : "l"(da), "l"(db), "r"(sc));
}
__device__ __forceinline__ void wgmma_n128_tn(float* d, desc_t da, desc_t db, int sc) {
    asm volatile("{.reg .pred p; setp.ne.b32 p, %66, 0;\n"
                 "wgmma.mma_async.sync.aligned.m64n128k16.f32.bf16.bf16 {%0,%1,%2,%3,%4,%5,%6,%7,%8,%9,%10,%11,%12,%13,%14,%15,%16,%17,%18,%19,%20,%21,%22,%23,%24,%25,%26,%27,%28,%29,%30,%31,%32,%33,%34,%35,%36,%37,%38,%39,%40,%41,%42,%43,%44,%45,%46,%47,%48,%49,%50,%51,%52,%53,%54,%55,%56,%57,%58,%59,%60,%61,%62,%63}, %64, %65, p, 1, 1, 1, 0;}"
                 : R8(0), R8(8), R8(16), R8(24), R8(32), R8(40), R8(48), R8(56)
                 : "l"(da), "l"(db), "r"(sc));
}
__device__ __forceinline__ void wgmma_n64(float* d, desc_t da, desc_t db, int sc) {
    asm volatile("{.reg .pred p; setp.ne.b32 p, %34, 0;\n"
                 "wgmma.mma_async.sync.aligned.m64n64k16.f32.bf16.bf16 {%0,%1,%2,%3,%4,%5,%6,%7,%8,%9,%10,%11,%12,%13,%14,%15,%16,%17,%18,%19,%20,%21,%22,%23,%24,%25,%26,%27,%28,%29,%30,%31}, %32, %33, p, 1, 1, 0, 1;}"
                 : R8(0), R8(8), R8(16), R8(24)
                 : "l"(da), "l"(db), "r"(sc));
}
__device__ __forceinline__ void wgmma_n40_tt(float* d, desc_t da, desc_t db, int sc) {
    asm volatile("{.reg .pred p; setp.ne.b32 p, %22, 0;\n"
                 "wgmma.mma_async.sync.aligned.m64n40k16.f32.bf16.bf16 {%0,%1,%2,%3,%4,%5,%6,%7,%8,%9,%10,%11,%12,%13,%14,%15,%16,%17,%18,%19}, %20, %21, p, 1, 1, 1, 1;}"
                 : R8(0), R8(8), R4(16)
                 : "l"(da), "l"(db), "r"(sc));
}

__device__ __forceinline__ void wgmma_n8_tt(float* d, desc_t da, desc_t db, int sc) {
    asm volatile("{.reg .pred p; setp.ne.b32 p, %6, 0;\n"
                 "wgmma.mma_async.sync.aligned.m64n8k16.f32.bf16.bf16 {%0,%1,%2,%3}, %4, %5, p, 1, 1, 1, 1;}"
                 : R4(0)
                 : "l"(da), "l"(db), "r"(sc));
}

__device__ __forceinline__ uint32_t atom_f32x2(float* p, float a, float b) {
    float x, y;
    asm volatile("atom.relaxed.gpu.global.add.v2.f32 {%0,%1}, [%2], {%3,%4};" : "=f"(x), "=f"(y) : "l"(p), "f"(a), "f"(b) : "memory");
    return __float_as_uint(x);
}
__device__ __forceinline__ uint32_t atom_f32_if(float* p, float a, bool pred) {
    float x = 0.f;
    asm volatile("{.reg .pred p; setp.ne.u32 p, %3, 0; @p atom.relaxed.gpu.global.add.f32 %0, [%1], %2;}" : "+f"(x) : "l"(p), "f"(a), "r"((uint32_t)pred) : "memory");
    return __float_as_uint(x);
}
__device__ __forceinline__ void signal_after(unsigned* cnt, uint32_t ack, uint32_t zero, bool pred) {
    asm volatile("{.reg .pred p; setp.ne.u32 p, %2, 0; @p red.relaxed.gpu.global.add.u32 [%0], %1;}"
                 ::"l"(cnt), "r"((ack & zero) + 1), "r"((uint32_t)pred) : "memory");
}
__device__ __forceinline__ void signal_late(unsigned* cnt, const uint32_t* a, uint32_t zero, bool pred) {
    uint32_t v;
    asm volatile("{.reg .b32 t; lop3.b32 t, %1, %2, %3, 0xfe; or.b32 %0, t, %4;}"
                 : "=r"(v) : "r"(a[0]), "r"(a[1]), "r"(a[2]), "r"(a[3]));
    signal_after(cnt, v, zero, pred);
}
__device__ __forceinline__ void red_f32_if(float* p, float a, bool pred) {
    asm volatile("{.reg .pred p; setp.ne.u32 p, %2, 0; @p red.relaxed.gpu.global.add.f32 [%0], %1;}" ::"l"(p), "f"(a), "r"((uint32_t)pred) : "memory");
}
__device__ __forceinline__ void stg_f2_if(float* p, float a, float b, bool pred) {
    asm volatile("{.reg .pred p; setp.ne.u32 p, %3, 0; @p st.global.v2.f32 [%0], {%1,%2};}" ::"l"(p), "f"(a), "f"(b), "r"((uint32_t)pred) : "memory");
}
__device__ __forceinline__ void stg64(void* p, uint32_t a, uint32_t b) {
    asm volatile("st.global.v2.u32 [%0], {%1,%2};" ::"l"(p), "r"(a), "r"(b) : "memory");
}
__device__ __forceinline__ void mma16816_z(float* c, const uint32_t* a, uint32_t b0, uint32_t b1) {
    asm("mma.sync.aligned.m16n8k16.row.col.f32.bf16.bf16.f32 {%0,%1,%2,%3}, {%4,%5,%6,%7}, {%8,%9}, {%10,%10,%10,%10};"
                 : "=f"(c[0]), "=f"(c[1]), "=f"(c[2]), "=f"(c[3])
                 : "r"(a[0]), "r"(a[1]), "r"(a[2]), "r"(a[3]), "r"(b0), "r"(b1), "f"(0.f));
}
__device__ __forceinline__ uint32_t max2(uint32_t a, uint32_t b) { uint32_t r; asm("max.bf16x2 %0, %1, %2;" : "=r"(r) : "r"(a), "r"(b)); return r; }
__device__ __forceinline__ uint32_t min2(uint32_t a, uint32_t b) { uint32_t r; asm("min.bf16x2 %0, %1, %2;" : "=r"(r) : "r"(a), "r"(b)); return r; }
__device__ __forceinline__ void bar_arrive(int id, int n) { asm volatile("bar.arrive %0, %1;" ::"r"(id), "r"(n) : "memory"); }
__device__ __forceinline__ void mbar_arrive_n_if(uint32_t bar, uint32_t n, bool pred) {
    asm volatile("{.reg .pred p; setp.ne.u32 p, %1, 0; @p mbarrier.arrive.shared::cta.b64 _, [%0], %2;}" ::"r"(bar), "r"((uint32_t)pred), "r"(n) : "memory");
}
__device__ __forceinline__ float4 lds_f4(uint32_t a) {
    float4 v;
    asm volatile("ld.shared.v4.f32 {%0,%1,%2,%3}, [%4];" : "=f"(v.x), "=f"(v.y), "=f"(v.z), "=f"(v.w) : "r"(a) : "memory");
    return v;
}
__device__ __forceinline__ uint4 ld_tagged(const unsigned long long* p) {
    unsigned long long a, b;
    asm volatile("ld.acquire.gpu.global.v2.b64 {%0,%1}, [%2];" : "=l"(a), "=l"(b) : "l"(p) : "memory");
    return make_uint4((unsigned)a, (unsigned)(a >> 32), (unsigned)b, (unsigned)(b >> 32));
}
__device__ __forceinline__ uint4 ld_tagged_rlx(const unsigned long long* p) {
    unsigned long long a, b;
    asm volatile("ld.relaxed.gpu.global.v2.b64 {%0,%1}, [%2];" : "=l"(a), "=l"(b) : "l"(p) : "memory");
    return make_uint4((unsigned)a, (unsigned)(a >> 32), (unsigned)b, (unsigned)(b >> 32));
}
__device__ __forceinline__ void st_tagged_if(unsigned long long* p, float a, float b, unsigned tag, bool pred) {
    const unsigned long long t = (unsigned long long)tag << 32;
    asm volatile("{.reg .pred p; setp.ne.u32 p, %3, 0; @p st.relaxed.gpu.global.v2.b64 [%0], {%1,%2};}"
                 ::"l"(p), "l"(t | __float_as_uint(a)), "l"(t | __float_as_uint(b)), "r"((uint32_t)pred) : "memory");
}

__device__ __forceinline__ void store_tile(uint32_t tile_rows, __nv_bfloat16* gdst, const uint32_t* lo, const uint32_t* hi, int lane, uint32_t* ack) {
    const int r = lane & 15;
#pragma unroll
    for (int b = 0; b < 4; b++)
        stsm4(tile_rows + r * 128 + (((2 * b + (lane >> 4)) ^ (r & 7)) << 4), lo[2 * b], hi[2 * b], lo[2 * b + 1], hi[2 * b + 1]);
    fence_async_smem();
    __syncwarp();
#pragma unroll
    for (int i = 0; i < 4; i++) {
        const int rr = 4 * i + (lane >> 3);
        const uint4 v = lds128(tile_rows + rr * 128 + (((lane & 7) ^ (rr & 7)) << 4));
        stg128(gdst + rr * DM + (lane & 7) * 8, v.x, v.y, v.z, v.w);
    }
#pragma unroll
    for (int i = 0; i < 4; i++) ack[i] = readback(gdst + (4 * i + (lane >> 3)) * DM + (lane & 7) * 8);
}

__device__ __forceinline__ void feature_maps(const uint32_t* a, const uint32_t* wb, float c0, float c1, uint32_t* plus, uint32_t* minus) {
    uint32_t P[16], mx[4], mn[4];
#pragma unroll
    for (int h = 0; h < 4; h++) {
        float p[8];
        mma16816_z(p, a + 4 * h, wb[4 * h], wb[4 * h + 1]);
        mma16816_z(p + 4, a + 4 * h, wb[4 * h + 2], wb[4 * h + 3]);
        P[4 * h] = pack_bf16(p[0], p[2]); P[4 * h + 1] = pack_bf16(p[1], p[3]);
        P[4 * h + 2] = pack_bf16(p[4], p[6]); P[4 * h + 3] = pack_bf16(p[5], p[7]);
        mx[h] = max2(max2(P[4 * h], P[4 * h + 1]), max2(P[4 * h + 2], P[4 * h + 3]));
        mn[h] = min2(min2(P[4 * h], P[4 * h + 1]), min2(P[4 * h + 2], P[4 * h + 3]));
    }
#pragma unroll
    for (int s = 1; s <= 2; s <<= 1) {
        uint32_t tx[4], tn[4];
#pragma unroll
        for (int h = 0; h < 4; h++) { tx[h] = __shfl_xor_sync(0xffffffffu, mx[h], s); tn[h] = __shfl_xor_sync(0xffffffffu, mn[h], s); }
#pragma unroll
        for (int h = 0; h < 4; h++) { mx[h] = max2(mx[h], tx[h]); mn[h] = min2(mn[h], tn[h]); }
    }
#pragma unroll
    for (int h = 0; h < 4; h++) {
        const float mx0 = bf_lo(mx[h]) * c0, mx1 = bf_hi(mx[h]) * c1, mn0 = bf_lo(mn[h]) * c0, mn1 = bf_hi(mn[h]) * c1;
        float ep[8], em[8];
#pragma unroll
        for (int i = 0; i < 8; i++) {
            const bool r1 = (i & 2);
            const uint32_t w = P[4 * h + (i >> 2) * 2 + (i & 1)];
            const float p = r1 ? bf_hi(w) : bf_lo(w);
            ep[i] = ex2(fmaf(p, r1 ? c1 : c0, r1 ? -mx1 : -mx0));
            em[i] = ex2(fmaf(p, r1 ? -c1 : -c0, r1 ? mn1 : mn0));
        }
        float sp[4], sm[4];
        uint32_t tp[4], tm[4];
#pragma unroll
        for (int i = 0; i < 4; i++) { tp[i] = pack_bf16(ep[2 * i], ep[2 * i + 1]); tm[i] = pack_bf16(em[2 * i], em[2 * i + 1]); }
        mma16816_z(sp, tp, 0x3f803f80u, 0x3f803f80u);
        mma16816_z(sm, tm, 0x3f803f80u, 0x3f803f80u);
        const float r0 = rcp(sp[0] * sm[0]), r1 = rcp(sp[2] * sm[2]);
        const float rs[4] = {r0 * sm[0], r1 * sm[2], r0 * sp[0], r1 * sp[2]};
#pragma unroll
        for (int i = 0; i < 4; i++) {
            plus[4 * h + i] = pack_bf16(ep[2 * i] * rs[i & 1], ep[2 * i + 1] * rs[i & 1]);
            minus[4 * h + i] = pack_bf16(em[2 * i] * rs[2 + (i & 1)], em[2 * i + 1] * rs[2 + (i & 1)]);
        }
    }
}

template <bool SCALE>
__device__ __forceinline__ void ln_frag(const float* acc, uint32_t cs_addr, float rs0, float nm0, float rs1, float nm1, uint32_t* a) {
    const float2 c0 = lds_f2(cs_addr), c1 = lds_f2(cs_addr + 32);
    const float s0 = SCALE ? rs0 : 1.f, s1 = SCALE ? rs1 : 1.f;
    a[0] = pack_bf16(fmaf(nm0, c0.x, acc[0]) * s0, fmaf(nm0, c0.y, acc[1]) * s0);
    a[1] = pack_bf16(fmaf(nm1, c0.x, acc[2]) * s1, fmaf(nm1, c0.y, acc[3]) * s1);
    a[2] = pack_bf16(fmaf(nm0, c1.x, acc[4]) * s0, fmaf(nm0, c1.y, acc[5]) * s0);
    a[3] = pack_bf16(fmaf(nm1, c1.x, acc[6]) * s1, fmaf(nm1, c1.y, acc[7]) * s1);
}

template <int UP>
__device__ __forceinline__ uint32_t hh_pair(const float* ag, float4 cs, float nmean) {
    const float g0 = fmaf(nmean, cs.x, ag[0]), g1 = fmaf(nmean, cs.y, ag[1]);
    const float u0 = fmaf(nmean, cs.z, ag[UP]), u1 = fmaf(nmean, cs.w, ag[UP + 1]);
    return pack_bf16(g0 * u0, g1 * u1);
}
template <int NTP>
__device__ __forceinline__ void hh_stage(const float* acc, const float4* cs, float nm0, float nm1, uint32_t stg, int lane) {
#pragma unroll
    for (int tp = 0; tp < NTP; tp++)
        stsm4(stg + (lane & 15) * 128 + (((2 * tp + (lane >> 4)) ^ (lane & 7)) << 4), hh_pair<32>(acc + 8 * tp, cs[2 * tp], nm0),
              hh_pair<32>(acc + 8 * tp + 2, cs[2 * tp], nm1), hh_pair<32>(acc + 8 * tp + 4, cs[2 * tp + 1], nm0),
              hh_pair<32>(acc + 8 * tp + 6, cs[2 * tp + 1], nm1));
    fence_async_smem();
    __syncwarp();
}

struct Ring {
    int slot; uint32_t phase;
    __device__ __forceinline__ void adv() { if (++slot == NB) { slot = 0; phase ^= 1; } }
    __device__ __forceinline__ void adv5() { slot += slot == 3; adv(); }
};

__global__ void __cluster_dims__(2, 1, 1) __launch_bounds__(NTHREADS, 1) fused_kernel(const __grid_constant__ Params P) {
    extern __shared__ __align__(1024) uint8_t smem_raw[];
    const uint32_t sb = smem_u32(smem_raw);
    const int tid = threadIdx.x, lane = tid & 31;
    const int warp = __shfl_sync(0xffffffffu, tid >> 5, 0);
    const unsigned role = P.role[blockIdx.x], rank = blockIdx.x & 1;
    const int m = role >> 3, j = role & 7;
    const bool helper = role >= 128;

    TL(0, tid == 0); TLG(0, tid == 0);
    float* const acc_j = g_acc + j * ACC_SIZE;
    unsigned* const cnt_j = g_cnt + j * 32;

    if (__builtin_expect(warp >= 8, 1)) {
        asm volatile("setmaxnreg.dec.sync.aligned.u32 72;");
        if (elect_one()) {
            if (warp == 8) {
                if (!helper) {
#pragma unroll
                    for (int i = 0; i < NB; i++) mbar_init(sb + BAR_FULLB + 8 * i, 1);
#pragma unroll
                    for (int i = 0; i < 2; i++) {
                        mbar_expect_tx(sb + BAR_FULLB + 8 * i, SLOT);
                        tma2d(sb + OFF_B + i * SLOT, &P.twq, sb + BAR_FULLB + 8 * i, DM + 64 * j, 64 * i);
                        tma2d(sb + OFF_B + i * SLOT + 8192, &P.twq, sb + BAR_FULLB + 8 * i, 2 * DM + 64 * j, 64 * i);
                    }
                }
            } else if (warp == 9) {
#pragma unroll
                for (int i = 0; i < 8; i++) mbar_init(sb + BAR_FULLA + 8 * i, 1);
                if (!helper) {
#pragma unroll
                    for (int i = 0; i < 2; i++) {
                        mbar_expect_tx(sb + BAR_FULLA + 8 * i, SLOT);
                        tma2d(sb + OFF_A + i * SLOT, &P.tx, sb + BAR_FULLA + 8 * i, 64 * i, 128 * m);
                    }
                }
            } else if (warp == 10) {
#pragma unroll
                for (int i = 0; i < 9; i++) mbar_init(sb + BAR_CS1 + 8 * i, i == 0 || i == 8 ? 64 : (i == 1 ? 96 : (i < 4 ? 32 : 8)));
                trap_if_gt(sb & 1023, 0);
            } else {
#pragma unroll
                for (int i = 0; i < 14; i++) mbar_init(sb + (i < 8 ? BAR_EMPTYA : BAR_EMPTYB - 64) + 8 * i, i < 8 ? 8 : 16);
            }
            asm volatile("fence.mbarrier_init.release.cluster;" ::: "memory");
        }
        __syncwarp();
        asm volatile("barrier.cluster.arrive.relaxed.aligned;" ::: "memory");
        const unsigned epoch = ld_relaxed(&g_epoch);
        bar_sync(0, NTHREADS);
        if (helper) {
            if (warp == 8) {
                if (elect_one()) {
#pragma unroll 1
                    for (int i = 0; i < 72; i++) {
                        const uint32_t full = sb + BAR_FULLA + 8 * (i & 7), dst = sb + OFF_A + (i & 7) * SLOT;
                        mbar_wait(sb + BAR_EMPTYA + 8 * (i & 7), ((i >> 3) & 1) ^ 1);
                        mbar_expect_tx(full, SLOT);
                        const bool qkv = i < 24;
                        const int u = (i >> 3) - 3;
                        const int c0 = qkv ? (i < 16 ? DM + 64 * (i & 8) : 0) + 128 * j + 16 * (i & 4) : 176 * (2 * j + (u & 1)) + 64 * (u >> 1);
                        const int r0 = qkv ? 128 * (i & 3) : 64 * (i & 7);
                        tma2d(dst, qkv ? &P.twq : &P.twg, full, c0, r0);
                        tma2d(dst + 8192, qkv ? &P.twq : &P.twu, full, c0, qkv ? r0 + 64 : r0);
                    }
                    prefetch_l2(P.wd + (size_t)j * 176128, 352256);
                }
            }
            return;
        }
        if (warp == 8) {
            asm volatile("barrier.cluster.wait.aligned;" ::: "memory");
            if (elect_one()) {
                if (m >= 6)
                    asm volatile("cp.async.bulk.prefetch.tensor.2d.L2.global [%0, {%1, %2}];" ::"l"(&P.twq), "r"(DM + DM * (m & 1) + 64 * j), "r"(64 * (m >> 1)) : "memory");
                if (j >= 3)
                    asm volatile("cp.async.bulk.prefetch.tensor.2d.L2.global [%0, {%1, %2}];" ::"l"(&P.tx), "r"(64 * j), "r"(128 * m) : "memory");
                Ring r{2, 0};
                const uint32_t dst = sb + OFF_B + rank * 8192;
#define B_LOAD(TM, C0, R0)                                                                                  \
        mbar_waitc(sb + BAR_EMPTYB + 8 * r.slot, r.phase ^ 1);                                              \
        mbar_expect_tx(sb + BAR_FULLB + 8 * r.slot, SLOT);                                                  \
        tma2d_mc(dst + r.slot * SLOT, TM, sb + BAR_FULLB + 8 * r.slot, C0, R0);
#pragma unroll 1
                for (int i = 2; i < 8; i++) {
                    if (i >= AHEAD && i < 6) mbar_waitc(sb + BAR_FULLB + 8 * (i - AHEAD), 0);
                    B_LOAD(&P.twq, DM + DM * rank + 64 * j, 64 * i)
                    r.adv();
                }
#pragma unroll 1
                for (int i = 8; i < 20; i++) {
                    if (i >= 10 && i < 14) {
                        mbar_waitc(sb + BAR_EMPTYB + 8 * r.slot, r.phase ^ 1);
                        mbar_arrive(sb + BAR_FULLB + 8 * r.slot);
                    } else {
                        const int e = 2 * (i & 3) + rank;
                        B_LOAD(i < 16 ? &P.twq : &P.two, 64 * j, 64 * (i < 16 ? e : KORD(e, j)))
                    }
                    r.adv();
                }
#pragma unroll 1
                for (int i = 0; i < 24; i++) {
                    B_LOAD(&P.twg + rank, 176 * j + 8 * (i & ~7), 64 * (i < 8 ? KORD(i, j) : i & 7))
                    r.adv5();
                }
#pragma unroll 1
                for (int i = 0; i < 12; i++) {
                    B_LOAD(&P.twd, 64 * j, 176 * (2 * (i & 3) + rank) + 64 * (i >> 2))
                    r.adv5();
                }
            }
            return;
        }
        if (warp == 9) {
            if (elect_one()) {
#pragma unroll 1
                for (int i = 2; i < 8; i++) {
                    if (i >= AHEAD + 1) mbar_wait(sb + BAR_FULLA + 8 * (i - AHEAD - 1), 0);
                    mbar_expect_tx(sb + BAR_FULLA + 8 * i, SLOT);
                    tma2d(sb + OFF_A + i * SLOT, &P.tx, sb + BAR_FULLA + 8 * i, 64 * i, 128 * m);
                }
#pragma unroll 1
                for (int i = 1; i < 10; i++) prefetch_tmap(&P.tx + i);
#pragma unroll 1
                for (int r = 1; r < 6; r++) {
                    const CUtensorMap* tm = &P.tx + min(r, 3);
                    const int cstep = r < 3 ? 64 : 192, cbase = r < 3 ? 0 : 64 * (r - 3), skip = r < 3 ? j : 8;
                    if (r < 4) mbar_wait(sb + BAR_EMPTYA + 8 * (skip == 0), (r - 1) & 1);
                    wait_count(g_flag + (m * 5 + r - 1) * 32, epoch * (r < 3 ? 64 : 8));
                    TL(64 + r, true);
#pragma unroll 1
                    for (int t = 0; t < 8; t++) {
                        if (t == skip) continue;
                        mbar_wait(sb + BAR_EMPTYA + 8 * t, (r - 1) & 1);
                        mbar_expect_tx(sb + BAR_FULLA + 8 * t, SLOT);
                        tma2d(sb + OFF_A + t * SLOT, tm, sb + BAR_FULLA + 8 * t, cbase + cstep * t, 128 * m);
                    }
                }
            }
            return;
        }
        const int a = warp - 10;
        {
            const int row = 16 * j + 8 * a + (lane >> 2);
            const uint32_t ra = sb + OFF_A + row * 128;
            float sh = 0.f, s0 = 0.f, s1 = 0.f, q0 = 0.f, q1 = 0.f;
#pragma unroll 1
            for (int kt = 0; kt < 8; kt++) {
                mbar_wait(sb + BAR_FULLA + 8 * kt, 0);
                if (kt == 0) sh = bf_lo(lds128(ra + ((row & 7) << 4)).x);
#pragma unroll
                for (int i = 0; i < 2; i++) {
                    const uint4 v = lds128(ra + kt * SLOT + (((2 * (lane & 3) + i) ^ (row & 7)) << 4));
                    const uint32_t ww[4] = {v.x, v.y, v.z, v.w};
#pragma unroll
                    for (int e = 0; e < 4; e++) {
                        const float d0 = bf_lo(ww[e]) - sh, d1 = bf_hi(ww[e]) - sh;
                        s0 += d0; q0 = fmaf(d0, d0, q0);
                        s1 += d1; q1 = fmaf(d1, d1, q1);
                    }
                }
            }
            s0 += s1; q0 += q1;
#pragma unroll
            for (int o = 1; o <= 2; o <<= 1) { s0 += __shfl_xor_sync(0xffffffffu, s0, o); q0 += __shfl_xor_sync(0xffffffffu, q0, o); }
            const float md = s0 * (1.f / DM);
            const float rs = rsqrtf(fmaxf(q0 * (1.f / DM) - md * md, 0.f) + 1e-5f);
            st_tagged_if(g_xstat + 2 * (128 * m + row), rs, -(sh + md), epoch, (lane & 3) == 0);
        }
        const unsigned long long* cs = g_cs + j * 768 + 2 * lane;
#pragma unroll 1
        for (int c = 0; c < (a ? 5 : 10); c++) {
            if (c == 4) {
                const int t = 32 * a + lane;
                const uint32_t kvs = sb + OFF_A + KVS(j) * SLOT;
                mbar_wait(sb + BAR_KVW, 0);
#pragma unroll 1
                for (int pass = 0; pass < 2; pass++) {
                    float4 v[8];
#pragma unroll
                    for (int i = 0; i < 8; i++) v[i] = ld_l2_f4(acc_j + ACC_KV + 4 * (t + 64 * i));
                    const float2 zz = ld_l2_f2(acc_j + ACC_Z + 2 * t);
#pragma unroll
                    for (int i = 0; i < 8; i++)
                        sts64(kvs + ((t >> 2) + 16 * i) * 48 + (t & 3) * 8, pack_bf16(v[i].x, v[i].y), pack_bf16(v[i].z, v[i].w));
                    const uint32_t z0 = pack_bf16(zz.x, zz.x), z1 = pack_bf16(zz.y, zz.y);
                    sts128(kvs + t * 96 + 32, z0, z0, z0, z0);
                    sts128(kvs + t * 96 + 80, z1, z1, z1, z1);
                    if (pass == 0) {
                        __syncwarp();
                        if (lane == 0) red_relaxed(cnt_j, 1);
                        TL(19, t == 0);
                        wait_count_warp(cnt_j, epoch * 32);
                        TL(14, t == 0);
                    }
                }
                mbar_arrive(sb + BAR_KVR);
                if (a) break;
            }
            if (c == 3 && !a) continue;
            const unsigned long long* src = c < 2 ? g_xstat + 2 * (128 * m + 64 * a + 32 * c + lane) : cs + (c < 4 ? 128 * (a + c - 2) : 128 + 64 * c);
            const uint32_t dst = c < 2 ? OFF_XST + (64 * a + 32 * c + lane) * 8
                                       : (c < 4 ? OFF_CS1 + (c == 2 ? 256 * (a + 1) : 0) + 8 * lane : OFF_CS3 + (32 * ((c - 4) >> 1) + lane) * 16 + 8 * (c & 1));
            uint4 v;
            uint32_t it = 0;
            while (true) {
                v = ld_tagged_rlx(src);
                if (!__any_sync(0xffffffffu, v.y != epoch || v.w != epoch)) break;
                __nanosleep(60);
                trap_if_gt(++it, 1u << 22);
            }
            sts64(sb + dst, v.x, v.z);
            if (c == 2 - a || (a && c > 1) || c == 9) mbar_arrive(sb + (c == 9 ? BAR_CS3 : (c == 2 - a ? BAR_CS1 : (c == 2 ? BAR_CSV : BAR_CSQ))));
        }
        {
            uint32_t it = 0;
            while (__any_sync(0xffffffffu, (int)(readback(g_flag + (m * 5 + 1) * 32) - epoch * 64) < 0)) {
                __nanosleep(200);
                trap_if_gt(++it, 1u << 22);
            }
#pragma unroll 1
            for (int rr = 0; rr < 2; rr++) {
                const int row = 64 * rr + 32 * a + lane;
                uint4 v[8];
                bool bad;
                do {
                    bad = false;
#pragma unroll
                    for (int i = 0; i < 8; i++) v[i] = ld_tagged_rlx(g_hstat + (1024 * m + 128 * i + row) * 2);
#pragma unroll
                    for (int i = 0; i < 8; i++) bad |= v[i].y != epoch || v[i].w != epoch;
                    trap_if_gt(++it, 1u << 22);
                } while (__any_sync(0xffffffffu, bad));
                float mean = 0.f;
#pragma unroll
                for (int i = 0; i < 8; i++) mean += __uint_as_float(v[i].x);
                mean *= 0.125f;
                float m2 = 0.f, dv = 0.f;
#pragma unroll
                for (int i = 0; i < 8; i++) { const float d = __uint_as_float(v[i].x) - mean; m2 += __uint_as_float(v[i].z); dv = fmaf(d, d, dv); }
                sts_f2(sb + OFF_CS1 + row * 8, -mean, rcp(fmaf(dv, 64.f, m2) * (1.f / DM) + 1e-5f));
            }
        }
        mbar_arrive(sb + BAR_CS3);
#pragma unroll 1
        for (int c = a; c < 3; c += 2) {
            mbar_wait(sb + BAR_STG + 8 * c, 0);
            if (elect_one()) {
                tma_store2d(&P.thh, sb + OFF_B + 4 * SLOT, 192 * j + 64 * c, 128 * m);
                asm volatile("cp.async.bulk.wait_group.read 0;" ::: "memory");
                mbar_arrive(sb + BAR_FULLB + 8 * 4);
                asm volatile("cp.async.bulk.wait_group 0;" ::: "memory");
            }
            __syncwarp();
            TL(60 + c, lane == 0);
            uint32_t ack = 0;
#pragma unroll
            for (int i = 0; i < 4; i++) ack |= readback(g_hh + (size_t)(128 * m + 32 * i + lane) * FFP + 192 * j + 64 * c);
            signal_after(g_flag + (m * 5 + 2 + c) * 32, ack, P.zero, lane == 0);
            TL(54 + c, lane == 0);
        }
        return;
    }
    const unsigned epoch = ld_relaxed(&g_epoch);
    uint32_t wraw[16];
    if (!helper) {
        const uint32_t* wp = reinterpret_cast<const uint32_t*>(P.wphi) + (4 * j) * 128 + (lane & 3) * 16 + (lane >> 2);
#pragma unroll
        for (int i = 0; i < 16; i++)
            asm volatile("ld.global.nc.u32 %0, [%1];" : "=r"(wraw[i]) : "l"(wp + (i >> 2) * 128 + ((i >> 1) & 1) * 64 + (i & 1) * 8));
    }
    asm volatile("barrier.cluster.arrive.relaxed.aligned;" ::: "memory");
    asm volatile("setmaxnreg.inc.sync.aligned.u32 216;");
    bar_sync(0, NTHREADS);
    if (helper) {
        if (warp < 4) {
            sts128(sb + OFF_B + 16 * tid, 0x3f803f80u, 0x3f803f80u, 0x3f803f80u, 0x3f803f80u);
            for (int i = tid; i < 2 * ACC_SIZE / 4; i += 128) stg128(g_acc + 2 * j * ACC_SIZE + 4 * i, 0, 0, 0, 0);
            fence_async_smem();
            fence_gpu();
            bar_sync(1, 128);
            float acc[8];
            int i = 0;
#pragma unroll 1
            for (int job = 0; job < 12; job++) {
                const int n = job < 6 ? 4 : 8;
#pragma unroll 1
                for (int t = 0; t < n; t++, i++) {
                    mbar_wait(sb + BAR_FULLA + 8 * (i & 7), (i >> 3) & 1);
                    wg_fence();
#pragma unroll
                    for (int k = 0; k < 8; k++)
                        wgmma_n8_tt(acc + (k & 4), desc_lo(sb + OFF_A) + (i & 7) * (SLOT >> 4) + 128 * k, desc_lo(sb + OFF_B), (t | (k & 3)) != 0);
                    wg_commit();
                    wg_wait<1>();
                    mbar_arrive_n_if(sb + BAR_EMPTYA + 8 * ((i + 7) & 7), 2, lane == 0 && i > 0);
                }
                wg_wait<0>();
                fence_acc<8>(acc);
                const int q = lane & 3;
                const float lo = (q & 1) ? acc[2] : acc[0], hi = (q & 1) ? acc[6] : acc[4];
                const float v = job < 6 ? lo + hi : ((q & 2) ? hi : lo);
                unsigned long long* dst = g_cs + ((2 * j + (job & 1)) * 6 + (job >> 1)) * 128 + (q >> 1) * 64 + 16 * warp + 8 * (q & 1) + (lane >> 2);
                asm volatile("st.relaxed.gpu.global.b64 [%0], %1;" ::"l"(dst), "l"(((unsigned long long)epoch << 32) | __float_as_uint(v)) : "memory");
            }
        }
        return;
    }
    {
        const int w = warp >> 2, wv = warp & 3, g = lane >> 2, q = lane & 3;
        const int row_w = 128 * m + 16 * warp;
        const uint32_t sa = sb + OFF_A + w * 8192;
        const desc_t dA = desc_lo(sa), dB = desc_lo(sb + OFF_B);
        unsigned* const flag_m = g_flag + m * 160;
        const bool l0 = lane == 0, l2 = lane < 2;
        const uint32_t eb = mapa(sb + BAR_EMPTYB, lane & 1);
        asm volatile("barrier.cluster.wait.aligned;" ::: "memory");
        Ring rg{0, 0};
        int prev = 0;

        uint32_t wb[16];
        constexpr float L2E = 1.4426950408889634f;
        const int ch = lane >> 4, sw = lane & 7;
        const uint32_t lrow = (lane & 15) * 128;
        uint32_t fp[16], fm[16];
        {
            float acc[64], accq[32];
#pragma unroll 1
            for (int kt = 0; kt < 8; kt++) {
                mbar_waitc(sb + BAR_FULLA + 8 * kt, 0);
                mbar_waitc(sb + BAR_FULLB + 8 * rg.slot, rg.phase);
                const desc_t da = dA + kt * (SLOT >> 4), db = dB + rg.slot * (SLOT >> 4);
                wg_fence();
#pragma unroll
                for (int k = 0; k < 4; k++) wgmma_n128(acc, da + 2 * k, db + 128 * k, (kt | k) != 0);
                wg_commit();
                wg_wait<1>();
                mbar_arrive_cl_if(eb + 8 * prev, l2 && kt > 0);
                prev = rg.slot; rg.adv();
            }
#pragma unroll
            for (int i = 0; i < 8; i++) {
                wb[(i >> 1) * 4 + (i & 1)] = __byte_perm(wraw[2 * i], wraw[2 * i + 1], 0x5410);
                wb[(i >> 1) * 4 + 2 + (i & 1)] = __byte_perm(wraw[2 * i], wraw[2 * i + 1], 0x7632);
            }
            float2 s0, s1;
            uint32_t a[16];
            wg_wait<0>();
            fence_acc<64>(acc);
            mbar_arrive_cl_if(eb + 8 * prev, l2);
#pragma unroll 1
            for (int it = 0; it < 2; it++) {
                mbar_waitc(sb + BAR_FULLB + 8 * 2, it ^ 1); mbar_waitc(sb + BAR_FULLB + 8 * 3, it ^ 1);
                const desc_t da = dA + it * (4 * SLOT >> 4);
                wg_fence();
#pragma unroll
                for (int k = 0; k < 16; k++) wgmma_n64(accq, da + (k >> 2) * (SLOT >> 4) + (k & 3) * 2, dB + 2 * (SLOT >> 4) + 128 * k, (it | k) != 0);
                wg_commit();
                TL(17 + it, tid == 0);
                mbar_waitc(sb + BAR_CS1 + 16 * it, 0);
                wg_wait<0>();
                fence_acc<32>(accq);
                mbar_arrive_cl_if(eb + 8 * (2 + (lane >> 1)), lane < 4);
                TL(2 + 2 * it, tid == 0);
                if (it == 0) {
                    s0 = lds_f2(sb + OFF_XST + (16 * warp + g) * 8); s1 = lds_f2(sb + OFF_XST + (16 * warp + g + 8) * 8);
#pragma unroll
                    for (int hh = 0; hh < 4; hh++)
                        ln_frag<false>(acc + 8 * hh, sb + OFF_CS1 + (64 + 16 * hh + 2 * q) * 4, 0.f, s0.y, 0.f, s1.y, a + 4 * hh);
                } else {
#pragma unroll
                    for (int hh = 0; hh < 4; hh++)
                        ln_frag<false>(accq + 8 * hh, sb + OFF_CS1 + (16 * hh + 2 * q) * 4, 0.f, s0.y, 0.f, s1.y, a + 4 * hh);
                }
                feature_maps(a, wb, s0.x * L2E, s1.x * L2E, fp, fm);
                if (it == 0) {
                    mbar_waitc(sb + BAR_FULLB + 8 * 4, 1); mbar_waitc(sb + BAR_FULLB + 8 * 5, 1);
                    mbar_waitc(sb + BAR_FULLB + 8 * 0, 0); mbar_waitc(sb + BAR_FULLB + 8 * 1, 0);
                    mbar_waitc(sb + BAR_CSV, 0);
                    const uint32_t st = sb + OFF_B + warp * 2048 + lrow;
#pragma unroll
                    for (int hh = 0; hh < 4; hh++) {
                        stsm4(st + (4 + (hh >> 1)) * SLOT + (((4 * (hh & 1) + ch) ^ sw) << 4), fp[4 * hh], fp[4 * hh + 1], fp[4 * hh + 2], fp[4 * hh + 3]);
                        stsm4(st + (4 + (hh >> 1)) * SLOT + (((4 * (hh & 1) + 2 + ch) ^ sw) << 4), fm[4 * hh], fm[4 * hh + 1], fm[4 * hh + 2], fm[4 * hh + 3]);
                        ln_frag<true>(acc + 32 + 8 * hh, sb + OFF_CS1 + (128 + 16 * hh + 2 * q) * 4, s0.x, s0.y, s1.x, s1.y, a);
                        stsm4(st + (hh >> 1) * SLOT + (((2 * (hh & 1) + ch) ^ sw) << 4), a[0], a[1], a[2], a[3]);
                    }
                    stsm4(st + ch * SLOT + ((4 ^ sw) << 4), 0x3f803f80u, 0x3f803f80u, 0x3f803f80u, 0x3f803f80u);
                    fence_async_smem();
                    bar_sync(1, 256);
                    float kvd[20];
                    wg_fence();
#pragma unroll
                    for (int k = 0; k < 8; k++)
                        wgmma_n40_tt(kvd, dB + (4 + w) * (SLOT >> 4) + 128 * k, dB + w * (SLOT >> 4) + 128 * k, k != 0);
                    wg_commit();
                    wg_wait<0>();
                    fence_acc<20>(kvd);
                    const bool h1 = wv >= 2;
                    const int f = 16 * warp + g;
                    float* kvp = acc_j + ACC_KV + f * 16 + 2 * q;
                    red_f32x2(kvp, h1 ? kvd[8] : kvd[0], h1 ? kvd[9] : kvd[1]);
                    red_f32x2(kvp + 128, h1 ? kvd[10] : kvd[2], h1 ? kvd[11] : kvd[3]);
                    red_f32x2(kvp + 8, h1 ? kvd[12] : kvd[4], h1 ? kvd[13] : kvd[5]);
                    red_f32x2(kvp + 136, h1 ? kvd[14] : kvd[6], h1 ? kvd[15] : kvd[7]);
                    red_f32_if(acc_j + ACC_Z + f + 8 * (q & 1), q ? kvd[18] : kvd[16], q < 2);
                    __syncwarp();
                    mbar_arrive_if(sb + BAR_KVW, l0);
                    mbar_arrive_cl_if(eb + 8 * ((4 + (lane >> 1)) % 6), lane < 8);
                    TL(3, tid == 0);
                }
            }
        }
        uint32_t res_lo[8], res_hi[8], ack[4];
        const uint32_t own_rows = sb + OFF_A + j * SLOT + warp * 2048;
#pragma unroll
        for (int b = 0; b < 4; b++)
            ldsm4(own_rows + lrow + (((2 * b + ch) ^ sw) << 4), res_lo[2 * b], res_hi[2 * b], res_lo[2 * b + 1], res_hi[2 * b + 1]);
        mbar_arrive_if(sb + BAR_EMPTYA + 8 * lane, lane < 8 && lane != j && lane != KVS(j));
        TL(5, tid == 0);
        mbar_waitc(sb + BAR_KVR, 0);
        TL(6, tid == 0);
        {
            const uint32_t kvs = sb + OFF_A + KVS(j) * SLOT;
            uint32_t o_lo[8], o_hi[8];
#pragma unroll
            for (int hh = 0; hh < 4; hh++) {
                uint32_t b[8], zb[4];
                const uint32_t base = kvs + hh * 32 * 48;
                ldsm4t(base + (lane & 15) * 48 + (lane >> 4) * 16, b[0], b[1], b[2], b[3]);
                ldsm4t(base + (16 + (lane & 15)) * 48 + (lane >> 4) * 16, b[4], b[5], b[6], b[7]);
                ldsm4t(base + lane * 48 + 32, zb[0], zb[1], zb[2], zb[3]);
                float n0[4], n1[4], dn[4];
                mma16816_z(n0, fp + 4 * hh, b[0], b[1]); mma16816_z(n1, fp + 4 * hh, b[2], b[3]); mma16816_z(dn, fp + 4 * hh, zb[0], zb[1]);
                mma16816(n0, fm + 4 * hh, b[4], b[5]); mma16816(n1, fm + 4 * hh, b[6], b[7]); mma16816(dn, fm + 4 * hh, zb[2], zb[3]);
                const float i0 = rcp(dn[0] + 1e-6f), i1 = rcp(dn[2] + 1e-6f);
                o_lo[2 * hh] = pack_bf16(n0[0] * i0, n0[1] * i0); o_hi[2 * hh] = pack_bf16(n0[2] * i1, n0[3] * i1);
                o_lo[2 * hh + 1] = pack_bf16(n1[0] * i0, n1[1] * i0); o_hi[2 * hh + 1] = pack_bf16(n1[2] * i1, n1[3] * i1);
            }
            __syncwarp();
            mbar_arrive_if(sb + BAR_EMPTYA + 8 * KVS(j), l0);
            rg.slot = 4; rg.phase = 0;
            store_tile(own_rows, g_o + (size_t)row_w * DM + 64 * j, o_lo, o_hi, lane, ack);
            TL(7, tid == 0);
        }
        {
            float acc[32];
#pragma unroll
            for (int t = 0; t < 8; t++) {
                acc[4 * t] = bf_lo(res_lo[t]); acc[4 * t + 1] = bf_hi(res_lo[t]);
                acc[4 * t + 2] = bf_lo(res_hi[t]); acc[4 * t + 3] = bf_hi(res_hi[t]);
            }
            fence_acc<32>(acc);
            int pa = 0;
#pragma unroll 1
            for (int kp = 0; kp < 4; kp++) {
                mbar_waitc(sb + BAR_FULLB + 8 * rg.slot, rg.phase);
#pragma unroll
                for (int hf = 0; hf < 2; hf++) {
                    const int i = 2 * kp + hf, kt = KORD(i, j);
                    mbar_waitc(sb + BAR_FULLA + 8 * kt, i != 0);
                    TL(8, i == 1 && tid == 0);
                    const desc_t da = dA + kt * (SLOT >> 4), db = dB + rg.slot * (SLOT >> 4);
                    wg_fence();
#pragma unroll
                    for (int k = 0; k < 4; k++) wgmma_n64(acc, da + 2 * k, db + (hf * 4 + k) * 128, 1);
                    wg_commit();
                    wg_wait<1>();
                    mbar_arrive_if(sb + BAR_EMPTYA + 8 * pa, l0 && i > 1);
                    if (hf == 0) {
                        mbar_arrive_cl_if(eb + 8 * prev, l2 && i > 0);
                        if (i == 0) { signal_late(flag_m, ack, P.zero, l0); TL(20, tid == 0); }
                    }
                    pa = kt;
                }
                prev = rg.slot; rg.adv();
            }
            wg_wait<0>();
            fence_acc<32>(acc);
            mbar_arrive_if(sb + BAR_EMPTYA + 8 * pa, l0);
            mbar_arrive_cl_if(eb + 8 * prev, l2);
            TL(9, tid == 0);
            float s0 = 0.f, s1 = 0.f;
#pragma unroll
            for (int t = 0; t < 8; t++) {
                res_lo[t] = pack_bf16(acc[4 * t], acc[4 * t + 1]);
                res_hi[t] = pack_bf16(acc[4 * t + 2], acc[4 * t + 3]);
                s0 += acc[4 * t] + acc[4 * t + 1];
                s1 += acc[4 * t + 2] + acc[4 * t + 3];
            }
            store_tile(own_rows, g_h + (size_t)row_w * DM + 64 * j, res_lo, res_hi, lane, ack);
            s0 += __shfl_xor_sync(0xffffffffu, s0, 1); s1 += __shfl_xor_sync(0xffffffffu, s1, 1);
            s0 += __shfl_xor_sync(0xffffffffu, s0, 2); s1 += __shfl_xor_sync(0xffffffffu, s1, 2);
            const float mu0 = s0 * (1.f / 64), mu1 = s1 * (1.f / 64);
            float q0 = 0.f, q1 = 0.f;
#pragma unroll
            for (int t = 0; t < 8; t++) {
                float d;
                d = acc[4 * t] - mu0; q0 = fmaf(d, d, q0);
                d = acc[4 * t + 1] - mu0; q0 = fmaf(d, d, q0);
                d = acc[4 * t + 2] - mu1; q1 = fmaf(d, d, q1);
                d = acc[4 * t + 3] - mu1; q1 = fmaf(d, d, q1);
            }
            q0 += __shfl_xor_sync(0xffffffffu, q0, 1); q1 += __shfl_xor_sync(0xffffffffu, q1, 1);
            q0 += __shfl_xor_sync(0xffffffffu, q0, 2); q1 += __shfl_xor_sync(0xffffffffu, q1, 2);
            st_tagged_if(g_hstat + (role * 128 + 16 * warp + g + 8 * (q & 1)) * 2, q ? mu1 : mu0, q ? q1 : q0, epoch, q < 2);
            TL(10, tid == 0);
        }
        float acc0[64], acc1[64], acc2[56], nm0, nm1;
        float4 cs[8];
        uint32_t hr[16];
#define P3_GROUP(MMA, ACC, KT)                                                                              \
        mbar_waitc(sb + BAR_FULLB + 8 * rg.slot, rg.phase);                                                 \
        {                                                                                                   \
            const desc_t da = dA + (KT) * (SLOT >> 4), db = dB + rg.slot * (SLOT >> 4);                     \
            wg_fence();                                                                                     \
            _Pragma("unroll") for (int k = 0; k < 4; k++) MMA(ACC, da + 2 * k, db + 128 * k, (i | k) != 0); \
            wg_commit();                                                                                    \
        }
#define P3_PRE(C, NT)                                           \
        if (C) mbar_waitc(sb + BAR_FULLB + 8 * 4, (C) & 1);                                                 \
        _Pragma("unroll") for (int t = 0; t < (NT); t++) cs[t] = lds_f4(sb + OFF_CS3 + q * 16 + 512 * (C) + 64 * t);
#define P3_EPI(C, ACC, N, NTP)                                                                              \
        fence_acc<N>(ACC);                                                                                  \
        TL(11 + (C), tid == 0);                                                                             \
        hh_stage<NTP>(ACC, cs, nm0, nm1, sb + OFF_B + 4 * SLOT + warp * 2048, lane);                 \
        mbar_arrive_if(sb + BAR_STG + 8 * (C), l0);                                                         \
        TL(50 + (C), tid == 0);
#pragma unroll 1
        for (int i = 0; i < 8; i++) {
            const int kt = KORD(i, j);
            mbar_waitc(sb + BAR_FULLA + 8 * kt, 0);
            TL(44, tid == 0 && i == 1);
            P3_GROUP(wgmma_n128, acc0, kt)
            wg_wait<1>();
            mbar_arrive_cl_if(eb + 8 * prev, l2 && i > 0);
            if (i == 0) { signal_late(flag_m + 32, ack, P.zero, l0); TL(21, tid == 0); }
            prev = rg.slot; rg.adv5();
        }
        mbar_waitc(sb + BAR_CS3, 0);
        nm0 = lds_f2(sb + OFF_CS1 + (16 * warp + g) * 8).x; nm1 = lds_f2(sb + OFF_CS1 + (16 * warp + g + 8) * 8).x;
        P3_PRE(0, 8)
#pragma unroll 1
        for (int i = 0; i < 8; i++) {
            P3_GROUP(wgmma_n128, acc1, i)
            wg_wait<1>();
            mbar_arrive_cl_if(eb + 8 * prev, l2);
            if (i == 0) { P3_EPI(0, acc0, 64, 4) }
            prev = rg.slot; rg.adv5();
        }
        const uint32_t blk = ((lane & 7) + (lane >> 4) * 8) * 128 + (((2 * wv + ((lane >> 3) & 1)) ^ (lane & 7)) << 4);
#pragma unroll
        for (int tp = 0; tp < 4; tp++) ldsm4t(sa + j * SLOT + blk + tp * 2048, hr[4 * tp], hr[4 * tp + 1], hr[4 * tp + 2], hr[4 * tp + 3]);
        P3_PRE(1, 8)
#pragma unroll 1
        for (int i = 0; i < 8; i++) {
            P3_GROUP(wgmma_n112, acc2, i)
            wg_wait<1>();
            mbar_arrive_cl_if(eb + 8 * prev, l2);
            mbar_arrive_if(sb + BAR_EMPTYA + 8 * ((i + 7) & 7), l0 && i > 0);
            if (i == 0) { P3_EPI(1, acc1, 64, 4) }
            prev = rg.slot; rg.adv5();
        }
        P3_PRE(2, 6)
        {
            float acc[64];
            const desc_t dA0 = desc_lo(sb + OFF_A);
#define KT_P4(I, NK)                                                                                        \
        const int s_ = (2 * (I) + w) & 7;                                                                   \
        mbar_waitc(sb + BAR_FULLB + 8 * rg.slot, rg.phase);                                                 \
        mbar_waitc(sb + BAR_FULLA + 8 * s_, (((I) >> 2) + 1) & 1);                                          \
        TL(30 + (I), tid == 0);                                                                             \
        const desc_t dh_ = dA0 + s_ * (SLOT >> 4), dw_ = dB + rg.slot * (SLOT >> 4) + w * 512;              \
        wg_fence();                                                                                         \
        _Pragma("unroll") for (int k = 0; k < (NK); k++) wgmma_n128_tn(acc, dw_ + 128 * k, dh_ + 2 * k, ((I) | k) != 0); \
        wg_commit();                                                                                        \
        wg_wait<1>();
#pragma unroll 1
            for (int i = 0; i < 8; i++) {
                KT_P4(i, 4)
                mbar_arrive_n_if(sb + BAR_EMPTYA + 8 * (i ? (s_ + 6) & 7 : 7), i ? 2 : 1, l0);
                mbar_arrive_cl_if(eb + 8 * prev, l2);
                if (i == 0) { P3_EPI(2, acc2, 56, 3) }
                prev = rg.slot; rg.adv5();
            }
#pragma unroll 1
            for (int i = 8; i < 12; i++) {
                KT_P4(i, 3)
                mbar_arrive_n_if(sb + BAR_EMPTYA + 8 * ((s_ + 6) & 7), 2, l0);
                rg.adv5();
            }
            float r2[16];
#pragma unroll
            for (int t = 0; t < 8; t++) {
                const float4 st = lds_f4(sb + OFF_CS1 + (64 * w + 8 * t + 2 * q) * 8);
                r2[2 * t] = st.y; r2[2 * t + 1] = st.w;
            }
            wg_wait<0>();
            fence_acc<64>(acc);
            TL(15, tid == 0);
            const uint32_t xch = sb + OFF_A + 2 * SLOT + (tid & 127) * 16;
            if (w) {
#pragma unroll
                for (int t = 0; t < 8; t++) {
                    sts128(xch + SLOT + t * 2048, __float_as_uint(acc[4 * t]), __float_as_uint(acc[4 * t + 1]),
                           __float_as_uint(acc[4 * t + 2]), __float_as_uint(acc[4 * t + 3]));
                }
#pragma unroll
                for (int t = 0; t < 32; t++) acc[t] = acc[32 + t];
            } else {
#pragma unroll
                for (int t = 0; t < 8; t++)
                    sts128(xch + t * 2048, __float_as_uint(acc[32 + 4 * t]), __float_as_uint(acc[33 + 4 * t]),
                           __float_as_uint(acc[34 + 4 * t]), __float_as_uint(acc[35 + 4 * t]));
            }
            bar_sync(1, 256);
            float4 o[8];
#pragma unroll
            for (int t = 0; t < 8; t++) o[t] = lds_f4(xch + (w ^ 1) * SLOT + t * 2048);
            const uint32_t tile = sb + OFF_A + w * SLOT;
#pragma unroll
            for (int t = 0; t < 8; t++) {
                hr[2 * t] = pack_bf16(fmaf(acc[4 * t] + o[t].x, r2[2 * t], bf_lo(hr[2 * t])), fmaf(acc[4 * t + 1] + o[t].y, r2[2 * t + 1], bf_hi(hr[2 * t])));
                hr[2 * t + 1] = pack_bf16(fmaf(acc[4 * t + 2] + o[t].z, r2[2 * t], bf_lo(hr[2 * t + 1])), fmaf(acc[4 * t + 3] + o[t].w, r2[2 * t + 1], bf_hi(hr[2 * t + 1])));
            }
#pragma unroll
            for (int tp = 0; tp < 4; tp++) stsm4t(tile + blk + tp * 2048, hr[4 * tp], hr[4 * tp + 1], hr[4 * tp + 2], hr[4 * tp + 3]);
            fence_async_smem();
            bar_sync(2 + w, 128);
            if ((tid & 127) == 0) {
                tma_store2d(&P.tout, tile, 64 * j, 128 * m + 64 * w);
                asm volatile("cp.async.bulk.wait_group.read 0;" ::: "memory");
            }
            if (tid == 0 && role == 0) g_epoch = epoch + 1;
            TL(16, tid == 0); TLG(1, tid == 0);
        }
    }
}

__global__ void probe_kernel() {}

typedef CUresult (*EncodeFn)(CUtensorMap*, CUtensorMapDataType, cuuint32_t, void*, const cuuint64_t*, const cuuint64_t*,
                             const cuuint32_t*, const cuuint32_t*, CUtensorMapInterleave, CUtensorMapSwizzle,
                             CUtensorMapL2promotion, CUtensorMapFloatOOBfill);

static void make_map2d(EncodeFn enc, CUtensorMap* tm, const void* base, uint64_t cols, uint64_t rows, uint64_t pitch_elems,
                       uint32_t box_rows) {
    cuuint64_t gd[2] = {cols, rows};
    cuuint64_t gs[1] = {pitch_elems * 2};
    cuuint32_t bd[2] = {64, box_rows};
    cuuint32_t es[2] = {1, 1};
    enc(tm, CU_TENSOR_MAP_DATA_TYPE_BFLOAT16, 2, const_cast<void*>(base), gd, gs, bd, es, CU_TENSOR_MAP_INTERLEAVE_NONE,
        CU_TENSOR_MAP_SWIZZLE_128B, CU_TENSOR_MAP_L2_PROMOTION_L2_256B, CU_TENSOR_MAP_FLOAT_OOB_FILL_NONE);
}

}

extern "C" void kernel_launch(void* const* d_in, const int* in_sizes, int n_in, void* d_out, int out_size) {
    using namespace hk;
    (void)in_sizes; (void)n_in; (void)out_size;
    static EncodeFn enc = nullptr;
    static void *po = nullptr, *ph = nullptr, *phh = nullptr;
    static int std_layout = 0;
    if (!enc) {
        void* fn = nullptr;
        cudaDriverEntryPointQueryResult qr;
        cudaGetDriverEntryPoint("cuTensorMapEncodeTiled", &fn, cudaEnableDefault, &qr);
        enc = (EncodeFn)fn;
        cudaGetSymbolAddress(&po, g_o);
        cudaGetSymbolAddress(&ph, g_h);
        cudaGetSymbolAddress(&phh, g_hh);
        cudaFuncSetAttribute(fused_kernel, cudaFuncAttributeMaxDynamicSharedMemorySize, SMEM_BYTES);
        int dev = 0, sms = 0;
        cudaGetDevice(&dev);
        cudaDeviceGetAttribute(&sms, cudaDevAttrMultiProcessorCount, dev);
        cudaFuncSetAttribute(probe_kernel, cudaFuncAttributeNonPortableClusterSizeAllowed, 1);
        cudaFuncSetAttribute(probe_kernel, cudaFuncAttributeMaxDynamicSharedMemorySize, SMEM_BYTES);
        const int sizes[3] = {8, 9, 16}, want[3] = {15, 9, 7};
        bool ok = sms == NCTA;
        for (int i = 0; i < 3 && ok; i++) {
            cudaLaunchConfig_t cfg = {};
            cfg.gridDim = dim3(sizes[i] * 8); cfg.blockDim = dim3(NTHREADS); cfg.dynamicSmemBytes = SMEM_BYTES;
            cudaLaunchAttribute at;
            at.id = cudaLaunchAttributeClusterDimension;
            at.val.clusterDim.x = sizes[i]; at.val.clusterDim.y = 1; at.val.clusterDim.z = 1;
            cfg.attrs = &at; cfg.numAttrs = 1;
            int n = 0;
            ok = cudaOccupancyMaxActiveClusters(&n, probe_kernel, &cfg) == cudaSuccess && n == want[i];
        }
        (void)cudaGetLastError();
        std_layout = ok ? 1 : 0;
    }
    Params P;
    const __nv_bfloat16* x = (const __nv_bfloat16*)d_in[0];
    P.x = x;
    P.wqkv = (const __nv_bfloat16*)d_in[1];
    P.wphi = (const __nv_bfloat16*)d_in[2];
    P.wo = (const __nv_bfloat16*)d_in[3];
    P.wg = (const __nv_bfloat16*)d_in[5];
    P.wu = (const __nv_bfloat16*)d_in[6];
    P.wd = (const __nv_bfloat16*)d_in[7];
    P.out = (__nv_bfloat16*)d_out;
    P.zero = 0;
    for (int i = 0; i < NCTA; i++) {
        const int odd = i & 1;
        int role = i < 4 ? 128 + i : (((i - 4) >> 4) * 2 + odd) * 8 + (((i - 4) >> 1) & 7);
        if (std_layout) {
            const int tpc = i < 8 ? 62 + (i >> 1) : (i - 8) >> 1;
            if (tpc < 32) role = (tpc & 7) ? (2 * ((tpc & 7) - 1) + odd) * 8 + (tpc >> 3) : (14 + odd) * 8 + (tpc >> 3);
            else if (tpc < 60) role = (2 * ((tpc - 32) % 7) + odd) * 8 + 4 + (tpc - 32) / 7;
            else if (tpc < 62) role = 128 + (tpc - 60) * 2 + odd;
            else role = (14 + odd) * 8 + 4 + (tpc - 62);
        }
        P.role[i] = (unsigned char)role;
    }
    make_map2d(enc, &P.tx, x, DM, SEQ, DM, 128);
    make_map2d(enc, &P.to, po, DM, SEQ, DM, 128);
    make_map2d(enc, &P.th, ph, DM, SEQ, DM, 128);
    make_map2d(enc, &P.thh, phh, FFP, SEQ, FFP, 128);
    make_map2d(enc, &P.twq, P.wqkv, 3 * DM, DM, 3 * DM, 64);
    make_map2d(enc, &P.two, P.wo, DM, DM, DM, 64);
    make_map2d(enc, &P.twg, P.wg, FF, DM, FF, 64);
    make_map2d(enc, &P.twu, P.wu, FF, DM, FF, 64);
    make_map2d(enc, &P.twd, P.wd, DM, FF, DM, 64);
    make_map2d(enc, &P.tout, d_out, DM, SEQ, DM, 64);
    fused_kernel<<<NCTA, NTHREADS, SMEM_BYTES>>>(P);
}
```

```cpp
#include <cuda_runtime.h>
#include <cuda_bf16.h>
#include <cuda.h>
#include <stdint.h>

namespace hk {

constexpr int SEQ = 2048, DM = 512, FF = 1376, FFP = 1536;
constexpr int NCTA = 132;
constexpr int NTHREADS = 384;
constexpr uint32_t SLOT = 16384;
constexpr uint32_t OFF_A = 0, OFF_B = 8 * SLOT, OFF_MISC = 14 * SLOT;
constexpr uint32_t BAR_FULLA = OFF_MISC + 0, BAR_EMPTYA = OFF_MISC + 64, BAR_FULLB = OFF_MISC + 128,
                   BAR_EMPTYB = OFF_MISC + 176, BAR_CS1 = OFF_MISC + 224, BAR_CS3 = OFF_MISC + 232,
                   BAR_CSQ = OFF_MISC + 240, BAR_CSV = OFF_MISC + 248,
                   BAR_STG = OFF_MISC + 256,
                   BAR_KVW = OFF_MISC + 280, BAR_KVR = OFF_MISC + 288, BAR_CSG = OFF_MISC + 296;
constexpr uint32_t OFF_CS1 = OFF_MISC + 384;
constexpr uint32_t OFF_CS3 = OFF_CS1 + 1024;
constexpr uint32_t OFF_XST = OFF_CS3;
constexpr uint32_t SMEM_BYTES = OFF_CS3 + 1536;
#define KVS(j) ((j) == 3 ? 2 : 3)
#define KORD(i, j) ((i) == 0 ? (j) : (i) - ((i) <= (j)))
constexpr int NB = 6;
constexpr int AHEAD = 3;

constexpr int ACC_KV = 0, ACC_Z = 2048, ACC_SIZE = 2176;

__device__ __align__(1024) __nv_bfloat16 g_o[SEQ * DM];
__device__ __align__(1024) __nv_bfloat16 g_h[SEQ * DM];
__device__ __align__(1024) __nv_bfloat16 g_hh[SEQ * FFP];
__device__ __align__(128) unsigned long long g_hstat[SEQ * 16];
__device__ __align__(128) unsigned long long g_xstat[SEQ * 2];
__device__ __align__(128) float g_acc[8 * ACC_SIZE];
__device__ __align__(128) unsigned g_cnt[8 * 32];
__device__ __align__(128) unsigned long long g_cs[8 * 6 * 128];
__device__ __align__(128) unsigned g_flag[16 * 5 * 32];
__device__ unsigned g_epoch = 1;

#define TL(i, pred) do {} while (0)
#define TLG(i, pred) do {} while (0)

struct Params {
    CUtensorMap tx, to, th, thh, twq, two, twg, twu, twd, tout;
    const __nv_bfloat16 *x, *wqkv, *wphi, *wo, *wg, *wu, *wd;
    __nv_bfloat16* out;
    unsigned zero;
    unsigned char role[NCTA];
};

__device__ __forceinline__ uint32_t smem_u32(const void* p) { return (uint32_t)__cvta_generic_to_shared(p); }
__device__ __forceinline__ void mbar_init(uint32_t bar, uint32_t cnt) {
    asm volatile("mbarrier.init.shared::cta.b64 [%0], %1;" ::"r"(bar), "r"(cnt) : "memory");
}
__device__ __forceinline__ void mbar_expect_tx(uint32_t bar, uint32_t bytes) {
    asm volatile("mbarrier.arrive.expect_tx.shared::cta.b64 _, [%0], %1;" ::"r"(bar), "r"(bytes) : "memory");
}
__device__ __forceinline__ void mbar_arrive(uint32_t bar) {
    asm volatile("mbarrier.arrive.shared::cta.b64 _, [%0];" ::"r"(bar) : "memory");
}
__device__ __forceinline__ void mbar_arrive_if(uint32_t bar, bool pred) {
    asm volatile("{.reg .pred p; setp.ne.u32 p, %1, 0; @p mbarrier.arrive.shared::cta.b64 _, [%0];}" ::"r"(bar), "r"((uint32_t)pred) : "memory");
}
__device__ __forceinline__ bool mbar_try(uint32_t bar, uint32_t parity) {
    uint32_t ok;
    asm volatile("{.reg .pred p; mbarrier.try_wait.parity.shared::cta.b64 p, [%1], %2; selp.u32 %0,1,0,p;}"
                 : "=r"(ok) : "r"(bar), "r"(parity) : "memory");
    return ok;
}
__device__ __forceinline__ bool mbar_test(uint32_t bar, uint32_t parity) {
    uint32_t ok;
    asm volatile("{.reg .pred p; mbarrier.test_wait.parity.shared::cta.b64 p, [%1], %2; selp.u32 %0,1,0,p;}"
                 : "=r"(ok) : "r"(bar), "r"(parity) : "memory");
    return ok;
}
__device__ __forceinline__ void trap_if_gt(uint32_t v, uint32_t lim) {
    asm volatile("{.reg .pred p; setp.gt.u32 p, %0, %1; @p trap;}" ::"r"(v), "r"(lim));
}
__device__ __forceinline__ void mbar_wait(uint32_t bar, uint32_t parity) {
    asm volatile("{\n"
                 ".reg .pred P1, P2;\n"
                 ".reg .u32 c;\n"
                 "mov.u32 c, 0;\n"
                 "LAB_WAIT:\n"
                 "mbarrier.try_wait.parity.shared::cta.b64 P1, [%0], %1;\n"
                 "@P1 bra LAB_DONE;\n"
                 "add.u32 c, c, 1;\n"
                 "setp.gt.u32 P2, c, 4194304;\n"
                 "@P2 trap;\n"
                 "bra LAB_WAIT;\n"
                 "LAB_DONE:\n"
                 "}" ::"r"(bar), "r"(parity) : "memory");
}
__device__ __forceinline__ void mbar_waitc(uint32_t bar, uint32_t parity) {
    asm volatile("{\n"
                 ".reg .pred P1;\n"
                 "LAB_WAIT:\n"
                 "mbarrier.try_wait.parity.shared::cta.b64 P1, [%0], %1;\n"
                 "@!P1 bra LAB_WAIT;\n"
                 "}" ::"r"(bar), "r"(parity) : "memory");
}
__device__ __forceinline__ void tma2d(uint32_t dst, const CUtensorMap* tm, uint32_t bar, int c0, int c1) {
    asm volatile("cp.async.bulk.tensor.2d.shared::cluster.global.mbarrier::complete_tx::bytes [%0], [%1, {%3, %4}], [%2];"
                 ::"r"(dst), "l"(tm), "r"(bar), "r"(c0), "r"(c1) : "memory");
}
__device__ __forceinline__ void tma2d_mc(uint32_t dst, const CUtensorMap* tm, uint32_t bar, int c0, int c1) {
    asm volatile("cp.async.bulk.tensor.2d.shared::cluster.global.mbarrier::complete_tx::bytes.multicast::cluster [%0], [%1, {%3, %4}], [%2], %5;"
                 ::"r"(dst), "l"(tm), "r"(bar), "r"(c0), "r"(c1), "h"((uint16_t)3) : "memory");
}
__device__ __forceinline__ uint32_t mapa(uint32_t addr, uint32_t rank) {
    uint32_t r; asm("mapa.shared::cluster.u32 %0, %1, %2;" : "=r"(r) : "r"(addr), "r"(rank)); return r;
}
__device__ __forceinline__ void mbar_arrive_cl_if(uint32_t cbar, bool pred) {
    asm volatile("{.reg .pred p; setp.ne.u32 p, %1, 0; @p mbarrier.arrive.shared::cluster.b64 _, [%0];}" ::"r"(cbar), "r"((uint32_t)pred) : "memory");
}
__device__ __forceinline__ bool elect_one() {
    uint32_t ok;
    asm volatile("{.reg .pred p; elect.sync _|p, 0xffffffff; selp.u32 %0, 1, 0, p;}" : "=r"(ok));
    return ok;
}
__device__ __forceinline__ void prefetch_tmap(const CUtensorMap* tm) {
    asm volatile("prefetch.tensormap [%0];" ::"l"(tm) : "memory");
}
__device__ __forceinline__ void prefetch_l2(const void* p, uint32_t bytes) {
    asm volatile("cp.async.bulk.prefetch.L2.global [%0], %1;" ::"l"(p), "r"(bytes) : "memory");
}
__device__ __forceinline__ unsigned ld_acquire(const unsigned* p) {
    unsigned v; asm volatile("ld.acquire.gpu.global.u32 %0, [%1];" : "=r"(v) : "l"(p) : "memory"); return v;
}
__device__ __forceinline__ uint4 ld_acquire4(const unsigned* p) {
    uint4 v;
    asm volatile("ld.acquire.gpu.global.v4.u32 {%0,%1,%2,%3}, [%4];" : "=r"(v.x), "=r"(v.y), "=r"(v.z), "=r"(v.w) : "l"(p) : "memory");
    return v;
}
__device__ __forceinline__ unsigned ld_relaxed(const unsigned* p) {
    unsigned v; asm volatile("ld.relaxed.gpu.global.u32 %0, [%1];" : "=r"(v) : "l"(p)); return v;
}
__device__ __forceinline__ void st_relaxed(unsigned* p, unsigned v) {
    asm volatile("st.relaxed.gpu.global.u32 [%0], %1;" ::"l"(p), "r"(v) : "memory");
}
__device__ __forceinline__ void red_relaxed(unsigned* p, unsigned v) {
    asm volatile("red.relaxed.gpu.global.add.u32 [%0], %1;" ::"l"(p), "r"(v) : "memory");
}
__device__ __forceinline__ void fence_gpu() { asm volatile("fence.acq_rel.gpu;" ::: "memory"); }
__device__ __forceinline__ void fence_async_smem() { asm volatile("fence.proxy.async.shared::cta;" ::: "memory"); }
__device__ __forceinline__ void fence_async_global() { asm volatile("fence.proxy.async.global;" ::: "memory"); }
__device__ __forceinline__ uint32_t readback(const void* p) {
    uint32_t v; asm volatile("ld.relaxed.gpu.global.u32 %0, [%1];" : "=r"(v) : "l"(p) : "memory"); return v;
}
__device__ __forceinline__ void wait_count(const unsigned* p, unsigned target) {
    uint32_t it = 0;
    while ((int)(readback(p) - target) < 0) trap_if_gt(++it, 1u << 22);
}
__device__ __forceinline__ void wait_count_warp(const unsigned* p, unsigned target) {
    uint32_t it = 0;
    while (__any_sync(0xffffffffu, (int)(readback(p) - target) < 0)) trap_if_gt(++it, 1u << 22);
}
__device__ __forceinline__ void red_f32(float* p, float a) {
    asm volatile("red.relaxed.gpu.global.add.f32 [%0], %1;" ::"l"(p), "f"(a) : "memory");
}
__device__ __forceinline__ void red_f32x2(float* p, float a, float b) {
    asm volatile("red.relaxed.gpu.global.add.v2.f32 [%0], {%1, %2};" ::"l"(p), "f"(a), "f"(b) : "memory");
}
__device__ __forceinline__ void red_f32x4(float* p, float a, float b, float c, float d) {
    asm volatile("red.relaxed.gpu.global.add.v4.f32 [%0], {%1, %2, %3, %4};" ::"l"(p), "f"(a), "f"(b), "f"(c), "f"(d) : "memory");
}
__device__ __forceinline__ float4 ld_l2_f4(const float* p) {
    float4 v;
    asm volatile("ld.relaxed.gpu.global.v4.f32 {%0,%1,%2,%3}, [%4];" : "=f"(v.x), "=f"(v.y), "=f"(v.z), "=f"(v.w) : "l"(p) : "memory");
    return v;
}
__device__ __forceinline__ float2 ld_l2_f2(const float* p) {
    float2 v;
    asm volatile("ld.relaxed.gpu.global.v2.f32 {%0,%1}, [%2];" : "=f"(v.x), "=f"(v.y) : "l"(p) : "memory");
    return v;
}
__device__ __forceinline__ float ld_l2_f(const float* p) {
    float v;
    asm volatile("ld.relaxed.gpu.global.f32 %0, [%1];" : "=f"(v) : "l"(p) : "memory");
    return v;
}
__device__ __forceinline__ uint4 ldg_nc(const void* p) {
    uint4 v;
    asm volatile("ld.global.nc.L1::no_allocate.v4.u32 {%0,%1,%2,%3}, [%4];" : "=r"(v.x), "=r"(v.y), "=r"(v.z), "=r"(v.w) : "l"(p));
    return v;
}
__device__ __forceinline__ void stg128(void* p, uint32_t a, uint32_t b, uint32_t c, uint32_t d) {
    asm volatile("st.global.v4.u32 [%0], {%1,%2,%3,%4};" ::"l"(p), "r"(a), "r"(b), "r"(c), "r"(d) : "memory");
}
__device__ __forceinline__ uint4 lds128(uint32_t a) {
    uint4 v;
    asm volatile("ld.shared.v4.u32 {%0,%1,%2,%3}, [%4];" : "=r"(v.x), "=r"(v.y), "=r"(v.z), "=r"(v.w) : "r"(a) : "memory");
    return v;
}
__device__ __forceinline__ float2 lds_f2(uint32_t a) {
    float2 v;
    asm volatile("ld.shared.v2.f32 {%0,%1}, [%2];" : "=f"(v.x), "=f"(v.y) : "r"(a) : "memory");
    return v;
}
__device__ __forceinline__ void sts_f2(uint32_t a, float x, float y) {
    asm volatile("st.shared.v2.f32 [%0], {%1,%2};" ::"r"(a), "f"(x), "f"(y) : "memory");
}
__device__ __forceinline__ void sts64(uint32_t a, uint32_t x, uint32_t y) {
    asm volatile("st.shared.v2.u32 [%0], {%1,%2};" ::"r"(a), "r"(x), "r"(y) : "memory");
}
__device__ __forceinline__ void sts128(uint32_t a, uint32_t x, uint32_t y, uint32_t z, uint32_t w) {
    asm volatile("st.shared.v4.u32 [%0], {%1,%2,%3,%4};" ::"r"(a), "r"(x), "r"(y), "r"(z), "r"(w) : "memory");
}
__device__ __forceinline__ void stsm4(uint32_t a, uint32_t r0, uint32_t r1, uint32_t r2, uint32_t r3) {
    asm volatile("stmatrix.sync.aligned.m8n8.x4.shared.b16 [%0], {%1,%2,%3,%4};" ::"r"(a), "r"(r0), "r"(r1), "r"(r2), "r"(r3) : "memory");
}
__device__ __forceinline__ void stsm4t(uint32_t a, uint32_t r0, uint32_t r1, uint32_t r2, uint32_t r3) {
    asm volatile("stmatrix.sync.aligned.m8n8.x4.trans.shared.b16 [%0], {%1,%2,%3,%4};" ::"r"(a), "r"(r0), "r"(r1), "r"(r2), "r"(r3) : "memory");
}
__device__ __forceinline__ void tma_store2d(const CUtensorMap* tm, uint32_t src, int c0, int c1) {
    asm volatile("cp.async.bulk.tensor.2d.global.shared::cta.bulk_group [%0, {%2, %3}], [%1];" ::"l"(tm), "r"(src), "r"(c0), "r"(c1) : "memory");
    asm volatile("cp.async.bulk.commit_group;" ::: "memory");
}
__device__ __forceinline__ void ldsm4(uint32_t a, uint32_t& r0, uint32_t& r1, uint32_t& r2, uint32_t& r3) {
    asm volatile("ldmatrix.sync.aligned.m8n8.x4.shared.b16 {%0,%1,%2,%3}, [%4];" : "=r"(r0), "=r"(r1), "=r"(r2), "=r"(r3) : "r"(a) : "memory");
}
__device__ __forceinline__ void ldsm4t(uint32_t a, uint32_t& r0, uint32_t& r1, uint32_t& r2, uint32_t& r3) {
    asm volatile("ldmatrix.sync.aligned.m8n8.x4.trans.shared.b16 {%0,%1,%2,%3}, [%4];" : "=r"(r0), "=r"(r1), "=r"(r2), "=r"(r3) : "r"(a) : "memory");
}
__device__ __forceinline__ void mma16816(float* c, const uint32_t* a, uint32_t b0, uint32_t b1) {
    asm("mma.sync.aligned.m16n8k16.row.col.f32.bf16.bf16.f32 {%0,%1,%2,%3}, {%4,%5,%6,%7}, {%8,%9}, {%0,%1,%2,%3};"
                 : "+f"(c[0]), "+f"(c[1]), "+f"(c[2]), "+f"(c[3])
                 : "r"(a[0]), "r"(a[1]), "r"(a[2]), "r"(a[3]), "r"(b0), "r"(b1));
}
__device__ __forceinline__ uint32_t pack_bf16(float lo, float hi) {
    uint32_t r; asm("cvt.rn.bf16x2.f32 %0, %1, %2;" : "=r"(r) : "f"(hi), "f"(lo)); return r;
}
__device__ __forceinline__ float bf_lo(uint32_t w) { return __uint_as_float(w << 16); }
__device__ __forceinline__ float bf_hi(uint32_t w) { return __uint_as_float(w & 0xffff0000u); }
__device__ __forceinline__ float ex2(float x) { float r; asm("ex2.approx.ftz.f32 %0, %1;" : "=f"(r) : "f"(x)); return r; }
__device__ __forceinline__ float rcp(float x) { float r; asm("rcp.approx.ftz.f32 %0, %1;" : "=f"(r) : "f"(x)); return r; }
__device__ __forceinline__ void bar_sync(int id, int n) { asm volatile("bar.sync %0, %1;" ::"r"(id), "r"(n) : "memory"); }

typedef unsigned long long desc_t;
__device__ __forceinline__ desc_t desc_lo(uint32_t addr) { return (desc_t)(((addr & 0x3FFFF) >> 4) | (512u << 16)) | (0x40000040ull << 32); }
__device__ __forceinline__ void wg_fence() { asm volatile("wgmma.fence.sync.aligned;" ::: "memory"); }
__device__ __forceinline__ void wg_commit() { asm volatile("wgmma.commit_group.sync.aligned;" ::: "memory"); }
template <int N> __device__ __forceinline__ void wg_wait() { asm volatile("wgmma.wait_group.sync.aligned %0;" ::"n"(N) : "memory"); }
template <int N> __device__ __forceinline__ void fence_acc(float* d) {
#pragma unroll
    for (int i = 0; i < N; i++) asm volatile("" : "+f"(d[i])::"memory");
}
#define R4(o) "+f"(d[o + 0]), "+f"(d[o + 1]), "+f"(d[o + 2]), "+f"(d[o + 3])
#define R8(o) R4(o), R4(o + 4)
__device__ __forceinline__ void wgmma_n128(float* d, desc_t da, desc_t db, int sc) {
    asm volatile("{.reg .pred p; setp.ne.b32 p, %66, 0;\n"
                 "wgmma.mma_async.sync.aligned.m64n128k16.f32.bf16.bf16 {%0,%1,%2,%3,%4,%5,%6,%7,%8,%9,%10,%11,%12,%13,%14,%15,%16,%17,%18,%19,%20,%21,%22,%23,%24,%25,%26,%27,%28,%29,%30,%31,"
                 "%32,%33,%34,%35,%36,%37,%38,%39,%40,%41,%42,%43,%44,%45,%46,%47,%48,%49,%50,%51,%52,%53,%54,%55,%56,%57,%58,%59,%60,%61,%62,%63}, %64, %65, p, 1, 1, 0, 1;}"
                 : R8(0), R8(8), R8(16), R8(24), R8(32), R8(40), R8(48), R8(56)
                 : "l"(da), "l"(db), "r"(sc));
}
__device__ __forceinline__ void wgmma_n112(float* d, desc_t da, desc_t db, int sc) {
    asm volatile("{.reg .pred p; setp.ne.b32 p, %58, 0;\n"
                 "wgmma.mma_async.sync.aligned.m64n112k16.f32.bf16.bf16 {%0,%1,%2,%3,%4,%5,%6,%7,%8,%9,%10,%11,%12,%13,%14,%15,%16,%17,%18,%19,%20,%21,%22,%23,%24,%25,%26,%27,%28,%29,%30,%31,%32,%33,%34,%35,%36,%37,%38,%39,%40,%41,%42,%43,%44,%45,%46,%47,%48,%49,%50,%51,%52,%53,%54,%55}, %56, %57, p, 1, 1, 0, 1;}"
                 : R8(0), R8(8), R8(16), R8(24), R8(32), R8(40), R8(48)
                 : "l"(da), "l"(db), "r"(sc));
}
__device__ __forceinline__ void wgmma_n128_tn(float* d, desc_t da, desc_t db, int sc) {
    asm volatile("{.reg .pred p; setp.ne.b32 p, %66, 0;\n"
                 "wgmma.mma_async.sync.aligned.m64n128k16.f32.bf16.bf16 {%0,%1,%2,%3,%4,%5,%6,%7,%8,%9,%10,%11,%12,%13,%14,%15,%16,%17,%18,%19,%20,%21,%22,%23,%24,%25,%26,%27,%28,%29,%30,%31,%32,%33,%34,%35,%36,%37,%38,%39,%40,%41,%42,%43,%44,%45,%46,%47,%48,%49,%50,%51,%52,%53,%54,%55,%56,%57,%58,%59,%60,%61,%62,%63}, %64, %65, p, 1, 1, 1, 0;}"
                 : R8(0), R8(8), R8(16), R8(24), R8(32), R8(40), R8(48), R8(56)
                 : "l"(da), "l"(db), "r"(sc));
}
__device__ __forceinline__ void wgmma_n64(float* d, desc_t da, desc_t db, int sc) {
    asm volatile("{.reg .pred p; setp.ne.b32 p, %34, 0;\n"
                 "wgmma.mma_async.sync.aligned.m64n64k16.f32.bf16.bf16 {%0,%1,%2,%3,%4,%5,%6,%7,%8,%9,%10,%11,%12,%13,%14,%15,%16,%17,%18,%19,%20,%21,%22,%23,%24,%25,%26,%27,%28,%29,%30,%31}, %32, %33, p, 1, 1, 0, 1;}"
                 : R8(0), R8(8), R8(16), R8(24)
                 : "l"(da), "l"(db), "r"(sc));
}
__device__ __forceinline__ void wgmma_n40_tt(float* d, desc_t da, desc_t db, int sc) {
    asm volatile("{.reg .pred p; setp.ne.b32 p, %22, 0;\n"
                 "wgmma.mma_async.sync.aligned.m64n40k16.f32.bf16.bf16 {%0,%1,%2,%3,%4,%5,%6,%7,%8,%9,%10,%11,%12,%13,%14,%15,%16,%17,%18,%19}, %20, %21, p, 1, 1, 1, 1;}"
                 : R8(0), R8(8), R4(16)
                 : "l"(da), "l"(db), "r"(sc));
}

__device__ __forceinline__ void wgmma_n8_tt(float* d, desc_t da, desc_t db, int sc) {
    asm volatile("{.reg .pred p; setp.ne.b32 p, %6, 0;\n"
                 "wgmma.mma_async.sync.aligned.m64n8k16.f32.bf16.bf16 {%0,%1,%2,%3}, %4, %5, p, 1, 1, 1, 1;}"
                 : R4(0)
                 : "l"(da), "l"(db), "r"(sc));
}

__device__ __forceinline__ uint32_t atom_f32x2(float* p, float a, float b) {
    float x, y;
    asm volatile("atom.relaxed.gpu.global.add.v2.f32 {%0,%1}, [%2], {%3,%4};" : "=f"(x), "=f"(y) : "l"(p), "f"(a), "f"(b) : "memory");
    return __float_as_uint(x);
}
__device__ __forceinline__ uint32_t atom_f32_if(float* p, float a, bool pred) {
    float x = 0.f;
    asm volatile("{.reg .pred p; setp.ne.u32 p, %3, 0; @p atom.relaxed.gpu.global.add.f32 %0, [%1], %2;}" : "+f"(x) : "l"(p), "f"(a), "r"((uint32_t)pred) : "memory");
    return __float_as_uint(x);
}
__device__ __forceinline__ void signal_after(unsigned* cnt, uint32_t ack, uint32_t zero, bool pred) {
    asm volatile("{.reg .pred p; setp.ne.u32 p, %2, 0; @p red.relaxed.gpu.global.add.u32 [%0], %1;}"
                 ::"l"(cnt), "r"((ack & zero) + 1), "r"((uint32_t)pred) : "memory");
}
__device__ __forceinline__ void signal_late(unsigned* cnt, const uint32_t* a, uint32_t zero, bool pred) {
    uint32_t v;
    asm volatile("{.reg .b32 t; lop3.b32 t, %1, %2, %3, 0xfe; or.b32 %0, t, %4;}"
                 : "=r"(v) : "r"(a[0]), "r"(a[1]), "r"(a[2]), "r"(a[3]));
    signal_after(cnt, v, zero, pred);
}
__device__ __forceinline__ void red_f32_if(float* p, float a, bool pred) {
    asm volatile("{.reg .pred p; setp.ne.u32 p, %2, 0; @p red.relaxed.gpu.global.add.f32 [%0], %1;}" ::"l"(p), "f"(a), "r"((uint32_t)pred) : "memory");
}
__device__ __forceinline__ void stg_f2_if(float* p, float a, float b, bool pred) {
    asm volatile("{.reg .pred p; setp.ne.u32 p, %3, 0; @p st.global.v2.f32 [%0], {%1,%2};}" ::"l"(p), "f"(a), "f"(b), "r"((uint32_t)pred) : "memory");
}
__device__ __forceinline__ void stg64(void* p, uint32_t a, uint32_t b) {
    asm volatile("st.global.v2.u32 [%0], {%1,%2};" ::"l"(p), "r"(a), "r"(b) : "memory");
}
__device__ __forceinline__ void mma16816_z(float* c, const uint32_t* a, uint32_t b0, uint32_t b1) {
    asm("mma.sync.aligned.m16n8k16.row.col.f32.bf16.bf16.f32 {%0,%1,%2,%3}, {%4,%5,%6,%7}, {%8,%9}, {%10,%10,%10,%10};"
                 : "=f"(c[0]), "=f"(c[1]), "=f"(c[2]), "=f"(c[3])
                 : "r"(a[0]), "r"(a[1]), "r"(a[2]), "r"(a[3]), "r"(b0), "r"(b1), "f"(0.f));
}
__device__ __forceinline__ uint32_t max2(uint32_t a, uint32_t b) { uint32_t r; asm("max.bf16x2 %0, %1, %2;" : "=r"(r) : "r"(a), "r"(b)); return r; }
__device__ __forceinline__ uint32_t min2(uint32_t a, uint32_t b) { uint32_t r; asm("min.bf16x2 %0, %1, %2;" : "=r"(r) : "r"(a), "r"(b)); return r; }
__device__ __forceinline__ void bar_arrive(int id, int n) { asm volatile("bar.arrive %0, %1;" ::"r"(id), "r"(n) : "memory"); }
__device__ __forceinline__ void mbar_arrive_n_if(uint32_t bar, uint32_t n, bool pred) {
    asm volatile("{.reg .pred p; setp.ne.u32 p, %1, 0; @p mbarrier.arrive.shared::cta.b64 _, [%0], %2;}" ::"r"(bar), "r"((uint32_t)pred), "r"(n) : "memory");
}
__device__ __forceinline__ float4 lds_f4(uint32_t a) {
    float4 v;
    asm volatile("ld.shared.v4.f32 {%0,%1,%2,%3}, [%4];" : "=f"(v.x), "=f"(v.y), "=f"(v.z), "=f"(v.w) : "r"(a) : "memory");
    return v;
}
__device__ __forceinline__ void lds_f4_if(float4& v, uint32_t a, bool pred) {
    asm volatile("{.reg .pred p; setp.ne.u32 p, %5, 0; @p ld.shared.v4.f32 {%0,%1,%2,%3}, [%4];}"
                 : "+f"(v.x), "+f"(v.y), "+f"(v.z), "+f"(v.w) : "r"(a), "r"((uint32_t)pred) : "memory");
}
__device__ __forceinline__ uint4 ld_tagged(const unsigned long long* p) {
    unsigned long long a, b;
    asm volatile("ld.acquire.gpu.global.v2.b64 {%0,%1}, [%2];" : "=l"(a), "=l"(b) : "l"(p) : "memory");
    return make_uint4((unsigned)a, (unsigned)(a >> 32), (unsigned)b, (unsigned)(b >> 32));
}
__device__ __forceinline__ uint4 ld_tagged_rlx(const unsigned long long* p) {
    unsigned long long a, b;
    asm volatile("ld.relaxed.gpu.global.v2.b64 {%0,%1}, [%2];" : "=l"(a), "=l"(b) : "l"(p) : "memory");
    return make_uint4((unsigned)a, (unsigned)(a >> 32), (unsigned)b, (unsigned)(b >> 32));
}
__device__ __forceinline__ void st_tagged_if(unsigned long long* p, float a, float b, unsigned tag, bool pred) {
    const unsigned long long t = (unsigned long long)tag << 32;
    asm volatile("{.reg .pred p; setp.ne.u32 p, %3, 0; @p st.relaxed.gpu.global.v2.b64 [%0], {%1,%2};}"
                 ::"l"(p), "l"(t | __float_as_uint(a)), "l"(t | __float_as_uint(b)), "r"((uint32_t)pred) : "memory");
}

__device__ __forceinline__ void store_tile(uint32_t tile_rows, __nv_bfloat16* gdst, const uint32_t* lo, const uint32_t* hi, int lane, uint32_t* ack) {
    const int r = lane & 15;
#pragma unroll
    for (int b = 0; b < 4; b++)
        stsm4(tile_rows + r * 128 + (((2 * b + (lane >> 4)) ^ (r & 7)) << 4), lo[2 * b], hi[2 * b], lo[2 * b + 1], hi[2 * b + 1]);
    fence_async_smem();
    __syncwarp();
#pragma unroll
    for (int i = 0; i < 4; i++) {
        const int rr = 4 * i + (lane >> 3);
        const uint4 v = lds128(tile_rows + rr * 128 + (((lane & 7) ^ (rr & 7)) << 4));
        stg128(gdst + rr * DM + (lane & 7) * 8, v.x, v.y, v.z, v.w);
    }
#pragma unroll
    for (int i = 0; i < 4; i++) ack[i] = readback(gdst + (4 * i + (lane >> 3)) * DM + (lane & 7) * 8);
}

__device__ __forceinline__ void feature_maps(const uint32_t* a, const uint32_t* wb, float c0, float c1, uint32_t* plus, uint32_t* minus) {
    uint32_t P[16], mx[4], mn[4];
#pragma unroll
    for (int h = 0; h < 4; h++) {
        float p[8];
        mma16816_z(p, a + 4 * h, wb[4 * h], wb[4 * h + 1]);
        mma16816_z(p + 4, a + 4 * h, wb[4 * h + 2], wb[4 * h + 3]);
        P[4 * h] = pack_bf16(p[0], p[2]); P[4 * h + 1] = pack_bf16(p[1], p[3]);
        P[4 * h + 2] = pack_bf16(p[4], p[6]); P[4 * h + 3] = pack_bf16(p[5], p[7]);
        mx[h] = max2(max2(P[4 * h], P[4 * h + 1]), max2(P[4 * h + 2], P[4 * h + 3]));
        mn[h] = min2(min2(P[4 * h], P[4 * h + 1]), min2(P[4 * h + 2], P[4 * h + 3]));
    }
#pragma unroll
    for (int s = 1; s <= 2; s <<= 1) {
        uint32_t tx[4], tn[4];
#pragma unroll
        for (int h = 0; h < 4; h++) { tx[h] = __shfl_xor_sync(0xffffffffu, mx[h], s); tn[h] = __shfl_xor_sync(0xffffffffu, mn[h], s); }
#pragma unroll
        for (int h = 0; h < 4; h++) { mx[h] = max2(mx[h], tx[h]); mn[h] = min2(mn[h], tn[h]); }
    }
#pragma unroll
    for (int h = 0; h < 4; h++) {
        const float mx0 = bf_lo(mx[h]) * c0, mx1 = bf_hi(mx[h]) * c1, mn0 = bf_lo(mn[h]) * c0, mn1 = bf_hi(mn[h]) * c1;
        float ep[8], em[8];
#pragma unroll
        for (int i = 0; i < 8; i++) {
            const bool r1 = (i & 2);
            const uint32_t w = P[4 * h + (i >> 2) * 2 + (i & 1)];
            const float p = r1 ? bf_hi(w) : bf_lo(w);
            ep[i] = ex2(fmaf(p, r1 ? c1 : c0, r1 ? -mx1 : -mx0));
            em[i] = ex2(fmaf(p, r1 ? -c1 : -c0, r1 ? mn1 : mn0));
        }
        float sp[4], sm[4];
        uint32_t tp[4], tm[4];
#pragma unroll
        for (int i = 0; i < 4; i++) { tp[i] = pack_bf16(ep[2 * i], ep[2 * i + 1]); tm[i] = pack_bf16(em[2 * i], em[2 * i + 1]); }
        mma16816_z(sp, tp, 0x3f803f80u, 0x3f803f80u);
        mma16816_z(sm, tm, 0x3f803f80u, 0x3f803f80u);
        const float r0 = rcp(sp[0] * sm[0]), r1 = rcp(sp[2] * sm[2]);
        const float rs[4] = {r0 * sm[0], r1 * sm[2], r0 * sp[0], r1 * sp[2]};
#pragma unroll
        for (int i = 0; i < 4; i++) {
            plus[4 * h + i] = pack_bf16(ep[2 * i] * rs[i & 1], ep[2 * i + 1] * rs[i & 1]);
            minus[4 * h + i] = pack_bf16(em[2 * i] * rs[2 + (i & 1)], em[2 * i + 1] * rs[2 + (i & 1)]);
        }
    }
}

template <bool SCALE>
__device__ __forceinline__ void ln_frag(const float* acc, uint32_t cs_addr, float rs0, float nm0, float rs1, float nm1, uint32_t* a) {
    const float2 c0 = lds_f2(cs_addr), c1 = lds_f2(cs_addr + 32);
    const float s0 = SCALE ? rs0 : 1.f, s1 = SCALE ? rs1 : 1.f;
    a[0] = pack_bf16(fmaf(nm0, c0.x, acc[0]) * s0, fmaf(nm0, c0.y, acc[1]) * s0);
    a[1] = pack_bf16(fmaf(nm1, c0.x, acc[2]) * s1, fmaf(nm1, c0.y, acc[3]) * s1);
    a[2] = pack_bf16(fmaf(nm0, c1.x, acc[4]) * s0, fmaf(nm0, c1.y, acc[5]) * s0);
    a[3] = pack_bf16(fmaf(nm1, c1.x, acc[6]) * s1, fmaf(nm1, c1.y, acc[7]) * s1);
}

template <int UP>
__device__ __forceinline__ uint32_t hh_pair(const float* ag, float4 cs, float nmean) {
    const float g0 = fmaf(nmean, cs.x, ag[0]), g1 = fmaf(nmean, cs.y, ag[1]);
    const float u0 = fmaf(nmean, cs.z, ag[UP]), u1 = fmaf(nmean, cs.w, ag[UP + 1]);
    return pack_bf16(g0 * u0, g1 * u1);
}
template <int NTP>
__device__ __forceinline__ void hh_stage(const float* acc, const float4* cs, float nm0, float nm1, uint32_t stg, int lane) {
#pragma unroll
    for (int tp = 0; tp < NTP; tp++)
        stsm4(stg + (lane & 15) * 128 + (((2 * tp + (lane >> 4)) ^ (lane & 7)) << 4), hh_pair<32>(acc + 8 * tp, cs[2 * tp], nm0),
              hh_pair<32>(acc + 8 * tp + 2, cs[2 * tp], nm1), hh_pair<32>(acc + 8 * tp + 4, cs[2 * tp + 1], nm0),
              hh_pair<32>(acc + 8 * tp + 6, cs[2 * tp + 1], nm1));
    fence_async_smem();
    __syncwarp();
}

struct Ring {
    int slot; uint32_t phase;
    __device__ __forceinline__ void adv() { if (++slot == NB) { slot = 0; phase ^= 1; } }
    __device__ __forceinline__ void adv5() { slot += slot == 3; adv(); }
};

__global__ void __cluster_dims__(2, 1, 1) __launch_bounds__(NTHREADS, 1) fused_kernel(const __grid_constant__ Params P) {
    extern __shared__ __align__(1024) uint8_t smem_raw[];
    const uint32_t sb = smem_u32(smem_raw);
    const int tid = threadIdx.x, lane = tid & 31;
    const int warp = __shfl_sync(0xffffffffu, tid >> 5, 0);
    const unsigned role = P.role[blockIdx.x], rank = blockIdx.x & 1;
    const int m = role >> 3, j = role & 7;
    const bool helper = role >= 128;

    TL(0, tid == 0); TLG(0, tid == 0);
    float* const acc_j = g_acc + j * ACC_SIZE;
    unsigned* const cnt_j = g_cnt + j * 32;

    if (__builtin_expect(warp >= 8, 1)) {
        asm volatile("setmaxnreg.dec.sync.aligned.u32 72;");
        if (elect_one()) {
            if (warp == 8) {
                if (!helper) {
#pragma unroll
                    for (int i = 0; i < NB; i++) mbar_init(sb + BAR_FULLB + 8 * i, 1);
#pragma unroll
                    for (int i = 0; i < 2; i++) {
                        mbar_expect_tx(sb + BAR_FULLB + 8 * i, SLOT);
                        tma2d(sb + OFF_B + i * SLOT, &P.twq, sb + BAR_FULLB + 8 * i, DM + 64 * j, 64 * i);
                        tma2d(sb + OFF_B + i * SLOT + 8192, &P.twq, sb + BAR_FULLB + 8 * i, 2 * DM + 64 * j, 64 * i);
                    }
                }
            } else if (warp == 9) {
#pragma unroll
                for (int i = 0; i < 8; i++) mbar_init(sb + BAR_FULLA + 8 * i, 1);
                if (!helper) {
#pragma unroll
                    for (int i = 0; i < 2; i++) {
                        mbar_expect_tx(sb + BAR_FULLA + 8 * i, SLOT);
                        tma2d(sb + OFF_A + i * SLOT, &P.tx, sb + BAR_FULLA + 8 * i, 64 * i, 128 * m);
                    }
                }
            } else if (warp == 10) {
#pragma unroll
                for (int i = 0; i < 10; i++) mbar_init(sb + BAR_CS1 + 8 * i, i < 2 || i == 8 ? 64 : (i < 4 || i == 9 ? 32 : 8));
                trap_if_gt(sb & 1023, 0);
            } else {
#pragma unroll
                for (int i = 0; i < 14; i++) mbar_init(sb + (i < 8 ? BAR_EMPTYA : BAR_EMPTYB - 64) + 8 * i, i < 8 ? 8 : 16);
            }
            asm volatile("fence.mbarrier_init.release.cluster;" ::: "memory");
        }
        __syncwarp();
        asm volatile("barrier.cluster.arrive.relaxed.aligned;" ::: "memory");
        const unsigned epoch = ld_relaxed(&g_epoch);
        bar_sync(0, NTHREADS);
        if (helper) {
            if (warp == 8) {
                if (elect_one()) {
#pragma unroll 1
                    for (int i = 0; i < 72; i++) {
                        const uint32_t full = sb + BAR_FULLA + 8 * (i & 7), dst = sb + OFF_A + (i & 7) * SLOT;
                        mbar_wait(sb + BAR_EMPTYA + 8 * (i & 7), ((i >> 3) & 1) ^ 1);
                        mbar_expect_tx(full, SLOT);
                        const bool qkv = i < 24;
                        const int u = (i >> 3) - 3;
                        const int c0 = qkv ? (i < 16 ? DM + 64 * (i & 8) : 0) + 128 * j + 16 * (i & 4) : 176 * (2 * j + (u & 1)) + 64 * (u >> 1);
                        const int r0 = qkv ? 128 * (i & 3) : 64 * (i & 7);
                        tma2d(dst, qkv ? &P.twq : &P.twg, full, c0, r0);
                        tma2d(dst + 8192, qkv ? &P.twq : &P.twu, full, c0, qkv ? r0 + 64 : r0);
                    }
                    prefetch_l2(P.wd + (size_t)j * 176128, 352256);
                }
            }
            return;
        }
        if (warp == 8) {
            asm volatile("barrier.cluster.wait.aligned;" ::: "memory");
            if (elect_one()) {
                if (m >= 6)
                    asm volatile("cp.async.bulk.prefetch.tensor.2d.L2.global [%0, {%1, %2}];" ::"l"(&P.twq), "r"(DM + DM * (m & 1) + 64 * j), "r"(64 * (m >> 1)) : "memory");
                if (j >= 3)
                    asm volatile("cp.async.bulk.prefetch.tensor.2d.L2.global [%0, {%1, %2}];" ::"l"(&P.tx), "r"(64 * j), "r"(128 * m) : "memory");
                Ring r{2, 0};
                const uint32_t dst = sb + OFF_B + rank * 8192;
#define B_LOAD(TM, C0, R0)                                                                                  \
        mbar_waitc(sb + BAR_EMPTYB + 8 * r.slot, r.phase ^ 1);                                              \
        mbar_expect_tx(sb + BAR_FULLB + 8 * r.slot, SLOT);                                                  \
        tma2d_mc(dst + r.slot * SLOT, TM, sb + BAR_FULLB + 8 * r.slot, C0, R0);
#pragma unroll 1
                for (int i = 2; i < 8; i++) {
                    if (i >= AHEAD && i < 6) mbar_waitc(sb + BAR_FULLB + 8 * (i - AHEAD), 0);
                    B_LOAD(&P.twq, DM + DM * rank + 64 * j, 64 * i)
                    r.adv();
                }
#pragma unroll 1
                for (int i = 8; i < 20; i++) {
                    if (i >= 10 && i < 14) {
                        mbar_waitc(sb + BAR_EMPTYB + 8 * r.slot, r.phase ^ 1);
                        mbar_arrive(sb + BAR_FULLB + 8 * r.slot);
                    } else {
                        const int e = 2 * (i & 3) + rank;
                        B_LOAD(i < 16 ? &P.twq : &P.two, 64 * j, 64 * (i < 16 ? e : KORD(e, j)))
                    }
                    r.adv();
                }
#pragma unroll 1
                for (int i = 0; i < 24; i++) {
                    B_LOAD(&P.twg + rank, 176 * j + 8 * (i & ~7), 64 * (i < 8 ? KORD(i, j) : i & 7))
                    r.adv5();
                }
#pragma unroll 1
                for (int i = 0; i < 12; i++) {
                    B_LOAD(&P.twd, 64 * j, 176 * (2 * (i & 3) + rank) + 64 * (i >> 2))
                    r.adv5();
                }
            }
            return;
        }
        if (warp == 9) {
            if (elect_one()) {
#pragma unroll 1
                for (int i = 2; i < 8; i++) {
                    if (i >= AHEAD + 1) mbar_wait(sb + BAR_FULLA + 8 * (i - AHEAD - 1), 0);
                    mbar_expect_tx(sb + BAR_FULLA + 8 * i, SLOT);
                    tma2d(sb + OFF_A + i * SLOT, &P.tx, sb + BAR_FULLA + 8 * i, 64 * i, 128 * m);
                }
#pragma unroll 1
                for (int i = 1; i < 10; i++) prefetch_tmap(&P.tx + i);
#pragma unroll 1
                for (int r = 1; r < 6; r++) {
                    const CUtensorMap* tm = &P.tx + min(r, 3);
                    const int cstep = r < 3 ? 64 : 192, cbase = r < 3 ? 0 : 64 * (r - 3), skip = r < 3 ? j : 8;
                    if (r < 4) mbar_wait(sb + BAR_EMPTYA + 8 * (skip == 0), (r - 1) & 1);
                    wait_count(g_flag + (m * 5 + r - 1) * 32, epoch * (r < 3 ? 64 : 8));
                    TL(64 + r, true);
#pragma unroll 1
                    for (int t = 0; t < 8; t++) {
                        if (t == skip) continue;
                        mbar_wait(sb + BAR_EMPTYA + 8 * t, (r - 1) & 1);
                        mbar_expect_tx(sb + BAR_FULLA + 8 * t, SLOT);
                        tma2d(sb + OFF_A + t * SLOT, tm, sb + BAR_FULLA + 8 * t, cbase + cstep * t, 128 * m);
                    }
                }
            }
            return;
        }
        const int a = warp - 10;
        {
            const int row = 16 * j + 8 * a + (lane >> 2);
            const uint32_t ra = sb + OFF_A + row * 128;
            float sh = 0.f, s0 = 0.f, s1 = 0.f, q0 = 0.f, q1 = 0.f;
#pragma unroll 1
            for (int kt = 0; kt < 8; kt++) {
                mbar_wait(sb + BAR_FULLA + 8 * kt, 0);
                if (kt == 0) sh = bf_lo(lds128(ra + ((row & 7) << 4)).x);
#pragma unroll
                for (int i = 0; i < 2; i++) {
                    const uint4 v = lds128(ra + kt * SLOT + (((2 * (lane & 3) + i) ^ (row & 7)) << 4));
                    const uint32_t ww[4] = {v.x, v.y, v.z, v.w};
#pragma unroll
                    for (int e = 0; e < 4; e++) {
                        const float d0 = bf_lo(ww[e]) - sh, d1 = bf_hi(ww[e]) - sh;
                        s0 += d0; q0 = fmaf(d0, d0, q0);
                        s1 += d1; q1 = fmaf(d1, d1, q1);
                    }
                }
            }
            s0 += s1; q0 += q1;
#pragma unroll
            for (int o = 1; o <= 2; o <<= 1) { s0 += __shfl_xor_sync(0xffffffffu, s0, o); q0 += __shfl_xor_sync(0xffffffffu, q0, o); }
            const float md = s0 * (1.f / DM);
            const float rs = rsqrtf(fmaxf(q0 * (1.f / DM) - md * md, 0.f) + 1e-5f);
            st_tagged_if(g_xstat + 2 * (128 * m + row), rs, -(sh + md), epoch, (lane & 3) == 0);
        }
        const unsigned long long* cs = g_cs + j * 768 + 2 * lane;
#pragma unroll 1
        for (int c = 0; c < (a ? 5 : 10); c++) {
            if (c == 4) {
                const int t = 32 * a + lane;
                const uint32_t kvs = sb + OFF_A + KVS(j) * SLOT;
                mbar_wait(sb + BAR_KVW, 0);
#pragma unroll 1
                for (int pass = 0; pass < 2; pass++) {
                    float4 v[8];
#pragma unroll
                    for (int i = 0; i < 8; i++) v[i] = ld_l2_f4(acc_j + ACC_KV + 4 * (t + 64 * i));
                    const float2 zz = ld_l2_f2(acc_j + ACC_Z + 2 * t);
#pragma unroll
                    for (int i = 0; i < 8; i++)
                        sts64(kvs + ((t >> 2) + 16 * i) * 48 + (t & 3) * 8, pack_bf16(v[i].x, v[i].y), pack_bf16(v[i].z, v[i].w));
                    const uint32_t z0 = pack_bf16(zz.x, zz.x), z1 = pack_bf16(zz.y, zz.y);
                    sts128(kvs + t * 96 + 32, z0, z0, z0, z0);
                    sts128(kvs + t * 96 + 80, z1, z1, z1, z1);
                    if (pass == 0) {
                        __syncwarp();
                        if (lane == 0) red_relaxed(cnt_j, 1);
                        TL(19, t == 0);
                        wait_count_warp(cnt_j, epoch * 32);
                        TL(14, t == 0);
                    }
                }
                mbar_arrive(sb + BAR_KVR);
                if (a) break;
            }
            if (c == 3 && !a) continue;
            const unsigned long long* src = c < 2 ? g_xstat + 2 * (128 * m + 64 * a + 32 * c + lane) : cs + (c < 4 ? 128 * (a + c - 2) : 128 + 64 * c);
            const uint32_t dst = c < 2 ? OFF_XST + (64 * a + 32 * c + lane) * 8
                                       : (c < 4 ? OFF_CS1 + (c == 2 ? 256 * (a + 1) : 0) + 8 * lane : OFF_CS3 + (32 * ((c - 4) >> 1) + lane) * 16 + 8 * (c & 1));
            uint4 v;
            uint32_t it = 0;
            while (true) {
                v = ld_tagged_rlx(src);
                if (!__any_sync(0xffffffffu, v.y != epoch || v.w != epoch)) break;
                __nanosleep(60);
                trap_if_gt(++it, 1u << 22);
            }
            sts64(sb + dst, v.x, v.z);
            if (c == 2 - a || (a && c > 1) || c == 9) mbar_arrive(sb + (c == 9 ? BAR_CSG : (c == 2 - a ? BAR_CS1 : (c == 2 ? BAR_CSV : BAR_CSQ))));
        }
        {
            uint32_t it = 0;
            while (__any_sync(0xffffffffu, (int)(readback(g_flag + (m * 5 + 1) * 32) - epoch * 64) < 0)) {
                __nanosleep(200);
                trap_if_gt(++it, 1u << 22);
            }
#pragma unroll 1
            for (int rr = 0; rr < 2; rr++) {
                const int row = 64 * rr + 32 * a + lane;
                uint4 v[8];
                bool bad;
                do {
                    bad = false;
#pragma unroll
                    for (int i = 0; i < 8; i++) v[i] = ld_tagged_rlx(g_hstat + (1024 * m + 128 * i + row) * 2);
#pragma unroll
                    for (int i = 0; i < 8; i++) bad |= v[i].y != epoch || v[i].w != epoch;
                    trap_if_gt(++it, 1u << 22);
                } while (__any_sync(0xffffffffu, bad));
                float mean = 0.f;
#pragma unroll
                for (int i = 0; i < 8; i++) mean += __uint_as_float(v[i].x);
                mean *= 0.125f;
                float m2 = 0.f, dv = 0.f;
#pragma unroll
                for (int i = 0; i < 8; i++) { const float d = __uint_as_float(v[i].x) - mean; m2 += __uint_as_float(v[i].z); dv = fmaf(d, d, dv); }
                sts_f2(sb + OFF_CS1 + row * 8, -mean, rcp(fmaf(dv, 64.f, m2) * (1.f / DM) + 1e-5f));
            }
        }
        mbar_arrive(sb + BAR_CS3);
#pragma unroll 1
        for (int c = a; c < 3; c += 2) {
            mbar_wait(sb + BAR_STG + 8 * c, 0);
            if (elect_one()) {
                tma_store2d(&P.thh, sb + OFF_B + 4 * SLOT, 192 * j + 64 * c, 128 * m);
                asm volatile("cp.async.bulk.wait_group.read 0;" ::: "memory");
                mbar_arrive(sb + BAR_FULLB + 8 * 4);
                asm volatile("cp.async.bulk.wait_group 0;" ::: "memory");
            }
            __syncwarp();
            TL(60 + c, lane == 0);
            uint32_t ack = 0;
#pragma unroll
            for (int i = 0; i < 4; i++) ack |= readback(g_hh + (size_t)(128 * m + 32 * i + lane) * FFP + 192 * j + 64 * c);
            signal_after(g_flag + (m * 5 + 2 + c) * 32, ack, P.zero, lane == 0);
            TL(54 + c, lane == 0);
        }
        return;
    }
    const unsigned epoch = ld_relaxed(&g_epoch);
    uint32_t wraw[16];
    if (!helper) {
        const uint32_t* wp = reinterpret_cast<const uint32_t*>(P.wphi) + (4 * j) * 128 + (lane & 3) * 16 + (lane >> 2);
#pragma unroll
        for (int i = 0; i < 16; i++)
            asm volatile("ld.global.nc.u32 %0, [%1];" : "=r"(wraw[i]) : "l"(wp + (i >> 2) * 128 + ((i >> 1) & 1) * 64 + (i & 1) * 8));
    }
    asm volatile("barrier.cluster.arrive.relaxed.aligned;" ::: "memory");
    asm volatile("setmaxnreg.inc.sync.aligned.u32 216;");
    bar_sync(0, NTHREADS);
    if (helper) {
        if (warp < 4) {
            sts128(sb + OFF_B + 16 * tid, 0x3f803f80u, 0x3f803f80u, 0x3f803f80u, 0x3f803f80u);
            for (int i = tid; i < 2 * ACC_SIZE / 4; i += 128) stg128(g_acc + 2 * j * ACC_SIZE + 4 * i, 0, 0, 0, 0);
            fence_async_smem();
            fence_gpu();
            bar_sync(1, 128);
            float acc[8];
            int i = 0;
#pragma unroll 1
            for (int job = 0; job < 12; job++) {
                const int n = job < 6 ? 4 : 8;
#pragma unroll 1
                for (int t = 0; t < n; t++, i++) {
                    mbar_wait(sb + BAR_FULLA + 8 * (i & 7), (i >> 3) & 1);
                    wg_fence();
#pragma unroll
                    for (int k = 0; k < 8; k++)
                        wgmma_n8_tt(acc + (k & 4), desc_lo(sb + OFF_A) + (i & 7) * (SLOT >> 4) + 128 * k, desc_lo(sb + OFF_B), (t | (k & 3)) != 0);
                    wg_commit();
                    wg_wait<1>();
                    mbar_arrive_n_if(sb + BAR_EMPTYA + 8 * ((i + 7) & 7), 2, lane == 0 && i > 0);
                }
                wg_wait<0>();
                fence_acc<8>(acc);
                const int q = lane & 3;
                const float lo = (q & 1) ? acc[2] : acc[0], hi = (q & 1) ? acc[6] : acc[4];
                const float v = job < 6 ? lo + hi : ((q & 2) ? hi : lo);
                unsigned long long* dst = g_cs + ((2 * j + (job & 1)) * 6 + (job >> 1)) * 128 + (q >> 1) * 64 + 16 * warp + 8 * (q & 1) + (lane >> 2);
                asm volatile("st.relaxed.gpu.global.b64 [%0], %1;" ::"l"(dst), "l"(((unsigned long long)epoch << 32) | __float_as_uint(v)) : "memory");
            }
        }
        return;
    }
    {
        const int w = warp >> 2, wv = warp & 3, g = lane >> 2, q = lane & 3;
        const int row_w = 128 * m + 16 * warp;
        const uint32_t sa = sb + OFF_A + w * 8192;
        const desc_t dA = desc_lo(sa), dB = desc_lo(sb + OFF_B);
        unsigned* const flag_m = g_flag + m * 160;
        const bool l0 = lane == 0, l2 = lane < 2;
        const uint32_t eb = mapa(sb + BAR_EMPTYB, lane & 1);
        asm volatile("barrier.cluster.wait.aligned;" ::: "memory");
        Ring rg{0, 0};
        int prev = 0;

        uint32_t wb[16];
        constexpr float L2E = 1.4426950408889634f;
        const int ch = lane >> 4, sw = lane & 7;
        const uint32_t lrow = (lane & 15) * 128;
        uint32_t fp[16], fm[16];
        {
            float acc[64], accq[32];
#pragma unroll 1
            for (int kt = 0; kt < 8; kt++) {
                mbar_waitc(sb + BAR_FULLA + 8 * kt, 0);
                mbar_waitc(sb + BAR_FULLB + 8 * rg.slot, rg.phase);
                const desc_t da = dA + kt * (SLOT >> 4), db = dB + rg.slot * (SLOT >> 4);
                wg_fence();
#pragma unroll
                for (int k = 0; k < 4; k++) wgmma_n128(acc, da + 2 * k, db + 128 * k, (kt | k) != 0);
                wg_commit();
                wg_wait<1>();
                mbar_arrive_cl_if(eb + 8 * prev, l2 && kt > 0);
                prev = rg.slot; rg.adv();
            }
#pragma unroll
            for (int i = 0; i < 8; i++) {
                wb[(i >> 1) * 4 + (i & 1)] = __byte_perm(wraw[2 * i], wraw[2 * i + 1], 0x5410);
                wb[(i >> 1) * 4 + 2 + (i & 1)] = __byte_perm(wraw[2 * i], wraw[2 * i + 1], 0x7632);
            }
            float2 s0, s1;
            uint32_t a[16];
            wg_wait<0>();
            fence_acc<64>(acc);
            mbar_arrive_cl_if(eb + 8 * prev, l2);
#pragma unroll 1
            for (int it = 0; it < 2; it++) {
                mbar_waitc(sb + BAR_FULLB + 8 * 2, it ^ 1); mbar_waitc(sb + BAR_FULLB + 8 * 3, it ^ 1);
                const desc_t da = dA + it * (4 * SLOT >> 4);
                wg_fence();
#pragma unroll
                for (int k = 0; k < 16; k++) wgmma_n64(accq, da + (k >> 2) * (SLOT >> 4) + (k & 3) * 2, dB + 2 * (SLOT >> 4) + 128 * k, (it | k) != 0);
                wg_commit();
                TL(17 + it, tid == 0);
                mbar_waitc(sb + BAR_CS1 + 16 * it, 0);
                wg_wait<0>();
                fence_acc<32>(accq);
                mbar_arrive_cl_if(eb + 8 * (2 + (lane >> 1)), lane < 4);
                TL(2 + 2 * it, tid == 0);
                if (it == 0) {
                    s0 = lds_f2(sb + OFF_XST + (16 * warp + g) * 8); s1 = lds_f2(sb + OFF_XST + (16 * warp + g + 8) * 8);
#pragma unroll
                    for (int hh = 0; hh < 4; hh++)
                        ln_frag<false>(acc + 8 * hh, sb + OFF_CS1 + (64 + 16 * hh + 2 * q) * 4, 0.f, s0.y, 0.f, s1.y, a + 4 * hh);
                } else {
#pragma unroll
                    for (int hh = 0; hh < 4; hh++)
                        ln_frag<false>(accq + 8 * hh, sb + OFF_CS1 + (16 * hh + 2 * q) * 4, 0.f, s0.y, 0.f, s1.y, a + 4 * hh);
                }
                feature_maps(a, wb, s0.x * L2E, s1.x * L2E, fp, fm);
                if (it == 0) {
                    mbar_waitc(sb + BAR_FULLB + 8 * 4, 1); mbar_waitc(sb + BAR_FULLB + 8 * 5, 1);
                    mbar_waitc(sb + BAR_FULLB + 8 * 0, 0); mbar_waitc(sb + BAR_FULLB + 8 * 1, 0);
                    mbar_waitc(sb + BAR_CSV, 0);
                    const uint32_t st = sb + OFF_B + warp * 2048 + lrow;
#pragma unroll
                    for (int hh = 0; hh < 4; hh++) {
                        stsm4(st + (4 + (hh >> 1)) * SLOT + (((4 * (hh & 1) + ch) ^ sw) << 4), fp[4 * hh], fp[4 * hh + 1], fp[4 * hh + 2], fp[4 * hh + 3]);
                        stsm4(st + (4 + (hh >> 1)) * SLOT + (((4 * (hh & 1) + 2 + ch) ^ sw) << 4), fm[4 * hh], fm[4 * hh + 1], fm[4 * hh + 2], fm[4 * hh + 3]);
                        ln_frag<true>(acc + 32 + 8 * hh, sb + OFF_CS1 + (128 + 16 * hh + 2 * q) * 4, s0.x, s0.y, s1.x, s1.y, a);
                        stsm4(st + (hh >> 1) * SLOT + (((2 * (hh & 1) + ch) ^ sw) << 4), a[0], a[1], a[2], a[3]);
                    }
                    stsm4(st + ch * SLOT + ((4 ^ sw) << 4), 0x3f803f80u, 0x3f803f80u, 0x3f803f80u, 0x3f803f80u);
                    fence_async_smem();
                    bar_sync(1, 256);
                    float kvd[20];
                    wg_fence();
#pragma unroll
                    for (int k = 0; k < 8; k++)
                        wgmma_n40_tt(kvd, dB + (4 + w) * (SLOT >> 4) + 128 * k, dB + w * (SLOT >> 4) + 128 * k, k != 0);
                    wg_commit();
                    wg_wait<0>();
                    fence_acc<20>(kvd);
                    const bool h1 = wv >= 2;
                    const int f = 16 * warp + g;
                    float* kvp = acc_j + ACC_KV + f * 16 + 2 * q;
                    red_f32x2(kvp, h1 ? kvd[8] : kvd[0], h1 ? kvd[9] : kvd[1]);
                    red_f32x2(kvp + 128, h1 ? kvd[10] : kvd[2], h1 ? kvd[11] : kvd[3]);
                    red_f32x2(kvp + 8, h1 ? kvd[12] : kvd[4], h1 ? kvd[13] : kvd[5]);
                    red_f32x2(kvp + 136, h1 ? kvd[14] : kvd[6], h1 ? kvd[15] : kvd[7]);
                    red_f32_if(acc_j + ACC_Z + f + 8 * (q & 1), q ? kvd[18] : kvd[16], q < 2);
                    __syncwarp();
                    mbar_arrive_if(sb + BAR_KVW, l0);
                    mbar_arrive_cl_if(eb + 8 * ((4 + (lane >> 1)) % 6), lane < 8);
                    TL(3, tid == 0);
                }
            }
        }
        uint32_t res_lo[8], res_hi[8], ack[4];
        const uint32_t own_rows = sb + OFF_A + j * SLOT + warp * 2048;
#pragma unroll
        for (int b = 0; b < 4; b++)
            ldsm4(own_rows + lrow + (((2 * b + ch) ^ sw) << 4), res_lo[2 * b], res_hi[2 * b], res_lo[2 * b + 1], res_hi[2 * b + 1]);
        mbar_arrive_if(sb + BAR_EMPTYA + 8 * lane, lane < 8 && lane != j && lane != KVS(j));
        TL(5, tid == 0);
        mbar_waitc(sb + BAR_KVR, 0);
        TL(6, tid == 0);
        {
            const uint32_t kvs = sb + OFF_A + KVS(j) * SLOT;
            uint32_t o_lo[8], o_hi[8];
#pragma unroll
            for (int hh = 0; hh < 4; hh++) {
                uint32_t b[8], zb[4];
                const uint32_t base = kvs + hh * 32 * 48;
                ldsm4t(base + (lane & 15) * 48 + (lane >> 4) * 16, b[0], b[1], b[2], b[3]);
                ldsm4t(base + (16 + (lane & 15)) * 48 + (lane >> 4) * 16, b[4], b[5], b[6], b[7]);
                ldsm4t(base + lane * 48 + 32, zb[0], zb[1], zb[2], zb[3]);
                float n0[4], n1[4], dn[4];
                mma16816_z(n0, fp + 4 * hh, b[0], b[1]); mma16816_z(n1, fp + 4 * hh, b[2], b[3]); mma16816_z(dn, fp + 4 * hh, zb[0], zb[1]);
                mma16816(n0, fm + 4 * hh, b[4], b[5]); mma16816(n1, fm + 4 * hh, b[6], b[7]); mma16816(dn, fm + 4 * hh, zb[2], zb[3]);
                const float i0 = rcp(dn[0] + 1e-6f), i1 = rcp(dn[2] + 1e-6f);
                o_lo[2 * hh] = pack_bf16(n0[0] * i0, n0[1] * i0); o_hi[2 * hh] = pack_bf16(n0[2] * i1, n0[3] * i1);
                o_lo[2 * hh + 1] = pack_bf16(n1[0] * i0, n1[1] * i0); o_hi[2 * hh + 1] = pack_bf16(n1[2] * i1, n1[3] * i1);
            }
            __syncwarp();
            mbar_arrive_if(sb + BAR_EMPTYA + 8 * KVS(j), l0);
            rg.slot = 4; rg.phase = 0;
            store_tile(own_rows, g_o + (size_t)row_w * DM + 64 * j, o_lo, o_hi, lane, ack);
            TL(7, tid == 0);
        }
        {
            float acc[32];
#pragma unroll
            for (int t = 0; t < 8; t++) {
                acc[4 * t] = bf_lo(res_lo[t]); acc[4 * t + 1] = bf_hi(res_lo[t]);
                acc[4 * t + 2] = bf_lo(res_hi[t]); acc[4 * t + 3] = bf_hi(res_hi[t]);
            }
            fence_acc<32>(acc);
            int pa = 0;
#pragma unroll 1
            for (int kp = 0; kp < 4; kp++) {
                mbar_waitc(sb + BAR_FULLB + 8 * rg.slot, rg.phase);
#pragma unroll
                for (int hf = 0; hf < 2; hf++) {
                    const int i = 2 * kp + hf, kt = KORD(i, j);
                    mbar_waitc(sb + BAR_FULLA + 8 * kt, i != 0);
                    TL(8, i == 1 && tid == 0);
                    const desc_t da = dA + kt * (SLOT >> 4), db = dB + rg.slot * (SLOT >> 4);
                    wg_fence();
#pragma unroll
                    for (int k = 0; k < 4; k++) wgmma_n64(acc, da + 2 * k, db + (hf * 4 + k) * 128, 1);
                    wg_commit();
                    wg_wait<1>();
                    mbar_arrive_if(sb + BAR_EMPTYA + 8 * pa, l0 && i > 1);
                    if (hf == 0) {
                        mbar_arrive_cl_if(eb + 8 * prev, l2 && i > 0);
                        if (i == 0) { signal_late(flag_m, ack, P.zero, l0); TL(20, tid == 0); }
                    }
                    pa = kt;
                }
                prev = rg.slot; rg.adv();
            }
            wg_wait<0>();
            fence_acc<32>(acc);
            mbar_arrive_if(sb + BAR_EMPTYA + 8 * pa, l0);
            mbar_arrive_cl_if(eb + 8 * prev, l2);
            TL(9, tid == 0);
            float s0 = 0.f, s1 = 0.f;
#pragma unroll
            for (int t = 0; t < 8; t++) {
                res_lo[t] = pack_bf16(acc[4 * t], acc[4 * t + 1]);
                res_hi[t] = pack_bf16(acc[4 * t + 2], acc[4 * t + 3]);
                s0 += acc[4 * t] + acc[4 * t + 1];
                s1 += acc[4 * t + 2] + acc[4 * t + 3];
            }
            store_tile(own_rows, g_h + (size_t)row_w * DM + 64 * j, res_lo, res_hi, lane, ack);
            s0 += __shfl_xor_sync(0xffffffffu, s0, 1); s1 += __shfl_xor_sync(0xffffffffu, s1, 1);
            s0 += __shfl_xor_sync(0xffffffffu, s0, 2); s1 += __shfl_xor_sync(0xffffffffu, s1, 2);
            const float mu0 = s0 * (1.f / 64), mu1 = s1 * (1.f / 64);
            float q0 = 0.f, q1 = 0.f;
#pragma unroll
            for (int t = 0; t < 8; t++) {
                float d;
                d = acc[4 * t] - mu0; q0 = fmaf(d, d, q0);
                d = acc[4 * t + 1] - mu0; q0 = fmaf(d, d, q0);
                d = acc[4 * t + 2] - mu1; q1 = fmaf(d, d, q1);
                d = acc[4 * t + 3] - mu1; q1 = fmaf(d, d, q1);
            }
            q0 += __shfl_xor_sync(0xffffffffu, q0, 1); q1 += __shfl_xor_sync(0xffffffffu, q1, 1);
            q0 += __shfl_xor_sync(0xffffffffu, q0, 2); q1 += __shfl_xor_sync(0xffffffffu, q1, 2);
            st_tagged_if(g_hstat + (role * 128 + 16 * warp + g + 8 * (q & 1)) * 2, q ? mu1 : mu0, q ? q1 : q0, epoch, q < 2);
            TL(10, tid == 0);
        }
        float acc0[64], acc1[64], acc2[56], nm0, nm1;
        float4 cs[8];
        uint32_t hr[16];
#define P3_GROUP(MMA, ACC, KT)                                                                              \
        mbar_waitc(sb + BAR_FULLB + 8 * rg.slot, rg.phase);                                                 \
        {                                                                                                   \
            const desc_t da = dA + (KT) * (SLOT >> 4), db = dB + rg.slot * (SLOT >> 4);                     \
            wg_fence();                                                                                     \
            _Pragma("unroll") for (int k = 0; k < 4; k++) MMA(ACC, da + 2 * k, db + 128 * k, (i | k) != 0); \
            wg_commit();                                                                                    \
        }
#define P3_CS(C, NT)    \
        _Pragma("unroll") for (int t = 0; t < (NT); t++) lds_f4_if(cs[t], sb + OFF_CS3 + q * 16 + 512 * (C) + 64 * t, i == t);
#define P3_EPI(C, ACC, N, NTP)                                                                              \
        fence_acc<N>(ACC);                                                                                  \
        TL(11 + (C), tid == 0);                                                                             \
        hh_stage<NTP>(ACC, cs, nm0, nm1, sb + OFF_B + 4 * SLOT + warp * 2048, lane);                        \
        mbar_arrive_if(sb + BAR_STG + 8 * (C), l0);                                                         \
        TL(50 + (C), tid == 0);
        const uint32_t blk = ((lane & 7) + (lane >> 4) * 8) * 128 + (((2 * wv + ((lane >> 3) & 1)) ^ (lane & 7)) << 4);
#pragma unroll 1
        for (int i = 0; i < 8; i++) {
            const int kt = KORD(i, j);
            mbar_waitc(sb + BAR_FULLA + 8 * kt, 0);
            TL(44, tid == 0 && i == 1);
            P3_GROUP(wgmma_n128, acc0, kt)
            if (i == 7) {
                mbar_waitc(sb + BAR_CS3, 0);
                nm0 = lds_f2(sb + OFF_CS1 + (16 * warp + g) * 8).x; nm1 = lds_f2(sb + OFF_CS1 + (16 * warp + g + 8) * 8).x;
            }
            wg_wait<1>();
            mbar_arrive_cl_if(eb + 8 * prev, l2 && i > 0);
            if (i == 0) {
                signal_late(flag_m + 32, ack, P.zero, l0);
                TL(21, tid == 0);
                bar_sync(2 + w, 128);
#pragma unroll
                for (int tp = 0; tp < 4; tp++) ldsm4t(sa + j * SLOT + blk + tp * 2048, hr[4 * tp], hr[4 * tp + 1], hr[4 * tp + 2], hr[4 * tp + 3]);
                mbar_waitc(sb + BAR_CSG, 0);
#pragma unroll
                for (int t = 0; t < 8; t++) cs[t] = lds_f4(sb + OFF_CS3 + q * 16 + 64 * t);
            }
            prev = rg.slot; rg.adv5();
        }
#pragma unroll 1
        for (int i = 0; i < 8; i++) {
            P3_GROUP(wgmma_n128, acc1, i)
            wg_wait<1>();
            mbar_arrive_cl_if(eb + 8 * prev, l2);
            if (i == 0) { P3_EPI(0, acc0, 64, 4) }
            P3_CS(1, 8)
            prev = rg.slot; rg.adv5();
        }
#pragma unroll 1
        for (int i = 0; i < 8; i++) {
            P3_GROUP(wgmma_n112, acc2, i)
            wg_wait<1>();
            mbar_arrive_cl_if(eb + 8 * prev, l2);
            mbar_arrive_if(sb + BAR_EMPTYA + 8 * ((i + 7) & 7), l0 && i > 0);
            if (i == 0) { mbar_waitc(sb + BAR_FULLB + 8 * 4, 1); P3_EPI(1, acc1, 64, 4) }
            P3_CS(2, 6)
            prev = rg.slot; rg.adv5();
        }
        {
            float acc[64];
            const desc_t dA0 = desc_lo(sb + OFF_A);
#define KT_P4(I, NK)                                                                                        \
        const int s_ = (2 * (I) + w) & 7;                                                                   \
        mbar_waitc(sb + BAR_FULLB + 8 * rg.slot, rg.phase);                                                 \
        mbar_waitc(sb + BAR_FULLA + 8 * s_, (((I) >> 2) + 1) & 1);                                          \
        TL(30 + (I), tid == 0);                                                                             \
        const desc_t dh_ = dA0 + s_ * (SLOT >> 4), dw_ = dB + rg.slot * (SLOT >> 4) + w * 512;              \
        wg_fence();                                                                                         \
        _Pragma("unroll") for (int k = 0; k < (NK); k++) wgmma_n128_tn(acc, dw_ + 128 * k, dh_ + 2 * k, ((I) | k) != 0); \
        wg_commit();                                                                                        \
        wg_wait<1>();
#pragma unroll 1
            for (int i = 0; i < 8; i++) {
                KT_P4(i, 4)
                mbar_arrive_n_if(sb + BAR_EMPTYA + 8 * (i ? (s_ + 6) & 7 : 7), i ? 2 : 1, l0);
                mbar_arrive_cl_if(eb + 8 * prev, l2);
                if (i == 0) { mbar_waitc(sb + BAR_FULLB + 8 * 4, 0); P3_EPI(2, acc2, 56, 3) }
#pragma unroll
                for (int t = 0; t < 8; t++) lds_f4_if(cs[t], sb + OFF_CS1 + (64 * w + 8 * t + 2 * q) * 8, i == t);
                prev = rg.slot; rg.adv5();
            }
#pragma unroll 1
            for (int i = 8; i < 12; i++) {
                KT_P4(i, 3)
                mbar_arrive_n_if(sb + BAR_EMPTYA + 8 * ((s_ + 6) & 7), 2, l0);
                rg.adv5();
            }
            wg_wait<0>();
            fence_acc<64>(acc);
            TL(15, tid == 0);
            const uint32_t xch = sb + OFF_A + 2 * SLOT + (tid & 127) * 16;
            if (w) {
#pragma unroll
                for (int t = 0; t < 8; t++) {
                    sts128(xch + SLOT + t * 2048, __float_as_uint(acc[4 * t]), __float_as_uint(acc[4 * t + 1]),
                           __float_as_uint(acc[4 * t + 2]), __float_as_uint(acc[4 * t + 3]));
                }
#pragma unroll
                for (int t = 0; t < 32; t++) acc[t] = acc[32 + t];
            } else {
#pragma unroll
                for (int t = 0; t < 8; t++)
                    sts128(xch + t * 2048, __float_as_uint(acc[32 + 4 * t]), __float_as_uint(acc[33 + 4 * t]),
                           __float_as_uint(acc[34 + 4 * t]), __float_as_uint(acc[35 + 4 * t]));
            }
            bar_sync(1, 256);
            float4 o[8];
#pragma unroll
            for (int t = 0; t < 8; t++) o[t] = lds_f4(xch + (w ^ 1) * SLOT + t * 2048);
            const uint32_t tile = sb + OFF_A + w * SLOT;
#pragma unroll
            for (int t = 0; t < 8; t++) {
                hr[2 * t] = pack_bf16(fmaf(acc[4 * t] + o[t].x, cs[t].y, bf_lo(hr[2 * t])), fmaf(acc[4 * t + 1] + o[t].y, cs[t].w, bf_hi(hr[2 * t])));
                hr[2 * t + 1] = pack_bf16(fmaf(acc[4 * t + 2] + o[t].z, cs[t].y, bf_lo(hr[2 * t + 1])), fmaf(acc[4 * t + 3] + o[t].w, cs[t].w, bf_hi(hr[2 * t + 1])));
            }
#pragma unroll
            for (int tp = 0; tp < 4; tp++) stsm4t(tile + blk + tp * 2048, hr[4 * tp], hr[4 * tp + 1], hr[4 * tp + 2], hr[4 * tp + 3]);
            fence_async_smem();
            bar_sync(2 + w, 128);
            if ((tid & 127) == 0) {
                tma_store2d(&P.tout, tile, 64 * j, 128 * m + 64 * w);
                asm volatile("cp.async.bulk.wait_group.read 0;" ::: "memory");
            }
            if (tid == 0 && role == 0) g_epoch = epoch + 1;
            TL(16, tid == 0); TLG(1, tid == 0);
        }
    }
}

__global__ void probe_kernel() {}

typedef CUresult (*EncodeFn)(CUtensorMap*, CUtensorMapDataType, cuuint32_t, void*, const cuuint64_t*, const cuuint64_t*,
                             const cuuint32_t*, const cuuint32_t*, CUtensorMapInterleave, CUtensorMapSwizzle,
                             CUtensorMapL2promotion, CUtensorMapFloatOOBfill);

static void make_map2d(EncodeFn enc, CUtensorMap* tm, const void* base, uint64_t cols, uint64_t rows, uint64_t pitch_elems,
                       uint32_t box_rows) {
    cuuint64_t gd[2] = {cols, rows};
    cuuint64_t gs[1] = {pitch_elems * 2};
    cuuint32_t bd[2] = {64, box_rows};
    cuuint32_t es[2] = {1, 1};
    enc(tm, CU_TENSOR_MAP_DATA_TYPE_BFLOAT16, 2, const_cast<void*>(base), gd, gs, bd, es, CU_TENSOR_MAP_INTERLEAVE_NONE,
        CU_TENSOR_MAP_SWIZZLE_128B, CU_TENSOR_MAP_L2_PROMOTION_L2_256B, CU_TENSOR_MAP_FLOAT_OOB_FILL_NONE);
}

}

extern "C" void kernel_launch(void* const* d_in, const int* in_sizes, int n_in, void* d_out, int out_size) {
    using namespace hk;
    (void)in_sizes; (void)n_in; (void)out_size;
    static EncodeFn enc = nullptr;
    static void *po = nullptr, *ph = nullptr, *phh = nullptr;
    static int std_layout = 0;
    if (!enc) {
        void* fn = nullptr;
        cudaDriverEntryPointQueryResult qr;
        cudaGetDriverEntryPoint("cuTensorMapEncodeTiled", &fn, cudaEnableDefault, &qr);
        enc = (EncodeFn)fn;
        cudaGetSymbolAddress(&po, g_o);
        cudaGetSymbolAddress(&ph, g_h);
        cudaGetSymbolAddress(&phh, g_hh);
        cudaFuncSetAttribute(fused_kernel, cudaFuncAttributeMaxDynamicSharedMemorySize, SMEM_BYTES);
        int dev = 0, sms = 0;
        cudaGetDevice(&dev);
        cudaDeviceGetAttribute(&sms, cudaDevAttrMultiProcessorCount, dev);
        cudaFuncSetAttribute(probe_kernel, cudaFuncAttributeNonPortableClusterSizeAllowed, 1);
        cudaFuncSetAttribute(probe_kernel, cudaFuncAttributeMaxDynamicSharedMemorySize, SMEM_BYTES);
        const int sizes[3] = {8, 9, 16}, want[3] = {15, 9, 7};
        bool ok = sms == NCTA;
        for (int i = 0; i < 3 && ok; i++) {
            cudaLaunchConfig_t cfg = {};
            cfg.gridDim = dim3(sizes[i] * 8); cfg.blockDim = dim3(NTHREADS); cfg.dynamicSmemBytes = SMEM_BYTES;
            cudaLaunchAttribute at;
            at.id = cudaLaunchAttributeClusterDimension;
            at.val.clusterDim.x = sizes[i]; at.val.clusterDim.y = 1; at.val.clusterDim.z = 1;
            cfg.attrs = &at; cfg.numAttrs = 1;
            int n = 0;
            ok = cudaOccupancyMaxActiveClusters(&n, probe_kernel, &cfg) == cudaSuccess && n == want[i];
        }
        (void)cudaGetLastError();
        std_layout = ok ? 1 : 0;
    }
    Params P;
    const __nv_bfloat16* x = (const __nv_bfloat16*)d_in[0];
    P.x = x;
    P.wqkv = (const __nv_bfloat16*)d_in[1];
    P.wphi = (const __nv_bfloat16*)d_in[2];
    P.wo = (const __nv_bfloat16*)d_in[3];
    P.wg = (const __nv_bfloat16*)d_in[5];
    P.wu = (const __nv_bfloat16*)d_in[6];
    P.wd = (const __nv_bfloat16*)d_in[7];
    P.out = (__nv_bfloat16*)d_out;
    P.zero = 0;
    for (int i = 0; i < NCTA; i++) {
        const int odd = i & 1;
        int role = i < 4 ? 128 + i : (((i - 4) >> 4) * 2 + odd) * 8 + (((i - 4) >> 1) & 7);
        if (std_layout) {
            const int tpc = i < 8 ? 62 + (i >> 1) : (i - 8) >> 1;
            if (tpc < 32) role = (tpc & 7) ? (2 * ((tpc & 7) - 1) + odd) * 8 + (tpc >> 3) : (14 + odd) * 8 + (tpc >> 3);
            else if (tpc < 60) role = (2 * ((tpc - 32) % 7) + odd) * 8 + 4 + (tpc - 32) / 7;
            else if (tpc < 62) role = 128 + (tpc - 60) * 2 + odd;
            else role = (14 + odd) * 8 + 4 + (tpc - 62);
        }
        P.role[i] = (unsigned char)role;
    }
    make_map2d(enc, &P.tx, x, DM, SEQ, DM, 128);
    make_map2d(enc, &P.to, po, DM, SEQ, DM, 128);
    make_map2d(enc, &P.th, ph, DM, SEQ, DM, 128);
    make_map2d(enc, &P.thh, phh, FFP, SEQ, FFP, 128);
    make_map2d(enc, &P.twq, P.wqkv, 3 * DM, DM, 3 * DM, 64);
    make_map2d(enc, &P.two, P.wo, DM, DM, DM, 64);
    make_map2d(enc, &P.twg, P.wg, FF, DM, FF, 64);
    make_map2d(enc, &P.twu, P.wu, FF, DM, FF, 64);
    make_map2d(enc, &P.twd, P.wd, DM, FF, DM, 64);
    make_map2d(enc, &P.tout, d_out, DM, SEQ, DM, 64);
    fused_kernel<<<NCTA, NTHREADS, SMEM_BYTES>>>(P);
}
```

```cpp
#include <cuda_runtime.h>
#include <cuda_bf16.h>
#include <cuda.h>
#include <stdint.h>

namespace hk {

constexpr int SEQ = 2048, DM = 512, FF = 1376;
constexpr int NCTA = 132;
constexpr int NTHREADS = 384;
constexpr uint32_t SLOT = 16384;
constexpr uint32_t OFF_A = 0, OFF_B = 8 * SLOT, OFF_MISC = 14 * SLOT;
constexpr uint32_t BAR_FULLA = OFF_MISC + 0, BAR_EMPTYA = OFF_MISC + 64, BAR_FULLB = OFF_MISC + 128,
                   BAR_EMPTYB = OFF_MISC + 176, BAR_CS1 = OFF_MISC + 224, BAR_CS3 = OFF_MISC + 232,
                   BAR_CSQ = OFF_MISC + 240, BAR_CSV = OFF_MISC + 248,
                   BAR_STG = OFF_MISC + 256,
                   BAR_KVW = OFF_MISC + 280, BAR_KVR = OFF_MISC + 288, BAR_CSG = OFF_MISC + 296;
constexpr uint32_t OFF_CS1 = OFF_MISC + 384;
constexpr uint32_t OFF_CS3 = OFF_CS1 + 1024;
constexpr uint32_t OFF_XST = OFF_CS3;
constexpr uint32_t SMEM_BYTES = OFF_CS3 + 1536;
#define KVS(j) ((j) == 3 ? 2 : 3)
#define KORD(i, j) ((i) == 0 ? (j) : (i) - ((i) <= (j)))
constexpr int NB = 6;
#define PF_DELAY 2
constexpr int AHEAD = 3;

constexpr int ACC_KV = 0, ACC_Z = 2048, ACC_SIZE = 2176;

__device__ __align__(1024) uint4 g_act[5 * 128 * 1024];
__device__ __align__(128) unsigned long long g_hstat[SEQ * 16];
__device__ __align__(128) unsigned long long g_xstat[SEQ * 2];
__device__ __align__(128) float g_acc[8 * ACC_SIZE];
__device__ __align__(128) unsigned g_cnt[8 * 32];
__device__ __align__(128) unsigned long long g_cs[8 * 6 * 128];
__device__ __align__(128) unsigned g_flag[16 * 5 * 32 + 32];
__device__ unsigned g_epoch = 1;

#define TL(i, pred) do {} while (0)
#define TLG(i, pred) do {} while (0)

struct Params {
    CUtensorMap tx, twq, two, twg, twu, twd, tout;
    const __nv_bfloat16 *x, *wqkv, *wphi, *wo, *wg, *wu, *wd;
    __nv_bfloat16* out;
    unsigned zero;
    unsigned char role[NCTA];
};

__device__ __forceinline__ uint32_t smem_u32(const void* p) { return (uint32_t)__cvta_generic_to_shared(p); }
__device__ __forceinline__ void mbar_init(uint32_t bar, uint32_t cnt) {
    asm volatile("mbarrier.init.shared::cta.b64 [%0], %1;" ::"r"(bar), "r"(cnt) : "memory");
}
__device__ __forceinline__ void mbar_expect_tx(uint32_t bar, uint32_t bytes) {
    asm volatile("mbarrier.arrive.expect_tx.shared::cta.b64 _, [%0], %1;" ::"r"(bar), "r"(bytes) : "memory");
}
__device__ __forceinline__ void mbar_arrive(uint32_t bar) {
    asm volatile("mbarrier.arrive.shared::cta.b64 _, [%0];" ::"r"(bar) : "memory");
}
__device__ __forceinline__ void mbar_arrive_if(uint32_t bar, bool pred) {
    asm volatile("{.reg .pred p; setp.ne.u32 p, %1, 0; @p mbarrier.arrive.shared::cta.b64 _, [%0];}" ::"r"(bar), "r"((uint32_t)pred) : "memory");
}
__device__ __forceinline__ bool mbar_try(uint32_t bar, uint32_t parity) {
    uint32_t ok;
    asm volatile("{.reg .pred p; mbarrier.try_wait.parity.shared::cta.b64 p, [%1], %2; selp.u32 %0,1,0,p;}"
                 : "=r"(ok) : "r"(bar), "r"(parity) : "memory");
    return ok;
}
__device__ __forceinline__ bool mbar_test(uint32_t bar, uint32_t parity) {
    uint32_t ok;
    asm volatile("{.reg .pred p; mbarrier.test_wait.parity.shared::cta.b64 p, [%1], %2; selp.u32 %0,1,0,p;}"
                 : "=r"(ok) : "r"(bar), "r"(parity) : "memory");
    return ok;
}
__device__ __forceinline__ void trap_if_gt(uint32_t v, uint32_t lim) {
    asm volatile("{.reg .pred p; setp.gt.u32 p, %0, %1; @p trap;}" ::"r"(v), "r"(lim));
}
__device__ __forceinline__ void mbar_wait(uint32_t bar, uint32_t parity) {
    asm volatile("{\n"
                 ".reg .pred P1, P2;\n"
                 ".reg .u32 c;\n"
                 "mov.u32 c, 0;\n"
                 "LAB_WAIT:\n"
                 "mbarrier.try_wait.parity.shared::cta.b64 P1, [%0], %1;\n"
                 "@P1 bra LAB_DONE;\n"
                 "add.u32 c, c, 1;\n"
                 "setp.gt.u32 P2, c, 4194304;\n"
                 "@P2 trap;\n"
                 "bra LAB_WAIT;\n"
                 "LAB_DONE:\n"
                 "}" ::"r"(bar), "r"(parity) : "memory");
}
__device__ __forceinline__ void mbar_waitc(uint32_t bar, uint32_t parity) {
    asm volatile("{\n"
                 ".reg .pred P1;\n"
                 "LAB_WAIT:\n"
                 "mbarrier.try_wait.parity.shared::cta.b64 P1, [%0], %1;\n"
                 "@!P1 bra LAB_WAIT;\n"
                 "}" ::"r"(bar), "r"(parity) : "memory");
}
__device__ __forceinline__ void tma2d(uint32_t dst, const CUtensorMap* tm, uint32_t bar, int c0, int c1) {
    asm volatile("cp.async.bulk.tensor.2d.shared::cluster.global.mbarrier::complete_tx::bytes [%0], [%1, {%3, %4}], [%2];"
                 ::"r"(dst), "l"(tm), "r"(bar), "r"(c0), "r"(c1) : "memory");
}
__device__ __forceinline__ void tma2d_mc(uint32_t dst, const CUtensorMap* tm, uint32_t bar, int c0, int c1) {
    asm volatile("cp.async.bulk.tensor.2d.shared::cluster.global.mbarrier::complete_tx::bytes.multicast::cluster [%0], [%1, {%3, %4}], [%2], %5;"
                 ::"r"(dst), "l"(tm), "r"(bar), "r"(c0), "r"(c1), "h"((uint16_t)3) : "memory");
}
__device__ __forceinline__ uint32_t mapa(uint32_t addr, uint32_t rank) {
    uint32_t r; asm("mapa.shared::cluster.u32 %0, %1, %2;" : "=r"(r) : "r"(addr), "r"(rank)); return r;
}
__device__ __forceinline__ void mbar_arrive_cl_if(uint32_t cbar, bool pred) {
    asm volatile("{.reg .pred p; setp.ne.u32 p, %1, 0; @p mbarrier.arrive.shared::cluster.b64 _, [%0];}" ::"r"(cbar), "r"((uint32_t)pred) : "memory");
}
__device__ __forceinline__ bool elect_one() {
    uint32_t ok;
    asm volatile("{.reg .pred p; elect.sync _|p, 0xffffffff; selp.u32 %0, 1, 0, p;}" : "=r"(ok));
    return ok;
}
__device__ __forceinline__ void prefetch_tmap(const CUtensorMap* tm) {
    asm volatile("prefetch.tensormap [%0];" ::"l"(tm) : "memory");
}
__device__ __forceinline__ void prefetch_l2(const void* p, uint32_t bytes) {
    asm volatile("cp.async.bulk.prefetch.L2.global [%0], %1;" ::"l"(p), "r"(bytes) : "memory");
}
__device__ __forceinline__ unsigned ld_acquire(const unsigned* p) {
    unsigned v; asm volatile("ld.acquire.gpu.global.u32 %0, [%1];" : "=r"(v) : "l"(p) : "memory"); return v;
}
__device__ __forceinline__ uint4 ld_acquire4(const unsigned* p) {
    uint4 v;
    asm volatile("ld.acquire.gpu.global.v4.u32 {%0,%1,%2,%3}, [%4];" : "=r"(v.x), "=r"(v.y), "=r"(v.z), "=r"(v.w) : "l"(p) : "memory");
    return v;
}
__device__ __forceinline__ unsigned ld_relaxed(const unsigned* p) {
    unsigned v; asm volatile("ld.relaxed.gpu.global.u32 %0, [%1];" : "=r"(v) : "l"(p)); return v;
}
__device__ __forceinline__ void st_relaxed(unsigned* p, unsigned v) {
    asm volatile("st.relaxed.gpu.global.u32 [%0], %1;" ::"l"(p), "r"(v) : "memory");
}
__device__ __forceinline__ void red_relaxed(unsigned* p, unsigned v) {
    asm volatile("red.relaxed.gpu.global.add.u32 [%0], %1;" ::"l"(p), "r"(v) : "memory");
}
__device__ __forceinline__ void fence_gpu() { asm volatile("fence.acq_rel.gpu;" ::: "memory"); }
__device__ __forceinline__ void fence_async_smem() { asm volatile("fence.proxy.async.shared::cta;" ::: "memory"); }
__device__ __forceinline__ void fence_async_global() { asm volatile("fence.proxy.async.global;" ::: "memory"); }
__device__ __forceinline__ uint32_t readback(const void* p) {
    uint32_t v; asm volatile("ld.relaxed.gpu.global.u32 %0, [%1];" : "=r"(v) : "l"(p) : "memory"); return v;
}
__device__ __forceinline__ void wait_count(const unsigned* p, unsigned target) {
    uint32_t it = 0;
    while ((int)(readback(p) - target) < 0) trap_if_gt(++it, 1u << 22);
}
__device__ __forceinline__ void wait_count_warp(const unsigned* p, unsigned target) {
    uint32_t it = 0;
    while (__any_sync(0xffffffffu, (int)(readback(p) - target) < 0)) trap_if_gt(++it, 1u << 22);
}
__device__ __forceinline__ void red_f32(float* p, float a) {
    asm volatile("red.relaxed.gpu.global.add.f32 [%0], %1;" ::"l"(p), "f"(a) : "memory");
}
__device__ __forceinline__ void red_f32x2(float* p, float a, float b) {
    asm volatile("red.relaxed.gpu.global.add.v2.f32 [%0], {%1, %2};" ::"l"(p), "f"(a), "f"(b) : "memory");
}
__device__ __forceinline__ void red_f32x4(float* p, float a, float b, float c, float d) {
    asm volatile("red.relaxed.gpu.global.add.v4.f32 [%0], {%1, %2, %3, %4};" ::"l"(p), "f"(a), "f"(b), "f"(c), "f"(d) : "memory");
}
__device__ __forceinline__ float4 ld_l2_f4(const float* p) {
    float4 v;
    asm volatile("ld.relaxed.gpu.global.v4.f32 {%0,%1,%2,%3}, [%4];" : "=f"(v.x), "=f"(v.y), "=f"(v.z), "=f"(v.w) : "l"(p) : "memory");
    return v;
}
__device__ __forceinline__ float2 ld_l2_f2(const float* p) {
    float2 v;
    asm volatile("ld.relaxed.gpu.global.v2.f32 {%0,%1}, [%2];" : "=f"(v.x), "=f"(v.y) : "l"(p) : "memory");
    return v;
}
__device__ __forceinline__ float ld_l2_f(const float* p) {
    float v;
    asm volatile("ld.relaxed.gpu.global.f32 %0, [%1];" : "=f"(v) : "l"(p) : "memory");
    return v;
}
__device__ __forceinline__ uint4 ldg_nc(const void* p) {
    uint4 v;
    asm volatile("ld.global.nc.L1::no_allocate.v4.u32 {%0,%1,%2,%3}, [%4];" : "=r"(v.x), "=r"(v.y), "=r"(v.z), "=r"(v.w) : "l"(p));
    return v;
}
__device__ __forceinline__ void stg128(void* p, uint32_t a, uint32_t b, uint32_t c, uint32_t d) {
    asm volatile("st.global.v4.u32 [%0], {%1,%2,%3,%4};" ::"l"(p), "r"(a), "r"(b), "r"(c), "r"(d) : "memory");
}
__device__ __forceinline__ uint4 lds128(uint32_t a) {
    uint4 v;
    asm volatile("ld.shared.v4.u32 {%0,%1,%2,%3}, [%4];" : "=r"(v.x), "=r"(v.y), "=r"(v.z), "=r"(v.w) : "r"(a) : "memory");
    return v;
}
__device__ __forceinline__ float2 lds_f2(uint32_t a) {
    float2 v;
    asm volatile("ld.shared.v2.f32 {%0,%1}, [%2];" : "=f"(v.x), "=f"(v.y) : "r"(a) : "memory");
    return v;
}
__device__ __forceinline__ void sts_f2(uint32_t a, float x, float y) {
    asm volatile("st.shared.v2.f32 [%0], {%1,%2};" ::"r"(a), "f"(x), "f"(y) : "memory");
}
__device__ __forceinline__ void sts64(uint32_t a, uint32_t x, uint32_t y) {
    asm volatile("st.shared.v2.u32 [%0], {%1,%2};" ::"r"(a), "r"(x), "r"(y) : "memory");
}
__device__ __forceinline__ void sts128(uint32_t a, uint32_t x, uint32_t y, uint32_t z, uint32_t w) {
    asm volatile("st.shared.v4.u32 [%0], {%1,%2,%3,%4};" ::"r"(a), "r"(x), "r"(y), "r"(z), "r"(w) : "memory");
}
__device__ __forceinline__ void stsm4(uint32_t a, uint32_t r0, uint32_t r1, uint32_t r2, uint32_t r3) {
    asm volatile("stmatrix.sync.aligned.m8n8.x4.shared.b16 [%0], {%1,%2,%3,%4};" ::"r"(a), "r"(r0), "r"(r1), "r"(r2), "r"(r3) : "memory");
}
__device__ __forceinline__ void stsm4t(uint32_t a, uint32_t r0, uint32_t r1, uint32_t r2, uint32_t r3) {
    asm volatile("stmatrix.sync.aligned.m8n8.x4.trans.shared.b16 [%0], {%1,%2,%3,%4};" ::"r"(a), "r"(r0), "r"(r1), "r"(r2), "r"(r3) : "memory");
}
__device__ __forceinline__ void tma_store2d(const CUtensorMap* tm, uint32_t src, int c0, int c1) {
    asm volatile("cp.async.bulk.tensor.2d.global.shared::cta.bulk_group [%0, {%2, %3}], [%1];" ::"l"(tm), "r"(src), "r"(c0), "r"(c1) : "memory");
    asm volatile("cp.async.bulk.commit_group;" ::: "memory");
}
__device__ __forceinline__ void ldsm4(uint32_t a, uint32_t& r0, uint32_t& r1, uint32_t& r2, uint32_t& r3) {
    asm volatile("ldmatrix.sync.aligned.m8n8.x4.shared.b16 {%0,%1,%2,%3}, [%4];" : "=r"(r0), "=r"(r1), "=r"(r2), "=r"(r3) : "r"(a) : "memory");
}
__device__ __forceinline__ void ldsm4t(uint32_t a, uint32_t& r0, uint32_t& r1, uint32_t& r2, uint32_t& r3) {
    asm volatile("ldmatrix.sync.aligned.m8n8.x4.trans.shared.b16 {%0,%1,%2,%3}, [%4];" : "=r"(r0), "=r"(r1), "=r"(r2), "=r"(r3) : "r"(a) : "memory");
}
__device__ __forceinline__ void mma16816(float* c, const uint32_t* a, uint32_t b0, uint32_t b1) {
    asm("mma.sync.aligned.m16n8k16.row.col.f32.bf16.bf16.f32 {%0,%1,%2,%3}, {%4,%5,%6,%7}, {%8,%9}, {%0,%1,%2,%3};"
                 : "+f"(c[0]), "+f"(c[1]), "+f"(c[2]), "+f"(c[3])
                 : "r"(a[0]), "r"(a[1]), "r"(a[2]), "r"(a[3]), "r"(b0), "r"(b1));
}
__device__ __forceinline__ uint32_t pack_bf16(float lo, float hi) {
    uint32_t r; asm("cvt.rn.bf16x2.f32 %0, %1, %2;" : "=r"(r) : "f"(hi), "f"(lo)); return r;
}
__device__ __forceinline__ float bf_lo(uint32_t w) { return __uint_as_float(w << 16); }
__device__ __forceinline__ float bf_hi(uint32_t w) { return __uint_as_float(w & 0xffff0000u); }
__device__ __forceinline__ float ex2(float x) { float r; asm("ex2.approx.ftz.f32 %0, %1;" : "=f"(r) : "f"(x)); return r; }
__device__ __forceinline__ float rcp(float x) { float r; asm("rcp.approx.ftz.f32 %0, %1;" : "=f"(r) : "f"(x)); return r; }
__device__ __forceinline__ void bar_sync(int id, int n) { asm volatile("bar.sync %0, %1;" ::"r"(id), "r"(n) : "memory"); }

typedef unsigned long long desc_t;
__device__ __forceinline__ desc_t desc_lo(uint32_t addr) { return (desc_t)(((addr & 0x3FFFF) >> 4) | (512u << 16)) | (0x40000040ull << 32); }
__device__ __forceinline__ void wg_fence() { asm volatile("wgmma.fence.sync.aligned;" ::: "memory"); }
__device__ __forceinline__ void wg_commit() { asm volatile("wgmma.commit_group.sync.aligned;" ::: "memory"); }
template <int N> __device__ __forceinline__ void wg_wait() { asm volatile("wgmma.wait_group.sync.aligned %0;" ::"n"(N) : "memory"); }
template <int N> __device__ __forceinline__ void fence_acc(float* d) {
#pragma unroll
    for (int i = 0; i < N; i++) asm volatile("" : "+f"(d[i])::"memory");
}
#define R4(o) "+f"(d[o + 0]), "+f"(d[o + 1]), "+f"(d[o + 2]), "+f"(d[o + 3])
#define R8(o) R4(o), R4(o + 4)
__device__ __forceinline__ void wgmma_n128(float* d, desc_t da, desc_t db, int sc) {
    asm volatile("{.reg .pred p; setp.ne.b32 p, %66, 0;\n"
                 "wgmma.mma_async.sync.aligned.m64n128k16.f32.bf16.bf16 {%0,%1,%2,%3,%4,%5,%6,%7,%8,%9,%10,%11,%12,%13,%14,%15,%16,%17,%18,%19,%20,%21,%22,%23,%24,%25,%26,%27,%28,%29,%30,%31,"
                 "%32,%33,%34,%35,%36,%37,%38,%39,%40,%41,%42,%43,%44,%45,%46,%47,%48,%49,%50,%51,%52,%53,%54,%55,%56,%57,%58,%59,%60,%61,%62,%63}, %64, %65, p, 1, 1, 0, 1;}"
                 : R8(0), R8(8), R8(16), R8(24), R8(32), R8(40), R8(48), R8(56)
                 : "l"(da), "l"(db), "r"(sc));
}
__device__ __forceinline__ void wgmma_n112(float* d, desc_t da, desc_t db, int sc) {
    asm volatile("{.reg .pred p; setp.ne.b32 p, %58, 0;\n"
                 "wgmma.mma_async.sync.aligned.m64n112k16.f32.bf16.bf16 {%0,%1,%2,%3,%4,%5,%6,%7,%8,%9,%10,%11,%12,%13,%14,%15,%16,%17,%18,%19,%20,%21,%22,%23,%24,%25,%26,%27,%28,%29,%30,%31,%32,%33,%34,%35,%36,%37,%38,%39,%40,%41,%42,%43,%44,%45,%46,%47,%48,%49,%50,%51,%52,%53,%54,%55}, %56, %57, p, 1, 1, 0, 1;}"
                 : R8(0), R8(8), R8(16), R8(24), R8(32), R8(40), R8(48)
                 : "l"(da), "l"(db), "r"(sc));
}
__device__ __forceinline__ void wgmma_n128_tn(float* d, desc_t da, desc_t db, int sc) {
    asm volatile("{.reg .pred p; setp.ne.b32 p, %66, 0;\n"
                 "wgmma.mma_async.sync.aligned.m64n128k16.f32.bf16.bf16 {%0,%1,%2,%3,%4,%5,%6,%7,%8,%9,%10,%11,%12,%13,%14,%15,%16,%17,%18,%19,%20,%21,%22,%23,%24,%25,%26,%27,%28,%29,%30,%31,%32,%33,%34,%35,%36,%37,%38,%39,%40,%41,%42,%43,%44,%45,%46,%47,%48,%49,%50,%51,%52,%53,%54,%55,%56,%57,%58,%59,%60,%61,%62,%63}, %64, %65, p, 1, 1, 1, 0;}"
                 : R8(0), R8(8), R8(16), R8(24), R8(32), R8(40), R8(48), R8(56)
                 : "l"(da), "l"(db), "r"(sc));
}
__device__ __forceinline__ void wgmma_n64(float* d, desc_t da, desc_t db, int sc) {
    asm volatile("{.reg .pred p; setp.ne.b32 p, %34, 0;\n"
                 "wgmma.mma_async.sync.aligned.m64n64k16.f32.bf16.bf16 {%0,%1,%2,%3,%4,%5,%6,%7,%8,%9,%10,%11,%12,%13,%14,%15,%16,%17,%18,%19,%20,%21,%22,%23,%24,%25,%26,%27,%28,%29,%30,%31}, %32, %33, p, 1, 1, 0, 1;}"
                 : R8(0), R8(8), R8(16), R8(24)
                 : "l"(da), "l"(db), "r"(sc));
}
__device__ __forceinline__ void wgmma_n40_tt(float* d, desc_t da, desc_t db, int sc) {
    asm volatile("{.reg .pred p; setp.ne.b32 p, %22, 0;\n"
                 "wgmma.mma_async.sync.aligned.m64n40k16.f32.bf16.bf16 {%0,%1,%2,%3,%4,%5,%6,%7,%8,%9,%10,%11,%12,%13,%14,%15,%16,%17,%18,%19}, %20, %21, p, 1, 1, 1, 1;}"
                 : R8(0), R8(8), R4(16)
                 : "l"(da), "l"(db), "r"(sc));
}

__device__ __forceinline__ void wgmma_n8_tt(float* d, desc_t da, desc_t db, int sc) {
    asm volatile("{.reg .pred p; setp.ne.b32 p, %6, 0;\n"
                 "wgmma.mma_async.sync.aligned.m64n8k16.f32.bf16.bf16 {%0,%1,%2,%3}, %4, %5, p, 1, 1, 1, 1;}"
                 : R4(0)
                 : "l"(da), "l"(db), "r"(sc));
}

__device__ __forceinline__ uint32_t atom_f32x2(float* p, float a, float b) {
    float x, y;
    asm volatile("atom.relaxed.gpu.global.add.v2.f32 {%0,%1}, [%2], {%3,%4};" : "=f"(x), "=f"(y) : "l"(p), "f"(a), "f"(b) : "memory");
    return __float_as_uint(x);
}
__device__ __forceinline__ uint32_t atom_f32_if(float* p, float a, bool pred) {
    float x = 0.f;
    asm volatile("{.reg .pred p; setp.ne.u32 p, %3, 0; @p atom.relaxed.gpu.global.add.f32 %0, [%1], %2;}" : "+f"(x) : "l"(p), "f"(a), "r"((uint32_t)pred) : "memory");
    return __float_as_uint(x);
}
__device__ __forceinline__ void signal_after(unsigned* cnt, uint32_t ack, uint32_t zero, bool pred) {
    asm volatile("{.reg .pred p; setp.ne.u32 p, %2, 0; @p red.relaxed.gpu.global.add.u32 [%0], %1;}"
                 ::"l"(cnt), "r"((ack & zero) + 1), "r"((uint32_t)pred) : "memory");
}
__device__ __forceinline__ void signal_late(unsigned* cnt, const uint32_t* a, uint32_t zero, bool pred) {
    uint32_t v;
    asm volatile("{.reg .b32 t; lop3.b32 t, %1, %2, %3, 0xfe; or.b32 %0, t, %4;}"
                 : "=r"(v) : "r"(a[0]), "r"(a[1]), "r"(a[2]), "r"(a[3]));
    signal_after(cnt, v, zero, pred);
}
__device__ __forceinline__ void red_f32_if(float* p, float a, bool pred) {
    asm volatile("{.reg .pred p; setp.ne.u32 p, %2, 0; @p red.relaxed.gpu.global.add.f32 [%0], %1;}" ::"l"(p), "f"(a), "r"((uint32_t)pred) : "memory");
}
__device__ __forceinline__ void stg_f2_if(float* p, float a, float b, bool pred) {
    asm volatile("{.reg .pred p; setp.ne.u32 p, %3, 0; @p st.global.v2.f32 [%0], {%1,%2};}" ::"l"(p), "f"(a), "f"(b), "r"((uint32_t)pred) : "memory");
}
__device__ __forceinline__ void stg64(void* p, uint32_t a, uint32_t b) {
    asm volatile("st.global.v2.u32 [%0], {%1,%2};" ::"l"(p), "r"(a), "r"(b) : "memory");
}
__device__ __forceinline__ void mma16816_z(float* c, const uint32_t* a, uint32_t b0, uint32_t b1) {
    asm("mma.sync.aligned.m16n8k16.row.col.f32.bf16.bf16.f32 {%0,%1,%2,%3}, {%4,%5,%6,%7}, {%8,%9}, {%10,%10,%10,%10};"
                 : "=f"(c[0]), "=f"(c[1]), "=f"(c[2]), "=f"(c[3])
                 : "r"(a[0]), "r"(a[1]), "r"(a[2]), "r"(a[3]), "r"(b0), "r"(b1), "f"(0.f));
}
__device__ __forceinline__ uint32_t max2(uint32_t a, uint32_t b) { uint32_t r; asm("max.bf16x2 %0, %1, %2;" : "=r"(r) : "r"(a), "r"(b)); return r; }
__device__ __forceinline__ uint32_t min2(uint32_t a, uint32_t b) { uint32_t r; asm("min.bf16x2 %0, %1, %2;" : "=r"(r) : "r"(a), "r"(b)); return r; }
__device__ __forceinline__ void bar_arrive(int id, int n) { asm volatile("bar.arrive %0, %1;" ::"r"(id), "r"(n) : "memory"); }
__device__ __forceinline__ void mbar_arrive_n_if(uint32_t bar, uint32_t n, bool pred) {
    asm volatile("{.reg .pred p; setp.ne.u32 p, %1, 0; @p mbarrier.arrive.shared::cta.b64 _, [%0], %2;}" ::"r"(bar), "r"((uint32_t)pred), "r"(n) : "memory");
}
__device__ __forceinline__ float4 lds_f4(uint32_t a) {
    float4 v;
    asm volatile("ld.shared.v4.f32 {%0,%1,%2,%3}, [%4];" : "=f"(v.x), "=f"(v.y), "=f"(v.z), "=f"(v.w) : "r"(a) : "memory");
    return v;
}
__device__ __forceinline__ void lds_f4_if(float4& v, uint32_t a, bool pred) {
    asm volatile("{.reg .pred p; setp.ne.u32 p, %5, 0; @p ld.shared.v4.f32 {%0,%1,%2,%3}, [%4];}"
                 : "+f"(v.x), "+f"(v.y), "+f"(v.z), "+f"(v.w) : "r"(a), "r"((uint32_t)pred) : "memory");
}
__device__ __forceinline__ uint4 ld_tagged(const unsigned long long* p) {
    unsigned long long a, b;
    asm volatile("ld.acquire.gpu.global.v2.b64 {%0,%1}, [%2];" : "=l"(a), "=l"(b) : "l"(p) : "memory");
    return make_uint4((unsigned)a, (unsigned)(a >> 32), (unsigned)b, (unsigned)(b >> 32));
}
__device__ __forceinline__ uint4 ld_tagged_rlx(const unsigned long long* p) {
    unsigned long long a, b;
    asm volatile("ld.relaxed.gpu.global.v2.b64 {%0,%1}, [%2];" : "=l"(a), "=l"(b) : "l"(p) : "memory");
    return make_uint4((unsigned)a, (unsigned)(a >> 32), (unsigned)b, (unsigned)(b >> 32));
}
__device__ __forceinline__ void st_tagged_if(unsigned long long* p, float a, float b, unsigned tag, bool pred) {
    const unsigned long long t = (unsigned long long)tag << 32;
    asm volatile("{.reg .pred p; setp.ne.u32 p, %3, 0; @p st.relaxed.gpu.global.v2.b64 [%0], {%1,%2};}"
                 ::"l"(p), "l"(t | __float_as_uint(a)), "l"(t | __float_as_uint(b)), "r"((uint32_t)pred) : "memory");
}

__device__ __forceinline__ void store_tile(uint32_t tile_rows, uint4* gdst, const uint32_t* lo, const uint32_t* hi, int lane, uint32_t* ack) {
    const int r = lane & 15;
#pragma unroll
    for (int b = 0; b < 4; b++)
        stsm4(tile_rows + r * 128 + (((2 * b + (lane >> 4)) ^ (r & 7)) << 4), lo[2 * b], hi[2 * b], lo[2 * b + 1], hi[2 * b + 1]);
    fence_async_smem();
    __syncwarp();
#pragma unroll
    for (int i = 0; i < 4; i++) {
        const uint4 v = lds128(tile_rows + i * 512 + lane * 16);
        stg128(gdst + 32 * i, v.x, v.y, v.z, v.w);
    }
#pragma unroll
    for (int i = 0; i < 4; i++) ack[i] = readback(gdst + 32 * i);
}

__device__ __forceinline__ void feature_maps(const uint32_t* a, const uint32_t* wb, float c0, float c1, uint32_t* plus, uint32_t* minus) {
    uint32_t P[16], mx[4], mn[4];
#pragma unroll
    for (int h = 0; h < 4; h++) {
        float p[8];
        mma16816_z(p, a + 4 * h, wb[4 * h], wb[4 * h + 1]);
        mma16816_z(p + 4, a + 4 * h, wb[4 * h + 2], wb[4 * h + 3]);
        P[4 * h] = pack_bf16(p[0], p[2]); P[4 * h + 1] = pack_bf16(p[1], p[3]);
        P[4 * h + 2] = pack_bf16(p[4], p[6]); P[4 * h + 3] = pack_bf16(p[5], p[7]);
        mx[h] = max2(max2(P[4 * h], P[4 * h + 1]), max2(P[4 * h + 2], P[4 * h + 3]));
        mn[h] = min2(min2(P[4 * h], P[4 * h + 1]), min2(P[4 * h + 2], P[4 * h + 3]));
    }
#pragma unroll
    for (int s = 1; s <= 2; s <<= 1) {
        uint32_t tx[4], tn[4];
#pragma unroll
        for (int h = 0; h < 4; h++) { tx[h] = __shfl_xor_sync(0xffffffffu, mx[h], s); tn[h] = __shfl_xor_sync(0xffffffffu, mn[h], s); }
#pragma unroll
        for (int h = 0; h < 4; h++) { mx[h] = max2(mx[h], tx[h]); mn[h] = min2(mn[h], tn[h]); }
    }
#pragma unroll
    for (int h = 0; h < 4; h++) {
        const float mx0 = bf_lo(mx[h]) * c0, mx1 = bf_hi(mx[h]) * c1, mn0 = bf_lo(mn[h]) * c0, mn1 = bf_hi(mn[h]) * c1;
        float ep[8], em[8];
#pragma unroll
        for (int i = 0; i < 8; i++) {
            const bool r1 = (i & 2);
            const uint32_t w = P[4 * h + (i >> 2) * 2 + (i & 1)];
            const float p = r1 ? bf_hi(w) : bf_lo(w);
            ep[i] = ex2(fmaf(p, r1 ? c1 : c0, r1 ? -mx1 : -mx0));
            em[i] = ex2(fmaf(p, r1 ? -c1 : -c0, r1 ? mn1 : mn0));
        }
        float sp[4], sm[4];
        uint32_t tp[4], tm[4];
#pragma unroll
        for (int i = 0; i < 4; i++) { tp[i] = pack_bf16(ep[2 * i], ep[2 * i + 1]); tm[i] = pack_bf16(em[2 * i], em[2 * i + 1]); }
        mma16816_z(sp, tp, 0x3f803f80u, 0x3f803f80u);
        mma16816_z(sm, tm, 0x3f803f80u, 0x3f803f80u);
        const float r0 = rcp(sp[0] * sm[0]), r1 = rcp(sp[2] * sm[2]);
        const float rs[4] = {r0 * sm[0], r1 * sm[2], r0 * sp[0], r1 * sp[2]};
#pragma unroll
        for (int i = 0; i < 4; i++) {
            plus[4 * h + i] = pack_bf16(ep[2 * i] * rs[i & 1], ep[2 * i + 1] * rs[i & 1]);
            minus[4 * h + i] = pack_bf16(em[2 * i] * rs[2 + (i & 1)], em[2 * i + 1] * rs[2 + (i & 1)]);
        }
    }
}

template <bool SCALE>
__device__ __forceinline__ void ln_frag(const float* acc, uint32_t cs_addr, float rs0, float nm0, float rs1, float nm1, uint32_t* a) {
    const float2 c0 = lds_f2(cs_addr), c1 = lds_f2(cs_addr + 32);
    const float s0 = SCALE ? rs0 : 1.f, s1 = SCALE ? rs1 : 1.f;
    a[0] = pack_bf16(fmaf(nm0, c0.x, acc[0]) * s0, fmaf(nm0, c0.y, acc[1]) * s0);
    a[1] = pack_bf16(fmaf(nm1, c0.x, acc[2]) * s1, fmaf(nm1, c0.y, acc[3]) * s1);
    a[2] = pack_bf16(fmaf(nm0, c1.x, acc[4]) * s0, fmaf(nm0, c1.y, acc[5]) * s0);
    a[3] = pack_bf16(fmaf(nm1, c1.x, acc[6]) * s1, fmaf(nm1, c1.y, acc[7]) * s1);
}

template <int UP>
__device__ __forceinline__ uint32_t hh_pair(const float* ag, float4 cs, float nmean) {
    const float g0 = fmaf(nmean, cs.x, ag[0]), g1 = fmaf(nmean, cs.y, ag[1]);
    const float u0 = fmaf(nmean, cs.z, ag[UP]), u1 = fmaf(nmean, cs.w, ag[UP + 1]);
    return pack_bf16(g0 * u0, g1 * u1);
}
template <int NTP>
__device__ __forceinline__ void hh_stage(const float* acc, const float4* cs, float nm0, float nm1, uint32_t stg, int lane) {
#pragma unroll
    for (int tp = 0; tp < NTP; tp++)
        stsm4(stg + (lane & 15) * 128 + (((2 * tp + (lane >> 4)) ^ (lane & 7)) << 4), hh_pair<32>(acc + 8 * tp, cs[2 * tp], nm0),
              hh_pair<32>(acc + 8 * tp + 2, cs[2 * tp], nm1), hh_pair<32>(acc + 8 * tp + 4, cs[2 * tp + 1], nm0),
              hh_pair<32>(acc + 8 * tp + 6, cs[2 * tp + 1], nm1));
    fence_async_smem();
    __syncwarp();
}

struct Ring {
    int slot; uint32_t phase;
    __device__ __forceinline__ void adv() { if (++slot == NB) { slot = 0; phase ^= 1; } }
    __device__ __forceinline__ void adv5() { slot += slot == 3; adv(); }
};

__global__ void __cluster_dims__(2, 1, 1) __launch_bounds__(NTHREADS, 1) fused_kernel(const __grid_constant__ Params P) {
    extern __shared__ __align__(1024) uint8_t smem_raw[];
    const uint32_t sb = smem_u32(smem_raw);
    const int tid = threadIdx.x, lane = tid & 31;
    const int warp = __shfl_sync(0xffffffffu, tid >> 5, 0);
    const unsigned role = P.role[blockIdx.x], rank = blockIdx.x & 1;
    const int m = role >> 3, j = role & 7;
    const bool helper = role >= 128;

    TL(0, tid == 0); TLG(0, tid == 0);
    float* const acc_j = g_acc + j * ACC_SIZE;
    unsigned* const cnt_j = g_cnt + j * 32;

    if (__builtin_expect(warp >= 8, 1)) {
        asm volatile("setmaxnreg.dec.sync.aligned.u32 72;");
        if (elect_one()) {
            if (warp == 8) {
                if (!helper) {
#pragma unroll
                    for (int i = 0; i < NB; i++) mbar_init(sb + BAR_FULLB + 8 * i, 1);
#pragma unroll
                    for (int i = 0; i < 2; i++) {
                        mbar_expect_tx(sb + BAR_FULLB + 8 * i, SLOT);
                        tma2d(sb + OFF_B + i * SLOT, &P.twq, sb + BAR_FULLB + 8 * i, DM + 64 * j, 64 * i);
                        tma2d(sb + OFF_B + i * SLOT + 8192, &P.twq, sb + BAR_FULLB + 8 * i, 2 * DM + 64 * j, 64 * i);
                    }
                }
            } else if (warp == 9) {
#pragma unroll
                for (int i = 0; i < 8; i++) mbar_init(sb + BAR_FULLA + 8 * i, 1);
                if (!helper) {
#pragma unroll
                    for (int i = 0; i < 2; i++) {
                        mbar_expect_tx(sb + BAR_FULLA + 8 * i, SLOT);
                        tma2d(sb + OFF_A + i * SLOT, &P.tx, sb + BAR_FULLA + 8 * i, 64 * i, 128 * m);
                    }
                }
            } else if (warp == 10) {
#pragma unroll
                for (int i = 0; i < 12; i++) mbar_init(sb + BAR_CS1 + 8 * i, i < 2 || i == 8 ? 64 : (i < 4 || i >= 9 ? 32 : 8));
                trap_if_gt(sb & 1023, 0);
            } else {
#pragma unroll
                for (int i = 0; i < 14; i++) mbar_init(sb + (i < 8 ? BAR_EMPTYA : BAR_EMPTYB - 64) + 8 * i, i < 8 ? 8 : 16);
            }
            asm volatile("fence.mbarrier_init.release.cluster;" ::: "memory");
        }
        __syncwarp();
        asm volatile("barrier.cluster.arrive.relaxed.aligned;" ::: "memory");
        const unsigned epoch = ld_relaxed(&g_epoch);
        bar_sync(0, NTHREADS);
        if (helper) {
            if (warp == 8) {
                if (elect_one()) {
#pragma unroll 1
                    for (int i = 0; i < 72; i++) {
                        const uint32_t full = sb + BAR_FULLA + 8 * (i & 7), dst = sb + OFF_A + (i & 7) * SLOT;
                        mbar_wait(sb + BAR_EMPTYA + 8 * (i & 7), ((i >> 3) & 1) ^ 1);
                        mbar_expect_tx(full, SLOT);
                        const bool qkv = i < 24;
                        const int u = (i >> 3) - 3;
                        const int c0 = qkv ? (i < 16 ? DM + 64 * (i & 8) : 0) + 128 * j + 16 * (i & 4) : 176 * (2 * j + (u & 1)) + 64 * (u >> 1);
                        const int r0 = qkv ? 128 * (i & 3) : 64 * (i & 7);
                        tma2d(dst, qkv ? &P.twq : &P.twg, full, c0, r0);
                        tma2d(dst + 8192, qkv ? &P.twq : &P.twu, full, c0, qkv ? r0 + 64 : r0);
                    }
                    prefetch_l2(P.wd + (size_t)j * 176128, 352256);
                }
            }
            return;
        }
        if (warp == 8) {
            asm volatile("barrier.cluster.wait.aligned;" ::: "memory");
            if (elect_one()) {
                if (m >= 6)
                    asm volatile("cp.async.bulk.prefetch.tensor.2d.L2.global [%0, {%1, %2}];" ::"l"(&P.twq), "r"(DM + DM * (m & 1) + 64 * j), "r"(64 * (m >> 1)) : "memory");
                if (j >= 3)
                    asm volatile("cp.async.bulk.prefetch.tensor.2d.L2.global [%0, {%1, %2}];" ::"l"(&P.tx), "r"(64 * j), "r"(128 * m) : "memory");
                Ring r{2, 0};
                const uint32_t dst = sb + OFF_B + rank * 8192;
#define B_LOAD(TM, C0, R0)                                                                                  \
        mbar_waitc(sb + BAR_EMPTYB + 8 * r.slot, r.phase ^ 1);                                              \
        mbar_expect_tx(sb + BAR_FULLB + 8 * r.slot, SLOT);                                                  \
        tma2d_mc(dst + r.slot * SLOT, TM, sb + BAR_FULLB + 8 * r.slot, C0, R0);
#pragma unroll 1
                for (int i = 2; i < 8; i++) {
                    if (i >= AHEAD && i < 6) mbar_waitc(sb + BAR_FULLB + 8 * (i - AHEAD), 0);
                    B_LOAD(&P.twq, DM + DM * rank + 64 * j, 64 * i)
                    r.adv();
                }
#pragma unroll 1
                for (int i = 8; i < 20; i++) {
                    if (i >= 10 && i < 14) {
                        mbar_waitc(sb + BAR_EMPTYB + 8 * r.slot, r.phase ^ 1);
                        mbar_arrive(sb + BAR_FULLB + 8 * r.slot);
                    } else {
                        const int e = 2 * (i & 3) + rank;
                        B_LOAD(i < 16 ? &P.twq : &P.two, 64 * j, 64 * (i < 16 ? e : KORD(e, j)))
                    }
                    r.adv();
                }
#pragma unroll 1
                for (int i = 0; i < 24; i++) {
                    B_LOAD(&P.twg + rank, 176 * j + 8 * (i & ~7), 64 * (i < 8 ? KORD(i, j) : i & 7))
                    r.adv5();
                }
#pragma unroll 1
                for (int i = 0; i < 12; i++) {
                    B_LOAD(&P.twd, 64 * j, 176 * (2 * (i & 3) + rank) + 64 * (i >> 2))
                    r.adv5();
                }
            }
            return;
        }
        if (warp == 9) {
            if (elect_one()) {
#pragma unroll 1
                for (int i = 2; i < 8; i++) {
                    if (i >= AHEAD + 1) mbar_wait(sb + BAR_FULLA + 8 * (i - AHEAD - 1), 0);
                    mbar_expect_tx(sb + BAR_FULLA + 8 * i, SLOT);
                    tma2d(sb + OFF_A + i * SLOT, &P.tx, sb + BAR_FULLA + 8 * i, 64 * i, 128 * m);
                }
#pragma unroll 1
                for (int i = 2; i < 7; i++) prefetch_tmap(&P.tx + i);
                unsigned nf = 0;
#pragma unroll 1
                for (int r = 1; r < 6; r++) {
                    const int skip = r < 3 ? j : 8;
                    const uint4* src = g_act + ((r - 1) * 128 + m * 8) * 1024;
                    const unsigned* fl = g_flag + (m * 5 + r - 1) * 32;
                    if (r < 4) mbar_wait(sb + BAR_EMPTYA + 8 * (r == 3 ? PF_DELAY : skip == 0), (r - 1) & 1);
                    if (r < 4 || nf != epoch * 8) wait_count(fl, epoch * (r < 3 ? 64 : 8));
                    TL(64 + r, true);
#pragma unroll 1
                    for (int t = 0; t < 8; t++) {
                        if (t == skip) continue;
                        if (t == 6) nf = readback(fl + 32);
                        mbar_wait(sb + BAR_EMPTYA + 8 * t, (r - 1) & 1);
                        mbar_expect_tx(sb + BAR_FULLA + 8 * t, SLOT);
                        asm volatile("cp.async.bulk.shared::cluster.global.mbarrier::complete_tx::bytes [%0], [%1], %2, [%3];"
                                     ::"r"(sb + OFF_A + t * SLOT), "l"(src + t * 1024), "r"(SLOT), "r"(sb + BAR_FULLA + 8 * t) : "memory");
                    }
                }
            }
            return;
        }
        const int a = warp - 10;
        {
            const int row = 16 * j + 8 * a + (lane >> 2);
            const uint32_t ra = sb + OFF_A + row * 128;
            float sh = 0.f, s0 = 0.f, s1 = 0.f, q0 = 0.f, q1 = 0.f;
#pragma unroll 1
            for (int kt = 0; kt < 8; kt++) {
                mbar_wait(sb + BAR_FULLA + 8 * kt, 0);
                if (kt == 0) sh = bf_lo(lds128(ra + ((row & 7) << 4)).x);
#pragma unroll
                for (int i = 0; i < 2; i++) {
                    const uint4 v = lds128(ra + kt * SLOT + (((2 * (lane & 3) + i) ^ (row & 7)) << 4));
                    const uint32_t ww[4] = {v.x, v.y, v.z, v.w};
#pragma unroll
                    for (int e = 0; e < 4; e++) {
                        const float d0 = bf_lo(ww[e]) - sh, d1 = bf_hi(ww[e]) - sh;
                        s0 += d0; q0 = fmaf(d0, d0, q0);
                        s1 += d1; q1 = fmaf(d1, d1, q1);
                    }
                }
            }
            s0 += s1; q0 += q1;
#pragma unroll
            for (int o = 1; o <= 2; o <<= 1) { s0 += __shfl_xor_sync(0xffffffffu, s0, o); q0 += __shfl_xor_sync(0xffffffffu, q0, o); }
            const float md = s0 * (1.f / DM);
            const float rs = rsqrtf(fmaxf(q0 * (1.f / DM) - md * md, 0.f) + 1e-5f);
            st_tagged_if(g_xstat + 2 * (128 * m + row), rs, -(sh + md), epoch, (lane & 3) == 0);
        }
        const unsigned long long* cs = g_cs + j * 768 + 2 * lane;
#pragma unroll 1
        for (int c = 0; c < (a ? 5 : 10); c++) {
            if (c == 4) {
                const int t = 32 * a + lane;
                const uint32_t kvs = sb + OFF_A + KVS(j) * SLOT;
                mbar_wait(sb + BAR_KVW, 0);
#pragma unroll 1
                for (int pass = 0; pass < 2; pass++) {
                    float4 v[8];
#pragma unroll
                    for (int i = 0; i < 8; i++) v[i] = ld_l2_f4(acc_j + ACC_KV + 4 * (t + 64 * i));
                    const float2 zz = ld_l2_f2(acc_j + ACC_Z + 2 * t);
#pragma unroll
                    for (int i = 0; i < 8; i++)
                        sts64(kvs + ((t >> 2) + 16 * i) * 48 + (t & 3) * 8, pack_bf16(v[i].x, v[i].y), pack_bf16(v[i].z, v[i].w));
                    const uint32_t z0 = pack_bf16(zz.x, zz.x), z1 = pack_bf16(zz.y, zz.y);
                    sts128(kvs + t * 96 + 32, z0, z0, z0, z0);
                    sts128(kvs + t * 96 + 80, z1, z1, z1, z1);
                    if (pass == 0) {
                        __syncwarp();
                        if (lane == 0) red_relaxed(cnt_j, 1);
                        TL(19, t == 0);
                        wait_count_warp(cnt_j, epoch * 32);
                        TL(14, t == 0);
                    }
                }
                mbar_arrive(sb + BAR_KVR);
                if (a) break;
            }
            if (c == 3 && !a) continue;
            const unsigned long long* src = c < 2 ? g_xstat + 2 * (128 * m + 64 * a + 32 * c + lane) : cs + (c < 4 ? 128 * (a + c - 2) : 128 + 64 * c);
            const uint32_t dst = c < 2 ? OFF_XST + (64 * a + 32 * c + lane) * 8
                                       : (c < 4 ? OFF_CS1 + (c == 2 ? 256 * (a + 1) : 0) + 8 * lane : OFF_CS3 + (32 * ((c - 4) >> 1) + lane) * 16 + 8 * (c & 1));
            uint4 v;
            uint32_t it = 0;
            while (true) {
                v = ld_tagged_rlx(src);
                if (!__any_sync(0xffffffffu, v.y != epoch || v.w != epoch)) break;
                __nanosleep(60);
                trap_if_gt(++it, 1u << 22);
            }
            sts64(sb + dst, v.x, v.z);
            if (c == 2 - a || (a && c > 1) || (c > 4 && (c & 1))) mbar_arrive(sb + (c > 4 ? BAR_CSG - 20 + 4 * c : (c == 2 - a ? BAR_CS1 : (c == 2 ? BAR_CSV : BAR_CSQ))));
        }
        {
            uint32_t it = 0;
            while (__any_sync(0xffffffffu, (int)(readback(g_flag + (m * 5 + 1) * 32) - epoch * 64) < 0)) {
                __nanosleep(200);
                trap_if_gt(++it, 1u << 22);
            }
#pragma unroll 1
            for (int rr = 0; rr < 2; rr++) {
                const int row = 64 * rr + 32 * a + lane;
                uint4 v[8];
                bool bad;
                do {
                    bad = false;
#pragma unroll
                    for (int i = 0; i < 8; i++) v[i] = ld_tagged_rlx(g_hstat + (1024 * m + 128 * i + row) * 2);
#pragma unroll
                    for (int i = 0; i < 8; i++) bad |= v[i].y != epoch || v[i].w != epoch;
                    trap_if_gt(++it, 1u << 22);
                } while (__any_sync(0xffffffffu, bad));
                float mean = 0.f;
#pragma unroll
                for (int i = 0; i < 8; i++) mean += __uint_as_float(v[i].x);
                mean *= 0.125f;
                float m2 = 0.f, dv = 0.f;
#pragma unroll
                for (int i = 0; i < 8; i++) { const float d = __uint_as_float(v[i].x) - mean; m2 += __uint_as_float(v[i].z); dv = fmaf(d, d, dv); }
                sts_f2(sb + OFF_CS1 + row * 8, -mean, rcp(fmaf(dv, 64.f, m2) * (1.f / DM) + 1e-5f));
            }
        }
        mbar_arrive(sb + BAR_CS3);
#pragma unroll 1
        for (int c = a; c < 3; c += 2) {
            mbar_wait(sb + BAR_STG + 8 * c, 0);
            if (elect_one()) {
                asm volatile("cp.async.bulk.global.shared::cta.bulk_group [%0], [%1], %2;" ::"l"(g_act + ((2 + c) * 128 + role) * 1024), "r"(sb + OFF_B + 4 * SLOT), "r"(SLOT) : "memory");
                asm volatile("cp.async.bulk.commit_group;" ::: "memory");
                asm volatile("cp.async.bulk.wait_group.read 0;" ::: "memory");
                mbar_arrive(sb + BAR_FULLB + 8 * 4);
                asm volatile("cp.async.bulk.wait_group 0;" ::: "memory");
            }
            __syncwarp();
            TL(60 + c, lane == 0);
            uint32_t ack = 0;
#pragma unroll
            for (int i = 0; i < 4; i++) ack |= readback(g_act + ((2 + c) * 128 + role) * 1024 + (32 * i + lane) * 8);
            signal_after(g_flag + (m * 5 + 2 + c) * 32, ack, P.zero, lane == 0);
            TL(54 + c, lane == 0);
        }
        return;
    }
    const unsigned epoch = ld_relaxed(&g_epoch);
    uint32_t wraw[16];
    if (!helper) {
        const uint32_t* wp = reinterpret_cast<const uint32_t*>(P.wphi) + (4 * j) * 128 + (lane & 3) * 16 + (lane >> 2);
#pragma unroll
        for (int i = 0; i < 16; i++)
            asm volatile("ld.global.nc.u32 %0, [%1];" : "=r"(wraw[i]) : "l"(wp + (i >> 2) * 128 + ((i >> 1) & 1) * 64 + (i & 1) * 8));
    }
    asm volatile("barrier.cluster.arrive.relaxed.aligned;" ::: "memory");
    asm volatile("setmaxnreg.inc.sync.aligned.u32 216;");
    bar_sync(0, NTHREADS);
    if (helper) {
        if (warp < 4) {
            sts128(sb + OFF_B + 16 * tid, 0x3f803f80u, 0x3f803f80u, 0x3f803f80u, 0x3f803f80u);
            for (int i = tid; i < 2 * ACC_SIZE / 4; i += 128) stg128(g_acc + 2 * j * ACC_SIZE + 4 * i, 0, 0, 0, 0);
            fence_async_smem();
            fence_gpu();
            bar_sync(1, 128);
            float acc[8];
            int i = 0;
#pragma unroll 1
            for (int job = 0; job < 12; job++) {
                const int n = job < 6 ? 4 : 8;
#pragma unroll 1
                for (int t = 0; t < n; t++, i++) {
                    mbar_wait(sb + BAR_FULLA + 8 * (i & 7), (i >> 3) & 1);
                    wg_fence();
#pragma unroll
                    for (int k = 0; k < 8; k++)
                        wgmma_n8_tt(acc + (k & 4), desc_lo(sb + OFF_A) + (i & 7) * (SLOT >> 4) + 128 * k, desc_lo(sb + OFF_B), (t | (k & 3)) != 0);
                    wg_commit();
                    wg_wait<1>();
                    mbar_arrive_n_if(sb + BAR_EMPTYA + 8 * ((i + 7) & 7), 2, lane == 0 && i > 0);
                }
                wg_wait<0>();
                fence_acc<8>(acc);
                const int q = lane & 3;
                const float lo = (q & 1) ? acc[2] : acc[0], hi = (q & 1) ? acc[6] : acc[4];
                const float v = job < 6 ? lo + hi : ((q & 2) ? hi : lo);
                unsigned long long* dst = g_cs + ((2 * j + (job & 1)) * 6 + (job >> 1)) * 128 + (q >> 1) * 64 + 16 * warp + 8 * (q & 1) + (lane >> 2);
                asm volatile("st.relaxed.gpu.global.b64 [%0], %1;" ::"l"(dst), "l"(((unsigned long long)epoch << 32) | __float_as_uint(v)) : "memory");
            }
        }
        return;
    }
    {
        const int w = warp >> 2, wv = warp & 3, g = lane >> 2, q = lane & 3;
        const int row_w = 128 * m + 16 * warp;
        const uint32_t sa = sb + OFF_A + w * 8192;
        const desc_t dA = desc_lo(sa), dB = desc_lo(sb + OFF_B);
        unsigned* const flag_m = g_flag + m * 160;
        const bool l0 = lane == 0, l2 = lane < 2;
        const uint32_t eb = mapa(sb + BAR_EMPTYB, lane & 1);
        asm volatile("barrier.cluster.wait.aligned;" ::: "memory");
        Ring rg{0, 0};
        int prev = 0;

        uint32_t wb[16];
        constexpr float L2E = 1.4426950408889634f;
        const int ch = lane >> 4, sw = lane & 7;
        const uint32_t lrow = (lane & 15) * 128;
        uint32_t fp[16], fm[16];
        {
            float acc[64], accq[32];
#pragma unroll 1
            for (int kt = 0; kt < 8; kt++) {
                mbar_waitc(sb + BAR_FULLA + 8 * kt, 0);
                mbar_waitc(sb + BAR_FULLB + 8 * rg.slot, rg.phase);
                const desc_t da = dA + kt * (SLOT >> 4), db = dB + rg.slot * (SLOT >> 4);
                wg_fence();
#pragma unroll
                for (int k = 0; k < 4; k++) wgmma_n128(acc, da + 2 * k, db + 128 * k, (kt | k) != 0);
                wg_commit();
                wg_wait<1>();
                mbar_arrive_cl_if(eb + 8 * prev, l2 && kt > 0);
                prev = rg.slot; rg.adv();
            }
#pragma unroll
            for (int i = 0; i < 8; i++) {
                wb[(i >> 1) * 4 + (i & 1)] = __byte_perm(wraw[2 * i], wraw[2 * i + 1], 0x5410);
                wb[(i >> 1) * 4 + 2 + (i & 1)] = __byte_perm(wraw[2 * i], wraw[2 * i + 1], 0x7632);
            }
            float2 s0, s1;
            uint32_t a[16];
            wg_wait<0>();
            fence_acc<64>(acc);
            mbar_arrive_cl_if(eb + 8 * prev, l2);
#pragma unroll 1
            for (int it = 0; it < 2; it++) {
                mbar_waitc(sb + BAR_FULLB + 8 * 2, it ^ 1); mbar_waitc(sb + BAR_FULLB + 8 * 3, it ^ 1);
                const desc_t da = dA + it * (4 * SLOT >> 4);
                wg_fence();
#pragma unroll
                for (int k = 0; k < 16; k++) wgmma_n64(accq, da + (k >> 2) * (SLOT >> 4) + (k & 3) * 2, dB + 2 * (SLOT >> 4) + 128 * k, (it | k) != 0);
                wg_commit();
                TL(17 + it, tid == 0);
                mbar_waitc(sb + BAR_CS1 + 16 * it, 0);
                wg_wait<0>();
                fence_acc<32>(accq);
                mbar_arrive_cl_if(eb + 8 * (2 + (lane >> 1)), lane < 4);
                TL(2 + 2 * it, tid == 0);
                if (it == 0) {
                    s0 = lds_f2(sb + OFF_XST + (16 * warp + g) * 8); s1 = lds_f2(sb + OFF_XST + (16 * warp + g + 8) * 8);
#pragma unroll
                    for (int hh = 0; hh < 4; hh++)
                        ln_frag<false>(acc + 8 * hh, sb + OFF_CS1 + (64 + 16 * hh + 2 * q) * 4, 0.f, s0.y, 0.f, s1.y, a + 4 * hh);
                } else {
#pragma unroll
                    for (int hh = 0; hh < 4; hh++)
                        ln_frag<false>(accq + 8 * hh, sb + OFF_CS1 + (16 * hh + 2 * q) * 4, 0.f, s0.y, 0.f, s1.y, a + 4 * hh);
                }
                feature_maps(a, wb, s0.x * L2E, s1.x * L2E, fp, fm);
                if (it == 0) {
                    mbar_waitc(sb + BAR_FULLB + 8 * 4, 1); mbar_waitc(sb + BAR_FULLB + 8 * 5, 1);
                    mbar_waitc(sb + BAR_FULLB + 8 * 0, 0); mbar_waitc(sb + BAR_FULLB + 8 * 1, 0);
                    mbar_waitc(sb + BAR_CSV, 0);
                    const uint32_t st = sb + OFF_B + warp * 2048 + lrow;
#pragma unroll
                    for (int hh = 0; hh < 4; hh++) {
                        stsm4(st + (4 + (hh >> 1)) * SLOT + (((4 * (hh & 1) + ch) ^ sw) << 4), fp[4 * hh], fp[4 * hh + 1], fp[4 * hh + 2], fp[4 * hh + 3]);
                        stsm4(st + (4 + (hh >> 1)) * SLOT + (((4 * (hh & 1) + 2 + ch) ^ sw) << 4), fm[4 * hh], fm[4 * hh + 1], fm[4 * hh + 2], fm[4 * hh + 3]);
                        ln_frag<true>(acc + 32 + 8 * hh, sb + OFF_CS1 + (128 + 16 * hh + 2 * q) * 4, s0.x, s0.y, s1.x, s1.y, a);
                        stsm4(st + (hh >> 1) * SLOT + (((2 * (hh & 1) + ch) ^ sw) << 4), a[0], a[1], a[2], a[3]);
                    }
                    stsm4(st + ch * SLOT + ((4 ^ sw) << 4), 0x3f803f80u, 0x3f803f80u, 0x3f803f80u, 0x3f803f80u);
                    fence_async_smem();
                    bar_sync(1, 256);
                    float kvd[20];
                    wg_fence();
#pragma unroll
                    for (int k = 0; k < 8; k++)
                        wgmma_n40_tt(kvd, dB + (4 + w) * (SLOT >> 4) + 128 * k, dB + w * (SLOT >> 4) + 128 * k, k != 0);
                    wg_commit();
                    wg_wait<0>();
                    fence_acc<20>(kvd);
                    const bool h1 = wv >= 2;
                    const int f = 16 * warp + g;
                    float* kvp = acc_j + ACC_KV + f * 16 + 2 * q;
                    red_f32x2(kvp, h1 ? kvd[8] : kvd[0], h1 ? kvd[9] : kvd[1]);
                    red_f32x2(kvp + 128, h1 ? kvd[10] : kvd[2], h1 ? kvd[11] : kvd[3]);
                    red_f32x2(kvp + 8, h1 ? kvd[12] : kvd[4], h1 ? kvd[13] : kvd[5]);
                    red_f32x2(kvp + 136, h1 ? kvd[14] : kvd[6], h1 ? kvd[15] : kvd[7]);
                    red_f32_if(acc_j + ACC_Z + f + 8 * (q & 1), q ? kvd[18] : kvd[16], q < 2);
                    __syncwarp();
                    mbar_arrive_if(sb + BAR_KVW, l0);
                    mbar_arrive_cl_if(eb + 8 * ((4 + (lane >> 1)) % 6), lane < 8);
                    TL(3, tid == 0);
                }
            }
        }
        uint32_t res_lo[8], res_hi[8], ack[4];
        const uint32_t own_rows = sb + OFF_A + j * SLOT + warp * 2048;
#pragma unroll
        for (int b = 0; b < 4; b++)
            ldsm4(own_rows + lrow + (((2 * b + ch) ^ sw) << 4), res_lo[2 * b], res_hi[2 * b], res_lo[2 * b + 1], res_hi[2 * b + 1]);
        mbar_arrive_if(sb + BAR_EMPTYA + 8 * lane, lane < 8 && lane != j && lane != KVS(j));
        TL(5, tid == 0);
        mbar_waitc(sb + BAR_KVR, 0);
        TL(6, tid == 0);
        {
            const uint32_t kvs = sb + OFF_A + KVS(j) * SLOT;
            uint32_t o_lo[8], o_hi[8];
#pragma unroll
            for (int hh = 0; hh < 4; hh++) {
                uint32_t b[8], zb[4];
                const uint32_t base = kvs + hh * 32 * 48;
                ldsm4t(base + (lane & 15) * 48 + (lane >> 4) * 16, b[0], b[1], b[2], b[3]);
                ldsm4t(base + (16 + (lane & 15)) * 48 + (lane >> 4) * 16, b[4], b[5], b[6], b[7]);
                ldsm4t(base + lane * 48 + 32, zb[0], zb[1], zb[2], zb[3]);
                float n0[4], n1[4], dn[4];
                mma16816_z(n0, fp + 4 * hh, b[0], b[1]); mma16816_z(n1, fp + 4 * hh, b[2], b[3]); mma16816_z(dn, fp + 4 * hh, zb[0], zb[1]);
                mma16816(n0, fm + 4 * hh, b[4], b[5]); mma16816(n1, fm + 4 * hh, b[6], b[7]); mma16816(dn, fm + 4 * hh, zb[2], zb[3]);
                const float i0 = rcp(dn[0] + 1e-6f), i1 = rcp(dn[2] + 1e-6f);
                o_lo[2 * hh] = pack_bf16(n0[0] * i0, n0[1] * i0); o_hi[2 * hh] = pack_bf16(n0[2] * i1, n0[3] * i1);
                o_lo[2 * hh + 1] = pack_bf16(n1[0] * i0, n1[1] * i0); o_hi[2 * hh + 1] = pack_bf16(n1[2] * i1, n1[3] * i1);
            }
            __syncwarp();
            mbar_arrive_if(sb + BAR_EMPTYA + 8 * KVS(j), l0);
            rg.slot = 4; rg.phase = 0;
            store_tile(own_rows, g_act + role * 1024 + warp * 128 + lane, o_lo, o_hi, lane, ack);
            TL(7, tid == 0);
        }
        {
            float acc[32];
#pragma unroll
            for (int t = 0; t < 8; t++) {
                acc[4 * t] = bf_lo(res_lo[t]); acc[4 * t + 1] = bf_hi(res_lo[t]);
                acc[4 * t + 2] = bf_lo(res_hi[t]); acc[4 * t + 3] = bf_hi(res_hi[t]);
            }
            fence_acc<32>(acc);
            int pa = 0;
#pragma unroll 1
            for (int kp = 0; kp < 4; kp++) {
                mbar_waitc(sb + BAR_FULLB + 8 * rg.slot, rg.phase);
#pragma unroll
                for (int hf = 0; hf < 2; hf++) {
                    const int i = 2 * kp + hf, kt = KORD(i, j);
                    mbar_waitc(sb + BAR_FULLA + 8 * kt, i != 0);
                    TL(8, i == 1 && tid == 0);
                    const desc_t da = dA + kt * (SLOT >> 4), db = dB + rg.slot * (SLOT >> 4);
                    wg_fence();
#pragma unroll
                    for (int k = 0; k < 4; k++) wgmma_n64(acc, da + 2 * k, db + (hf * 4 + k) * 128, 1);
                    wg_commit();
                    wg_wait<1>();
                    mbar_arrive_if(sb + BAR_EMPTYA + 8 * pa, l0 && i > 1);
                    if (hf == 0) {
                        mbar_arrive_cl_if(eb + 8 * prev, l2 && i > 0);
                        if (i == 0) { signal_late(flag_m, ack, P.zero, l0); TL(20, tid == 0); }
                    }
                    pa = kt;
                }
                prev = rg.slot; rg.adv();
            }
            wg_wait<0>();
            fence_acc<32>(acc);
            mbar_arrive_if(sb + BAR_EMPTYA + 8 * pa, l0);
            mbar_arrive_cl_if(eb + 8 * prev, l2);
            TL(9, tid == 0);
            float s0 = 0.f, s1 = 0.f;
#pragma unroll
            for (int t = 0; t < 8; t++) {
                res_lo[t] = pack_bf16(acc[4 * t], acc[4 * t + 1]);
                res_hi[t] = pack_bf16(acc[4 * t + 2], acc[4 * t + 3]);
                s0 += acc[4 * t] + acc[4 * t + 1];
                s1 += acc[4 * t + 2] + acc[4 * t + 3];
            }
            store_tile(own_rows, g_act + (128 + role) * 1024 + warp * 128 + lane, res_lo, res_hi, lane, ack);
            s0 += __shfl_xor_sync(0xffffffffu, s0, 1); s1 += __shfl_xor_sync(0xffffffffu, s1, 1);
            s0 += __shfl_xor_sync(0xffffffffu, s0, 2); s1 += __shfl_xor_sync(0xffffffffu, s1, 2);
            const float mu0 = s0 * (1.f / 64), mu1 = s1 * (1.f / 64);
            float q0 = 0.f, q1 = 0.f;
#pragma unroll
            for (int t = 0; t < 8; t++) {
                float d;
                d = acc[4 * t] - mu0; q0 = fmaf(d, d, q0);
                d = acc[4 * t + 1] - mu0; q0 = fmaf(d, d, q0);
                d = acc[4 * t + 2] - mu1; q1 = fmaf(d, d, q1);
                d = acc[4 * t + 3] - mu1; q1 = fmaf(d, d, q1);
            }
            q0 += __shfl_xor_sync(0xffffffffu, q0, 1); q1 += __shfl_xor_sync(0xffffffffu, q1, 1);
            q0 += __shfl_xor_sync(0xffffffffu, q0, 2); q1 += __shfl_xor_sync(0xffffffffu, q1, 2);
            st_tagged_if(g_hstat + (role * 128 + 16 * warp + g + 8 * (q & 1)) * 2, q ? mu1 : mu0, q ? q1 : q0, epoch, q < 2);
            TL(10, tid == 0);
        }
        float acc0[64], acc1[64], acc2[56], nm0, nm1;
        float4 cs[8];
        uint32_t hr[16];
#define P3_GROUP(MMA, ACC, KT)                                                                              \
        mbar_waitc(sb + BAR_FULLB + 8 * rg.slot, rg.phase);                                                 \
        {                                                                                                   \
            const desc_t da = dA + (KT) * (SLOT >> 4), db = dB + rg.slot * (SLOT >> 4);                     \
            wg_fence();                                                                                     \
            _Pragma("unroll") for (int k = 0; k < 4; k++) MMA(ACC, da + 2 * k, db + 128 * k, (i | k) != 0); \
            wg_commit();                                                                                    \
        }
#define P3_CS(C, NT)    \
        _Pragma("unroll") for (int t = 0; t < (NT); t++) lds_f4_if(cs[t], sb + OFF_CS3 + q * 16 + 512 * (C) + 64 * t, i == t);
#define P3_EPI(C, ACC, N, NTP)                                                                              \
        fence_acc<N>(ACC);                                                                                  \
        TL(11 + (C), tid == 0);                                                                             \
        hh_stage<NTP>(ACC, cs, nm0, nm1, sb + OFF_B + 4 * SLOT + warp * 2048, lane);                        \
        mbar_arrive_if(sb + BAR_STG + 8 * (C), l0);                                                         \
        TL(50 + (C), tid == 0);
        const uint32_t blk = ((lane & 7) + (lane >> 4) * 8) * 128 + (((2 * wv + ((lane >> 3) & 1)) ^ (lane & 7)) << 4);
#pragma unroll 1
        for (int i = 0; i < 8; i++) {
            const int kt = KORD(i, j);
            mbar_waitc(sb + BAR_FULLA + 8 * kt, 0);
            TL(44, tid == 0 && i == 1);
            P3_GROUP(wgmma_n128, acc0, kt)
            if (i == 7) {
                mbar_waitc(sb + BAR_CS3, 0);
                nm0 = lds_f2(sb + OFF_CS1 + (16 * warp + g) * 8).x; nm1 = lds_f2(sb + OFF_CS1 + (16 * warp + g + 8) * 8).x;
            }
            wg_wait<1>();
            mbar_arrive_cl_if(eb + 8 * prev, l2 && i > 0);
            if (i == 0) {
                signal_late(flag_m + 32, ack, P.zero, l0);
                TL(21, tid == 0);
                bar_sync(2 + w, 128);
#pragma unroll
                for (int tp = 0; tp < 4; tp++) ldsm4t(sa + j * SLOT + blk + tp * 2048, hr[4 * tp], hr[4 * tp + 1], hr[4 * tp + 2], hr[4 * tp + 3]);
                mbar_waitc(sb + BAR_CSG, 0);
#pragma unroll
                for (int t = 0; t < 8; t++) cs[t] = lds_f4(sb + OFF_CS3 + q * 16 + 64 * t);
            }
            prev = rg.slot; rg.adv5();
        }
#pragma unroll 1
        for (int i = 0; i < 8; i++) {
            P3_GROUP(wgmma_n128, acc1, i)
            wg_wait<1>();
            mbar_arrive_cl_if(eb + 8 * prev, l2);
            if (i == 0) { P3_EPI(0, acc0, 64, 4) mbar_waitc(sb + BAR_CSG + 8, 0); }
            P3_CS(1, 8)
            prev = rg.slot; rg.adv5();
        }
#pragma unroll 1
        for (int i = 0; i < 8; i++) {
            P3_GROUP(wgmma_n112, acc2, i)
            wg_wait<1>();
            mbar_arrive_cl_if(eb + 8 * prev, l2);
            mbar_arrive_if(sb + BAR_EMPTYA + 8 * ((i + 7) & 7), l0 && i > 0);
            if (i == 0) { mbar_waitc(sb + BAR_FULLB + 8 * 4, 1); P3_EPI(1, acc1, 64, 4) mbar_waitc(sb + BAR_CSG + 16, 0); }
            P3_CS(2, 6)
            prev = rg.slot; rg.adv5();
        }
        mbar_waitc(sb + BAR_FULLB + 8 * 4, 0);
        wg_wait<0>();
        mbar_arrive_cl_if(eb + 8 * prev, l2);
        mbar_arrive_if(sb + BAR_EMPTYA + 8 * 7, l0);
        P3_EPI(2, acc2, 56, 3)
        {
            float acc[64];
            const desc_t dA0 = desc_lo(sb + OFF_A);
#define KT_P4(I, NK)                                                                                        \
        const int s_ = (2 * (I) + w) & 7;                                                                   \
        mbar_waitc(sb + BAR_FULLB + 8 * rg.slot, rg.phase);                                                 \
        mbar_waitc(sb + BAR_FULLA + 8 * s_, (((I) >> 2) + 1) & 1);                                          \
        TL(30 + (I), tid == 0);                                                                             \
        const desc_t dh_ = dA0 + s_ * (SLOT >> 4), dw_ = dB + rg.slot * (SLOT >> 4) + w * 512;              \
        wg_fence();                                                                                         \
        _Pragma("unroll") for (int k = 0; k < (NK); k++) wgmma_n128_tn(acc, dw_ + 128 * k, dh_ + 2 * k, ((I) | k) != 0); \
        wg_commit();                                                                                        \
        wg_wait<1>();
#pragma unroll 1
            for (int i = 0; i < 8; i++) {
                KT_P4(i, 4)
                mbar_arrive_n_if(sb + BAR_EMPTYA + 8 * ((s_ + 6) & 7), 2, l0 && i > 0);
                mbar_arrive_cl_if(eb + 8 * prev, l2 && i > 0);
#pragma unroll
                for (int t = 0; t < 8; t++) lds_f4_if(cs[t], sb + OFF_CS1 + (64 * w + 8 * t + 2 * q) * 8, i == t);
                prev = rg.slot; rg.adv5();
            }
#pragma unroll 1
            for (int i = 8; i < 12; i++) {
                KT_P4(i, 3)
                mbar_arrive_n_if(sb + BAR_EMPTYA + 8 * ((s_ + 6) & 7), 2, l0);
                rg.adv5();
            }
            wg_wait<0>();
            fence_acc<64>(acc);
            TL(15, tid == 0);
            const uint32_t xch = sb + OFF_A + 2 * SLOT + (tid & 127) * 16;
            if (w) {
#pragma unroll
                for (int t = 0; t < 8; t++) {
                    sts128(xch + SLOT + t * 2048, __float_as_uint(acc[4 * t]), __float_as_uint(acc[4 * t + 1]),
                           __float_as_uint(acc[4 * t + 2]), __float_as_uint(acc[4 * t + 3]));
                }
#pragma unroll
                for (int t = 0; t < 32; t++) acc[t] = acc[32 + t];
            } else {
#pragma unroll
                for (int t = 0; t < 8; t++)
                    sts128(xch + t * 2048, __float_as_uint(acc[32 + 4 * t]), __float_as_uint(acc[33 + 4 * t]),
                           __float_as_uint(acc[34 + 4 * t]), __float_as_uint(acc[35 + 4 * t]));
            }
            bar_sync(1, 256);
            float4 o[8];
#pragma unroll
            for (int t = 0; t < 8; t++) o[t] = lds_f4(xch + (w ^ 1) * SLOT + t * 2048);
            const uint32_t tile = sb + OFF_A + w * SLOT;
#pragma unroll
            for (int t = 0; t < 8; t++) {
                hr[2 * t] = pack_bf16(fmaf(acc[4 * t] + o[t].x, cs[t].y, bf_lo(hr[2 * t])), fmaf(acc[4 * t + 1] + o[t].y, cs[t].w, bf_hi(hr[2 * t])));
                hr[2 * t + 1] = pack_bf16(fmaf(acc[4 * t + 2] + o[t].z, cs[t].y, bf_lo(hr[2 * t + 1])), fmaf(acc[4 * t + 3] + o[t].w, cs[t].w, bf_hi(hr[2 * t + 1])));
            }
#pragma unroll
            for (int tp = 0; tp < 4; tp++) stsm4t(tile + blk + tp * 2048, hr[4 * tp], hr[4 * tp + 1], hr[4 * tp + 2], hr[4 * tp + 3]);
            fence_async_smem();
            bar_sync(2 + w, 128);
            if ((tid & 127) == 0) {
                tma_store2d(&P.tout, tile, 64 * j, 128 * m + 64 * w);
                asm volatile("cp.async.bulk.wait_group.read 0;" ::: "memory");
            }
            if (tid == 0 && role == 0) g_epoch = epoch + 1;
            TL(16, tid == 0); TLG(1, tid == 0);
        }
    }
}

__global__ void probe_kernel() {}

typedef CUresult (*EncodeFn)(CUtensorMap*, CUtensorMapDataType, cuuint32_t, void*, const cuuint64_t*, const cuuint64_t*,
                             const cuuint32_t*, const cuuint32_t*, CUtensorMapInterleave, CUtensorMapSwizzle,
                             CUtensorMapL2promotion, CUtensorMapFloatOOBfill);

static void make_map2d(EncodeFn enc, CUtensorMap* tm, const void* base, uint64_t cols, uint64_t rows, uint64_t pitch_elems,
                       uint32_t box_rows) {
    cuuint64_t gd[2] = {cols, rows};
    cuuint64_t gs[1] = {pitch_elems * 2};
    cuuint32_t bd[2] = {64, box_rows};
    cuuint32_t es[2] = {1, 1};
    enc(tm, CU_TENSOR_MAP_DATA_TYPE_BFLOAT16, 2, const_cast<void*>(base), gd, gs, bd, es, CU_TENSOR_MAP_INTERLEAVE_NONE,
        CU_TENSOR_MAP_SWIZZLE_128B, CU_TENSOR_MAP_L2_PROMOTION_L2_256B, CU_TENSOR_MAP_FLOAT_OOB_FILL_NONE);
}

}

extern "C" void kernel_launch(void* const* d_in, const int* in_sizes, int n_in, void* d_out, int out_size) {
    using namespace hk;
    (void)in_sizes; (void)n_in; (void)out_size;
    static EncodeFn enc = nullptr;
    static int std_layout = 0;
    if (!enc) {
        void* fn = nullptr;
        cudaDriverEntryPointQueryResult qr;
        cudaGetDriverEntryPoint("cuTensorMapEncodeTiled", &fn, cudaEnableDefault, &qr);
        enc = (EncodeFn)fn;
        cudaFuncSetAttribute(fused_kernel, cudaFuncAttributeMaxDynamicSharedMemorySize, SMEM_BYTES);
        int dev = 0, sms = 0;
        cudaGetDevice(&dev);
        cudaDeviceGetAttribute(&sms, cudaDevAttrMultiProcessorCount, dev);
        cudaFuncSetAttribute(probe_kernel, cudaFuncAttributeNonPortableClusterSizeAllowed, 1);
        cudaFuncSetAttribute(probe_kernel, cudaFuncAttributeMaxDynamicSharedMemorySize, SMEM_BYTES);
        const int sizes[3] = {8, 9, 16}, want[3] = {15, 9, 7};
        bool ok = sms == NCTA;
        for (int i = 0; i < 3 && ok; i++) {
            cudaLaunchConfig_t cfg = {};
            cfg.gridDim = dim3(sizes[i] * 8); cfg.blockDim = dim3(NTHREADS); cfg.dynamicSmemBytes = SMEM_BYTES;
            cudaLaunchAttribute at;
            at.id = cudaLaunchAttributeClusterDimension;
            at.val.clusterDim.x = sizes[i]; at.val.clusterDim.y = 1; at.val.clusterDim.z = 1;
            cfg.attrs = &at; cfg.numAttrs = 1;
            int n = 0;
            ok = cudaOccupancyMaxActiveClusters(&n, probe_kernel, &cfg) == cudaSuccess && n == want[i];
        }
        (void)cudaGetLastError();
        std_layout = ok ? 1 : 0;
    }
    Params P;
    const __nv_bfloat16* x = (const __nv_bfloat16*)d_in[0];
    P.x = x;
    P.wqkv = (const __nv_bfloat16*)d_in[1];
    P.wphi = (const __nv_bfloat16*)d_in[2];
    P.wo = (const __nv_bfloat16*)d_in[3];
    P.wg = (const __nv_bfloat16*)d_in[5];
    P.wu = (const __nv_bfloat16*)d_in[6];
    P.wd = (const __nv_bfloat16*)d_in[7];
    P.out = (__nv_bfloat16*)d_out;
    P.zero = 0;
    for (int i = 0; i < NCTA; i++) {
        const int odd = i & 1;
        int role = i < 4 ? 128 + i : (((i - 4) >> 4) * 2 + odd) * 8 + (((i - 4) >> 1) & 7);
        if (std_layout) {
            const int tpc = i < 8 ? 62 + (i >> 1) : (i - 8) >> 1;
            if (tpc < 32) role = (tpc & 7) ? (2 * ((tpc & 7) - 1) + odd) * 8 + (tpc >> 3) : (14 + odd) * 8 + (tpc >> 3);
            else if (tpc < 60) role = (2 * ((tpc - 32) % 7) + odd) * 8 + 4 + (tpc - 32) / 7;
            else if (tpc < 62) role = 128 + (tpc - 60) * 2 + odd;
            else role = (14 + odd) * 8 + 4 + (tpc - 62);
        }
        P.role[i] = (unsigned char)role;
    }
    make_map2d(enc, &P.tx, x, DM, SEQ, DM, 128);
    make_map2d(enc, &P.twq, P.wqkv, 3 * DM, DM, 3 * DM, 64);
    make_map2d(enc, &P.two, P.wo, DM, DM, DM, 64);
    make_map2d(enc, &P.twg, P.wg, FF, DM, FF, 64);
    make_map2d(enc, &P.twu, P.wu, FF, DM, FF, 64);
    make_map2d(enc, &P.twd, P.wd, DM, FF, DM, 64);
    make_map2d(enc, &P.tout, d_out, DM, SEQ, DM, 64);
    fused_kernel<<<NCTA, NTHREADS, SMEM_BYTES>>>(P);
}
```

```cpp
#include <cuda_runtime.h>
#include <cuda_bf16.h>
#include <cuda.h>
#include <stdint.h>

namespace hk {

constexpr int SEQ = 2048, DM = 512, FF = 1376;
constexpr int NCTA = 132;
constexpr int NTHREADS = 384;
constexpr uint32_t SLOT = 16384;
constexpr uint32_t OFF_A = 0, OFF_B = 8 * SLOT, OFF_MISC = 14 * SLOT;
constexpr uint32_t BAR_FULLA = OFF_MISC + 0, BAR_EMPTYA = OFF_MISC + 64, BAR_FULLB = OFF_MISC + 128,
                   BAR_EMPTYB = OFF_MISC + 176, BAR_CS1 = OFF_MISC + 224, BAR_CS3 = OFF_MISC + 232,
                   BAR_CSQ = OFF_MISC + 240, BAR_CSV = OFF_MISC + 248,
                   BAR_STG = OFF_MISC + 256,
                   BAR_KVW = OFF_MISC + 280, BAR_KVR = OFF_MISC + 288, BAR_CSG = OFF_MISC + 296;
constexpr uint32_t OFF_CS1 = OFF_MISC + 384;
constexpr uint32_t OFF_CS3 = OFF_CS1 + 1024;
constexpr uint32_t OFF_XST = OFF_CS3;
constexpr uint32_t SMEM_BYTES = OFF_CS3 + 1536;
#define KVS(j) ((j) == 3 ? 2 : 3)
#define KORD(i, j) ((i) == 0 ? (j) : (i) - ((i) <= (j)))
constexpr int NB = 6;
#define PF_DELAY 2
constexpr int AHEAD = 3;

constexpr int ACC_SIZE = 3 * 256 * 4;

__device__ __align__(1024) uint4 g_act[5 * 128 * 1024];
__device__ __align__(128) unsigned long long g_hstat[SEQ * 16];
__device__ __align__(128) unsigned long long g_xstat[SEQ * 2];
__device__ __align__(128) float g_acc[8 * ACC_SIZE];
__device__ __align__(128) unsigned long long g_cs[8 * 6 * 128];
__device__ __align__(128) unsigned g_flag[16 * 5 * 32 + 32];
__device__ unsigned g_epoch = 1;

#define TL(i, pred) do {} while (0)
#define TLG(i, pred) do {} while (0)

struct Params {
    CUtensorMap tx, twq, two, twg, twu, twd, tout;
    const __nv_bfloat16 *x, *wqkv, *wphi, *wo, *wg, *wu, *wd;
    __nv_bfloat16* out;
    unsigned zero;
    unsigned char role[NCTA];
};

__device__ __forceinline__ uint32_t smem_u32(const void* p) { return (uint32_t)__cvta_generic_to_shared(p); }
__device__ __forceinline__ void mbar_init(uint32_t bar, uint32_t cnt) {
    asm volatile("mbarrier.init.shared::cta.b64 [%0], %1;" ::"r"(bar), "r"(cnt) : "memory");
}
__device__ __forceinline__ void mbar_expect_tx(uint32_t bar, uint32_t bytes) {
    asm volatile("mbarrier.arrive.expect_tx.shared::cta.b64 _, [%0], %1;" ::"r"(bar), "r"(bytes) : "memory");
}
__device__ __forceinline__ void mbar_arrive(uint32_t bar) {
    asm volatile("mbarrier.arrive.shared::cta.b64 _, [%0];" ::"r"(bar) : "memory");
}
__device__ __forceinline__ void mbar_arrive_if(uint32_t bar, bool pred) {
    asm volatile("{.reg .pred p; setp.ne.u32 p, %1, 0; @p mbarrier.arrive.shared::cta.b64 _, [%0];}" ::"r"(bar), "r"((uint32_t)pred) : "memory");
}
__device__ __forceinline__ bool mbar_try(uint32_t bar, uint32_t parity) {
    uint32_t ok;
    asm volatile("{.reg .pred p; mbarrier.try_wait.parity.shared::cta.b64 p, [%1], %2; selp.u32 %0,1,0,p;}"
                 : "=r"(ok) : "r"(bar), "r"(parity) : "memory");
    return ok;
}
__device__ __forceinline__ bool mbar_test(uint32_t bar, uint32_t parity) {
    uint32_t ok;
    asm volatile("{.reg .pred p; mbarrier.test_wait.parity.shared::cta.b64 p, [%1], %2; selp.u32 %0,1,0,p;}"
                 : "=r"(ok) : "r"(bar), "r"(parity) : "memory");
    return ok;
}
__device__ __forceinline__ void trap_if_gt(uint32_t v, uint32_t lim) {
    asm volatile("{.reg .pred p; setp.gt.u32 p, %0, %1; @p trap;}" ::"r"(v), "r"(lim));
}
__device__ __forceinline__ void mbar_wait(uint32_t bar, uint32_t parity) {
    asm volatile("{\n"
                 ".reg .pred P1, P2;\n"
                 ".reg .u32 c;\n"
                 "mov.u32 c, 0;\n"
                 "LAB_WAIT:\n"
                 "mbarrier.try_wait.parity.shared::cta.b64 P1, [%0], %1;\n"
                 "@P1 bra LAB_DONE;\n"
                 "add.u32 c, c, 1;\n"
                 "setp.gt.u32 P2, c, 4194304;\n"
                 "@P2 trap;\n"
                 "bra LAB_WAIT;\n"
                 "LAB_DONE:\n"
                 "}" ::"r"(bar), "r"(parity) : "memory");
}
__device__ __forceinline__ void mbar_waitc(uint32_t bar, uint32_t parity) {
    asm volatile("{\n"
                 ".reg .pred P1;\n"
                 "LAB_WAIT:\n"
                 "mbarrier.try_wait.parity.shared::cta.b64 P1, [%0], %1;\n"
                 "@!P1 bra LAB_WAIT;\n"
                 "}" ::"r"(bar), "r"(parity) : "memory");
}
__device__ __forceinline__ void tma2d(uint32_t dst, const CUtensorMap* tm, uint32_t bar, int c0, int c1) {
    asm volatile("cp.async.bulk.tensor.2d.shared::cluster.global.mbarrier::complete_tx::bytes [%0], [%1, {%3, %4}], [%2];"
                 ::"r"(dst), "l"(tm), "r"(bar), "r"(c0), "r"(c1) : "memory");
}
__device__ __forceinline__ void tma2d_mc(uint32_t dst, const CUtensorMap* tm, uint32_t bar, int c0, int c1) {
    asm volatile("cp.async.bulk.tensor.2d.shared::cluster.global.mbarrier::complete_tx::bytes.multicast::cluster [%0], [%1, {%3, %4}], [%2], %5;"
                 ::"r"(dst), "l"(tm), "r"(bar), "r"(c0), "r"(c1), "h"((uint16_t)3) : "memory");
}
__device__ __forceinline__ uint32_t mapa(uint32_t addr, uint32_t rank) {
    uint32_t r; asm("mapa.shared::cluster.u32 %0, %1, %2;" : "=r"(r) : "r"(addr), "r"(rank)); return r;
}
__device__ __forceinline__ void mbar_arrive_cl_if(uint32_t cbar, bool pred) {
    asm volatile("{.reg .pred p; setp.ne.u32 p, %1, 0; @p mbarrier.arrive.shared::cluster.b64 _, [%0];}" ::"r"(cbar), "r"((uint32_t)pred) : "memory");
}
__device__ __forceinline__ bool elect_one() {
    uint32_t ok;
    asm volatile("{.reg .pred p; elect.sync _|p, 0xffffffff; selp.u32 %0, 1, 0, p;}" : "=r"(ok));
    return ok;
}
__device__ __forceinline__ void prefetch_tmap(const CUtensorMap* tm) {
    asm volatile("prefetch.tensormap [%0];" ::"l"(tm) : "memory");
}
__device__ __forceinline__ void prefetch_l2(const void* p, uint32_t bytes) {
    asm volatile("cp.async.bulk.prefetch.L2.global [%0], %1;" ::"l"(p), "r"(bytes) : "memory");
}
__device__ __forceinline__ unsigned ld_acquire(const unsigned* p) {
    unsigned v; asm volatile("ld.acquire.gpu.global.u32 %0, [%1];" : "=r"(v) : "l"(p) : "memory"); return v;
}
__device__ __forceinline__ uint4 ld_acquire4(const unsigned* p) {
    uint4 v;
    asm volatile("ld.acquire.gpu.global.v4.u32 {%0,%1,%2,%3}, [%4];" : "=r"(v.x), "=r"(v.y), "=r"(v.z), "=r"(v.w) : "l"(p) : "memory");
    return v;
}
__device__ __forceinline__ unsigned ld_relaxed(const unsigned* p) {
    unsigned v; asm volatile("ld.relaxed.gpu.global.u32 %0, [%1];" : "=r"(v) : "l"(p)); return v;
}
__device__ __forceinline__ void st_relaxed(unsigned* p, unsigned v) {
    asm volatile("st.relaxed.gpu.global.u32 [%0], %1;" ::"l"(p), "r"(v) : "memory");
}
__device__ __forceinline__ void red_relaxed(unsigned* p, unsigned v) {
    asm volatile("red.relaxed.gpu.global.add.u32 [%0], %1;" ::"l"(p), "r"(v) : "memory");
}
__device__ __forceinline__ void fence_gpu() { asm volatile("fence.acq_rel.gpu;" ::: "memory"); }
__device__ __forceinline__ void fence_async_smem() { asm volatile("fence.proxy.async.shared::cta;" ::: "memory"); }
__device__ __forceinline__ void fence_async_global() { asm volatile("fence.proxy.async.global;" ::: "memory"); }
__device__ __forceinline__ uint32_t readback(const void* p) {
    uint32_t v; asm volatile("ld.relaxed.gpu.global.u32 %0, [%1];" : "=r"(v) : "l"(p) : "memory"); return v;
}
__device__ __forceinline__ void wait_count(const unsigned* p, unsigned target) {
    uint32_t it = 0;
    while ((int)(readback(p) - target) < 0) trap_if_gt(++it, 1u << 22);
}
__device__ __forceinline__ void wait_count_warp(const unsigned* p, unsigned target) {
    uint32_t it = 0;
    while (__any_sync(0xffffffffu, (int)(readback(p) - target) < 0)) trap_if_gt(++it, 1u << 22);
}
__device__ __forceinline__ void red_f32(float* p, float a) {
    asm volatile("red.relaxed.gpu.global.add.f32 [%0], %1;" ::"l"(p), "f"(a) : "memory");
}
__device__ __forceinline__ void red_f32x2(float* p, float a, float b) {
    asm volatile("red.relaxed.gpu.global.add.v2.f32 [%0], {%1, %2};" ::"l"(p), "f"(a), "f"(b) : "memory");
}
__device__ __forceinline__ void red_f32x4(float* p, float a, float b, float c, float d) {
    asm volatile("red.relaxed.gpu.global.add.v4.f32 [%0], {%1, %2, %3, %4};" ::"l"(p), "f"(a), "f"(b), "f"(c), "f"(d) : "memory");
}
__device__ __forceinline__ float4 ld_l2_f4(const float* p) {
    float4 v;
    asm volatile("ld.relaxed.gpu.global.v4.f32 {%0,%1,%2,%3}, [%4];" : "=f"(v.x), "=f"(v.y), "=f"(v.z), "=f"(v.w) : "l"(p) : "memory");
    return v;
}
__device__ __forceinline__ float2 ld_l2_f2(const float* p) {
    float2 v;
    asm volatile("ld.relaxed.gpu.global.v2.f32 {%0,%1}, [%2];" : "=f"(v.x), "=f"(v.y) : "l"(p) : "memory");
    return v;
}
__device__ __forceinline__ float ld_l2_f(const float* p) {
    float v;
    asm volatile("ld.relaxed.gpu.global.f32 %0, [%1];" : "=f"(v) : "l"(p) : "memory");
    return v;
}
__device__ __forceinline__ uint4 ldg_nc(const void* p) {
    uint4 v;
    asm volatile("ld.global.nc.L1::no_allocate.v4.u32 {%0,%1,%2,%3}, [%4];" : "=r"(v.x), "=r"(v.y), "=r"(v.z), "=r"(v.w) : "l"(p));
    return v;
}
__device__ __forceinline__ void stg128(void* p, uint32_t a, uint32_t b, uint32_t c, uint32_t d) {
    asm volatile("st.global.v4.u32 [%0], {%1,%2,%3,%4};" ::"l"(p), "r"(a), "r"(b), "r"(c), "r"(d) : "memory");
}
__device__ __forceinline__ uint4 lds128(uint32_t a) {
    uint4 v;
    asm volatile("ld.shared.v4.u32 {%0,%1,%2,%3}, [%4];" : "=r"(v.x), "=r"(v.y), "=r"(v.z), "=r"(v.w) : "r"(a) : "memory");
    return v;
}
__device__ __forceinline__ float2 lds_f2(uint32_t a) {
    float2 v;
    asm volatile("ld.shared.v2.f32 {%0,%1}, [%2];" : "=f"(v.x), "=f"(v.y) : "r"(a) : "memory");
    return v;
}
__device__ __forceinline__ void sts_f2(uint32_t a, float x, float y) {
    asm volatile("st.shared.v2.f32 [%0], {%1,%2};" ::"r"(a), "f"(x), "f"(y) : "memory");
}
__device__ __forceinline__ void sts64(uint32_t a, uint32_t x, uint32_t y) {
    asm volatile("st.shared.v2.u32 [%0], {%1,%2};" ::"r"(a), "r"(x), "r"(y) : "memory");
}
__device__ __forceinline__ void sts128(uint32_t a, uint32_t x, uint32_t y, uint32_t z, uint32_t w) {
    asm volatile("st.shared.v4.u32 [%0], {%1,%2,%3,%4};" ::"r"(a), "r"(x), "r"(y), "r"(z), "r"(w) : "memory");
}
__device__ __forceinline__ void stsm4(uint32_t a, uint32_t r0, uint32_t r1, uint32_t r2, uint32_t r3) {
    asm volatile("stmatrix.sync.aligned.m8n8.x4.shared.b16 [%0], {%1,%2,%3,%4};" ::"r"(a), "r"(r0), "r"(r1), "r"(r2), "r"(r3) : "memory");
}
__device__ __forceinline__ void stsm4t(uint32_t a, uint32_t r0, uint32_t r1, uint32_t r2, uint32_t r3) {
    asm volatile("stmatrix.sync.aligned.m8n8.x4.trans.shared.b16 [%0], {%1,%2,%3,%4};" ::"r"(a), "r"(r0), "r"(r1), "r"(r2), "r"(r3) : "memory");
}
__device__ __forceinline__ void tma_store2d(const CUtensorMap* tm, uint32_t src, int c0, int c1) {
    asm volatile("cp.async.bulk.tensor.2d.global.shared::cta.bulk_group [%0, {%2, %3}], [%1];" ::"l"(tm), "r"(src), "r"(c0), "r"(c1) : "memory");
    asm volatile("cp.async.bulk.commit_group;" ::: "memory");
}
__device__ __forceinline__ void ldsm4(uint32_t a, uint32_t& r0, uint32_t& r1, uint32_t& r2, uint32_t& r3) {
    asm volatile("ldmatrix.sync.aligned.m8n8.x4.shared.b16 {%0,%1,%2,%3}, [%4];" : "=r"(r0), "=r"(r1), "=r"(r2), "=r"(r3) : "r"(a) : "memory");
}
__device__ __forceinline__ void ldsm4t(uint32_t a, uint32_t& r0, uint32_t& r1, uint32_t& r2, uint32_t& r3) {
    asm volatile("ldmatrix.sync.aligned.m8n8.x4.trans.shared.b16 {%0,%1,%2,%3}, [%4];" : "=r"(r0), "=r"(r1), "=r"(r2), "=r"(r3) : "r"(a) : "memory");
}
__device__ __forceinline__ void mma16816(float* c, const uint32_t* a, uint32_t b0, uint32_t b1) {
    asm("mma.sync.aligned.m16n8k16.row.col.f32.bf16.bf16.f32 {%0,%1,%2,%3}, {%4,%5,%6,%7}, {%8,%9}, {%0,%1,%2,%3};"
                 : "+f"(c[0]), "+f"(c[1]), "+f"(c[2]), "+f"(c[3])
                 : "r"(a[0]), "r"(a[1]), "r"(a[2]), "r"(a[3]), "r"(b0), "r"(b1));
}
__device__ __forceinline__ uint32_t pack_bf16(float lo, float hi) {
    uint32_t r; asm("cvt.rn.bf16x2.f32 %0, %1, %2;" : "=r"(r) : "f"(hi), "f"(lo)); return r;
}
__device__ __forceinline__ float bf_lo(uint32_t w) { return __uint_as_float(w << 16); }
__device__ __forceinline__ float bf_hi(uint32_t w) { return __uint_as_float(w & 0xffff0000u); }
__device__ __forceinline__ float ex2(float x) { float r; asm("ex2.approx.ftz.f32 %0, %1;" : "=f"(r) : "f"(x)); return r; }
__device__ __forceinline__ float rcp(float x) { float r; asm("rcp.approx.ftz.f32 %0, %1;" : "=f"(r) : "f"(x)); return r; }
__device__ __forceinline__ void bar_sync(int id, int n) { asm volatile("bar.sync %0, %1;" ::"r"(id), "r"(n) : "memory"); }

typedef unsigned long long desc_t;
__device__ __forceinline__ desc_t desc_lo(uint32_t addr) { return (desc_t)(((addr & 0x3FFFF) >> 4) | (512u << 16)) | (0x40000040ull << 32); }
__device__ __forceinline__ void wg_fence() { asm volatile("wgmma.fence.sync.aligned;" ::: "memory"); }
__device__ __forceinline__ void wg_commit() { asm volatile("wgmma.commit_group.sync.aligned;" ::: "memory"); }
template <int N> __device__ __forceinline__ void wg_wait() { asm volatile("wgmma.wait_group.sync.aligned %0;" ::"n"(N) : "memory"); }
template <int N> __device__ __forceinline__ void fence_acc(float* d) {
#pragma unroll
    for (int i = 0; i < N; i++) asm volatile("" : "+f"(d[i])::"memory");
}
#define R4(o) "+f"(d[o + 0]), "+f"(d[o + 1]), "+f"(d[o + 2]), "+f"(d[o + 3])
#define R8(o) R4(o), R4(o + 4)
__device__ __forceinline__ void wgmma_n128(float* d, desc_t da, desc_t db, int sc) {
    asm volatile("{.reg .pred p; setp.ne.b32 p, %66, 0;\n"
                 "wgmma.mma_async.sync.aligned.m64n128k16.f32.bf16.bf16 {%0,%1,%2,%3,%4,%5,%6,%7,%8,%9,%10,%11,%12,%13,%14,%15,%16,%17,%18,%19,%20,%21,%22,%23,%24,%25,%26,%27,%28,%29,%30,%31,"
                 "%32,%33,%34,%35,%36,%37,%38,%39,%40,%41,%42,%43,%44,%45,%46,%47,%48,%49,%50,%51,%52,%53,%54,%55,%56,%57,%58,%59,%60,%61,%62,%63}, %64, %65, p, 1, 1, 0, 1;}"
                 : R8(0), R8(8), R8(16), R8(24), R8(32), R8(40), R8(48), R8(56)
                 : "l"(da), "l"(db), "r"(sc));
}
__device__ __forceinline__ void wgmma_n112(float* d, desc_t da, desc_t db, int sc) {
    asm volatile("{.reg .pred p; setp.ne.b32 p, %58, 0;\n"
                 "wgmma.mma_async.sync.aligned.m64n112k16.f32.bf16.bf16 {%0,%1,%2,%3,%4,%5,%6,%7,%8,%9,%10,%11,%12,%13,%14,%15,%16,%17,%18,%19,%20,%21,%22,%23,%24,%25,%26,%27,%28,%29,%30,%31,%32,%33,%34,%35,%36,%37,%38,%39,%40,%41,%42,%43,%44,%45,%46,%47,%48,%49,%50,%51,%52,%53,%54,%55}, %56, %57, p, 1, 1, 0, 1;}"
                 : R8(0), R8(8), R8(16), R8(24), R8(32), R8(40), R8(48)
                 : "l"(da), "l"(db), "r"(sc));
}
__device__ __forceinline__ void wgmma_n128_tn(float* d, desc_t da, desc_t db, int sc) {
    asm volatile("{.reg .pred p; setp.ne.b32 p, %66, 0;\n"
                 "wgmma.mma_async.sync.aligned.m64n128k16.f32.bf16.bf16 {%0,%1,%2,%3,%4,%5,%6,%7,%8,%9,%10,%11,%12,%13,%14,%15,%16,%17,%18,%19,%20,%21,%22,%23,%24,%25,%26,%27,%28,%29,%30,%31,%32,%33,%34,%35,%36,%37,%38,%39,%40,%41,%42,%43,%44,%45,%46,%47,%48,%49,%50,%51,%52,%53,%54,%55,%56,%57,%58,%59,%60,%61,%62,%63}, %64, %65, p, 1, 1, 1, 0;}"
                 : R8(0), R8(8), R8(16), R8(24), R8(32), R8(40), R8(48), R8(56)
                 : "l"(da), "l"(db), "r"(sc));
}
__device__ __forceinline__ void wgmma_n64(float* d, desc_t da, desc_t db, int sc) {
    asm volatile("{.reg .pred p; setp.ne.b32 p, %34, 0;\n"
                 "wgmma.mma_async.sync.aligned.m64n64k16.f32.bf16.bf16 {%0,%1,%2,%3,%4,%5,%6,%7,%8,%9,%10,%11,%12,%13,%14,%15,%16,%17,%18,%19,%20,%21,%22,%23,%24,%25,%26,%27,%28,%29,%30,%31}, %32, %33, p, 1, 1, 0, 1;}"
                 : R8(0), R8(8), R8(16), R8(24)
                 : "l"(da), "l"(db), "r"(sc));
}
__device__ __forceinline__ void wgmma_n40_tt(float* d, desc_t da, desc_t db, int sc) {
    asm volatile("{.reg .pred p; setp.ne.b32 p, %22, 0;\n"
                 "wgmma.mma_async.sync.aligned.m64n40k16.f32.bf16.bf16 {%0,%1,%2,%3,%4,%5,%6,%7,%8,%9,%10,%11,%12,%13,%14,%15,%16,%17,%18,%19}, %20, %21, p, 1, 1, 1, 1;}"
                 : R8(0), R8(8), R4(16)
                 : "l"(da), "l"(db), "r"(sc));
}

__device__ __forceinline__ void wgmma_n8_tt(float* d, desc_t da, desc_t db, int sc) {
    asm volatile("{.reg .pred p; setp.ne.b32 p, %6, 0;\n"
                 "wgmma.mma_async.sync.aligned.m64n8k16.f32.bf16.bf16 {%0,%1,%2,%3}, %4, %5, p, 1, 1, 1, 1;}"
                 : R4(0)
                 : "l"(da), "l"(db), "r"(sc));
}

__device__ __forceinline__ void signal_after(unsigned* cnt, uint32_t ack, uint32_t zero, bool pred) {
    asm volatile("{.reg .pred p; setp.ne.u32 p, %2, 0; @p red.relaxed.gpu.global.add.u32 [%0], %1;}"
                 ::"l"(cnt), "r"((ack & zero) + 1), "r"((uint32_t)pred) : "memory");
}
__device__ __forceinline__ void signal_late(unsigned* cnt, const uint32_t* a, uint32_t zero, bool pred) {
    uint32_t v;
    asm volatile("{.reg .b32 t; lop3.b32 t, %1, %2, %3, 0xfe; or.b32 %0, t, %4;}"
                 : "=r"(v) : "r"(a[0]), "r"(a[1]), "r"(a[2]), "r"(a[3]));
    signal_after(cnt, v, zero, pred);
}
__device__ __forceinline__ void red_f32_if(float* p, float a, bool pred) {
    asm volatile("{.reg .pred p; setp.ne.u32 p, %2, 0; @p red.relaxed.gpu.global.add.f32 [%0], %1;}" ::"l"(p), "f"(a), "r"((uint32_t)pred) : "memory");
}
__device__ __forceinline__ void stg_f2_if(float* p, float a, float b, bool pred) {
    asm volatile("{.reg .pred p; setp.ne.u32 p, %3, 0; @p st.global.v2.f32 [%0], {%1,%2};}" ::"l"(p), "f"(a), "f"(b), "r"((uint32_t)pred) : "memory");
}
__device__ __forceinline__ void stg64(void* p, uint32_t a, uint32_t b) {
    asm volatile("st.global.v2.u32 [%0], {%1,%2};" ::"l"(p), "r"(a), "r"(b) : "memory");
}
__device__ __forceinline__ void mma16816_z(float* c, const uint32_t* a, uint32_t b0, uint32_t b1) {
    asm("mma.sync.aligned.m16n8k16.row.col.f32.bf16.bf16.f32 {%0,%1,%2,%3}, {%4,%5,%6,%7}, {%8,%9}, {%10,%10,%10,%10};"
                 : "=f"(c[0]), "=f"(c[1]), "=f"(c[2]), "=f"(c[3])
                 : "r"(a[0]), "r"(a[1]), "r"(a[2]), "r"(a[3]), "r"(b0), "r"(b1), "f"(0.f));
}
__device__ __forceinline__ uint32_t max2(uint32_t a, uint32_t b) { uint32_t r; asm("max.bf16x2 %0, %1, %2;" : "=r"(r) : "r"(a), "r"(b)); return r; }
__device__ __forceinline__ uint32_t min2(uint32_t a, uint32_t b) { uint32_t r; asm("min.bf16x2 %0, %1, %2;" : "=r"(r) : "r"(a), "r"(b)); return r; }
__device__ __forceinline__ void bar_arrive(int id, int n) { asm volatile("bar.arrive %0, %1;" ::"r"(id), "r"(n) : "memory"); }
__device__ __forceinline__ void mbar_arrive_n_if(uint32_t bar, uint32_t n, bool pred) {
    asm volatile("{.reg .pred p; setp.ne.u32 p, %1, 0; @p mbarrier.arrive.shared::cta.b64 _, [%0], %2;}" ::"r"(bar), "r"((uint32_t)pred), "r"(n) : "memory");
}
__device__ __forceinline__ float4 lds_f4(uint32_t a) {
    float4 v;
    asm volatile("ld.shared.v4.f32 {%0,%1,%2,%3}, [%4];" : "=f"(v.x), "=f"(v.y), "=f"(v.z), "=f"(v.w) : "r"(a) : "memory");
    return v;
}
__device__ __forceinline__ void lds_f4_if(float4& v, uint32_t a, bool pred) {
    asm volatile("{.reg .pred p; setp.ne.u32 p, %5, 0; @p ld.shared.v4.f32 {%0,%1,%2,%3}, [%4];}"
                 : "+f"(v.x), "+f"(v.y), "+f"(v.z), "+f"(v.w) : "r"(a), "r"((uint32_t)pred) : "memory");
}
__device__ __forceinline__ uint4 ld_tagged(const unsigned long long* p) {
    unsigned long long a, b;
    asm volatile("ld.acquire.gpu.global.v2.b64 {%0,%1}, [%2];" : "=l"(a), "=l"(b) : "l"(p) : "memory");
    return make_uint4((unsigned)a, (unsigned)(a >> 32), (unsigned)b, (unsigned)(b >> 32));
}
__device__ __forceinline__ uint4 ld_tagged_rlx(const unsigned long long* p) {
    unsigned long long a, b;
    asm volatile("ld.relaxed.gpu.global.v2.b64 {%0,%1}, [%2];" : "=l"(a), "=l"(b) : "l"(p) : "memory");
    return make_uint4((unsigned)a, (unsigned)(a >> 32), (unsigned)b, (unsigned)(b >> 32));
}
__device__ __forceinline__ void sts32(uint32_t a, uint32_t x) { asm volatile("st.shared.u32 [%0], %1;" ::"r"(a), "r"(x) : "memory"); }
__device__ __forceinline__ void fetch_tagged(const unsigned long long* src, uint32_t dst, unsigned epoch) {
    uint4 v;
    uint32_t it = 0;
    while (true) {
        v = ld_tagged_rlx(src);
        if (!__any_sync(0xffffffffu, v.y != epoch || v.w != epoch)) break;
        __nanosleep(60);
        trap_if_gt(++it, 1u << 22);
    }
    sts64(dst, v.x, v.z);
}
__device__ __forceinline__ void st_tagged_if(unsigned long long* p, float a, float b, unsigned tag, bool pred) {
    const unsigned long long t = (unsigned long long)tag << 32;
    asm volatile("{.reg .pred p; setp.ne.u32 p, %3, 0; @p st.relaxed.gpu.global.v2.b64 [%0], {%1,%2};}"
                 ::"l"(p), "l"(t | __float_as_uint(a)), "l"(t | __float_as_uint(b)), "r"((uint32_t)pred) : "memory");
}

__device__ __forceinline__ void store_tile(uint32_t tile_rows, uint4* gdst, const uint32_t* lo, const uint32_t* hi, int lane, uint32_t* ack) {
    const int r = lane & 15;
#pragma unroll
    for (int b = 0; b < 4; b++)
        stsm4(tile_rows + r * 128 + (((2 * b + (lane >> 4)) ^ (r & 7)) << 4), lo[2 * b], hi[2 * b], lo[2 * b + 1], hi[2 * b + 1]);
    fence_async_smem();
    __syncwarp();
#pragma unroll
    for (int i = 0; i < 4; i++) {
        const uint4 v = lds128(tile_rows + i * 512 + lane * 16);
        stg128(gdst + 32 * i, v.x, v.y, v.z, v.w);
    }
#pragma unroll
    for (int i = 0; i < 4; i++) ack[i] = readback(gdst + 32 * i);
}

__device__ __forceinline__ void feature_maps(const uint32_t* a, const uint32_t* wb, float c0, float c1, uint32_t* plus, uint32_t* minus) {
    uint32_t P[16], mx[4], mn[4];
#pragma unroll
    for (int h = 0; h < 4; h++) {
        float p[8];
        mma16816_z(p, a + 4 * h, wb[4 * h], wb[4 * h + 1]);
        mma16816_z(p + 4, a + 4 * h, wb[4 * h + 2], wb[4 * h + 3]);
        P[4 * h] = pack_bf16(p[0], p[2]); P[4 * h + 1] = pack_bf16(p[1], p[3]);
        P[4 * h + 2] = pack_bf16(p[4], p[6]); P[4 * h + 3] = pack_bf16(p[5], p[7]);
        mx[h] = max2(max2(P[4 * h], P[4 * h + 1]), max2(P[4 * h + 2], P[4 * h + 3]));
        mn[h] = min2(min2(P[4 * h], P[4 * h + 1]), min2(P[4 * h + 2], P[4 * h + 3]));
    }
#pragma unroll
    for (int s = 1; s <= 2; s <<= 1) {
        uint32_t tx[4], tn[4];
#pragma unroll
        for (int h = 0; h < 4; h++) { tx[h] = __shfl_xor_sync(0xffffffffu, mx[h], s); tn[h] = __shfl_xor_sync(0xffffffffu, mn[h], s); }
#pragma unroll
        for (int h = 0; h < 4; h++) { mx[h] = max2(mx[h], tx[h]); mn[h] = min2(mn[h], tn[h]); }
    }
#pragma unroll
    for (int h = 0; h < 4; h++) {
        const float mx0 = bf_lo(mx[h]) * c0, mx1 = bf_hi(mx[h]) * c1, mn0 = bf_lo(mn[h]) * c0, mn1 = bf_hi(mn[h]) * c1;
        float ep[8], em[8];
#pragma unroll
        for (int i = 0; i < 8; i++) {
            const bool r1 = (i & 2);
            const uint32_t w = P[4 * h + (i >> 2) * 2 + (i & 1)];
            const float p = r1 ? bf_hi(w) : bf_lo(w);
            ep[i] = ex2(fmaf(p, r1 ? c1 : c0, r1 ? -mx1 : -mx0));
            em[i] = ex2(fmaf(p, r1 ? -c1 : -c0, r1 ? mn1 : mn0));
        }
        float sp[4], sm[4];
        uint32_t tp[4], tm[4];
#pragma unroll
        for (int i = 0; i < 4; i++) { tp[i] = pack_bf16(ep[2 * i], ep[2 * i + 1]); tm[i] = pack_bf16(em[2 * i], em[2 * i + 1]); }
        mma16816_z(sp, tp, 0x3f803f80u, 0x3f803f80u);
        mma16816_z(sm, tm, 0x3f803f80u, 0x3f803f80u);
        const float r0 = rcp(sp[0] * sm[0]), r1 = rcp(sp[2] * sm[2]);
        const float rs[4] = {r0 * sm[0], r1 * sm[2], r0 * sp[0], r1 * sp[2]};
#pragma unroll
        for (int i = 0; i < 4; i++) {
            plus[4 * h + i] = pack_bf16(ep[2 * i] * rs[i & 1], ep[2 * i + 1] * rs[i & 1]);
            minus[4 * h + i] = pack_bf16(em[2 * i] * rs[2 + (i & 1)], em[2 * i + 1] * rs[2 + (i & 1)]);
        }
    }
}

template <bool SCALE>
__device__ __forceinline__ void ln_frag(const float* acc, uint32_t cs_addr, float rs0, float nm0, float rs1, float nm1, uint32_t* a) {
    const float2 c0 = lds_f2(cs_addr), c1 = lds_f2(cs_addr + 32);
    const float s0 = SCALE ? rs0 : 1.f, s1 = SCALE ? rs1 : 1.f;
    a[0] = pack_bf16(fmaf(nm0, c0.x, acc[0]) * s0, fmaf(nm0, c0.y, acc[1]) * s0);
    a[1] = pack_bf16(fmaf(nm1, c0.x, acc[2]) * s1, fmaf(nm1, c0.y, acc[3]) * s1);
    a[2] = pack_bf16(fmaf(nm0, c1.x, acc[4]) * s0, fmaf(nm0, c1.y, acc[5]) * s0);
    a[3] = pack_bf16(fmaf(nm1, c1.x, acc[6]) * s1, fmaf(nm1, c1.y, acc[7]) * s1);
}

template <int UP>
__device__ __forceinline__ uint32_t hh_pair(const float* ag, float4 cs, float nmean) {
    const float g0 = fmaf(nmean, cs.x, ag[0]), g1 = fmaf(nmean, cs.y, ag[1]);
    const float u0 = fmaf(nmean, cs.z, ag[UP]), u1 = fmaf(nmean, cs.w, ag[UP + 1]);
    return pack_bf16(g0 * u0, g1 * u1);
}
template <int NTP>
__device__ __forceinline__ void hh_stage(const float* acc, const float4* cs, float nm0, float nm1, uint32_t stg, int lane) {
#pragma unroll
    for (int tp = 0; tp < NTP; tp++)
        stsm4(stg + (lane & 15) * 128 + (((2 * tp + (lane >> 4)) ^ (lane & 7)) << 4), hh_pair<32>(acc + 8 * tp, cs[2 * tp], nm0),
              hh_pair<32>(acc + 8 * tp + 2, cs[2 * tp], nm1), hh_pair<32>(acc + 8 * tp + 4, cs[2 * tp + 1], nm0),
              hh_pair<32>(acc + 8 * tp + 6, cs[2 * tp + 1], nm1));
    fence_async_smem();
    __syncwarp();
}

struct Ring {
    int slot; uint32_t phase;
    __device__ __forceinline__ void adv() { if (++slot == NB) { slot = 0; phase ^= 1; } }
    __device__ __forceinline__ void adv5() { slot += slot == 3; adv(); }
};

__global__ void __cluster_dims__(2, 1, 1) __launch_bounds__(NTHREADS, 1) fused_kernel(const __grid_constant__ Params P) {
    extern __shared__ __align__(1024) uint8_t smem_raw[];
    const uint32_t sb = smem_u32(smem_raw);
    const int tid = threadIdx.x, lane = tid & 31;
    const int warp = __shfl_sync(0xffffffffu, tid >> 5, 0);
    const unsigned role = P.role[blockIdx.x], rank = blockIdx.x & 1;
    const int m = role >> 3, j = role & 7;
    const bool helper = role >= 128;

    TL(0, tid == 0); TLG(0, tid == 0);
    float* const acc_j = g_acc + j * ACC_SIZE;

    if (__builtin_expect(warp >= 8, 1)) {
        asm volatile("setmaxnreg.dec.sync.aligned.u32 72;");
        if (elect_one()) {
            if (warp == 8) {
                if (!helper) {
#pragma unroll
                    for (int i = 0; i < NB; i++) mbar_init(sb + BAR_FULLB + 8 * i, 1);
#pragma unroll
                    for (int i = 0; i < 2; i++) {
                        mbar_expect_tx(sb + BAR_FULLB + 8 * i, SLOT);
                        tma2d(sb + OFF_B + i * SLOT, &P.twq, sb + BAR_FULLB + 8 * i, DM + 64 * j, 64 * i);
                        tma2d(sb + OFF_B + i * SLOT + 8192, &P.twq, sb + BAR_FULLB + 8 * i, 2 * DM + 64 * j, 64 * i);
                    }
                }
            } else if (warp == 9) {
#pragma unroll
                for (int i = 0; i < 8; i++) mbar_init(sb + BAR_FULLA + 8 * i, 1);
                if (!helper) {
#pragma unroll
                    for (int i = 0; i < 2; i++) {
                        mbar_expect_tx(sb + BAR_FULLA + 8 * i, SLOT);
                        tma2d(sb + OFF_A + i * SLOT, &P.tx, sb + BAR_FULLA + 8 * i, 64 * i, 128 * m);
                    }
                }
            } else if (warp == 10) {
#pragma unroll
                for (int i = 0; i < 12; i++) mbar_init(sb + BAR_CS1 + 8 * i, i < 2 || i >= 8 ? 64 : (i < 4 ? 32 : 8));
                trap_if_gt(sb & 1023, 0);
            } else {
#pragma unroll
                for (int i = 0; i < 14; i++) mbar_init(sb + (i < 8 ? BAR_EMPTYA : BAR_EMPTYB - 64) + 8 * i, i < 8 ? 8 : 16);
            }
            asm volatile("fence.mbarrier_init.release.cluster;" ::: "memory");
        }
        __syncwarp();
        asm volatile("barrier.cluster.arrive.relaxed.aligned;" ::: "memory");
        const unsigned epoch = ld_relaxed(&g_epoch);
        bar_sync(0, NTHREADS);
        if (helper) {
            if (warp == 8) {
                if (elect_one()) {
#pragma unroll 1
                    for (int i = 0; i < 72; i++) {
                        const uint32_t full = sb + BAR_FULLA + 8 * (i & 7), dst = sb + OFF_A + (i & 7) * SLOT;
                        mbar_wait(sb + BAR_EMPTYA + 8 * (i & 7), ((i >> 3) & 1) ^ 1);
                        mbar_expect_tx(full, SLOT);
                        const bool qkv = i < 24;
                        const int u = (i >> 3) - 3;
                        const int c0 = qkv ? (i < 16 ? DM + 64 * (i & 8) : 0) + 128 * j + 16 * (i & 4) : 176 * (2 * j + (u & 1)) + 64 * (u >> 1);
                        const int r0 = qkv ? 128 * (i & 3) : 64 * (i & 7);
                        tma2d(dst, qkv ? &P.twq : &P.twg, full, c0, r0);
                        tma2d(dst + 8192, qkv ? &P.twq : &P.twu, full, c0, qkv ? r0 + 64 : r0);
                    }
                    prefetch_l2(P.wd + (size_t)j * 176128, 352256);
                }
            }
            return;
        }
        if (warp == 8) {
            asm volatile("barrier.cluster.wait.aligned;" ::: "memory");
            if (elect_one()) {
                if (m >= 6)
                    asm volatile("cp.async.bulk.prefetch.tensor.2d.L2.global [%0, {%1, %2}];" ::"l"(&P.twq), "r"(DM + DM * (m & 1) + 64 * j), "r"(64 * (m >> 1)) : "memory");
                if (j >= 3)
                    asm volatile("cp.async.bulk.prefetch.tensor.2d.L2.global [%0, {%1, %2}];" ::"l"(&P.tx), "r"(64 * j), "r"(128 * m) : "memory");
                Ring r{2, 0};
                const uint32_t dst = sb + OFF_B + rank * 8192;
#define B_LOAD(TM, C0, R0)                                                                                  \
        mbar_waitc(sb + BAR_EMPTYB + 8 * r.slot, r.phase ^ 1);                                              \
        mbar_expect_tx(sb + BAR_FULLB + 8 * r.slot, SLOT);                                                  \
        tma2d_mc(dst + r.slot * SLOT, TM, sb + BAR_FULLB + 8 * r.slot, C0, R0);
#pragma unroll 1
                for (int i = 2; i < 8; i++) {
                    if (i >= AHEAD && i < 6) mbar_waitc(sb + BAR_FULLB + 8 * (i - AHEAD), 0);
                    B_LOAD(&P.twq, DM + DM * rank + 64 * j, 64 * i)
                    r.adv();
                }
#pragma unroll 1
                for (int i = 8; i < 20; i++) {
                    if (i >= 10 && i < 14) {
                        mbar_waitc(sb + BAR_EMPTYB + 8 * r.slot, r.phase ^ 1);
                        mbar_arrive(sb + BAR_FULLB + 8 * r.slot);
                    } else {
                        const int e = 2 * (i & 3) + rank;
                        B_LOAD(i < 16 ? &P.twq : &P.two, 64 * j, 64 * (i < 16 ? e : KORD(e, j)))
                    }
                    r.adv();
                }
#pragma unroll 1
                for (int i = 0; i < 24; i++) {
                    B_LOAD(&P.twg + rank, 176 * j + 8 * (i & ~7), 64 * (i < 8 ? KORD(i, j) : i & 7))
                    r.adv5();
                }
#pragma unroll 1
                for (int i = 0; i < 12; i++) {
                    B_LOAD(&P.twd, 64 * j, 176 * (2 * (i & 3) + rank) + 64 * (i >> 2))
                    r.adv5();
                }
            }
            return;
        }
        if (warp == 9) {
            if (elect_one()) {
#pragma unroll 1
                for (int i = 2; i < 8; i++) {
                    if (i >= AHEAD + 1) mbar_wait(sb + BAR_FULLA + 8 * (i - AHEAD - 1), 0);
                    mbar_expect_tx(sb + BAR_FULLA + 8 * i, SLOT);
                    tma2d(sb + OFF_A + i * SLOT, &P.tx, sb + BAR_FULLA + 8 * i, 64 * i, 128 * m);
                }
#pragma unroll 1
                for (int i = 2; i < 7; i++) prefetch_tmap(&P.tx + i);
                unsigned nf = 0;
#pragma unroll 1
                for (int r = 1; r < 6; r++) {
                    const int skip = r < 3 ? j : 8;
                    const uint4* src = g_act + ((r - 1) * 128 + m * 8) * 1024;
                    const unsigned* fl = g_flag + (m * 5 + r - 1) * 32;
                    if (r < 4) mbar_wait(sb + BAR_EMPTYA + 8 * (r == 3 ? PF_DELAY : skip == 0), (r - 1) & 1);
                    if (r < 4 || nf != epoch * 8) wait_count(fl, epoch * (r < 3 ? 64 : 8));
                    TL(64 + r, true);
#pragma unroll 1
                    for (int t = 0; t < 8; t++) {
                        if (t == skip) continue;
                        if (t == 6) nf = readback(fl + 32);
                        mbar_wait(sb + BAR_EMPTYA + 8 * t, (r - 1) & 1);
                        mbar_expect_tx(sb + BAR_FULLA + 8 * t, SLOT);
                        asm volatile("cp.async.bulk.shared::cluster.global.mbarrier::complete_tx::bytes [%0], [%1], %2, [%3];"
                                     ::"r"(sb + OFF_A + t * SLOT), "l"(src + t * 1024), "r"(SLOT), "r"(sb + BAR_FULLA + 8 * t) : "memory");
                    }
                }
            }
            return;
        }
        const int a = warp - 10;
        {
            const int row = 16 * j + 8 * a + (lane >> 2);
            const uint32_t ra = sb + OFF_A + row * 128;
            float sh = 0.f, s0 = 0.f, s1 = 0.f, q0 = 0.f, q1 = 0.f;
#pragma unroll 1
            for (int kt = 0; kt < 8; kt++) {
                mbar_wait(sb + BAR_FULLA + 8 * kt, 0);
                if (kt == 0) sh = bf_lo(lds128(ra + ((row & 7) << 4)).x);
#pragma unroll
                for (int i = 0; i < 2; i++) {
                    const uint4 v = lds128(ra + kt * SLOT + (((2 * (lane & 3) + i) ^ (row & 7)) << 4));
                    const uint32_t ww[4] = {v.x, v.y, v.z, v.w};
#pragma unroll
                    for (int e = 0; e < 4; e++) {
                        const float d0 = bf_lo(ww[e]) - sh, d1 = bf_hi(ww[e]) - sh;
                        s0 += d0; q0 = fmaf(d0, d0, q0);
                        s1 += d1; q1 = fmaf(d1, d1, q1);
                    }
                }
            }
            s0 += s1; q0 += q1;
#pragma unroll
            for (int o = 1; o <= 2; o <<= 1) { s0 += __shfl_xor_sync(0xffffffffu, s0, o); q0 += __shfl_xor_sync(0xffffffffu, q0, o); }
            const float md = s0 * (1.f / DM);
            const float rs = rsqrtf(fmaxf(q0 * (1.f / DM) - md * md, 0.f) + 1e-5f);
            st_tagged_if(g_xstat + 2 * (128 * m + row), rs, -(sh + md), epoch, (lane & 3) == 0);
        }
        const unsigned long long* cs = g_cs + j * 768 + 2 * lane;
#pragma unroll 1
        for (int c = 0; c < 3 + a; c++) {
            fetch_tagged(c < 2 ? g_xstat + 2 * (128 * m + 64 * a + 32 * c + lane) : cs + 128 * (a + c - 2),
                         sb + (c < 2 ? OFF_XST + (64 * a + 32 * c) * 8 : OFF_CS1 + (c == 2 ? 256 * (a + 1) : 0)) + 8 * lane, epoch);
            if (c >= 2 - a) mbar_arrive(sb + (c == 2 - a ? BAR_CS1 : (c == 2 ? BAR_CSV : BAR_CSQ)));
        }
        {
            mbar_wait(sb + BAR_KVW, 0);
            const float* src = acc_j + 4 * (128 * a + lane);
            float4 v[12];
            uint32_t it = 0;
            bool bad;
            do {
                bad = false;
#pragma unroll
                for (int i = 0; i < 12; i++) v[i] = ld_l2_f4(src + 1024 * (i % 3) + 128 * (i / 3));
#pragma unroll
                for (int i = 0; i < 12; i++) bad |= v[i].w != 16.f;
                trap_if_gt(++it, 1u << 22);
            } while (__any_sync(0xffffffffu, bad));
            TL(14, lane == 0 && a == 0);
            const uint32_t d0 = sb + OFF_A + KVS(j) * SLOT + (64 * a + (lane >> 2)) * 48;
            const uint32_t d = d0 + (lane & 3) * 4, dz = d0 + (lane & 1) * 384 + 32 + (lane & 2) * 4;
#pragma unroll
            for (int u = 0; u < 4; u++) {
                sts32(d + 768 * u, pack_bf16(v[3 * u].x, v[3 * u].y));
                sts32(d + 768 * u + 384, pack_bf16(v[3 * u].z, v[3 * u + 1].z));
                sts32(d + 768 * u + 16, pack_bf16(v[3 * u + 1].x, v[3 * u + 1].y));
                sts32(d + 768 * u + 400, pack_bf16(v[3 * u + 2].x, v[3 * u + 2].y));
                const uint32_t z2 = pack_bf16(v[3 * u + 2].z, v[3 * u + 2].z);
                sts64(dz + 768 * u, z2, z2);
            }
            mbar_arrive(sb + BAR_KVR);
        }
#pragma unroll 1
        for (int c = 0; c < 3; c++) {
            fetch_tagged(cs + 384 + 128 * c + 64 * a, sb + OFF_CS3 + (32 * c + lane) * 16 + 8 * a, epoch);
            mbar_arrive(sb + BAR_CSG + 8 * c);
        }
        {
            uint32_t it = 0;
            while (__any_sync(0xffffffffu, (int)(readback(g_flag + (m * 5 + 1) * 32) - epoch * 64) < 0)) {
                __nanosleep(200);
                trap_if_gt(++it, 1u << 22);
            }
#pragma unroll 1
            for (int rr = 0; rr < 2; rr++) {
                const int row = 64 * rr + 32 * a + lane;
                const unsigned long long* hs = g_hstat + (1024 * m + row) * 2;
                uint4 v[8];
                bool bad;
                do {
                    bad = false;
#pragma unroll
                    for (int i = 0; i < 8; i++) v[i] = ld_tagged_rlx(hs + 256 * i);
#pragma unroll
                    for (int i = 0; i < 8; i++) bad |= v[i].y != epoch || v[i].w != epoch;
                    trap_if_gt(++it, 1u << 22);
                } while (__any_sync(0xffffffffu, bad));
                float mean = 0.f;
#pragma unroll
                for (int i = 0; i < 8; i++) mean += __uint_as_float(v[i].x);
                mean *= 0.125f;
                float m2 = 0.f, dv = 0.f;
#pragma unroll
                for (int i = 0; i < 8; i++) { const float d = __uint_as_float(v[i].x) - mean; m2 += __uint_as_float(v[i].z); dv = fmaf(d, d, dv); }
                sts_f2(sb + OFF_CS1 + row * 8, -mean, rcp(fmaf(dv, 64.f, m2) * (1.f / DM) + 1e-5f));
            }
        }
        mbar_arrive(sb + BAR_CS3);
#pragma unroll 1
        for (int c = a; c < 3; c += 2) {
            mbar_wait(sb + BAR_STG + 8 * c, 0);
            if (elect_one()) {
                asm volatile("cp.async.bulk.global.shared::cta.bulk_group [%0], [%1], %2;" ::"l"(g_act + ((2 + c) * 128 + role) * 1024), "r"(sb + OFF_B + 4 * SLOT), "r"(SLOT) : "memory");
                asm volatile("cp.async.bulk.commit_group;" ::: "memory");
                asm volatile("cp.async.bulk.wait_group.read 0;" ::: "memory");
                mbar_arrive(sb + BAR_FULLB + 8 * 4);
                asm volatile("cp.async.bulk.wait_group 0;" ::: "memory");
            }
            __syncwarp();
            TL(60 + c, lane == 0);
            uint32_t ack = 0;
            const uint4* rb = g_act + ((2 + c) * 128 + role) * 1024 + lane * 8;
#pragma unroll
            for (int i = 0; i < 4; i++) ack |= readback(rb + 256 * i);
            signal_after(g_flag + (m * 5 + 2 + c) * 32, ack, P.zero, lane == 0);
            TL(54 + c, lane == 0);
        }
        return;
    }
    const unsigned epoch = ld_relaxed(&g_epoch);
    uint32_t wraw[16];
    if (!helper) {
        const uint32_t* wp = reinterpret_cast<const uint32_t*>(P.wphi) + (4 * j) * 128 + (lane & 3) * 16 + (lane >> 2);
#pragma unroll
        for (int i = 0; i < 16; i++)
            asm volatile("ld.global.nc.u32 %0, [%1];" : "=r"(wraw[i]) : "l"(wp + (i >> 2) * 128 + ((i >> 1) & 1) * 64 + (i & 1) * 8));
    }
    asm volatile("barrier.cluster.arrive.relaxed.aligned;" ::: "memory");
    asm volatile("setmaxnreg.inc.sync.aligned.u32 216;");
    bar_sync(0, NTHREADS);
    if (helper) {
        if (warp < 4) {
            sts128(sb + OFF_B + 16 * tid, 0x3f803f80u, 0x3f803f80u, 0x3f803f80u, 0x3f803f80u);
            for (int i = tid; i < 2 * ACC_SIZE / 4; i += 128) stg128(g_acc + 2 * j * ACC_SIZE + 4 * i, 0, 0, 0, 0);
            fence_async_smem();
            fence_gpu();
            bar_sync(1, 128);
            float acc[8];
            int i = 0;
#pragma unroll 1
            for (int job = 0; job < 12; job++) {
                const int n = job < 6 ? 4 : 8;
#pragma unroll 1
                for (int t = 0; t < n; t++, i++) {
                    mbar_wait(sb + BAR_FULLA + 8 * (i & 7), (i >> 3) & 1);
                    wg_fence();
#pragma unroll
                    for (int k = 0; k < 8; k++)
                        wgmma_n8_tt(acc + (k & 4), desc_lo(sb + OFF_A) + (i & 7) * (SLOT >> 4) + 128 * k, desc_lo(sb + OFF_B), (t | (k & 3)) != 0);
                    wg_commit();
                    wg_wait<1>();
                    mbar_arrive_n_if(sb + BAR_EMPTYA + 8 * ((i + 7) & 7), 2, lane == 0 && i > 0);
                }
                wg_wait<0>();
                fence_acc<8>(acc);
                const int q = lane & 3;
                const float lo = (q & 1) ? acc[2] : acc[0], hi = (q & 1) ? acc[6] : acc[4];
                const float v = job < 6 ? lo + hi : ((q & 2) ? hi : lo);
                unsigned long long* dst = g_cs + ((2 * j + (job & 1)) * 6 + (job >> 1)) * 128 + (q >> 1) * 64 + 16 * warp + 8 * (q & 1) + (lane >> 2);
                asm volatile("st.relaxed.gpu.global.b64 [%0], %1;" ::"l"(dst), "l"(((unsigned long long)epoch << 32) | __float_as_uint(v)) : "memory");
            }
        }
        return;
    }
    {
        const int w = warp >> 2, wv = warp & 3, g = lane >> 2, q = lane & 3;
        const uint32_t sa = sb + OFF_A + w * 8192;
        const desc_t dA = desc_lo(sa), dB = desc_lo(sb + OFF_B);
        unsigned* const flag_m = g_flag + m * 160;
        const bool l0 = lane == 0, l2 = lane < 2;
        const uint32_t eb = mapa(sb + BAR_EMPTYB, lane & 1);
        asm volatile("barrier.cluster.wait.aligned;" ::: "memory");
        Ring rg{0, 0};
        int prev = 0;

        uint32_t wb[16];
        constexpr float L2E = 1.4426950408889634f;
        const int ch = lane >> 4, sw = lane & 7;
        const uint32_t lrow = (lane & 15) * 128;
        uint32_t fp[16], fm[16];
        {
            float acc[64], accq[32];
#pragma unroll 1
            for (int kt = 0; kt < 8; kt++) {
                mbar_waitc(sb + BAR_FULLA + 8 * kt, 0);
                mbar_waitc(sb + BAR_FULLB + 8 * rg.slot, rg.phase);
                const desc_t da = dA + kt * (SLOT >> 4), db = dB + rg.slot * (SLOT >> 4);
                wg_fence();
#pragma unroll
                for (int k = 0; k < 4; k++) wgmma_n128(acc, da + 2 * k, db + 128 * k, (kt | k) != 0);
                wg_commit();
                wg_wait<1>();
                mbar_arrive_cl_if(eb + 8 * prev, l2 && kt > 0);
                prev = rg.slot; rg.adv();
            }
#pragma unroll
            for (int i = 0; i < 8; i++) {
                wb[(i >> 1) * 4 + (i & 1)] = __byte_perm(wraw[2 * i], wraw[2 * i + 1], 0x5410);
                wb[(i >> 1) * 4 + 2 + (i & 1)] = __byte_perm(wraw[2 * i], wraw[2 * i + 1], 0x7632);
            }
            float2 s0, s1;
            uint32_t a[16];
            wg_wait<0>();
            fence_acc<64>(acc);
            mbar_arrive_cl_if(eb + 8 * prev, l2);
#pragma unroll 1
            for (int it = 0; it < 2; it++) {
                mbar_waitc(sb + BAR_FULLB + 8 * 2, it ^ 1); mbar_waitc(sb + BAR_FULLB + 8 * 3, it ^ 1);
                const desc_t da = dA + it * (4 * SLOT >> 4);
                wg_fence();
#pragma unroll
                for (int k = 0; k < 16; k++) wgmma_n64(accq, da + (k >> 2) * (SLOT >> 4) + (k & 3) * 2, dB + 2 * (SLOT >> 4) + 128 * k, (it | k) != 0);
                wg_commit();
                TL(17 + it, tid == 0);
                mbar_waitc(sb + BAR_CS1 + 16 * it, 0);
                wg_wait<0>();
                fence_acc<32>(accq);
                mbar_arrive_cl_if(eb + 8 * (2 + (lane >> 1)), lane < 4);
                TL(2 + 2 * it, tid == 0);
                if (it == 0) {
                    s0 = lds_f2(sb + OFF_XST + (16 * warp + g) * 8); s1 = lds_f2(sb + OFF_XST + (16 * warp + g + 8) * 8);
#pragma unroll
                    for (int hh = 0; hh < 4; hh++)
                        ln_frag<false>(acc + 8 * hh, sb + OFF_CS1 + (64 + 16 * hh + 2 * q) * 4, 0.f, s0.y, 0.f, s1.y, a + 4 * hh);
                } else {
#pragma unroll
                    for (int hh = 0; hh < 4; hh++)
                        ln_frag<false>(accq + 8 * hh, sb + OFF_CS1 + (16 * hh + 2 * q) * 4, 0.f, s0.y, 0.f, s1.y, a + 4 * hh);
                }
                feature_maps(a, wb, s0.x * L2E, s1.x * L2E, fp, fm);
                if (it == 0) {
                    mbar_waitc(sb + BAR_FULLB + 8 * 4, 1); mbar_waitc(sb + BAR_FULLB + 8 * 5, 1);
                    mbar_waitc(sb + BAR_FULLB + 8 * 0, 0); mbar_waitc(sb + BAR_FULLB + 8 * 1, 0);
                    mbar_waitc(sb + BAR_CSV, 0);
                    const uint32_t st = sb + OFF_B + warp * 2048 + lrow;
#pragma unroll
                    for (int hh = 0; hh < 4; hh++) {
                        stsm4(st + (4 + (hh >> 1)) * SLOT + (((4 * (hh & 1) + ch) ^ sw) << 4), fp[4 * hh], fp[4 * hh + 1], fp[4 * hh + 2], fp[4 * hh + 3]);
                        stsm4(st + (4 + (hh >> 1)) * SLOT + (((4 * (hh & 1) + 2 + ch) ^ sw) << 4), fm[4 * hh], fm[4 * hh + 1], fm[4 * hh + 2], fm[4 * hh + 3]);
                        ln_frag<true>(acc + 32 + 8 * hh, sb + OFF_CS1 + (128 + 16 * hh + 2 * q) * 4, s0.x, s0.y, s1.x, s1.y, a);
                        stsm4(st + (hh >> 1) * SLOT + (((2 * (hh & 1) + ch) ^ sw) << 4), a[0], a[1], a[2], a[3]);
                    }
                    stsm4(st + ch * SLOT + ((4 ^ sw) << 4), 0x3f803f80u, 0x3f803f80u, 0x3f803f80u, 0x3f803f80u);
                    fence_async_smem();
                    bar_sync(1, 256);
                    float kvd[20];
                    wg_fence();
#pragma unroll
                    for (int k = 0; k < 8; k++)
                        wgmma_n40_tt(kvd, dB + (4 + w) * (SLOT >> 4) + 128 * k, dB + w * (SLOT >> 4) + 128 * k, k != 0);
                    wg_commit();
                    wg_wait<0>();
                    fence_acc<20>(kvd);
                    const bool h1 = wv >= 2;
                    float* kvp = acc_j + 4 * tid;
                    red_f32x4(kvp, h1 ? kvd[8] : kvd[0], h1 ? kvd[9] : kvd[1], h1 ? kvd[10] : kvd[2], 1.f);
                    red_f32x4(kvp + 1024, h1 ? kvd[12] : kvd[4], h1 ? kvd[13] : kvd[5], h1 ? kvd[11] : kvd[3], 1.f);
                    red_f32x4(kvp + 2048, h1 ? kvd[14] : kvd[6], h1 ? kvd[15] : kvd[7], (q & 1) ? kvd[18] : kvd[16], 1.f);
                    __syncwarp();
                    mbar_arrive_if(sb + BAR_KVW, l0);
                    mbar_arrive_cl_if(eb + 8 * ((4 + (lane >> 1)) % 6), lane < 8);
                    TL(3, tid == 0);
                }
            }
        }
        uint32_t res_lo[8], res_hi[8], ack[4];
        const uint32_t own_rows = sb + OFF_A + j * SLOT + warp * 2048;
#pragma unroll
        for (int b = 0; b < 4; b++)
            ldsm4(own_rows + lrow + (((2 * b + ch) ^ sw) << 4), res_lo[2 * b], res_hi[2 * b], res_lo[2 * b + 1], res_hi[2 * b + 1]);
        mbar_arrive_if(sb + BAR_EMPTYA + 8 * lane, lane < 8 && lane != j && lane != KVS(j));
        TL(5, tid == 0);
        mbar_waitc(sb + BAR_KVR, 0);
        TL(6, tid == 0);
        {
            const uint32_t kvs = sb + OFF_A + KVS(j) * SLOT;
            uint32_t o_lo[8], o_hi[8];
#pragma unroll
            for (int hh = 0; hh < 4; hh++) {
                uint32_t b[8], zb[4];
                const uint32_t base = kvs + hh * 32 * 48;
                ldsm4t(base + (lane & 15) * 48 + (lane >> 4) * 16, b[0], b[1], b[2], b[3]);
                ldsm4t(base + (16 + (lane & 15)) * 48 + (lane >> 4) * 16, b[4], b[5], b[6], b[7]);
                ldsm4t(base + lane * 48 + 32, zb[0], zb[1], zb[2], zb[3]);
                float n0[4], n1[4], dn[4];
                mma16816_z(n0, fp + 4 * hh, b[0], b[1]); mma16816_z(n1, fp + 4 * hh, b[2], b[3]); mma16816_z(dn, fp + 4 * hh, zb[0], zb[1]);
                mma16816(n0, fm + 4 * hh, b[4], b[5]); mma16816(n1, fm + 4 * hh, b[6], b[7]); mma16816(dn, fm + 4 * hh, zb[2], zb[3]);
                const float i0 = rcp(dn[0] + 1e-6f), i1 = rcp(dn[2] + 1e-6f);
                o_lo[2 * hh] = pack_bf16(n0[0] * i0, n0[1] * i0); o_hi[2 * hh] = pack_bf16(n0[2] * i1, n0[3] * i1);
                o_lo[2 * hh + 1] = pack_bf16(n1[0] * i0, n1[1] * i0); o_hi[2 * hh + 1] = pack_bf16(n1[2] * i1, n1[3] * i1);
            }
            __syncwarp();
            mbar_arrive_if(sb + BAR_EMPTYA + 8 * KVS(j), l0);
            rg.slot = 4; rg.phase = 0;
            store_tile(own_rows, g_act + role * 1024 + warp * 128 + lane, o_lo, o_hi, lane, ack);
            TL(7, tid == 0);
        }
        float acch[32];
        {
            float* acc = acch;
#pragma unroll
            for (int t = 0; t < 8; t++) {
                acc[4 * t] = bf_lo(res_lo[t]); acc[4 * t + 1] = bf_hi(res_lo[t]);
                acc[4 * t + 2] = bf_lo(res_hi[t]); acc[4 * t + 3] = bf_hi(res_hi[t]);
            }
            fence_acc<32>(acc);
            int pa = 0;
#pragma unroll 1
            for (int kp = 0; kp < 4; kp++) {
                mbar_waitc(sb + BAR_FULLB + 8 * rg.slot, rg.phase);
#pragma unroll
                for (int hf = 0; hf < 2; hf++) {
                    const int i = 2 * kp + hf, kt = KORD(i, j);
                    mbar_waitc(sb + BAR_FULLA + 8 * kt, i != 0);
                    TL(8, i == 1 && tid == 0);
                    const desc_t da = dA + kt * (SLOT >> 4), db = dB + rg.slot * (SLOT >> 4);
                    wg_fence();
#pragma unroll
                    for (int k = 0; k < 4; k++) wgmma_n64(acc, da + 2 * k, db + (hf * 4 + k) * 128, 1);
                    wg_commit();
                    wg_wait<1>();
                    mbar_arrive_if(sb + BAR_EMPTYA + 8 * pa, l0 && i > 1);
                    if (hf == 0) {
                        mbar_arrive_cl_if(eb + 8 * prev, l2 && i > 0);
                        if (i == 0) { signal_late(flag_m, ack, P.zero, l0); TL(20, tid == 0); }
                    }
                    pa = kt;
                }
                prev = rg.slot; rg.adv();
            }
            wg_wait<0>();
            fence_acc<32>(acc);
            mbar_arrive_if(sb + BAR_EMPTYA + 8 * pa, l0);
            mbar_arrive_cl_if(eb + 8 * prev, l2);
            TL(9, tid == 0);
#pragma unroll
            for (int t = 0; t < 8; t++) {
                res_lo[t] = pack_bf16(acc[4 * t], acc[4 * t + 1]);
                res_hi[t] = pack_bf16(acc[4 * t + 2], acc[4 * t + 3]);
            }
            store_tile(own_rows, g_act + (128 + role) * 1024 + warp * 128 + lane, res_lo, res_hi, lane, ack);
            TL(10, tid == 0);
        }
        float acc0[64], acc1[64], acc2[56], nm0, nm1;
        float4 cs[8];
        uint32_t hr[16];
#define P3_GROUP(MMA, ACC, KT)                                                                              \
        mbar_waitc(sb + BAR_FULLB + 8 * rg.slot, rg.phase);                                                 \
        {                                                                                                   \
            const desc_t da = dA + (KT) * (SLOT >> 4), db = dB + rg.slot * (SLOT >> 4);                     \
            wg_fence();                                                                                     \
            _Pragma("unroll") for (int k = 0; k < 4; k++) MMA(ACC, da + 2 * k, db + 128 * k, (i | k) != 0); \
            wg_commit();                                                                                    \
        }
#define P3_CS(C, NT)    \
        _Pragma("unroll") for (int t = 0; t < (NT); t++) lds_f4_if(cs[t], sb + OFF_CS3 + q * 16 + 512 * (C) + 64 * t, i == t);
#define P3_EPI(C, ACC, N, NTP)                                                                              \
        fence_acc<N>(ACC);                                                                                  \
        TL(11 + (C), tid == 0);                                                                             \
        hh_stage<NTP>(ACC, cs, nm0, nm1, sb + OFF_B + 4 * SLOT + warp * 2048, lane);                        \
        mbar_arrive_if(sb + BAR_STG + 8 * (C), l0);                                                         \
        TL(50 + (C), tid == 0);
        const uint32_t blk = ((lane & 7) + (lane >> 4) * 8) * 128 + (((2 * wv + ((lane >> 3) & 1)) ^ (lane & 7)) << 4);
#pragma unroll 1
        for (int i = 0; i < 8; i++) {
            const int kt = KORD(i, j);
            mbar_waitc(sb + BAR_FULLA + 8 * kt, 0);
            TL(44, tid == 0 && i == 1);
            P3_GROUP(wgmma_n128, acc0, kt)
            if (i == 7) {
                mbar_waitc(sb + BAR_CS3, 0);
                nm0 = lds_f2(sb + OFF_CS1 + (16 * warp + g) * 8).x; nm1 = lds_f2(sb + OFF_CS1 + (16 * warp + g + 8) * 8).x;
            }
            wg_wait<1>();
            mbar_arrive_cl_if(eb + 8 * prev, l2 && i > 0);
            if (i == 0) {
                signal_late(flag_m + 32, ack, P.zero, l0);
                TL(21, tid == 0);
                {
                    fence_acc<32>(acch);
                    const float* acc = acch;
                    float s0 = 0.f, s1 = 0.f;
#pragma unroll
                    for (int t = 0; t < 8; t++) { s0 += acc[4 * t] + acc[4 * t + 1]; s1 += acc[4 * t + 2] + acc[4 * t + 3]; }
            s0 += __shfl_xor_sync(0xffffffffu, s0, 1); s1 += __shfl_xor_sync(0xffffffffu, s1, 1);
            s0 += __shfl_xor_sync(0xffffffffu, s0, 2); s1 += __shfl_xor_sync(0xffffffffu, s1, 2);
            const float mu0 = s0 * (1.f / 64), mu1 = s1 * (1.f / 64);
            float q0 = 0.f, q1 = 0.f;
#pragma unroll
            for (int t = 0; t < 8; t++) {
                float d;
                d = acc[4 * t] - mu0; q0 = fmaf(d, d, q0);
                d = acc[4 * t + 1] - mu0; q0 = fmaf(d, d, q0);
                d = acc[4 * t + 2] - mu1; q1 = fmaf(d, d, q1);
                d = acc[4 * t + 3] - mu1; q1 = fmaf(d, d, q1);
            }
            q0 += __shfl_xor_sync(0xffffffffu, q0, 1); q1 += __shfl_xor_sync(0xffffffffu, q1, 1);
            q0 += __shfl_xor_sync(0xffffffffu, q0, 2); q1 += __shfl_xor_sync(0xffffffffu, q1, 2);
            st_tagged_if(g_hstat + (role * 128 + 16 * warp + g + 8 * (q & 1)) * 2, q ? mu1 : mu0, q ? q1 : q0, epoch, q < 2);
                }
                bar_sync(2 + w, 128);
#pragma unroll
                for (int tp = 0; tp < 4; tp++) ldsm4t(sa + j * SLOT + blk + tp * 2048, hr[4 * tp], hr[4 * tp + 1], hr[4 * tp + 2], hr[4 * tp + 3]);
                mbar_waitc(sb + BAR_CSG, 0);
#pragma unroll
                for (int t = 0; t < 8; t++) cs[t] = lds_f4(sb + OFF_CS3 + q * 16 + 64 * t);
            }
            prev = rg.slot; rg.adv5();
        }
#pragma unroll 1
        for (int i = 0; i < 8; i++) {
            P3_GROUP(wgmma_n128, acc1, i)
            wg_wait<1>();
            mbar_arrive_cl_if(eb + 8 * prev, l2);
            if (i == 0) { P3_EPI(0, acc0, 64, 4) mbar_waitc(sb + BAR_CSG + 8, 0); }
            P3_CS(1, 8)
            prev = rg.slot; rg.adv5();
        }
#pragma unroll 1
        for (int i = 0; i < 8; i++) {
            P3_GROUP(wgmma_n112, acc2, i)
            wg_wait<1>();
            mbar_arrive_cl_if(eb + 8 * prev, l2);
            mbar_arrive_if(sb + BAR_EMPTYA + 8 * ((i + 7) & 7), l0 && i > 0);
            if (i == 0) { mbar_waitc(sb + BAR_FULLB + 8 * 4, 1); P3_EPI(1, acc1, 64, 4) mbar_waitc(sb + BAR_CSG + 16, 0); }
            P3_CS(2, 6)
            prev = rg.slot; rg.adv5();
        }
        mbar_waitc(sb + BAR_FULLB + 8 * 4, 0);
        wg_wait<0>();
        mbar_arrive_cl_if(eb + 8 * prev, l2);
        mbar_arrive_if(sb + BAR_EMPTYA + 8 * 7, l0);
        P3_EPI(2, acc2, 56, 3)
        {
            float acc[64];
            const desc_t dA0 = desc_lo(sb + OFF_A);
#define KT_P4(I, NK)                                                                                        \
        const int s_ = (2 * (I) + w) & 7;                                                                   \
        mbar_waitc(sb + BAR_FULLB + 8 * rg.slot, rg.phase);                                                 \
        mbar_waitc(sb + BAR_FULLA + 8 * s_, (((I) >> 2) + 1) & 1);                                          \
        TL(30 + (I), tid == 0);                                                                             \
        const desc_t dh_ = dA0 + s_ * (SLOT >> 4), dw_ = dB + rg.slot * (SLOT >> 4) + w * 512;              \
        wg_fence();                                                                                         \
        _Pragma("unroll") for (int k = 0; k < (NK); k++) wgmma_n128_tn(acc, dw_ + 128 * k, dh_ + 2 * k, ((I) | k) != 0); \
        wg_commit();                                                                                        \
        wg_wait<1>();
#pragma unroll 1
            for (int i = 0; i < 8; i++) {
                KT_P4(i, 4)
                mbar_arrive_n_if(sb + BAR_EMPTYA + 8 * ((s_ + 6) & 7), 2, l0 && i > 0);
                mbar_arrive_cl_if(eb + 8 * prev, l2 && i > 0);
#pragma unroll
                for (int t = 0; t < 8; t++) lds_f4_if(cs[t], sb + OFF_CS1 + (64 * w + 8 * t + 2 * q) * 8, i == t);
                prev = rg.slot; rg.adv5();
            }
#pragma unroll 1
            for (int i = 8; i < 12; i++) {
                KT_P4(i, 3)
                mbar_arrive_n_if(sb + BAR_EMPTYA + 8 * ((s_ + 6) & 7), 2, l0);
                rg.adv5();
            }
            wg_wait<0>();
            fence_acc<64>(acc);
            TL(15, tid == 0);
            const uint32_t xch = sb + OFF_A + 2 * SLOT + (tid & 127) * 16;
            if (w) {
#pragma unroll
                for (int t = 0; t < 8; t++) {
                    sts128(xch + SLOT + t * 2048, __float_as_uint(acc[4 * t]), __float_as_uint(acc[4 * t + 1]),
                           __float_as_uint(acc[4 * t + 2]), __float_as_uint(acc[4 * t + 3]));
                }
#pragma unroll
                for (int t = 0; t < 32; t++) acc[t] = acc[32 + t];
            } else {
#pragma unroll
                for (int t = 0; t < 8; t++)
                    sts128(xch + t * 2048, __float_as_uint(acc[32 + 4 * t]), __float_as_uint(acc[33 + 4 * t]),
                           __float_as_uint(acc[34 + 4 * t]), __float_as_uint(acc[35 + 4 * t]));
            }
            bar_sync(1, 256);
            float4 o[8];
#pragma unroll
            for (int t = 0; t < 8; t++) o[t] = lds_f4(xch + (w ^ 1) * SLOT + t * 2048);
            const uint32_t tile = sb + OFF_A + w * SLOT;
#pragma unroll
            for (int t = 0; t < 8; t++) {
                hr[2 * t] = pack_bf16(fmaf(acc[4 * t] + o[t].x, cs[t].y, bf_lo(hr[2 * t])), fmaf(acc[4 * t + 1] + o[t].y, cs[t].w, bf_hi(hr[2 * t])));
                hr[2 * t + 1] = pack_bf16(fmaf(acc[4 * t + 2] + o[t].z, cs[t].y, bf_lo(hr[2 * t + 1])), fmaf(acc[4 * t + 3] + o[t].w, cs[t].w, bf_hi(hr[2 * t + 1])));
            }
#pragma unroll
            for (int tp = 0; tp < 4; tp++) stsm4t(tile + blk + tp * 2048, hr[4 * tp], hr[4 * tp + 1], hr[4 * tp + 2], hr[4 * tp + 3]);
            fence_async_smem();
            bar_sync(2 + w, 128);
            if ((tid & 127) == 0) {
                tma_store2d(&P.tout, tile, 64 * j, 128 * m + 64 * w);
                asm volatile("cp.async.bulk.wait_group.read 0;" ::: "memory");
            }
            if (tid == 0 && role == 0) g_epoch = epoch + 1;
            TL(16, tid == 0); TLG(1, tid == 0);
        }
    }
}

__global__ void probe_kernel() {}

typedef CUresult (*EncodeFn)(CUtensorMap*, CUtensorMapDataType, cuuint32_t, void*, const cuuint64_t*, const cuuint64_t*,
                             const cuuint32_t*, const cuuint32_t*, CUtensorMapInterleave, CUtensorMapSwizzle,
                             CUtensorMapL2promotion, CUtensorMapFloatOOBfill);

static void make_map2d(EncodeFn enc, CUtensorMap* tm, const void* base, uint64_t cols, uint64_t rows, uint64_t pitch_elems,
                       uint32_t box_rows) {
    cuuint64_t gd[2] = {cols, rows};
    cuuint64_t gs[1] = {pitch_elems * 2};
    cuuint32_t bd[2] = {64, box_rows};
    cuuint32_t es[2] = {1, 1};
    enc(tm, CU_TENSOR_MAP_DATA_TYPE_BFLOAT16, 2, const_cast<void*>(base), gd, gs, bd, es, CU_TENSOR_MAP_INTERLEAVE_NONE,
        CU_TENSOR_MAP_SWIZZLE_128B, CU_TENSOR_MAP_L2_PROMOTION_L2_256B, CU_TENSOR_MAP_FLOAT_OOB_FILL_NONE);
}

}

extern "C" void kernel_launch(void* const* d_in, const int* in_sizes, int n_in, void* d_out, int out_size) {
    using namespace hk;
    (void)in_sizes; (void)n_in; (void)out_size;
    static EncodeFn enc = nullptr;
    static int std_layout = 0;
    if (!enc) {
        void* fn = nullptr;
        cudaDriverEntryPointQueryResult qr;
        cudaGetDriverEntryPoint("cuTensorMapEncodeTiled", &fn, cudaEnableDefault, &qr);
        enc = (EncodeFn)fn;
        cudaFuncSetAttribute(fused_kernel, cudaFuncAttributeMaxDynamicSharedMemorySize, SMEM_BYTES);
        int dev = 0, sms = 0;
        cudaGetDevice(&dev);
        cudaDeviceGetAttribute(&sms, cudaDevAttrMultiProcessorCount, dev);
        cudaFuncSetAttribute(probe_kernel, cudaFuncAttributeNonPortableClusterSizeAllowed, 1);
        cudaFuncSetAttribute(probe_kernel, cudaFuncAttributeMaxDynamicSharedMemorySize, SMEM_BYTES);
        const int sizes[3] = {8, 9, 16}, want[3] = {15, 9, 7};
        bool ok = sms == NCTA;
        for (int i = 0; i < 3 && ok; i++) {
            cudaLaunchConfig_t cfg = {};
            cfg.gridDim = dim3(sizes[i] * 8); cfg.blockDim = dim3(NTHREADS); cfg.dynamicSmemBytes = SMEM_BYTES;
            cudaLaunchAttribute at;
            at.id = cudaLaunchAttributeClusterDimension;
            at.val.clusterDim.x = sizes[i]; at.val.clusterDim.y = 1; at.val.clusterDim.z = 1;
            cfg.attrs = &at; cfg.numAttrs = 1;
            int n = 0;
            ok = cudaOccupancyMaxActiveClusters(&n, probe_kernel, &cfg) == cudaSuccess && n == want[i];
        }
        (void)cudaGetLastError();
        std_layout = ok ? 1 : 0;
    }
    Params P;
    const __nv_bfloat16* x = (const __nv_bfloat16*)d_in[0];
    P.x = x;
    P.wqkv = (const __nv_bfloat16*)d_in[1];
    P.wphi = (const __nv_bfloat16*)d_in[2];
    P.wo = (const __nv_bfloat16*)d_in[3];
    P.wg = (const __nv_bfloat16*)d_in[5];
    P.wu = (const __nv_bfloat16*)d_in[6];
    P.wd = (const __nv_bfloat16*)d_in[7];
    P.out = (__nv_bfloat16*)d_out;
    P.zero = 0;
    for (int i = 0; i < NCTA; i++) {
        const int odd = i & 1;
        int role = i < 4 ? 128 + i : (((i - 4) >> 4) * 2 + odd) * 8 + (((i - 4) >> 1) & 7);
        if (std_layout) {
            const int tpc = i < 8 ? 62 + (i >> 1) : (i - 8) >> 1;
            if (tpc < 32) role = (tpc & 7) ? (2 * ((tpc & 7) - 1) + odd) * 8 + (tpc >> 3) : (14 + odd) * 8 + (tpc >> 3);
            else if (tpc < 60) role = (2 * ((tpc - 32) % 7) + odd) * 8 + 4 + (tpc - 32) / 7;
            else if (tpc < 62) role = 128 + (tpc - 60) * 2 + odd;
            else role = (14 + odd) * 8 + 4 + (tpc - 62);
        }
        P.role[i] = (unsigned char)role;
    }
    make_map2d(enc, &P.tx, x, DM, SEQ, DM, 128);
    make_map2d(enc, &P.twq, P.wqkv, 3 * DM, DM, 3 * DM, 64);
    make_map2d(enc, &P.two, P.wo, DM, DM, DM, 64);
    make_map2d(enc, &P.twg, P.wg, FF, DM, FF, 64);
    make_map2d(enc, &P.twu, P.wu, FF, DM, FF, 64);
    make_map2d(enc, &P.twd, P.wd, DM, FF, DM, 64);
    make_map2d(enc, &P.tout, d_out, DM, SEQ, DM, 64);
    fused_kernel<<<NCTA, NTHREADS, SMEM_BYTES>>>(P);
}
```

```cpp
#include <cuda_runtime.h>
#include <cuda_bf16.h>
#include <cuda.h>
#include <stdint.h>

namespace hk {

constexpr int SEQ = 2048, DM = 512, FF = 1376;
constexpr int NCTA = 132;
constexpr int NTHREADS = 384;
constexpr uint32_t SLOT = 16384;
constexpr uint32_t OFF_A = 0, OFF_B = 8 * SLOT, OFF_MISC = 14 * SLOT;
constexpr uint32_t BAR_FULLA = OFF_MISC + 0, BAR_EMPTYA = OFF_MISC + 64, BAR_FULLB = OFF_MISC + 128,
                   BAR_EMPTYB = OFF_MISC + 176, BAR_CS1 = OFF_MISC + 224, BAR_CS3 = OFF_MISC + 232,
                   BAR_CSQ = OFF_MISC + 240, BAR_CSV = OFF_MISC + 248,
                   BAR_STG = OFF_MISC + 256,
                   BAR_KVW = OFF_MISC + 280, BAR_KVR = OFF_MISC + 288, BAR_CSG = OFF_MISC + 296;
constexpr uint32_t OFF_CS1 = OFF_MISC + 384;
constexpr uint32_t OFF_CS3 = OFF_CS1 + 1024;
constexpr uint32_t OFF_XST = OFF_CS3;
constexpr uint32_t SMEM_BYTES = OFF_CS3 + 1536;
#define KVS(j) ((j) == 3 ? 2 : 3)
#define KORD(i, j) ((i) == 0 ? (j) : (i) - ((i) <= (j)))
constexpr int NB = 6;
#define PF_DELAY 2
#define KV_POLL 1
constexpr int AHEAD = 3;

constexpr int ACC_SIZE = 3 * 256 * 4;

__device__ __align__(1024) uint4 g_act[5 * 128 * 1024];
__device__ __align__(128) unsigned long long g_hstat[SEQ * 16];
__device__ __align__(128) unsigned long long g_xstat[SEQ * 2];
__device__ __align__(128) float g_acc[8 * ACC_SIZE];
__device__ __align__(128) unsigned long long g_cs[8 * 6 * 128];
__device__ __align__(128) unsigned g_flag[16 * 5 * 32 + 32];
__device__ unsigned g_epoch = 1;

#define TL(i, pred) do {} while (0)
#define TLG(i, pred) do {} while (0)

struct Params {
    CUtensorMap tx, twq, two, twg, twu, twd, tout;
    const __nv_bfloat16 *x, *wqkv, *wphi, *wo, *wg, *wu, *wd;
    __nv_bfloat16* out;
    unsigned zero;
    unsigned char role[NCTA];
};

__device__ __forceinline__ uint32_t smem_u32(const void* p) { return (uint32_t)__cvta_generic_to_shared(p); }
__device__ __forceinline__ void mbar_init(uint32_t bar, uint32_t cnt) {
    asm volatile("mbarrier.init.shared::cta.b64 [%0], %1;" ::"r"(bar), "r"(cnt) : "memory");
}
__device__ __forceinline__ void mbar_expect_tx(uint32_t bar, uint32_t bytes) {
    asm volatile("mbarrier.arrive.expect_tx.shared::cta.b64 _, [%0], %1;" ::"r"(bar), "r"(bytes) : "memory");
}
__device__ __forceinline__ void mbar_arrive(uint32_t bar) {
    asm volatile("mbarrier.arrive.shared::cta.b64 _, [%0];" ::"r"(bar) : "memory");
}
__device__ __forceinline__ void mbar_arrive_if(uint32_t bar, bool pred) {
    asm volatile("{.reg .pred p; setp.ne.u32 p, %1, 0; @p mbarrier.arrive.shared::cta.b64 _, [%0];}" ::"r"(bar), "r"((uint32_t)pred) : "memory");
}
__device__ __forceinline__ bool mbar_try(uint32_t bar, uint32_t parity) {
    uint32_t ok;
    asm volatile("{.reg .pred p; mbarrier.try_wait.parity.shared::cta.b64 p, [%1], %2; selp.u32 %0,1,0,p;}"
                 : "=r"(ok) : "r"(bar), "r"(parity) : "memory");
    return ok;
}
__device__ __forceinline__ bool mbar_test(uint32_t bar, uint32_t parity) {
    uint32_t ok;
    asm volatile("{.reg .pred p; mbarrier.test_wait.parity.shared::cta.b64 p, [%1], %2; selp.u32 %0,1,0,p;}"
                 : "=r"(ok) : "r"(bar), "r"(parity) : "memory");
    return ok;
}
__device__ __forceinline__ void trap_if_gt(uint32_t v, uint32_t lim) {
    asm volatile("{.reg .pred p; setp.gt.u32 p, %0, %1; @p trap;}" ::"r"(v), "r"(lim));
}
__device__ __forceinline__ void mbar_wait(uint32_t bar, uint32_t parity) {
    asm volatile("{\n"
                 ".reg .pred P1, P2;\n"
                 ".reg .u32 c;\n"
                 "mov.u32 c, 0;\n"
                 "LAB_WAIT:\n"
                 "mbarrier.try_wait.parity.shared::cta.b64 P1, [%0], %1;\n"
                 "@P1 bra LAB_DONE;\n"
                 "add.u32 c, c, 1;\n"
                 "setp.gt.u32 P2, c, 4194304;\n"
                 "@P2 trap;\n"
                 "bra LAB_WAIT;\n"
                 "LAB_DONE:\n"
                 "}" ::"r"(bar), "r"(parity) : "memory");
}
__device__ __forceinline__ void mbar_waitc(uint32_t bar, uint32_t parity) {
    asm volatile("{\n"
                 ".reg .pred P1;\n"
                 "LAB_WAIT:\n"
                 "mbarrier.try_wait.parity.shared::cta.b64 P1, [%0], %1;\n"
                 "@!P1 bra LAB_WAIT;\n"
                 "}" ::"r"(bar), "r"(parity) : "memory");
}
__device__ __forceinline__ void tma2d(uint32_t dst, const CUtensorMap* tm, uint32_t bar, int c0, int c1) {
    asm volatile("cp.async.bulk.tensor.2d.shared::cluster.global.mbarrier::complete_tx::bytes [%0], [%1, {%3, %4}], [%2];"
                 ::"r"(dst), "l"(tm), "r"(bar), "r"(c0), "r"(c1) : "memory");
}
__device__ __forceinline__ void tma2d_mc(uint32_t dst, const CUtensorMap* tm, uint32_t bar, int c0, int c1) {
    asm volatile("cp.async.bulk.tensor.2d.shared::cluster.global.mbarrier::complete_tx::bytes.multicast::cluster [%0], [%1, {%3, %4}], [%2], %5;"
                 ::"r"(dst), "l"(tm), "r"(bar), "r"(c0), "r"(c1), "h"((uint16_t)3) : "memory");
}
__device__ __forceinline__ uint32_t mapa(uint32_t addr, uint32_t rank) {
    uint32_t r; asm("mapa.shared::cluster.u32 %0, %1, %2;" : "=r"(r) : "r"(addr), "r"(rank)); return r;
}
__device__ __forceinline__ void mbar_arrive_cl_if(uint32_t cbar, bool pred) {
    asm volatile("{.reg .pred p; setp.ne.u32 p, %1, 0; @p mbarrier.arrive.shared::cluster.b64 _, [%0];}" ::"r"(cbar), "r"((uint32_t)pred) : "memory");
}
__device__ __forceinline__ bool elect_one() {
    uint32_t ok;
    asm volatile("{.reg .pred p; elect.sync _|p, 0xffffffff; selp.u32 %0, 1, 0, p;}" : "=r"(ok));
    return ok;
}
__device__ __forceinline__ void prefetch_tmap(const CUtensorMap* tm) {
    asm volatile("prefetch.tensormap [%0];" ::"l"(tm) : "memory");
}
__device__ __forceinline__ void prefetch_l2(const void* p, uint32_t bytes) {
    asm volatile("cp.async.bulk.prefetch.L2.global [%0], %1;" ::"l"(p), "r"(bytes) : "memory");
}
__device__ __forceinline__ unsigned ld_acquire(const unsigned* p) {
    unsigned v; asm volatile("ld.acquire.gpu.global.u32 %0, [%1];" : "=r"(v) : "l"(p) : "memory"); return v;
}
__device__ __forceinline__ uint4 ld_acquire4(const unsigned* p) {
    uint4 v;
    asm volatile("ld.acquire.gpu.global.v4.u32 {%0,%1,%2,%3}, [%4];" : "=r"(v.x), "=r"(v.y), "=r"(v.z), "=r"(v.w) : "l"(p) : "memory");
    return v;
}
__device__ __forceinline__ unsigned ld_relaxed(const unsigned* p) {
    unsigned v; asm volatile("ld.relaxed.gpu.global.u32 %0, [%1];" : "=r"(v) : "l"(p)); return v;
}
__device__ __forceinline__ void st_relaxed(unsigned* p, unsigned v) {
    asm volatile("st.relaxed.gpu.global.u32 [%0], %1;" ::"l"(p), "r"(v) : "memory");
}
__device__ __forceinline__ void red_relaxed(unsigned* p, unsigned v) {
    asm volatile("red.relaxed.gpu.global.add.u32 [%0], %1;" ::"l"(p), "r"(v) : "memory");
}
__device__ __forceinline__ void fence_gpu() { asm volatile("fence.acq_rel.gpu;" ::: "memory"); }
__device__ __forceinline__ void fence_async_smem() { asm volatile("fence.proxy.async.shared::cta;" ::: "memory"); }
__device__ __forceinline__ void fence_async_global() { asm volatile("fence.proxy.async.global;" ::: "memory"); }
__device__ __forceinline__ uint32_t readback(const void* p) {
    uint32_t v; asm volatile("ld.relaxed.gpu.global.u32 %0, [%1];" : "=r"(v) : "l"(p) : "memory"); return v;
}
__device__ __forceinline__ void wait_count(const unsigned* p, unsigned target) {
    uint32_t it = 0;
    while ((int)(readback(p) - target) < 0) trap_if_gt(++it, 1u << 22);
}
__device__ __forceinline__ void wait_count_warp(const unsigned* p, unsigned target) {
    uint32_t it = 0;
    while (__any_sync(0xffffffffu, (int)(readback(p) - target) < 0)) trap_if_gt(++it, 1u << 22);
}
__device__ __forceinline__ void red_f32(float* p, float a) {
    asm volatile("red.relaxed.gpu.global.add.f32 [%0], %1;" ::"l"(p), "f"(a) : "memory");
}
__device__ __forceinline__ void red_f32x2(float* p, float a, float b) {
    asm volatile("red.relaxed.gpu.global.add.v2.f32 [%0], {%1, %2};" ::"l"(p), "f"(a), "f"(b) : "memory");
}
__device__ __forceinline__ void red_f32x4(float* p, float a, float b, float c, float d) {
    asm volatile("red.relaxed.gpu.global.add.v4.f32 [%0], {%1, %2, %3, %4};" ::"l"(p), "f"(a), "f"(b), "f"(c), "f"(d) : "memory");
}
__device__ __forceinline__ float4 ld_l2_f4(const float* p) {
    float4 v;
    asm volatile("ld.relaxed.gpu.global.v4.f32 {%0,%1,%2,%3}, [%4];" : "=f"(v.x), "=f"(v.y), "=f"(v.z), "=f"(v.w) : "l"(p) : "memory");
    return v;
}
__device__ __forceinline__ float2 ld_l2_f2(const float* p) {
    float2 v;
    asm volatile("ld.relaxed.gpu.global.v2.f32 {%0,%1}, [%2];" : "=f"(v.x), "=f"(v.y) : "l"(p) : "memory");
    return v;
}
__device__ __forceinline__ float ld_l2_f(const float* p) {
    float v;
    asm volatile("ld.relaxed.gpu.global.f32 %0, [%1];" : "=f"(v) : "l"(p) : "memory");
    return v;
}
__device__ __forceinline__ uint4 ldg_nc(const void* p) {
    uint4 v;
    asm volatile("ld.global.nc.L1::no_allocate.v4.u32 {%0,%1,%2,%3}, [%4];" : "=r"(v.x), "=r"(v.y), "=r"(v.z), "=r"(v.w) : "l"(p));
    return v;
}
__device__ __forceinline__ void stg128(void* p, uint32_t a, uint32_t b, uint32_t c, uint32_t d) {
    asm volatile("st.global.v4.u32 [%0], {%1,%2,%3,%4};" ::"l"(p), "r"(a), "r"(b), "r"(c), "r"(d) : "memory");
}
__device__ __forceinline__ uint4 lds128(uint32_t a) {
    uint4 v;
    asm volatile("ld.shared.v4.u32 {%0,%1,%2,%3}, [%4];" : "=r"(v.x), "=r"(v.y), "=r"(v.z), "=r"(v.w) : "r"(a) : "memory");
    return v;
}
__device__ __forceinline__ float2 lds_f2(uint32_t a) {
    float2 v;
    asm volatile("ld.shared.v2.f32 {%0,%1}, [%2];" : "=f"(v.x), "=f"(v.y) : "r"(a) : "memory");
    return v;
}
__device__ __forceinline__ void sts_f2(uint32_t a, float x, float y) {
    asm volatile("st.shared.v2.f32 [%0], {%1,%2};" ::"r"(a), "f"(x), "f"(y) : "memory");
}
__device__ __forceinline__ void sts64(uint32_t a, uint32_t x, uint32_t y) {
    asm volatile("st.shared.v2.u32 [%0], {%1,%2};" ::"r"(a), "r"(x), "r"(y) : "memory");
}
__device__ __forceinline__ void sts128(uint32_t a, uint32_t x, uint32_t y, uint32_t z, uint32_t w) {
    asm volatile("st.shared.v4.u32 [%0], {%1,%2,%3,%4};" ::"r"(a), "r"(x), "r"(y), "r"(z), "r"(w) : "memory");
}
__device__ __forceinline__ void stsm4(uint32_t a, uint32_t r0, uint32_t r1, uint32_t r2, uint32_t r3) {
    asm volatile("stmatrix.sync.aligned.m8n8.x4.shared.b16 [%0], {%1,%2,%3,%4};" ::"r"(a), "r"(r0), "r"(r1), "r"(r2), "r"(r3) : "memory");
}
__device__ __forceinline__ void stsm4t(uint32_t a, uint32_t r0, uint32_t r1, uint32_t r2, uint32_t r3) {
    asm volatile("stmatrix.sync.aligned.m8n8.x4.trans.shared.b16 [%0], {%1,%2,%3,%4};" ::"r"(a), "r"(r0), "r"(r1), "r"(r2), "r"(r3) : "memory");
}
__device__ __forceinline__ void tma_store2d(const CUtensorMap* tm, uint32_t src, int c0, int c1) {
    asm volatile("cp.async.bulk.tensor.2d.global.shared::cta.bulk_group [%0, {%2, %3}], [%1];" ::"l"(tm), "r"(src), "r"(c0), "r"(c1) : "memory");
    asm volatile("cp.async.bulk.commit_group;" ::: "memory");
}
__device__ __forceinline__ void ldsm4(uint32_t a, uint32_t& r0, uint32_t& r1, uint32_t& r2, uint32_t& r3) {
    asm volatile("ldmatrix.sync.aligned.m8n8.x4.shared.b16 {%0,%1,%2,%3}, [%4];" : "=r"(r0), "=r"(r1), "=r"(r2), "=r"(r3) : "r"(a) : "memory");
}
__device__ __forceinline__ void ldsm4t(uint32_t a, uint32_t& r0, uint32_t& r1, uint32_t& r2, uint32_t& r3) {
    asm volatile("ldmatrix.sync.aligned.m8n8.x4.trans.shared.b16 {%0,%1,%2,%3}, [%4];" : "=r"(r0), "=r"(r1), "=r"(r2), "=r"(r3) : "r"(a) : "memory");
}
__device__ __forceinline__ void mma16816(float* c, const uint32_t* a, uint32_t b0, uint32_t b1) {
    asm("mma.sync.aligned.m16n8k16.row.col.f32.bf16.bf16.f32 {%0,%1,%2,%3}, {%4,%5,%6,%7}, {%8,%9}, {%0,%1,%2,%3};"
                 : "+f"(c[0]), "+f"(c[1]), "+f"(c[2]), "+f"(c[3])
                 : "r"(a[0]), "r"(a[1]), "r"(a[2]), "r"(a[3]), "r"(b0), "r"(b1));
}
__device__ __forceinline__ uint32_t pack_bf16(float lo, float hi) {
    uint32_t r; asm("cvt.rn.bf16x2.f32 %0, %1, %2;" : "=r"(r) : "f"(hi), "f"(lo)); return r;
}
__device__ __forceinline__ float bf_lo(uint32_t w) { return __uint_as_float(w << 16); }
__device__ __forceinline__ float bf_hi(uint32_t w) { return __uint_as_float(w & 0xffff0000u); }
__device__ __forceinline__ float ex2(float x) { float r; asm("ex2.approx.ftz.f32 %0, %1;" : "=f"(r) : "f"(x)); return r; }
__device__ __forceinline__ float rcp(float x) { float r; asm("rcp.approx.ftz.f32 %0, %1;" : "=f"(r) : "f"(x)); return r; }
__device__ __forceinline__ void bar_sync(int id, int n) { asm volatile("bar.sync %0, %1;" ::"r"(id), "r"(n) : "memory"); }

typedef unsigned long long desc_t;
__device__ __forceinline__ desc_t desc_lo(uint32_t addr) { return (desc_t)(((addr & 0x3FFFF) >> 4) | (512u << 16)) | (0x40000040ull << 32); }
__device__ __forceinline__ void wg_fence() { asm volatile("wgmma.fence.sync.aligned;" ::: "memory"); }
__device__ __forceinline__ void wg_commit() { asm volatile("wgmma.commit_group.sync.aligned;" ::: "memory"); }
template <int N> __device__ __forceinline__ void wg_wait() { asm volatile("wgmma.wait_group.sync.aligned %0;" ::"n"(N) : "memory"); }
template <int N> __device__ __forceinline__ void fence_acc(float* d) {
#pragma unroll
    for (int i = 0; i < N; i++) asm volatile("" : "+f"(d[i])::"memory");
}
#define R4(o) "+f"(d[o + 0]), "+f"(d[o + 1]), "+f"(d[o + 2]), "+f"(d[o + 3])
#define R8(o) R4(o), R4(o + 4)
__device__ __forceinline__ void wgmma_n128(float* d, desc_t da, desc_t db, int sc) {
    asm volatile("{.reg .pred p; setp.ne.b32 p, %66, 0;\n"
                 "wgmma.mma_async.sync.aligned.m64n128k16.f32.bf16.bf16 {%0,%1,%2,%3,%4,%5,%6,%7,%8,%9,%10,%11,%12,%13,%14,%15,%16,%17,%18,%19,%20,%21,%22,%23,%24,%25,%26,%27,%28,%29,%30,%31,"
                 "%32,%33,%34,%35,%36,%37,%38,%39,%40,%41,%42,%43,%44,%45,%46,%47,%48,%49,%50,%51,%52,%53,%54,%55,%56,%57,%58,%59,%60,%61,%62,%63}, %64, %65, p, 1, 1, 0, 1;}"
                 : R8(0), R8(8), R8(16), R8(24), R8(32), R8(40), R8(48), R8(56)
                 : "l"(da), "l"(db), "r"(sc));
}
__device__ __forceinline__ void wgmma_n112(float* d, desc_t da, desc_t db, int sc) {
    asm volatile("{.reg .pred p; setp.ne.b32 p, %58, 0;\n"
                 "wgmma.mma_async.sync.aligned.m64n112k16.f32.bf16.bf16 {%0,%1,%2,%3,%4,%5,%6,%7,%8,%9,%10,%11,%12,%13,%14,%15,%16,%17,%18,%19,%20,%21,%22,%23,%24,%25,%26,%27,%28,%29,%30,%31,%32,%33,%34,%35,%36,%37,%38,%39,%40,%41,%42,%43,%44,%45,%46,%47,%48,%49,%50,%51,%52,%53,%54,%55}, %56, %57, p, 1, 1, 0, 1;}"
                 : R8(0), R8(8), R8(16), R8(24), R8(32), R8(40), R8(48)
                 : "l"(da), "l"(db), "r"(sc));
}
__device__ __forceinline__ void wgmma_n128_tn(float* d, desc_t da, desc_t db, int sc) {
    asm volatile("{.reg .pred p; setp.ne.b32 p, %66, 0;\n"
                 "wgmma.mma_async.sync.aligned.m64n128k16.f32.bf16.bf16 {%0,%1,%2,%3,%4,%5,%6,%7,%8,%9,%10,%11,%12,%13,%14,%15,%16,%17,%18,%19,%20,%21,%22,%23,%24,%25,%26,%27,%28,%29,%30,%31,%32,%33,%34,%35,%36,%37,%38,%39,%40,%41,%42,%43,%44,%45,%46,%47,%48,%49,%50,%51,%52,%53,%54,%55,%56,%57,%58,%59,%60,%61,%62,%63}, %64, %65, p, 1, 1, 1, 0;}"
                 : R8(0), R8(8), R8(16), R8(24), R8(32), R8(40), R8(48), R8(56)
                 : "l"(da), "l"(db), "r"(sc));
}
__device__ __forceinline__ void wgmma_n64(float* d, desc_t da, desc_t db, int sc) {
    asm volatile("{.reg .pred p; setp.ne.b32 p, %34, 0;\n"
                 "wgmma.mma_async.sync.aligned.m64n64k16.f32.bf16.bf16 {%0,%1,%2,%3,%4,%5,%6,%7,%8,%9,%10,%11,%12,%13,%14,%15,%16,%17,%18,%19,%20,%21,%22,%23,%24,%25,%26,%27,%28,%29,%30,%31}, %32, %33, p, 1, 1, 0, 1;}"
                 : R8(0), R8(8), R8(16), R8(24)
                 : "l"(da), "l"(db), "r"(sc));
}
__device__ __forceinline__ void wgmma_n40_tt(float* d, desc_t da, desc_t db, int sc) {
    asm volatile("{.reg .pred p; setp.ne.b32 p, %22, 0;\n"
                 "wgmma.mma_async.sync.aligned.m64n40k16.f32.bf16.bf16 {%0,%1,%2,%3,%4,%5,%6,%7,%8,%9,%10,%11,%12,%13,%14,%15,%16,%17,%18,%19}, %20, %21, p, 1, 1, 1, 1;}"
                 : R8(0), R8(8), R4(16)
                 : "l"(da), "l"(db), "r"(sc));
}

__device__ __forceinline__ void wgmma_n8_tt(float* d, desc_t da, desc_t db, int sc) {
    asm volatile("{.reg .pred p; setp.ne.b32 p, %6, 0;\n"
                 "wgmma.mma_async.sync.aligned.m64n8k16.f32.bf16.bf16 {%0,%1,%2,%3}, %4, %5, p, 1, 1, 1, 1;}"
                 : R4(0)
                 : "l"(da), "l"(db), "r"(sc));
}

__device__ __forceinline__ void signal_after(unsigned* cnt, uint32_t ack, uint32_t zero, bool pred) {
    asm volatile("{.reg .pred p; setp.ne.u32 p, %2, 0; @p red.relaxed.gpu.global.add.u32 [%0], %1;}"
                 ::"l"(cnt), "r"((ack & zero) + 1), "r"((uint32_t)pred) : "memory");
}
__device__ __forceinline__ void signal_late(unsigned* cnt, const uint32_t* a, uint32_t zero, bool pred) {
    uint32_t v;
    asm volatile("{.reg .b32 t; lop3.b32 t, %1, %2, %3, 0xfe; or.b32 %0, t, %4;}"
                 : "=r"(v) : "r"(a[0]), "r"(a[1]), "r"(a[2]), "r"(a[3]));
    signal_after(cnt, v, zero, pred);
}
__device__ __forceinline__ void red_f32_if(float* p, float a, bool pred) {
    asm volatile("{.reg .pred p; setp.ne.u32 p, %2, 0; @p red.relaxed.gpu.global.add.f32 [%0], %1;}" ::"l"(p), "f"(a), "r"((uint32_t)pred) : "memory");
}
__device__ __forceinline__ void stg_f2_if(float* p, float a, float b, bool pred) {
    asm volatile("{.reg .pred p; setp.ne.u32 p, %3, 0; @p st.global.v2.f32 [%0], {%1,%2};}" ::"l"(p), "f"(a), "f"(b), "r"((uint32_t)pred) : "memory");
}
__device__ __forceinline__ void stg64(void* p, uint32_t a, uint32_t b) {
    asm volatile("st.global.v2.u32 [%0], {%1,%2};" ::"l"(p), "r"(a), "r"(b) : "memory");
}
__device__ __forceinline__ void mma16816_z(float* c, const uint32_t* a, uint32_t b0, uint32_t b1) {
    asm("mma.sync.aligned.m16n8k16.row.col.f32.bf16.bf16.f32 {%0,%1,%2,%3}, {%4,%5,%6,%7}, {%8,%9}, {%10,%10,%10,%10};"
                 : "=f"(c[0]), "=f"(c[1]), "=f"(c[2]), "=f"(c[3])
                 : "r"(a[0]), "r"(a[1]), "r"(a[2]), "r"(a[3]), "r"(b0), "r"(b1), "f"(0.f));
}
__device__ __forceinline__ uint32_t max2(uint32_t a, uint32_t b) { uint32_t r; asm("max.bf16x2 %0, %1, %2;" : "=r"(r) : "r"(a), "r"(b)); return r; }
__device__ __forceinline__ uint32_t min2(uint32_t a, uint32_t b) { uint32_t r; asm("min.bf16x2 %0, %1, %2;" : "=r"(r) : "r"(a), "r"(b)); return r; }
__device__ __forceinline__ void bar_arrive(int id, int n) { asm volatile("bar.arrive %0, %1;" ::"r"(id), "r"(n) : "memory"); }
__device__ __forceinline__ void mbar_arrive_n_if(uint32_t bar, uint32_t n, bool pred) {
    asm volatile("{.reg .pred p; setp.ne.u32 p, %1, 0; @p mbarrier.arrive.shared::cta.b64 _, [%0], %2;}" ::"r"(bar), "r"((uint32_t)pred), "r"(n) : "memory");
}
__device__ __forceinline__ float4 lds_f4(uint32_t a) {
    float4 v;
    asm volatile("ld.shared.v4.f32 {%0,%1,%2,%3}, [%4];" : "=f"(v.x), "=f"(v.y), "=f"(v.z), "=f"(v.w) : "r"(a) : "memory");
    return v;
}
__device__ __forceinline__ void lds_f4_if(float4& v, uint32_t a, bool pred) {
    asm volatile("{.reg .pred p; setp.ne.u32 p, %5, 0; @p ld.shared.v4.f32 {%0,%1,%2,%3}, [%4];}"
                 : "+f"(v.x), "+f"(v.y), "+f"(v.z), "+f"(v.w) : "r"(a), "r"((uint32_t)pred) : "memory");
}
__device__ __forceinline__ uint4 ld_tagged(const unsigned long long* p) {
    unsigned long long a, b;
    asm volatile("ld.acquire.gpu.global.v2.b64 {%0,%1}, [%2];" : "=l"(a), "=l"(b) : "l"(p) : "memory");
    return make_uint4((unsigned)a, (unsigned)(a >> 32), (unsigned)b, (unsigned)(b >> 32));
}
__device__ __forceinline__ uint4 ld_tagged_rlx(const unsigned long long* p) {
    unsigned long long a, b;
    asm volatile("ld.relaxed.gpu.global.v2.b64 {%0,%1}, [%2];" : "=l"(a), "=l"(b) : "l"(p) : "memory");
    return make_uint4((unsigned)a, (unsigned)(a >> 32), (unsigned)b, (unsigned)(b >> 32));
}
__device__ __forceinline__ void sts32(uint32_t a, uint32_t x) { asm volatile("st.shared.u32 [%0], %1;" ::"r"(a), "r"(x) : "memory"); }
__device__ __forceinline__ void fetch_tagged(const unsigned long long* src, uint32_t dst, unsigned epoch) {
    uint4 v;
    uint32_t it = 0;
    while (true) {
        v = ld_tagged_rlx(src);
        if (!__any_sync(0xffffffffu, v.y != epoch || v.w != epoch)) break;
        __nanosleep(60);
        trap_if_gt(++it, 1u << 22);
    }
    sts64(dst, v.x, v.z);
}
__device__ __forceinline__ void st_tagged_if(unsigned long long* p, float a, float b, unsigned tag, bool pred) {
    const unsigned long long t = (unsigned long long)tag << 32;
    asm volatile("{.reg .pred p; setp.ne.u32 p, %3, 0; @p st.relaxed.gpu.global.v2.b64 [%0], {%1,%2};}"
                 ::"l"(p), "l"(t | __float_as_uint(a)), "l"(t | __float_as_uint(b)), "r"((uint32_t)pred) : "memory");
}

__device__ __forceinline__ void store_tile(uint32_t tile_rows, uint4* gdst, const uint32_t* lo, const uint32_t* hi, int lane, uint32_t* ack) {
    const int r = lane & 15;
#pragma unroll
    for (int b = 0; b < 4; b++)
        stsm4(tile_rows + r * 128 + (((2 * b + (lane >> 4)) ^ (r & 7)) << 4), lo[2 * b], hi[2 * b], lo[2 * b + 1], hi[2 * b + 1]);
    fence_async_smem();
    __syncwarp();
#pragma unroll
    for (int i = 0; i < 4; i++) {
        const uint4 v = lds128(tile_rows + i * 512 + lane * 16);
        stg128(gdst + 32 * i, v.x, v.y, v.z, v.w);
    }
#pragma unroll
    for (int i = 0; i < 4; i++) ack[i] = readback(gdst + 32 * i);
}

template <class Hook>
__device__ __forceinline__ void feature_maps(const uint32_t* a, const uint32_t* wb, float c0, float c1, uint32_t* plus, uint32_t* minus, Hook hook) {
    uint32_t P[16], mx[4], mn[4];
#pragma unroll
    for (int h = 0; h < 4; h++) {
        float p[8];
        mma16816_z(p, a + 4 * h, wb[4 * h], wb[4 * h + 1]);
        mma16816_z(p + 4, a + 4 * h, wb[4 * h + 2], wb[4 * h + 3]);
        P[4 * h] = pack_bf16(p[0], p[2]); P[4 * h + 1] = pack_bf16(p[1], p[3]);
        P[4 * h + 2] = pack_bf16(p[4], p[6]); P[4 * h + 3] = pack_bf16(p[5], p[7]);
        mx[h] = max2(max2(P[4 * h], P[4 * h + 1]), max2(P[4 * h + 2], P[4 * h + 3]));
        mn[h] = min2(min2(P[4 * h], P[4 * h + 1]), min2(P[4 * h + 2], P[4 * h + 3]));
    }
#pragma unroll
    for (int s = 1; s <= 2; s <<= 1) {
        uint32_t tx[4], tn[4];
#pragma unroll
        for (int h = 0; h < 4; h++) { tx[h] = __shfl_xor_sync(0xffffffffu, mx[h], s); tn[h] = __shfl_xor_sync(0xffffffffu, mn[h], s); }
#pragma unroll
        for (int h = 0; h < 4; h++) { mx[h] = max2(mx[h], tx[h]); mn[h] = min2(mn[h], tn[h]); }
    }
#pragma unroll
    for (int h = 0; h < 4; h++) {
        hook(h);
        const float mx0 = bf_lo(mx[h]) * c0, mx1 = bf_hi(mx[h]) * c1, mn0 = bf_lo(mn[h]) * c0, mn1 = bf_hi(mn[h]) * c1;
        float ep[8], em[8];
#pragma unroll
        for (int i = 0; i < 8; i++) {
            const bool r1 = (i & 2);
            const uint32_t w = P[4 * h + (i >> 2) * 2 + (i & 1)];
            const float p = r1 ? bf_hi(w) : bf_lo(w);
            ep[i] = ex2(fmaf(p, r1 ? c1 : c0, r1 ? -mx1 : -mx0));
            em[i] = ex2(fmaf(p, r1 ? -c1 : -c0, r1 ? mn1 : mn0));
        }
        float sp[4], sm[4];
        uint32_t tp[4], tm[4];
#pragma unroll
        for (int i = 0; i < 4; i++) { tp[i] = pack_bf16(ep[2 * i], ep[2 * i + 1]); tm[i] = pack_bf16(em[2 * i], em[2 * i + 1]); }
        mma16816_z(sp, tp, 0x3f803f80u, 0x3f803f80u);
        mma16816_z(sm, tm, 0x3f803f80u, 0x3f803f80u);
        const float r0 = rcp(sp[0] * sm[0]), r1 = rcp(sp[2] * sm[2]);
        const float rs[4] = {r0 * sm[0], r1 * sm[2], r0 * sp[0], r1 * sp[2]};
#pragma unroll
        for (int i = 0; i < 4; i++) {
            plus[4 * h + i] = pack_bf16(ep[2 * i] * rs[i & 1], ep[2 * i + 1] * rs[i & 1]);
            minus[4 * h + i] = pack_bf16(em[2 * i] * rs[2 + (i & 1)], em[2 * i + 1] * rs[2 + (i & 1)]);
        }
    }
}

template <bool SCALE>
__device__ __forceinline__ void ln_frag(const float* acc, uint32_t cs_addr, float rs0, float nm0, float rs1, float nm1, uint32_t* a) {
    const float2 c0 = lds_f2(cs_addr), c1 = lds_f2(cs_addr + 32);
    const float s0 = SCALE ? rs0 : 1.f, s1 = SCALE ? rs1 : 1.f;
    a[0] = pack_bf16(fmaf(nm0, c0.x, acc[0]) * s0, fmaf(nm0, c0.y, acc[1]) * s0);
    a[1] = pack_bf16(fmaf(nm1, c0.x, acc[2]) * s1, fmaf(nm1, c0.y, acc[3]) * s1);
    a[2] = pack_bf16(fmaf(nm0, c1.x, acc[4]) * s0, fmaf(nm0, c1.y, acc[5]) * s0);
    a[3] = pack_bf16(fmaf(nm1, c1.x, acc[6]) * s1, fmaf(nm1, c1.y, acc[7]) * s1);
}

template <int UP>
__device__ __forceinline__ uint32_t hh_pair(const float* ag, float4 cs, float nmean) {
    const float g0 = fmaf(nmean, cs.x, ag[0]), g1 = fmaf(nmean, cs.y, ag[1]);
    const float u0 = fmaf(nmean, cs.z, ag[UP]), u1 = fmaf(nmean, cs.w, ag[UP + 1]);
    return pack_bf16(g0 * u0, g1 * u1);
}
template <int NTP>
__device__ __forceinline__ void hh_stage(const float* acc, const float4* cs, float nm0, float nm1, uint32_t stg, int lane) {
#pragma unroll
    for (int tp = 0; tp < NTP; tp++)
        stsm4(stg + (lane & 15) * 128 + (((2 * tp + (lane >> 4)) ^ (lane & 7)) << 4), hh_pair<32>(acc + 8 * tp, cs[2 * tp], nm0),
              hh_pair<32>(acc + 8 * tp + 2, cs[2 * tp], nm1), hh_pair<32>(acc + 8 * tp + 4, cs[2 * tp + 1], nm0),
              hh_pair<32>(acc + 8 * tp + 6, cs[2 * tp + 1], nm1));
    fence_async_smem();
    __syncwarp();
}

struct Ring {
    int slot; uint32_t phase;
    __device__ __forceinline__ void adv() { if (++slot == NB) { slot = 0; phase ^= 1; } }
    __device__ __forceinline__ void adv5() { slot += slot == 3; adv(); }
};

__global__ void __cluster_dims__(2, 1, 1) __launch_bounds__(NTHREADS, 1) fused_kernel(const __grid_constant__ Params P) {
    extern __shared__ __align__(1024) uint8_t smem_raw[];
    const uint32_t sb = smem_u32(smem_raw);
    const int tid = threadIdx.x, lane = tid & 31;
    const int warp = __shfl_sync(0xffffffffu, tid >> 5, 0);
    const unsigned role = P.role[blockIdx.x], rank = blockIdx.x & 1;
    const int m = role >> 3, j = role & 7;
    const bool helper = role >= 128;

    TL(0, tid == 0); TLG(0, tid == 0);
    float* const acc_j = g_acc + j * ACC_SIZE;

    if (__builtin_expect(warp >= 8, 1)) {
        asm volatile("setmaxnreg.dec.sync.aligned.u32 72;");
        if (elect_one()) {
            if (warp == 8) {
                if (!helper) {
#pragma unroll
                    for (int i = 0; i < NB; i++) mbar_init(sb + BAR_FULLB + 8 * i, 1);
#pragma unroll
                    for (int i = 0; i < 2; i++) {
                        mbar_expect_tx(sb + BAR_FULLB + 8 * i, SLOT);
                        tma2d(sb + OFF_B + i * SLOT, &P.twq, sb + BAR_FULLB + 8 * i, DM + 64 * j, 64 * i);
                        tma2d(sb + OFF_B + i * SLOT + 8192, &P.twq, sb + BAR_FULLB + 8 * i, 2 * DM + 64 * j, 64 * i);
                    }
                }
            } else if (warp == 9) {
#pragma unroll
                for (int i = 0; i < 8; i++) mbar_init(sb + BAR_FULLA + 8 * i, 1);
                if (!helper) {
#pragma unroll
                    for (int i = 0; i < 2; i++) {
                        mbar_expect_tx(sb + BAR_FULLA + 8 * i, SLOT);
                        tma2d(sb + OFF_A + i * SLOT, &P.tx, sb + BAR_FULLA + 8 * i, 64 * i, 128 * m);
                    }
                }
            } else if (warp == 10) {
#pragma unroll
                for (int i = 0; i < 12; i++) mbar_init(sb + BAR_CS1 + 8 * i, i < 2 || i >= 8 ? 64 : (i < 4 ? 32 : 8));
                trap_if_gt(sb & 1023, 0);
            } else {
#pragma unroll
                for (int i = 0; i < 14; i++) mbar_init(sb + (i < 8 ? BAR_EMPTYA : BAR_EMPTYB - 64) + 8 * i, i < 8 ? 8 : 16);
            }
            asm volatile("fence.mbarrier_init.release.cluster;" ::: "memory");
        }
        __syncwarp();
        asm volatile("barrier.cluster.arrive.relaxed.aligned;" ::: "memory");
        const unsigned epoch = ld_relaxed(&g_epoch);
        bar_sync(0, NTHREADS);
        if (helper) {
            if (warp == 8) {
                if (elect_one()) {
#pragma unroll 1
                    for (int i = 0; i < 72; i++) {
                        const uint32_t full = sb + BAR_FULLA + 8 * (i & 7), dst = sb + OFF_A + (i & 7) * SLOT;
                        mbar_wait(sb + BAR_EMPTYA + 8 * (i & 7), ((i >> 3) & 1) ^ 1);
                        mbar_expect_tx(full, SLOT);
                        const bool qkv = i < 24;
                        const int u = (i >> 3) - 3;
                        const int c0 = qkv ? (i < 16 ? DM + 64 * (i & 8) : 0) + 128 * j + 16 * (i & 4) : 176 * (2 * j + (u & 1)) + 64 * (u >> 1);
                        const int r0 = qkv ? 128 * (i & 3) : 64 * (i & 7);
                        tma2d(dst, qkv ? &P.twq : &P.twg, full, c0, r0);
                        tma2d(dst + 8192, qkv ? &P.twq : &P.twu, full, c0, qkv ? r0 + 64 : r0);
                    }
                    prefetch_l2(P.wd + (size_t)j * 176128, 352256);
                }
            }
            return;
        }
        if (warp == 8) {
            asm volatile("barrier.cluster.wait.aligned;" ::: "memory");
            if (elect_one()) {
                if (m >= 6)
                    asm volatile("cp.async.bulk.prefetch.tensor.2d.L2.global [%0, {%1, %2}];" ::"l"(&P.twq), "r"(DM + DM * (m & 1) + 64 * j), "r"(64 * (m >> 1)) : "memory");
                if (j >= 3)
                    asm volatile("cp.async.bulk.prefetch.tensor.2d.L2.global [%0, {%1, %2}];" ::"l"(&P.tx), "r"(64 * j), "r"(128 * m) : "memory");
                Ring r{2, 0};
                const uint32_t dst = sb + OFF_B + rank * 8192;
#define B_LOAD(TM, C0, R0)                                                                                  \
        mbar_waitc(sb + BAR_EMPTYB + 8 * r.slot, r.phase ^ 1);                                              \
        mbar_expect_tx(sb + BAR_FULLB + 8 * r.slot, SLOT);                                                  \
        tma2d_mc(dst + r.slot * SLOT, TM, sb + BAR_FULLB + 8 * r.slot, C0, R0);
#pragma unroll 1
                for (int i = 2; i < 8; i++) {
                    if (i >= AHEAD && i < 6) mbar_waitc(sb + BAR_FULLB + 8 * (i - AHEAD), 0);
                    B_LOAD(&P.twq, DM + DM * rank + 64 * j, 64 * i)
                    r.adv();
                }
#pragma unroll 1
                for (int i = 8; i < 20; i++) {
                    if (i >= 10 && i < 14) {
                        mbar_waitc(sb + BAR_EMPTYB + 8 * r.slot, r.phase ^ 1);
                        mbar_arrive(sb + BAR_FULLB + 8 * r.slot);
                    } else {
                        const int e = 2 * (i & 3) + rank;
                        B_LOAD(i < 16 ? &P.twq : &P.two, 64 * j, 64 * (i < 16 ? e : KORD(e, j)))
                    }
                    r.adv();
                }
#pragma unroll 1
                for (int i = 0; i < 24; i++) {
                    B_LOAD(&P.twg + rank, 176 * j + 8 * (i & ~7), 64 * (i < 8 ? KORD(i, j) : i & 7))
                    r.adv5();
                }
#pragma unroll 1
                for (int i = 0; i < 12; i++) {
                    B_LOAD(&P.twd, 64 * j, 176 * (2 * (i & 3) + rank) + 64 * (i >> 2))
                    r.adv5();
                }
            }
            return;
        }
        if (warp == 9) {
            if (elect_one()) {
#pragma unroll 1
                for (int i = 2; i < 8; i++) {
                    if (i >= AHEAD + 1) mbar_wait(sb + BAR_FULLA + 8 * (i - AHEAD - 1), 0);
                    mbar_expect_tx(sb + BAR_FULLA + 8 * i, SLOT);
                    tma2d(sb + OFF_A + i * SLOT, &P.tx, sb + BAR_FULLA + 8 * i, 64 * i, 128 * m);
                }
#pragma unroll 1
                for (int i = 2; i < 7; i++) prefetch_tmap(&P.tx + i);
                unsigned nf = 0;
#pragma unroll 1
                for (int r = 1; r < 6; r++) {
                    const int skip = r < 3 ? j : 8;
                    const uint4* src = g_act + ((r - 1) * 128 + m * 8) * 1024;
                    const unsigned* fl = g_flag + (m * 5 + r - 1) * 32;
                    if (r < 4) mbar_wait(sb + BAR_EMPTYA + 8 * (r == 3 ? PF_DELAY : skip == 0), (r - 1) & 1);
                    if (r < 4 || nf != epoch * 8) wait_count(fl, epoch * (r < 3 ? 64 : 8));
                    TL(64 + r, true);
#pragma unroll 1
                    for (int t = 0; t < 8; t++) {
                        if (t == skip) continue;
                        if (t == 6) nf = readback(fl + 32);
                        mbar_wait(sb + BAR_EMPTYA + 8 * t, (r - 1) & 1);
                        mbar_expect_tx(sb + BAR_FULLA + 8 * t, SLOT);
                        asm volatile("cp.async.bulk.shared::cluster.global.mbarrier::complete_tx::bytes [%0], [%1], %2, [%3];"
                                     ::"r"(sb + OFF_A + t * SLOT), "l"(src + t * 1024), "r"(SLOT), "r"(sb + BAR_FULLA + 8 * t) : "memory");
                    }
                }
            }
            return;
        }
        const int a = warp - 10;
        {
            const int row = 16 * j + 8 * a + (lane >> 2);
            const uint32_t ra = sb + OFF_A + row * 128;
            float sh = 0.f, s0 = 0.f, s1 = 0.f, q0 = 0.f, q1 = 0.f;
#pragma unroll 1
            for (int kt = 0; kt < 8; kt++) {
                mbar_wait(sb + BAR_FULLA + 8 * kt, 0);
                if (kt == 0) sh = bf_lo(lds128(ra + ((row & 7) << 4)).x);
#pragma unroll
                for (int i = 0; i < 2; i++) {
                    const uint4 v = lds128(ra + kt * SLOT + (((2 * (lane & 3) + i) ^ (row & 7)) << 4));
                    const uint32_t ww[4] = {v.x, v.y, v.z, v.w};
#pragma unroll
                    for (int e = 0; e < 4; e++) {
                        const float d0 = bf_lo(ww[e]) - sh, d1 = bf_hi(ww[e]) - sh;
                        s0 += d0; q0 = fmaf(d0, d0, q0);
                        s1 += d1; q1 = fmaf(d1, d1, q1);
                    }
                }
            }
            s0 += s1; q0 += q1;
#pragma unroll
            for (int o = 1; o <= 2; o <<= 1) { s0 += __shfl_xor_sync(0xffffffffu, s0, o); q0 += __shfl_xor_sync(0xffffffffu, q0, o); }
            const float md = s0 * (1.f / DM);
            const float rs = rsqrtf(fmaxf(q0 * (1.f / DM) - md * md, 0.f) + 1e-5f);
            st_tagged_if(g_xstat + 2 * (128 * m + row), rs, -(sh + md), epoch, (lane & 3) == 0);
        }
        const unsigned long long* cs = g_cs + j * 768 + 2 * lane;
#pragma unroll 1
        for (int c = 0; c < 3 + a; c++) {
            fetch_tagged(c < 2 ? g_xstat + 2 * (128 * m + 64 * a + 32 * c + lane) : cs + 128 * (a + c - 2),
                         sb + (c < 2 ? OFF_XST + (64 * a + 32 * c) * 8 : OFF_CS1 + (c == 2 ? 256 * (a + 1) : 0)) + 8 * lane, epoch);
            if (c >= 2 - a) mbar_arrive(sb + (c == 2 - a ? BAR_CS1 : (c == 2 ? BAR_CSV : BAR_CSQ)));
        }
        {
            mbar_wait(sb + BAR_KVW, 0);
            const float* src = acc_j + 4 * (128 * a + lane);
            float4 v[12];
            uint32_t it = 0;
            bool bad;
            while (__any_sync(0xffffffffu, readback(acc_j + 2048 + 128 * (lane & 7) + 127) != 0x41800000u)) trap_if_gt(++it, 1u << 22);
            TL(19, lane == 0 && a == 0);
            do {
                bad = false;
#pragma unroll
                for (int i = 0; i < 12; i++) v[i] = ld_l2_f4(src + 1024 * (i % 3) + 128 * (i / 3));
#pragma unroll
                for (int i = 0; i < 12; i++) bad |= v[i].w != 16.f;
                trap_if_gt(++it, 1u << 22);
            } while (__any_sync(0xffffffffu, bad));
            TL(14, lane == 0 && a == 0);
            const uint32_t d0 = sb + OFF_A + KVS(j) * SLOT + (64 * a + (lane >> 2)) * 48;
            const uint32_t d = d0 + (lane & 3) * 4, dz = d0 + (lane & 1) * 384 + 32 + (lane & 2) * 4;
#pragma unroll
            for (int u = 0; u < 4; u++) {
                sts32(d + 768 * u, pack_bf16(v[3 * u].x, v[3 * u].y));
                sts32(d + 768 * u + 384, pack_bf16(v[3 * u].z, v[3 * u + 1].z));
                sts32(d + 768 * u + 16, pack_bf16(v[3 * u + 1].x, v[3 * u + 1].y));
                sts32(d + 768 * u + 400, pack_bf16(v[3 * u + 2].x, v[3 * u + 2].y));
                const uint32_t z2 = pack_bf16(v[3 * u + 2].z, v[3 * u + 2].z);
                sts64(dz + 768 * u, z2, z2);
            }
            mbar_arrive(sb + BAR_KVR);
        }
#pragma unroll 1
        for (int c = 0; c < 3; c++) {
            fetch_tagged(cs + 384 + 128 * c + 64 * a, sb + OFF_CS3 + (32 * c + lane) * 16 + 8 * a, epoch);
            mbar_arrive(sb + BAR_CSG + 8 * c);
        }
        {
            uint32_t it = 0;
            while (__any_sync(0xffffffffu, (int)(readback(g_flag + (m * 5 + 1) * 32) - epoch * 64) < 0)) {
                __nanosleep(200);
                trap_if_gt(++it, 1u << 22);
            }
#pragma unroll 1
            for (int rr = 0; rr < 2; rr++) {
                const int row = 64 * rr + 32 * a + lane;
                const unsigned long long* hs = g_hstat + (1024 * m + row) * 2;
                uint4 v[8];
                bool bad;
                do {
                    bad = false;
#pragma unroll
                    for (int i = 0; i < 8; i++) v[i] = ld_tagged_rlx(hs + 256 * i);
#pragma unroll
                    for (int i = 0; i < 8; i++) bad |= v[i].y != epoch || v[i].w != epoch;
                    trap_if_gt(++it, 1u << 22);
                } while (__any_sync(0xffffffffu, bad));
                float mean = 0.f;
#pragma unroll
                for (int i = 0; i < 8; i++) mean += __uint_as_float(v[i].x);
                mean *= 0.125f;
                float m2 = 0.f, dv = 0.f;
#pragma unroll
                for (int i = 0; i < 8; i++) { const float d = __uint_as_float(v[i].x) - mean; m2 += __uint_as_float(v[i].z); dv = fmaf(d, d, dv); }
                sts_f2(sb + OFF_CS1 + row * 8, -mean, rcp(fmaf(dv, 64.f, m2) * (1.f / DM) + 1e-5f));
            }
        }
        mbar_arrive(sb + BAR_CS3);
#pragma unroll 1
        for (int c = a; c < 3; c += 2) {
            mbar_wait(sb + BAR_STG + 8 * c, 0);
            if (elect_one()) {
                asm volatile("cp.async.bulk.global.shared::cta.bulk_group [%0], [%1], %2;" ::"l"(g_act + ((2 + c) * 128 + role) * 1024), "r"(sb + OFF_B + 4 * SLOT), "r"(SLOT) : "memory");
                asm volatile("cp.async.bulk.commit_group;" ::: "memory");
                asm volatile("cp.async.bulk.wait_group.read 0;" ::: "memory");
                mbar_arrive(sb + BAR_FULLB + 8 * 4);
                asm volatile("cp.async.bulk.wait_group 0;" ::: "memory");
            }
            __syncwarp();
            TL(60 + c, lane == 0);
            uint32_t ack = 0;
            const uint4* rb = g_act + ((2 + c) * 128 + role) * 1024 + lane * 8;
#pragma unroll
            for (int i = 0; i < 4; i++) ack |= readback(rb + 256 * i);
            signal_after(g_flag + (m * 5 + 2 + c) * 32, ack, P.zero, lane == 0);
            TL(54 + c, lane == 0);
        }
        return;
    }
    const unsigned epoch = ld_relaxed(&g_epoch);
    uint32_t wraw[16];
    if (!helper) {
        const uint32_t* wp = reinterpret_cast<const uint32_t*>(P.wphi) + (4 * j) * 128 + (lane & 3) * 16 + (lane >> 2);
#pragma unroll
        for (int i = 0; i < 16; i++)
            asm volatile("ld.global.nc.u32 %0, [%1];" : "=r"(wraw[i]) : "l"(wp + (i >> 2) * 128 + ((i >> 1) & 1) * 64 + (i & 1) * 8));
    }
    asm volatile("barrier.cluster.arrive.relaxed.aligned;" ::: "memory");
    asm volatile("setmaxnreg.inc.sync.aligned.u32 216;");
    bar_sync(0, NTHREADS);
    if (helper) {
        if (warp < 4) {
            sts128(sb + OFF_B + 16 * tid, 0x3f803f80u, 0x3f803f80u, 0x3f803f80u, 0x3f803f80u);
            for (int i = tid; i < 2 * ACC_SIZE / 4; i += 128) stg128(g_acc + 2 * j * ACC_SIZE + 4 * i, 0, 0, 0, 0);
            fence_async_smem();
            fence_gpu();
            bar_sync(1, 128);
            float acc[8];
            int i = 0;
#pragma unroll 1
            for (int job = 0; job < 12; job++) {
                const int n = job < 6 ? 4 : 8;
#pragma unroll 1
                for (int t = 0; t < n; t++, i++) {
                    mbar_wait(sb + BAR_FULLA + 8 * (i & 7), (i >> 3) & 1);
                    wg_fence();
#pragma unroll
                    for (int k = 0; k < 8; k++)
                        wgmma_n8_tt(acc + (k & 4), desc_lo(sb + OFF_A) + (i & 7) * (SLOT >> 4) + 128 * k, desc_lo(sb + OFF_B), (t | (k & 3)) != 0);
                    wg_commit();
                    wg_wait<1>();
                    mbar_arrive_n_if(sb + BAR_EMPTYA + 8 * ((i + 7) & 7), 2, lane == 0 && i > 0);
                }
                wg_wait<0>();
                fence_acc<8>(acc);
                const int q = lane & 3;
                const float lo = (q & 1) ? acc[2] : acc[0], hi = (q & 1) ? acc[6] : acc[4];
                const float v = job < 6 ? lo + hi : ((q & 2) ? hi : lo);
                unsigned long long* dst = g_cs + ((2 * j + (job & 1)) * 6 + (job >> 1)) * 128 + (q >> 1) * 64 + 16 * warp + 8 * (q & 1) + (lane >> 2);
                asm volatile("st.relaxed.gpu.global.b64 [%0], %1;" ::"l"(dst), "l"(((unsigned long long)epoch << 32) | __float_as_uint(v)) : "memory");
            }
        }
        return;
    }
    {
        const int w = warp >> 2, wv = warp & 3, g = lane >> 2, q = lane & 3;
        const uint32_t sa = sb + OFF_A + w * 8192;
        const desc_t dA = desc_lo(sa), dB = desc_lo(sb + OFF_B);
        unsigned* const flag_m = g_flag + m * 160;
        const bool l0 = lane == 0, l2 = lane < 2;
        const uint32_t eb = mapa(sb + BAR_EMPTYB, lane & 1);
        asm volatile("barrier.cluster.wait.aligned;" ::: "memory");
        Ring rg{0, 0};
        int prev = 0;

        uint32_t wb[16];
        constexpr float L2E = 1.4426950408889634f;
        const int ch = lane >> 4, sw = lane & 7;
        const uint32_t lrow = (lane & 15) * 128;
        uint32_t fp[16], fm[16];
        {
            float acc[64], accq[32];
#pragma unroll 1
            for (int kt = 0; kt < 8; kt++) {
                mbar_waitc(sb + BAR_FULLA + 8 * kt, 0);
                mbar_waitc(sb + BAR_FULLB + 8 * rg.slot, rg.phase);
                const desc_t da = dA + kt * (SLOT >> 4), db = dB + rg.slot * (SLOT >> 4);
                wg_fence();
#pragma unroll
                for (int k = 0; k < 4; k++) wgmma_n128(acc, da + 2 * k, db + 128 * k, (kt | k) != 0);
                wg_commit();
                wg_wait<1>();
                mbar_arrive_cl_if(eb + 8 * prev, l2 && kt > 0);
                prev = rg.slot; rg.adv();
            }
#pragma unroll
            for (int i = 0; i < 8; i++) {
                wb[(i >> 1) * 4 + (i & 1)] = __byte_perm(wraw[2 * i], wraw[2 * i + 1], 0x5410);
                wb[(i >> 1) * 4 + 2 + (i & 1)] = __byte_perm(wraw[2 * i], wraw[2 * i + 1], 0x7632);
            }
            float2 s0, s1;
            uint32_t a[16];
            wg_wait<0>();
            fence_acc<64>(acc);
            mbar_arrive_cl_if(eb + 8 * prev, l2);
            mbar_waitc(sb + BAR_FULLB + 8 * 2, 1); mbar_waitc(sb + BAR_FULLB + 8 * 3, 1);
            wg_fence();
#pragma unroll
            for (int k = 0; k < 16; k++) wgmma_n64(accq, dA + (k >> 2) * (SLOT >> 4) + (k & 3) * 2, dB + 2 * (SLOT >> 4) + 128 * k, k != 0);
            wg_commit();
            mbar_waitc(sb + BAR_CS1, 0);
            wg_wait<0>();
            fence_acc<32>(accq);
            mbar_arrive_cl_if(eb + 8 * (2 + (lane >> 1)), lane < 4);
            TL(2, tid == 0);
            s0 = lds_f2(sb + OFF_XST + (16 * warp + g) * 8); s1 = lds_f2(sb + OFF_XST + (16 * warp + g + 8) * 8);
#pragma unroll
            for (int hh = 0; hh < 4; hh++)
                ln_frag<false>(acc + 8 * hh, sb + OFF_CS1 + (64 + 16 * hh + 2 * q) * 4, 0.f, s0.y, 0.f, s1.y, a + 4 * hh);
#pragma unroll 1
            for (int it = 0; it < 2; it++) {
                feature_maps(a, wb, s0.x * L2E, s1.x * L2E, fp, fm, [&](int h) {
                    if (it == 0) {
                        if (!(h & 1)) mbar_waitc(sb + BAR_FULLB + 8 * (2 + (h >> 1)), 0);
                        wg_fence();
#pragma unroll
                        for (int k = 0; k < 4; k++) wgmma_n64(accq, dA + (4 + h) * (SLOT >> 4) + 2 * k, dB + 2 * (SLOT >> 4) + 128 * (4 * h + k), 1);
                        wg_commit();
                    }
                });
                if (it == 0) {
                    mbar_waitc(sb + BAR_FULLB + 8 * 4, 1); mbar_waitc(sb + BAR_FULLB + 8 * 5, 1);
                    mbar_waitc(sb + BAR_FULLB + 8 * 0, 0); mbar_waitc(sb + BAR_FULLB + 8 * 1, 0);
                    mbar_waitc(sb + BAR_CSV, 0);
                    const uint32_t st = sb + OFF_B + warp * 2048 + lrow;
#pragma unroll
                    for (int hh = 0; hh < 4; hh++) {
                        stsm4(st + (4 + (hh >> 1)) * SLOT + (((4 * (hh & 1) + ch) ^ sw) << 4), fp[4 * hh], fp[4 * hh + 1], fp[4 * hh + 2], fp[4 * hh + 3]);
                        stsm4(st + (4 + (hh >> 1)) * SLOT + (((4 * (hh & 1) + 2 + ch) ^ sw) << 4), fm[4 * hh], fm[4 * hh + 1], fm[4 * hh + 2], fm[4 * hh + 3]);
                        ln_frag<true>(acc + 32 + 8 * hh, sb + OFF_CS1 + (128 + 16 * hh + 2 * q) * 4, s0.x, s0.y, s1.x, s1.y, a);
                        stsm4(st + (hh >> 1) * SLOT + (((2 * (hh & 1) + ch) ^ sw) << 4), a[0], a[1], a[2], a[3]);
                    }
                    stsm4(st + ch * SLOT + ((4 ^ sw) << 4), 0x3f803f80u, 0x3f803f80u, 0x3f803f80u, 0x3f803f80u);
                    fence_async_smem();
                    bar_sync(1, 256);
                    float kvd[20];
                    wg_fence();
#pragma unroll
                    for (int k = 0; k < 8; k++)
                        wgmma_n40_tt(kvd, dB + (4 + w) * (SLOT >> 4) + 128 * k, dB + w * (SLOT >> 4) + 128 * k, k != 0);
                    wg_commit();
                    wg_wait<0>();
                    fence_acc<20>(kvd);
                    const bool h1 = wv >= 2;
                    float* kvp = acc_j + 4 * tid;
                    red_f32x4(kvp, h1 ? kvd[8] : kvd[0], h1 ? kvd[9] : kvd[1], h1 ? kvd[10] : kvd[2], 1.f);
                    red_f32x4(kvp + 1024, h1 ? kvd[12] : kvd[4], h1 ? kvd[13] : kvd[5], h1 ? kvd[11] : kvd[3], 1.f);
                    red_f32x4(kvp + 2048, h1 ? kvd[14] : kvd[6], h1 ? kvd[15] : kvd[7], (q & 1) ? kvd[18] : kvd[16], 1.f);
                    __syncwarp();
                    mbar_arrive_if(sb + BAR_KVW, l0);
                    mbar_arrive_cl_if(eb + 8 * ((4 + (lane >> 1)) % 6), lane < 8);
                    TL(3, tid == 0);
                    fence_acc<32>(accq);
                    mbar_arrive_cl_if(eb + 8 * (2 + (lane >> 1)), lane < 4);
                    mbar_waitc(sb + BAR_CSQ, 0);
#pragma unroll
                    for (int hh = 0; hh < 4; hh++)
                        ln_frag<false>(accq + 8 * hh, sb + OFF_CS1 + (16 * hh + 2 * q) * 4, 0.f, s0.y, 0.f, s1.y, a + 4 * hh);
                }
            }
        }
        uint32_t res_lo[8], res_hi[8], ack[4];
        const uint32_t own_rows = sb + OFF_A + j * SLOT + warp * 2048;
#pragma unroll
        for (int b = 0; b < 4; b++)
            ldsm4(own_rows + lrow + (((2 * b + ch) ^ sw) << 4), res_lo[2 * b], res_hi[2 * b], res_lo[2 * b + 1], res_hi[2 * b + 1]);
        mbar_arrive_if(sb + BAR_EMPTYA + 8 * lane, lane < 8 && lane != j && lane != KVS(j));
        TL(5, tid == 0);
        mbar_waitc(sb + BAR_KVR, 0);
        TL(6, tid == 0);
        {
            const uint32_t kvs = sb + OFF_A + KVS(j) * SLOT;
            uint32_t o_lo[8], o_hi[8];
#pragma unroll
            for (int hh = 0; hh < 4; hh++) {
                uint32_t b[8], zb[4];
                const uint32_t base = kvs + hh * 32 * 48;
                ldsm4t(base + (lane & 15) * 48 + (lane >> 4) * 16, b[0], b[1], b[2], b[3]);
                ldsm4t(base + (16 + (lane & 15)) * 48 + (lane >> 4) * 16, b[4], b[5], b[6], b[7]);
                ldsm4t(base + lane * 48 + 32, zb[0], zb[1], zb[2], zb[3]);
                float n0[4], n1[4], dn[4];
                mma16816_z(n0, fp + 4 * hh, b[0], b[1]); mma16816_z(n1, fp + 4 * hh, b[2], b[3]); mma16816_z(dn, fp + 4 * hh, zb[0], zb[1]);
                mma16816(n0, fm + 4 * hh, b[4], b[5]); mma16816(n1, fm + 4 * hh, b[6], b[7]); mma16816(dn, fm + 4 * hh, zb[2], zb[3]);
                const float i0 = rcp(dn[0] + 1e-6f), i1 = rcp(dn[2] + 1e-6f);
                o_lo[2 * hh] = pack_bf16(n0[0] * i0, n0[1] * i0); o_hi[2 * hh] = pack_bf16(n0[2] * i1, n0[3] * i1);
                o_lo[2 * hh + 1] = pack_bf16(n1[0] * i0, n1[1] * i0); o_hi[2 * hh + 1] = pack_bf16(n1[2] * i1, n1[3] * i1);
            }
            __syncwarp();
            mbar_arrive_if(sb + BAR_EMPTYA + 8 * KVS(j), l0);
            rg.slot = 4; rg.phase = 0;
            store_tile(own_rows, g_act + role * 1024 + warp * 128 + lane, o_lo, o_hi, lane, ack);
            TL(7, tid == 0);
        }
        float acch[32];
        {
            float* acc = acch;
#pragma unroll
            for (int t = 0; t < 8; t++) {
                acc[4 * t] = bf_lo(res_lo[t]); acc[4 * t + 1] = bf_hi(res_lo[t]);
                acc[4 * t + 2] = bf_lo(res_hi[t]); acc[4 * t + 3] = bf_hi(res_hi[t]);
            }
            fence_acc<32>(acc);
            int pa = 0;
#pragma unroll 1
            for (int kp = 0; kp < 4; kp++) {
                mbar_waitc(sb + BAR_FULLB + 8 * rg.slot, rg.phase);
#pragma unroll
                for (int hf = 0; hf < 2; hf++) {
                    const int i = 2 * kp + hf, kt = KORD(i, j);
                    mbar_waitc(sb + BAR_FULLA + 8 * kt, i != 0);
                    TL(8, i == 1 && tid == 0);
                    const desc_t da = dA + kt * (SLOT >> 4), db = dB + rg.slot * (SLOT >> 4);
                    wg_fence();
#pragma unroll
                    for (int k = 0; k < 4; k++) wgmma_n64(acc, da + 2 * k, db + (hf * 4 + k) * 128, 1);
                    wg_commit();
                    wg_wait<1>();
                    mbar_arrive_if(sb + BAR_EMPTYA + 8 * pa, l0 && i > 1);
                    if (hf == 0) {
                        mbar_arrive_cl_if(eb + 8 * prev, l2 && i > 0);
                        if (i == 0) { signal_late(flag_m, ack, P.zero, l0); TL(20, tid == 0); }
                    }
                    pa = kt;
                }
                prev = rg.slot; rg.adv();
            }
            wg_wait<0>();
            fence_acc<32>(acc);
            mbar_arrive_if(sb + BAR_EMPTYA + 8 * pa, l0);
            mbar_arrive_cl_if(eb + 8 * prev, l2);
            TL(9, tid == 0);
#pragma unroll
            for (int t = 0; t < 8; t++) {
                res_lo[t] = pack_bf16(acc[4 * t], acc[4 * t + 1]);
                res_hi[t] = pack_bf16(acc[4 * t + 2], acc[4 * t + 3]);
            }
            store_tile(own_rows, g_act + (128 + role) * 1024 + warp * 128 + lane, res_lo, res_hi, lane, ack);
            TL(10, tid == 0);
        }
        float acc0[64], acc1[64], acc2[56], nm0, nm1;
        float4 cs[8];
        uint32_t hr[16];
#define P3_GROUP(MMA, ACC, KT)                                                                              \
        mbar_waitc(sb + BAR_FULLB + 8 * rg.slot, rg.phase);                                                 \
        {                                                                                                   \
            const desc_t da = dA + (KT) * (SLOT >> 4), db = dB + rg.slot * (SLOT >> 4);                     \
            wg_fence();                                                                                     \
            _Pragma("unroll") for (int k = 0; k < 4; k++) MMA(ACC, da + 2 * k, db + 128 * k, (i | k) != 0); \
            wg_commit();                                                                                    \
        }
#define P3_CS(C, NT)    \
        _Pragma("unroll") for (int t = 0; t < (NT); t++) lds_f4_if(cs[t], sb + OFF_CS3 + q * 16 + 512 * (C) + 64 * t, i == t);
#define P3_EPI(C, ACC, N, NTP)                                                                              \
        fence_acc<N>(ACC);                                                                                  \
        TL(11 + (C), tid == 0);                                                                             \
        hh_stage<NTP>(ACC, cs, nm0, nm1, sb + OFF_B + 4 * SLOT + warp * 2048, lane);                        \
        mbar_arrive_if(sb + BAR_STG + 8 * (C), l0);                                                         \
        TL(50 + (C), tid == 0);
        const uint32_t blk = ((lane & 7) + (lane >> 4) * 8) * 128 + (((2 * wv + ((lane >> 3) & 1)) ^ (lane & 7)) << 4);
#pragma unroll 1
        for (int i = 0; i < 8; i++) {
            const int kt = KORD(i, j);
            mbar_waitc(sb + BAR_FULLA + 8 * kt, 0);
            TL(44, tid == 0 && i == 1);
            P3_GROUP(wgmma_n128, acc0, kt)
            if (i == 7) {
                mbar_waitc(sb + BAR_CS3, 0);
                nm0 = lds_f2(sb + OFF_CS1 + (16 * warp + g) * 8).x; nm1 = lds_f2(sb + OFF_CS1 + (16 * warp + g + 8) * 8).x;
            }
            wg_wait<1>();
            mbar_arrive_cl_if(eb + 8 * prev, l2 && i > 0);
            if (i == 0) {
                signal_late(flag_m + 32, ack, P.zero, l0);
                TL(21, tid == 0);
                {
                    fence_acc<32>(acch);
                    const float* acc = acch;
                    float s0 = 0.f, s1 = 0.f;
#pragma unroll
                    for (int t = 0; t < 8; t++) { s0 += acc[4 * t] + acc[4 * t + 1]; s1 += acc[4 * t + 2] + acc[4 * t + 3]; }
            s0 += __shfl_xor_sync(0xffffffffu, s0, 1); s1 += __shfl_xor_sync(0xffffffffu, s1, 1);
            s0 += __shfl_xor_sync(0xffffffffu, s0, 2); s1 += __shfl_xor_sync(0xffffffffu, s1, 2);
            const float mu0 = s0 * (1.f / 64), mu1 = s1 * (1.f / 64);
            float q0 = 0.f, q1 = 0.f;
#pragma unroll
            for (int t = 0; t < 8; t++) {
                float d;
                d = acc[4 * t] - mu0; q0 = fmaf(d, d, q0);
                d = acc[4 * t + 1] - mu0; q0 = fmaf(d, d, q0);
                d = acc[4 * t + 2] - mu1; q1 = fmaf(d, d, q1);
                d = acc[4 * t + 3] - mu1; q1 = fmaf(d, d, q1);
            }
            q0 += __shfl_xor_sync(0xffffffffu, q0, 1); q1 += __shfl_xor_sync(0xffffffffu, q1, 1);
            q0 += __shfl_xor_sync(0xffffffffu, q0, 2); q1 += __shfl_xor_sync(0xffffffffu, q1, 2);
            st_tagged_if(g_hstat + (role * 128 + 16 * warp + g + 8 * (q & 1)) * 2, q ? mu1 : mu0, q ? q1 : q0, epoch, q < 2);
                }
                bar_sync(2 + w, 128);
#pragma unroll
                for (int tp = 0; tp < 4; tp++) ldsm4t(sa + j * SLOT + blk + tp * 2048, hr[4 * tp], hr[4 * tp + 1], hr[4 * tp + 2], hr[4 * tp + 3]);
                mbar_waitc(sb + BAR_CSG, 0);
#pragma unroll
                for (int t = 0; t < 8; t++) cs[t] = lds_f4(sb + OFF_CS3 + q * 16 + 64 * t);
            }
            prev = rg.slot; rg.adv5();
        }
#pragma unroll 1
        for (int i = 0; i < 8; i++) {
            P3_GROUP(wgmma_n128, acc1, i)
            wg_wait<1>();
            mbar_arrive_cl_if(eb + 8 * prev, l2);
            if (i == 0) { P3_EPI(0, acc0, 64, 4) mbar_waitc(sb + BAR_CSG + 8, 0); }
            P3_CS(1, 8)
            prev = rg.slot; rg.adv5();
        }
#pragma unroll 1
        for (int i = 0; i < 8; i++) {
            P3_GROUP(wgmma_n112, acc2, i)
            wg_wait<1>();
            mbar_arrive_cl_if(eb + 8 * prev, l2);
            mbar_arrive_if(sb + BAR_EMPTYA + 8 * ((i + 7) & 7), l0 && i > 0);
            if (i == 0) { mbar_waitc(sb + BAR_FULLB + 8 * 4, 1); P3_EPI(1, acc1, 64, 4) mbar_waitc(sb + BAR_CSG + 16, 0); }
            P3_CS(2, 6)
            prev = rg.slot; rg.adv5();
        }
        mbar_waitc(sb + BAR_FULLB + 8 * 4, 0);
        wg_wait<0>();
        mbar_arrive_cl_if(eb + 8 * prev, l2);
        mbar_arrive_if(sb + BAR_EMPTYA + 8 * 7, l0);
        P3_EPI(2, acc2, 56, 3)
        {
            float acc[64];
            const desc_t dA0 = desc_lo(sb + OFF_A);
#define KT_P4(I, NK)                                                                                        \
        const int s_ = (2 * (I) + w) & 7;                                                                   \
        mbar_waitc(sb + BAR_FULLB + 8 * rg.slot, rg.phase);                                                 \
        mbar_waitc(sb + BAR_FULLA + 8 * s_, (((I) >> 2) + 1) & 1);                                          \
        TL(30 + (I), tid == 0);                                                                             \
        const desc_t dh_ = dA0 + s_ * (SLOT >> 4), dw_ = dB + rg.slot * (SLOT >> 4) + w * 512;              \
        wg_fence();                                                                                         \
        _Pragma("unroll") for (int k = 0; k < (NK); k++) wgmma_n128_tn(acc, dw_ + 128 * k, dh_ + 2 * k, ((I) | k) != 0); \
        wg_commit();                                                                                        \
        wg_wait<1>();
#pragma unroll 1
            for (int i = 0; i < 8; i++) {
                KT_P4(i, 4)
                mbar_arrive_n_if(sb + BAR_EMPTYA + 8 * ((s_ + 6) & 7), 2, l0 && i > 0);
                mbar_arrive_cl_if(eb + 8 * prev, l2 && i > 0);
#pragma unroll
                for (int t = 0; t < 8; t++) lds_f4_if(cs[t], sb + OFF_CS1 + (64 * w + 8 * t + 2 * q) * 8, i == t);
                prev = rg.slot; rg.adv5();
            }
#pragma unroll 1
            for (int i = 8; i < 12; i++) {
                KT_P4(i, 3)
                mbar_arrive_n_if(sb + BAR_EMPTYA + 8 * ((s_ + 6) & 7), 2, l0);
                rg.adv5();
            }
            wg_wait<0>();
            fence_acc<64>(acc);
            TL(15, tid == 0);
            const uint32_t xch = sb + OFF_A + 2 * SLOT + (tid & 127) * 16;
            if (w) {
#pragma unroll
                for (int t = 0; t < 8; t++) {
                    sts128(xch + SLOT + t * 2048, __float_as_uint(acc[4 * t]), __float_as_uint(acc[4 * t + 1]),
                           __float_as_uint(acc[4 * t + 2]), __float_as_uint(acc[4 * t + 3]));
                }
#pragma unroll
                for (int t = 0; t < 32; t++) acc[t] = acc[32 + t];
            } else {
#pragma unroll
                for (int t = 0; t < 8; t++)
                    sts128(xch + t * 2048, __float_as_uint(acc[32 + 4 * t]), __float_as_uint(acc[33 + 4 * t]),
                           __float_as_uint(acc[34 + 4 * t]), __float_as_uint(acc[35 + 4 * t]));
            }
            bar_sync(1, 256);
            float4 o[8];
#pragma unroll
            for (int t = 0; t < 8; t++) o[t] = lds_f4(xch + (w ^ 1) * SLOT + t * 2048);
            const uint32_t tile = sb + OFF_A + w * SLOT;
#pragma unroll
            for (int t = 0; t < 8; t++) {
                hr[2 * t] = pack_bf16(fmaf(acc[4 * t] + o[t].x, cs[t].y, bf_lo(hr[2 * t])), fmaf(acc[4 * t + 1] + o[t].y, cs[t].w, bf_hi(hr[2 * t])));
                hr[2 * t + 1] = pack_bf16(fmaf(acc[4 * t + 2] + o[t].z, cs[t].y, bf_lo(hr[2 * t + 1])), fmaf(acc[4 * t + 3] + o[t].w, cs[t].w, bf_hi(hr[2 * t + 1])));
            }
#pragma unroll
            for (int tp = 0; tp < 4; tp++) stsm4t(tile + blk + tp * 2048, hr[4 * tp], hr[4 * tp + 1], hr[4 * tp + 2], hr[4 * tp + 3]);
            fence_async_smem();
            bar_sync(2 + w, 128);
            if ((tid & 127) == 0) {
                tma_store2d(&P.tout, tile, 64 * j, 128 * m + 64 * w);
                asm volatile("cp.async.bulk.wait_group.read 0;" ::: "memory");
            }
            if (tid == 0 && role == 0) g_epoch = epoch + 1;
            TL(16, tid == 0); TLG(1, tid == 0);
        }
    }
}

__global__ void probe_kernel() {}

typedef CUresult (*EncodeFn)(CUtensorMap*, CUtensorMapDataType, cuuint32_t, void*, const cuuint64_t*, const cuuint64_t*,
                             const cuuint32_t*, const cuuint32_t*, CUtensorMapInterleave, CUtensorMapSwizzle,
                             CUtensorMapL2promotion, CUtensorMapFloatOOBfill);

static void make_map2d(EncodeFn enc, CUtensorMap* tm, const void* base, uint64_t cols, uint64_t rows, uint64_t pitch_elems,
                       uint32_t box_rows) {
    cuuint64_t gd[2] = {cols, rows};
    cuuint64_t gs[1] = {pitch_elems * 2};
    cuuint32_t bd[2] = {64, box_rows};
    cuuint32_t es[2] = {1, 1};
    enc(tm, CU_TENSOR_MAP_DATA_TYPE_BFLOAT16, 2, const_cast<void*>(base), gd, gs, bd, es, CU_TENSOR_MAP_INTERLEAVE_NONE,
        CU_TENSOR_MAP_SWIZZLE_128B, CU_TENSOR_MAP_L2_PROMOTION_L2_256B, CU_TENSOR_MAP_FLOAT_OOB_FILL_NONE);
}

}

extern "C" void kernel_launch(void* const* d_in, const int* in_sizes, int n_in, void* d_out, int out_size) {
    using namespace hk;
    (void)in_sizes; (void)n_in; (void)out_size;
    static EncodeFn enc = nullptr;
    static int std_layout = 0;
    if (!enc) {
        void* fn = nullptr;
        cudaDriverEntryPointQueryResult qr;
        cudaGetDriverEntryPoint("cuTensorMapEncodeTiled", &fn, cudaEnableDefault, &qr);
        enc = (EncodeFn)fn;
        cudaFuncSetAttribute(fused_kernel, cudaFuncAttributeMaxDynamicSharedMemorySize, SMEM_BYTES);
        int dev = 0, sms = 0;
        cudaGetDevice(&dev);
        cudaDeviceGetAttribute(&sms, cudaDevAttrMultiProcessorCount, dev);
        cudaFuncSetAttribute(probe_kernel, cudaFuncAttributeNonPortableClusterSizeAllowed, 1);
        cudaFuncSetAttribute(probe_kernel, cudaFuncAttributeMaxDynamicSharedMemorySize, SMEM_BYTES);
        const int sizes[3] = {8, 9, 16}, want[3] = {15, 9, 7};
        bool ok = sms == NCTA;
        for (int i = 0; i < 3 && ok; i++) {
            cudaLaunchConfig_t cfg = {};
            cfg.gridDim = dim3(sizes[i] * 8); cfg.blockDim = dim3(NTHREADS); cfg.dynamicSmemBytes = SMEM_BYTES;
            cudaLaunchAttribute at;
            at.id = cudaLaunchAttributeClusterDimension;
            at.val.clusterDim.x = sizes[i]; at.val.clusterDim.y = 1; at.val.clusterDim.z = 1;
            cfg.attrs = &at; cfg.numAttrs = 1;
            int n = 0;
            ok = cudaOccupancyMaxActiveClusters(&n, probe_kernel, &cfg) == cudaSuccess && n == want[i];
        }
        (void)cudaGetLastError();
        std_layout = ok ? 1 : 0;
    }
    Params P;
    const __nv_bfloat16* x = (const __nv_bfloat16*)d_in[0];
    P.x = x;
    P.wqkv = (const __nv_bfloat16*)d_in[1];
    P.wphi = (const __nv_bfloat16*)d_in[2];
    P.wo = (const __nv_bfloat16*)d_in[3];
    P.wg = (const __nv_bfloat16*)d_in[5];
    P.wu = (const __nv_bfloat16*)d_in[6];
    P.wd = (const __nv_bfloat16*)d_in[7];
    P.out = (__nv_bfloat16*)d_out;
    P.zero = 0;
    for (int i = 0; i < NCTA; i++) {
        const int odd = i & 1;
        int role = i < 4 ? 128 + i : (((i - 4) >> 4) * 2 + odd) * 8 + (((i - 4) >> 1) & 7);
        if (std_layout) {
            const int tpc = i < 8 ? 62 + (i >> 1) : (i - 8) >> 1;
            if (tpc < 32) role = (tpc & 7) ? (2 * ((tpc & 7) - 1) + odd) * 8 + (tpc >> 3) : (14 + odd) * 8 + (tpc >> 3);
            else if (tpc < 60) role = (2 * ((tpc - 32) % 7) + odd) * 8 + 4 + (tpc - 32) / 7;
            else if (tpc < 62) role = 128 + (tpc - 60) * 2 + odd;
            else role = (14 + odd) * 8 + 4 + (tpc - 62);
        }
        P.role[i] = (unsigned char)role;
    }
    make_map2d(enc, &P.tx, x, DM, SEQ, DM, 128);
    make_map2d(enc, &P.twq, P.wqkv, 3 * DM, DM, 3 * DM, 64);
    make_map2d(enc, &P.two, P.wo, DM, DM, DM, 64);
    make_map2d(enc, &P.twg, P.wg, FF, DM, FF, 64);
    make_map2d(enc, &P.twu, P.wu, FF, DM, FF, 64);
    make_map2d(enc, &P.twd, P.wd, DM, FF, DM, 64);
    make_map2d(enc, &P.tout, d_out, DM, SEQ, DM, 64);
    fused_kernel<<<NCTA, NTHREADS, SMEM_BYTES>>>(P);
}
```

```cpp
#include <cuda_runtime.h>
#include <cuda_bf16.h>
#include <cuda.h>
#include <stdint.h>

namespace hk {

constexpr int SEQ = 2048, DM = 512, FF = 1376;
constexpr int NCTA = 132;
constexpr int NTHREADS = 384;
constexpr uint32_t SLOT = 16384;
constexpr uint32_t OFF_A = 0, OFF_B = 8 * SLOT, OFF_MISC = 14 * SLOT;
constexpr uint32_t BAR_FULLA = OFF_MISC + 0, BAR_EMPTYA = OFF_MISC + 64, BAR_FULLB = OFF_MISC + 128,
                   BAR_EMPTYB = OFF_MISC + 176, BAR_CS1 = OFF_MISC + 224, BAR_CS3 = OFF_MISC + 232,
                   BAR_CSQ = OFF_MISC + 240, BAR_CSV = OFF_MISC + 248,
                   BAR_STG = OFF_MISC + 256,
                   BAR_KVW = OFF_MISC + 280, BAR_KVR = OFF_MISC + 288, BAR_CSG = OFF_MISC + 296;
constexpr uint32_t OFF_CS1 = OFF_MISC + 384;
constexpr uint32_t OFF_CS3 = OFF_CS1 + 1024;
constexpr uint32_t OFF_XST = OFF_CS3;
constexpr uint32_t SMEM_BYTES = OFF_CS3 + 1536;
#define KVS(j) ((j) == 3 ? 2 : 3)
#define KORD(i, j) ((i) == 0 ? (j) : (i) - ((i) <= (j)))
constexpr int NB = 6;
#define PF_DELAY 2
#define KV_POLL 1
constexpr int AHEAD = 3;

constexpr int ACC_SIZE = 3 * 256 * 4;

__device__ __align__(1024) uint4 g_act[5 * 128 * 1024];
__device__ __align__(128) unsigned long long g_hstat[SEQ * 16];
__device__ __align__(128) unsigned long long g_xstat[SEQ * 2];
__device__ __align__(128) float g_acc[8 * ACC_SIZE];
__device__ __align__(128) unsigned long long g_cs[8 * 6 * 128];
__device__ __align__(128) unsigned g_flag[16 * 5 * 32 + 32];
__device__ unsigned g_epoch = 1;

#define TL(i, pred) do {} while (0)
#define TLG(i, pred) do {} while (0)

struct Params {
    CUtensorMap tx, twq, two, twg, twu, twd, tout;
    const __nv_bfloat16 *x, *wqkv, *wphi, *wo, *wg, *wu, *wd;
    __nv_bfloat16* out;
    unsigned zero;
    unsigned char role[NCTA];
};

__device__ __forceinline__ uint32_t smem_u32(const void* p) { return (uint32_t)__cvta_generic_to_shared(p); }
__device__ __forceinline__ void mbar_init(uint32_t bar, uint32_t cnt) {
    asm volatile("mbarrier.init.shared::cta.b64 [%0], %1;" ::"r"(bar), "r"(cnt) : "memory");
}
__device__ __forceinline__ void mbar_expect_tx(uint32_t bar, uint32_t bytes) {
    asm volatile("mbarrier.arrive.expect_tx.shared::cta.b64 _, [%0], %1;" ::"r"(bar), "r"(bytes) : "memory");
}
__device__ __forceinline__ void mbar_arrive(uint32_t bar) {
    asm volatile("mbarrier.arrive.shared::cta.b64 _, [%0];" ::"r"(bar) : "memory");
}
__device__ __forceinline__ void mbar_arrive_if(uint32_t bar, bool pred) {
    asm volatile("{.reg .pred p; setp.ne.u32 p, %1, 0; @p mbarrier.arrive.shared::cta.b64 _, [%0];}" ::"r"(bar), "r"((uint32_t)pred) : "memory");
}
__device__ __forceinline__ bool mbar_try(uint32_t bar, uint32_t parity) {
    uint32_t ok;
    asm volatile("{.reg .pred p; mbarrier.try_wait.parity.shared::cta.b64 p, [%1], %2; selp.u32 %0,1,0,p;}"
                 : "=r"(ok) : "r"(bar), "r"(parity) : "memory");
    return ok;
}
__device__ __forceinline__ bool mbar_test(uint32_t bar, uint32_t parity) {
    uint32_t ok;
    asm volatile("{.reg .pred p; mbarrier.test_wait.parity.shared::cta.b64 p, [%1], %2; selp.u32 %0,1,0,p;}"
                 : "=r"(ok) : "r"(bar), "r"(parity) : "memory");
    return ok;
}
__device__ __forceinline__ void trap_if_gt(uint32_t v, uint32_t lim) {
    asm volatile("{.reg .pred p; setp.gt.u32 p, %0, %1; @p trap;}" ::"r"(v), "r"(lim));
}
__device__ __forceinline__ void mbar_wait(uint32_t bar, uint32_t parity) {
    asm volatile("{\n"
                 ".reg .pred P1, P2;\n"
                 ".reg .u32 c;\n"
                 "mov.u32 c, 0;\n"
                 "LAB_WAIT:\n"
                 "mbarrier.try_wait.parity.shared::cta.b64 P1, [%0], %1;\n"
                 "@P1 bra LAB_DONE;\n"
                 "add.u32 c, c, 1;\n"
                 "setp.gt.u32 P2, c, 4194304;\n"
                 "@P2 trap;\n"
                 "bra LAB_WAIT;\n"
                 "LAB_DONE:\n"
                 "}" ::"r"(bar), "r"(parity) : "memory");
}
__device__ __forceinline__ void mbar_waitc(uint32_t bar, uint32_t parity) {
    asm volatile("{\n"
                 ".reg .pred P1;\n"
                 "LAB_WAIT:\n"
                 "mbarrier.try_wait.parity.shared::cta.b64 P1, [%0], %1;\n"
                 "@!P1 bra LAB_WAIT;\n"
                 "}" ::"r"(bar), "r"(parity) : "memory");
}
__device__ __forceinline__ void tma2d(uint32_t dst, const CUtensorMap* tm, uint32_t bar, int c0, int c1) {
    asm volatile("cp.async.bulk.tensor.2d.shared::cluster.global.mbarrier::complete_tx::bytes [%0], [%1, {%3, %4}], [%2];"
                 ::"r"(dst), "l"(tm), "r"(bar), "r"(c0), "r"(c1) : "memory");
}
__device__ __forceinline__ void tma2d_mc(uint32_t dst, const CUtensorMap* tm, uint32_t bar, int c0, int c1) {
    asm volatile("cp.async.bulk.tensor.2d.shared::cluster.global.mbarrier::complete_tx::bytes.multicast::cluster [%0], [%1, {%3, %4}], [%2], %5;"
                 ::"r"(dst), "l"(tm), "r"(bar), "r"(c0), "r"(c1), "h"((uint16_t)3) : "memory");
}
__device__ __forceinline__ uint32_t mapa(uint32_t addr, uint32_t rank) {
    uint32_t r; asm("mapa.shared::cluster.u32 %0, %1, %2;" : "=r"(r) : "r"(addr), "r"(rank)); return r;
}
__device__ __forceinline__ void mbar_arrive_cl_if(uint32_t cbar, bool pred) {
    asm volatile("{.reg .pred p; setp.ne.u32 p, %1, 0; @p mbarrier.arrive.shared::cluster.b64 _, [%0];}" ::"r"(cbar), "r"((uint32_t)pred) : "memory");
}
__device__ __forceinline__ bool elect_one() {
    uint32_t ok;
    asm volatile("{.reg .pred p; elect.sync _|p, 0xffffffff; selp.u32 %0, 1, 0, p;}" : "=r"(ok));
    return ok;
}
__device__ __forceinline__ void prefetch_tmap(const CUtensorMap* tm) {
    asm volatile("prefetch.tensormap [%0];" ::"l"(tm) : "memory");
}
__device__ __forceinline__ void prefetch_l2(const void* p, uint32_t bytes) {
    asm volatile("cp.async.bulk.prefetch.L2.global [%0], %1;" ::"l"(p), "r"(bytes) : "memory");
}
__device__ __forceinline__ unsigned ld_acquire(const unsigned* p) {
    unsigned v; asm volatile("ld.acquire.gpu.global.u32 %0, [%1];" : "=r"(v) : "l"(p) : "memory"); return v;
}
__device__ __forceinline__ uint4 ld_acquire4(const unsigned* p) {
    uint4 v;
    asm volatile("ld.acquire.gpu.global.v4.u32 {%0,%1,%2,%3}, [%4];" : "=r"(v.x), "=r"(v.y), "=r"(v.z), "=r"(v.w) : "l"(p) : "memory");
    return v;
}
__device__ __forceinline__ unsigned ld_relaxed(const unsigned* p) {
    unsigned v; asm volatile("ld.relaxed.gpu.global.u32 %0, [%1];" : "=r"(v) : "l"(p)); return v;
}
__device__ __forceinline__ void st_relaxed(unsigned* p, unsigned v) {
    asm volatile("st.relaxed.gpu.global.u32 [%0], %1;" ::"l"(p), "r"(v) : "memory");
}
__device__ __forceinline__ void red_relaxed(unsigned* p, unsigned v) {
    asm volatile("red.relaxed.gpu.global.add.u32 [%0], %1;" ::"l"(p), "r"(v) : "memory");
}
__device__ __forceinline__ void fence_gpu() { asm volatile("fence.acq_rel.gpu;" ::: "memory"); }
__device__ __forceinline__ void fence_async_smem() { asm volatile("fence.proxy.async.shared::cta;" ::: "memory"); }
__device__ __forceinline__ void fence_async_global() { asm volatile("fence.proxy.async.global;" ::: "memory"); }
__device__ __forceinline__ uint32_t readback(const void* p) {
    uint32_t v; asm volatile("ld.relaxed.gpu.global.u32 %0, [%1];" : "=r"(v) : "l"(p) : "memory"); return v;
}
__device__ __forceinline__ void wait_count(const unsigned* p, unsigned target) {
    uint32_t it = 0;
    while ((int)(readback(p) - target) < 0) trap_if_gt(++it, 1u << 22);
}
__device__ __forceinline__ void wait_count_warp(const unsigned* p, unsigned target) {
    uint32_t it = 0;
    while (__any_sync(0xffffffffu, (int)(readback(p) - target) < 0)) trap_if_gt(++it, 1u << 22);
}
__device__ __forceinline__ void red_f32(float* p, float a) {
    asm volatile("red.relaxed.gpu.global.add.f32 [%0], %1;" ::"l"(p), "f"(a) : "memory");
}
__device__ __forceinline__ void red_f32x2(float* p, float a, float b) {
    asm volatile("red.relaxed.gpu.global.add.v2.f32 [%0], {%1, %2};" ::"l"(p), "f"(a), "f"(b) : "memory");
}
__device__ __forceinline__ void red_f32x4(float* p, float a, float b, float c, float d) {
    asm volatile("red.relaxed.gpu.global.add.v4.f32 [%0], {%1, %2, %3, %4};" ::"l"(p), "f"(a), "f"(b), "f"(c), "f"(d) : "memory");
}
__device__ __forceinline__ float4 ld_l2_f4(const float* p) {
    float4 v;
    asm volatile("ld.relaxed.gpu.global.v4.f32 {%0,%1,%2,%3}, [%4];" : "=f"(v.x), "=f"(v.y), "=f"(v.z), "=f"(v.w) : "l"(p) : "memory");
    return v;
}
__device__ __forceinline__ float2 ld_l2_f2(const float* p) {
    float2 v;
    asm volatile("ld.relaxed.gpu.global.v2.f32 {%0,%1}, [%2];" : "=f"(v.x), "=f"(v.y) : "l"(p) : "memory");
    return v;
}
__device__ __forceinline__ float ld_l2_f(const float* p) {
    float v;
    asm volatile("ld.relaxed.gpu.global.f32 %0, [%1];" : "=f"(v) : "l"(p) : "memory");
    return v;
}
__device__ __forceinline__ uint4 ldg_nc(const void* p) {
    uint4 v;
    asm volatile("ld.global.nc.L1::no_allocate.v4.u32 {%0,%1,%2,%3}, [%4];" : "=r"(v.x), "=r"(v.y), "=r"(v.z), "=r"(v.w) : "l"(p));
    return v;
}
__device__ __forceinline__ void stg128(void* p, uint32_t a, uint32_t b, uint32_t c, uint32_t d) {
    asm volatile("st.global.v4.u32 [%0], {%1,%2,%3,%4};" ::"l"(p), "r"(a), "r"(b), "r"(c), "r"(d) : "memory");
}
__device__ __forceinline__ uint4 lds128(uint32_t a) {
    uint4 v;
    asm volatile("ld.shared.v4.u32 {%0,%1,%2,%3}, [%4];" : "=r"(v.x), "=r"(v.y), "=r"(v.z), "=r"(v.w) : "r"(a) : "memory");
    return v;
}
__device__ __forceinline__ float2 lds_f2(uint32_t a) {
    float2 v;
    asm volatile("ld.shared.v2.f32 {%0,%1}, [%2];" : "=f"(v.x), "=f"(v.y) : "r"(a) : "memory");
    return v;
}
__device__ __forceinline__ void sts_f2(uint32_t a, float x, float y) {
    asm volatile("st.shared.v2.f32 [%0], {%1,%2};" ::"r"(a), "f"(x), "f"(y) : "memory");
}
__device__ __forceinline__ void sts64(uint32_t a, uint32_t x, uint32_t y) {
    asm volatile("st.shared.v2.u32 [%0], {%1,%2};" ::"r"(a), "r"(x), "r"(y) : "memory");
}
__device__ __forceinline__ void sts128(uint32_t a, uint32_t x, uint32_t y, uint32_t z, uint32_t w) {
    asm volatile("st.shared.v4.u32 [%0], {%1,%2,%3,%4};" ::"r"(a), "r"(x), "r"(y), "r"(z), "r"(w) : "memory");
}
__device__ __forceinline__ void stsm4(uint32_t a, uint32_t r0, uint32_t r1, uint32_t r2, uint32_t r3) {
    asm volatile("stmatrix.sync.aligned.m8n8.x4.shared.b16 [%0], {%1,%2,%3,%4};" ::"r"(a), "r"(r0), "r"(r1), "r"(r2), "r"(r3) : "memory");
}
__device__ __forceinline__ void stsm4t(uint32_t a, uint32_t r0, uint32_t r1, uint32_t r2, uint32_t r3) {
    asm volatile("stmatrix.sync.aligned.m8n8.x4.trans.shared.b16 [%0], {%1,%2,%3,%4};" ::"r"(a), "r"(r0), "r"(r1), "r"(r2), "r"(r3) : "memory");
}
__device__ __forceinline__ void tma_store2d(const CUtensorMap* tm, uint32_t src, int c0, int c1) {
    asm volatile("cp.async.bulk.tensor.2d.global.shared::cta.bulk_group [%0, {%2, %3}], [%1];" ::"l"(tm), "r"(src), "r"(c0), "r"(c1) : "memory");
    asm volatile("cp.async.bulk.commit_group;" ::: "memory");
}
__device__ __forceinline__ void ldsm4(uint32_t a, uint32_t& r0, uint32_t& r1, uint32_t& r2, uint32_t& r3) {
    asm volatile("ldmatrix.sync.aligned.m8n8.x4.shared.b16 {%0,%1,%2,%3}, [%4];" : "=r"(r0), "=r"(r1), "=r"(r2), "=r"(r3) : "r"(a) : "memory");
}
__device__ __forceinline__ void ldsm4t(uint32_t a, uint32_t& r0, uint32_t& r1, uint32_t& r2, uint32_t& r3) {
    asm volatile("ldmatrix.sync.aligned.m8n8.x4.trans.shared.b16 {%0,%1,%2,%3}, [%4];" : "=r"(r0), "=r"(r1), "=r"(r2), "=r"(r3) : "r"(a) : "memory");
}
__device__ __forceinline__ void mma16816(float* c, const uint32_t* a, uint32_t b0, uint32_t b1) {
    asm("mma.sync.aligned.m16n8k16.row.col.f32.bf16.bf16.f32 {%0,%1,%2,%3}, {%4,%5,%6,%7}, {%8,%9}, {%0,%1,%2,%3};"
                 : "+f"(c[0]), "+f"(c[1]), "+f"(c[2]), "+f"(c[3])
                 : "r"(a[0]), "r"(a[1]), "r"(a[2]), "r"(a[3]), "r"(b0), "r"(b1));
}
__device__ __forceinline__ uint32_t pack_bf16(float lo, float hi) {
    uint32_t r; asm("cvt.rn.bf16x2.f32 %0, %1, %2;" : "=r"(r) : "f"(hi), "f"(lo)); return r;
}
__device__ __forceinline__ float bf_lo(uint32_t w) { return __uint_as_float(w << 16); }
__device__ __forceinline__ float bf_hi(uint32_t w) { return __uint_as_float(w & 0xffff0000u); }
__device__ __forceinline__ float ex2(float x) { float r; asm("ex2.approx.ftz.f32 %0, %1;" : "=f"(r) : "f"(x)); return r; }
__device__ __forceinline__ float rcp(float x) { float r; asm("rcp.approx.ftz.f32 %0, %1;" : "=f"(r) : "f"(x)); return r; }
__device__ __forceinline__ void bar_sync(int id, int n) { asm volatile("bar.sync %0, %1;" ::"r"(id), "r"(n) : "memory"); }

typedef unsigned long long desc_t;
__device__ __forceinline__ desc_t desc_lo(uint32_t addr) { return (desc_t)(((addr & 0x3FFFF) >> 4) | (512u << 16)) | (0x40000040ull << 32); }
__device__ __forceinline__ void wg_fence() { asm volatile("wgmma.fence.sync.aligned;" ::: "memory"); }
__device__ __forceinline__ void wg_commit() { asm volatile("wgmma.commit_group.sync.aligned;" ::: "memory"); }
template <int N> __device__ __forceinline__ void wg_wait() { asm volatile("wgmma.wait_group.sync.aligned %0;" ::"n"(N) : "memory"); }
template <int N> __device__ __forceinline__ void fence_acc(float* d) {
#pragma unroll
    for (int i = 0; i < N; i++) asm volatile("" : "+f"(d[i])::"memory");
}
#define R4(o) "+f"(d[o + 0]), "+f"(d[o + 1]), "+f"(d[o + 2]), "+f"(d[o + 3])
#define R8(o) R4(o), R4(o + 4)
__device__ __forceinline__ void wgmma_n128(float* d, desc_t da, desc_t db, int sc) {
    asm volatile("{.reg .pred p; setp.ne.b32 p, %66, 0;\n"
                 "wgmma.mma_async.sync.aligned.m64n128k16.f32.bf16.bf16 {%0,%1,%2,%3,%4,%5,%6,%7,%8,%9,%10,%11,%12,%13,%14,%15,%16,%17,%18,%19,%20,%21,%22,%23,%24,%25,%26,%27,%28,%29,%30,%31,"
                 "%32,%33,%34,%35,%36,%37,%38,%39,%40,%41,%42,%43,%44,%45,%46,%47,%48,%49,%50,%51,%52,%53,%54,%55,%56,%57,%58,%59,%60,%61,%62,%63}, %64, %65, p, 1, 1, 0, 1;}"
                 : R8(0), R8(8), R8(16), R8(24), R8(32), R8(40), R8(48), R8(56)
                 : "l"(da), "l"(db), "r"(sc));
}
__device__ __forceinline__ void wgmma_n112(float* d, desc_t da, desc_t db, int sc) {
    asm volatile("{.reg .pred p; setp.ne.b32 p, %58, 0;\n"
                 "wgmma.mma_async.sync.aligned.m64n112k16.f32.bf16.bf16 {%0,%1,%2,%3,%4,%5,%6,%7,%8,%9,%10,%11,%12,%13,%14,%15,%16,%17,%18,%19,%20,%21,%22,%23,%24,%25,%26,%27,%28,%29,%30,%31,%32,%33,%34,%35,%36,%37,%38,%39,%40,%41,%42,%43,%44,%45,%46,%47,%48,%49,%50,%51,%52,%53,%54,%55}, %56, %57, p, 1, 1, 0, 1;}"
                 : R8(0), R8(8), R8(16), R8(24), R8(32), R8(40), R8(48)
                 : "l"(da), "l"(db), "r"(sc));
}
__device__ __forceinline__ void wgmma_n128_tn(float* d, desc_t da, desc_t db, int sc) {
    asm volatile("{.reg .pred p; setp.ne.b32 p, %66, 0;\n"
                 "wgmma.mma_async.sync.aligned.m64n128k16.f32.bf16.bf16 {%0,%1,%2,%3,%4,%5,%6,%7,%8,%9,%10,%11,%12,%13,%14,%15,%16,%17,%18,%19,%20,%21,%22,%23,%24,%25,%26,%27,%28,%29,%30,%31,%32,%33,%34,%35,%36,%37,%38,%39,%40,%41,%42,%43,%44,%45,%46,%47,%48,%49,%50,%51,%52,%53,%54,%55,%56,%57,%58,%59,%60,%61,%62,%63}, %64, %65, p, 1, 1, 1, 0;}"
                 : R8(0), R8(8), R8(16), R8(24), R8(32), R8(40), R8(48), R8(56)
                 : "l"(da), "l"(db), "r"(sc));
}
__device__ __forceinline__ void wgmma_n64(float* d, desc_t da, desc_t db, int sc) {
    asm volatile("{.reg .pred p; setp.ne.b32 p, %34, 0;\n"
                 "wgmma.mma_async.sync.aligned.m64n64k16.f32.bf16.bf16 {%0,%1,%2,%3,%4,%5,%6,%7,%8,%9,%10,%11,%12,%13,%14,%15,%16,%17,%18,%19,%20,%21,%22,%23,%24,%25,%26,%27,%28,%29,%30,%31}, %32, %33, p, 1, 1, 0, 1;}"
                 : R8(0), R8(8), R8(16), R8(24)
                 : "l"(da), "l"(db), "r"(sc));
}
__device__ __forceinline__ void wgmma_n40_tt(float* d, desc_t da, desc_t db, int sc) {
    asm volatile("{.reg .pred p; setp.ne.b32 p, %22, 0;\n"
                 "wgmma.mma_async.sync.aligned.m64n40k16.f32.bf16.bf16 {%0,%1,%2,%3,%4,%5,%6,%7,%8,%9,%10,%11,%12,%13,%14,%15,%16,%17,%18,%19}, %20, %21, p, 1, 1, 1, 1;}"
                 : R8(0), R8(8), R4(16)
                 : "l"(da), "l"(db), "r"(sc));
}

__device__ __forceinline__ void wgmma_n8_tt(float* d, desc_t da, desc_t db, int sc) {
    asm volatile("{.reg .pred p; setp.ne.b32 p, %6, 0;\n"
                 "wgmma.mma_async.sync.aligned.m64n8k16.f32.bf16.bf16 {%0,%1,%2,%3}, %4, %5, p, 1, 1, 1, 1;}"
                 : R4(0)
                 : "l"(da), "l"(db), "r"(sc));
}

__device__ __forceinline__ void signal_after(unsigned* cnt, uint32_t ack, uint32_t zero, bool pred) {
    asm volatile("{.reg .pred p; setp.ne.u32 p, %2, 0; @p red.relaxed.gpu.global.add.u32 [%0], %1;}"
                 ::"l"(cnt), "r"((ack & zero) + 1), "r"((uint32_t)pred) : "memory");
}
__device__ __forceinline__ void signal_late(unsigned* cnt, const uint32_t* a, uint32_t zero, bool pred) {
    uint32_t v;
    asm volatile("{.reg .b32 t; lop3.b32 t, %1, %2, %3, 0xfe; or.b32 %0, t, %4;}"
                 : "=r"(v) : "r"(a[0]), "r"(a[1]), "r"(a[2]), "r"(a[3]));
    signal_after(cnt, v, zero, pred);
}
__device__ __forceinline__ void red_f32_if(float* p, float a, bool pred) {
    asm volatile("{.reg .pred p; setp.ne.u32 p, %2, 0; @p red.relaxed.gpu.global.add.f32 [%0], %1;}" ::"l"(p), "f"(a), "r"((uint32_t)pred) : "memory");
}
__device__ __forceinline__ void stg_f2_if(float* p, float a, float b, bool pred) {
    asm volatile("{.reg .pred p; setp.ne.u32 p, %3, 0; @p st.global.v2.f32 [%0], {%1,%2};}" ::"l"(p), "f"(a), "f"(b), "r"((uint32_t)pred) : "memory");
}
__device__ __forceinline__ void stg64(void* p, uint32_t a, uint32_t b) {
    asm volatile("st.global.v2.u32 [%0], {%1,%2};" ::"l"(p), "r"(a), "r"(b) : "memory");
}
__device__ __forceinline__ void mma16816_z(float* c, const uint32_t* a, uint32_t b0, uint32_t b1) {
    asm("mma.sync.aligned.m16n8k16.row.col.f32.bf16.bf16.f32 {%0,%1,%2,%3}, {%4,%5,%6,%7}, {%8,%9}, {%10,%10,%10,%10};"
                 : "=f"(c[0]), "=f"(c[1]), "=f"(c[2]), "=f"(c[3])
                 : "r"(a[0]), "r"(a[1]), "r"(a[2]), "r"(a[3]), "r"(b0), "r"(b1), "f"(0.f));
}
__device__ __forceinline__ uint32_t max2(uint32_t a, uint32_t b) { uint32_t r; asm("max.bf16x2 %0, %1, %2;" : "=r"(r) : "r"(a), "r"(b)); return r; }
__device__ __forceinline__ uint32_t min2(uint32_t a, uint32_t b) { uint32_t r; asm("min.bf16x2 %0, %1, %2;" : "=r"(r) : "r"(a), "r"(b)); return r; }
__device__ __forceinline__ void bar_arrive(int id, int n) { asm volatile("bar.arrive %0, %1;" ::"r"(id), "r"(n) : "memory"); }
__device__ __forceinline__ void mbar_arrive_n_if(uint32_t bar, uint32_t n, bool pred) {
    asm volatile("{.reg .pred p; setp.ne.u32 p, %1, 0; @p mbarrier.arrive.shared::cta.b64 _, [%0], %2;}" ::"r"(bar), "r"((uint32_t)pred), "r"(n) : "memory");
}
__device__ __forceinline__ float4 lds_f4(uint32_t a) {
    float4 v;
    asm volatile("ld.shared.v4.f32 {%0,%1,%2,%3}, [%4];" : "=f"(v.x), "=f"(v.y), "=f"(v.z), "=f"(v.w) : "r"(a) : "memory");
    return v;
}
__device__ __forceinline__ void lds_f4_if(float4& v, uint32_t a, bool pred) {
    asm volatile("{.reg .pred p; setp.ne.u32 p, %5, 0; @p ld.shared.v4.f32 {%0,%1,%2,%3}, [%4];}"
                 : "+f"(v.x), "+f"(v.y), "+f"(v.z), "+f"(v.w) : "r"(a), "r"((uint32_t)pred) : "memory");
}
__device__ __forceinline__ uint4 ld_tagged(const unsigned long long* p) {
    unsigned long long a, b;
    asm volatile("ld.acquire.gpu.global.v2.b64 {%0,%1}, [%2];" : "=l"(a), "=l"(b) : "l"(p) : "memory");
    return make_uint4((unsigned)a, (unsigned)(a >> 32), (unsigned)b, (unsigned)(b >> 32));
}
__device__ __forceinline__ uint4 ld_tagged_rlx(const unsigned long long* p) {
    unsigned long long a, b;
    asm volatile("ld.relaxed.gpu.global.v2.b64 {%0,%1}, [%2];" : "=l"(a), "=l"(b) : "l"(p) : "memory");
    return make_uint4((unsigned)a, (unsigned)(a >> 32), (unsigned)b, (unsigned)(b >> 32));
}
__device__ __forceinline__ void sts32(uint32_t a, uint32_t x) { asm volatile("st.shared.u32 [%0], %1;" ::"r"(a), "r"(x) : "memory"); }
__device__ __forceinline__ void fetch_tagged(const unsigned long long* src, uint32_t dst, unsigned epoch) {
    uint4 v;
    uint32_t it = 0;
    while (true) {
        v = ld_tagged_rlx(src);
        if (!__any_sync(0xffffffffu, v.y != epoch || v.w != epoch)) break;
        __nanosleep(60);
        trap_if_gt(++it, 1u << 22);
    }
    sts64(dst, v.x, v.z);
}
__device__ __forceinline__ void st_tagged_if(unsigned long long* p, float a, float b, unsigned tag, bool pred) {
    const unsigned long long t = (unsigned long long)tag << 32;
    asm volatile("{.reg .pred p; setp.ne.u32 p, %3, 0; @p st.relaxed.gpu.global.v2.b64 [%0], {%1,%2};}"
                 ::"l"(p), "l"(t | __float_as_uint(a)), "l"(t | __float_as_uint(b)), "r"((uint32_t)pred) : "memory");
}

__device__ __forceinline__ void store_tile(uint32_t tile_rows, uint4* gdst, const uint32_t* lo, const uint32_t* hi, int lane, uint32_t* ack) {
    const int r = lane & 15;
#pragma unroll
    for (int b = 0; b < 4; b++)
        stsm4(tile_rows + r * 128 + (((2 * b + (lane >> 4)) ^ (r & 7)) << 4), lo[2 * b], hi[2 * b], lo[2 * b + 1], hi[2 * b + 1]);
    fence_async_smem();
    __syncwarp();
#pragma unroll
    for (int i = 0; i < 4; i++) {
        const uint4 v = lds128(tile_rows + i * 512 + lane * 16);
        stg128(gdst + 32 * i, v.x, v.y, v.z, v.w);
    }
#pragma unroll
    for (int i = 0; i < 4; i++) ack[i] = readback(gdst + 32 * i);
}

__device__ __forceinline__ void feature_maps(const uint32_t* a, const uint32_t* wb, float c0, float c1, uint32_t* plus, uint32_t* minus) {
    uint32_t P[16], mx[4], mn[4];
#pragma unroll
    for (int h = 0; h < 4; h++) {
        float p[8];
        mma16816_z(p, a + 4 * h, wb[4 * h], wb[4 * h + 1]);
        mma16816_z(p + 4, a + 4 * h, wb[4 * h + 2], wb[4 * h + 3]);
        P[4 * h] = pack_bf16(p[0], p[2]); P[4 * h + 1] = pack_bf16(p[1], p[3]);
        P[4 * h + 2] = pack_bf16(p[4], p[6]); P[4 * h + 3] = pack_bf16(p[5], p[7]);
        mx[h] = max2(max2(P[4 * h], P[4 * h + 1]), max2(P[4 * h + 2], P[4 * h + 3]));
        mn[h] = min2(min2(P[4 * h], P[4 * h + 1]), min2(P[4 * h + 2], P[4 * h + 3]));
    }
#pragma unroll
    for (int s = 1; s <= 2; s <<= 1) {
        uint32_t tx[4], tn[4];
#pragma unroll
        for (int h = 0; h < 4; h++) { tx[h] = __shfl_xor_sync(0xffffffffu, mx[h], s); tn[h] = __shfl_xor_sync(0xffffffffu, mn[h], s); }
#pragma unroll
        for (int h = 0; h < 4; h++) { mx[h] = max2(mx[h], tx[h]); mn[h] = min2(mn[h], tn[h]); }
    }
#pragma unroll
    for (int h = 0; h < 4; h++) {
        const float mx0 = bf_lo(mx[h]) * c0, mx1 = bf_hi(mx[h]) * c1, mn0 = bf_lo(mn[h]) * c0, mn1 = bf_hi(mn[h]) * c1;
        float ep[8], em[8];
#pragma unroll
        for (int i = 0; i < 8; i++) {
            const bool r1 = (i & 2);
            const uint32_t w = P[4 * h + (i >> 2) * 2 + (i & 1)];
            const float p = r1 ? bf_hi(w) : bf_lo(w);
            ep[i] = ex2(fmaf(p, r1 ? c1 : c0, r1 ? -mx1 : -mx0));
            em[i] = ex2(fmaf(p, r1 ? -c1 : -c0, r1 ? mn1 : mn0));
        }
        float sp[4], sm[4];
        uint32_t tp[4], tm[4];
#pragma unroll
        for (int i = 0; i < 4; i++) { tp[i] = pack_bf16(ep[2 * i], ep[2 * i + 1]); tm[i] = pack_bf16(em[2 * i], em[2 * i + 1]); }
        mma16816_z(sp, tp, 0x3f803f80u, 0x3f803f80u);
        mma16816_z(sm, tm, 0x3f803f80u, 0x3f803f80u);
        const float r0 = rcp(sp[0] * sm[0]), r1 = rcp(sp[2] * sm[2]);
        const float rs[4] = {r0 * sm[0], r1 * sm[2], r0 * sp[0], r1 * sp[2]};
#pragma unroll
        for (int i = 0; i < 4; i++) {
            plus[4 * h + i] = pack_bf16(ep[2 * i] * rs[i & 1], ep[2 * i + 1] * rs[i & 1]);
            minus[4 * h + i] = pack_bf16(em[2 * i] * rs[2 + (i & 1)], em[2 * i + 1] * rs[2 + (i & 1)]);
        }
    }
}

template <bool SCALE>
__device__ __forceinline__ void ln_frag(const float* acc, uint32_t cs_addr, float rs0, float nm0, float rs1, float nm1, uint32_t* a) {
    const float2 c0 = lds_f2(cs_addr), c1 = lds_f2(cs_addr + 32);
    const float s0 = SCALE ? rs0 : 1.f, s1 = SCALE ? rs1 : 1.f;
    a[0] = pack_bf16(fmaf(nm0, c0.x, acc[0]) * s0, fmaf(nm0, c0.y, acc[1]) * s0);
    a[1] = pack_bf16(fmaf(nm1, c0.x, acc[2]) * s1, fmaf(nm1, c0.y, acc[3]) * s1);
    a[2] = pack_bf16(fmaf(nm0, c1.x, acc[4]) * s0, fmaf(nm0, c1.y, acc[5]) * s0);
    a[3] = pack_bf16(fmaf(nm1, c1.x, acc[6]) * s1, fmaf(nm1, c1.y, acc[7]) * s1);
}

template <int UP>
__device__ __forceinline__ uint32_t hh_pair(const float* ag, float4 cs, float nmean) {
    const float g0 = fmaf(nmean, cs.x, ag[0]), g1 = fmaf(nmean, cs.y, ag[1]);
    const float u0 = fmaf(nmean, cs.z, ag[UP]), u1 = fmaf(nmean, cs.w, ag[UP + 1]);
    return pack_bf16(g0 * u0, g1 * u1);
}
template <int NTP>
__device__ __forceinline__ void hh_stage(const float* acc, const float4* cs, float nm0, float nm1, uint32_t stg, int lane) {
#pragma unroll
    for (int tp = 0; tp < NTP; tp++)
        stsm4(stg + (lane & 15) * 128 + (((2 * tp + (lane >> 4)) ^ (lane & 7)) << 4), hh_pair<32>(acc + 8 * tp, cs[2 * tp], nm0),
              hh_pair<32>(acc + 8 * tp + 2, cs[2 * tp], nm1), hh_pair<32>(acc + 8 * tp + 4, cs[2 * tp + 1], nm0),
              hh_pair<32>(acc + 8 * tp + 6, cs[2 * tp + 1], nm1));
    fence_async_smem();
    __syncwarp();
}

struct Ring {
    int slot; uint32_t phase;
    __device__ __forceinline__ void adv() { if (++slot == NB) { slot = 0; phase ^= 1; } }
    __device__ __forceinline__ void adv5() { slot += slot == 3; adv(); }
};

__global__ void __cluster_dims__(2, 1, 1) __launch_bounds__(NTHREADS, 1) fused_kernel(const __grid_constant__ Params P) {
    extern __shared__ __align__(1024) uint8_t smem_raw[];
    const uint32_t sb = smem_u32(smem_raw);
    const int tid = threadIdx.x, lane = tid & 31;
    const int warp = __shfl_sync(0xffffffffu, tid >> 5, 0);
    const unsigned role = P.role[blockIdx.x], rank = blockIdx.x & 1;
    const int m = role >> 3, j = role & 7;
    const bool helper = role >= 128;

    TL(0, tid == 0); TLG(0, tid == 0);
    float* const acc_j = g_acc + j * ACC_SIZE;

    if (__builtin_expect(warp >= 8, 1)) {
        asm volatile("setmaxnreg.dec.sync.aligned.u32 72;");
        if (elect_one()) {
            if (warp == 8) {
                if (!helper) {
#pragma unroll
                    for (int i = 0; i < NB; i++) mbar_init(sb + BAR_FULLB + 8 * i, 1);
#pragma unroll
                    for (int i = 0; i < 2; i++) {
                        mbar_expect_tx(sb + BAR_FULLB + 8 * i, SLOT);
                        tma2d(sb + OFF_B + i * SLOT, &P.twq, sb + BAR_FULLB + 8 * i, DM + 64 * j, 64 * i);
                        tma2d(sb + OFF_B + i * SLOT + 8192, &P.twq, sb + BAR_FULLB + 8 * i, 2 * DM + 64 * j, 64 * i);
                    }
                }
            } else if (warp == 9) {
#pragma unroll
                for (int i = 0; i < 8; i++) mbar_init(sb + BAR_FULLA + 8 * i, 1);
                if (!helper) {
#pragma unroll
                    for (int i = 0; i < 2; i++) {
                        mbar_expect_tx(sb + BAR_FULLA + 8 * i, SLOT);
                        tma2d(sb + OFF_A + i * SLOT, &P.tx, sb + BAR_FULLA + 8 * i, 64 * i, 128 * m);
                    }
                }
            } else if (warp == 10) {
#pragma unroll
                for (int i = 0; i < 12; i++) mbar_init(sb + BAR_CS1 + 8 * i, i < 2 || i >= 8 ? 64 : (i < 4 ? 32 : 8));
                trap_if_gt(sb & 1023, 0);
            } else {
#pragma unroll
                for (int i = 0; i < 14; i++) mbar_init(sb + (i < 8 ? BAR_EMPTYA : BAR_EMPTYB - 64) + 8 * i, i < 8 ? 8 : 16);
            }
            asm volatile("fence.mbarrier_init.release.cluster;" ::: "memory");
        }
        __syncwarp();
        asm volatile("barrier.cluster.arrive.relaxed.aligned;" ::: "memory");
        const unsigned epoch = ld_relaxed(&g_epoch);
        bar_sync(0, NTHREADS);
        if (helper) {
            if (elect_one()) {
#pragma unroll 1
                for (int i = warp - 8; i < 72; i += 4) {
                    const uint32_t full = sb + BAR_FULLA + 8 * (i & 7), dst = sb + OFF_A + (i & 7) * SLOT;
                    const int n = i >> 1, jj = 2 * j + (i & 1);
                    const bool qkv = n < 12;
                    const int c0 = qkv ? (n < 8 ? DM + 128 * (n & 4) : 0) + 64 * jj : 176 * jj + 8 * ((n - 12) & ~7);
                    const int r0 = qkv ? 128 * (n & 3) : 64 * ((n - 12) & 7);
                    mbar_wait(sb + BAR_EMPTYA + 8 * (i & 7), ((i >> 3) & 1) ^ 1);
                    mbar_expect_tx(full, SLOT);
                    tma2d(dst, qkv ? &P.twq : &P.twg, full, c0, r0);
                    tma2d(dst + 8192, qkv ? &P.twq : &P.twu, full, c0, qkv ? r0 + 64 : r0);
                }
                prefetch_l2(P.wd + (size_t)(4 * j + warp - 8) * 44032, 88064);
            }
            return;
        }
        if (warp == 8) {
            asm volatile("barrier.cluster.wait.aligned;" ::: "memory");
            if (elect_one()) {
                if (m >= 6)
                    asm volatile("cp.async.bulk.prefetch.tensor.2d.L2.global [%0, {%1, %2}];" ::"l"(&P.twq), "r"(DM + DM * (m & 1) + 64 * j), "r"(64 * (m >> 1)) : "memory");
                if (j >= 3)
                    asm volatile("cp.async.bulk.prefetch.tensor.2d.L2.global [%0, {%1, %2}];" ::"l"(&P.tx), "r"(64 * j), "r"(128 * m) : "memory");
                Ring r{2, 0};
                const uint32_t dst = sb + OFF_B + rank * 8192;
#define B_LOAD(TM, C0, R0)                                                                                  \
        mbar_waitc(sb + BAR_EMPTYB + 8 * r.slot, r.phase ^ 1);                                              \
        mbar_expect_tx(sb + BAR_FULLB + 8 * r.slot, SLOT);                                                  \
        tma2d_mc(dst + r.slot * SLOT, TM, sb + BAR_FULLB + 8 * r.slot, C0, R0);
#pragma unroll 1
                for (int i = 2; i < 8; i++) {
                    if (i >= AHEAD && i < 6) mbar_waitc(sb + BAR_FULLB + 8 * (i - AHEAD), 0);
                    B_LOAD(&P.twq, DM + DM * rank + 64 * j, 64 * i)
                    r.adv();
                }
#pragma unroll 1
                for (int i = 8; i < 20; i++) {
                    if (i >= 10 && i < 14) {
                        mbar_waitc(sb + BAR_EMPTYB + 8 * r.slot, r.phase ^ 1);
                        mbar_arrive(sb + BAR_FULLB + 8 * r.slot);
                    } else {
                        const int e = 2 * (i & 3) + rank;
                        B_LOAD(i < 16 ? &P.twq : &P.two, 64 * j, 64 * (i < 16 ? e : KORD(e, j)))
                    }
                    r.adv();
                }
#pragma unroll 1
                for (int i = 0; i < 24; i++) {
                    B_LOAD(&P.twg + rank, 176 * j + 8 * (i & ~7), 64 * (i < 8 ? KORD(i, j) : i & 7))
                    r.adv5();
                }
#pragma unroll 1
                for (int i = 0; i < 12; i++) {
                    B_LOAD(&P.twd, 64 * j, 176 * (2 * (i & 3) + rank) + 64 * (i >> 2))
                    r.adv5();
                }
            }
            return;
        }
        if (warp == 9) {
            if (elect_one()) {
#pragma unroll 1
                for (int i = 2; i < 8; i++) {
                    if (i >= AHEAD + 1) mbar_wait(sb + BAR_FULLA + 8 * (i - AHEAD - 1), 0);
                    mbar_expect_tx(sb + BAR_FULLA + 8 * i, SLOT);
                    tma2d(sb + OFF_A + i * SLOT, &P.tx, sb + BAR_FULLA + 8 * i, 64 * i, 128 * m);
                }
#pragma unroll 1
                for (int i = 2; i < 7; i++) prefetch_tmap(&P.tx + i);
                unsigned nf = 0;
#pragma unroll 1
                for (int r = 1; r < 6; r++) {
                    const int skip = r < 3 ? j : 8;
                    const uint4* src = g_act + ((r - 1) * 128 + m * 8) * 1024;
                    const unsigned* fl = g_flag + (m * 5 + r - 1) * 32;
                    if (r < 4) mbar_wait(sb + BAR_EMPTYA + 8 * (r == 3 ? PF_DELAY : skip == 0), (r - 1) & 1);
                    if (r < 4 || nf != epoch * 8) wait_count(fl, epoch * (r < 3 ? 64 : 8));
                    TL(64 + r, true);
#pragma unroll 1
                    for (int t = 0; t < 8; t++) {
                        if (t == skip) continue;
                        if (t == 6) nf = readback(fl + 32);
                        mbar_wait(sb + BAR_EMPTYA + 8 * t, (r - 1) & 1);
                        mbar_expect_tx(sb + BAR_FULLA + 8 * t, SLOT);
                        asm volatile("cp.async.bulk.shared::cluster.global.mbarrier::complete_tx::bytes [%0], [%1], %2, [%3];"
                                     ::"r"(sb + OFF_A + t * SLOT), "l"(src + t * 1024), "r"(SLOT), "r"(sb + BAR_FULLA + 8 * t) : "memory");
                    }
                }
            }
            return;
        }
        const int a = warp - 10;
        {
            const int row = 16 * j + 8 * a + (lane >> 2);
            const uint32_t ra = sb + OFF_A + row * 128;
            float sh = 0.f, s0 = 0.f, s1 = 0.f, q0 = 0.f, q1 = 0.f;
#pragma unroll 1
            for (int kt = 0; kt < 8; kt++) {
                mbar_wait(sb + BAR_FULLA + 8 * kt, 0);
                if (kt == 0) sh = bf_lo(lds128(ra + ((row & 7) << 4)).x);
#pragma unroll
                for (int i = 0; i < 2; i++) {
                    const uint4 v = lds128(ra + kt * SLOT + (((2 * (lane & 3) + i) ^ (row & 7)) << 4));
                    const uint32_t ww[4] = {v.x, v.y, v.z, v.w};
#pragma unroll
                    for (int e = 0; e < 4; e++) {
                        const float d0 = bf_lo(ww[e]) - sh, d1 = bf_hi(ww[e]) - sh;
                        s0 += d0; q0 = fmaf(d0, d0, q0);
                        s1 += d1; q1 = fmaf(d1, d1, q1);
                    }
                }
            }
            s0 += s1; q0 += q1;
#pragma unroll
            for (int o = 1; o <= 2; o <<= 1) { s0 += __shfl_xor_sync(0xffffffffu, s0, o); q0 += __shfl_xor_sync(0xffffffffu, q0, o); }
            const float md = s0 * (1.f / DM);
            const float rs = rsqrtf(fmaxf(q0 * (1.f / DM) - md * md, 0.f) + 1e-5f);
            st_tagged_if(g_xstat + 2 * (128 * m + row), rs, -(sh + md), epoch, (lane & 3) == 0);
            TL(1, lane == 0 && a == 0);
        }
        const unsigned long long* cs = g_cs + j * 768 + 2 * lane;
        {
            const unsigned long long* xs = g_xstat + 2 * (128 * m + 64 * a + lane);
            uint4 v0, v1, v2;
            uint32_t it = 0;
            do {
                v0 = ld_tagged_rlx(xs); v1 = ld_tagged_rlx(xs + 64); v2 = ld_tagged_rlx(cs + 128 * a);
                trap_if_gt(++it, 1u << 22);
            } while (__any_sync(0xffffffffu, v0.y != epoch || v0.w != epoch || v1.y != epoch || v1.w != epoch || v2.y != epoch || v2.w != epoch));
            sts64(sb + OFF_XST + (64 * a + lane) * 8, v0.x, v0.z);
            sts64(sb + OFF_XST + (64 * a + 32 + lane) * 8, v1.x, v1.z);
            sts64(sb + OFF_CS1 + 256 * (a + 1) + 8 * lane, v2.x, v2.z);
            mbar_arrive(sb + BAR_CS1);
            TL(22 + a, lane == 0);
            if (a) {
                fetch_tagged(cs + 256, sb + OFF_CS1 + 8 * lane, epoch);
                mbar_arrive(sb + BAR_CSQ);
                TL(24, lane == 0);
            }
        }
        {
            mbar_wait(sb + BAR_KVW, 0);
            const float* src = acc_j + 4 * (128 * a + lane);
            float4 v[12];
            uint32_t it = 0;
            bool bad;
            while (__any_sync(0xffffffffu, readback(acc_j + 2048 + 128 * (lane & 7) + 127) != 0x41800000u)) trap_if_gt(++it, 1u << 22);
            TL(19, lane == 0 && a == 0);
            do {
                bad = false;
#pragma unroll
                for (int i = 0; i < 12; i++) v[i] = ld_l2_f4(src + 1024 * (i % 3) + 128 * (i / 3));
#pragma unroll
                for (int i = 0; i < 12; i++) bad |= v[i].w != 16.f;
                trap_if_gt(++it, 1u << 22);
            } while (__any_sync(0xffffffffu, bad));
            TL(14, lane == 0 && a == 0);
            const uint32_t d0 = sb + OFF_A + KVS(j) * SLOT + (64 * a + (lane >> 2)) * 48;
            const uint32_t d = d0 + (lane & 3) * 4, dz = d0 + (lane & 1) * 384 + 32 + (lane & 2) * 4;
#pragma unroll
            for (int u = 0; u < 4; u++) {
                sts32(d + 768 * u, pack_bf16(v[3 * u].x, v[3 * u].y));
                sts32(d + 768 * u + 384, pack_bf16(v[3 * u].z, v[3 * u + 1].z));
                sts32(d + 768 * u + 16, pack_bf16(v[3 * u + 1].x, v[3 * u + 1].y));
                sts32(d + 768 * u + 400, pack_bf16(v[3 * u + 2].x, v[3 * u + 2].y));
                const uint32_t z2 = pack_bf16(v[3 * u + 2].z, v[3 * u + 2].z);
                sts64(dz + 768 * u, z2, z2);
            }
            mbar_arrive(sb + BAR_KVR);
        }
#pragma unroll 1
        for (int c = 0; c < 3; c++) {
            fetch_tagged(cs + 384 + 128 * c + 64 * a, sb + OFF_CS3 + (32 * c + lane) * 16 + 8 * a, epoch);
            mbar_arrive(sb + BAR_CSG + 8 * c);
            TL(45 + c, lane == 0 && a == 0);
        }
        {
            uint32_t it = 0;
            while (__any_sync(0xffffffffu, (int)(readback(g_flag + (m * 5 + 1) * 32) - epoch * 64) < 0)) {
                __nanosleep(200);
                trap_if_gt(++it, 1u << 22);
            }
#pragma unroll 1
            for (int rr = 0; rr < 2; rr++) {
                const int row = 64 * rr + 32 * a + lane;
                const unsigned long long* hs = g_hstat + (1024 * m + row) * 2;
                uint4 v[8];
                bool bad;
                do {
                    bad = false;
#pragma unroll
                    for (int i = 0; i < 8; i++) v[i] = ld_tagged_rlx(hs + 256 * i);
#pragma unroll
                    for (int i = 0; i < 8; i++) bad |= v[i].y != epoch || v[i].w != epoch;
                    trap_if_gt(++it, 1u << 22);
                } while (__any_sync(0xffffffffu, bad));
                float mean = 0.f;
#pragma unroll
                for (int i = 0; i < 8; i++) mean += __uint_as_float(v[i].x);
                mean *= 0.125f;
                float m2 = 0.f, dv = 0.f;
#pragma unroll
                for (int i = 0; i < 8; i++) { const float d = __uint_as_float(v[i].x) - mean; m2 += __uint_as_float(v[i].z); dv = fmaf(d, d, dv); }
                sts_f2(sb + OFF_CS1 + row * 8, -mean, rcp(fmaf(dv, 64.f, m2) * (1.f / DM) + 1e-5f));
            }
        }
        mbar_arrive(sb + BAR_CS3);
#pragma unroll 1
        for (int c = a; c < 3; c += 2) {
            mbar_wait(sb + BAR_STG + 8 * c, 0);
            if (elect_one()) {
                asm volatile("cp.async.bulk.global.shared::cta.bulk_group [%0], [%1], %2;" ::"l"(g_act + ((2 + c) * 128 + role) * 1024), "r"(sb + OFF_B + 4 * SLOT), "r"(SLOT) : "memory");
                asm volatile("cp.async.bulk.commit_group;" ::: "memory");
                asm volatile("cp.async.bulk.wait_group.read 0;" ::: "memory");
                mbar_arrive(sb + BAR_FULLB + 8 * 4);
                asm volatile("cp.async.bulk.wait_group 0;" ::: "memory");
            }
            __syncwarp();
            TL(60 + c, lane == 0);
            uint32_t ack = 0;
            const uint4* rb = g_act + ((2 + c) * 128 + role) * 1024 + lane * 8;
#pragma unroll
            for (int i = 0; i < 4; i++) ack |= readback(rb + 256 * i);
            signal_after(g_flag + (m * 5 + 2 + c) * 32, ack, P.zero, lane == 0);
            TL(54 + c, lane == 0);
        }
        return;
    }
    const unsigned epoch = ld_relaxed(&g_epoch);
    uint32_t wraw[16];
    if (!helper) {
        const uint32_t* wp = reinterpret_cast<const uint32_t*>(P.wphi) + (4 * j) * 128 + (lane & 3) * 16 + (lane >> 2);
#pragma unroll
        for (int i = 0; i < 16; i++)
            asm volatile("ld.global.nc.u32 %0, [%1];" : "=r"(wraw[i]) : "l"(wp + (i >> 2) * 128 + ((i >> 1) & 1) * 64 + (i & 1) * 8));
    }
    asm volatile("barrier.cluster.arrive.relaxed.aligned;" ::: "memory");
    asm volatile("setmaxnreg.inc.sync.aligned.u32 216;");
    bar_sync(0, NTHREADS);
    if (helper) {
        const int w = warp >> 2;
        sts64(sb + OFF_B + 8 * tid, 0x3f803f80u, 0x3f803f80u);
#pragma unroll 1
        for (int i = tid; i < 2 * ACC_SIZE / 4; i += 256) stg128(g_acc + 2 * j * ACC_SIZE + 4 * i, 0, 0, 0, 0);
        fence_async_smem();
        fence_gpu();
        bar_sync(1, 256);
        float acc[8];
        int i = w;
#pragma unroll 1
        for (int job = 0; job < 6; job++) {
            const int n = job < 3 ? 4 : 8;
#pragma unroll 1
            for (int t = 0; t < n; t++, i += 2) {
                mbar_waitc(sb + BAR_FULLA + 8 * (i & 7), (i >> 3) & 1);
                const desc_t da = desc_lo(sb + OFF_A) + (i & 7) * (SLOT >> 4);
                wg_fence();
#pragma unroll
                for (int k = 0; k < 8; k++) wgmma_n8_tt(acc + (k & 4), da + 128 * k, desc_lo(sb + OFF_B), (t | (k & 3)) != 0);
                wg_commit();
                wg_wait<0>();
                mbar_arrive_n_if(sb + BAR_EMPTYA + 8 * (i & 7), 2, lane == 0);
            }
            fence_acc<8>(acc);
            const int q = lane & 3;
            const float lo = (q & 1) ? acc[2] : acc[0], hi = (q & 1) ? acc[6] : acc[4];
            const float v = job < 3 ? lo + hi : ((q & 2) ? hi : lo);
            unsigned long long* dst = g_cs + ((2 * j + w) * 6 + job) * 128 + (q >> 1) * 64 + 16 * (warp & 3) + 8 * (q & 1) + (lane >> 2);
            asm volatile("st.relaxed.gpu.global.b64 [%0], %1;" ::"l"(dst), "l"(((unsigned long long)epoch << 32) | __float_as_uint(v)) : "memory");
        }
        return;
    }
    {
        const int w = warp >> 2, wv = warp & 3, g = lane >> 2, q = lane & 3;
        const uint32_t sa = sb + OFF_A + w * 8192;
        const desc_t dA = desc_lo(sa), dB = desc_lo(sb + OFF_B);
        unsigned* const flag_m = g_flag + m * 160;
        const bool l0 = lane == 0, l2 = lane < 2;
        const uint32_t eb = mapa(sb + BAR_EMPTYB, lane & 1);
        asm volatile("barrier.cluster.wait.aligned;" ::: "memory");
        Ring rg{0, 0};
        int prev = 0;

        uint32_t wb[16];
        constexpr float L2E = 1.4426950408889634f;
        const int ch = lane >> 4, sw = lane & 7;
        const uint32_t lrow = (lane & 15) * 128;
        uint32_t fp[16], fm[16];
        {
            float acc[64], accq[32];
#pragma unroll 1
            for (int kt = 0; kt < 8; kt++) {
                mbar_waitc(sb + BAR_FULLA + 8 * kt, 0);
                mbar_waitc(sb + BAR_FULLB + 8 * rg.slot, rg.phase);
                const desc_t da = dA + kt * (SLOT >> 4), db = dB + rg.slot * (SLOT >> 4);
                wg_fence();
#pragma unroll
                for (int k = 0; k < 4; k++) wgmma_n128(acc, da + 2 * k, db + 128 * k, (kt | k) != 0);
                wg_commit();
                wg_wait<1>();
                mbar_arrive_cl_if(eb + 8 * prev, l2 && kt > 0);
                prev = rg.slot; rg.adv();
            }
#pragma unroll
            for (int i = 0; i < 8; i++) {
                wb[(i >> 1) * 4 + (i & 1)] = __byte_perm(wraw[2 * i], wraw[2 * i + 1], 0x5410);
                wb[(i >> 1) * 4 + 2 + (i & 1)] = __byte_perm(wraw[2 * i], wraw[2 * i + 1], 0x7632);
            }
            float2 s0, s1;
            uint32_t a[16];
            wg_wait<0>();
            fence_acc<64>(acc);
            mbar_arrive_cl_if(eb + 8 * prev, l2);
#pragma unroll 1
            for (int it = 0; it < 2; it++) {
                mbar_waitc(sb + BAR_FULLB + 8 * 2, it ^ 1); mbar_waitc(sb + BAR_FULLB + 8 * 3, it ^ 1);
                const desc_t da = dA + it * (4 * SLOT >> 4);
                wg_fence();
#pragma unroll
                for (int k = 0; k < 16; k++) wgmma_n64(accq, da + (k >> 2) * (SLOT >> 4) + (k & 3) * 2, dB + 2 * (SLOT >> 4) + 128 * k, (it | k) != 0);
                wg_commit();
                TL(17 + it, tid == 0);
                mbar_waitc(sb + BAR_CS1 + 16 * it, 0);
                wg_wait<0>();
                fence_acc<32>(accq);
                mbar_arrive_cl_if(eb + 8 * (2 + (lane >> 1)), lane < 4);
                TL(2 + 2 * it, tid == 0);
                if (it == 0) {
                    s0 = lds_f2(sb + OFF_XST + (16 * warp + g) * 8); s1 = lds_f2(sb + OFF_XST + (16 * warp + g + 8) * 8);
#pragma unroll
                    for (int hh = 0; hh < 4; hh++)
                        ln_frag<false>(acc + 8 * hh, sb + OFF_CS1 + (64 + 16 * hh + 2 * q) * 4, 0.f, s0.y, 0.f, s1.y, a + 4 * hh);
                } else {
#pragma unroll
                    for (int hh = 0; hh < 4; hh++)
                        ln_frag<false>(accq + 8 * hh, sb + OFF_CS1 + (16 * hh + 2 * q) * 4, 0.f, s0.y, 0.f, s1.y, a + 4 * hh);
                }
                feature_maps(a, wb, s0.x * L2E, s1.x * L2E, fp, fm);
                if (it == 0) {
                    mbar_waitc(sb + BAR_FULLB + 8 * 4, 1); mbar_waitc(sb + BAR_FULLB + 8 * 5, 1);
                    mbar_waitc(sb + BAR_FULLB + 8 * 0, 0); mbar_waitc(sb + BAR_FULLB + 8 * 1, 0);
                    const uint32_t st = sb + OFF_B + warp * 2048 + lrow;
#pragma unroll
                    for (int hh = 0; hh < 4; hh++) {
                        stsm4(st + (4 + (hh >> 1)) * SLOT + (((4 * (hh & 1) + ch) ^ sw) << 4), fp[4 * hh], fp[4 * hh + 1], fp[4 * hh + 2], fp[4 * hh + 3]);
                        stsm4(st + (4 + (hh >> 1)) * SLOT + (((4 * (hh & 1) + 2 + ch) ^ sw) << 4), fm[4 * hh], fm[4 * hh + 1], fm[4 * hh + 2], fm[4 * hh + 3]);
                        ln_frag<true>(acc + 32 + 8 * hh, sb + OFF_CS1 + (128 + 16 * hh + 2 * q) * 4, s0.x, s0.y, s1.x, s1.y, a);
                        stsm4(st + (hh >> 1) * SLOT + (((2 * (hh & 1) + ch) ^ sw) << 4), a[0], a[1], a[2], a[3]);
                    }
                    stsm4(st + ch * SLOT + ((4 ^ sw) << 4), 0x3f803f80u, 0x3f803f80u, 0x3f803f80u, 0x3f803f80u);
                    fence_async_smem();
                    bar_sync(1, 256);
                    float kvd[20];
                    wg_fence();
#pragma unroll
                    for (int k = 0; k < 8; k++)
                        wgmma_n40_tt(kvd, dB + (4 + w) * (SLOT >> 4) + 128 * k, dB + w * (SLOT >> 4) + 128 * k, k != 0);
                    wg_commit();
                    wg_wait<0>();
                    fence_acc<20>(kvd);
                    const bool h1 = wv >= 2;
                    float* kvp = acc_j + 4 * tid;
                    red_f32x4(kvp, h1 ? kvd[8] : kvd[0], h1 ? kvd[9] : kvd[1], h1 ? kvd[10] : kvd[2], 1.f);
                    red_f32x4(kvp + 1024, h1 ? kvd[12] : kvd[4], h1 ? kvd[13] : kvd[5], h1 ? kvd[11] : kvd[3], 1.f);
                    red_f32x4(kvp + 2048, h1 ? kvd[14] : kvd[6], h1 ? kvd[15] : kvd[7], (q & 1) ? kvd[18] : kvd[16], 1.f);
                    __syncwarp();
                    mbar_arrive_if(sb + BAR_KVW, l0);
                    mbar_arrive_cl_if(eb + 8 * ((4 + (lane >> 1)) % 6), lane < 8);
                    TL(3, tid == 0);
                }
            }
        }
        uint32_t res_lo[8], res_hi[8], ack[4];
        const uint32_t own_rows = sb + OFF_A + j * SLOT + warp * 2048;
#pragma unroll
        for (int b = 0; b < 4; b++)
            ldsm4(own_rows + lrow + (((2 * b + ch) ^ sw) << 4), res_lo[2 * b], res_hi[2 * b], res_lo[2 * b + 1], res_hi[2 * b + 1]);
        mbar_arrive_if(sb + BAR_EMPTYA + 8 * lane, lane < 8 && lane != j && lane != KVS(j));
        TL(5, tid == 0);
        mbar_waitc(sb + BAR_KVR, 0);
        TL(6, tid == 0);
        {
            const uint32_t kvs = sb + OFF_A + KVS(j) * SLOT;
            uint32_t o_lo[8], o_hi[8];
#pragma unroll
            for (int hh = 0; hh < 4; hh++) {
                uint32_t b[8], zb[4];
                const uint32_t base = kvs + hh * 32 * 48;
                ldsm4t(base + (lane & 15) * 48 + (lane >> 4) * 16, b[0], b[1], b[2], b[3]);
                ldsm4t(base + (16 + (lane & 15)) * 48 + (lane >> 4) * 16, b[4], b[5], b[6], b[7]);
                ldsm4t(base + lane * 48 + 32, zb[0], zb[1], zb[2], zb[3]);
                float n0[4], n1[4], dn[4];
                mma16816_z(n0, fp + 4 * hh, b[0], b[1]); mma16816_z(n1, fp + 4 * hh, b[2], b[3]); mma16816_z(dn, fp + 4 * hh, zb[0], zb[1]);
                mma16816(n0, fm + 4 * hh, b[4], b[5]); mma16816(n1, fm + 4 * hh, b[6], b[7]); mma16816(dn, fm + 4 * hh, zb[2], zb[3]);
                const float i0 = rcp(dn[0] + 1e-6f), i1 = rcp(dn[2] + 1e-6f);
                o_lo[2 * hh] = pack_bf16(n0[0] * i0, n0[1] * i0); o_hi[2 * hh] = pack_bf16(n0[2] * i1, n0[3] * i1);
                o_lo[2 * hh + 1] = pack_bf16(n1[0] * i0, n1[1] * i0); o_hi[2 * hh + 1] = pack_bf16(n1[2] * i1, n1[3] * i1);
            }
            __syncwarp();
            mbar_arrive_if(sb + BAR_EMPTYA + 8 * KVS(j), l0);
            rg.slot = 4; rg.phase = 0;
            store_tile(own_rows, g_act + role * 1024 + warp * 128 + lane, o_lo, o_hi, lane, ack);
            TL(7, tid == 0);
        }
        float acch[32];
        {
            float* acc = acch;
#pragma unroll
            for (int t = 0; t < 8; t++) {
                acc[4 * t] = bf_lo(res_lo[t]); acc[4 * t + 1] = bf_hi(res_lo[t]);
                acc[4 * t + 2] = bf_lo(res_hi[t]); acc[4 * t + 3] = bf_hi(res_hi[t]);
            }
            fence_acc<32>(acc);
            int pa = 0;
#pragma unroll 1
            for (int kp = 0; kp < 4; kp++) {
                mbar_waitc(sb + BAR_FULLB + 8 * rg.slot, rg.phase);
#pragma unroll
                for (int hf = 0; hf < 2; hf++) {
                    const int i = 2 * kp + hf, kt = KORD(i, j);
                    mbar_waitc(sb + BAR_FULLA + 8 * kt, i != 0);
                    TL(8, i == 1 && tid == 0);
                    const desc_t da = dA + kt * (SLOT >> 4), db = dB + rg.slot * (SLOT >> 4);
                    wg_fence();
#pragma unroll
                    for (int k = 0; k < 4; k++) wgmma_n64(acc, da + 2 * k, db + (hf * 4 + k) * 128, 1);
                    wg_commit();
                    wg_wait<1>();
                    mbar_arrive_if(sb + BAR_EMPTYA + 8 * pa, l0 && i > 1);
                    if (hf == 0) {
                        mbar_arrive_cl_if(eb + 8 * prev, l2 && i > 0);
                        if (i == 0) { signal_late(flag_m, ack, P.zero, l0); TL(20, tid == 0); }
                    }
                    pa = kt;
                }
                prev = rg.slot; rg.adv();
            }
            wg_wait<0>();
            fence_acc<32>(acc);
            mbar_arrive_if(sb + BAR_EMPTYA + 8 * pa, l0);
            mbar_arrive_cl_if(eb + 8 * prev, l2);
            TL(9, tid == 0);
#pragma unroll
            for (int t = 0; t < 8; t++) {
                res_lo[t] = pack_bf16(acc[4 * t], acc[4 * t + 1]);
                res_hi[t] = pack_bf16(acc[4 * t + 2], acc[4 * t + 3]);
            }
            store_tile(own_rows, g_act + (128 + role) * 1024 + warp * 128 + lane, res_lo, res_hi, lane, ack);
            TL(10, tid == 0);
        }
        float acc0[64], acc1[64], acc2[56], nm0, nm1;
        float4 cs[8];
        uint32_t hr[16];
#define P3_GROUP(MMA, ACC, KT)                                                                              \
        mbar_waitc(sb + BAR_FULLB + 8 * rg.slot, rg.phase);                                                 \
        {                                                                                                   \
            const desc_t da = dA + (KT) * (SLOT >> 4), db = dB + rg.slot * (SLOT >> 4);                     \
            wg_fence();                                                                                     \
            _Pragma("unroll") for (int k = 0; k < 4; k++) MMA(ACC, da + 2 * k, db + 128 * k, (i | k) != 0); \
            wg_commit();                                                                                    \
        }
#define P3_CS(C, NT)    \
        _Pragma("unroll") for (int t = 0; t < (NT); t++) lds_f4_if(cs[t], sb + OFF_CS3 + q * 16 + 512 * (C) + 64 * t, i == t);
#define P3_EPI(C, ACC, N, NTP)                                                                              \
        fence_acc<N>(ACC);                                                                                  \
        TL(11 + (C), tid == 0);                                                                             \
        hh_stage<NTP>(ACC, cs, nm0, nm1, sb + OFF_B + 4 * SLOT + warp * 2048, lane);                        \
        mbar_arrive_if(sb + BAR_STG + 8 * (C), l0);                                                         \
        TL(50 + (C), tid == 0);
        const uint32_t blk = ((lane & 7) + (lane >> 4) * 8) * 128 + (((2 * wv + ((lane >> 3) & 1)) ^ (lane & 7)) << 4);
#pragma unroll 1
        for (int i = 0; i < 8; i++) {
            const int kt = KORD(i, j);
            mbar_waitc(sb + BAR_FULLA + 8 * kt, 0);
            TL(44, tid == 0 && i == 1);
            P3_GROUP(wgmma_n128, acc0, kt)
            if (i == 7) {
                mbar_waitc(sb + BAR_CS3, 0);
                nm0 = lds_f2(sb + OFF_CS1 + (16 * warp + g) * 8).x; nm1 = lds_f2(sb + OFF_CS1 + (16 * warp + g + 8) * 8).x;
            }
            wg_wait<1>();
            mbar_arrive_cl_if(eb + 8 * prev, l2 && i > 0);
            if (i == 0) {
                signal_late(flag_m + 32, ack, P.zero, l0);
                TL(21, tid == 0);
                {
                    fence_acc<32>(acch);
                    const float* acc = acch;
                    float s0 = 0.f, s1 = 0.f;
#pragma unroll
                    for (int t = 0; t < 8; t++) { s0 += acc[4 * t] + acc[4 * t + 1]; s1 += acc[4 * t + 2] + acc[4 * t + 3]; }
            s0 += __shfl_xor_sync(0xffffffffu, s0, 1); s1 += __shfl_xor_sync(0xffffffffu, s1, 1);
            s0 += __shfl_xor_sync(0xffffffffu, s0, 2); s1 += __shfl_xor_sync(0xffffffffu, s1, 2);
            const float mu0 = s0 * (1.f / 64), mu1 = s1 * (1.f / 64);
            float q0 = 0.f, q1 = 0.f;
#pragma unroll
            for (int t = 0; t < 8; t++) {
                float d;
                d = acc[4 * t] - mu0; q0 = fmaf(d, d, q0);
                d = acc[4 * t + 1] - mu0; q0 = fmaf(d, d, q0);
                d = acc[4 * t + 2] - mu1; q1 = fmaf(d, d, q1);
                d = acc[4 * t + 3] - mu1; q1 = fmaf(d, d, q1);
            }
            q0 += __shfl_xor_sync(0xffffffffu, q0, 1); q1 += __shfl_xor_sync(0xffffffffu, q1, 1);
            q0 += __shfl_xor_sync(0xffffffffu, q0, 2); q1 += __shfl_xor_sync(0xffffffffu, q1, 2);
            st_tagged_if(g_hstat + (role * 128 + 16 * warp + g + 8 * (q & 1)) * 2, q ? mu1 : mu0, q ? q1 : q0, epoch, q < 2);
                }
                bar_sync(2 + w, 128);
#pragma unroll
                for (int tp = 0; tp < 4; tp++) ldsm4t(sa + j * SLOT + blk + tp * 2048, hr[4 * tp], hr[4 * tp + 1], hr[4 * tp + 2], hr[4 * tp + 3]);
                mbar_waitc(sb + BAR_CSG, 0);
#pragma unroll
                for (int t = 0; t < 8; t++) cs[t] = lds_f4(sb + OFF_CS3 + q * 16 + 64 * t);
            }
            prev = rg.slot; rg.adv5();
        }
#pragma unroll 1
        for (int i = 0; i < 8; i++) {
            P3_GROUP(wgmma_n128, acc1, i)
            wg_wait<1>();
            mbar_arrive_cl_if(eb + 8 * prev, l2);
            if (i == 0) { P3_EPI(0, acc0, 64, 4) mbar_waitc(sb + BAR_CSG + 8, 0); }
            P3_CS(1, 8)
            prev = rg.slot; rg.adv5();
        }
#pragma unroll 1
        for (int i = 0; i < 8; i++) {
            P3_GROUP(wgmma_n112, acc2, i)
            wg_wait<1>();
            mbar_arrive_cl_if(eb + 8 * prev, l2);
            mbar_arrive_if(sb + BAR_EMPTYA + 8 * ((i + 7) & 7), l0 && i > 0);
            if (i == 0) { mbar_waitc(sb + BAR_FULLB + 8 * 4, 1); P3_EPI(1, acc1, 64, 4) mbar_waitc(sb + BAR_CSG + 16, 0); }
            P3_CS(2, 6)
            prev = rg.slot; rg.adv5();
        }
        mbar_waitc(sb + BAR_FULLB + 8 * 4, 0);
        wg_wait<0>();
        mbar_arrive_cl_if(eb + 8 * prev, l2);
        mbar_arrive_if(sb + BAR_EMPTYA + 8 * 7, l0);
        P3_EPI(2, acc2, 56, 3)
        {
            float acc[64];
            const desc_t dA0 = desc_lo(sb + OFF_A);
#define KT_P4(I, NK)                                                                                        \
        const int s_ = (2 * (I) + w) & 7;                                                                   \
        mbar_waitc(sb + BAR_FULLB + 8 * rg.slot, rg.phase);                                                 \
        mbar_waitc(sb + BAR_FULLA + 8 * s_, (((I) >> 2) + 1) & 1);                                          \
        const desc_t dh_ = dA0 + s_ * (SLOT >> 4), dw_ = dB + rg.slot * (SLOT >> 4) + w * 512;              \
        wg_fence();                                                                                         \
        _Pragma("unroll") for (int k = 0; k < (NK); k++) wgmma_n128_tn(acc, dw_ + 128 * k, dh_ + 2 * k, ((I) | k) != 0); \
        wg_commit();                                                                                        \
        wg_wait<1>();
#pragma unroll 1
            for (int i = 0; i < 8; i++) {
                KT_P4(i, 4)
                mbar_arrive_n_if(sb + BAR_EMPTYA + 8 * ((s_ + 6) & 7), 2, l0 && i > 0);
                mbar_arrive_cl_if(eb + 8 * prev, l2 && i > 0);
#pragma unroll
                for (int t = 0; t < 8; t++) lds_f4_if(cs[t], sb + OFF_CS1 + (64 * w + 8 * t + 2 * q) * 8, i == t);
                prev = rg.slot; rg.adv5();
            }
#pragma unroll 1
            for (int i = 8; i < 12; i++) {
                KT_P4(i, 3)
                mbar_arrive_n_if(sb + BAR_EMPTYA + 8 * ((s_ + 6) & 7), 2, l0);
                rg.adv5();
            }
            wg_wait<0>();
            fence_acc<64>(acc);
            TL(15, tid == 0);
            const uint32_t xch = sb + OFF_A + 2 * SLOT + (tid & 127) * 16;
            if (w) {
#pragma unroll
                for (int t = 0; t < 8; t++) {
                    sts128(xch + SLOT + t * 2048, __float_as_uint(acc[4 * t]), __float_as_uint(acc[4 * t + 1]),
                           __float_as_uint(acc[4 * t + 2]), __float_as_uint(acc[4 * t + 3]));
                }
#pragma unroll
                for (int t = 0; t < 32; t++) acc[t] = acc[32 + t];
            } else {
#pragma unroll
                for (int t = 0; t < 8; t++)
                    sts128(xch + t * 2048, __float_as_uint(acc[32 + 4 * t]), __float_as_uint(acc[33 + 4 * t]),
                           __float_as_uint(acc[34 + 4 * t]), __float_as_uint(acc[35 + 4 * t]));
            }
            bar_sync(1, 256);
            float4 o[8];
#pragma unroll
            for (int t = 0; t < 8; t++) o[t] = lds_f4(xch + (w ^ 1) * SLOT + t * 2048);
            const uint32_t tile = sb + OFF_A + w * SLOT;
#pragma unroll
            for (int t = 0; t < 8; t++) {
                hr[2 * t] = pack_bf16(fmaf(acc[4 * t] + o[t].x, cs[t].y, bf_lo(hr[2 * t])), fmaf(acc[4 * t + 1] + o[t].y, cs[t].w, bf_hi(hr[2 * t])));
                hr[2 * t + 1] = pack_bf16(fmaf(acc[4 * t + 2] + o[t].z, cs[t].y, bf_lo(hr[2 * t + 1])), fmaf(acc[4 * t + 3] + o[t].w, cs[t].w, bf_hi(hr[2 * t + 1])));
            }
#pragma unroll
            for (int tp = 0; tp < 4; tp++) stsm4t(tile + blk + tp * 2048, hr[4 * tp], hr[4 * tp + 1], hr[4 * tp + 2], hr[4 * tp + 3]);
            fence_async_smem();
            bar_sync(2 + w, 128);
            if ((tid & 127) == 0) {
                tma_store2d(&P.tout, tile, 64 * j, 128 * m + 64 * w);
                asm volatile("cp.async.bulk.wait_group.read 0;" ::: "memory");
            }
            if (tid == 0 && role == 0) g_epoch = epoch + 1;
            TL(16, tid == 0); TLG(1, tid == 0);
        }
    }
}

__global__ void probe_kernel() {}

typedef CUresult (*EncodeFn)(CUtensorMap*, CUtensorMapDataType, cuuint32_t, void*, const cuuint64_t*, const cuuint64_t*,
                             const cuuint32_t*, const cuuint32_t*, CUtensorMapInterleave, CUtensorMapSwizzle,
                             CUtensorMapL2promotion, CUtensorMapFloatOOBfill);

static void make_map2d(EncodeFn enc, CUtensorMap* tm, const void* base, uint64_t cols, uint64_t rows, uint64_t pitch_elems,
                       uint32_t box_rows) {
    cuuint64_t gd[2] = {cols, rows};
    cuuint64_t gs[1] = {pitch_elems * 2};
    cuuint32_t bd[2] = {64, box_rows};
    cuuint32_t es[2] = {1, 1};
    enc(tm, CU_TENSOR_MAP_DATA_TYPE_BFLOAT16, 2, const_cast<void*>(base), gd, gs, bd, es, CU_TENSOR_MAP_INTERLEAVE_NONE,
        CU_TENSOR_MAP_SWIZZLE_128B, CU_TENSOR_MAP_L2_PROMOTION_L2_256B, CU_TENSOR_MAP_FLOAT_OOB_FILL_NONE);
}

}

extern "C" void kernel_launch(void* const* d_in, const int* in_sizes, int n_in, void* d_out, int out_size) {
    using namespace hk;
    (void)in_sizes; (void)n_in; (void)out_size;
    static EncodeFn enc = nullptr;
    static int std_layout = 0;
    if (!enc) {
        void* fn = nullptr;
        cudaDriverEntryPointQueryResult qr;
        cudaGetDriverEntryPoint("cuTensorMapEncodeTiled", &fn, cudaEnableDefault, &qr);
        enc = (EncodeFn)fn;
        cudaFuncSetAttribute(fused_kernel, cudaFuncAttributeMaxDynamicSharedMemorySize, SMEM_BYTES);
        int dev = 0, sms = 0;
        cudaGetDevice(&dev);
        cudaDeviceGetAttribute(&sms, cudaDevAttrMultiProcessorCount, dev);
        cudaFuncSetAttribute(probe_kernel, cudaFuncAttributeNonPortableClusterSizeAllowed, 1);
        cudaFuncSetAttribute(probe_kernel, cudaFuncAttributeMaxDynamicSharedMemorySize, SMEM_BYTES);
        const int sizes[3] = {8, 9, 16}, want[3] = {15, 9, 7};
        bool ok = sms == NCTA;
        for (int i = 0; i < 3 && ok; i++) {
            cudaLaunchConfig_t cfg = {};
            cfg.gridDim = dim3(sizes[i] * 8); cfg.blockDim = dim3(NTHREADS); cfg.dynamicSmemBytes = SMEM_BYTES;
            cudaLaunchAttribute at;
            at.id = cudaLaunchAttributeClusterDimension;
            at.val.clusterDim.x = sizes[i]; at.val.clusterDim.y = 1; at.val.clusterDim.z = 1;
            cfg.attrs = &at; cfg.numAttrs = 1;
            int n = 0;
            ok = cudaOccupancyMaxActiveClusters(&n, probe_kernel, &cfg) == cudaSuccess && n == want[i];
        }
        (void)cudaGetLastError();
        std_layout = ok ? 1 : 0;
    }
    Params P;
    const __nv_bfloat16* x = (const __nv_bfloat16*)d_in[0];
    P.x = x;
    P.wqkv = (const __nv_bfloat16*)d_in[1];
    P.wphi = (const __nv_bfloat16*)d_in[2];
    P.wo = (const __nv_bfloat16*)d_in[3];
    P.wg = (const __nv_bfloat16*)d_in[5];
    P.wu = (const __nv_bfloat16*)d_in[6];
    P.wd = (const __nv_bfloat16*)d_in[7];
    P.out = (__nv_bfloat16*)d_out;
    P.zero = 0;
    for (int i = 0; i < NCTA; i++) {
        const int odd = i & 1;
        int role = i < 4 ? 128 + i : (((i - 4) >> 4) * 2 + odd) * 8 + (((i - 4) >> 1) & 7);
        if (std_layout) {
            const int tpc = i < 8 ? 62 + (i >> 1) : (i - 8) >> 1;
            if (tpc < 32) role = (tpc & 7) ? (2 * ((tpc & 7) - 1) + odd) * 8 + (tpc >> 3) : (14 + odd) * 8 + (tpc >> 3);
            else if (tpc < 60) role = (2 * ((tpc - 32) % 7) + odd) * 8 + 4 + (tpc - 32) / 7;
            else if (tpc < 62) role = 128 + (tpc - 60) * 2 + odd;
            else role = (14 + odd) * 8 + 4 + (tpc - 62);
        }
        P.role[i] = (unsigned char)role;
    }
    make_map2d(enc, &P.tx, x, DM, SEQ, DM, 128);
    make_map2d(enc, &P.twq, P.wqkv, 3 * DM, DM, 3 * DM, 64);
    make_map2d(enc, &P.two, P.wo, DM, DM, DM, 64);
    make_map2d(enc, &P.twg, P.wg, FF, DM, FF, 64);
    make_map2d(enc, &P.twu, P.wu, FF, DM, FF, 64);
    make_map2d(enc, &P.twd, P.wd, DM, FF, DM, 64);
    make_map2d(enc, &P.tout, d_out, DM, SEQ, DM, 64);
    fused_kernel<<<NCTA, NTHREADS, SMEM_BYTES>>>(P);
}
```

```cpp
#include <cuda_runtime.h>
#include <cuda_bf16.h>
#include <cuda.h>
#include <stdint.h>

namespace hk {

constexpr int SEQ = 2048, DM = 512, FF = 1376;
constexpr int NCTA = 132;
constexpr int NTHREADS = 384;
constexpr uint32_t SLOT = 16384;
constexpr uint32_t OFF_A = 0, OFF_B = 8 * SLOT, OFF_MISC = 14 * SLOT;
constexpr uint32_t BAR_FULLA = OFF_MISC + 0, BAR_EMPTYA = OFF_MISC + 64, BAR_FULLB = OFF_MISC + 128,
                   BAR_EMPTYB = OFF_MISC + 176, BAR_CS1 = OFF_MISC + 224, BAR_CS3 = OFF_MISC + 232,
                   BAR_CSQ = OFF_MISC + 240, BAR_CSV = OFF_MISC + 248,
                   BAR_STG = OFF_MISC + 256,
                   BAR_KVW = OFF_MISC + 280, BAR_KVR = OFF_MISC + 288, BAR_CSG = OFF_MISC + 296;
constexpr uint32_t OFF_CS1 = OFF_MISC + 384;
constexpr uint32_t OFF_CS3 = OFF_CS1 + 1024;
constexpr uint32_t OFF_XST = OFF_CS3;
constexpr uint32_t SMEM_BYTES = OFF_CS3 + 1536;
#define KVS(j) ((j) == 3 ? 2 : 3)
#define KORD(i, j) ((i) == 0 ? (j) : (i) - ((i) <= (j)))
constexpr int NB = 6;
#define PF_DELAY 2
#define KV_POLL 1
constexpr int AHEAD = 3;

constexpr int ACC_SIZE = 3 * 256 * 4;

__device__ __align__(1024) uint4 g_act[5 * 128 * 1024];
__device__ __align__(128) unsigned long long g_hstat[SEQ * 16];
__device__ __align__(128) unsigned long long g_xstat[SEQ * 2];
__device__ __align__(128) float g_acc[8 * ACC_SIZE];
__device__ __align__(128) unsigned long long g_cs[8 * 6 * 128];
__device__ __align__(128) unsigned g_flag[16 * 5 * 32 + 32];
__device__ unsigned g_epoch = 1;

#define TL(i, pred) do {} while (0)
#define TLG(i, pred) do {} while (0)

struct Params {
    CUtensorMap tx, twq, two, twg, twu, twd, tout;
    const __nv_bfloat16 *x, *wqkv, *wphi, *wo, *wg, *wu, *wd;
    __nv_bfloat16* out;
    unsigned zero;
    unsigned char role[NCTA];
};

__device__ __forceinline__ uint32_t smem_u32(const void* p) { return (uint32_t)__cvta_generic_to_shared(p); }
__device__ __forceinline__ void mbar_init(uint32_t bar, uint32_t cnt) {
    asm volatile("mbarrier.init.shared::cta.b64 [%0], %1;" ::"r"(bar), "r"(cnt) : "memory");
}
__device__ __forceinline__ void mbar_expect_tx(uint32_t bar, uint32_t bytes) {
    asm volatile("mbarrier.arrive.expect_tx.shared::cta.b64 _, [%0], %1;" ::"r"(bar), "r"(bytes) : "memory");
}
__device__ __forceinline__ void mbar_arrive(uint32_t bar) {
    asm volatile("mbarrier.arrive.shared::cta.b64 _, [%0];" ::"r"(bar) : "memory");
}
__device__ __forceinline__ void mbar_arrive_if(uint32_t bar, bool pred) {
    asm volatile("{.reg .pred p; setp.ne.u32 p, %1, 0; @p mbarrier.arrive.shared::cta.b64 _, [%0];}" ::"r"(bar), "r"((uint32_t)pred) : "memory");
}
__device__ __forceinline__ bool mbar_try(uint32_t bar, uint32_t parity) {
    uint32_t ok;
    asm volatile("{.reg .pred p; mbarrier.try_wait.parity.shared::cta.b64 p, [%1], %2; selp.u32 %0,1,0,p;}"
                 : "=r"(ok) : "r"(bar), "r"(parity) : "memory");
    return ok;
}
__device__ __forceinline__ bool mbar_test(uint32_t bar, uint32_t parity) {
    uint32_t ok;
    asm volatile("{.reg .pred p; mbarrier.test_wait.parity.shared::cta.b64 p, [%1], %2; selp.u32 %0,1,0,p;}"
                 : "=r"(ok) : "r"(bar), "r"(parity) : "memory");
    return ok;
}
__device__ __forceinline__ void trap_if_gt(uint32_t v, uint32_t lim) {
    asm volatile("{.reg .pred p; setp.gt.u32 p, %0, %1; @p trap;}" ::"r"(v), "r"(lim));
}
__device__ __forceinline__ void mbar_wait(uint32_t bar, uint32_t parity) {
    asm volatile("{\n"
                 ".reg .pred P1, P2;\n"
                 ".reg .u32 c;\n"
                 "mov.u32 c, 0;\n"
                 "LAB_WAIT:\n"
                 "mbarrier.try_wait.parity.shared::cta.b64 P1, [%0], %1;\n"
                 "@P1 bra LAB_DONE;\n"
                 "add.u32 c, c, 1;\n"
                 "setp.gt.u32 P2, c, 4194304;\n"
                 "@P2 trap;\n"
                 "bra LAB_WAIT;\n"
                 "LAB_DONE:\n"
                 "}" ::"r"(bar), "r"(parity) : "memory");
}
__device__ __forceinline__ void mbar_waitc(uint32_t bar, uint32_t parity) {
    asm volatile("{\n"
                 ".reg .pred P1;\n"
                 "LAB_WAIT:\n"
                 "mbarrier.try_wait.parity.shared::cta.b64 P1, [%0], %1;\n"
                 "@!P1 bra LAB_WAIT;\n"
                 "}" ::"r"(bar), "r"(parity) : "memory");
}
__device__ __forceinline__ void tma2d(uint32_t dst, const CUtensorMap* tm, uint32_t bar, int c0, int c1) {
    asm volatile("cp.async.bulk.tensor.2d.shared::cluster.global.mbarrier::complete_tx::bytes [%0], [%1, {%3, %4}], [%2];"
                 ::"r"(dst), "l"(tm), "r"(bar), "r"(c0), "r"(c1) : "memory");
}
__device__ __forceinline__ void tma2d_mc(uint32_t dst, const CUtensorMap* tm, uint32_t bar, int c0, int c1) {
    asm volatile("cp.async.bulk.tensor.2d.shared::cluster.global.mbarrier::complete_tx::bytes.multicast::cluster [%0], [%1, {%3, %4}], [%2], %5;"
                 ::"r"(dst), "l"(tm), "r"(bar), "r"(c0), "r"(c1), "h"((uint16_t)3) : "memory");
}
__device__ __forceinline__ uint32_t mapa(uint32_t addr, uint32_t rank) {
    uint32_t r; asm("mapa.shared::cluster.u32 %0, %1, %2;" : "=r"(r) : "r"(addr), "r"(rank)); return r;
}
__device__ __forceinline__ void mbar_arrive_cl_if(uint32_t cbar, bool pred) {
    asm volatile("{.reg .pred p; setp.ne.u32 p, %1, 0; @p mbarrier.arrive.shared::cluster.b64 _, [%0];}" ::"r"(cbar), "r"((uint32_t)pred) : "memory");
}
__device__ __forceinline__ bool elect_one() {
    uint32_t ok;
    asm volatile("{.reg .pred p; elect.sync _|p, 0xffffffff; selp.u32 %0, 1, 0, p;}" : "=r"(ok));
    return ok;
}
__device__ __forceinline__ void prefetch_tmap(const CUtensorMap* tm) {
    asm volatile("prefetch.tensormap [%0];" ::"l"(tm) : "memory");
}
__device__ __forceinline__ void prefetch_l2(const void* p, uint32_t bytes) {
    asm volatile("cp.async.bulk.prefetch.L2.global [%0], %1;" ::"l"(p), "r"(bytes) : "memory");
}
__device__ __forceinline__ unsigned ld_acquire(const unsigned* p) {
    unsigned v; asm volatile("ld.acquire.gpu.global.u32 %0, [%1];" : "=r"(v) : "l"(p) : "memory"); return v;
}
__device__ __forceinline__ uint4 ld_acquire4(const unsigned* p) {
    uint4 v;
    asm volatile("ld.acquire.gpu.global.v4.u32 {%0,%1,%2,%3}, [%4];" : "=r"(v.x), "=r"(v.y), "=r"(v.z), "=r"(v.w) : "l"(p) : "memory");
    return v;
}
__device__ __forceinline__ unsigned ld_relaxed(const unsigned* p) {
    unsigned v; asm volatile("ld.relaxed.gpu.global.u32 %0, [%1];" : "=r"(v) : "l"(p)); return v;
}
__device__ __forceinline__ void st_relaxed(unsigned* p, unsigned v) {
    asm volatile("st.relaxed.gpu.global.u32 [%0], %1;" ::"l"(p), "r"(v) : "memory");
}
__device__ __forceinline__ void red_relaxed(unsigned* p, unsigned v) {
    asm volatile("red.relaxed.gpu.global.add.u32 [%0], %1;" ::"l"(p), "r"(v) : "memory");
}
__device__ __forceinline__ void fence_gpu() { asm volatile("fence.acq_rel.gpu;" ::: "memory"); }
__device__ __forceinline__ void fence_async_smem() { asm volatile("fence.proxy.async.shared::cta;" ::: "memory"); }
__device__ __forceinline__ void fence_async_global() { asm volatile("fence.proxy.async.global;" ::: "memory"); }
__device__ __forceinline__ uint32_t readback(const void* p) {
    uint32_t v; asm volatile("ld.relaxed.gpu.global.u32 %0, [%1];" : "=r"(v) : "l"(p) : "memory"); return v;
}
__device__ __forceinline__ void wait_count(const unsigned* p, unsigned target) {
    uint32_t it = 0;
    while ((int)(readback(p) - target) < 0) trap_if_gt(++it, 1u << 22);
}
__device__ __forceinline__ void wait_count_warp(const unsigned* p, unsigned target) {
    uint32_t it = 0;
    while (__any_sync(0xffffffffu, (int)(readback(p) - target) < 0)) trap_if_gt(++it, 1u << 22);
}
__device__ __forceinline__ void red_f32(float* p, float a) {
    asm volatile("red.relaxed.gpu.global.add.f32 [%0], %1;" ::"l"(p), "f"(a) : "memory");
}
__device__ __forceinline__ void red_f32x2(float* p, float a, float b) {
    asm volatile("red.relaxed.gpu.global.add.v2.f32 [%0], {%1, %2};" ::"l"(p), "f"(a), "f"(b) : "memory");
}
__device__ __forceinline__ void red_f32x4(float* p, float a, float b, float c, float d) {
    asm volatile("red.relaxed.gpu.global.add.v4.f32 [%0], {%1, %2, %3, %4};" ::"l"(p), "f"(a), "f"(b), "f"(c), "f"(d) : "memory");
}
__device__ __forceinline__ float4 ld_l2_f4(const float* p) {
    float4 v;
    asm volatile("ld.relaxed.gpu.global.v4.f32 {%0,%1,%2,%3}, [%4];" : "=f"(v.x), "=f"(v.y), "=f"(v.z), "=f"(v.w) : "l"(p) : "memory");
    return v;
}
__device__ __forceinline__ float2 ld_l2_f2(const float* p) {
    float2 v;
    asm volatile("ld.relaxed.gpu.global.v2.f32 {%0,%1}, [%2];" : "=f"(v.x), "=f"(v.y) : "l"(p) : "memory");
    return v;
}
__device__ __forceinline__ float ld_l2_f(const float* p) {
    float v;
    asm volatile("ld.relaxed.gpu.global.f32 %0, [%1];" : "=f"(v) : "l"(p) : "memory");
    return v;
}
__device__ __forceinline__ uint4 ldg_nc(const void* p) {
    uint4 v;
    asm volatile("ld.global.nc.L1::no_allocate.v4.u32 {%0,%1,%2,%3}, [%4];" : "=r"(v.x), "=r"(v.y), "=r"(v.z), "=r"(v.w) : "l"(p));
    return v;
}
__device__ __forceinline__ void stg128(void* p, uint32_t a, uint32_t b, uint32_t c, uint32_t d) {
    asm volatile("st.global.v4.u32 [%0], {%1,%2,%3,%4};" ::"l"(p), "r"(a), "r"(b), "r"(c), "r"(d) : "memory");
}
__device__ __forceinline__ uint4 lds128(uint32_t a) {
    uint4 v;
    asm volatile("ld.shared.v4.u32 {%0,%1,%2,%3}, [%4];" : "=r"(v.x), "=r"(v.y), "=r"(v.z), "=r"(v.w) : "r"(a) : "memory");
    return v;
}
__device__ __forceinline__ float2 lds_f2(uint32_t a) {
    float2 v;
    asm volatile("ld.shared.v2.f32 {%0,%1}, [%2];" : "=f"(v.x), "=f"(v.y) : "r"(a) : "memory");
    return v;
}
__device__ __forceinline__ void sts_f2(uint32_t a, float x, float y) {
    asm volatile("st.shared.v2.f32 [%0], {%1,%2};" ::"r"(a), "f"(x), "f"(y) : "memory");
}
__device__ __forceinline__ void sts64(uint32_t a, uint32_t x, uint32_t y) {
    asm volatile("st.shared.v2.u32 [%0], {%1,%2};" ::"r"(a), "r"(x), "r"(y) : "memory");
}
__device__ __forceinline__ void sts128(uint32_t a, uint32_t x, uint32_t y, uint32_t z, uint32_t w) {
    asm volatile("st.shared.v4.u32 [%0], {%1,%2,%3,%4};" ::"r"(a), "r"(x), "r"(y), "r"(z), "r"(w) : "memory");
}
__device__ __forceinline__ void stsm4(uint32_t a, uint32_t r0, uint32_t r1, uint32_t r2, uint32_t r3) {
    asm volatile("stmatrix.sync.aligned.m8n8.x4.shared.b16 [%0], {%1,%2,%3,%4};" ::"r"(a), "r"(r0), "r"(r1), "r"(r2), "r"(r3) : "memory");
}
__device__ __forceinline__ void stsm4t(uint32_t a, uint32_t r0, uint32_t r1, uint32_t r2, uint32_t r3) {
    asm volatile("stmatrix.sync.aligned.m8n8.x4.trans.shared.b16 [%0], {%1,%2,%3,%4};" ::"r"(a), "r"(r0), "r"(r1), "r"(r2), "r"(r3) : "memory");
}
__device__ __forceinline__ void tma_store2d(const CUtensorMap* tm, uint32_t src, int c0, int c1) {
    asm volatile("cp.async.bulk.tensor.2d.global.shared::cta.bulk_group [%0, {%2, %3}], [%1];" ::"l"(tm), "r"(src), "r"(c0), "r"(c1) : "memory");
    asm volatile("cp.async.bulk.commit_group;" ::: "memory");
}
__device__ __forceinline__ void ldsm4(uint32_t a, uint32_t& r0, uint32_t& r1, uint32_t& r2, uint32_t& r3) {
    asm volatile("ldmatrix.sync.aligned.m8n8.x4.shared.b16 {%0,%1,%2,%3}, [%4];" : "=r"(r0), "=r"(r1), "=r"(r2), "=r"(r3) : "r"(a) : "memory");
}
__device__ __forceinline__ void ldsm4t(uint32_t a, uint32_t& r0, uint32_t& r1, uint32_t& r2, uint32_t& r3) {
    asm volatile("ldmatrix.sync.aligned.m8n8.x4.trans.shared.b16 {%0,%1,%2,%3}, [%4];" : "=r"(r0), "=r"(r1), "=r"(r2), "=r"(r3) : "r"(a) : "memory");
}
__device__ __forceinline__ void mma16816(float* c, const uint32_t* a, uint32_t b0, uint32_t b1) {
    asm("mma.sync.aligned.m16n8k16.row.col.f32.bf16.bf16.f32 {%0,%1,%2,%3}, {%4,%5,%6,%7}, {%8,%9}, {%0,%1,%2,%3};"
                 : "+f"(c[0]), "+f"(c[1]), "+f"(c[2]), "+f"(c[3])
                 : "r"(a[0]), "r"(a[1]), "r"(a[2]), "r"(a[3]), "r"(b0), "r"(b1));
}
__device__ __forceinline__ uint32_t pack_bf16(float lo, float hi) {
    uint32_t r; asm("cvt.rn.bf16x2.f32 %0, %1, %2;" : "=r"(r) : "f"(hi), "f"(lo)); return r;
}
__device__ __forceinline__ float bf_lo(uint32_t w) { return __uint_as_float(w << 16); }
__device__ __forceinline__ float bf_hi(uint32_t w) { return __uint_as_float(w & 0xffff0000u); }
__device__ __forceinline__ float ex2(float x) { float r; asm("ex2.approx.ftz.f32 %0, %1;" : "=f"(r) : "f"(x)); return r; }
__device__ __forceinline__ float rcp(float x) { float r; asm("rcp.approx.ftz.f32 %0, %1;" : "=f"(r) : "f"(x)); return r; }
__device__ __forceinline__ void bar_sync(int id, int n) { asm volatile("bar.sync %0, %1;" ::"r"(id), "r"(n) : "memory"); }

typedef unsigned long long desc_t;
__device__ __forceinline__ desc_t desc_lo(uint32_t addr) { return (desc_t)(((addr & 0x3FFFF) >> 4) | (512u << 16)) | (0x40000040ull << 32); }
__device__ __forceinline__ void wg_fence() { asm volatile("wgmma.fence.sync.aligned;" ::: "memory"); }
__device__ __forceinline__ void wg_commit() { asm volatile("wgmma.commit_group.sync.aligned;" ::: "memory"); }
template <int N> __device__ __forceinline__ void wg_wait() { asm volatile("wgmma.wait_group.sync.aligned %0;" ::"n"(N) : "memory"); }
template <int N> __device__ __forceinline__ void fence_acc(float* d) {
#pragma unroll
    for (int i = 0; i < N; i++) asm volatile("" : "+f"(d[i])::"memory");
}
#define R4(o) "+f"(d[o + 0]), "+f"(d[o + 1]), "+f"(d[o + 2]), "+f"(d[o + 3])
#define R8(o) R4(o), R4(o + 4)
__device__ __forceinline__ void wgmma_n128(float* d, desc_t da, desc_t db, int sc) {
    asm volatile("{.reg .pred p; setp.ne.b32 p, %66, 0;\n"
                 "wgmma.mma_async.sync.aligned.m64n128k16.f32.bf16.bf16 {%0,%1,%2,%3,%4,%5,%6,%7,%8,%9,%10,%11,%12,%13,%14,%15,%16,%17,%18,%19,%20,%21,%22,%23,%24,%25,%26,%27,%28,%29,%30,%31,"
                 "%32,%33,%34,%35,%36,%37,%38,%39,%40,%41,%42,%43,%44,%45,%46,%47,%48,%49,%50,%51,%52,%53,%54,%55,%56,%57,%58,%59,%60,%61,%62,%63}, %64, %65, p, 1, 1, 0, 1;}"
                 : R8(0), R8(8), R8(16), R8(24), R8(32), R8(40), R8(48), R8(56)
                 : "l"(da), "l"(db), "r"(sc));
}
__device__ __forceinline__ void wgmma_n112(float* d, desc_t da, desc_t db, int sc) {
    asm volatile("{.reg .pred p; setp.ne.b32 p, %58, 0;\n"
                 "wgmma.mma_async.sync.aligned.m64n112k16.f32.bf16.bf16 {%0,%1,%2,%3,%4,%5,%6,%7,%8,%9,%10,%11,%12,%13,%14,%15,%16,%17,%18,%19,%20,%21,%22,%23,%24,%25,%26,%27,%28,%29,%30,%31,%32,%33,%34,%35,%36,%37,%38,%39,%40,%41,%42,%43,%44,%45,%46,%47,%48,%49,%50,%51,%52,%53,%54,%55}, %56, %57, p, 1, 1, 0, 1;}"
                 : R8(0), R8(8), R8(16), R8(24), R8(32), R8(40), R8(48)
                 : "l"(da), "l"(db), "r"(sc));
}
__device__ __forceinline__ void wgmma_n128_tn(float* d, desc_t da, desc_t db, int sc) {
    asm volatile("{.reg .pred p; setp.ne.b32 p, %66, 0;\n"
                 "wgmma.mma_async.sync.aligned.m64n128k16.f32.bf16.bf16 {%0,%1,%2,%3,%4,%5,%6,%7,%8,%9,%10,%11,%12,%13,%14,%15,%16,%17,%18,%19,%20,%21,%22,%23,%24,%25,%26,%27,%28,%29,%30,%31,%32,%33,%34,%35,%36,%37,%38,%39,%40,%41,%42,%43,%44,%45,%46,%47,%48,%49,%50,%51,%52,%53,%54,%55,%56,%57,%58,%59,%60,%61,%62,%63}, %64, %65, p, 1, 1, 1, 0;}"
                 : R8(0), R8(8), R8(16), R8(24), R8(32), R8(40), R8(48), R8(56)
                 : "l"(da), "l"(db), "r"(sc));
}
__device__ __forceinline__ void wgmma_n64(float* d, desc_t da, desc_t db, int sc) {
    asm volatile("{.reg .pred p; setp.ne.b32 p, %34, 0;\n"
                 "wgmma.mma_async.sync.aligned.m64n64k16.f32.bf16.bf16 {%0,%1,%2,%3,%4,%5,%6,%7,%8,%9,%10,%11,%12,%13,%14,%15,%16,%17,%18,%19,%20,%21,%22,%23,%24,%25,%26,%27,%28,%29,%30,%31}, %32, %33, p, 1, 1, 0, 1;}"
                 : R8(0), R8(8), R8(16), R8(24)
                 : "l"(da), "l"(db), "r"(sc));
}
__device__ __forceinline__ void wgmma_n40_tt(float* d, desc_t da, desc_t db, int sc) {
    asm volatile("{.reg .pred p; setp.ne.b32 p, %22, 0;\n"
                 "wgmma.mma_async.sync.aligned.m64n40k16.f32.bf16.bf16 {%0,%1,%2,%3,%4,%5,%6,%7,%8,%9,%10,%11,%12,%13,%14,%15,%16,%17,%18,%19}, %20, %21, p, 1, 1, 1, 1;}"
                 : R8(0), R8(8), R4(16)
                 : "l"(da), "l"(db), "r"(sc));
}

__device__ __forceinline__ void wgmma_n8_tt(float* d, desc_t da, desc_t db, int sc) {
    asm volatile("{.reg .pred p; setp.ne.b32 p, %6, 0;\n"
                 "wgmma.mma_async.sync.aligned.m64n8k16.f32.bf16.bf16 {%0,%1,%2,%3}, %4, %5, p, 1, 1, 1, 1;}"
                 : R4(0)
                 : "l"(da), "l"(db), "r"(sc));
}

__device__ __forceinline__ void signal_after(unsigned* cnt, uint32_t ack, uint32_t zero, bool pred) {
    asm volatile("{.reg .pred p; setp.ne.u32 p, %2, 0; @p red.relaxed.gpu.global.add.u32 [%0], %1;}"
                 ::"l"(cnt), "r"((ack & zero) + 1), "r"((uint32_t)pred) : "memory");
}
__device__ __forceinline__ void signal_late(unsigned* cnt, const uint32_t* a, uint32_t zero, bool pred) {
    uint32_t v;
    asm volatile("{.reg .b32 t; lop3.b32 t, %1, %2, %3, 0xfe; or.b32 %0, t, %4;}"
                 : "=r"(v) : "r"(a[0]), "r"(a[1]), "r"(a[2]), "r"(a[3]));
    signal_after(cnt, v, zero, pred);
}
__device__ __forceinline__ void red_f32_if(float* p, float a, bool pred) {
    asm volatile("{.reg .pred p; setp.ne.u32 p, %2, 0; @p red.relaxed.gpu.global.add.f32 [%0], %1;}" ::"l"(p), "f"(a), "r"((uint32_t)pred) : "memory");
}
__device__ __forceinline__ void stg_f2_if(float* p, float a, float b, bool pred) {
    asm volatile("{.reg .pred p; setp.ne.u32 p, %3, 0; @p st.global.v2.f32 [%0], {%1,%2};}" ::"l"(p), "f"(a), "f"(b), "r"((uint32_t)pred) : "memory");
}
__device__ __forceinline__ void stg64(void* p, uint32_t a, uint32_t b) {
    asm volatile("st.global.v2.u32 [%0], {%1,%2};" ::"l"(p), "r"(a), "r"(b) : "memory");
}
__device__ __forceinline__ void mma16816_z(float* c, const uint32_t* a, uint32_t b0, uint32_t b1) {
    asm("mma.sync.aligned.m16n8k16.row.col.f32.bf16.bf16.f32 {%0,%1,%2,%3}, {%4,%5,%6,%7}, {%8,%9}, {%10,%10,%10,%10};"
                 : "=f"(c[0]), "=f"(c[1]), "=f"(c[2]), "=f"(c[3])
                 : "r"(a[0]), "r"(a[1]), "r"(a[2]), "r"(a[3]), "r"(b0), "r"(b1), "f"(0.f));
}
__device__ __forceinline__ uint32_t max2(uint32_t a, uint32_t b) { uint32_t r; asm("max.bf16x2 %0, %1, %2;" : "=r"(r) : "r"(a), "r"(b)); return r; }
__device__ __forceinline__ uint32_t min2(uint32_t a, uint32_t b) { uint32_t r; asm("min.bf16x2 %0, %1, %2;" : "=r"(r) : "r"(a), "r"(b)); return r; }
__device__ __forceinline__ void bar_arrive(int id, int n) { asm volatile("bar.arrive %0, %1;" ::"r"(id), "r"(n) : "memory"); }
__device__ __forceinline__ void mbar_arrive_n_if(uint32_t bar, uint32_t n, bool pred) {
    asm volatile("{.reg .pred p; setp.ne.u32 p, %1, 0; @p mbarrier.arrive.shared::cta.b64 _, [%0], %2;}" ::"r"(bar), "r"((uint32_t)pred), "r"(n) : "memory");
}
__device__ __forceinline__ float4 lds_f4(uint32_t a) {
    float4 v;
    asm volatile("ld.shared.v4.f32 {%0,%1,%2,%3}, [%4];" : "=f"(v.x), "=f"(v.y), "=f"(v.z), "=f"(v.w) : "r"(a) : "memory");
    return v;
}
__device__ __forceinline__ void lds_f4_if(float4& v, uint32_t a, bool pred) {
    asm volatile("{.reg .pred p; setp.ne.u32 p, %5, 0; @p ld.shared.v4.f32 {%0,%1,%2,%3}, [%4];}"
                 : "+f"(v.x), "+f"(v.y), "+f"(v.z), "+f"(v.w) : "r"(a), "r"((uint32_t)pred) : "memory");
}
__device__ __forceinline__ uint4 ld_tagged(const unsigned long long* p) {
    unsigned long long a, b;
    asm volatile("ld.acquire.gpu.global.v2.b64 {%0,%1}, [%2];" : "=l"(a), "=l"(b) : "l"(p) : "memory");
    return make_uint4((unsigned)a, (unsigned)(a >> 32), (unsigned)b, (unsigned)(b >> 32));
}
__device__ __forceinline__ uint4 ld_tagged_rlx(const unsigned long long* p) {
    unsigned long long a, b;
    asm volatile("ld.relaxed.gpu.global.v2.b64 {%0,%1}, [%2];" : "=l"(a), "=l"(b) : "l"(p) : "memory");
    return make_uint4((unsigned)a, (unsigned)(a >> 32), (unsigned)b, (unsigned)(b >> 32));
}
__device__ __forceinline__ void sts32(uint32_t a, uint32_t x) { asm volatile("st.shared.u32 [%0], %1;" ::"r"(a), "r"(x) : "memory"); }
__device__ __forceinline__ void fetch_tagged(const unsigned long long* src, uint32_t dst, unsigned epoch) {
    uint4 v;
    uint32_t it = 0;
    while (true) {
        v = ld_tagged_rlx(src);
        if (!__any_sync(0xffffffffu, v.y != epoch || v.w != epoch)) break;
        __nanosleep(60);
        trap_if_gt(++it, 1u << 22);
    }
    sts64(dst, v.x, v.z);
}
__device__ __forceinline__ void st_tagged_if(unsigned long long* p, float a, float b, unsigned tag, bool pred) {
    const unsigned long long t = (unsigned long long)tag << 32;
    asm volatile("{.reg .pred p; setp.ne.u32 p, %3, 0; @p st.relaxed.gpu.global.v2.b64 [%0], {%1,%2};}"
                 ::"l"(p), "l"(t | __float_as_uint(a)), "l"(t | __float_as_uint(b)), "r"((uint32_t)pred) : "memory");
}

__device__ __forceinline__ void store_tile(uint32_t tile_rows, uint4* gdst, const uint32_t* lo, const uint32_t* hi, int lane, uint32_t* ack) {
    const int r = lane & 15;
#pragma unroll
    for (int b = 0; b < 4; b++)
        stsm4(tile_rows + r * 128 + (((2 * b + (lane >> 4)) ^ (r & 7)) << 4), lo[2 * b], hi[2 * b], lo[2 * b + 1], hi[2 * b + 1]);
    fence_async_smem();
    __syncwarp();
#pragma unroll
    for (int i = 0; i < 4; i++) {
        const uint4 v = lds128(tile_rows + i * 512 + lane * 16);
        stg128(gdst + 32 * i, v.x, v.y, v.z, v.w);
    }
#pragma unroll
    for (int i = 0; i < 4; i++) ack[i] = readback(gdst + 32 * i);
}

__device__ __forceinline__ void feature_maps(const uint32_t* a, const uint32_t* wb, float c0, float c1, uint32_t* plus, uint32_t* minus) {
    uint32_t P[16], mx[4], mn[4];
#pragma unroll
    for (int h = 0; h < 4; h++) {
        float p[8];
        mma16816_z(p, a + 4 * h, wb[4 * h], wb[4 * h + 1]);
        mma16816_z(p + 4, a + 4 * h, wb[4 * h + 2], wb[4 * h + 3]);
        P[4 * h] = pack_bf16(p[0], p[2]); P[4 * h + 1] = pack_bf16(p[1], p[3]);
        P[4 * h + 2] = pack_bf16(p[4], p[6]); P[4 * h + 3] = pack_bf16(p[5], p[7]);
        mx[h] = max2(max2(P[4 * h], P[4 * h + 1]), max2(P[4 * h + 2], P[4 * h + 3]));
        mn[h] = min2(min2(P[4 * h], P[4 * h + 1]), min2(P[4 * h + 2], P[4 * h + 3]));
    }
#pragma unroll
    for (int s = 1; s <= 2; s <<= 1) {
        uint32_t tx[4], tn[4];
#pragma unroll
        for (int h = 0; h < 4; h++) { tx[h] = __shfl_xor_sync(0xffffffffu, mx[h], s); tn[h] = __shfl_xor_sync(0xffffffffu, mn[h], s); }
#pragma unroll
        for (int h = 0; h < 4; h++) { mx[h] = max2(mx[h], tx[h]); mn[h] = min2(mn[h], tn[h]); }
    }
#pragma unroll
    for (int h = 0; h < 4; h++) {
        const float mx0 = bf_lo(mx[h]) * c0, mx1 = bf_hi(mx[h]) * c1, mn0 = bf_lo(mn[h]) * c0, mn1 = bf_hi(mn[h]) * c1;
        float ep[8], em[8];
#pragma unroll
        for (int i = 0; i < 8; i++) {
            const bool r1 = (i & 2);
            const uint32_t w = P[4 * h + (i >> 2) * 2 + (i & 1)];
            const float p = r1 ? bf_hi(w) : bf_lo(w);
            ep[i] = ex2(fmaf(p, r1 ? c1 : c0, r1 ? -mx1 : -mx0));
            em[i] = ex2(fmaf(p, r1 ? -c1 : -c0, r1 ? mn1 : mn0));
        }
        float sp[4], sm[4];
        uint32_t tp[4], tm[4];
#pragma unroll
        for (int i = 0; i < 4; i++) { tp[i] = pack_bf16(ep[2 * i], ep[2 * i + 1]); tm[i] = pack_bf16(em[2 * i], em[2 * i + 1]); }
        mma16816_z(sp, tp, 0x3f803f80u, 0x3f803f80u);
        mma16816_z(sm, tm, 0x3f803f80u, 0x3f803f80u);
        const float r0 = rcp(sp[0] * sm[0]), r1 = rcp(sp[2] * sm[2]);
        const float rs[4] = {r0 * sm[0], r1 * sm[2], r0 * sp[0], r1 * sp[2]};
#pragma unroll
        for (int i = 0; i < 4; i++) {
            plus[4 * h + i] = pack_bf16(ep[2 * i] * rs[i & 1], ep[2 * i + 1] * rs[i & 1]);
            minus[4 * h + i] = pack_bf16(em[2 * i] * rs[2 + (i & 1)], em[2 * i + 1] * rs[2 + (i & 1)]);
        }
    }
}

template <bool SCALE>
__device__ __forceinline__ void ln_frag(const float* acc, uint32_t cs_addr, float rs0, float nm0, float rs1, float nm1, uint32_t* a) {
    const float2 c0 = lds_f2(cs_addr), c1 = lds_f2(cs_addr + 32);
    const float s0 = SCALE ? rs0 : 1.f, s1 = SCALE ? rs1 : 1.f;
    a[0] = pack_bf16(fmaf(nm0, c0.x, acc[0]) * s0, fmaf(nm0, c0.y, acc[1]) * s0);
    a[1] = pack_bf16(fmaf(nm1, c0.x, acc[2]) * s1, fmaf(nm1, c0.y, acc[3]) * s1);
    a[2] = pack_bf16(fmaf(nm0, c1.x, acc[4]) * s0, fmaf(nm0, c1.y, acc[5]) * s0);
    a[3] = pack_bf16(fmaf(nm1, c1.x, acc[6]) * s1, fmaf(nm1, c1.y, acc[7]) * s1);
}

template <int UP>
__device__ __forceinline__ uint32_t hh_pair(const float* ag, float4 cs, float nmean) {
    const float g0 = fmaf(nmean, cs.x, ag[0]), g1 = fmaf(nmean, cs.y, ag[1]);
    const float u0 = fmaf(nmean, cs.z, ag[UP]), u1 = fmaf(nmean, cs.w, ag[UP + 1]);
    return pack_bf16(g0 * u0, g1 * u1);
}
template <int TP0, int TP1>
__device__ __forceinline__ void hh_stage(const float* acc, const float4* cs, float nm0, float nm1, uint32_t stg, int lane) {
#pragma unroll
    for (int tp = TP0; tp < TP1; tp++)
        stsm4(stg + (lane & 15) * 128 + (((2 * tp + (lane >> 4)) ^ (lane & 7)) << 4), hh_pair<32>(acc + 8 * tp, cs[2 * tp], nm0),
              hh_pair<32>(acc + 8 * tp + 2, cs[2 * tp], nm1), hh_pair<32>(acc + 8 * tp + 4, cs[2 * tp + 1], nm0),
              hh_pair<32>(acc + 8 * tp + 6, cs[2 * tp + 1], nm1));
}

struct Ring {
    int slot; uint32_t phase;
    __device__ __forceinline__ void adv() { if (++slot == NB) { slot = 0; phase ^= 1; } }
    __device__ __forceinline__ void adv5() { slot += slot == 3; adv(); }
};

__global__ void __cluster_dims__(2, 1, 1) __launch_bounds__(NTHREADS, 1) fused_kernel(const __grid_constant__ Params P) {
    extern __shared__ __align__(1024) uint8_t smem_raw[];
    const uint32_t sb = smem_u32(smem_raw);
    const int tid = threadIdx.x, lane = tid & 31;
    if (tid >= 256 && tid < 258) prefetch_tmap(&P.tx + (tid & 1));
    const int warp = __shfl_sync(0xffffffffu, tid >> 5, 0);
    const unsigned role = P.role[blockIdx.x], rank = blockIdx.x & 1;
    const int m = role >> 3, j = role & 7;
    const bool helper = role >= 128;

    TL(0, tid == 0); TLG(0, tid == 0);
    float* const acc_j = g_acc + j * ACC_SIZE;

    if (__builtin_expect(warp >= 8, 1)) {
        asm volatile("setmaxnreg.dec.sync.aligned.u32 72;");
        if (elect_one()) {
            if (warp == 8) {
                if (!helper) {
#pragma unroll
                    for (int i = 0; i < NB; i++) mbar_init(sb + BAR_FULLB + 8 * i, 1);
#pragma unroll
                    for (int i = 0; i < 2; i++) {
                        mbar_expect_tx(sb + BAR_FULLB + 8 * i, SLOT);
                        tma2d(sb + OFF_B + i * SLOT, &P.twq, sb + BAR_FULLB + 8 * i, DM + 64 * j, 64 * i);
                        tma2d(sb + OFF_B + i * SLOT + 8192, &P.twq, sb + BAR_FULLB + 8 * i, 2 * DM + 64 * j, 64 * i);
                    }
                }
            } else if (warp == 9) {
#pragma unroll
                for (int i = 0; i < 8; i++) mbar_init(sb + BAR_FULLA + 8 * i, 1);
                if (!helper) {
#pragma unroll
                    for (int i = 0; i < 2; i++) {
                        mbar_expect_tx(sb + BAR_FULLA + 8 * i, SLOT);
                        tma2d(sb + OFF_A + i * SLOT, &P.tx, sb + BAR_FULLA + 8 * i, 64 * i, 128 * m);
                    }
                }
            } else if (warp == 10) {
#pragma unroll
                for (int i = 0; i < 12; i++) mbar_init(sb + BAR_CS1 + 8 * i, i < 2 || i >= 8 ? 64 : (i < 4 ? 32 : 8));
                trap_if_gt(sb & 1023, 0);
            } else {
#pragma unroll
                for (int i = 0; i < 14; i++) mbar_init(sb + (i < 8 ? BAR_EMPTYA : BAR_EMPTYB - 64) + 8 * i, i < 8 ? 8 : 16);
            }
            asm volatile("fence.mbarrier_init.release.cluster;" ::: "memory");
        }
        __syncwarp();
        asm volatile("barrier.cluster.arrive.relaxed.aligned;" ::: "memory");
        const unsigned epoch = ld_relaxed(&g_epoch);
        bar_sync(0, NTHREADS);
        if (helper) {
            if (elect_one()) {
#pragma unroll 1
                for (int i = warp - 8; i < 72; i += 4) {
                    const uint32_t full = sb + BAR_FULLA + 8 * (i & 7), dst = sb + OFF_A + (i & 7) * SLOT;
                    const int n = i >> 1, jj = 2 * j + (i & 1);
                    const bool qkv = n < 12;
                    const int c0 = qkv ? (n < 8 ? DM + 128 * (n & 4) : 0) + 64 * jj : 176 * jj + 8 * ((n - 12) & ~7);
                    const int r0 = qkv ? 128 * (n & 3) : 64 * ((n - 12) & 7);
                    mbar_wait(sb + BAR_EMPTYA + 8 * (i & 7), ((i >> 3) & 1) ^ 1);
                    mbar_expect_tx(full, SLOT);
                    tma2d(dst, qkv ? &P.twq : &P.twg, full, c0, r0);
                    tma2d(dst + 8192, qkv ? &P.twq : &P.twu, full, c0, qkv ? r0 + 64 : r0);
                }
                prefetch_l2(P.wd + (size_t)(4 * j + warp - 8) * 44032, 88064);
            }
            return;
        }
        if (warp == 8) {
            asm volatile("barrier.cluster.wait.aligned;" ::: "memory");
            if (elect_one()) {
                if (m >= 6)
                    asm volatile("cp.async.bulk.prefetch.tensor.2d.L2.global [%0, {%1, %2}];" ::"l"(&P.twq), "r"(DM + DM * (m & 1) + 64 * j), "r"(64 * (m >> 1)) : "memory");
                if (j >= 3)
                    asm volatile("cp.async.bulk.prefetch.tensor.2d.L2.global [%0, {%1, %2}];" ::"l"(&P.tx), "r"(64 * j), "r"(128 * m) : "memory");
                Ring r{2, 0};
                const uint32_t dst = sb + OFF_B + rank * 8192;
#define B_LOAD(TM, C0, R0)                                                                                  \
        mbar_waitc(sb + BAR_EMPTYB + 8 * r.slot, r.phase ^ 1);                                              \
        mbar_expect_tx(sb + BAR_FULLB + 8 * r.slot, SLOT);                                                  \
        tma2d_mc(dst + r.slot * SLOT, TM, sb + BAR_FULLB + 8 * r.slot, C0, R0);
#pragma unroll 1
                for (int i = 2; i < 8; i++) {
                    if (i >= AHEAD && i < 6) mbar_waitc(sb + BAR_FULLB + 8 * (i - AHEAD), 0);
                    B_LOAD(&P.twq, DM + DM * rank + 64 * j, 64 * i)
                    r.adv();
                }
#pragma unroll 1
                for (int i = 8; i < 20; i++) {
                    if (i >= 10 && i < 14) {
                        mbar_waitc(sb + BAR_EMPTYB + 8 * r.slot, r.phase ^ 1);
                        mbar_arrive(sb + BAR_FULLB + 8 * r.slot);
                    } else {
                        const int e = 2 * (i & 3) + rank;
                        B_LOAD(i < 16 ? &P.twq : &P.two, 64 * j, 64 * (i < 16 ? e : KORD(e, j)))
                    }
                    r.adv();
                }
#pragma unroll 1
                for (int i = 0; i < 24; i++) {
                    B_LOAD(&P.twg + rank, 176 * j + 8 * (i & ~7), 64 * (i < 8 ? KORD(i, j) : i & 7))
                    r.adv5();
                }
#pragma unroll 1
                for (int i = 0; i < 12; i++) {
                    B_LOAD(&P.twd, 64 * j, 176 * (2 * (i & 3) + rank) + 64 * (i >> 2))
                    r.adv5();
                }
            }
            return;
        }
        if (warp == 9) {
            if (elect_one()) {
#pragma unroll 1
                for (int i = 2; i < 8; i++) {
                    if (i >= AHEAD + 1) mbar_wait(sb + BAR_FULLA + 8 * (i - AHEAD - 1), 0);
                    mbar_expect_tx(sb + BAR_FULLA + 8 * i, SLOT);
                    tma2d(sb + OFF_A + i * SLOT, &P.tx, sb + BAR_FULLA + 8 * i, 64 * i, 128 * m);
                }
#pragma unroll 1
                for (int i = 2; i < 7; i++) prefetch_tmap(&P.tx + i);
                unsigned nf = 0;
#pragma unroll 1
                for (int r = 1; r < 6; r++) {
                    const int skip = r < 3 ? j : 8;
                    const uint4* src = g_act + ((r - 1) * 128 + m * 8) * 1024;
                    const unsigned* fl = g_flag + (m * 5 + r - 1) * 32;
                    if (r < 4) mbar_wait(sb + BAR_EMPTYA + 8 * (r == 3 ? PF_DELAY : skip == 0), (r - 1) & 1);
                    const unsigned tgt = epoch * ((r == 3 || r == 4) ? 8 : 64);
                    if (r < 4 || nf != tgt) wait_count(fl, tgt);
                    TL(64 + r, true);
#pragma unroll 1
                    for (int t = 0; t < 8; t++) {
                        if (t == skip) continue;
                        if (t == 6) nf = readback(fl + 32);
                        mbar_wait(sb + BAR_EMPTYA + 8 * t, (r - 1) & 1);
                        mbar_expect_tx(sb + BAR_FULLA + 8 * t, SLOT);
                        asm volatile("cp.async.bulk.shared::cluster.global.mbarrier::complete_tx::bytes [%0], [%1], %2, [%3];"
                                     ::"r"(sb + OFF_A + t * SLOT), "l"(src + t * 1024), "r"(SLOT), "r"(sb + BAR_FULLA + 8 * t) : "memory");
                    }
                }
            }
            return;
        }
        const int a = warp - 10;
        {
            const int row = 16 * j + 8 * a + (lane >> 2);
            const uint32_t ra = sb + OFF_A + row * 128;
            float sh = 0.f, s0 = 0.f, s1 = 0.f, q0 = 0.f, q1 = 0.f;
#pragma unroll 1
            for (int kt = 0; kt < 8; kt++) {
                mbar_wait(sb + BAR_FULLA + 8 * kt, 0);
                if (kt == 0) sh = bf_lo(lds128(ra + ((row & 7) << 4)).x);
#pragma unroll
                for (int i = 0; i < 2; i++) {
                    const uint4 v = lds128(ra + kt * SLOT + (((2 * (lane & 3) + i) ^ (row & 7)) << 4));
                    const uint32_t ww[4] = {v.x, v.y, v.z, v.w};
#pragma unroll
                    for (int e = 0; e < 4; e++) {
                        const float d0 = bf_lo(ww[e]) - sh, d1 = bf_hi(ww[e]) - sh;
                        s0 += d0; q0 = fmaf(d0, d0, q0);
                        s1 += d1; q1 = fmaf(d1, d1, q1);
                    }
                }
            }
            s0 += s1; q0 += q1;
#pragma unroll
            for (int o = 1; o <= 2; o <<= 1) { s0 += __shfl_xor_sync(0xffffffffu, s0, o); q0 += __shfl_xor_sync(0xffffffffu, q0, o); }
            const float md = s0 * (1.f / DM);
            const float rs = rsqrtf(fmaxf(q0 * (1.f / DM) - md * md, 0.f) + 1e-5f);
            st_tagged_if(g_xstat + 2 * (128 * m + row), rs, -(sh + md), epoch, (lane & 3) == 0);
            TL(1, lane == 0 && a == 0);
        }
        const unsigned long long* cs = g_cs + j * 768 + 2 * lane;
        {
            const unsigned long long* xs = g_xstat + 2 * (128 * m + 64 * a + lane);
            uint4 v0, v1, v2;
            uint32_t it = 0;
            do {
                v0 = ld_tagged_rlx(xs); v1 = ld_tagged_rlx(xs + 64); v2 = ld_tagged_rlx(cs + 128 * a);
                trap_if_gt(++it, 1u << 22);
            } while (__any_sync(0xffffffffu, v0.y != epoch || v0.w != epoch || v1.y != epoch || v1.w != epoch || v2.y != epoch || v2.w != epoch));
            sts64(sb + OFF_XST + (64 * a + lane) * 8, v0.x, v0.z);
            sts64(sb + OFF_XST + (64 * a + 32 + lane) * 8, v1.x, v1.z);
            sts64(sb + OFF_CS1 + 256 * (a + 1) + 8 * lane, v2.x, v2.z);
            mbar_arrive(sb + BAR_CS1);
            TL(22 + a, lane == 0);
            if (a) {
                fetch_tagged(cs + 256, sb + OFF_CS1 + 8 * lane, epoch);
                mbar_arrive(sb + BAR_CSQ);
                TL(24, lane == 0);
            }
        }
        {
            mbar_wait(sb + BAR_KVW, 0);
            const float* src = acc_j + 4 * (128 * a + lane);
            float4 v[12];
            uint32_t it = 0;
            bool bad;
            while (__any_sync(0xffffffffu, readback(acc_j + 2048 + 128 * (lane & 7) + 127) != 0x41800000u)) trap_if_gt(++it, 1u << 22);
            TL(19, lane == 0 && a == 0);
            do {
                bad = false;
#pragma unroll
                for (int i = 0; i < 12; i++) v[i] = ld_l2_f4(src + 1024 * (i % 3) + 128 * (i / 3));
#pragma unroll
                for (int i = 0; i < 12; i++) bad |= v[i].w != 16.f;
                trap_if_gt(++it, 1u << 22);
            } while (__any_sync(0xffffffffu, bad));
            TL(14, lane == 0 && a == 0);
            const uint32_t d0 = sb + OFF_A + KVS(j) * SLOT + (64 * a + (lane >> 2)) * 48;
            const uint32_t d = d0 + (lane & 3) * 4, dz = d0 + (lane & 1) * 384 + 32 + (lane & 2) * 4;
#pragma unroll
            for (int u = 0; u < 4; u++) {
                sts32(d + 768 * u, pack_bf16(v[3 * u].x, v[3 * u].y));
                sts32(d + 768 * u + 384, pack_bf16(v[3 * u].z, v[3 * u + 1].z));
                sts32(d + 768 * u + 16, pack_bf16(v[3 * u + 1].x, v[3 * u + 1].y));
                sts32(d + 768 * u + 400, pack_bf16(v[3 * u + 2].x, v[3 * u + 2].y));
                const uint32_t z2 = pack_bf16(v[3 * u + 2].z, v[3 * u + 2].z);
                sts64(dz + 768 * u, z2, z2);
            }
            mbar_arrive(sb + BAR_KVR);
        }
#pragma unroll 1
        for (int c = 0; c < 3; c++) {
            fetch_tagged(cs + 384 + 128 * c + 64 * a, sb + OFF_CS3 + (32 * c + lane) * 16 + 8 * a, epoch);
            mbar_arrive(sb + BAR_CSG + 8 * c);
            TL(45 + c, lane == 0 && a == 0);
        }
        {
            uint32_t it = 0;
            while (__any_sync(0xffffffffu, (int)(readback(g_flag + (m * 5 + 1) * 32) - epoch * 64) < 0)) {
                __nanosleep(200);
                trap_if_gt(++it, 1u << 22);
            }
#pragma unroll 1
            for (int rr = 0; rr < 2; rr++) {
                const int row = 64 * rr + 32 * a + lane;
                const unsigned long long* hs = g_hstat + (1024 * m + row) * 2;
                uint4 v[8];
                bool bad;
                do {
                    bad = false;
#pragma unroll
                    for (int i = 0; i < 8; i++) v[i] = ld_tagged_rlx(hs + 256 * i);
#pragma unroll
                    for (int i = 0; i < 8; i++) bad |= v[i].y != epoch || v[i].w != epoch;
                    trap_if_gt(++it, 1u << 22);
                } while (__any_sync(0xffffffffu, bad));
                float mean = 0.f;
#pragma unroll
                for (int i = 0; i < 8; i++) mean += __uint_as_float(v[i].x);
                mean *= 0.125f;
                float m2 = 0.f, dv = 0.f;
#pragma unroll
                for (int i = 0; i < 8; i++) { const float d = __uint_as_float(v[i].x) - mean; m2 += __uint_as_float(v[i].z); dv = fmaf(d, d, dv); }
                sts_f2(sb + OFF_CS1 + row * 8, -mean, rcp(fmaf(dv, 64.f, m2) * (1.f / DM) + 1e-5f));
            }
        }
        mbar_arrive(sb + BAR_CS3);
        {
            const int c = a;
            mbar_wait(sb + BAR_STG + 8 * c, 0);
            if (elect_one()) {
                asm volatile("cp.async.bulk.global.shared::cta.bulk_group [%0], [%1], %2;" ::"l"(g_act + ((2 + c) * 128 + role) * 1024), "r"(sb + OFF_B + 4 * SLOT), "r"(SLOT) : "memory");
                asm volatile("cp.async.bulk.commit_group;" ::: "memory");
                asm volatile("cp.async.bulk.wait_group.read 0;" ::: "memory");
                mbar_arrive(sb + BAR_FULLB + 8 * 4);
                asm volatile("cp.async.bulk.wait_group 0;" ::: "memory");
            }
            __syncwarp();
            TL(60 + c, lane == 0);
            uint32_t ack = 0;
            const uint4* rb = g_act + ((2 + c) * 128 + role) * 1024 + lane * 8;
#pragma unroll
            for (int i = 0; i < 4; i++) ack |= readback(rb + 256 * i);
            signal_after(g_flag + (m * 5 + 2 + c) * 32, ack, P.zero, lane == 0);
            TL(54 + c, lane == 0);
        }
        return;
    }
    const unsigned epoch = ld_relaxed(&g_epoch);
    uint32_t wraw[16];
    if (!helper) {
        const uint32_t* wp = reinterpret_cast<const uint32_t*>(P.wphi) + (4 * j) * 128 + (lane & 3) * 16 + (lane >> 2);
#pragma unroll
        for (int i = 0; i < 16; i++)
            asm volatile("ld.global.nc.u32 %0, [%1];" : "=r"(wraw[i]) : "l"(wp + (i >> 2) * 128 + ((i >> 1) & 1) * 64 + (i & 1) * 8));
    }
    asm volatile("barrier.cluster.arrive.relaxed.aligned;" ::: "memory");
    asm volatile("setmaxnreg.inc.sync.aligned.u32 216;");
    bar_sync(0, NTHREADS);
    if (helper) {
        const int w = warp >> 2;
        sts64(sb + OFF_B + 8 * tid, 0x3f803f80u, 0x3f803f80u);
#pragma unroll 1
        for (int i = tid; i < 2 * ACC_SIZE / 4; i += 256) stg128(g_acc + 2 * j * ACC_SIZE + 4 * i, 0, 0, 0, 0);
        fence_async_smem();
        bar_sync(1, 256);
        TL(70, tid == 0);
        float acc[8];
        int i = w;
#pragma unroll 1
        for (int job = 0; job < 6; job++) {
            const int n = job < 3 ? 4 : 8;
#pragma unroll 1
            for (int t = 0; t < n; t++, i += 2) {
                mbar_waitc(sb + BAR_FULLA + 8 * (i & 7), (i >> 3) & 1);
                const desc_t da = desc_lo(sb + OFF_A) + (i & 7) * (SLOT >> 4);
                wg_fence();
#pragma unroll
                for (int k = 0; k < 8; k++) wgmma_n8_tt(acc + (k & 4), da + 128 * k, desc_lo(sb + OFF_B), (t | (k & 3)) != 0);
                wg_commit();
                wg_wait<0>();
                mbar_arrive_n_if(sb + BAR_EMPTYA + 8 * (i & 7), 2, lane == 0);
            }
            fence_acc<8>(acc);
            TL(71 + job, tid == 0);
            if (job == 2) { fence_gpu(); bar_sync(1, 256); }
            const int q = lane & 3;
            const float lo = (q & 1) ? acc[2] : acc[0], hi = (q & 1) ? acc[6] : acc[4];
            const float v = job < 3 ? lo + hi : ((q & 2) ? hi : lo);
            unsigned long long* dst = g_cs + ((2 * j + w) * 6 + job) * 128 + (q >> 1) * 64 + 16 * (warp & 3) + 8 * (q & 1) + (lane >> 2);
            asm volatile("st.relaxed.gpu.global.b64 [%0], %1;" ::"l"(dst), "l"(((unsigned long long)epoch << 32) | __float_as_uint(v)) : "memory");
        }
        return;
    }
    {
        const int w = warp >> 2, wv = warp & 3, g = lane >> 2, q = lane & 3;
        const uint32_t sa = sb + OFF_A + w * 8192;
        const desc_t dA = desc_lo(sa), dB = desc_lo(sb + OFF_B);
        unsigned* const flag_m = g_flag + m * 160;
        const bool l0 = lane == 0, l2 = lane < 2;
        const uint32_t eb = mapa(sb + BAR_EMPTYB, lane & 1);
        asm volatile("barrier.cluster.wait.aligned;" ::: "memory");
        Ring rg{0, 0};
        int prev = 0;

        uint32_t wb[16];
        constexpr float L2E = 1.4426950408889634f;
        const int ch = lane >> 4, sw = lane & 7;
        const uint32_t lrow = (lane & 15) * 128;
        uint32_t fp[16], fm[16];
        {
            float acc[64], accq[32];
#pragma unroll 1
            for (int kt = 0; kt < 8; kt++) {
                mbar_waitc(sb + BAR_FULLA + 8 * kt, 0);
                mbar_waitc(sb + BAR_FULLB + 8 * rg.slot, rg.phase);
                const desc_t da = dA + kt * (SLOT >> 4), db = dB + rg.slot * (SLOT >> 4);
                wg_fence();
#pragma unroll
                for (int k = 0; k < 4; k++) wgmma_n128(acc, da + 2 * k, db + 128 * k, (kt | k) != 0);
                wg_commit();
                wg_wait<1>();
                mbar_arrive_cl_if(eb + 8 * prev, l2 && kt > 0);
                prev = rg.slot; rg.adv();
            }
#pragma unroll
            for (int i = 0; i < 8; i++) {
                wb[(i >> 1) * 4 + (i & 1)] = __byte_perm(wraw[2 * i], wraw[2 * i + 1], 0x5410);
                wb[(i >> 1) * 4 + 2 + (i & 1)] = __byte_perm(wraw[2 * i], wraw[2 * i + 1], 0x7632);
            }
            float2 s0, s1;
            uint32_t a[16];
            wg_wait<0>();
            fence_acc<64>(acc);
            mbar_arrive_cl_if(eb + 8 * prev, l2);
#pragma unroll 1
            for (int it = 0; it < 2; it++) {
                mbar_waitc(sb + BAR_FULLB + 8 * 2, it ^ 1); mbar_waitc(sb + BAR_FULLB + 8 * 3, it ^ 1);
                const desc_t da = dA + it * (4 * SLOT >> 4);
                wg_fence();
#pragma unroll
                for (int k = 0; k < 16; k++) wgmma_n64(accq, da + (k >> 2) * (SLOT >> 4) + (k & 3) * 2, dB + 2 * (SLOT >> 4) + 128 * k, (it | k) != 0);
                wg_commit();
                TL(17 + it, tid == 0);
                mbar_waitc(sb + BAR_CS1 + 16 * it, 0);
                wg_wait<0>();
                fence_acc<32>(accq);
                mbar_arrive_cl_if(eb + 8 * (2 + (lane >> 1)), lane < 4);
                TL(2 + 2 * it, tid == 0);
                if (it == 0) {
                    s0 = lds_f2(sb + OFF_XST + (16 * warp + g) * 8); s1 = lds_f2(sb + OFF_XST + (16 * warp + g + 8) * 8);
#pragma unroll
                    for (int hh = 0; hh < 4; hh++)
                        ln_frag<false>(acc + 8 * hh, sb + OFF_CS1 + (64 + 16 * hh + 2 * q) * 4, 0.f, s0.y, 0.f, s1.y, a + 4 * hh);
                } else {
#pragma unroll
                    for (int hh = 0; hh < 4; hh++)
                        ln_frag<false>(accq + 8 * hh, sb + OFF_CS1 + (16 * hh + 2 * q) * 4, 0.f, s0.y, 0.f, s1.y, a + 4 * hh);
                }
                feature_maps(a, wb, s0.x * L2E, s1.x * L2E, fp, fm);
                if (it == 0) {
                    mbar_waitc(sb + BAR_FULLB + 8 * 4, 1); mbar_waitc(sb + BAR_FULLB + 8 * 5, 1);
                    mbar_waitc(sb + BAR_FULLB + 8 * 0, 0); mbar_waitc(sb + BAR_FULLB + 8 * 1, 0);
                    const uint32_t st = sb + OFF_B + warp * 2048 + lrow;
#pragma unroll
                    for (int hh = 0; hh < 4; hh++) {
                        stsm4(st + (4 + (hh >> 1)) * SLOT + (((4 * (hh & 1) + ch) ^ sw) << 4), fp[4 * hh], fp[4 * hh + 1], fp[4 * hh + 2], fp[4 * hh + 3]);
                        stsm4(st + (4 + (hh >> 1)) * SLOT + (((4 * (hh & 1) + 2 + ch) ^ sw) << 4), fm[4 * hh], fm[4 * hh + 1], fm[4 * hh + 2], fm[4 * hh + 3]);
                        ln_frag<true>(acc + 32 + 8 * hh, sb + OFF_CS1 + (128 + 16 * hh + 2 * q) * 4, s0.x, s0.y, s1.x, s1.y, a);
                        stsm4(st + (hh >> 1) * SLOT + (((2 * (hh & 1) + ch) ^ sw) << 4), a[0], a[1], a[2], a[3]);
                    }
                    stsm4(st + ch * SLOT + ((4 ^ sw) << 4), 0x3f803f80u, 0x3f803f80u, 0x3f803f80u, 0x3f803f80u);
                    fence_async_smem();
                    bar_sync(1, 256);
                    float kvd[20];
                    wg_fence();
#pragma unroll
                    for (int k = 0; k < 8; k++)
                        wgmma_n40_tt(kvd, dB + (4 + w) * (SLOT >> 4) + 128 * k, dB + w * (SLOT >> 4) + 128 * k, k != 0);
                    wg_commit();
                    wg_wait<0>();
                    fence_acc<20>(kvd);
                    const bool h1 = wv >= 2;
                    float* kvp = acc_j + 4 * tid;
                    mbar_waitc(sb + BAR_CSQ, 0);
                    red_f32x4(kvp, h1 ? kvd[8] : kvd[0], h1 ? kvd[9] : kvd[1], h1 ? kvd[10] : kvd[2], 1.f);
                    red_f32x4(kvp + 1024, h1 ? kvd[12] : kvd[4], h1 ? kvd[13] : kvd[5], h1 ? kvd[11] : kvd[3], 1.f);
                    red_f32x4(kvp + 2048, h1 ? kvd[14] : kvd[6], h1 ? kvd[15] : kvd[7], (q & 1) ? kvd[18] : kvd[16], 1.f);
                    __syncwarp();
                    mbar_arrive_if(sb + BAR_KVW, l0);
                    mbar_arrive_cl_if(eb + 8 * ((4 + (lane >> 1)) % 6), lane < 8);
                    TL(3, tid == 0);
                }
            }
        }
        uint32_t res_lo[8], res_hi[8], ack[4];
        const uint32_t own_rows = sb + OFF_A + j * SLOT + warp * 2048;
#pragma unroll
        for (int b = 0; b < 4; b++)
            ldsm4(own_rows + lrow + (((2 * b + ch) ^ sw) << 4), res_lo[2 * b], res_hi[2 * b], res_lo[2 * b + 1], res_hi[2 * b + 1]);
        mbar_arrive_if(sb + BAR_EMPTYA + 8 * lane, lane < 8 && lane != j && lane != KVS(j));
        TL(5, tid == 0);
        mbar_waitc(sb + BAR_KVR, 0);
        TL(6, tid == 0);
        {
            const uint32_t kvs = sb + OFF_A + KVS(j) * SLOT;
            uint32_t o_lo[8], o_hi[8];
#pragma unroll
            for (int hh = 0; hh < 4; hh++) {
                uint32_t b[8], zb[4];
                const uint32_t base = kvs + hh * 32 * 48;
                ldsm4t(base + (lane & 15) * 48 + (lane >> 4) * 16, b[0], b[1], b[2], b[3]);
                ldsm4t(base + (16 + (lane & 15)) * 48 + (lane >> 4) * 16, b[4], b[5], b[6], b[7]);
                ldsm4t(base + lane * 48 + 32, zb[0], zb[1], zb[2], zb[3]);
                float n0[4], n1[4], dn[4];
                mma16816_z(n0, fp + 4 * hh, b[0], b[1]); mma16816_z(n1, fp + 4 * hh, b[2], b[3]); mma16816_z(dn, fp + 4 * hh, zb[0], zb[1]);
                mma16816(n0, fm + 4 * hh, b[4], b[5]); mma16816(n1, fm + 4 * hh, b[6], b[7]); mma16816(dn, fm + 4 * hh, zb[2], zb[3]);
                const float i0 = rcp(dn[0] + 1e-6f), i1 = rcp(dn[2] + 1e-6f);
                o_lo[2 * hh] = pack_bf16(n0[0] * i0, n0[1] * i0); o_hi[2 * hh] = pack_bf16(n0[2] * i1, n0[3] * i1);
                o_lo[2 * hh + 1] = pack_bf16(n1[0] * i0, n1[1] * i0); o_hi[2 * hh + 1] = pack_bf16(n1[2] * i1, n1[3] * i1);
            }
            __syncwarp();
            mbar_arrive_if(sb + BAR_EMPTYA + 8 * KVS(j), l0);
            rg.slot = 4; rg.phase = 0;
            store_tile(own_rows, g_act + role * 1024 + warp * 128 + lane, o_lo, o_hi, lane, ack);
            TL(7, tid == 0);
        }
        float acch[32];
        {
            float* acc = acch;
#pragma unroll
            for (int t = 0; t < 8; t++) {
                acc[4 * t] = bf_lo(res_lo[t]); acc[4 * t + 1] = bf_hi(res_lo[t]);
                acc[4 * t + 2] = bf_lo(res_hi[t]); acc[4 * t + 3] = bf_hi(res_hi[t]);
            }
            fence_acc<32>(acc);
            int pa = 0;
#pragma unroll 1
            for (int kp = 0; kp < 4; kp++) {
                mbar_waitc(sb + BAR_FULLB + 8 * rg.slot, rg.phase);
#pragma unroll
                for (int hf = 0; hf < 2; hf++) {
                    const int i = 2 * kp + hf, kt = KORD(i, j);
                    mbar_waitc(sb + BAR_FULLA + 8 * kt, i != 0);
                    TL(8, i == 1 && tid == 0);
                    const desc_t da = dA + kt * (SLOT >> 4), db = dB + rg.slot * (SLOT >> 4);
                    wg_fence();
#pragma unroll
                    for (int k = 0; k < 4; k++) wgmma_n64(acc, da + 2 * k, db + (hf * 4 + k) * 128, 1);
                    wg_commit();
                    wg_wait<1>();
                    mbar_arrive_if(sb + BAR_EMPTYA + 8 * pa, l0 && i > 1);
                    if (hf == 0) {
                        mbar_arrive_cl_if(eb + 8 * prev, l2 && i > 0);
                        if (i == 0) { signal_late(flag_m, ack, P.zero, l0); TL(20, tid == 0); }
                    }
                    pa = kt;
                }
                prev = rg.slot; rg.adv();
            }
            wg_wait<0>();
            fence_acc<32>(acc);
            mbar_arrive_if(sb + BAR_EMPTYA + 8 * pa, l0);
            mbar_arrive_cl_if(eb + 8 * prev, l2);
            TL(9, tid == 0);
#pragma unroll
            for (int t = 0; t < 8; t++) {
                res_lo[t] = pack_bf16(acc[4 * t], acc[4 * t + 1]);
                res_hi[t] = pack_bf16(acc[4 * t + 2], acc[4 * t + 3]);
            }
            store_tile(own_rows, g_act + (128 + role) * 1024 + warp * 128 + lane, res_lo, res_hi, lane, ack);
            TL(10, tid == 0);
        }
        float acc0[64], acc1[64], acc2[56], nm0, nm1;
        float4 cs[8];
        uint32_t hr[16];
#define P3_GROUP(MMA, ACC, KT)                                                                              \
        mbar_waitc(sb + BAR_FULLB + 8 * rg.slot, rg.phase);                                                 \
        {                                                                                                   \
            const desc_t da = dA + (KT) * (SLOT >> 4), db = dB + rg.slot * (SLOT >> 4);                     \
            wg_fence();                                                                                     \
            _Pragma("unroll") for (int k = 0; k < 4; k++) MMA(ACC, da + 2 * k, db + 128 * k, (i | k) != 0); \
            wg_commit();                                                                                    \
        }
#define P3_CS(C, NT)    \
        _Pragma("unroll") for (int t = 0; t < (NT); t++) lds_f4_if(cs[t], sb + OFF_CS3 + q * 16 + 512 * (C) + 64 * t, i == t);
#define P3_EPI(C, ACC)                                                                                      \
        if (i == 0) {                                                                                       \
            fence_acc<64>(ACC);                                                                             \
            TL(11 + (C), tid == 0);                                                                         \
            if (C) mbar_waitc(sb + BAR_FULLB + 8 * 4, 1);                                                   \
            hh_stage<0, 2>(ACC, cs, nm0, nm1, stg, lane);                                                   \
            mbar_waitc(sb + BAR_CSG + 8 * (C) + 8, 0);                                                      \
        }                                                                                                   \
        if (i == 1) {                                                                                       \
            hh_stage<2, 4>(ACC, cs, nm0, nm1, stg, lane);                                                   \
            fence_async_smem();                                                                             \
            __syncwarp();                                                                                   \
            mbar_arrive_if(sb + BAR_STG + 8 * (C), l0);                                                     \
            TL(50 + (C), tid == 0);                                                                         \
        }
        const uint32_t stg = sb + OFF_B + 4 * SLOT + warp * 2048;
        const uint32_t blk = ((lane & 7) + (lane >> 4) * 8) * 128 + (((2 * wv + ((lane >> 3) & 1)) ^ (lane & 7)) << 4);
#pragma unroll 1
        for (int i = 0; i < 8; i++) {
            const int kt = KORD(i, j);
            mbar_waitc(sb + BAR_FULLA + 8 * kt, 0);
            TL(44, tid == 0 && i == 1);
            P3_GROUP(wgmma_n128, acc0, kt)
            if (i == 7) {
                mbar_waitc(sb + BAR_CS3, 0);
                nm0 = lds_f2(sb + OFF_CS1 + (16 * warp + g) * 8).x; nm1 = lds_f2(sb + OFF_CS1 + (16 * warp + g + 8) * 8).x;
            }
            wg_wait<1>();
            mbar_arrive_cl_if(eb + 8 * prev, l2 && i > 0);
            if (i == 0) {
                signal_late(flag_m + 32, ack, P.zero, l0);
                TL(21, tid == 0);
                {
                    fence_acc<32>(acch);
                    const float* acc = acch;
                    float s0 = 0.f, s1 = 0.f;
#pragma unroll
                    for (int t = 0; t < 8; t++) { s0 += acc[4 * t] + acc[4 * t + 1]; s1 += acc[4 * t + 2] + acc[4 * t + 3]; }
            s0 += __shfl_xor_sync(0xffffffffu, s0, 1); s1 += __shfl_xor_sync(0xffffffffu, s1, 1);
            s0 += __shfl_xor_sync(0xffffffffu, s0, 2); s1 += __shfl_xor_sync(0xffffffffu, s1, 2);
            const float mu0 = s0 * (1.f / 64), mu1 = s1 * (1.f / 64);
            float q0 = 0.f, q1 = 0.f;
#pragma unroll
            for (int t = 0; t < 8; t++) {
                float d;
                d = acc[4 * t] - mu0; q0 = fmaf(d, d, q0);
                d = acc[4 * t + 1] - mu0; q0 = fmaf(d, d, q0);
                d = acc[4 * t + 2] - mu1; q1 = fmaf(d, d, q1);
                d = acc[4 * t + 3] - mu1; q1 = fmaf(d, d, q1);
            }
            q0 += __shfl_xor_sync(0xffffffffu, q0, 1); q1 += __shfl_xor_sync(0xffffffffu, q1, 1);
            q0 += __shfl_xor_sync(0xffffffffu, q0, 2); q1 += __shfl_xor_sync(0xffffffffu, q1, 2);
            st_tagged_if(g_hstat + (role * 128 + 16 * warp + g + 8 * (q & 1)) * 2, q ? mu1 : mu0, q ? q1 : q0, epoch, q < 2);
                }
                bar_sync(2 + w, 128);
#pragma unroll
                for (int tp = 0; tp < 4; tp++) ldsm4t(sa + j * SLOT + blk + tp * 2048, hr[4 * tp], hr[4 * tp + 1], hr[4 * tp + 2], hr[4 * tp + 3]);
                mbar_waitc(sb + BAR_CSG, 0);
#pragma unroll
                for (int t = 0; t < 8; t++) cs[t] = lds_f4(sb + OFF_CS3 + q * 16 + 64 * t);
            }
            prev = rg.slot; rg.adv5();
        }
#pragma unroll 1
        for (int i = 0; i < 8; i++) {
            P3_GROUP(wgmma_n128, acc1, i)
            wg_wait<1>();
            mbar_arrive_cl_if(eb + 8 * prev, l2);
            P3_EPI(0, acc0)
            P3_CS(1, 8)
            prev = rg.slot; rg.adv5();
        }
#pragma unroll 1
        for (int i = 0; i < 8; i++) {
            P3_GROUP(wgmma_n112, acc2, i)
            wg_wait<1>();
            mbar_arrive_cl_if(eb + 8 * prev, l2);
            mbar_arrive_if(sb + BAR_EMPTYA + 8 * ((i + 7) & 7), l0 && i > 0);
            P3_EPI(1, acc1)
            P3_CS(2, 6)
            prev = rg.slot; rg.adv5();
        }
        mbar_waitc(sb + BAR_FULLB + 8 * 4, 0);
        wg_wait<0>();
        mbar_arrive_cl_if(eb + 8 * prev, l2);
        mbar_arrive_if(sb + BAR_EMPTYA + 8 * 7, l0);
        fence_acc<56>(acc2);
        TL(13, tid == 0);
        hh_stage<0, 3>(acc2, cs, nm0, nm1, stg, lane);
        __syncwarp();
        {
            uint4* gd = g_act + (4 * 128 + role) * 1024 + warp * 128 + lane;
#pragma unroll
            for (int i = 0; i < 4; i++) {
                const uint4 v = lds128(stg + i * 512 + lane * 16);
                stg128(gd + 32 * i, v.x, v.y, v.z, v.w);
            }
#pragma unroll
            for (int i = 0; i < 4; i++) ack[i] = readback(gd + 32 * i);
        }
        TL(52, tid == 0);
        {
            float acc[64];
            const desc_t dA0 = desc_lo(sb + OFF_A);
#define KT_P4(I, NK)                                                                                        \
        const int s_ = (2 * (I) + w) & 7;                                                                   \
        mbar_waitc(sb + BAR_FULLB + 8 * rg.slot, rg.phase);                                                 \
        mbar_waitc(sb + BAR_FULLA + 8 * s_, (((I) >> 2) + 1) & 1);                                          \
        const desc_t dh_ = dA0 + s_ * (SLOT >> 4), dw_ = dB + rg.slot * (SLOT >> 4) + w * 512;              \
        wg_fence();                                                                                         \
        _Pragma("unroll") for (int k = 0; k < (NK); k++) wgmma_n128_tn(acc, dw_ + 128 * k, dh_ + 2 * k, ((I) | k) != 0); \
        wg_commit();                                                                                        \
        wg_wait<1>();
#pragma unroll 1
            for (int i = 0; i < 8; i++) {
                KT_P4(i, 4)
                mbar_arrive_n_if(sb + BAR_EMPTYA + 8 * ((s_ + 6) & 7), 2, l0 && i > 0);
                mbar_arrive_cl_if(eb + 8 * prev, l2 && i > 0);
                if (i == 1) { signal_late(flag_m + 128, ack, P.zero, l0); TL(56, tid == 0); }
#pragma unroll
                for (int t = 0; t < 8; t++) lds_f4_if(cs[t], sb + OFF_CS1 + (64 * w + 8 * t + 2 * q) * 8, i == t);
                prev = rg.slot; rg.adv5();
            }
#pragma unroll 1
            for (int i = 8; i < 12; i++) {
                KT_P4(i, 3)
                mbar_arrive_n_if(sb + BAR_EMPTYA + 8 * ((s_ + 6) & 7), 2, l0);
                rg.adv5();
            }
            wg_wait<0>();
            fence_acc<64>(acc);
            TL(15, tid == 0);
            const uint32_t xch = sb + OFF_A + 2 * SLOT + (tid & 127) * 16;
            if (w) {
#pragma unroll
                for (int t = 0; t < 8; t++) {
                    sts128(xch + SLOT + t * 2048, __float_as_uint(acc[4 * t]), __float_as_uint(acc[4 * t + 1]),
                           __float_as_uint(acc[4 * t + 2]), __float_as_uint(acc[4 * t + 3]));
                }
#pragma unroll
                for (int t = 0; t < 32; t++) acc[t] = acc[32 + t];
            } else {
#pragma unroll
                for (int t = 0; t < 8; t++)
                    sts128(xch + t * 2048, __float_as_uint(acc[32 + 4 * t]), __float_as_uint(acc[33 + 4 * t]),
                           __float_as_uint(acc[34 + 4 * t]), __float_as_uint(acc[35 + 4 * t]));
            }
            bar_sync(1, 256);
            float4 o[8];
#pragma unroll
            for (int t = 0; t < 8; t++) o[t] = lds_f4(xch + (w ^ 1) * SLOT + t * 2048);
            const uint32_t tile = sb + OFF_A + w * SLOT;
#pragma unroll
            for (int t = 0; t < 8; t++) {
                hr[2 * t] = pack_bf16(fmaf(acc[4 * t] + o[t].x, cs[t].y, bf_lo(hr[2 * t])), fmaf(acc[4 * t + 1] + o[t].y, cs[t].w, bf_hi(hr[2 * t])));
                hr[2 * t + 1] = pack_bf16(fmaf(acc[4 * t + 2] + o[t].z, cs[t].y, bf_lo(hr[2 * t + 1])), fmaf(acc[4 * t + 3] + o[t].w, cs[t].w, bf_hi(hr[2 * t + 1])));
            }
#pragma unroll
            for (int tp = 0; tp < 4; tp++) stsm4t(tile + blk + tp * 2048, hr[4 * tp], hr[4 * tp + 1], hr[4 * tp + 2], hr[4 * tp + 3]);
            fence_async_smem();
            bar_sync(2 + w, 128);
            if ((tid & 127) == 0) {
                tma_store2d(&P.tout, tile, 64 * j, 128 * m + 64 * w);
                asm volatile("cp.async.bulk.wait_group.read 0;" ::: "memory");
            }
            if (tid == 0 && role == 0) g_epoch = epoch + 1;
            TL(16, tid == 0); TLG(1, tid == 0);
        }
    }
}

__global__ void probe_kernel() {}

typedef CUresult (*EncodeFn)(CUtensorMap*, CUtensorMapDataType, cuuint32_t, void*, const cuuint64_t*, const cuuint64_t*,
                             const cuuint32_t*, const cuuint32_t*, CUtensorMapInterleave, CUtensorMapSwizzle,
                             CUtensorMapL2promotion, CUtensorMapFloatOOBfill);

static void make_map2d(EncodeFn enc, CUtensorMap* tm, const void* base, uint64_t cols, uint64_t rows, uint64_t pitch_elems,
                       uint32_t box_rows) {
    cuuint64_t gd[2] = {cols, rows};
    cuuint64_t gs[1] = {pitch_elems * 2};
    cuuint32_t bd[2] = {64, box_rows};
    cuuint32_t es[2] = {1, 1};
    enc(tm, CU_TENSOR_MAP_DATA_TYPE_BFLOAT16, 2, const_cast<void*>(base), gd, gs, bd, es, CU_TENSOR_MAP_INTERLEAVE_NONE,
        CU_TENSOR_MAP_SWIZZLE_128B, CU_TENSOR_MAP_L2_PROMOTION_L2_256B, CU_TENSOR_MAP_FLOAT_OOB_FILL_NONE);
}

}

extern "C" void kernel_launch(void* const* d_in, const int* in_sizes, int n_in, void* d_out, int out_size) {
    using namespace hk;
    (void)in_sizes; (void)n_in; (void)out_size;
    static EncodeFn enc = nullptr;
    static int std_layout = 0;
    if (!enc) {
        void* fn = nullptr;
        cudaDriverEntryPointQueryResult qr;
        cudaGetDriverEntryPoint("cuTensorMapEncodeTiled", &fn, cudaEnableDefault, &qr);
        enc = (EncodeFn)fn;
        cudaFuncSetAttribute(fused_kernel, cudaFuncAttributeMaxDynamicSharedMemorySize, SMEM_BYTES);
        int dev = 0, sms = 0;
        cudaGetDevice(&dev);
        cudaDeviceGetAttribute(&sms, cudaDevAttrMultiProcessorCount, dev);
        cudaFuncSetAttribute(probe_kernel, cudaFuncAttributeNonPortableClusterSizeAllowed, 1);
        cudaFuncSetAttribute(probe_kernel, cudaFuncAttributeMaxDynamicSharedMemorySize, SMEM_BYTES);
        const int sizes[3] = {8, 9, 16}, want[3] = {15, 9, 7};
        bool ok = sms == NCTA;
        for (int i = 0; i < 3 && ok; i++) {
            cudaLaunchConfig_t cfg = {};
            cfg.gridDim = dim3(sizes[i] * 8); cfg.blockDim = dim3(NTHREADS); cfg.dynamicSmemBytes = SMEM_BYTES;
            cudaLaunchAttribute at;
            at.id = cudaLaunchAttributeClusterDimension;
            at.val.clusterDim.x = sizes[i]; at.val.clusterDim.y = 1; at.val.clusterDim.z = 1;
            cfg.attrs = &at; cfg.numAttrs = 1;
            int n = 0;
            ok = cudaOccupancyMaxActiveClusters(&n, probe_kernel, &cfg) == cudaSuccess && n == want[i];
        }
        (void)cudaGetLastError();
        std_layout = ok ? 1 : 0;
    }
    Params P;
    const __nv_bfloat16* x = (const __nv_bfloat16*)d_in[0];
    P.x = x;
    P.wqkv = (const __nv_bfloat16*)d_in[1];
    P.wphi = (const __nv_bfloat16*)d_in[2];
    P.wo = (const __nv_bfloat16*)d_in[3];
    P.wg = (const __nv_bfloat16*)d_in[5];
    P.wu = (const __nv_bfloat16*)d_in[6];
    P.wd = (const __nv_bfloat16*)d_in[7];
    P.out = (__nv_bfloat16*)d_out;
    P.zero = 0;
    for (int i = 0; i < NCTA; i++) {
        const int odd = i & 1;
        int role = i < 4 ? 128 + i : (((i - 4) >> 4) * 2 + odd) * 8 + (((i - 4) >> 1) & 7);
        if (std_layout) {
            const int tpc = i < 8 ? 62 + (i >> 1) : (i - 8) >> 1;
            if (tpc < 32) role = (tpc & 7) ? (2 * ((tpc & 7) - 1) + odd) * 8 + (tpc >> 3) : (14 + odd) * 8 + (tpc >> 3);
            else if (tpc < 60) role = (2 * ((tpc - 32) % 7) + odd) * 8 + 4 + (tpc - 32) / 7;
            else if (tpc < 62) role = 128 + (tpc - 60) * 2 + odd;
            else role = (14 + odd) * 8 + 4 + (tpc - 62);
        }
        P.role[i] = (unsigned char)role;
    }
    make_map2d(enc, &P.tx, x, DM, SEQ, DM, 128);
    make_map2d(enc, &P.twq, P.wqkv, 3 * DM, DM, 3 * DM, 64);
    make_map2d(enc, &P.two, P.wo, DM, DM, DM, 64);
    make_map2d(enc, &P.twg, P.wg, FF, DM, FF, 64);
    make_map2d(enc, &P.twu, P.wu, FF, DM, FF, 64);
    make_map2d(enc, &P.twd, P.wd, DM, FF, DM, 64);
    make_map2d(enc, &P.tout, d_out, DM, SEQ, DM, 64);
    fused_kernel<<<NCTA, NTHREADS, SMEM_BYTES>>>(P);
}
```

```cpp
#include <cuda_runtime.h>
#include <cuda_bf16.h>
#include <cuda.h>
#include <stdint.h>

namespace hk {

constexpr int SEQ = 2048, DM = 512, FF = 1376;
constexpr int NCTA = 132;
constexpr int NTHREADS = 384;
constexpr uint32_t SLOT = 16384;
constexpr uint32_t OFF_A = 0, OFF_B = 8 * SLOT, OFF_MISC = 14 * SLOT;
constexpr uint32_t BAR_FULLA = OFF_MISC + 0, BAR_EMPTYA = OFF_MISC + 64, BAR_FULLB = OFF_MISC + 128,
                   BAR_EMPTYB = OFF_MISC + 176, BAR_CS1 = OFF_MISC + 224, BAR_CS3 = OFF_MISC + 232,
                   BAR_CSQ = OFF_MISC + 240, BAR_CSV = OFF_MISC + 248,
                   BAR_STG = OFF_MISC + 256,
                   BAR_KVW = OFF_MISC + 280, BAR_KVR = OFF_MISC + 288, BAR_CSG = OFF_MISC + 296;
constexpr uint32_t OFF_CS1 = OFF_MISC + 384;
constexpr uint32_t OFF_CS3 = OFF_CS1 + 1024;
constexpr uint32_t OFF_XST = OFF_CS3;
constexpr uint32_t SMEM_BYTES = OFF_CS3 + 1536;
#define KORD(i, j) ((i) == 0 ? (j) : (i) - ((i) <= (j)))
constexpr int NB = 6;
#define PF_DELAY 2
#define KV_POLL 1
constexpr int AHEAD = 3;

constexpr int ACC_SIZE = 3 * 256 * 4;

__device__ __align__(1024) uint4 g_act[5 * 128 * 1024];
__device__ __align__(128) unsigned long long g_hstat[SEQ * 16];
__device__ __align__(128) unsigned long long g_xstat[SEQ * 2];
__device__ __align__(128) float g_acc[8 * ACC_SIZE];
__device__ __align__(128) unsigned long long g_cs[8 * 6 * 128];
__device__ __align__(128) unsigned g_flag[16 * 5 * 32 + 32];
__device__ unsigned g_epoch = 1;

#define TL(i, pred) do {} while (0)
#define TLG(i, pred) do {} while (0)

struct Params {
    CUtensorMap tx, twq, two, twg, twu, twd, tout;
    const __nv_bfloat16 *x, *wqkv, *wphi, *wo, *wg, *wu, *wd;
    __nv_bfloat16* out;
    unsigned zero;
    unsigned char role[NCTA];
};

__device__ __forceinline__ uint32_t smem_u32(const void* p) { return (uint32_t)__cvta_generic_to_shared(p); }
__device__ __forceinline__ void mbar_init(uint32_t bar, uint32_t cnt) {
    asm volatile("mbarrier.init.shared::cta.b64 [%0], %1;" ::"r"(bar), "r"(cnt) : "memory");
}
__device__ __forceinline__ void mbar_expect_tx(uint32_t bar, uint32_t bytes) {
    asm volatile("mbarrier.arrive.expect_tx.shared::cta.b64 _, [%0], %1;" ::"r"(bar), "r"(bytes) : "memory");
}
__device__ __forceinline__ void mbar_arrive(uint32_t bar) {
    asm volatile("mbarrier.arrive.shared::cta.b64 _, [%0];" ::"r"(bar) : "memory");
}
__device__ __forceinline__ void mbar_arrive_if(uint32_t bar, bool pred) {
    asm volatile("{.reg .pred p; setp.ne.u32 p, %1, 0; @p mbarrier.arrive.shared::cta.b64 _, [%0];}" ::"r"(bar), "r"((uint32_t)pred) : "memory");
}
__device__ __forceinline__ bool mbar_try(uint32_t bar, uint32_t parity) {
    uint32_t ok;
    asm volatile("{.reg .pred p; mbarrier.try_wait.parity.shared::cta.b64 p, [%1], %2; selp.u32 %0,1,0,p;}"
                 : "=r"(ok) : "r"(bar), "r"(parity) : "memory");
    return ok;
}
__device__ __forceinline__ bool mbar_test(uint32_t bar, uint32_t parity) {
    uint32_t ok;
    asm volatile("{.reg .pred p; mbarrier.test_wait.parity.shared::cta.b64 p, [%1], %2; selp.u32 %0,1,0,p;}"
                 : "=r"(ok) : "r"(bar), "r"(parity) : "memory");
    return ok;
}
__device__ __forceinline__ void trap_if_gt(uint32_t v, uint32_t lim) {
    asm volatile("{.reg .pred p; setp.gt.u32 p, %0, %1; @p trap;}" ::"r"(v), "r"(lim));
}
__device__ __forceinline__ void mbar_wait(uint32_t bar, uint32_t parity) {
    asm volatile("{\n"
                 ".reg .pred P1, P2;\n"
                 ".reg .u32 c;\n"
                 "mov.u32 c, 0;\n"
                 "LAB_WAIT:\n"
                 "mbarrier.try_wait.parity.shared::cta.b64 P1, [%0], %1;\n"
                 "@P1 bra LAB_DONE;\n"
                 "add.u32 c, c, 1;\n"
                 "setp.gt.u32 P2, c, 4194304;\n"
                 "@P2 trap;\n"
                 "bra LAB_WAIT;\n"
                 "LAB_DONE:\n"
                 "}" ::"r"(bar), "r"(parity) : "memory");
}
__device__ __forceinline__ void mbar_waitc(uint32_t bar, uint32_t parity) {
    asm volatile("{\n"
                 ".reg .pred P1;\n"
                 "LAB_WAIT:\n"
                 "mbarrier.try_wait.parity.shared::cta.b64 P1, [%0], %1;\n"
                 "@!P1 bra LAB_WAIT;\n"
                 "}" ::"r"(bar), "r"(parity) : "memory");
}
__device__ __forceinline__ void tma2d(uint32_t dst, const CUtensorMap* tm, uint32_t bar, int c0, int c1) {
    asm volatile("cp.async.bulk.tensor.2d.shared::cluster.global.mbarrier::complete_tx::bytes [%0], [%1, {%3, %4}], [%2];"
                 ::"r"(dst), "l"(tm), "r"(bar), "r"(c0), "r"(c1) : "memory");
}
__device__ __forceinline__ void tma2d_mc(uint32_t dst, const CUtensorMap* tm, uint32_t bar, int c0, int c1) {
    asm volatile("cp.async.bulk.tensor.2d.shared::cluster.global.mbarrier::complete_tx::bytes.multicast::cluster [%0], [%1, {%3, %4}], [%2], %5;"
                 ::"r"(dst), "l"(tm), "r"(bar), "r"(c0), "r"(c1), "h"((uint16_t)3) : "memory");
}
__device__ __forceinline__ uint32_t mapa(uint32_t addr, uint32_t rank) {
    uint32_t r; asm("mapa.shared::cluster.u32 %0, %1, %2;" : "=r"(r) : "r"(addr), "r"(rank)); return r;
}
__device__ __forceinline__ void mbar_arrive_cl_if(uint32_t cbar, bool pred) {
    asm volatile("{.reg .pred p; setp.ne.u32 p, %1, 0; @p mbarrier.arrive.shared::cluster.b64 _, [%0];}" ::"r"(cbar), "r"((uint32_t)pred) : "memory");
}
__device__ __forceinline__ bool elect_one() {
    uint32_t ok;
    asm volatile("{.reg .pred p; elect.sync _|p, 0xffffffff; selp.u32 %0, 1, 0, p;}" : "=r"(ok));
    return ok;
}
__device__ __forceinline__ void prefetch_tmap(const CUtensorMap* tm) {
    asm volatile("prefetch.tensormap [%0];" ::"l"(tm) : "memory");
}
__device__ __forceinline__ void prefetch_l2(const void* p, uint32_t bytes) {
    asm volatile("cp.async.bulk.prefetch.L2.global [%0], %1;" ::"l"(p), "r"(bytes) : "memory");
}
__device__ __forceinline__ unsigned ld_acquire(const unsigned* p) {
    unsigned v; asm volatile("ld.acquire.gpu.global.u32 %0, [%1];" : "=r"(v) : "l"(p) : "memory"); return v;
}
__device__ __forceinline__ uint4 ld_acquire4(const unsigned* p) {
    uint4 v;
    asm volatile("ld.acquire.gpu.global.v4.u32 {%0,%1,%2,%3}, [%4];" : "=r"(v.x), "=r"(v.y), "=r"(v.z), "=r"(v.w) : "l"(p) : "memory");
    return v;
}
__device__ __forceinline__ unsigned ld_relaxed(const unsigned* p) {
    unsigned v; asm volatile("ld.relaxed.gpu.global.u32 %0, [%1];" : "=r"(v) : "l"(p)); return v;
}
__device__ __forceinline__ void st_relaxed(unsigned* p, unsigned v) {
    asm volatile("st.relaxed.gpu.global.u32 [%0], %1;" ::"l"(p), "r"(v) : "memory");
}
__device__ __forceinline__ void red_relaxed(unsigned* p, unsigned v) {
    asm volatile("red.relaxed.gpu.global.add.u32 [%0], %1;" ::"l"(p), "r"(v) : "memory");
}
__device__ __forceinline__ void fence_gpu() { asm volatile("fence.acq_rel.gpu;" ::: "memory"); }
__device__ __forceinline__ void fence_async_smem() { asm volatile("fence.proxy.async.shared::cta;" ::: "memory"); }
__device__ __forceinline__ void fence_async_global() { asm volatile("fence.proxy.async.global;" ::: "memory"); }
__device__ __forceinline__ uint32_t readback(const void* p) {
    uint32_t v; asm volatile("ld.relaxed.gpu.global.u32 %0, [%1];" : "=r"(v) : "l"(p) : "memory"); return v;
}
__device__ __forceinline__ void wait_count(const unsigned* p, unsigned target) {
    uint32_t it = 0;
    while ((int)(readback(p) - target) < 0) trap_if_gt(++it, 1u << 22);
}
__device__ __forceinline__ void wait_count_warp(const unsigned* p, unsigned target) {
    uint32_t it = 0;
    while (__any_sync(0xffffffffu, (int)(readback(p) - target) < 0)) trap_if_gt(++it, 1u << 22);
}
__device__ __forceinline__ void red_f32(float* p, float a) {
    asm volatile("red.relaxed.gpu.global.add.f32 [%0], %1;" ::"l"(p), "f"(a) : "memory");
}
__device__ __forceinline__ void red_f32x2(float* p, float a, float b) {
    asm volatile("red.relaxed.gpu.global.add.v2.f32 [%0], {%1, %2};" ::"l"(p), "f"(a), "f"(b) : "memory");
}
__device__ __forceinline__ void red_f32x4(float* p, float a, float b, float c, float d) {
    asm volatile("red.relaxed.gpu.global.add.v4.f32 [%0], {%1, %2, %3, %4};" ::"l"(p), "f"(a), "f"(b), "f"(c), "f"(d) : "memory");
}
__device__ __forceinline__ float4 ld_l2_f4(const float* p) {
    float4 v;
    asm volatile("ld.relaxed.gpu.global.v4.f32 {%0,%1,%2,%3}, [%4];" : "=f"(v.x), "=f"(v.y), "=f"(v.z), "=f"(v.w) : "l"(p) : "memory");
    return v;
}
__device__ __forceinline__ float2 ld_l2_f2(const float* p) {
    float2 v;
    asm volatile("ld.relaxed.gpu.global.v2.f32 {%0,%1}, [%2];" : "=f"(v.x), "=f"(v.y) : "l"(p) : "memory");
    return v;
}
__device__ __forceinline__ float ld_l2_f(const float* p) {
    float v;
    asm volatile("ld.relaxed.gpu.global.f32 %0, [%1];" : "=f"(v) : "l"(p) : "memory");
    return v;
}
__device__ __forceinline__ uint4 ldg_nc(const void* p) {
    uint4 v;
    asm volatile("ld.global.nc.L1::no_allocate.v4.u32 {%0,%1,%2,%3}, [%4];" : "=r"(v.x), "=r"(v.y), "=r"(v.z), "=r"(v.w) : "l"(p));
    return v;
}
__device__ __forceinline__ void stg128(void* p, uint32_t a, uint32_t b, uint32_t c, uint32_t d) {
    asm volatile("st.global.v4.u32 [%0], {%1,%2,%3,%4};" ::"l"(p), "r"(a), "r"(b), "r"(c), "r"(d) : "memory");
}
__device__ __forceinline__ uint4 lds128(uint32_t a) {
    uint4 v;
    asm volatile("ld.shared.v4.u32 {%0,%1,%2,%3}, [%4];" : "=r"(v.x), "=r"(v.y), "=r"(v.z), "=r"(v.w) : "r"(a) : "memory");
    return v;
}
__device__ __forceinline__ float2 lds_f2(uint32_t a) {
    float2 v;
    asm volatile("ld.shared.v2.f32 {%0,%1}, [%2];" : "=f"(v.x), "=f"(v.y) : "r"(a) : "memory");
    return v;
}
__device__ __forceinline__ void sts_f2(uint32_t a, float x, float y) {
    asm volatile("st.shared.v2.f32 [%0], {%1,%2};" ::"r"(a), "f"(x), "f"(y) : "memory");
}
__device__ __forceinline__ void sts64(uint32_t a, uint32_t x, uint32_t y) {
    asm volatile("st.shared.v2.u32 [%0], {%1,%2};" ::"r"(a), "r"(x), "r"(y) : "memory");
}
__device__ __forceinline__ void sts128(uint32_t a, uint32_t x, uint32_t y, uint32_t z, uint32_t w) {
    asm volatile("st.shared.v4.u32 [%0], {%1,%2,%3,%4};" ::"r"(a), "r"(x), "r"(y), "r"(z), "r"(w) : "memory");
}
__device__ __forceinline__ void stsm4(uint32_t a, uint32_t r0, uint32_t r1, uint32_t r2, uint32_t r3) {
    asm volatile("stmatrix.sync.aligned.m8n8.x4.shared.b16 [%0], {%1,%2,%3,%4};" ::"r"(a), "r"(r0), "r"(r1), "r"(r2), "r"(r3) : "memory");
}
__device__ __forceinline__ void stsm4t(uint32_t a, uint32_t r0, uint32_t r1, uint32_t r2, uint32_t r3) {
    asm volatile("stmatrix.sync.aligned.m8n8.x4.trans.shared.b16 [%0], {%1,%2,%3,%4};" ::"r"(a), "r"(r0), "r"(r1), "r"(r2), "r"(r3) : "memory");
}
__device__ __forceinline__ void tma_store2d(const CUtensorMap* tm, uint32_t src, int c0, int c1) {
    asm volatile("cp.async.bulk.tensor.2d.global.shared::cta.bulk_group [%0, {%2, %3}], [%1];" ::"l"(tm), "r"(src), "r"(c0), "r"(c1) : "memory");
    asm volatile("cp.async.bulk.commit_group;" ::: "memory");
}
__device__ __forceinline__ void ldsm4(uint32_t a, uint32_t& r0, uint32_t& r1, uint32_t& r2, uint32_t& r3) {
    asm volatile("ldmatrix.sync.aligned.m8n8.x4.shared.b16 {%0,%1,%2,%3}, [%4];" : "=r"(r0), "=r"(r1), "=r"(r2), "=r"(r3) : "r"(a) : "memory");
}
__device__ __forceinline__ void ldsm4t(uint32_t a, uint32_t& r0, uint32_t& r1, uint32_t& r2, uint32_t& r3) {
    asm volatile("ldmatrix.sync.aligned.m8n8.x4.trans.shared.b16 {%0,%1,%2,%3}, [%4];" : "=r"(r0), "=r"(r1), "=r"(r2), "=r"(r3) : "r"(a) : "memory");
}
__device__ __forceinline__ void mma16816(float* c, const uint32_t* a, uint32_t b0, uint32_t b1) {
    asm("mma.sync.aligned.m16n8k16.row.col.f32.bf16.bf16.f32 {%0,%1,%2,%3}, {%4,%5,%6,%7}, {%8,%9}, {%0,%1,%2,%3};"
                 : "+f"(c[0]), "+f"(c[1]), "+f"(c[2]), "+f"(c[3])
                 : "r"(a[0]), "r"(a[1]), "r"(a[2]), "r"(a[3]), "r"(b0), "r"(b1));
}
__device__ __forceinline__ uint32_t pack_bf16(float lo, float hi) {
    uint32_t r; asm("cvt.rn.bf16x2.f32 %0, %1, %2;" : "=r"(r) : "f"(hi), "f"(lo)); return r;
}
__device__ __forceinline__ float bf_lo(uint32_t w) { return __uint_as_float(w << 16); }
__device__ __forceinline__ float bf_hi(uint32_t w) { return __uint_as_float(w & 0xffff0000u); }
__device__ __forceinline__ float ex2(float x) { float r; asm("ex2.approx.ftz.f32 %0, %1;" : "=f"(r) : "f"(x)); return r; }
__device__ __forceinline__ float rcp(float x) { float r; asm("rcp.approx.ftz.f32 %0, %1;" : "=f"(r) : "f"(x)); return r; }
__device__ __forceinline__ void bar_sync(int id, int n) { asm volatile("bar.sync %0, %1;" ::"r"(id), "r"(n) : "memory"); }

typedef unsigned long long desc_t;
__device__ __forceinline__ desc_t desc_lo(uint32_t addr) { return (desc_t)(((addr & 0x3FFFF) >> 4) | (512u << 16)) | (0x40000040ull << 32); }
__device__ __forceinline__ void wg_fence() { asm volatile("wgmma.fence.sync.aligned;" ::: "memory"); }
__device__ __forceinline__ void wg_commit() { asm volatile("wgmma.commit_group.sync.aligned;" ::: "memory"); }
template <int N> __device__ __forceinline__ void wg_wait() { asm volatile("wgmma.wait_group.sync.aligned %0;" ::"n"(N) : "memory"); }
template <int N> __device__ __forceinline__ void fence_acc(float* d) {
#pragma unroll
    for (int i = 0; i < N; i++) asm volatile("" : "+f"(d[i])::"memory");
}
#define R4(o) "+f"(d[o + 0]), "+f"(d[o + 1]), "+f"(d[o + 2]), "+f"(d[o + 3])
#define R8(o) R4(o), R4(o + 4)
__device__ __forceinline__ void wgmma_n128(float* d, desc_t da, desc_t db, int sc) {
    asm volatile("{.reg .pred p; setp.ne.b32 p, %66, 0;\n"
                 "wgmma.mma_async.sync.aligned.m64n128k16.f32.bf16.bf16 {%0,%1,%2,%3,%4,%5,%6,%7,%8,%9,%10,%11,%12,%13,%14,%15,%16,%17,%18,%19,%20,%21,%22,%23,%24,%25,%26,%27,%28,%29,%30,%31,"
                 "%32,%33,%34,%35,%36,%37,%38,%39,%40,%41,%42,%43,%44,%45,%46,%47,%48,%49,%50,%51,%52,%53,%54,%55,%56,%57,%58,%59,%60,%61,%62,%63}, %64, %65, p, 1, 1, 0, 1;}"
                 : R8(0), R8(8), R8(16), R8(24), R8(32), R8(40), R8(48), R8(56)
                 : "l"(da), "l"(db), "r"(sc));
}
__device__ __forceinline__ void wgmma_n112(float* d, desc_t da, desc_t db, int sc) {
    asm volatile("{.reg .pred p; setp.ne.b32 p, %58, 0;\n"
                 "wgmma.mma_async.sync.aligned.m64n112k16.f32.bf16.bf16 {%0,%1,%2,%3,%4,%5,%6,%7,%8,%9,%10,%11,%12,%13,%14,%15,%16,%17,%18,%19,%20,%21,%22,%23,%24,%25,%26,%27,%28,%29,%30,%31,%32,%33,%34,%35,%36,%37,%38,%39,%40,%41,%42,%43,%44,%45,%46,%47,%48,%49,%50,%51,%52,%53,%54,%55}, %56, %57, p, 1, 1, 0, 1;}"
                 : R8(0), R8(8), R8(16), R8(24), R8(32), R8(40), R8(48)
                 : "l"(da), "l"(db), "r"(sc));
}
__device__ __forceinline__ void wgmma_n128_tn(float* d, desc_t da, desc_t db, int sc) {
    asm volatile("{.reg .pred p; setp.ne.b32 p, %66, 0;\n"
                 "wgmma.mma_async.sync.aligned.m64n128k16.f32.bf16.bf16 {%0,%1,%2,%3,%4,%5,%6,%7,%8,%9,%10,%11,%12,%13,%14,%15,%16,%17,%18,%19,%20,%21,%22,%23,%24,%25,%26,%27,%28,%29,%30,%31,%32,%33,%34,%35,%36,%37,%38,%39,%40,%41,%42,%43,%44,%45,%46,%47,%48,%49,%50,%51,%52,%53,%54,%55,%56,%57,%58,%59,%60,%61,%62,%63}, %64, %65, p, 1, 1, 1, 0;}"
                 : R8(0), R8(8), R8(16), R8(24), R8(32), R8(40), R8(48), R8(56)
                 : "l"(da), "l"(db), "r"(sc));
}
__device__ __forceinline__ void wgmma_n64(float* d, desc_t da, desc_t db, int sc) {
    asm volatile("{.reg .pred p; setp.ne.b32 p, %34, 0;\n"
                 "wgmma.mma_async.sync.aligned.m64n64k16.f32.bf16.bf16 {%0,%1,%2,%3,%4,%5,%6,%7,%8,%9,%10,%11,%12,%13,%14,%15,%16,%17,%18,%19,%20,%21,%22,%23,%24,%25,%26,%27,%28,%29,%30,%31}, %32, %33, p, 1, 1, 0, 1;}"
                 : R8(0), R8(8), R8(16), R8(24)
                 : "l"(da), "l"(db), "r"(sc));
}
__device__ __forceinline__ void wgmma_n40_tt(float* d, desc_t da, desc_t db, int sc) {
    asm volatile("{.reg .pred p; setp.ne.b32 p, %22, 0;\n"
                 "wgmma.mma_async.sync.aligned.m64n40k16.f32.bf16.bf16 {%0,%1,%2,%3,%4,%5,%6,%7,%8,%9,%10,%11,%12,%13,%14,%15,%16,%17,%18,%19}, %20, %21, p, 1, 1, 1, 1;}"
                 : R8(0), R8(8), R4(16)
                 : "l"(da), "l"(db), "r"(sc));
}

__device__ __forceinline__ void wgmma_n8_tt(float* d, desc_t da, desc_t db, int sc) {
    asm volatile("{.reg .pred p; setp.ne.b32 p, %6, 0;\n"
                 "wgmma.mma_async.sync.aligned.m64n8k16.f32.bf16.bf16 {%0,%1,%2,%3}, %4, %5, p, 1, 1, 1, 1;}"
                 : R4(0)
                 : "l"(da), "l"(db), "r"(sc));
}

__device__ __forceinline__ void signal_after(unsigned* cnt, uint32_t ack, uint32_t zero, bool pred) {
    asm volatile("{.reg .pred p; setp.ne.u32 p, %2, 0; @p red.relaxed.gpu.global.add.u32 [%0], %1;}"
                 ::"l"(cnt), "r"((ack & zero) + 1), "r"((uint32_t)pred) : "memory");
}
__device__ __forceinline__ void signal_late(unsigned* cnt, const uint32_t* a, uint32_t zero, bool pred) {
    uint32_t v;
    asm volatile("{.reg .b32 t; lop3.b32 t, %1, %2, %3, 0xfe; or.b32 %0, t, %4;}"
                 : "=r"(v) : "r"(a[0]), "r"(a[1]), "r"(a[2]), "r"(a[3]));
    signal_after(cnt, v, zero, pred);
}
__device__ __forceinline__ void red_f32_if(float* p, float a, bool pred) {
    asm volatile("{.reg .pred p; setp.ne.u32 p, %2, 0; @p red.relaxed.gpu.global.add.f32 [%0], %1;}" ::"l"(p), "f"(a), "r"((uint32_t)pred) : "memory");
}
__device__ __forceinline__ void stg_f2_if(float* p, float a, float b, bool pred) {
    asm volatile("{.reg .pred p; setp.ne.u32 p, %3, 0; @p st.global.v2.f32 [%0], {%1,%2};}" ::"l"(p), "f"(a), "f"(b), "r"((uint32_t)pred) : "memory");
}
__device__ __forceinline__ void stg64(void* p, uint32_t a, uint32_t b) {
    asm volatile("st.global.v2.u32 [%0], {%1,%2};" ::"l"(p), "r"(a), "r"(b) : "memory");
}
__device__ __forceinline__ void mma16816_z(float* c, const uint32_t* a, uint32_t b0, uint32_t b1) {
    asm("mma.sync.aligned.m16n8k16.row.col.f32.bf16.bf16.f32 {%0,%1,%2,%3}, {%4,%5,%6,%7}, {%8,%9}, {%10,%10,%10,%10};"
                 : "=f"(c[0]), "=f"(c[1]), "=f"(c[2]), "=f"(c[3])
                 : "r"(a[0]), "r"(a[1]), "r"(a[2]), "r"(a[3]), "r"(b0), "r"(b1), "f"(0.f));
}
__device__ __forceinline__ uint32_t max2(uint32_t a, uint32_t b) { uint32_t r; asm("max.bf16x2 %0, %1, %2;" : "=r"(r) : "r"(a), "r"(b)); return r; }
__device__ __forceinline__ uint32_t min2(uint32_t a, uint32_t b) { uint32_t r; asm("min.bf16x2 %0, %1, %2;" : "=r"(r) : "r"(a), "r"(b)); return r; }
__device__ __forceinline__ void bar_arrive(int id, int n) { asm volatile("bar.arrive %0, %1;" ::"r"(id), "r"(n) : "memory"); }
__device__ __forceinline__ void mbar_arrive_n_if(uint32_t bar, uint32_t n, bool pred) {
    asm volatile("{.reg .pred p; setp.ne.u32 p, %1, 0; @p mbarrier.arrive.shared::cta.b64 _, [%0], %2;}" ::"r"(bar), "r"((uint32_t)pred), "r"(n) : "memory");
}
__device__ __forceinline__ float4 lds_f4(uint32_t a) {
    float4 v;
    asm volatile("ld.shared.v4.f32 {%0,%1,%2,%3}, [%4];" : "=f"(v.x), "=f"(v.y), "=f"(v.z), "=f"(v.w) : "r"(a) : "memory");
    return v;
}
__device__ __forceinline__ void lds_f4_if(float4& v, uint32_t a, bool pred) {
    asm volatile("{.reg .pred p; setp.ne.u32 p, %5, 0; @p ld.shared.v4.f32 {%0,%1,%2,%3}, [%4];}"
                 : "+f"(v.x), "+f"(v.y), "+f"(v.z), "+f"(v.w) : "r"(a), "r"((uint32_t)pred) : "memory");
}
__device__ __forceinline__ uint4 ld_tagged(const unsigned long long* p) {
    unsigned long long a, b;
    asm volatile("ld.acquire.gpu.global.v2.b64 {%0,%1}, [%2];" : "=l"(a), "=l"(b) : "l"(p) : "memory");
    return make_uint4((unsigned)a, (unsigned)(a >> 32), (unsigned)b, (unsigned)(b >> 32));
}
__device__ __forceinline__ uint4 ld_tagged_rlx(const unsigned long long* p) {
    unsigned long long a, b;
    asm volatile("ld.relaxed.gpu.global.v2.b64 {%0,%1}, [%2];" : "=l"(a), "=l"(b) : "l"(p) : "memory");
    return make_uint4((unsigned)a, (unsigned)(a >> 32), (unsigned)b, (unsigned)(b >> 32));
}
__device__ __forceinline__ void sts32(uint32_t a, uint32_t x) { asm volatile("st.shared.u32 [%0], %1;" ::"r"(a), "r"(x) : "memory"); }
__device__ __forceinline__ void fetch_tagged(const unsigned long long* src, uint32_t dst, unsigned epoch) {
    uint4 v;
    uint32_t it = 0;
    while (true) {
        v = ld_tagged_rlx(src);
        if (!__any_sync(0xffffffffu, v.y != epoch || v.w != epoch)) break;
        __nanosleep(60);
        trap_if_gt(++it, 1u << 22);
    }
    sts64(dst, v.x, v.z);
}
__device__ __forceinline__ void st_tagged_if(unsigned long long* p, float a, float b, unsigned tag, bool pred) {
    const unsigned long long t = (unsigned long long)tag << 32;
    asm volatile("{.reg .pred p; setp.ne.u32 p, %3, 0; @p st.relaxed.gpu.global.v2.b64 [%0], {%1,%2};}"
                 ::"l"(p), "l"(t | __float_as_uint(a)), "l"(t | __float_as_uint(b)), "r"((uint32_t)pred) : "memory");
}

__device__ __forceinline__ void store_tile(uint32_t tile_rows, uint4* gdst, const uint32_t* lo, const uint32_t* hi, int lane, uint32_t* ack) {
    const int r = lane & 15;
#pragma unroll
    for (int b = 0; b < 4; b++)
        stsm4(tile_rows + r * 128 + (((2 * b + (lane >> 4)) ^ (r & 7)) << 4), lo[2 * b], hi[2 * b], lo[2 * b + 1], hi[2 * b + 1]);
    fence_async_smem();
    __syncwarp();
#pragma unroll
    for (int i = 0; i < 4; i++) {
        const uint4 v = lds128(tile_rows + i * 512 + lane * 16);
        stg128(gdst + 32 * i, v.x, v.y, v.z, v.w);
    }
#pragma unroll
    for (int i = 0; i < 4; i++) ack[i] = readback(gdst + 32 * i);
}

__device__ __forceinline__ void feature_maps(const uint32_t* a, const uint32_t* wb, float c0, float c1, uint32_t* plus, uint32_t* minus) {
    uint32_t P[16], mx[4], mn[4];
#pragma unroll
    for (int h = 0; h < 4; h++) {
        float p[8];
        mma16816_z(p, a + 4 * h, wb[4 * h], wb[4 * h + 1]);
        mma16816_z(p + 4, a + 4 * h, wb[4 * h + 2], wb[4 * h + 3]);
        P[4 * h] = pack_bf16(p[0], p[2]); P[4 * h + 1] = pack_bf16(p[1], p[3]);
        P[4 * h + 2] = pack_bf16(p[4], p[6]); P[4 * h + 3] = pack_bf16(p[5], p[7]);
        mx[h] = max2(max2(P[4 * h], P[4 * h + 1]), max2(P[4 * h + 2], P[4 * h + 3]));
        mn[h] = min2(min2(P[4 * h], P[4 * h + 1]), min2(P[4 * h + 2], P[4 * h + 3]));
    }
#pragma unroll
    for (int s = 1; s <= 2; s <<= 1) {
        uint32_t tx[4], tn[4];
#pragma unroll
        for (int h = 0; h < 4; h++) { tx[h] = __shfl_xor_sync(0xffffffffu, mx[h], s); tn[h] = __shfl_xor_sync(0xffffffffu, mn[h], s); }
#pragma unroll
        for (int h = 0; h < 4; h++) { mx[h] = max2(mx[h], tx[h]); mn[h] = min2(mn[h], tn[h]); }
    }
#pragma unroll
    for (int h = 0; h < 4; h++) {
        const float mx0 = bf_lo(mx[h]) * c0, mx1 = bf_hi(mx[h]) * c1, mn0 = bf_lo(mn[h]) * c0, mn1 = bf_hi(mn[h]) * c1;
        float ep[8], em[8];
#pragma unroll
        for (int i = 0; i < 8; i++) {
            const bool r1 = (i & 2);
            const uint32_t w = P[4 * h + (i >> 2) * 2 + (i & 1)];
            const float p = r1 ? bf_hi(w) : bf_lo(w);
            ep[i] = ex2(fmaf(p, r1 ? c1 : c0, r1 ? -mx1 : -mx0));
            em[i] = ex2(fmaf(p, r1 ? -c1 : -c0, r1 ? mn1 : mn0));
        }
        float sp[4], sm[4];
        uint32_t tp[4], tm[4];
#pragma unroll
        for (int i = 0; i < 4; i++) { tp[i] = pack_bf16(ep[2 * i], ep[2 * i + 1]); tm[i] = pack_bf16(em[2 * i], em[2 * i + 1]); }
        mma16816_z(sp, tp, 0x3f803f80u, 0x3f803f80u);
        mma16816_z(sm, tm, 0x3f803f80u, 0x3f803f80u);
        const float r0 = rcp(sp[0] * sm[0]), r1 = rcp(sp[2] * sm[2]);
        const float rs[4] = {r0 * sm[0], r1 * sm[2], r0 * sp[0], r1 * sp[2]};
#pragma unroll
        for (int i = 0; i < 4; i++) {
            plus[4 * h + i] = pack_bf16(ep[2 * i] * rs[i & 1], ep[2 * i + 1] * rs[i & 1]);
            minus[4 * h + i] = pack_bf16(em[2 * i] * rs[2 + (i & 1)], em[2 * i + 1] * rs[2 + (i & 1)]);
        }
    }
}

template <bool SCALE>
__device__ __forceinline__ void ln_frag(const float* acc, uint32_t cs_addr, float rs0, float nm0, float rs1, float nm1, uint32_t* a) {
    const float2 c0 = lds_f2(cs_addr), c1 = lds_f2(cs_addr + 32);
    const float s0 = SCALE ? rs0 : 1.f, s1 = SCALE ? rs1 : 1.f;
    a[0] = pack_bf16(fmaf(nm0, c0.x, acc[0]) * s0, fmaf(nm0, c0.y, acc[1]) * s0);
    a[1] = pack_bf16(fmaf(nm1, c0.x, acc[2]) * s1, fmaf(nm1, c0.y, acc[3]) * s1);
    a[2] = pack_bf16(fmaf(nm0, c1.x, acc[4]) * s0, fmaf(nm0, c1.y, acc[5]) * s0);
    a[3] = pack_bf16(fmaf(nm1, c1.x, acc[6]) * s1, fmaf(nm1, c1.y, acc[7]) * s1);
}

template <int UP>
__device__ __forceinline__ uint32_t hh_pair(const float* ag, float4 cs, float nmean) {
    const float g0 = fmaf(nmean, cs.x, ag[0]), g1 = fmaf(nmean, cs.y, ag[1]);
    const float u0 = fmaf(nmean, cs.z, ag[UP]), u1 = fmaf(nmean, cs.w, ag[UP + 1]);
    return pack_bf16(g0 * u0, g1 * u1);
}
template <int NTP>
__device__ __forceinline__ void hh_stage(const float* acc, const float4* cs, float nm0, float nm1, uint32_t stg, int lane) {
#pragma unroll
    for (int tp = 0; tp < NTP; tp++)
        stsm4(stg + (lane & 15) * 128 + (((2 * tp + (lane >> 4)) ^ (lane & 7)) << 4), hh_pair<32>(acc + 8 * tp, cs[2 * tp], nm0),
              hh_pair<32>(acc + 8 * tp + 2, cs[2 * tp], nm1), hh_pair<32>(acc + 8 * tp + 4, cs[2 * tp + 1], nm0),
              hh_pair<32>(acc + 8 * tp + 6, cs[2 * tp + 1], nm1));
    fence_async_smem();
    __syncwarp();
}

template <int TP0, int TP1>
__device__ __forceinline__ void hh_stage2(const float* acc, const float4* cs, float nm0, float nm1, uint32_t stg, int lane) {
#pragma unroll
    for (int tp = TP0; tp < TP1; tp++)
        stsm4(stg + (lane & 15) * 128 + (((2 * tp + (lane >> 4)) ^ (lane & 7)) << 4), hh_pair<32>(acc + 8 * tp, cs[2 * tp], nm0),
              hh_pair<32>(acc + 8 * tp + 2, cs[2 * tp], nm1), hh_pair<32>(acc + 8 * tp + 4, cs[2 * tp + 1], nm0),
              hh_pair<32>(acc + 8 * tp + 6, cs[2 * tp + 1], nm1));
}
struct Ring {
    int slot; uint32_t phase;
    __device__ __forceinline__ void adv() { if (++slot == NB) { slot = 0; phase ^= 1; } }
    __device__ __forceinline__ void adv5() { slot += slot == 3; adv(); }
};

__global__ void __cluster_dims__(2, 1, 1) __launch_bounds__(NTHREADS, 1) fused_kernel(const __grid_constant__ Params P) {
    extern __shared__ __align__(1024) uint8_t smem_raw[];
    const uint32_t sb = smem_u32(smem_raw);
    const int tid = threadIdx.x, lane = tid & 31;
    if (tid >= 256 && tid < 258) prefetch_tmap(&P.tx + (tid & 1));
    const int warp = __shfl_sync(0xffffffffu, tid >> 5, 0);
    const unsigned role = P.role[blockIdx.x], rank = blockIdx.x & 1;
    const int m = role >> 3, j = role & 7;
    const bool helper = role >= 128;

    TL(0, tid == 0); TLG(0, tid == 0);
    float* const acc_j = g_acc + j * ACC_SIZE;

    if (__builtin_expect(warp >= 8, 1)) {
        asm volatile("setmaxnreg.dec.sync.aligned.u32 72;");
        if (elect_one()) {
            if (warp == 8) {
                if (!helper) {
#pragma unroll
                    for (int i = 0; i < NB; i++) mbar_init(sb + BAR_FULLB + 8 * i, 1);
#pragma unroll
                    for (int i = 0; i < 2; i++) {
                        mbar_expect_tx(sb + BAR_FULLB + 8 * i, SLOT);
                        tma2d(sb + OFF_B + i * SLOT, &P.twq, sb + BAR_FULLB + 8 * i, DM + 64 * j, 64 * i);
                        tma2d(sb + OFF_B + i * SLOT + 8192, &P.twq, sb + BAR_FULLB + 8 * i, 2 * DM + 64 * j, 64 * i);
                    }
                }
            } else if (warp == 9) {
#pragma unroll
                for (int i = 0; i < 8; i++) mbar_init(sb + BAR_FULLA + 8 * i, 1);
                if (!helper) {
#pragma unroll
                    for (int i = 0; i < 2; i++) {
                        mbar_expect_tx(sb + BAR_FULLA + 8 * i, SLOT);
                        tma2d(sb + OFF_A + i * SLOT, &P.tx, sb + BAR_FULLA + 8 * i, 64 * i, 128 * m);
                    }
                }
            } else if (warp == 10) {
#pragma unroll
                for (int i = 0; i < 12; i++) mbar_init(sb + BAR_CS1 + 8 * i, i < 2 || i >= 8 ? 64 : (i < 4 ? 32 : 8));
                trap_if_gt(sb & 1023, 0);
            } else {
#pragma unroll
                for (int i = 0; i < 14; i++) mbar_init(sb + (i < 8 ? BAR_EMPTYA : BAR_EMPTYB - 64) + 8 * i, i < 8 ? 8 : 16);
            }
            asm volatile("fence.mbarrier_init.release.cluster;" ::: "memory");
        }
        __syncwarp();
        asm volatile("barrier.cluster.arrive.relaxed.aligned;" ::: "memory");
        const unsigned epoch = ld_relaxed(&g_epoch);
        bar_sync(0, NTHREADS);
        if (helper) {
            if (elect_one()) {
#pragma unroll 1
                for (int i = warp - 8; i < 72; i += 4) {
                    const uint32_t full = sb + BAR_FULLA + 8 * (i & 7), dst = sb + OFF_A + (i & 7) * SLOT;
                    const int n = i >> 1, jj = 2 * j + (i & 1);
                    const bool qkv = n < 12;
                    const int c0 = qkv ? (n < 8 ? DM + 128 * (n & 4) : 0) + 64 * jj : 176 * jj + 8 * ((n - 12) & ~7);
                    const int r0 = qkv ? 128 * (n & 3) : 64 * ((n - 12) & 7);
                    mbar_wait(sb + BAR_EMPTYA + 8 * (i & 7), ((i >> 3) & 1) ^ 1);
                    mbar_expect_tx(full, SLOT);
                    tma2d(dst, qkv ? &P.twq : &P.twg, full, c0, r0);
                    tma2d(dst + 8192, qkv ? &P.twq : &P.twu, full, c0, qkv ? r0 + 64 : r0);
                }
                prefetch_l2(P.wd + (size_t)(4 * j + warp - 8) * 44032, 88064);
            }
            return;
        }
        if (warp == 8) {
            asm volatile("barrier.cluster.wait.aligned;" ::: "memory");
            if (elect_one()) {
                if (m >= 6)
                    asm volatile("cp.async.bulk.prefetch.tensor.2d.L2.global [%0, {%1, %2}];" ::"l"(&P.twq), "r"(DM + DM * (m & 1) + 64 * j), "r"(64 * (m >> 1)) : "memory");
                if (j >= 3)
                    asm volatile("cp.async.bulk.prefetch.tensor.2d.L2.global [%0, {%1, %2}];" ::"l"(&P.tx), "r"(64 * j), "r"(128 * m) : "memory");
                Ring r{2, 0};
                const uint32_t dst = sb + OFF_B + rank * 8192;
#define B_LOAD(TM, C0, R0)                                                                                  \
        mbar_waitc(sb + BAR_EMPTYB + 8 * r.slot, r.phase ^ 1);                                              \
        mbar_expect_tx(sb + BAR_FULLB + 8 * r.slot, SLOT);                                                  \
        tma2d_mc(dst + r.slot * SLOT, TM, sb + BAR_FULLB + 8 * r.slot, C0, R0);
#pragma unroll 1
                for (int i = 2; i < 8; i++) {
                    if (i >= AHEAD && i < 6) mbar_waitc(sb + BAR_FULLB + 8 * (i - AHEAD), 0);
                    B_LOAD(&P.twq, DM + DM * rank + 64 * j, 64 * i)
                    r.adv();
                }
#pragma unroll 1
                for (int i = 8; i < 20; i++) {
                    if (i < 12) {
                        mbar_waitc(sb + BAR_EMPTYB + 8 * r.slot, r.phase ^ 1);
                        mbar_arrive(sb + BAR_FULLB + 8 * r.slot);
                    } else {
                        const int e = 2 * (i & 3) + rank;
                        B_LOAD(i < 16 ? &P.twq : &P.two, 64 * j, 64 * (i < 16 ? e : KORD(e, j)))
                    }
                    r.adv();
                }
#pragma unroll 1
                for (int i = 0; i < 24; i++) {
                    B_LOAD(&P.twg + rank, 176 * j + 8 * (i & ~7), 64 * (i < 8 ? KORD(i, j) : i & 7))
                    r.adv5();
                }
#pragma unroll 1
                for (int i = 0; i < 12; i++) {
                    B_LOAD(&P.twd, 64 * j, 176 * (2 * (i & 3) + rank) + 64 * (i >> 2))
                    r.adv5();
                }
            }
            return;
        }
        if (warp == 9) {
            if (elect_one()) {
#pragma unroll 1
                for (int i = 2; i < 8; i++) {
                    if (i >= AHEAD + 1) mbar_wait(sb + BAR_FULLA + 8 * (i - AHEAD - 1), 0);
                    mbar_expect_tx(sb + BAR_FULLA + 8 * i, SLOT);
                    tma2d(sb + OFF_A + i * SLOT, &P.tx, sb + BAR_FULLA + 8 * i, 64 * i, 128 * m);
                }
#pragma unroll 1
                for (int i = 2; i < 7; i++) prefetch_tmap(&P.tx + i);
                unsigned nf = 0;
#pragma unroll 1
                for (int r = 1; r < 6; r++) {
                    const int skip = r < 3 ? j : 8;
                    const uint4* src = g_act + ((r - 1) * 128 + m * 8) * 1024;
                    const unsigned* fl = g_flag + (m * 5 + r - 1) * 32;
                    if (r < 4) mbar_wait(sb + BAR_EMPTYA + 8 * (r == 3 ? PF_DELAY : skip == 0), (r - 1) & 1);
                    if (r < 4 || nf != epoch * 8) wait_count(fl, epoch * (r < 3 ? 64 : 8));
                    TL(64 + r, true);
#pragma unroll 1
                    for (int t = 0; t < 8; t++) {
                        if (t == skip) continue;
                        if (t == 6) nf = readback(fl + 32);
                        mbar_wait(sb + BAR_EMPTYA + 8 * t, (r - 1) & 1);
                        mbar_expect_tx(sb + BAR_FULLA + 8 * t, SLOT);
                        asm volatile("cp.async.bulk.shared::cluster.global.mbarrier::complete_tx::bytes [%0], [%1], %2, [%3];"
                                     ::"r"(sb + OFF_A + t * SLOT), "l"(src + t * 1024), "r"(SLOT), "r"(sb + BAR_FULLA + 8 * t) : "memory");
                    }
                }
            }
            return;
        }
        const int a = warp - 10;
        {
            const int row = 16 * j + 8 * a + (lane >> 2);
            const uint32_t ra = sb + OFF_A + row * 128;
            float sh = 0.f, s0 = 0.f, s1 = 0.f, q0 = 0.f, q1 = 0.f;
#pragma unroll 1
            for (int kt = 0; kt < 8; kt++) {
                mbar_wait(sb + BAR_FULLA + 8 * kt, 0);
                if (kt == 0) sh = bf_lo(lds128(ra + ((row & 7) << 4)).x);
#pragma unroll
                for (int i = 0; i < 2; i++) {
                    const uint4 v = lds128(ra + kt * SLOT + (((2 * (lane & 3) + i) ^ (row & 7)) << 4));
                    const uint32_t ww[4] = {v.x, v.y, v.z, v.w};
#pragma unroll
                    for (int e = 0; e < 4; e++) {
                        const float d0 = bf_lo(ww[e]) - sh, d1 = bf_hi(ww[e]) - sh;
                        s0 += d0; q0 = fmaf(d0, d0, q0);
                        s1 += d1; q1 = fmaf(d1, d1, q1);
                    }
                }
            }
            s0 += s1; q0 += q1;
#pragma unroll
            for (int o = 1; o <= 2; o <<= 1) { s0 += __shfl_xor_sync(0xffffffffu, s0, o); q0 += __shfl_xor_sync(0xffffffffu, q0, o); }
            const float md = s0 * (1.f / DM);
            const float rs = rsqrtf(fmaxf(q0 * (1.f / DM) - md * md, 0.f) + 1e-5f);
            st_tagged_if(g_xstat + 2 * (128 * m + row), rs, -(sh + md), epoch, (lane & 3) == 0);
            TL(1, lane == 0 && a == 0);
        }
        const unsigned long long* cs = g_cs + j * 768 + 2 * lane;
        {
            const unsigned long long* xs = g_xstat + 2 * (128 * m + 64 * a + lane);
            uint4 v0, v1, v2;
            uint32_t it = 0;
            do {
                v0 = ld_tagged_rlx(xs); v1 = ld_tagged_rlx(xs + 64); v2 = ld_tagged_rlx(cs + 128 * a);
                trap_if_gt(++it, 1u << 22);
            } while (__any_sync(0xffffffffu, v0.y != epoch || v0.w != epoch || v1.y != epoch || v1.w != epoch || v2.y != epoch || v2.w != epoch));
            sts64(sb + OFF_XST + (64 * a + lane) * 8, v0.x, v0.z);
            sts64(sb + OFF_XST + (64 * a + 32 + lane) * 8, v1.x, v1.z);
            sts64(sb + OFF_CS1 + 256 * (a + 1) + 8 * lane, v2.x, v2.z);
            mbar_arrive(sb + BAR_CS1);
            TL(22 + a, lane == 0);
            if (a) {
                fetch_tagged(cs + 256, sb + OFF_CS1 + 8 * lane, epoch);
                mbar_arrive(sb + BAR_CSQ);
                TL(24, lane == 0);
            }
        }
        {
            mbar_wait(sb + BAR_KVW, 0);
            const float* src = acc_j + 4 * (128 * a + lane);
            float4 v[12];
            uint32_t it = 0;
            bool bad;
            while (__any_sync(0xffffffffu, readback(acc_j + 2048 + 128 * (lane & 7) + 127) != 0x41800000u)) trap_if_gt(++it, 1u << 22);
            TL(19, lane == 0 && a == 0);
            do {
                bad = false;
#pragma unroll
                for (int i = 0; i < 12; i++) v[i] = ld_l2_f4(src + 1024 * (i % 3) + 128 * (i / 3));
#pragma unroll
                for (int i = 0; i < 12; i++) bad |= v[i].w != 16.f;
                trap_if_gt(++it, 1u << 22);
            } while (__any_sync(0xffffffffu, bad));
            TL(14, lane == 0 && a == 0);
            const uint32_t d0 = sb + OFF_B + 5 * SLOT + (64 * a + (lane >> 2)) * 48;
            const uint32_t d = d0 + (lane & 3) * 4, dz = d0 + (lane & 1) * 384 + 32 + (lane & 2) * 4;
#pragma unroll
            for (int u = 0; u < 4; u++) {
                sts32(d + 768 * u, pack_bf16(v[3 * u].x, v[3 * u].y));
                sts32(d + 768 * u + 384, pack_bf16(v[3 * u].z, v[3 * u + 1].z));
                sts32(d + 768 * u + 16, pack_bf16(v[3 * u + 1].x, v[3 * u + 1].y));
                sts32(d + 768 * u + 400, pack_bf16(v[3 * u + 2].x, v[3 * u + 2].y));
                const uint32_t z2 = pack_bf16(v[3 * u + 2].z, v[3 * u + 2].z);
                sts64(dz + 768 * u, z2, z2);
            }
            mbar_arrive(sb + BAR_KVR);
        }
#pragma unroll 1
        for (int c = 0; c < 3; c++) {
            fetch_tagged(cs + 384 + 128 * c + 64 * a, sb + OFF_CS3 + (32 * c + lane) * 16 + 8 * a, epoch);
            mbar_arrive(sb + BAR_CSG + 8 * c);
            TL(45 + c, lane == 0 && a == 0);
        }
        {
            uint32_t it = 0;
            while (__any_sync(0xffffffffu, (int)(readback(g_flag + (m * 5 + 1) * 32) - epoch * 64) < 0)) {
                __nanosleep(200);
                trap_if_gt(++it, 1u << 22);
            }
#pragma unroll 1
            for (int rr = 0; rr < 2; rr++) {
                const int row = 64 * rr + 32 * a + lane;
                const unsigned long long* hs = g_hstat + (1024 * m + row) * 2;
                uint4 v[8];
                bool bad;
                do {
                    bad = false;
#pragma unroll
                    for (int i = 0; i < 8; i++) v[i] = ld_tagged_rlx(hs + 256 * i);
#pragma unroll
                    for (int i = 0; i < 8; i++) bad |= v[i].y != epoch || v[i].w != epoch;
                    trap_if_gt(++it, 1u << 22);
                } while (__any_sync(0xffffffffu, bad));
                float mean = 0.f;
#pragma unroll
                for (int i = 0; i < 8; i++) mean += __uint_as_float(v[i].x);
                mean *= 0.125f;
                float m2 = 0.f, dv = 0.f;
#pragma unroll
                for (int i = 0; i < 8; i++) { const float d = __uint_as_float(v[i].x) - mean; m2 += __uint_as_float(v[i].z); dv = fmaf(d, d, dv); }
                sts_f2(sb + OFF_CS1 + row * 8, -mean, rcp(fmaf(dv, 64.f, m2) * (1.f / DM) + 1e-5f));
            }
        }
        mbar_arrive(sb + BAR_CS3);
#pragma unroll 1
        for (int c = a; c < 3; c += 2) {
            mbar_wait(sb + BAR_STG + 8 * c, 0);
            if (elect_one()) {
                asm volatile("cp.async.bulk.global.shared::cta.bulk_group [%0], [%1], %2;" ::"l"(g_act + ((2 + c) * 128 + role) * 1024), "r"(sb + OFF_B + 4 * SLOT), "r"(SLOT) : "memory");
                asm volatile("cp.async.bulk.commit_group;" ::: "memory");
                asm volatile("cp.async.bulk.wait_group.read 0;" ::: "memory");
                mbar_arrive(sb + BAR_FULLB + 8 * 4);
                asm volatile("cp.async.bulk.wait_group 0;" ::: "memory");
            }
            __syncwarp();
            TL(60 + c, lane == 0);
            uint32_t ack = 0;
            const uint4* rb = g_act + ((2 + c) * 128 + role) * 1024 + lane * 8;
#pragma unroll
            for (int i = 0; i < 4; i++) ack |= readback(rb + 256 * i);
            signal_after(g_flag + (m * 5 + 2 + c) * 32, ack, P.zero, lane == 0);
            TL(54 + c, lane == 0);
        }
        return;
    }
    const unsigned epoch = ld_relaxed(&g_epoch);
    uint32_t wraw[16];
    if (!helper) {
        const uint32_t* wp = reinterpret_cast<const uint32_t*>(P.wphi) + (4 * j) * 128 + (lane & 3) * 16 + (lane >> 2);
#pragma unroll
        for (int i = 0; i < 16; i++)
            asm volatile("ld.global.nc.u32 %0, [%1];" : "=r"(wraw[i]) : "l"(wp + (i >> 2) * 128 + ((i >> 1) & 1) * 64 + (i & 1) * 8));
    }
    asm volatile("barrier.cluster.arrive.relaxed.aligned;" ::: "memory");
    asm volatile("setmaxnreg.inc.sync.aligned.u32 216;");
    bar_sync(0, NTHREADS);
    if (helper) {
        const int w = warp >> 2;
        sts64(sb + OFF_B + 8 * tid, 0x3f803f80u, 0x3f803f80u);
#pragma unroll 1
        for (int i = tid; i < 2 * ACC_SIZE / 4; i += 256) stg128(g_acc + 2 * j * ACC_SIZE + 4 * i, 0, 0, 0, 0);
        fence_async_smem();
        bar_sync(1, 256);
        TL(70, tid == 0);
        float acc[8];
        int i = w;
#pragma unroll 1
        for (int job = 0; job < 6; job++) {
            const int n = job < 3 ? 4 : 8;
#pragma unroll 1
            for (int t = 0; t < n; t++, i += 2) {
                mbar_waitc(sb + BAR_FULLA + 8 * (i & 7), (i >> 3) & 1);
                const desc_t da = desc_lo(sb + OFF_A) + (i & 7) * (SLOT >> 4);
                wg_fence();
#pragma unroll
                for (int k = 0; k < 8; k++) wgmma_n8_tt(acc + (k & 4), da + 128 * k, desc_lo(sb + OFF_B), (t | (k & 3)) != 0);
                wg_commit();
                wg_wait<0>();
                mbar_arrive_n_if(sb + BAR_EMPTYA + 8 * (i & 7), 2, lane == 0);
            }
            fence_acc<8>(acc);
            TL(71 + job, tid == 0);
            if (job == 1) {
                uint32_t z = 0;
#pragma unroll
                for (int u = 0; u < 6; u++) z |= readback(g_acc + 2 * j * ACC_SIZE + 4 * (tid + 256 * u));
                trap_if_gt(z, 0);
                bar_sync(1, 256);
            }
            const int q = lane & 3;
            const float lo = (q & 1) ? acc[2] : acc[0], hi = (q & 1) ? acc[6] : acc[4];
            const float v = job < 3 ? lo + hi : ((q & 2) ? hi : lo);
            unsigned long long* dst = g_cs + ((2 * j + w) * 6 + job) * 128 + (q >> 1) * 64 + 16 * (warp & 3) + 8 * (q & 1) + (lane >> 2);
            asm volatile("st.relaxed.gpu.global.b64 [%0], %1;" ::"l"(dst), "l"(((unsigned long long)epoch << 32) | __float_as_uint(v)) : "memory");
        }
        return;
    }
    {
        const int w = warp >> 2, wv = warp & 3, g = lane >> 2, q = lane & 3;
        const uint32_t sa = sb + OFF_A + w * 8192;
        const desc_t dA = desc_lo(sa), dB = desc_lo(sb + OFF_B);
        unsigned* const flag_m = g_flag + m * 160;
        const bool l0 = lane == 0, l2 = lane < 2;
        const uint32_t eb = mapa(sb + BAR_EMPTYB, lane & 1);
        asm volatile("barrier.cluster.wait.aligned;" ::: "memory");
        Ring rg{0, 0};
        int prev = 0;

        uint32_t wb[16];
        constexpr float L2E = 1.4426950408889634f;
        const int ch = lane >> 4, sw = lane & 7;
        const uint32_t lrow = (lane & 15) * 128;
        uint32_t fp[16], fm[16];
        {
            float acc[64];
#pragma unroll 1
            for (int kt = 0; kt < 8; kt++) {
                mbar_waitc(sb + BAR_FULLA + 8 * kt, 0);
                mbar_waitc(sb + BAR_FULLB + 8 * rg.slot, rg.phase);
                const desc_t da = dA + kt * (SLOT >> 4), db = dB + rg.slot * (SLOT >> 4);
                wg_fence();
#pragma unroll
                for (int k = 0; k < 4; k++) wgmma_n128(acc, da + 2 * k, db + 128 * k, (kt | k) != 0);
                wg_commit();
                wg_wait<1>();
                mbar_arrive_cl_if(eb + 8 * prev, l2 && kt > 0);
                prev = rg.slot; rg.adv();
            }
#pragma unroll
            for (int i = 0; i < 8; i++) {
                wb[(i >> 1) * 4 + (i & 1)] = __byte_perm(wraw[2 * i], wraw[2 * i + 1], 0x5410);
                wb[(i >> 1) * 4 + 2 + (i & 1)] = __byte_perm(wraw[2 * i], wraw[2 * i + 1], 0x7632);
            }
            uint32_t a[16];
#pragma unroll
            for (int i = 2; i < 6; i++) mbar_waitc(sb + BAR_FULLB + 8 * i, 1);
            TL(17, tid == 0);
            mbar_waitc(sb + BAR_CS1, 0);
            const float2 s0 = lds_f2(sb + OFF_XST + (16 * warp + g) * 8), s1 = lds_f2(sb + OFF_XST + (16 * warp + g + 8) * 8);
            wg_wait<0>();
            fence_acc<64>(acc);
            mbar_arrive_cl_if(eb + 8 * prev, l2);
            TL(2, tid == 0);
            const uint32_t st = sb + OFF_B + 2 * SLOT + warp * 2048 + lrow;
#pragma unroll
            for (int hh = 0; hh < 4; hh++) {
                ln_frag<true>(acc + 32 + 8 * hh, sb + OFF_CS1 + (128 + 16 * hh + 2 * q) * 4, s0.x, s0.y, s1.x, s1.y, a);
                stsm4(st + (2 + (hh >> 1)) * SLOT + (((2 * (hh & 1) + ch) ^ sw) << 4), a[0], a[1], a[2], a[3]);
            }
            stsm4(st + (2 + ch) * SLOT + ((4 ^ sw) << 4), 0x3f803f80u, 0x3f803f80u, 0x3f803f80u, 0x3f803f80u);
#pragma unroll
            for (int hh = 0; hh < 4; hh++)
                ln_frag<false>(acc + 8 * hh, sb + OFF_CS1 + (64 + 16 * hh + 2 * q) * 4, 0.f, s0.y, 0.f, s1.y, a + 4 * hh);
#pragma unroll 1
            for (int it = 0; it < 2; it++) {
                feature_maps(a, wb, s0.x * L2E, s1.x * L2E, fp, fm);
                if (it == 0) {
#pragma unroll
                    for (int hh = 0; hh < 4; hh++) {
                        stsm4(st + (hh >> 1) * SLOT + (((4 * (hh & 1) + ch) ^ sw) << 4), fp[4 * hh], fp[4 * hh + 1], fp[4 * hh + 2], fp[4 * hh + 3]);
                        stsm4(st + (hh >> 1) * SLOT + (((4 * (hh & 1) + 2 + ch) ^ sw) << 4), fm[4 * hh], fm[4 * hh + 1], fm[4 * hh + 2], fm[4 * hh + 3]);
                    }
                    fence_async_smem();
                    bar_sync(1, 256);
                    float kvd[20];
                    wg_fence();
#pragma unroll
                    for (int k = 0; k < 8; k++)
                        wgmma_n40_tt(kvd, dB + (2 + w) * (SLOT >> 4) + 128 * k, dB + (4 + w) * (SLOT >> 4) + 128 * k, k != 0);
                    wg_commit();
                    wg_wait<0>();
                    fence_acc<20>(kvd);
                    mbar_arrive_cl_if(eb + 8 * (2 + (lane >> 1)), lane < 6);
                    const bool h1 = wv >= 2;
                    float* kvp = acc_j + 4 * tid;
                    red_f32x4(kvp, h1 ? kvd[8] : kvd[0], h1 ? kvd[9] : kvd[1], h1 ? kvd[10] : kvd[2], 1.f);
                    red_f32x4(kvp + 1024, h1 ? kvd[12] : kvd[4], h1 ? kvd[13] : kvd[5], h1 ? kvd[11] : kvd[3], 1.f);
                    red_f32x4(kvp + 2048, h1 ? kvd[14] : kvd[6], h1 ? kvd[15] : kvd[7], (q & 1) ? kvd[18] : kvd[16], 1.f);
                    mbar_arrive_if(sb + BAR_KVW, l0);
                    TL(3, tid == 0);
                    float accq[32];
#pragma unroll 1
                    for (int b = 0; b < 4; b++) {
                        mbar_waitc(sb + BAR_FULLB + 8 * b, 0);
                        const desc_t da = dA + b * (2 * SLOT >> 4), db = dB + b * (SLOT >> 4);
                        wg_fence();
#pragma unroll
                        for (int k = 0; k < 8; k++) wgmma_n64(accq, da + (k >> 2) * (SLOT >> 4) + (k & 3) * 2, db + 128 * k, (b | k) != 0);
                        wg_commit();
                    }
                    mbar_waitc(sb + BAR_CSQ, 0);
                    wg_wait<0>();
                    fence_acc<32>(accq);
                    mbar_arrive_cl_if(eb + 8 * (lane >> 1), lane < 8);
                    TL(4, tid == 0);
#pragma unroll
                    for (int hh = 0; hh < 4; hh++)
                        ln_frag<false>(accq + 8 * hh, sb + OFF_CS1 + (16 * hh + 2 * q) * 4, 0.f, s0.y, 0.f, s1.y, a + 4 * hh);
                }
            }
        }
        uint32_t res_lo[8], res_hi[8], ack[4];
        const uint32_t own_rows = sb + OFF_A + j * SLOT + warp * 2048;
#pragma unroll
        for (int b = 0; b < 4; b++)
            ldsm4(own_rows + lrow + (((2 * b + ch) ^ sw) << 4), res_lo[2 * b], res_hi[2 * b], res_lo[2 * b + 1], res_hi[2 * b + 1]);
        mbar_arrive_if(sb + BAR_EMPTYA + 8 * lane, lane < 8 && lane != j);
        TL(5, tid == 0);
        mbar_waitc(sb + BAR_KVR, 0);
        TL(6, tid == 0);
        {
            const uint32_t kvs = sb + OFF_B + 5 * SLOT;
            uint32_t o_lo[8], o_hi[8];
#pragma unroll
            for (int hh = 0; hh < 4; hh++) {
                uint32_t b[8], zb[4];
                const uint32_t base = kvs + hh * 32 * 48;
                ldsm4t(base + (lane & 15) * 48 + (lane >> 4) * 16, b[0], b[1], b[2], b[3]);
                ldsm4t(base + (16 + (lane & 15)) * 48 + (lane >> 4) * 16, b[4], b[5], b[6], b[7]);
                ldsm4t(base + lane * 48 + 32, zb[0], zb[1], zb[2], zb[3]);
                float n0[4], n1[4], dn[4];
                mma16816_z(n0, fp + 4 * hh, b[0], b[1]); mma16816_z(n1, fp + 4 * hh, b[2], b[3]); mma16816_z(dn, fp + 4 * hh, zb[0], zb[1]);
                mma16816(n0, fm + 4 * hh, b[4], b[5]); mma16816(n1, fm + 4 * hh, b[6], b[7]); mma16816(dn, fm + 4 * hh, zb[2], zb[3]);
                const float i0 = rcp(dn[0] + 1e-6f), i1 = rcp(dn[2] + 1e-6f);
                o_lo[2 * hh] = pack_bf16(n0[0] * i0, n0[1] * i0); o_hi[2 * hh] = pack_bf16(n0[2] * i1, n0[3] * i1);
                o_lo[2 * hh + 1] = pack_bf16(n1[0] * i0, n1[1] * i0); o_hi[2 * hh + 1] = pack_bf16(n1[2] * i1, n1[3] * i1);
            }
            __syncwarp();
            mbar_arrive_cl_if(eb + 8 * 5, l2);
            rg.slot = 4; rg.phase = 0;
            store_tile(own_rows, g_act + role * 1024 + warp * 128 + lane, o_lo, o_hi, lane, ack);
            TL(7, tid == 0);
        }
        float acch[32];
        {
            float* acc = acch;
#pragma unroll
            for (int t = 0; t < 8; t++) {
                acc[4 * t] = bf_lo(res_lo[t]); acc[4 * t + 1] = bf_hi(res_lo[t]);
                acc[4 * t + 2] = bf_lo(res_hi[t]); acc[4 * t + 3] = bf_hi(res_hi[t]);
            }
            fence_acc<32>(acc);
            int pa = 0;
#pragma unroll 1
            for (int kp = 0; kp < 4; kp++) {
                mbar_waitc(sb + BAR_FULLB + 8 * rg.slot, rg.phase);
#pragma unroll
                for (int hf = 0; hf < 2; hf++) {
                    const int i = 2 * kp + hf, kt = KORD(i, j);
                    mbar_waitc(sb + BAR_FULLA + 8 * kt, i != 0);
                    TL(8, i == 1 && tid == 0);
                    const desc_t da = dA + kt * (SLOT >> 4), db = dB + rg.slot * (SLOT >> 4);
                    wg_fence();
#pragma unroll
                    for (int k = 0; k < 4; k++) wgmma_n64(acc, da + 2 * k, db + (hf * 4 + k) * 128, 1);
                    wg_commit();
                    wg_wait<1>();
                    mbar_arrive_if(sb + BAR_EMPTYA + 8 * pa, l0 && i > 1);
                    if (hf == 0) {
                        mbar_arrive_cl_if(eb + 8 * prev, l2 && i > 0);
                        if (i == 0) { signal_late(flag_m, ack, P.zero, l0); TL(20, tid == 0); }
                    }
                    pa = kt;
                }
                prev = rg.slot; rg.adv();
            }
            wg_wait<0>();
            fence_acc<32>(acc);
            mbar_arrive_if(sb + BAR_EMPTYA + 8 * pa, l0);
            mbar_arrive_cl_if(eb + 8 * prev, l2);
            TL(9, tid == 0);
#pragma unroll
            for (int t = 0; t < 8; t++) {
                res_lo[t] = pack_bf16(acc[4 * t], acc[4 * t + 1]);
                res_hi[t] = pack_bf16(acc[4 * t + 2], acc[4 * t + 3]);
            }
            store_tile(own_rows, g_act + (128 + role) * 1024 + warp * 128 + lane, res_lo, res_hi, lane, ack);
            TL(10, tid == 0);
        }
        float acc0[64], acc1[64], acc2[56], nm0, nm1;
        float4 cs[8];
        uint32_t hr[16];
#define P3_GROUP(MMA, ACC, KT)                                                                              \
        mbar_waitc(sb + BAR_FULLB + 8 * rg.slot, rg.phase);                                                 \
        {                                                                                                   \
            const desc_t da = dA + (KT) * (SLOT >> 4), db = dB + rg.slot * (SLOT >> 4);                     \
            wg_fence();                                                                                     \
            _Pragma("unroll") for (int k = 0; k < 4; k++) MMA(ACC, da + 2 * k, db + 128 * k, (i | k) != 0); \
            wg_commit();                                                                                    \
        }
#define P3_CS(C, NT)    \
        _Pragma("unroll") for (int t = 0; t < (NT); t++) lds_f4_if(cs[t], sb + OFF_CS3 + q * 16 + 512 * (C) + 64 * t, i == t);
#define P3_EPI2(C, ACC)                                                                                     \
        if (i == 0) {                                                                                       \
            fence_acc<64>(ACC);                                                                             \
            if (C) mbar_waitc(sb + BAR_FULLB + 8 * 4, 1);                                                   \
            hh_stage2<0, 2>(ACC, cs, nm0, nm1, stg, lane);                                                  \
            mbar_waitc(sb + BAR_CSG + 8 * (C) + 8, 0);                                                      \
        }                                                                                                   \
        if (i == 1) {                                                                                       \
            hh_stage2<2, 4>(ACC, cs, nm0, nm1, stg, lane);                                                  \
            fence_async_smem();                                                                             \
            __syncwarp();                                                                                   \
            mbar_arrive_if(sb + BAR_STG + 8 * (C), l0);                                                     \
        }
#define P3_EPI(C, ACC, N, NTP)                                                                              \
        fence_acc<N>(ACC);                                                                                  \
        TL(11 + (C), tid == 0);                                                                             \
        hh_stage<NTP>(ACC, cs, nm0, nm1, sb + OFF_B + 4 * SLOT + warp * 2048, lane);                        \
        mbar_arrive_if(sb + BAR_STG + 8 * (C), l0);                                                         \
        TL(50 + (C), tid == 0);
        const uint32_t stg = sb + OFF_B + 4 * SLOT + warp * 2048;
        const uint32_t blk = ((lane & 7) + (lane >> 4) * 8) * 128 + (((2 * wv + ((lane >> 3) & 1)) ^ (lane & 7)) << 4);
#pragma unroll 1
        for (int i = 0; i < 8; i++) {
            const int kt = KORD(i, j);
            mbar_waitc(sb + BAR_FULLA + 8 * kt, 0);
            TL(44, tid == 0 && i == 1);
            P3_GROUP(wgmma_n128, acc0, kt)
            if (i == 7) {
                mbar_waitc(sb + BAR_CS3, 0);
                nm0 = lds_f2(sb + OFF_CS1 + (16 * warp + g) * 8).x; nm1 = lds_f2(sb + OFF_CS1 + (16 * warp + g + 8) * 8).x;
            }
            wg_wait<1>();
            mbar_arrive_cl_if(eb + 8 * prev, l2 && i > 0);
            if (i == 0) {
                signal_late(flag_m + 32, ack, P.zero, l0);
                TL(21, tid == 0);
                {
                    fence_acc<32>(acch);
                    const float* acc = acch;
                    float s0 = 0.f, s1 = 0.f;
#pragma unroll
                    for (int t = 0; t < 8; t++) { s0 += acc[4 * t] + acc[4 * t + 1]; s1 += acc[4 * t + 2] + acc[4 * t + 3]; }
            s0 += __shfl_xor_sync(0xffffffffu, s0, 1); s1 += __shfl_xor_sync(0xffffffffu, s1, 1);
            s0 += __shfl_xor_sync(0xffffffffu, s0, 2); s1 += __shfl_xor_sync(0xffffffffu, s1, 2);
            const float mu0 = s0 * (1.f / 64), mu1 = s1 * (1.f / 64);
            float q0 = 0.f, q1 = 0.f;
#pragma unroll
            for (int t = 0; t < 8; t++) {
                float d;
                d = acc[4 * t] - mu0; q0 = fmaf(d, d, q0);
                d = acc[4 * t + 1] - mu0; q0 = fmaf(d, d, q0);
                d = acc[4 * t + 2] - mu1; q1 = fmaf(d, d, q1);
                d = acc[4 * t + 3] - mu1; q1 = fmaf(d, d, q1);
            }
            q0 += __shfl_xor_sync(0xffffffffu, q0, 1); q1 += __shfl_xor_sync(0xffffffffu, q1, 1);
            q0 += __shfl_xor_sync(0xffffffffu, q0, 2); q1 += __shfl_xor_sync(0xffffffffu, q1, 2);
            st_tagged_if(g_hstat + (role * 128 + 16 * warp + g + 8 * (q & 1)) * 2, q ? mu1 : mu0, q ? q1 : q0, epoch, q < 2);
                }
                bar_sync(2 + w, 128);
#pragma unroll
                for (int tp = 0; tp < 4; tp++) ldsm4t(sa + j * SLOT + blk + tp * 2048, hr[4 * tp], hr[4 * tp + 1], hr[4 * tp + 2], hr[4 * tp + 3]);
                mbar_waitc(sb + BAR_CSG, 0);
#pragma unroll
                for (int t = 0; t < 8; t++) cs[t] = lds_f4(sb + OFF_CS3 + q * 16 + 64 * t);
            }
            prev = rg.slot; rg.adv5();
        }
#pragma unroll 1
        for (int i = 0; i < 8; i++) {
            P3_GROUP(wgmma_n128, acc1, i)
            wg_wait<1>();
            mbar_arrive_cl_if(eb + 8 * prev, l2);
            P3_EPI2(0, acc0)
            P3_CS(1, 8)
            prev = rg.slot; rg.adv5();
        }
#pragma unroll 1
        for (int i = 0; i < 8; i++) {
            P3_GROUP(wgmma_n112, acc2, i)
            wg_wait<1>();
            mbar_arrive_cl_if(eb + 8 * prev, l2);
            mbar_arrive_if(sb + BAR_EMPTYA + 8 * ((i + 7) & 7), l0 && i > 0);
            if (i == 0) { mbar_waitc(sb + BAR_FULLB + 8 * 4, 1); P3_EPI(1, acc1, 64, 4) mbar_waitc(sb + BAR_CSG + 16, 0); }
            P3_CS(2, 6)
            prev = rg.slot; rg.adv5();
        }
        mbar_waitc(sb + BAR_FULLB + 8 * 4, 0);
        wg_wait<0>();
        mbar_arrive_cl_if(eb + 8 * prev, l2);
        mbar_arrive_if(sb + BAR_EMPTYA + 8 * 7, l0);
        P3_EPI(2, acc2, 56, 3)
        {
            float acc[64];
            const desc_t dA0 = desc_lo(sb + OFF_A);
#define KT_P4(I, NK)                                                                                        \
        const int s_ = (2 * (I) + w) & 7;                                                                   \
        mbar_waitc(sb + BAR_FULLB + 8 * rg.slot, rg.phase);                                                 \
        mbar_waitc(sb + BAR_FULLA + 8 * s_, (((I) >> 2) + 1) & 1);                                          \
        const desc_t dh_ = dA0 + s_ * (SLOT >> 4), dw_ = dB + rg.slot * (SLOT >> 4) + w * 512;              \
        wg_fence();                                                                                         \
        _Pragma("unroll") for (int k = 0; k < (NK); k++) wgmma_n128_tn(acc, dw_ + 128 * k, dh_ + 2 * k, ((I) | k) != 0); \
        wg_commit();                                                                                        \
        wg_wait<1>();
#pragma unroll 1
            for (int i = 0; i < 8; i++) {
                KT_P4(i, 4)
                mbar_arrive_n_if(sb + BAR_EMPTYA + 8 * ((s_ + 6) & 7), 2, l0 && i > 0);
                mbar_arrive_cl_if(eb + 8 * prev, l2 && i > 0);
#pragma unroll
                for (int t = 0; t < 8; t++) lds_f4_if(cs[t], sb + OFF_CS1 + (64 * w + 8 * t + 2 * q) * 8, i == t);
                prev = rg.slot; rg.adv5();
            }
#pragma unroll 1
            for (int i = 8; i < 12; i++) {
                KT_P4(i, 3)
                mbar_arrive_n_if(sb + BAR_EMPTYA + 8 * ((s_ + 6) & 7), 2, l0);
                rg.adv5();
            }
            wg_wait<0>();
            fence_acc<64>(acc);
            TL(15, tid == 0);
            const uint32_t xch = sb + OFF_A + 2 * SLOT + (tid & 127) * 16;
            if (w) {
#pragma unroll
                for (int t = 0; t < 8; t++) {
                    sts128(xch + SLOT + t * 2048, __float_as_uint(acc[4 * t]), __float_as_uint(acc[4 * t + 1]),
                           __float_as_uint(acc[4 * t + 2]), __float_as_uint(acc[4 * t + 3]));
                }
#pragma unroll
                for (int t = 0; t < 32; t++) acc[t] = acc[32 + t];
            } else {
#pragma unroll
                for (int t = 0; t < 8; t++)
                    sts128(xch + t * 2048, __float_as_uint(acc[32 + 4 * t]), __float_as_uint(acc[33 + 4 * t]),
                           __float_as_uint(acc[34 + 4 * t]), __float_as_uint(acc[35 + 4 * t]));
            }
            bar_sync(1, 256);
            float4 o[8];
#pragma unroll
            for (int t = 0; t < 8; t++) o[t] = lds_f4(xch + (w ^ 1) * SLOT + t * 2048);
            const uint32_t tile = sb + OFF_A + w * SLOT;
#pragma unroll
            for (int t = 0; t < 8; t++) {
                hr[2 * t] = pack_bf16(fmaf(acc[4 * t] + o[t].x, cs[t].y, bf_lo(hr[2 * t])), fmaf(acc[4 * t + 1] + o[t].y, cs[t].w, bf_hi(hr[2 * t])));
                hr[2 * t + 1] = pack_bf16(fmaf(acc[4 * t + 2] + o[t].z, cs[t].y, bf_lo(hr[2 * t + 1])), fmaf(acc[4 * t + 3] + o[t].w, cs[t].w, bf_hi(hr[2 * t + 1])));
            }
#pragma unroll
            for (int tp = 0; tp < 4; tp++) stsm4t(tile + blk + tp * 2048, hr[4 * tp], hr[4 * tp + 1], hr[4 * tp + 2], hr[4 * tp + 3]);
            fence_async_smem();
            bar_sync(2 + w, 128);
            if ((tid & 127) == 0) {
                tma_store2d(&P.tout, tile, 64 * j, 128 * m + 64 * w);
                asm volatile("cp.async.bulk.wait_group.read 0;" ::: "memory");
            }
            if (tid == 0 && role == 0) g_epoch = epoch + 1;
            TL(16, tid == 0); TLG(1, tid == 0);
        }
    }
}

__global__ void probe_kernel() {}

typedef CUresult (*EncodeFn)(CUtensorMap*, CUtensorMapDataType, cuuint32_t, void*, const cuuint64_t*, const cuuint64_t*,
                             const cuuint32_t*, const cuuint32_t*, CUtensorMapInterleave, CUtensorMapSwizzle,
                             CUtensorMapL2promotion, CUtensorMapFloatOOBfill);

static void make_map2d(EncodeFn enc, CUtensorMap* tm, const void* base, uint64_t cols, uint64_t rows, uint64_t pitch_elems,
                       uint32_t box_rows) {
    cuuint64_t gd[2] = {cols, rows};
    cuuint64_t gs[1] = {pitch_elems * 2};
    cuuint32_t bd[2] = {64, box_rows};
    cuuint32_t es[2] = {1, 1};
    enc(tm, CU_TENSOR_MAP_DATA_TYPE_BFLOAT16, 2, const_cast<void*>(base), gd, gs, bd, es, CU_TENSOR_MAP_INTERLEAVE_NONE,
        CU_TENSOR_MAP_SWIZZLE_128B, CU_TENSOR_MAP_L2_PROMOTION_L2_256B, CU_TENSOR_MAP_FLOAT_OOB_FILL_NONE);
}

}

extern "C" void kernel_launch(void* const* d_in, const int* in_sizes, int n_in, void* d_out, int out_size) {
    using namespace hk;
    (void)in_sizes; (void)n_in; (void)out_size;
    static EncodeFn enc = nullptr;
    static int std_layout = 0;
    if (!enc) {
        void* fn = nullptr;
        cudaDriverEntryPointQueryResult qr;
        cudaGetDriverEntryPoint("cuTensorMapEncodeTiled", &fn, cudaEnableDefault, &qr);
        enc = (EncodeFn)fn;
        cudaFuncSetAttribute(fused_kernel, cudaFuncAttributeMaxDynamicSharedMemorySize, SMEM_BYTES);
        int dev = 0, sms = 0;
        cudaGetDevice(&dev);
        cudaDeviceGetAttribute(&sms, cudaDevAttrMultiProcessorCount, dev);
        cudaFuncSetAttribute(probe_kernel, cudaFuncAttributeNonPortableClusterSizeAllowed, 1);
        cudaFuncSetAttribute(probe_kernel, cudaFuncAttributeMaxDynamicSharedMemorySize, SMEM_BYTES);
        const int sizes[3] = {8, 9, 16}, want[3] = {15, 9, 7};
        bool ok = sms == NCTA;
        for (int i = 0; i < 3 && ok; i++) {
            cudaLaunchConfig_t cfg = {};
            cfg.gridDim = dim3(sizes[i] * 8); cfg.blockDim = dim3(NTHREADS); cfg.dynamicSmemBytes = SMEM_BYTES;
            cudaLaunchAttribute at;
            at.id = cudaLaunchAttributeClusterDimension;
            at.val.clusterDim.x = sizes[i]; at.val.clusterDim.y = 1; at.val.clusterDim.z = 1;
            cfg.attrs = &at; cfg.numAttrs = 1;
            int n = 0;
            ok = cudaOccupancyMaxActiveClusters(&n, probe_kernel, &cfg) == cudaSuccess && n == want[i];
        }
        (void)cudaGetLastError();
        std_layout = ok ? 1 : 0;
    }
    Params P;
    const __nv_bfloat16* x = (const __nv_bfloat16*)d_in[0];
    P.x = x;
    P.wqkv = (const __nv_bfloat16*)d_in[1];
    P.wphi = (const __nv_bfloat16*)d_in[2];
    P.wo = (const __nv_bfloat16*)d_in[3];
    P.wg = (const __nv_bfloat16*)d_in[5];
    P.wu = (const __nv_bfloat16*)d_in[6];
    P.wd = (const __nv_bfloat16*)d_in[7];
    P.out = (__nv_bfloat16*)d_out;
    P.zero = 0;
    for (int i = 0; i < NCTA; i++) {
        const int odd = i & 1;
        int role = i < 4 ? 128 + i : (((i - 4) >> 4) * 2 + odd) * 8 + (((i - 4) >> 1) & 7);
        if (std_layout) {
            const int tpc = i < 8 ? 62 + (i >> 1) : (i - 8) >> 1;
            if (tpc < 32) role = (tpc & 7) ? (2 * ((tpc & 7) - 1) + odd) * 8 + (tpc >> 3) : (14 + odd) * 8 + (tpc >> 3);
            else if (tpc < 60) role = (2 * ((tpc - 32) % 7) + odd) * 8 + 4 + (tpc - 32) / 7;
            else if (tpc < 62) role = 128 + (tpc - 60) * 2 + odd;
            else role = (14 + odd) * 8 + 4 + (tpc - 62);
        }
        P.role[i] = (unsigned char)role;
    }
    make_map2d(enc, &P.tx, x, DM, SEQ, DM, 128);
    make_map2d(enc, &P.twq, P.wqkv, 3 * DM, DM, 3 * DM, 64);
    make_map2d(enc, &P.two, P.wo, DM, DM, DM, 64);
    make_map2d(enc, &P.twg, P.wg, FF, DM, FF, 64);
    make_map2d(enc, &P.twu, P.wu, FF, DM, FF, 64);
    make_map2d(enc, &P.twd, P.wd, DM, FF, DM, 64);
    make_map2d(enc, &P.tout, d_out, DM, SEQ, DM, 64);
    fused_kernel<<<NCTA, NTHREADS, SMEM_BYTES>>>(P);
}
```

```cpp
#include <cuda_runtime.h>
#include <cuda_bf16.h>
#include <cuda.h>
#include <stdint.h>

namespace hk {

constexpr int SEQ = 2048, DM = 512, FF = 1376;
constexpr int NCTA = 132;
constexpr int NTHREADS = 384;
constexpr uint32_t SLOT = 16384;
constexpr uint32_t OFF_A = 0, OFF_B = 8 * SLOT, OFF_MISC = 14 * SLOT;
constexpr uint32_t BAR_FULLA = OFF_MISC + 0, BAR_EMPTYA = OFF_MISC + 64, BAR_FULLB = OFF_MISC + 128,
                   BAR_EMPTYB = OFF_MISC + 176, BAR_CS1 = OFF_MISC + 224, BAR_CS3 = OFF_MISC + 232,
                   BAR_CSQ = OFF_MISC + 240, BAR_CSV = OFF_MISC + 248,
                   BAR_STG = OFF_MISC + 256,
                   BAR_KVW = OFF_MISC + 280, BAR_KVR = OFF_MISC + 288, BAR_CSG = OFF_MISC + 296;
constexpr uint32_t OFF_CS1 = OFF_MISC + 384;
constexpr uint32_t OFF_CS3 = OFF_CS1 + 1024;
constexpr uint32_t OFF_XST = OFF_CS3;
constexpr uint32_t SMEM_BYTES = OFF_CS3 + 1536;
#define KORD(i, j) ((i) == 0 ? (j) : (i) - ((i) <= (j)))
constexpr int NB = 6;
#define PF_DELAY 2
#define KV_POLL 1
constexpr int AHEAD = 3;

constexpr int ACC_SIZE = 3 * 256 * 4;

__device__ __align__(1024) uint4 g_act[5 * 128 * 1024];
__device__ __align__(128) unsigned long long g_hstat[SEQ * 16];
__device__ __align__(128) unsigned long long g_xstat[SEQ * 2];
__device__ __align__(128) float g_acc[8 * ACC_SIZE];
__device__ __align__(128) unsigned long long g_cs[8 * 6 * 128];
__device__ __align__(128) unsigned g_flag[16 * 5 * 32 + 32];
__device__ unsigned g_epoch = 1;

#define TL(i, pred) do {} while (0)
#define TLG(i, pred) do {} while (0)

struct Params {
    CUtensorMap tx, twq, two, twg, twu, twd, tout;
    const __nv_bfloat16 *x, *wqkv, *wphi, *wo, *wg, *wu, *wd;
    __nv_bfloat16* out;
    unsigned zero;
    unsigned char role[NCTA];
};

__device__ __forceinline__ uint32_t smem_u32(const void* p) { return (uint32_t)__cvta_generic_to_shared(p); }
__device__ __forceinline__ void mbar_init(uint32_t bar, uint32_t cnt) {
    asm volatile("mbarrier.init.shared::cta.b64 [%0], %1;" ::"r"(bar), "r"(cnt) : "memory");
}
__device__ __forceinline__ void mbar_expect_tx(uint32_t bar, uint32_t bytes) {
    asm volatile("mbarrier.arrive.expect_tx.shared::cta.b64 _, [%0], %1;" ::"r"(bar), "r"(bytes) : "memory");
}
__device__ __forceinline__ void mbar_arrive(uint32_t bar) {
    asm volatile("mbarrier.arrive.shared::cta.b64 _, [%0];" ::"r"(bar) : "memory");
}
__device__ __forceinline__ void mbar_arrive_if(uint32_t bar, bool pred) {
    asm volatile("{.reg .pred p; setp.ne.u32 p, %1, 0; @p mbarrier.arrive.shared::cta.b64 _, [%0];}" ::"r"(bar), "r"((uint32_t)pred) : "memory");
}
__device__ __forceinline__ bool mbar_try(uint32_t bar, uint32_t parity) {
    uint32_t ok;
    asm volatile("{.reg .pred p; mbarrier.try_wait.parity.shared::cta.b64 p, [%1], %2; selp.u32 %0,1,0,p;}"
                 : "=r"(ok) : "r"(bar), "r"(parity) : "memory");
    return ok;
}
__device__ __forceinline__ bool mbar_test(uint32_t bar, uint32_t parity) {
    uint32_t ok;
    asm volatile("{.reg .pred p; mbarrier.test_wait.parity.shared::cta.b64 p, [%1], %2; selp.u32 %0,1,0,p;}"
                 : "=r"(ok) : "r"(bar), "r"(parity) : "memory");
    return ok;
}
__device__ __forceinline__ void trap_if_gt(uint32_t v, uint32_t lim) {
    asm volatile("{.reg .pred p; setp.gt.u32 p, %0, %1; @p trap;}" ::"r"(v), "r"(lim));
}
__device__ __forceinline__ void mbar_wait(uint32_t bar, uint32_t parity) {
    asm volatile("{\n"
                 ".reg .pred P1, P2;\n"
                 ".reg .u32 c;\n"
                 "mov.u32 c, 0;\n"
                 "LAB_WAIT:\n"
                 "mbarrier.try_wait.parity.shared::cta.b64 P1, [%0], %1;\n"
                 "@P1 bra LAB_DONE;\n"
                 "add.u32 c, c, 1;\n"
                 "setp.gt.u32 P2, c, 4194304;\n"
                 "@P2 trap;\n"
                 "bra LAB_WAIT;\n"
                 "LAB_DONE:\n"
                 "}" ::"r"(bar), "r"(parity) : "memory");
}
__device__ __forceinline__ void mbar_waitc(uint32_t bar, uint32_t parity) {
    asm volatile("{\n"
                 ".reg .pred P1;\n"
                 "LAB_WAIT:\n"
                 "mbarrier.try_wait.parity.shared::cta.b64 P1, [%0], %1;\n"
                 "@!P1 bra LAB_WAIT;\n"
                 "}" ::"r"(bar), "r"(parity) : "memory");
}
__device__ __forceinline__ void tma2d(uint32_t dst, const CUtensorMap* tm, uint32_t bar, int c0, int c1) {
    asm volatile("cp.async.bulk.tensor.2d.shared::cluster.global.mbarrier::complete_tx::bytes [%0], [%1, {%3, %4}], [%2];"
                 ::"r"(dst), "l"(tm), "r"(bar), "r"(c0), "r"(c1) : "memory");
}
__device__ __forceinline__ void tma2d_mc(uint32_t dst, const CUtensorMap* tm, uint32_t bar, int c0, int c1) {
    asm volatile("cp.async.bulk.tensor.2d.shared::cluster.global.mbarrier::complete_tx::bytes.multicast::cluster [%0], [%1, {%3, %4}], [%2], %5;"
                 ::"r"(dst), "l"(tm), "r"(bar), "r"(c0), "r"(c1), "h"((uint16_t)3) : "memory");
}
__device__ __forceinline__ uint32_t mapa(uint32_t addr, uint32_t rank) {
    uint32_t r; asm("mapa.shared::cluster.u32 %0, %1, %2;" : "=r"(r) : "r"(addr), "r"(rank)); return r;
}
__device__ __forceinline__ void mbar_arrive_cl_if(uint32_t cbar, bool pred) {
    asm volatile("{.reg .pred p; setp.ne.u32 p, %1, 0; @p mbarrier.arrive.shared::cluster.b64 _, [%0];}" ::"r"(cbar), "r"((uint32_t)pred) : "memory");
}
__device__ __forceinline__ bool elect_one() {
    uint32_t ok;
    asm volatile("{.reg .pred p; elect.sync _|p, 0xffffffff; selp.u32 %0, 1, 0, p;}" : "=r"(ok));
    return ok;
}
__device__ __forceinline__ void prefetch_tmap(const CUtensorMap* tm) {
    asm volatile("prefetch.tensormap [%0];" ::"l"(tm) : "memory");
}
__device__ __forceinline__ void prefetch_l2(const void* p, uint32_t bytes) {
    asm volatile("cp.async.bulk.prefetch.L2.global [%0], %1;" ::"l"(p), "r"(bytes) : "memory");
}
__device__ __forceinline__ unsigned ld_acquire(const unsigned* p) {
    unsigned v; asm volatile("ld.acquire.gpu.global.u32 %0, [%1];" : "=r"(v) : "l"(p) : "memory"); return v;
}
__device__ __forceinline__ uint4 ld_acquire4(const unsigned* p) {
    uint4 v;
    asm volatile("ld.acquire.gpu.global.v4.u32 {%0,%1,%2,%3}, [%4];" : "=r"(v.x), "=r"(v.y), "=r"(v.z), "=r"(v.w) : "l"(p) : "memory");
    return v;
}
__device__ __forceinline__ unsigned ld_relaxed(const unsigned* p) {
    unsigned v; asm volatile("ld.relaxed.gpu.global.u32 %0, [%1];" : "=r"(v) : "l"(p)); return v;
}
__device__ __forceinline__ void st_relaxed(unsigned* p, unsigned v) {
    asm volatile("st.relaxed.gpu.global.u32 [%0], %1;" ::"l"(p), "r"(v) : "memory");
}
__device__ __forceinline__ void red_relaxed(unsigned* p, unsigned v) {
    asm volatile("red.relaxed.gpu.global.add.u32 [%0], %1;" ::"l"(p), "r"(v) : "memory");
}
__device__ __forceinline__ void fence_gpu() { asm volatile("fence.acq_rel.gpu;" ::: "memory"); }
__device__ __forceinline__ void fence_async_smem() { asm volatile("fence.proxy.async.shared::cta;" ::: "memory"); }
__device__ __forceinline__ void fence_async_global() { asm volatile("fence.proxy.async.global;" ::: "memory"); }
__device__ __forceinline__ uint32_t readback(const void* p) {
    uint32_t v; asm volatile("ld.relaxed.gpu.global.u32 %0, [%1];" : "=r"(v) : "l"(p) : "memory"); return v;
}
__device__ __forceinline__ void wait_count(const unsigned* p, unsigned target) {
    uint32_t it = 0;
    while ((int)(readback(p) - target) < 0) trap_if_gt(++it, 1u << 22);
}
__device__ __forceinline__ void wait_count_warp(const unsigned* p, unsigned target) {
    uint32_t it = 0;
    while (__any_sync(0xffffffffu, (int)(readback(p) - target) < 0)) trap_if_gt(++it, 1u << 22);
}
__device__ __forceinline__ void red_f32(float* p, float a) {
    asm volatile("red.relaxed.gpu.global.add.f32 [%0], %1;" ::"l"(p), "f"(a) : "memory");
}
__device__ __forceinline__ void red_f32x2(float* p, float a, float b) {
    asm volatile("red.relaxed.gpu.global.add.v2.f32 [%0], {%1, %2};" ::"l"(p), "f"(a), "f"(b) : "memory");
}
__device__ __forceinline__ void red_f32x4(float* p, float a, float b, float c, float d) {
    asm volatile("red.relaxed.gpu.global.add.v4.f32 [%0], {%1, %2, %3, %4};" ::"l"(p), "f"(a), "f"(b), "f"(c), "f"(d) : "memory");
}
__device__ __forceinline__ float4 ld_l2_f4(const float* p) {
    float4 v;
    asm volatile("ld.relaxed.gpu.global.v4.f32 {%0,%1,%2,%3}, [%4];" : "=f"(v.x), "=f"(v.y), "=f"(v.z), "=f"(v.w) : "l"(p) : "memory");
    return v;
}
__device__ __forceinline__ float2 ld_l2_f2(const float* p) {
    float2 v;
    asm volatile("ld.relaxed.gpu.global.v2.f32 {%0,%1}, [%2];" : "=f"(v.x), "=f"(v.y) : "l"(p) : "memory");
    return v;
}
__device__ __forceinline__ float ld_l2_f(const float* p) {
    float v;
    asm volatile("ld.relaxed.gpu.global.f32 %0, [%1];" : "=f"(v) : "l"(p) : "memory");
    return v;
}
__device__ __forceinline__ uint4 ldg_nc(const void* p) {
    uint4 v;
    asm volatile("ld.global.nc.L1::no_allocate.v4.u32 {%0,%1,%2,%3}, [%4];" : "=r"(v.x), "=r"(v.y), "=r"(v.z), "=r"(v.w) : "l"(p));
    return v;
}
__device__ __forceinline__ void stg128(void* p, uint32_t a, uint32_t b, uint32_t c, uint32_t d) {
    asm volatile("st.global.v4.u32 [%0], {%1,%2,%3,%4};" ::"l"(p), "r"(a), "r"(b), "r"(c), "r"(d) : "memory");
}
__device__ __forceinline__ uint4 lds128(uint32_t a) {
    uint4 v;
    asm volatile("ld.shared.v4.u32 {%0,%1,%2,%3}, [%4];" : "=r"(v.x), "=r"(v.y), "=r"(v.z), "=r"(v.w) : "r"(a) : "memory");
    return v;
}
__device__ __forceinline__ float2 lds_f2(uint32_t a) {
    float2 v;
    asm volatile("ld.shared.v2.f32 {%0,%1}, [%2];" : "=f"(v.x), "=f"(v.y) : "r"(a) : "memory");
    return v;
}
__device__ __forceinline__ void sts_f2(uint32_t a, float x, float y) {
    asm volatile("st.shared.v2.f32 [%0], {%1,%2};" ::"r"(a), "f"(x), "f"(y) : "memory");
}
__device__ __forceinline__ void sts64(uint32_t a, uint32_t x, uint32_t y) {
    asm volatile("st.shared.v2.u32 [%0], {%1,%2};" ::"r"(a), "r"(x), "r"(y) : "memory");
}
__device__ __forceinline__ void sts128(uint32_t a, uint32_t x, uint32_t y, uint32_t z, uint32_t w) {
    asm volatile("st.shared.v4.u32 [%0], {%1,%2,%3,%4};" ::"r"(a), "r"(x), "r"(y), "r"(z), "r"(w) : "memory");
}
__device__ __forceinline__ void stsm4(uint32_t a, uint32_t r0, uint32_t r1, uint32_t r2, uint32_t r3) {
    asm volatile("stmatrix.sync.aligned.m8n8.x4.shared.b16 [%0], {%1,%2,%3,%4};" ::"r"(a), "r"(r0), "r"(r1), "r"(r2), "r"(r3) : "memory");
}
__device__ __forceinline__ void stsm4t(uint32_t a, uint32_t r0, uint32_t r1, uint32_t r2, uint32_t r3) {
    asm volatile("stmatrix.sync.aligned.m8n8.x4.trans.shared.b16 [%0], {%1,%2,%3,%4};" ::"r"(a), "r"(r0), "r"(r1), "r"(r2), "r"(r3) : "memory");
}
__device__ __forceinline__ void tma_store2d(const CUtensorMap* tm, uint32_t src, int c0, int c1) {
    asm volatile("cp.async.bulk.tensor.2d.global.shared::cta.bulk_group [%0, {%2, %3}], [%1];" ::"l"(tm), "r"(src), "r"(c0), "r"(c1) : "memory");
    asm volatile("cp.async.bulk.commit_group;" ::: "memory");
}
__device__ __forceinline__ void ldsm4(uint32_t a, uint32_t& r0, uint32_t& r1, uint32_t& r2, uint32_t& r3) {
    asm volatile("ldmatrix.sync.aligned.m8n8.x4.shared.b16 {%0,%1,%2,%3}, [%4];" : "=r"(r0), "=r"(r1), "=r"(r2), "=r"(r3) : "r"(a) : "memory");
}
__device__ __forceinline__ void ldsm4t(uint32_t a, uint32_t& r0, uint32_t& r1, uint32_t& r2, uint32_t& r3) {
    asm volatile("ldmatrix.sync.aligned.m8n8.x4.trans.shared.b16 {%0,%1,%2,%3}, [%4];" : "=r"(r0), "=r"(r1), "=r"(r2), "=r"(r3) : "r"(a) : "memory");
}
__device__ __forceinline__ void mma16816(float* c, const uint32_t* a, uint32_t b0, uint32_t b1) {
    asm("mma.sync.aligned.m16n8k16.row.col.f32.bf16.bf16.f32 {%0,%1,%2,%3}, {%4,%5,%6,%7}, {%8,%9}, {%0,%1,%2,%3};"
                 : "+f"(c[0]), "+f"(c[1]), "+f"(c[2]), "+f"(c[3])
                 : "r"(a[0]), "r"(a[1]), "r"(a[2]), "r"(a[3]), "r"(b0), "r"(b1));
}
__device__ __forceinline__ uint32_t pack_bf16(float lo, float hi) {
    uint32_t r; asm("cvt.rn.bf16x2.f32 %0, %1, %2;" : "=r"(r) : "f"(hi), "f"(lo)); return r;
}
__device__ __forceinline__ float bf_lo(uint32_t w) { return __uint_as_float(w << 16); }
__device__ __forceinline__ float bf_hi(uint32_t w) { return __uint_as_float(w & 0xffff0000u); }
__device__ __forceinline__ float ex2(float x) { float r; asm("ex2.approx.ftz.f32 %0, %1;" : "=f"(r) : "f"(x)); return r; }
__device__ __forceinline__ float rcp(float x) { float r; asm("rcp.approx.ftz.f32 %0, %1;" : "=f"(r) : "f"(x)); return r; }
__device__ __forceinline__ void bar_sync(int id, int n) { asm volatile("bar.sync %0, %1;" ::"r"(id), "r"(n) : "memory"); }

typedef unsigned long long desc_t;
__device__ __forceinline__ desc_t desc_lo(uint32_t addr) { return (desc_t)(((addr & 0x3FFFF) >> 4) | (512u << 16)) | (0x40000040ull << 32); }
__device__ __forceinline__ void wg_fence() { asm volatile("wgmma.fence.sync.aligned;" ::: "memory"); }
__device__ __forceinline__ void wg_commit() { asm volatile("wgmma.commit_group.sync.aligned;" ::: "memory"); }
template <int N> __device__ __forceinline__ void wg_wait() { asm volatile("wgmma.wait_group.sync.aligned %0;" ::"n"(N) : "memory"); }
template <int N> __device__ __forceinline__ void fence_acc(float* d) {
#pragma unroll
    for (int i = 0; i < N; i++) asm volatile("" : "+f"(d[i])::"memory");
}
#define R4(o) "+f"(d[o + 0]), "+f"(d[o + 1]), "+f"(d[o + 2]), "+f"(d[o + 3])
#define R8(o) R4(o), R4(o + 4)
__device__ __forceinline__ void wgmma_n128(float* d, desc_t da, desc_t db, int sc) {
    asm volatile("{.reg .pred p; setp.ne.b32 p, %66, 0;\n"
                 "wgmma.mma_async.sync.aligned.m64n128k16.f32.bf16.bf16 {%0,%1,%2,%3,%4,%5,%6,%7,%8,%9,%10,%11,%12,%13,%14,%15,%16,%17,%18,%19,%20,%21,%22,%23,%24,%25,%26,%27,%28,%29,%30,%31,"
                 "%32,%33,%34,%35,%36,%37,%38,%39,%40,%41,%42,%43,%44,%45,%46,%47,%48,%49,%50,%51,%52,%53,%54,%55,%56,%57,%58,%59,%60,%61,%62,%63}, %64, %65, p, 1, 1, 0, 1;}"
                 : R8(0), R8(8), R8(16), R8(24), R8(32), R8(40), R8(48), R8(56)
                 : "l"(da), "l"(db), "r"(sc));
}
__device__ __forceinline__ void wgmma_n112(float* d, desc_t da, desc_t db, int sc) {
    asm volatile("{.reg .pred p; setp.ne.b32 p, %58, 0;\n"
                 "wgmma.mma_async.sync.aligned.m64n112k16.f32.bf16.bf16 {%0,%1,%2,%3,%4,%5,%6,%7,%8,%9,%10,%11,%12,%13,%14,%15,%16,%17,%18,%19,%20,%21,%22,%23,%24,%25,%26,%27,%28,%29,%30,%31,%32,%33,%34,%35,%36,%37,%38,%39,%40,%41,%42,%43,%44,%45,%46,%47,%48,%49,%50,%51,%52,%53,%54,%55}, %56, %57, p, 1, 1, 0, 1;}"
                 : R8(0), R8(8), R8(16), R8(24), R8(32), R8(40), R8(48)
                 : "l"(da), "l"(db), "r"(sc));
}
__device__ __forceinline__ void wgmma_n128_tn(float* d, desc_t da, desc_t db, int sc) {
    asm volatile("{.reg .pred p; setp.ne.b32 p, %66, 0;\n"
                 "wgmma.mma_async.sync.aligned.m64n128k16.f32.bf16.bf16 {%0,%1,%2,%3,%4,%5,%6,%7,%8,%9,%10,%11,%12,%13,%14,%15,%16,%17,%18,%19,%20,%21,%22,%23,%24,%25,%26,%27,%28,%29,%30,%31,%32,%33,%34,%35,%36,%37,%38,%39,%40,%41,%42,%43,%44,%45,%46,%47,%48,%49,%50,%51,%52,%53,%54,%55,%56,%57,%58,%59,%60,%61,%62,%63}, %64, %65, p, 1, 1, 1, 0;}"
                 : R8(0), R8(8), R8(16), R8(24), R8(32), R8(40), R8(48), R8(56)
                 : "l"(da), "l"(db), "r"(sc));
}
__device__ __forceinline__ void wgmma_n64(float* d, desc_t da, desc_t db, int sc) {
    asm volatile("{.reg .pred p; setp.ne.b32 p, %34, 0;\n"
                 "wgmma.mma_async.sync.aligned.m64n64k16.f32.bf16.bf16 {%0,%1,%2,%3,%4,%5,%6,%7,%8,%9,%10,%11,%12,%13,%14,%15,%16,%17,%18,%19,%20,%21,%22,%23,%24,%25,%26,%27,%28,%29,%30,%31}, %32, %33, p, 1, 1, 0, 1;}"
                 : R8(0), R8(8), R8(16), R8(24)
                 : "l"(da), "l"(db), "r"(sc));
}
__device__ __forceinline__ void wgmma_n40_tt(float* d, desc_t da, desc_t db, int sc) {
    asm volatile("{.reg .pred p; setp.ne.b32 p, %22, 0;\n"
                 "wgmma.mma_async.sync.aligned.m64n40k16.f32.bf16.bf16 {%0,%1,%2,%3,%4,%5,%6,%7,%8,%9,%10,%11,%12,%13,%14,%15,%16,%17,%18,%19}, %20, %21, p, 1, 1, 1, 1;}"
                 : R8(0), R8(8), R4(16)
                 : "l"(da), "l"(db), "r"(sc));
}

__device__ __forceinline__ void wgmma_n8_tt(float* d, desc_t da, desc_t db, int sc) {
    asm volatile("{.reg .pred p; setp.ne.b32 p, %6, 0;\n"
                 "wgmma.mma_async.sync.aligned.m64n8k16.f32.bf16.bf16 {%0,%1,%2,%3}, %4, %5, p, 1, 1, 1, 1;}"
                 : R4(0)
                 : "l"(da), "l"(db), "r"(sc));
}

__device__ __forceinline__ void signal_after(unsigned* cnt, uint32_t ack, uint32_t zero, bool pred) {
    asm volatile("{.reg .pred p; setp.ne.u32 p, %2, 0; @p red.relaxed.gpu.global.add.u32 [%0], %1;}"
                 ::"l"(cnt), "r"((ack & zero) + 1), "r"((uint32_t)pred) : "memory");
}
__device__ __forceinline__ void signal_late(unsigned* cnt, const uint32_t* a, uint32_t zero, bool pred) {
    uint32_t v;
    asm volatile("{.reg .b32 t; lop3.b32 t, %1, %2, %3, 0xfe; or.b32 %0, t, %4;}"
                 : "=r"(v) : "r"(a[0]), "r"(a[1]), "r"(a[2]), "r"(a[3]));
    signal_after(cnt, v, zero, pred);
}
__device__ __forceinline__ void red_f32_if(float* p, float a, bool pred) {
    asm volatile("{.reg .pred p; setp.ne.u32 p, %2, 0; @p red.relaxed.gpu.global.add.f32 [%0], %1;}" ::"l"(p), "f"(a), "r"((uint32_t)pred) : "memory");
}
__device__ __forceinline__ void stg_f2_if(float* p, float a, float b, bool pred) {
    asm volatile("{.reg .pred p; setp.ne.u32 p, %3, 0; @p st.global.v2.f32 [%0], {%1,%2};}" ::"l"(p), "f"(a), "f"(b), "r"((uint32_t)pred) : "memory");
}
__device__ __forceinline__ void stg64(void* p, uint32_t a, uint32_t b) {
    asm volatile("st.global.v2.u32 [%0], {%1,%2};" ::"l"(p), "r"(a), "r"(b) : "memory");
}
__device__ __forceinline__ void mma16816_z(float* c, const uint32_t* a, uint32_t b0, uint32_t b1) {
    asm("mma.sync.aligned.m16n8k16.row.col.f32.bf16.bf16.f32 {%0,%1,%2,%3}, {%4,%5,%6,%7}, {%8,%9}, {%10,%10,%10,%10};"
                 : "=f"(c[0]), "=f"(c[1]), "=f"(c[2]), "=f"(c[3])
                 : "r"(a[0]), "r"(a[1]), "r"(a[2]), "r"(a[3]), "r"(b0), "r"(b1), "f"(0.f));
}
__device__ __forceinline__ uint32_t max2(uint32_t a, uint32_t b) { uint32_t r; asm("max.bf16x2 %0, %1, %2;" : "=r"(r) : "r"(a), "r"(b)); return r; }
__device__ __forceinline__ uint32_t min2(uint32_t a, uint32_t b) { uint32_t r; asm("min.bf16x2 %0, %1, %2;" : "=r"(r) : "r"(a), "r"(b)); return r; }
__device__ __forceinline__ void bar_arrive(int id, int n) { asm volatile("bar.arrive %0, %1;" ::"r"(id), "r"(n) : "memory"); }
__device__ __forceinline__ void mbar_arrive_n_if(uint32_t bar, uint32_t n, bool pred) {
    asm volatile("{.reg .pred p; setp.ne.u32 p, %1, 0; @p mbarrier.arrive.shared::cta.b64 _, [%0], %2;}" ::"r"(bar), "r"((uint32_t)pred), "r"(n) : "memory");
}
__device__ __forceinline__ float4 lds_f4(uint32_t a) {
    float4 v;
    asm volatile("ld.shared.v4.f32 {%0,%1,%2,%3}, [%4];" : "=f"(v.x), "=f"(v.y), "=f"(v.z), "=f"(v.w) : "r"(a) : "memory");
    return v;
}
__device__ __forceinline__ void lds_f4_if(float4& v, uint32_t a, bool pred) {
    asm volatile("{.reg .pred p; setp.ne.u32 p, %5, 0; @p ld.shared.v4.f32 {%0,%1,%2,%3}, [%4];}"
                 : "+f"(v.x), "+f"(v.y), "+f"(v.z), "+f"(v.w) : "r"(a), "r"((uint32_t)pred) : "memory");
}
__device__ __forceinline__ uint4 ld_tagged(const unsigned long long* p) {
    unsigned long long a, b;
    asm volatile("ld.acquire.gpu.global.v2.b64 {%0,%1}, [%2];" : "=l"(a), "=l"(b) : "l"(p) : "memory");
    return make_uint4((unsigned)a, (unsigned)(a >> 32), (unsigned)b, (unsigned)(b >> 32));
}
__device__ __forceinline__ uint4 ld_tagged_rlx(const unsigned long long* p) {
    unsigned long long a, b;
    asm volatile("ld.relaxed.gpu.global.v2.b64 {%0,%1}, [%2];" : "=l"(a), "=l"(b) : "l"(p) : "memory");
    return make_uint4((unsigned)a, (unsigned)(a >> 32), (unsigned)b, (unsigned)(b >> 32));
}
__device__ __forceinline__ void sts32(uint32_t a, uint32_t x) { asm volatile("st.shared.u32 [%0], %1;" ::"r"(a), "r"(x) : "memory"); }
__device__ __forceinline__ void fetch_tagged(const unsigned long long* src, uint32_t dst, unsigned epoch) {
    uint4 v;
    uint32_t it = 0;
    while (true) {
        v = ld_tagged_rlx(src);
        if (!__any_sync(0xffffffffu, v.y != epoch || v.w != epoch)) break;
        __nanosleep(60);
        trap_if_gt(++it, 1u << 22);
    }
    sts64(dst, v.x, v.z);
}
__device__ __forceinline__ void st_tagged_if(unsigned long long* p, float a, float b, unsigned tag, bool pred) {
    const unsigned long long t = (unsigned long long)tag << 32;
    asm volatile("{.reg .pred p; setp.ne.u32 p, %3, 0; @p st.relaxed.gpu.global.v2.b64 [%0], {%1,%2};}"
                 ::"l"(p), "l"(t | __float_as_uint(a)), "l"(t | __float_as_uint(b)), "r"((uint32_t)pred) : "memory");
}

__device__ __forceinline__ void store_tile(uint32_t tile_rows, uint4* gdst, const uint32_t* lo, const uint32_t* hi, int lane, uint32_t* ack) {
    const int r = lane & 15;
#pragma unroll
    for (int b = 0; b < 4; b++)
        stsm4(tile_rows + r * 128 + (((2 * b + (lane >> 4)) ^ (r & 7)) << 4), lo[2 * b], hi[2 * b], lo[2 * b + 1], hi[2 * b + 1]);
    fence_async_smem();
    __syncwarp();
#pragma unroll
    for (int i = 0; i < 4; i++) {
        const uint4 v = lds128(tile_rows + i * 512 + lane * 16);
        stg128(gdst + 32 * i, v.x, v.y, v.z, v.w);
    }
#pragma unroll
    for (int i = 0; i < 4; i++) ack[i] = readback(gdst + 32 * i);
}

__device__ __forceinline__ void feature_maps(const uint32_t* a, const uint32_t* wb, float c0, float c1, uint32_t* plus, uint32_t* minus) {
    uint32_t P[16], mx[4], mn[4];
#pragma unroll
    for (int h = 0; h < 4; h++) {
        float p[8];
        mma16816_z(p, a + 4 * h, wb[4 * h], wb[4 * h + 1]);
        mma16816_z(p + 4, a + 4 * h, wb[4 * h + 2], wb[4 * h + 3]);
        P[4 * h] = pack_bf16(p[0], p[2]); P[4 * h + 1] = pack_bf16(p[1], p[3]);
        P[4 * h + 2] = pack_bf16(p[4], p[6]); P[4 * h + 3] = pack_bf16(p[5], p[7]);
        mx[h] = max2(max2(P[4 * h], P[4 * h + 1]), max2(P[4 * h + 2], P[4 * h + 3]));
        mn[h] = min2(min2(P[4 * h], P[4 * h + 1]), min2(P[4 * h + 2], P[4 * h + 3]));
    }
#pragma unroll
    for (int s = 1; s <= 2; s <<= 1) {
        uint32_t tx[4], tn[4];
#pragma unroll
        for (int h = 0; h < 4; h++) { tx[h] = __shfl_xor_sync(0xffffffffu, mx[h], s); tn[h] = __shfl_xor_sync(0xffffffffu, mn[h], s); }
#pragma unroll
        for (int h = 0; h < 4; h++) { mx[h] = max2(mx[h], tx[h]); mn[h] = min2(mn[h], tn[h]); }
    }
#pragma unroll
    for (int h = 0; h < 4; h++) {
        const float mx0 = bf_lo(mx[h]) * c0, mx1 = bf_hi(mx[h]) * c1, mn0 = bf_lo(mn[h]) * c0, mn1 = bf_hi(mn[h]) * c1;
        float ep[8], em[8];
#pragma unroll
        for (int i = 0; i < 8; i++) {
            const bool r1 = (i & 2);
            const uint32_t w = P[4 * h + (i >> 2) * 2 + (i & 1)];
            const float p = r1 ? bf_hi(w) : bf_lo(w);
            ep[i] = ex2(fmaf(p, r1 ? c1 : c0, r1 ? -mx1 : -mx0));
            em[i] = ex2(fmaf(p, r1 ? -c1 : -c0, r1 ? mn1 : mn0));
        }
        float sp[4], sm[4];
        uint32_t tp[4], tm[4];
#pragma unroll
        for (int i = 0; i < 4; i++) { tp[i] = pack_bf16(ep[2 * i], ep[2 * i + 1]); tm[i] = pack_bf16(em[2 * i], em[2 * i + 1]); }
        mma16816_z(sp, tp, 0x3f803f80u, 0x3f803f80u);
        mma16816_z(sm, tm, 0x3f803f80u, 0x3f803f80u);
        const float r0 = rcp(sp[0] * sm[0]), r1 = rcp(sp[2] * sm[2]);
        const float rs[4] = {r0 * sm[0], r1 * sm[2], r0 * sp[0], r1 * sp[2]};
#pragma unroll
        for (int i = 0; i < 4; i++) {
            plus[4 * h + i] = pack_bf16(ep[2 * i] * rs[i & 1], ep[2 * i + 1] * rs[i & 1]);
            minus[4 * h + i] = pack_bf16(em[2 * i] * rs[2 + (i & 1)], em[2 * i + 1] * rs[2 + (i & 1)]);
        }
    }
}

template <bool SCALE>
__device__ __forceinline__ void ln_frag(const float* acc, uint32_t cs_addr, float rs0, float nm0, float rs1, float nm1, uint32_t* a) {
    const float2 c0 = lds_f2(cs_addr), c1 = lds_f2(cs_addr + 32);
    const float s0 = SCALE ? rs0 : 1.f, s1 = SCALE ? rs1 : 1.f;
    a[0] = pack_bf16(fmaf(nm0, c0.x, acc[0]) * s0, fmaf(nm0, c0.y, acc[1]) * s0);
    a[1] = pack_bf16(fmaf(nm1, c0.x, acc[2]) * s1, fmaf(nm1, c0.y, acc[3]) * s1);
    a[2] = pack_bf16(fmaf(nm0, c1.x, acc[4]) * s0, fmaf(nm0, c1.y, acc[5]) * s0);
    a[3] = pack_bf16(fmaf(nm1, c1.x, acc[6]) * s1, fmaf(nm1, c1.y, acc[7]) * s1);
}

template <int UP>
__device__ __forceinline__ uint32_t hh_pair(const float* ag, float4 cs, float nmean) {
    const float g0 = fmaf(nmean, cs.x, ag[0]), g1 = fmaf(nmean, cs.y, ag[1]);
    const float u0 = fmaf(nmean, cs.z, ag[UP]), u1 = fmaf(nmean, cs.w, ag[UP + 1]);
    return pack_bf16(g0 * u0, g1 * u1);
}
template <int NTP>
__device__ __forceinline__ void hh_stage(const float* acc, const float4* cs, float nm0, float nm1, uint32_t stg, int lane) {
#pragma unroll
    for (int tp = 0; tp < NTP; tp++)
        stsm4(stg + (lane & 15) * 128 + (((2 * tp + (lane >> 4)) ^ (lane & 7)) << 4), hh_pair<32>(acc + 8 * tp, cs[2 * tp], nm0),
              hh_pair<32>(acc + 8 * tp + 2, cs[2 * tp], nm1), hh_pair<32>(acc + 8 * tp + 4, cs[2 * tp + 1], nm0),
              hh_pair<32>(acc + 8 * tp + 6, cs[2 * tp + 1], nm1));
    fence_async_smem();
    __syncwarp();
}

template <int TP0, int TP1>
__device__ __forceinline__ void hh_stage2(const float* acc, const float4* cs, float nm0, float nm1, uint32_t stg, int lane) {
#pragma unroll
    for (int tp = TP0; tp < TP1; tp++)
        stsm4(stg + (lane & 15) * 128 + (((2 * tp + (lane >> 4)) ^ (lane & 7)) << 4), hh_pair<32>(acc + 8 * tp, cs[2 * tp], nm0),
              hh_pair<32>(acc + 8 * tp + 2, cs[2 * tp], nm1), hh_pair<32>(acc + 8 * tp + 4, cs[2 * tp + 1], nm0),
              hh_pair<32>(acc + 8 * tp + 6, cs[2 * tp + 1], nm1));
}
struct Ring {
    int slot; uint32_t phase;
    __device__ __forceinline__ void adv() { if (++slot == NB) { slot = 0; phase ^= 1; } }
    __device__ __forceinline__ void adv5() { slot += slot == 3; adv(); }
};

__global__ void __cluster_dims__(2, 1, 1) __launch_bounds__(NTHREADS, 1) fused_kernel(const __grid_constant__ Params P) {
    extern __shared__ __align__(1024) uint8_t smem_raw[];
    const uint32_t sb = smem_u32(smem_raw);
    const int tid = threadIdx.x, lane = tid & 31;
    if (tid >= 256 && tid < 258) prefetch_tmap(&P.tx + (tid & 1));
    const int warp = __shfl_sync(0xffffffffu, tid >> 5, 0);
    const unsigned role = P.role[blockIdx.x], rank = blockIdx.x & 1;
    const int m = role >> 3, j = role & 7;
    const bool helper = role >= 128;

    TL(0, tid == 0); TLG(0, tid == 0);
    float* const acc_j = g_acc + j * ACC_SIZE;

    if (__builtin_expect(warp >= 8, 1)) {
        asm volatile("setmaxnreg.dec.sync.aligned.u32 72;");
        if (elect_one()) {
            if (warp == 8) {
                if (!helper) {
#pragma unroll
                    for (int i = 0; i < NB; i++) mbar_init(sb + BAR_FULLB + 8 * i, 1);
#pragma unroll
                    for (int i = 0; i < 2; i++) {
                        mbar_expect_tx(sb + BAR_FULLB + 8 * i, SLOT);
                        tma2d(sb + OFF_B + i * SLOT, &P.twq, sb + BAR_FULLB + 8 * i, DM + 64 * j, 64 * i);
                        tma2d(sb + OFF_B + i * SLOT + 8192, &P.twq, sb + BAR_FULLB + 8 * i, 2 * DM + 64 * j, 64 * i);
                    }
                }
            } else if (warp == 9) {
#pragma unroll
                for (int i = 0; i < 8; i++) mbar_init(sb + BAR_FULLA + 8 * i, 1);
                if (!helper) {
#pragma unroll
                    for (int i = 0; i < 2; i++) {
                        mbar_expect_tx(sb + BAR_FULLA + 8 * i, SLOT);
                        tma2d(sb + OFF_A + i * SLOT, &P.tx, sb + BAR_FULLA + 8 * i, 64 * i, 128 * m);
                    }
                }
            } else if (warp == 10) {
#pragma unroll
                for (int i = 0; i < 12; i++) mbar_init(sb + BAR_CS1 + 8 * i, i < 2 || i >= 8 ? 64 : (i < 4 ? 32 : 8));
                trap_if_gt(sb & 1023, 0);
            } else {
#pragma unroll
                for (int i = 0; i < 14; i++) mbar_init(sb + (i < 8 ? BAR_EMPTYA : BAR_EMPTYB - 64) + 8 * i, i < 8 ? 8 : 16);
            }
            asm volatile("fence.mbarrier_init.release.cluster;" ::: "memory");
        }
        __syncwarp();
        asm volatile("barrier.cluster.arrive.relaxed.aligned;" ::: "memory");
        const unsigned epoch = ld_relaxed(&g_epoch);
        bar_sync(0, NTHREADS);
        if (helper) {
            if (elect_one()) {
#pragma unroll 1
                for (int i = warp - 8; i < 72; i += 4) {
                    const uint32_t full = sb + BAR_FULLA + 8 * (i & 7), dst = sb + OFF_A + (i & 7) * SLOT;
                    const int n = i >> 1, jj = 2 * j + (i & 1);
                    const bool qkv = n < 12;
                    const int c0 = qkv ? (n < 8 ? DM + 128 * (n & 4) : 0) + 64 * jj : 176 * jj + 8 * ((n - 12) & ~7);
                    const int r0 = qkv ? 128 * (n & 3) : 64 * ((n - 12) & 7);
                    mbar_wait(sb + BAR_EMPTYA + 8 * (i & 7), ((i >> 3) & 1) ^ 1);
                    mbar_expect_tx(full, SLOT);
                    tma2d(dst, qkv ? &P.twq : &P.twg, full, c0, r0);
                    tma2d(dst + 8192, qkv ? &P.twq : &P.twu, full, c0, qkv ? r0 + 64 : r0);
                }
                prefetch_l2(P.wd + (size_t)(4 * j + warp - 8) * 44032, 88064);
            }
            return;
        }
        if (warp == 8) {
            asm volatile("barrier.cluster.wait.aligned;" ::: "memory");
            if (elect_one()) {
                if (m >= 6)
                    asm volatile("cp.async.bulk.prefetch.tensor.2d.L2.global [%0, {%1, %2}];" ::"l"(&P.twq), "r"(DM + DM * (m & 1) + 64 * j), "r"(64 * (m >> 1)) : "memory");
                if (j >= 3)
                    asm volatile("cp.async.bulk.prefetch.tensor.2d.L2.global [%0, {%1, %2}];" ::"l"(&P.tx), "r"(64 * j), "r"(128 * m) : "memory");
                Ring r{2, 0};
                const uint32_t dst = sb + OFF_B + rank * 8192;
#define B_LOAD(TM, C0, R0)                                                                                  \
        mbar_waitc(sb + BAR_EMPTYB + 8 * r.slot, r.phase ^ 1);                                              \
        mbar_expect_tx(sb + BAR_FULLB + 8 * r.slot, SLOT);                                                  \
        tma2d_mc(dst + r.slot * SLOT, TM, sb + BAR_FULLB + 8 * r.slot, C0, R0);
#pragma unroll 1
                for (int i = 2; i < 8; i++) {
                    if (i >= AHEAD && i < 6) mbar_waitc(sb + BAR_FULLB + 8 * (i - AHEAD), 0);
                    B_LOAD(&P.twq, DM + DM * rank + 64 * j, 64 * i)
                    r.adv();
                }
#pragma unroll 1
                for (int i = 8; i < 20; i++) {
                    if (i < 12) {
                        mbar_waitc(sb + BAR_EMPTYB + 8 * r.slot, r.phase ^ 1);
                        mbar_arrive(sb + BAR_FULLB + 8 * r.slot);
                    } else {
                        const int e = 2 * (i & 3) + rank;
                        B_LOAD(i < 16 ? &P.twq : &P.two, 64 * j, 64 * (i < 16 ? e : KORD(e, j)))
                    }
                    r.adv();
                }
#pragma unroll 1
                for (int i = 0; i < 24; i++) {
                    B_LOAD(&P.twg + rank, 176 * j + 8 * (i & ~7), 64 * (i < 8 ? KORD(i, j) : i & 7))
                    r.adv5();
                }
#pragma unroll 1
                for (int i = 0; i < 12; i++) {
                    B_LOAD(&P.twd, 64 * j, 176 * (2 * (i & 3) + rank) + 64 * (i >> 2))
                    r.adv5();
                }
            }
            return;
        }
        if (warp == 9) {
            if (elect_one()) {
#pragma unroll 1
                for (int i = 2; i < 8; i++) {
                    if (i >= AHEAD + 1) mbar_wait(sb + BAR_FULLA + 8 * (i - AHEAD - 1), 0);
                    mbar_expect_tx(sb + BAR_FULLA + 8 * i, SLOT);
                    tma2d(sb + OFF_A + i * SLOT, &P.tx, sb + BAR_FULLA + 8 * i, 64 * i, 128 * m);
                }
#pragma unroll 1
                for (int i = 2; i < 7; i++) prefetch_tmap(&P.tx + i);
                unsigned nf = 0;
#pragma unroll 1
                for (int r = 1; r < 6; r++) {
                    const int skip = r < 3 ? j : 8;
                    const uint4* src = g_act + ((r - 1) * 128 + m * 8) * 1024;
                    const unsigned* fl = g_flag + (m * 5 + r - 1) * 32;
                    if (r < 4) mbar_wait(sb + BAR_EMPTYA + 8 * (r == 3 ? PF_DELAY : (j ^ 2)), (r - 1) & 1);
                    if (r < 4 || nf != epoch * 8) wait_count(fl, epoch * (r < 3 ? 64 : 8));
                    TL(64 + r, true);
#pragma unroll 1
                    for (int t = 0; t < 8; t++) {
                        if (t == skip) continue;
                        if (t == 6) nf = readback(fl + 32);
                        mbar_wait(sb + BAR_EMPTYA + 8 * t, (r - 1) & 1);
                        mbar_expect_tx(sb + BAR_FULLA + 8 * t, SLOT);
                        asm volatile("cp.async.bulk.shared::cluster.global.mbarrier::complete_tx::bytes [%0], [%1], %2, [%3];"
                                     ::"r"(sb + OFF_A + t * SLOT), "l"(src + t * 1024), "r"(SLOT), "r"(sb + BAR_FULLA + 8 * t) : "memory");
                    }
                }
            }
            return;
        }
        const int a = warp - 10;
        {
            const int row = 16 * j + 8 * a + (lane >> 2);
            const uint32_t ra = sb + OFF_A + row * 128;
            float sh = 0.f, s0 = 0.f, s1 = 0.f, q0 = 0.f, q1 = 0.f;
#pragma unroll 1
            for (int kt = 0; kt < 8; kt++) {
                mbar_wait(sb + BAR_FULLA + 8 * kt, 0);
                if (kt == 0) sh = bf_lo(lds128(ra + ((row & 7) << 4)).x);
#pragma unroll
                for (int i = 0; i < 2; i++) {
                    const uint4 v = lds128(ra + kt * SLOT + (((2 * (lane & 3) + i) ^ (row & 7)) << 4));
                    const uint32_t ww[4] = {v.x, v.y, v.z, v.w};
#pragma unroll
                    for (int e = 0; e < 4; e++) {
                        const float d0 = bf_lo(ww[e]) - sh, d1 = bf_hi(ww[e]) - sh;
                        s0 += d0; q0 = fmaf(d0, d0, q0);
                        s1 += d1; q1 = fmaf(d1, d1, q1);
                    }
                }
            }
            s0 += s1; q0 += q1;
#pragma unroll
            for (int o = 1; o <= 2; o <<= 1) { s0 += __shfl_xor_sync(0xffffffffu, s0, o); q0 += __shfl_xor_sync(0xffffffffu, q0, o); }
            const float md = s0 * (1.f / DM);
            const float rs = rsqrtf(fmaxf(q0 * (1.f / DM) - md * md, 0.f) + 1e-5f);
            st_tagged_if(g_xstat + 2 * (128 * m + row), rs, -(sh + md), epoch, (lane & 3) == 0);
            TL(1, lane == 0 && a == 0);
        }
        const unsigned long long* cs = g_cs + j * 768 + 2 * lane;
        {
            const unsigned long long* xs = g_xstat + 2 * (128 * m + 64 * a + lane);
            uint4 v0, v1, v2;
            uint32_t it = 0;
            do {
                v0 = ld_tagged_rlx(xs); v1 = ld_tagged_rlx(xs + 64); v2 = ld_tagged_rlx(cs + 128 * a);
                trap_if_gt(++it, 1u << 22);
            } while (__any_sync(0xffffffffu, v0.y != epoch || v0.w != epoch || v1.y != epoch || v1.w != epoch || v2.y != epoch || v2.w != epoch));
            sts64(sb + OFF_XST + (64 * a + lane) * 8, v0.x, v0.z);
            sts64(sb + OFF_XST + (64 * a + 32 + lane) * 8, v1.x, v1.z);
            sts64(sb + OFF_CS1 + 256 * (a + 1) + 8 * lane, v2.x, v2.z);
            mbar_arrive(sb + BAR_CS1);
            TL(22 + a, lane == 0);
            if (a) {
                fetch_tagged(cs + 256, sb + OFF_CS1 + 8 * lane, epoch);
                mbar_arrive(sb + BAR_CSQ);
                TL(24, lane == 0);
            }
        }
        {
            mbar_wait(sb + BAR_KVW, 0);
            const float* src = acc_j + 4 * (128 * a + lane);
            float4 v[12];
            uint32_t it = 0;
            bool bad;
            while (__any_sync(0xffffffffu, readback(acc_j + 2048 + 128 * (lane & 7) + 127) != 0x41800000u)) trap_if_gt(++it, 1u << 22);
            TL(19, lane == 0 && a == 0);
            do {
                bad = false;
#pragma unroll
                for (int i = 0; i < 12; i++) v[i] = ld_l2_f4(src + 1024 * (i % 3) + 128 * (i / 3));
#pragma unroll
                for (int i = 0; i < 12; i++) bad |= v[i].w != 16.f;
                trap_if_gt(++it, 1u << 22);
            } while (__any_sync(0xffffffffu, bad));
            TL(14, lane == 0 && a == 0);
            mbar_wait(sb + BAR_EMPTYB, 0);
            const uint32_t d0 = sb + OFF_A + (j ^ 1) * SLOT + (64 * a + (lane >> 2)) * 48;
            const uint32_t d = d0 + (lane & 3) * 4, dz = d0 + (lane & 1) * 384 + 32 + (lane & 2) * 4;
#pragma unroll
            for (int u = 0; u < 4; u++) {
                sts32(d + 768 * u, pack_bf16(v[3 * u].x, v[3 * u].y));
                sts32(d + 768 * u + 384, pack_bf16(v[3 * u].z, v[3 * u + 1].z));
                sts32(d + 768 * u + 16, pack_bf16(v[3 * u + 1].x, v[3 * u + 1].y));
                sts32(d + 768 * u + 400, pack_bf16(v[3 * u + 2].x, v[3 * u + 2].y));
                const uint32_t z2 = pack_bf16(v[3 * u + 2].z, v[3 * u + 2].z);
                sts64(dz + 768 * u, z2, z2);
            }
            mbar_arrive(sb + BAR_KVR);
        }
#pragma unroll 1
        for (int c = 0; c < 3; c++) {
            fetch_tagged(cs + 384 + 128 * c + 64 * a, sb + OFF_CS3 + (32 * c + lane) * 16 + 8 * a, epoch);
            mbar_arrive(sb + BAR_CSG + 8 * c);
            TL(45 + c, lane == 0 && a == 0);
        }
        {
            uint32_t it = 0;
            while (__any_sync(0xffffffffu, (int)(readback(g_flag + (m * 5 + 1) * 32) - epoch * 64) < 0)) {
                __nanosleep(200);
                trap_if_gt(++it, 1u << 22);
            }
#pragma unroll 1
            for (int rr = 0; rr < 2; rr++) {
                const int row = 64 * rr + 32 * a + lane;
                const unsigned long long* hs = g_hstat + (1024 * m + row) * 2;
                uint4 v[8];
                bool bad;
                do {
                    bad = false;
#pragma unroll
                    for (int i = 0; i < 8; i++) v[i] = ld_tagged_rlx(hs + 256 * i);
#pragma unroll
                    for (int i = 0; i < 8; i++) bad |= v[i].y != epoch || v[i].w != epoch;
                    trap_if_gt(++it, 1u << 22);
                } while (__any_sync(0xffffffffu, bad));
                float mean = 0.f;
#pragma unroll
                for (int i = 0; i < 8; i++) mean += __uint_as_float(v[i].x);
                mean *= 0.125f;
                float m2 = 0.f, dv = 0.f;
#pragma unroll
                for (int i = 0; i < 8; i++) { const float d = __uint_as_float(v[i].x) - mean; m2 += __uint_as_float(v[i].z); dv = fmaf(d, d, dv); }
                sts_f2(sb + OFF_CS1 + row * 8, -mean, rcp(fmaf(dv, 64.f, m2) * (1.f / DM) + 1e-5f));
            }
        }
        mbar_arrive(sb + BAR_CS3);
#pragma unroll 1
        for (int c = a; c < 3; c += 2) {
            mbar_wait(sb + BAR_STG + 8 * c, 0);
            if (elect_one()) {
                asm volatile("cp.async.bulk.global.shared::cta.bulk_group [%0], [%1], %2;" ::"l"(g_act + ((2 + c) * 128 + role) * 1024), "r"(sb + OFF_B + 4 * SLOT), "r"(SLOT) : "memory");
                asm volatile("cp.async.bulk.commit_group;" ::: "memory");
                asm volatile("cp.async.bulk.wait_group.read 0;" ::: "memory");
                mbar_arrive(sb + BAR_FULLB + 8 * 4);
                asm volatile("cp.async.bulk.wait_group 0;" ::: "memory");
            }
            __syncwarp();
            TL(60 + c, lane == 0);
            uint32_t ack = 0;
            const uint4* rb = g_act + ((2 + c) * 128 + role) * 1024 + lane * 8;
#pragma unroll
            for (int i = 0; i < 4; i++) ack |= readback(rb + 256 * i);
            signal_after(g_flag + (m * 5 + 2 + c) * 32, ack, P.zero, lane == 0);
            TL(54 + c, lane == 0);
        }
        return;
    }
    const unsigned epoch = ld_relaxed(&g_epoch);
    uint32_t wraw[16];
    if (!helper) {
        const uint32_t* wp = reinterpret_cast<const uint32_t*>(P.wphi) + (4 * j) * 128 + (lane & 3) * 16 + (lane >> 2);
#pragma unroll
        for (int i = 0; i < 16; i++)
            asm volatile("ld.global.nc.u32 %0, [%1];" : "=r"(wraw[i]) : "l"(wp + (i >> 2) * 128 + ((i >> 1) & 1) * 64 + (i & 1) * 8));
    }
    asm volatile("barrier.cluster.arrive.relaxed.aligned;" ::: "memory");
    asm volatile("setmaxnreg.inc.sync.aligned.u32 216;");
    bar_sync(0, NTHREADS);
    if (helper) {
        const int w = warp >> 2;
        sts64(sb + OFF_B + 8 * tid, 0x3f803f80u, 0x3f803f80u);
        {
            float* z = g_acc + 2 * j * ACC_SIZE + 4 * tid;
            uint32_t ack = 0;
#pragma unroll
            for (int u = 0; u < 6; u++) stg128(z + 1024 * u, 0, 0, 0, 0);
#pragma unroll
            for (int u = 0; u < 6; u++) ack |= readback(z + 1024 * u);
            trap_if_gt(ack, 0);
        }
        fence_async_smem();
        bar_sync(1, 256);
        TL(70, tid == 0);
        float acc[8];
        int i = w;
#pragma unroll 1
        for (int job = 0; job < 6; job++) {
            const int n = job < 3 ? 4 : 8;
#pragma unroll 1
            for (int t = 0; t < n; t++, i += 2) {
                mbar_waitc(sb + BAR_FULLA + 8 * (i & 7), (i >> 3) & 1);
                const desc_t da = desc_lo(sb + OFF_A) + (i & 7) * (SLOT >> 4);
                wg_fence();
#pragma unroll
                for (int k = 0; k < 8; k++) wgmma_n8_tt(acc + (k & 4), da + 128 * k, desc_lo(sb + OFF_B), (t | (k & 3)) != 0);
                wg_commit();
                wg_wait<0>();
                mbar_arrive_n_if(sb + BAR_EMPTYA + 8 * (i & 7), 2, lane == 0);
            }
            fence_acc<8>(acc);
            TL(71 + job, tid == 0);
            const int q = lane & 3;
            const float lo = (q & 1) ? acc[2] : acc[0], hi = (q & 1) ? acc[6] : acc[4];
            const float v = job < 3 ? lo + hi : ((q & 2) ? hi : lo);
            unsigned long long* dst = g_cs + ((2 * j + w) * 6 + job) * 128 + (q >> 1) * 64 + 16 * (warp & 3) + 8 * (q & 1) + (lane >> 2);
            asm volatile("st.relaxed.gpu.global.b64 [%0], %1;" ::"l"(dst), "l"(((unsigned long long)epoch << 32) | __float_as_uint(v)) : "memory");
        }
        return;
    }
    {
        const int w = warp >> 2, wv = warp & 3, g = lane >> 2, q = lane & 3;
        const uint32_t sa = sb + OFF_A + w * 8192;
        const desc_t dA = desc_lo(sa), dB = desc_lo(sb + OFF_B);
        unsigned* const flag_m = g_flag + m * 160;
        const bool l0 = lane == 0, l2 = lane < 2;
        const uint32_t eb = mapa(sb + BAR_EMPTYB, lane & 1);
        asm volatile("barrier.cluster.wait.aligned;" ::: "memory");
        Ring rg{0, 0};
        int prev = 0;

        uint32_t wb[16];
        constexpr float L2E = 1.4426950408889634f;
        const int ch = lane >> 4, sw = lane & 7;
        const uint32_t lrow = (lane & 15) * 128;
        uint32_t fp[16], fm[16];
        {
            float acc[64];
#pragma unroll 1
            for (int kt = 0; kt < 8; kt++) {
                mbar_waitc(sb + BAR_FULLA + 8 * kt, 0);
                mbar_waitc(sb + BAR_FULLB + 8 * rg.slot, rg.phase);
                const desc_t da = dA + kt * (SLOT >> 4), db = dB + rg.slot * (SLOT >> 4);
                wg_fence();
#pragma unroll
                for (int k = 0; k < 4; k++) wgmma_n128(acc, da + 2 * k, db + 128 * k, (kt | k) != 0);
                wg_commit();
                wg_wait<1>();
                mbar_arrive_cl_if(eb + 8 * prev, l2 && kt > 0);
                prev = rg.slot; rg.adv();
            }
#pragma unroll
            for (int i = 0; i < 8; i++) {
                wb[(i >> 1) * 4 + (i & 1)] = __byte_perm(wraw[2 * i], wraw[2 * i + 1], 0x5410);
                wb[(i >> 1) * 4 + 2 + (i & 1)] = __byte_perm(wraw[2 * i], wraw[2 * i + 1], 0x7632);
            }
            uint32_t a[16];
#pragma unroll
            for (int i = 2; i < 6; i++) mbar_waitc(sb + BAR_FULLB + 8 * i, 1);
            TL(17, tid == 0);
            mbar_waitc(sb + BAR_CS1, 0);
            const float2 s0 = lds_f2(sb + OFF_XST + (16 * warp + g) * 8), s1 = lds_f2(sb + OFF_XST + (16 * warp + g + 8) * 8);
            wg_wait<0>();
            fence_acc<64>(acc);
            mbar_arrive_cl_if(eb + 8 * prev, l2);
            TL(2, tid == 0);
            const uint32_t st = sb + OFF_B + 2 * SLOT + warp * 2048 + lrow;
#pragma unroll
            for (int hh = 0; hh < 4; hh++) {
                ln_frag<true>(acc + 32 + 8 * hh, sb + OFF_CS1 + (128 + 16 * hh + 2 * q) * 4, s0.x, s0.y, s1.x, s1.y, a);
                stsm4(st + (2 + (hh >> 1)) * SLOT + (((2 * (hh & 1) + ch) ^ sw) << 4), a[0], a[1], a[2], a[3]);
            }
            stsm4(st + (2 + ch) * SLOT + ((4 ^ sw) << 4), 0x3f803f80u, 0x3f803f80u, 0x3f803f80u, 0x3f803f80u);
#pragma unroll
            for (int hh = 0; hh < 4; hh++)
                ln_frag<false>(acc + 8 * hh, sb + OFF_CS1 + (64 + 16 * hh + 2 * q) * 4, 0.f, s0.y, 0.f, s1.y, a + 4 * hh);
#pragma unroll 1
            for (int it = 0; it < 2; it++) {
                feature_maps(a, wb, s0.x * L2E, s1.x * L2E, fp, fm);
                if (it == 0) {
#pragma unroll
                    for (int hh = 0; hh < 4; hh++) {
                        stsm4(st + (hh >> 1) * SLOT + (((4 * (hh & 1) + ch) ^ sw) << 4), fp[4 * hh], fp[4 * hh + 1], fp[4 * hh + 2], fp[4 * hh + 3]);
                        stsm4(st + (hh >> 1) * SLOT + (((4 * (hh & 1) + 2 + ch) ^ sw) << 4), fm[4 * hh], fm[4 * hh + 1], fm[4 * hh + 2], fm[4 * hh + 3]);
                    }
                    fence_async_smem();
                    bar_sync(1, 256);
                    float kvd[20];
                    wg_fence();
#pragma unroll
                    for (int k = 0; k < 8; k++)
                        wgmma_n40_tt(kvd, dB + (2 + w) * (SLOT >> 4) + 128 * k, dB + (4 + w) * (SLOT >> 4) + 128 * k, k != 0);
                    wg_commit();
                    wg_wait<0>();
                    fence_acc<20>(kvd);
                    mbar_arrive_cl_if(eb + 8 * (2 + (lane >> 1)), lane < 8);
                    const bool h1 = wv >= 2;
                    float* kvp = acc_j + 4 * tid;
                    red_f32x4(kvp, h1 ? kvd[8] : kvd[0], h1 ? kvd[9] : kvd[1], h1 ? kvd[10] : kvd[2], 1.f);
                    red_f32x4(kvp + 1024, h1 ? kvd[12] : kvd[4], h1 ? kvd[13] : kvd[5], h1 ? kvd[11] : kvd[3], 1.f);
                    red_f32x4(kvp + 2048, h1 ? kvd[14] : kvd[6], h1 ? kvd[15] : kvd[7], (q & 1) ? kvd[18] : kvd[16], 1.f);
                    mbar_arrive_if(sb + BAR_KVW, l0);
                    TL(3, tid == 0);
                    float accq[32];
#pragma unroll 1
                    for (int b = 0; b < 4; b++) {
                        mbar_waitc(sb + BAR_FULLB + 8 * b, 0);
                        const desc_t da = dA + b * (2 * SLOT >> 4), db = dB + b * (SLOT >> 4);
                        wg_fence();
#pragma unroll
                        for (int k = 0; k < 8; k++) wgmma_n64(accq, da + (k >> 2) * (SLOT >> 4) + (k & 3) * 2, db + 128 * k, (b | k) != 0);
                        wg_commit();
                    }
                    mbar_waitc(sb + BAR_CSQ, 0);
                    wg_wait<0>();
                    fence_acc<32>(accq);
                    mbar_arrive_cl_if(eb + 8 * (lane >> 1), lane < 8);
                    TL(4, tid == 0);
#pragma unroll
                    for (int hh = 0; hh < 4; hh++)
                        ln_frag<false>(accq + 8 * hh, sb + OFF_CS1 + (16 * hh + 2 * q) * 4, 0.f, s0.y, 0.f, s1.y, a + 4 * hh);
                }
            }
        }
        uint32_t res_lo[8], res_hi[8], ack[4];
        const uint32_t own_rows = sb + OFF_A + j * SLOT + warp * 2048;
#pragma unroll
        for (int b = 0; b < 4; b++)
            ldsm4(own_rows + lrow + (((2 * b + ch) ^ sw) << 4), res_lo[2 * b], res_hi[2 * b], res_lo[2 * b + 1], res_hi[2 * b + 1]);
        mbar_arrive_if(sb + BAR_EMPTYA + 8 * lane, lane < 8 && (lane | 1) != (j | 1));
        TL(5, tid == 0);
        mbar_waitc(sb + BAR_KVR, 0);
        TL(6, tid == 0);
        {
            const uint32_t kvs = sb + OFF_A + (j ^ 1) * SLOT;
            uint32_t o_lo[8], o_hi[8];
#pragma unroll
            for (int hh = 0; hh < 4; hh++) {
                uint32_t b[8], zb[4];
                const uint32_t base = kvs + hh * 32 * 48;
                ldsm4t(base + (lane & 15) * 48 + (lane >> 4) * 16, b[0], b[1], b[2], b[3]);
                ldsm4t(base + (16 + (lane & 15)) * 48 + (lane >> 4) * 16, b[4], b[5], b[6], b[7]);
                ldsm4t(base + lane * 48 + 32, zb[0], zb[1], zb[2], zb[3]);
                float n0[4], n1[4], dn[4];
                mma16816_z(n0, fp + 4 * hh, b[0], b[1]); mma16816_z(n1, fp + 4 * hh, b[2], b[3]); mma16816_z(dn, fp + 4 * hh, zb[0], zb[1]);
                mma16816(n0, fm + 4 * hh, b[4], b[5]); mma16816(n1, fm + 4 * hh, b[6], b[7]); mma16816(dn, fm + 4 * hh, zb[2], zb[3]);
                const float i0 = rcp(dn[0] + 1e-6f), i1 = rcp(dn[2] + 1e-6f);
                o_lo[2 * hh] = pack_bf16(n0[0] * i0, n0[1] * i0); o_hi[2 * hh] = pack_bf16(n0[2] * i1, n0[3] * i1);
                o_lo[2 * hh + 1] = pack_bf16(n1[0] * i0, n1[1] * i0); o_hi[2 * hh + 1] = pack_bf16(n1[2] * i1, n1[3] * i1);
            }
            __syncwarp();
            mbar_arrive_if(sb + BAR_EMPTYA + 8 * (j ^ 1), l0);
            rg.slot = 4; rg.phase = 0;
            store_tile(own_rows, g_act + role * 1024 + warp * 128 + lane, o_lo, o_hi, lane, ack);
            TL(7, tid == 0);
        }
        float acch[32];
        {
            float* acc = acch;
#pragma unroll
            for (int t = 0; t < 8; t++) {
                acc[4 * t] = bf_lo(res_lo[t]); acc[4 * t + 1] = bf_hi(res_lo[t]);
                acc[4 * t + 2] = bf_lo(res_hi[t]); acc[4 * t + 3] = bf_hi(res_hi[t]);
            }
            fence_acc<32>(acc);
            int pa = 0;
#pragma unroll 1
            for (int kp = 0; kp < 4; kp++) {
                mbar_waitc(sb + BAR_FULLB + 8 * rg.slot, rg.phase);
#pragma unroll
                for (int hf = 0; hf < 2; hf++) {
                    const int i = 2 * kp + hf, kt = KORD(i, j);
                    mbar_waitc(sb + BAR_FULLA + 8 * kt, i != 0);
                    TL(8, i == 1 && tid == 0);
                    const desc_t da = dA + kt * (SLOT >> 4), db = dB + rg.slot * (SLOT >> 4);
                    wg_fence();
#pragma unroll
                    for (int k = 0; k < 4; k++) wgmma_n64(acc, da + 2 * k, db + (hf * 4 + k) * 128, 1);
                    wg_commit();
                    wg_wait<1>();
                    mbar_arrive_if(sb + BAR_EMPTYA + 8 * pa, l0 && i > 1);
                    if (hf == 0) {
                        mbar_arrive_cl_if(eb + 8 * prev, l2 && i > 0);
                        if (i == 0) { signal_late(flag_m, ack, P.zero, l0); TL(20, tid == 0); }
                    }
                    pa = kt;
                }
                prev = rg.slot; rg.adv();
            }
            wg_wait<0>();
            fence_acc<32>(acc);
            mbar_arrive_if(sb + BAR_EMPTYA + 8 * pa, l0);
            mbar_arrive_cl_if(eb + 8 * prev, l2);
            TL(9, tid == 0);
#pragma unroll
            for (int t = 0; t < 8; t++) {
                res_lo[t] = pack_bf16(acc[4 * t], acc[4 * t + 1]);
                res_hi[t] = pack_bf16(acc[4 * t + 2], acc[4 * t + 3]);
            }
            store_tile(own_rows, g_act + (128 + role) * 1024 + warp * 128 + lane, res_lo, res_hi, lane, ack);
            TL(10, tid == 0);
        }
        float acc0[64], acc1[64], acc2[56], nm0, nm1;
        float4 cs[8];
        uint32_t hr[16];
#define P3_GROUP(MMA, ACC, KT)                                                                              \
        mbar_waitc(sb + BAR_FULLB + 8 * rg.slot, rg.phase);                                                 \
        {                                                                                                   \
            const desc_t da = dA + (KT) * (SLOT >> 4), db = dB + rg.slot * (SLOT >> 4);                     \
            wg_fence();                                                                                     \
            _Pragma("unroll") for (int k = 0; k < 4; k++) MMA(ACC, da + 2 * k, db + 128 * k, (i | k) != 0); \
            wg_commit();                                                                                    \
        }
#define P3_CS(C, NT)    \
        _Pragma("unroll") for (int t = 0; t < (NT); t++) lds_f4_if(cs[t], sb + OFF_CS3 + q * 16 + 512 * (C) + 64 * t, i == t);
#define P3_EPI2(C, ACC)                                                                                     \
        if (i == 0) {                                                                                       \
            fence_acc<64>(ACC);                                                                             \
            if (C) mbar_waitc(sb + BAR_FULLB + 8 * 4, 1);                                                   \
            hh_stage2<0, 2>(ACC, cs, nm0, nm1, stg, lane);                                                  \
            mbar_waitc(sb + BAR_CSG + 8 * (C) + 8, 0);                                                      \
        }                                                                                                   \
        if (i == 1) {                                                                                       \
            hh_stage2<2, 4>(ACC, cs, nm0, nm1, stg, lane);                                                  \
            fence_async_smem();                                                                             \
            __syncwarp();                                                                                   \
            mbar_arrive_if(sb + BAR_STG + 8 * (C), l0);                                                     \
        }
#define P3_EPI(C, ACC, N, NTP)                                                                              \
        fence_acc<N>(ACC);                                                                                  \
        TL(11 + (C), tid == 0);                                                                             \
        hh_stage<NTP>(ACC, cs, nm0, nm1, sb + OFF_B + 4 * SLOT + warp * 2048, lane);                        \
        mbar_arrive_if(sb + BAR_STG + 8 * (C), l0);                                                         \
        TL(50 + (C), tid == 0);
        const uint32_t stg = sb + OFF_B + 4 * SLOT + warp * 2048;
        const uint32_t blk = ((lane & 7) + (lane >> 4) * 8) * 128 + (((2 * wv + ((lane >> 3) & 1)) ^ (lane & 7)) << 4);
#pragma unroll 1
        for (int i = 0; i < 8; i++) {
            const int kt = KORD(i, j);
            mbar_waitc(sb + BAR_FULLA + 8 * kt, 0);
            TL(44, tid == 0 && i == 1);
            P3_GROUP(wgmma_n128, acc0, kt)
            if (i == 7) {
                mbar_waitc(sb + BAR_CS3, 0);
                nm0 = lds_f2(sb + OFF_CS1 + (16 * warp + g) * 8).x; nm1 = lds_f2(sb + OFF_CS1 + (16 * warp + g + 8) * 8).x;
            }
            wg_wait<1>();
            mbar_arrive_cl_if(eb + 8 * prev, l2 && i > 0);
            if (i == 0) {
                signal_late(flag_m + 32, ack, P.zero, l0);
                TL(21, tid == 0);
                {
                    fence_acc<32>(acch);
                    const float* acc = acch;
                    float s0 = 0.f, s1 = 0.f;
#pragma unroll
                    for (int t = 0; t < 8; t++) { s0 += acc[4 * t] + acc[4 * t + 1]; s1 += acc[4 * t + 2] + acc[4 * t + 3]; }
            s0 += __shfl_xor_sync(0xffffffffu, s0, 1); s1 += __shfl_xor_sync(0xffffffffu, s1, 1);
            s0 += __shfl_xor_sync(0xffffffffu, s0, 2); s1 += __shfl_xor_sync(0xffffffffu, s1, 2);
            const float mu0 = s0 * (1.f / 64), mu1 = s1 * (1.f / 64);
            float q0 = 0.f, q1 = 0.f;
#pragma unroll
            for (int t = 0; t < 8; t++) {
                float d;
                d = acc[4 * t] - mu0; q0 = fmaf(d, d, q0);
                d = acc[4 * t + 1] - mu0; q0 = fmaf(d, d, q0);
                d = acc[4 * t + 2] - mu1; q1 = fmaf(d, d, q1);
                d = acc[4 * t + 3] - mu1; q1 = fmaf(d, d, q1);
            }
            q0 += __shfl_xor_sync(0xffffffffu, q0, 1); q1 += __shfl_xor_sync(0xffffffffu, q1, 1);
            q0 += __shfl_xor_sync(0xffffffffu, q0, 2); q1 += __shfl_xor_sync(0xffffffffu, q1, 2);
            st_tagged_if(g_hstat + (role * 128 + 16 * warp + g + 8 * (q & 1)) * 2, q ? mu1 : mu0, q ? q1 : q0, epoch, q < 2);
                }
                bar_sync(2 + w, 128);
#pragma unroll
                for (int tp = 0; tp < 4; tp++) ldsm4t(sa + j * SLOT + blk + tp * 2048, hr[4 * tp], hr[4 * tp + 1], hr[4 * tp + 2], hr[4 * tp + 3]);
                mbar_waitc(sb + BAR_CSG, 0);
#pragma unroll
                for (int t = 0; t < 8; t++) cs[t] = lds_f4(sb + OFF_CS3 + q * 16 + 64 * t);
            }
            prev = rg.slot; rg.adv5();
        }
#pragma unroll 1
        for (int i = 0; i < 8; i++) {
            P3_GROUP(wgmma_n128, acc1, i)
            wg_wait<1>();
            mbar_arrive_cl_if(eb + 8 * prev, l2);
            P3_EPI2(0, acc0)
            P3_CS(1, 8)
            prev = rg.slot; rg.adv5();
        }
#pragma unroll 1
        for (int i = 0; i < 8; i++) {
            P3_GROUP(wgmma_n112, acc2, i)
            wg_wait<1>();
            mbar_arrive_cl_if(eb + 8 * prev, l2);
            mbar_arrive_if(sb + BAR_EMPTYA + 8 * ((i + 7) & 7), l0 && i > 0);
            if (i == 0) { mbar_waitc(sb + BAR_FULLB + 8 * 4, 1); P3_EPI(1, acc1, 64, 4) mbar_waitc(sb + BAR_CSG + 16, 0); }
            P3_CS(2, 6)
            prev = rg.slot; rg.adv5();
        }
        mbar_waitc(sb + BAR_FULLB + 8 * 4, 0);
        wg_wait<0>();
        mbar_arrive_cl_if(eb + 8 * prev, l2);
        mbar_arrive_if(sb + BAR_EMPTYA + 8 * 7, l0);
        P3_EPI(2, acc2, 56, 3)
        {
            float acc[64];
            const desc_t dA0 = desc_lo(sb + OFF_A);
#define KT_P4(I, NK)                                                                                        \
        const int s_ = (2 * (I) + w) & 7;                                                                   \
        mbar_waitc(sb + BAR_FULLB + 8 * rg.slot, rg.phase);                                                 \
        mbar_waitc(sb + BAR_FULLA + 8 * s_, (((I) >> 2) + 1) & 1);                                          \
        const desc_t dh_ = dA0 + s_ * (SLOT >> 4), dw_ = dB + rg.slot * (SLOT >> 4) + w * 512;              \
        wg_fence();                                                                                         \
        _Pragma("unroll") for (int k = 0; k < (NK); k++) wgmma_n128_tn(acc, dw_ + 128 * k, dh_ + 2 * k, ((I) | k) != 0); \
        wg_commit();                                                                                        \
        wg_wait<1>();
#pragma unroll 1
            for (int i = 0; i < 8; i++) {
                KT_P4(i, 4)
                mbar_arrive_n_if(sb + BAR_EMPTYA + 8 * ((s_ + 6) & 7), 2, l0 && i > 0);
                mbar_arrive_cl_if(eb + 8 * prev, l2 && i > 0);
#pragma unroll
                for (int t = 0; t < 8; t++) lds_f4_if(cs[t], sb + OFF_CS1 + (64 * w + 8 * t + 2 * q) * 8, i == t);
                prev = rg.slot; rg.adv5();
            }
#pragma unroll 1
            for (int i = 8; i < 12; i++) {
                KT_P4(i, 3)
                mbar_arrive_n_if(sb + BAR_EMPTYA + 8 * ((s_ + 6) & 7), 2, l0);
                rg.adv5();
            }
            wg_wait<0>();
            fence_acc<64>(acc);
            TL(15, tid == 0);
            const uint32_t xch = sb + OFF_A + 2 * SLOT + (tid & 127) * 16;
            if (w) {
#pragma unroll
                for (int t = 0; t < 8; t++) {
                    sts128(xch + SLOT + t * 2048, __float_as_uint(acc[4 * t]), __float_as_uint(acc[4 * t + 1]),
                           __float_as_uint(acc[4 * t + 2]), __float_as_uint(acc[4 * t + 3]));
                }
#pragma unroll
                for (int t = 0; t < 32; t++) acc[t] = acc[32 + t];
            } else {
#pragma unroll
                for (int t = 0; t < 8; t++)
                    sts128(xch + t * 2048, __float_as_uint(acc[32 + 4 * t]), __float_as_uint(acc[33 + 4 * t]),
                           __float_as_uint(acc[34 + 4 * t]), __float_as_uint(acc[35 + 4 * t]));
            }
            bar_sync(1, 256);
            float4 o[8];
#pragma unroll
            for (int t = 0; t < 8; t++) o[t] = lds_f4(xch + (w ^ 1) * SLOT + t * 2048);
            const uint32_t tile = sb + OFF_A + w * SLOT;
#pragma unroll
            for (int t = 0; t < 8; t++) {
                hr[2 * t] = pack_bf16(fmaf(acc[4 * t] + o[t].x, cs[t].y, bf_lo(hr[2 * t])), fmaf(acc[4 * t + 1] + o[t].y, cs[t].w, bf_hi(hr[2 * t])));
                hr[2 * t + 1] = pack_bf16(fmaf(acc[4 * t + 2] + o[t].z, cs[t].y, bf_lo(hr[2 * t + 1])), fmaf(acc[4 * t + 3] + o[t].w, cs[t].w, bf_hi(hr[2 * t + 1])));
            }
#pragma unroll
            for (int tp = 0; tp < 4; tp++) stsm4t(tile + blk + tp * 2048, hr[4 * tp], hr[4 * tp + 1], hr[4 * tp + 2], hr[4 * tp + 3]);
            fence_async_smem();
            bar_sync(2 + w, 128);
            if ((tid & 127) == 0) {
                tma_store2d(&P.tout, tile, 64 * j, 128 * m + 64 * w);
                asm volatile("cp.async.bulk.wait_group.read 0;" ::: "memory");
            }
            if (tid == 0 && role == 0) g_epoch = epoch + 1;
            TL(16, tid == 0); TLG(1, tid == 0);
        }
    }
}

__global__ void probe_kernel() {}

typedef CUresult (*EncodeFn)(CUtensorMap*, CUtensorMapDataType, cuuint32_t, void*, const cuuint64_t*, const cuuint64_t*,
                             const cuuint32_t*, const cuuint32_t*, CUtensorMapInterleave, CUtensorMapSwizzle,
                             CUtensorMapL2promotion, CUtensorMapFloatOOBfill);

static void make_map2d(EncodeFn enc, CUtensorMap* tm, const void* base, uint64_t cols, uint64_t rows, uint64_t pitch_elems,
                       uint32_t box_rows) {
    cuuint64_t gd[2] = {cols, rows};
    cuuint64_t gs[1] = {pitch_elems * 2};
    cuuint32_t bd[2] = {64, box_rows};
    cuuint32_t es[2] = {1, 1};
    enc(tm, CU_TENSOR_MAP_DATA_TYPE_BFLOAT16, 2, const_cast<void*>(base), gd, gs, bd, es, CU_TENSOR_MAP_INTERLEAVE_NONE,
        CU_TENSOR_MAP_SWIZZLE_128B, CU_TENSOR_MAP_L2_PROMOTION_L2_256B, CU_TENSOR_MAP_FLOAT_OOB_FILL_NONE);
}

}

extern "C" void kernel_launch(void* const* d_in, const int* in_sizes, int n_in, void* d_out, int out_size) {
    using namespace hk;
    (void)in_sizes; (void)n_in; (void)out_size;
    static EncodeFn enc = nullptr;
    static int std_layout = 0;
    if (!enc) {
        void* fn = nullptr;
        cudaDriverEntryPointQueryResult qr;
        cudaGetDriverEntryPoint("cuTensorMapEncodeTiled", &fn, cudaEnableDefault, &qr);
        enc = (EncodeFn)fn;
        cudaFuncSetAttribute(fused_kernel, cudaFuncAttributeMaxDynamicSharedMemorySize, SMEM_BYTES);
        int dev = 0, sms = 0;
        cudaGetDevice(&dev);
        cudaDeviceGetAttribute(&sms, cudaDevAttrMultiProcessorCount, dev);
        cudaFuncSetAttribute(probe_kernel, cudaFuncAttributeNonPortableClusterSizeAllowed, 1);
        cudaFuncSetAttribute(probe_kernel, cudaFuncAttributeMaxDynamicSharedMemorySize, SMEM_BYTES);
        const int sizes[3] = {8, 9, 16}, want[3] = {15, 9, 7};
        bool ok = sms == NCTA;
        for (int i = 0; i < 3 && ok; i++) {
            cudaLaunchConfig_t cfg = {};
            cfg.gridDim = dim3(sizes[i] * 8); cfg.blockDim = dim3(NTHREADS); cfg.dynamicSmemBytes = SMEM_BYTES;
            cudaLaunchAttribute at;
            at.id = cudaLaunchAttributeClusterDimension;
            at.val.clusterDim.x = sizes[i]; at.val.clusterDim.y = 1; at.val.clusterDim.z = 1;
            cfg.attrs = &at; cfg.numAttrs = 1;
            int n = 0;
            ok = cudaOccupancyMaxActiveClusters(&n, probe_kernel, &cfg) == cudaSuccess && n == want[i];
        }
        (void)cudaGetLastError();
        std_layout = ok ? 1 : 0;
    }
    Params P;
    const __nv_bfloat16* x = (const __nv_bfloat16*)d_in[0];
    P.x = x;
    P.wqkv = (const __nv_bfloat16*)d_in[1];
    P.wphi = (const __nv_bfloat16*)d_in[2];
    P.wo = (const __nv_bfloat16*)d_in[3];
    P.wg = (const __nv_bfloat16*)d_in[5];
    P.wu = (const __nv_bfloat16*)d_in[6];
    P.wd = (const __nv_bfloat16*)d_in[7];
    P.out = (__nv_bfloat16*)d_out;
    P.zero = 0;
    for (int i = 0; i < NCTA; i++) {
        const int odd = i & 1;
        int role = i < 4 ? 128 + i : (((i - 4) >> 4) * 2 + odd) * 8 + (((i - 4) >> 1) & 7);
        if (std_layout) {
            const int tpc = i < 8 ? 62 + (i >> 1) : (i - 8) >> 1;
            if (tpc < 32) role = (tpc & 7) ? (2 * ((tpc & 7) - 1) + odd) * 8 + (tpc >> 3) : (14 + odd) * 8 + (tpc >> 3);
            else if (tpc < 60) role = (2 * ((tpc - 32) % 7) + odd) * 8 + 4 + (tpc - 32) / 7;
            else if (tpc < 62) role = 128 + (tpc - 60) * 2 + odd;
            else role = (14 + odd) * 8 + 4 + (tpc - 62);
        }
        P.role[i] = (unsigned char)role;
    }
    make_map2d(enc, &P.tx, x, DM, SEQ, DM, 128);
    make_map2d(enc, &P.twq, P.wqkv, 3 * DM, DM, 3 * DM, 64);
    make_map2d(enc, &P.two, P.wo, DM, DM, DM, 64);
    make_map2d(enc, &P.twg, P.wg, FF, DM, FF, 64);
    make_map2d(enc, &P.twu, P.wu, FF, DM, FF, 64);
    make_map2d(enc, &P.twd, P.wd, DM, FF, DM, 64);
    make_map2d(enc, &P.tout, d_out, DM, SEQ, DM, 64);
    fused_kernel<<<NCTA, NTHREADS, SMEM_BYTES>>>(P);
}
```

```cpp
#include <cuda_runtime.h>
#include <cuda_bf16.h>
#include <cuda.h>
#include <stdint.h>

namespace hk {

constexpr int SEQ = 2048, DM = 512, FF = 1376;
constexpr int NCTA = 132;
constexpr int NTHREADS = 384;
constexpr uint32_t SLOT = 16384;
constexpr uint32_t OFF_A = 0, OFF_B = 8 * SLOT, OFF_MISC = 14 * SLOT;
constexpr uint32_t BAR_FULLA = OFF_MISC + 0, BAR_EMPTYA = OFF_MISC + 64, BAR_FULLB = OFF_MISC + 128,
                   BAR_EMPTYB = OFF_MISC + 176, BAR_CS1 = OFF_MISC + 224, BAR_CS3 = OFF_MISC + 232,
                   BAR_CSQ = OFF_MISC + 240, BAR_CSV = OFF_MISC + 248,
                   BAR_STG = OFF_MISC + 256,
                   BAR_KVW = OFF_MISC + 280, BAR_KVR = OFF_MISC + 288, BAR_CSG = OFF_MISC + 296;
constexpr uint32_t OFF_CS1 = OFF_MISC + 384;
constexpr uint32_t OFF_CS3 = OFF_CS1 + 1024;
constexpr uint32_t OFF_XST = OFF_CS3;
constexpr uint32_t SMEM_BYTES = OFF_CS3 + 1536;
#define KORD(i, j) ((i) == 0 ? (j) : (i) - ((i) <= (j)))
constexpr int NB = 6;
#define PF_DELAY 2
#define KV_POLL 1
constexpr int AHEAD = 3;

constexpr int ACC_SIZE = 3 * 256 * 4;

__device__ __align__(1024) uint4 g_act[5 * 128 * 1024];
__device__ __align__(128) unsigned long long g_hstat[SEQ * 16];
__device__ __align__(128) unsigned long long g_xstat[SEQ * 2];
__device__ __align__(128) float g_acc[8 * ACC_SIZE];
__device__ __align__(128) unsigned long long g_cs[8 * 6 * 128];
__device__ __align__(128) unsigned g_flag[16 * 5 * 32 + 32];
__device__ unsigned g_epoch = 1;

#define TL(i, pred) do {} while (0)
#define TLG(i, pred) do {} while (0)

struct Params {
    CUtensorMap tx, twq, two, twg, twu, twd, tout;
    const __nv_bfloat16 *x, *wqkv, *wphi, *wo, *wg, *wu, *wd;
    __nv_bfloat16* out;
    unsigned zero;
    unsigned char role[NCTA];
};

__device__ __forceinline__ uint32_t smem_u32(const void* p) { return (uint32_t)__cvta_generic_to_shared(p); }
__device__ __forceinline__ void mbar_init(uint32_t bar, uint32_t cnt) {
    asm volatile("mbarrier.init.shared::cta.b64 [%0], %1;" ::"r"(bar), "r"(cnt) : "memory");
}
__device__ __forceinline__ void mbar_expect_tx(uint32_t bar, uint32_t bytes) {
    asm volatile("mbarrier.arrive.expect_tx.shared::cta.b64 _, [%0], %1;" ::"r"(bar), "r"(bytes) : "memory");
}
__device__ __forceinline__ void mbar_arrive(uint32_t bar) {
    asm volatile("mbarrier.arrive.shared::cta.b64 _, [%0];" ::"r"(bar) : "memory");
}
__device__ __forceinline__ void mbar_arrive_if(uint32_t bar, bool pred) {
    asm volatile("{.reg .pred p; setp.ne.u32 p, %1, 0; @p mbarrier.arrive.shared::cta.b64 _, [%0];}" ::"r"(bar), "r"((uint32_t)pred) : "memory");
}
__device__ __forceinline__ bool mbar_try(uint32_t bar, uint32_t parity) {
    uint32_t ok;
    asm volatile("{.reg .pred p; mbarrier.try_wait.parity.shared::cta.b64 p, [%1], %2; selp.u32 %0,1,0,p;}"
                 : "=r"(ok) : "r"(bar), "r"(parity) : "memory");
    return ok;
}
__device__ __forceinline__ bool mbar_test(uint32_t bar, uint32_t parity) {
    uint32_t ok;
    asm volatile("{.reg .pred p; mbarrier.test_wait.parity.shared::cta.b64 p, [%1], %2; selp.u32 %0,1,0,p;}"
                 : "=r"(ok) : "r"(bar), "r"(parity) : "memory");
    return ok;
}
__device__ __forceinline__ void trap_if_gt(uint32_t v, uint32_t lim) {
    asm volatile("{.reg .pred p; setp.gt.u32 p, %0, %1; @p trap;}" ::"r"(v), "r"(lim));
}
__device__ __forceinline__ void mbar_wait(uint32_t bar, uint32_t parity) {
    asm volatile("{\n"
                 ".reg .pred P1, P2;\n"
                 ".reg .u32 c;\n"
                 "mov.u32 c, 0;\n"
                 "LAB_WAIT:\n"
                 "mbarrier.try_wait.parity.shared::cta.b64 P1, [%0], %1;\n"
                 "@P1 bra LAB_DONE;\n"
                 "add.u32 c, c, 1;\n"
                 "setp.gt.u32 P2, c, 4194304;\n"
                 "@P2 trap;\n"
                 "bra LAB_WAIT;\n"
                 "LAB_DONE:\n"
                 "}" ::"r"(bar), "r"(parity) : "memory");
}
__device__ __forceinline__ void mbar_waitc(uint32_t bar, uint32_t parity) {
    asm volatile("{\n"
                 ".reg .pred P1;\n"
                 "LAB_WAIT:\n"
                 "mbarrier.try_wait.parity.shared::cta.b64 P1, [%0], %1;\n"
                 "@!P1 bra LAB_WAIT;\n"
                 "}" ::"r"(bar), "r"(parity) : "memory");
}
__device__ __forceinline__ void tma2d(uint32_t dst, const CUtensorMap* tm, uint32_t bar, int c0, int c1) {
    asm volatile("cp.async.bulk.tensor.2d.shared::cluster.global.mbarrier::complete_tx::bytes [%0], [%1, {%3, %4}], [%2];"
                 ::"r"(dst), "l"(tm), "r"(bar), "r"(c0), "r"(c1) : "memory");
}
__device__ __forceinline__ void tma2d_mc(uint32_t dst, const CUtensorMap* tm, uint32_t bar, int c0, int c1) {
    asm volatile("cp.async.bulk.tensor.2d.shared::cluster.global.mbarrier::complete_tx::bytes.multicast::cluster [%0], [%1, {%3, %4}], [%2], %5;"
                 ::"r"(dst), "l"(tm), "r"(bar), "r"(c0), "r"(c1), "h"((uint16_t)3) : "memory");
}
__device__ __forceinline__ uint32_t mapa(uint32_t addr, uint32_t rank) {
    uint32_t r; asm("mapa.shared::cluster.u32 %0, %1, %2;" : "=r"(r) : "r"(addr), "r"(rank)); return r;
}
__device__ __forceinline__ void mbar_arrive_cl_if(uint32_t cbar, bool pred) {
    asm volatile("{.reg .pred p; setp.ne.u32 p, %1, 0; @p mbarrier.arrive.shared::cluster.b64 _, [%0];}" ::"r"(cbar), "r"((uint32_t)pred) : "memory");
}
__device__ __forceinline__ bool elect_one() {
    uint32_t ok;
    asm volatile("{.reg .pred p; elect.sync _|p, 0xffffffff; selp.u32 %0, 1, 0, p;}" : "=r"(ok));
    return ok;
}
__device__ __forceinline__ void prefetch_tmap(const CUtensorMap* tm) {
    asm volatile("prefetch.tensormap [%0];" ::"l"(tm) : "memory");
}
__device__ __forceinline__ void prefetch_l2(const void* p, uint32_t bytes) {
    asm volatile("cp.async.bulk.prefetch.L2.global [%0], %1;" ::"l"(p), "r"(bytes) : "memory");
}
__device__ __forceinline__ unsigned ld_acquire(const unsigned* p) {
    unsigned v; asm volatile("ld.acquire.gpu.global.u32 %0, [%1];" : "=r"(v) : "l"(p) : "memory"); return v;
}
__device__ __forceinline__ uint4 ld_acquire4(const unsigned* p) {
    uint4 v;
    asm volatile("ld.acquire.gpu.global.v4.u32 {%0,%1,%2,%3}, [%4];" : "=r"(v.x), "=r"(v.y), "=r"(v.z), "=r"(v.w) : "l"(p) : "memory");
    return v;
}
__device__ __forceinline__ unsigned ld_relaxed(const unsigned* p) {
    unsigned v; asm volatile("ld.relaxed.gpu.global.u32 %0, [%1];" : "=r"(v) : "l"(p)); return v;
}
__device__ __forceinline__ void st_relaxed(unsigned* p, unsigned v) {
    asm volatile("st.relaxed.gpu.global.u32 [%0], %1;" ::"l"(p), "r"(v) : "memory");
}
__device__ __forceinline__ void red_relaxed(unsigned* p, unsigned v) {
    asm volatile("red.relaxed.gpu.global.add.u32 [%0], %1;" ::"l"(p), "r"(v) : "memory");
}
__device__ __forceinline__ void fence_gpu() { asm volatile("fence.acq_rel.gpu;" ::: "memory"); }
__device__ __forceinline__ void fence_async_smem() { asm volatile("fence.proxy.async.shared::cta;" ::: "memory"); }
__device__ __forceinline__ void fence_async_global() { asm volatile("fence.proxy.async.global;" ::: "memory"); }
__device__ __forceinline__ uint32_t readback(const void* p) {
    uint32_t v; asm volatile("ld.relaxed.gpu.global.u32 %0, [%1];" : "=r"(v) : "l"(p) : "memory"); return v;
}
__device__ __forceinline__ void wait_count(const unsigned* p, unsigned target) {
    uint32_t it = 0;
    while ((int)(readback(p) - target) < 0) trap_if_gt(++it, 1u << 22);
}
__device__ __forceinline__ void wait_count_warp(const unsigned* p, unsigned target) {
    uint32_t it = 0;
    while (__any_sync(0xffffffffu, (int)(readback(p) - target) < 0)) trap_if_gt(++it, 1u << 22);
}
__device__ __forceinline__ void red_f32(float* p, float a) {
    asm volatile("red.relaxed.gpu.global.add.f32 [%0], %1;" ::"l"(p), "f"(a) : "memory");
}
__device__ __forceinline__ void red_f32x2(float* p, float a, float b) {
    asm volatile("red.relaxed.gpu.global.add.v2.f32 [%0], {%1, %2};" ::"l"(p), "f"(a), "f"(b) : "memory");
}
__device__ __forceinline__ void red_f32x4(float* p, float a, float b, float c, float d) {
    asm volatile("red.relaxed.gpu.global.add.v4.f32 [%0], {%1, %2, %3, %4};" ::"l"(p), "f"(a), "f"(b), "f"(c), "f"(d) : "memory");
}
__device__ __forceinline__ float4 ld_l2_f4(const float* p) {
    float4 v;
    asm volatile("ld.relaxed.gpu.global.v4.f32 {%0,%1,%2,%3}, [%4];" : "=f"(v.x), "=f"(v.y), "=f"(v.z), "=f"(v.w) : "l"(p) : "memory");
    return v;
}
__device__ __forceinline__ float2 ld_l2_f2(const float* p) {
    float2 v;
    asm volatile("ld.relaxed.gpu.global.v2.f32 {%0,%1}, [%2];" : "=f"(v.x), "=f"(v.y) : "l"(p) : "memory");
    return v;
}
__device__ __forceinline__ float ld_l2_f(const float* p) {
    float v;
    asm volatile("ld.relaxed.gpu.global.f32 %0, [%1];" : "=f"(v) : "l"(p) : "memory");
    return v;
}
__device__ __forceinline__ uint4 ldg_nc(const void* p) {
    uint4 v;
    asm volatile("ld.global.nc.L1::no_allocate.v4.u32 {%0,%1,%2,%3}, [%4];" : "=r"(v.x), "=r"(v.y), "=r"(v.z), "=r"(v.w) : "l"(p));
    return v;
}
__device__ __forceinline__ void stg128(void* p, uint32_t a, uint32_t b, uint32_t c, uint32_t d) {
    asm volatile("st.global.v4.u32 [%0], {%1,%2,%3,%4};" ::"l"(p), "r"(a), "r"(b), "r"(c), "r"(d) : "memory");
}
__device__ __forceinline__ uint4 lds128(uint32_t a) {
    uint4 v;
    asm volatile("ld.shared.v4.u32 {%0,%1,%2,%3}, [%4];" : "=r"(v.x), "=r"(v.y), "=r"(v.z), "=r"(v.w) : "r"(a) : "memory");
    return v;
}
__device__ __forceinline__ float2 lds_f2(uint32_t a) {
    float2 v;
    asm volatile("ld.shared.v2.f32 {%0,%1}, [%2];" : "=f"(v.x), "=f"(v.y) : "r"(a) : "memory");
    return v;
}
__device__ __forceinline__ void sts_f2(uint32_t a, float x, float y) {
    asm volatile("st.shared.v2.f32 [%0], {%1,%2};" ::"r"(a), "f"(x), "f"(y) : "memory");
}
__device__ __forceinline__ void sts64(uint32_t a, uint32_t x, uint32_t y) {
    asm volatile("st.shared.v2.u32 [%0], {%1,%2};" ::"r"(a), "r"(x), "r"(y) : "memory");
}
__device__ __forceinline__ void sts128(uint32_t a, uint32_t x, uint32_t y, uint32_t z, uint32_t w) {
    asm volatile("st.shared.v4.u32 [%0], {%1,%2,%3,%4};" ::"r"(a), "r"(x), "r"(y), "r"(z), "r"(w) : "memory");
}
__device__ __forceinline__ void stsm4(uint32_t a, uint32_t r0, uint32_t r1, uint32_t r2, uint32_t r3) {
    asm volatile("stmatrix.sync.aligned.m8n8.x4.shared.b16 [%0], {%1,%2,%3,%4};" ::"r"(a), "r"(r0), "r"(r1), "r"(r2), "r"(r3) : "memory");
}
__device__ __forceinline__ void stsm4t(uint32_t a, uint32_t r0, uint32_t r1, uint32_t r2, uint32_t r3) {
    asm volatile("stmatrix.sync.aligned.m8n8.x4.trans.shared.b16 [%0], {%1,%2,%3,%4};" ::"r"(a), "r"(r0), "r"(r1), "r"(r2), "r"(r3) : "memory");
}
__device__ __forceinline__ void tma_store2d(const CUtensorMap* tm, uint32_t src, int c0, int c1) {
    asm volatile("cp.async.bulk.tensor.2d.global.shared::cta.bulk_group [%0, {%2, %3}], [%1];" ::"l"(tm), "r"(src), "r"(c0), "r"(c1) : "memory");
    asm volatile("cp.async.bulk.commit_group;" ::: "memory");
}
__device__ __forceinline__ void ldsm4(uint32_t a, uint32_t& r0, uint32_t& r1, uint32_t& r2, uint32_t& r3) {
    asm volatile("ldmatrix.sync.aligned.m8n8.x4.shared.b16 {%0,%1,%2,%3}, [%4];" : "=r"(r0), "=r"(r1), "=r"(r2), "=r"(r3) : "r"(a) : "memory");
}
__device__ __forceinline__ void ldsm4t(uint32_t a, uint32_t& r0, uint32_t& r1, uint32_t& r2, uint32_t& r3) {
    asm volatile("ldmatrix.sync.aligned.m8n8.x4.trans.shared.b16 {%0,%1,%2,%3}, [%4];" : "=r"(r0), "=r"(r1), "=r"(r2), "=r"(r3) : "r"(a) : "memory");
}
__device__ __forceinline__ void mma16816(float* c, const uint32_t* a, uint32_t b0, uint32_t b1) {
    asm("mma.sync.aligned.m16n8k16.row.col.f32.bf16.bf16.f32 {%0,%1,%2,%3}, {%4,%5,%6,%7}, {%8,%9}, {%0,%1,%2,%3};"
                 : "+f"(c[0]), "+f"(c[1]), "+f"(c[2]), "+f"(c[3])
                 : "r"(a[0]), "r"(a[1]), "r"(a[2]), "r"(a[3]), "r"(b0), "r"(b1));
}
__device__ __forceinline__ uint32_t pack_bf16(float lo, float hi) {
    uint32_t r; asm("cvt.rn.bf16x2.f32 %0, %1, %2;" : "=r"(r) : "f"(hi), "f"(lo)); return r;
}
__device__ __forceinline__ float bf_lo(uint32_t w) { return __uint_as_float(w << 16); }
__device__ __forceinline__ float bf_hi(uint32_t w) { return __uint_as_float(w & 0xffff0000u); }
__device__ __forceinline__ float ex2(float x) { float r; asm("ex2.approx.ftz.f32 %0, %1;" : "=f"(r) : "f"(x)); return r; }
__device__ __forceinline__ float rcp(float x) { float r; asm("rcp.approx.ftz.f32 %0, %1;" : "=f"(r) : "f"(x)); return r; }
__device__ __forceinline__ void bar_sync(int id, int n) { asm volatile("bar.sync %0, %1;" ::"r"(id), "r"(n) : "memory"); }

typedef unsigned long long desc_t;
__device__ __forceinline__ desc_t desc_lo(uint32_t addr) { return (desc_t)(((addr & 0x3FFFF) >> 4) | (512u << 16)) | (0x40000040ull << 32); }
__device__ __forceinline__ void wg_fence() { asm volatile("wgmma.fence.sync.aligned;" ::: "memory"); }
__device__ __forceinline__ void wg_commit() { asm volatile("wgmma.commit_group.sync.aligned;" ::: "memory"); }
template <int N> __device__ __forceinline__ void wg_wait() { asm volatile("wgmma.wait_group.sync.aligned %0;" ::"n"(N) : "memory"); }
template <int N> __device__ __forceinline__ void fence_acc(float* d) {
#pragma unroll
    for (int i = 0; i < N; i++) asm volatile("" : "+f"(d[i])::"memory");
}
#define R4(o) "+f"(d[o + 0]), "+f"(d[o + 1]), "+f"(d[o + 2]), "+f"(d[o + 3])
#define R8(o) R4(o), R4(o + 4)
__device__ __forceinline__ void wgmma_n128(float* d, desc_t da, desc_t db, int sc) {
    asm volatile("{.reg .pred p; setp.ne.b32 p, %66, 0;\n"
                 "wgmma.mma_async.sync.aligned.m64n128k16.f32.bf16.bf16 {%0,%1,%2,%3,%4,%5,%6,%7,%8,%9,%10,%11,%12,%13,%14,%15,%16,%17,%18,%19,%20,%21,%22,%23,%24,%25,%26,%27,%28,%29,%30,%31,"
                 "%32,%33,%34,%35,%36,%37,%38,%39,%40,%41,%42,%43,%44,%45,%46,%47,%48,%49,%50,%51,%52,%53,%54,%55,%56,%57,%58,%59,%60,%61,%62,%63}, %64, %65, p, 1, 1, 0, 1;}"
                 : R8(0), R8(8), R8(16), R8(24), R8(32), R8(40), R8(48), R8(56)
                 : "l"(da), "l"(db), "r"(sc));
}
__device__ __forceinline__ void wgmma_n112(float* d, desc_t da, desc_t db, int sc) {
    asm volatile("{.reg .pred p; setp.ne.b32 p, %58, 0;\n"
                 "wgmma.mma_async.sync.aligned.m64n112k16.f32.bf16.bf16 {%0,%1,%2,%3,%4,%5,%6,%7,%8,%9,%10,%11,%12,%13,%14,%15,%16,%17,%18,%19,%20,%21,%22,%23,%24,%25,%26,%27,%28,%29,%30,%31,%32,%33,%34,%35,%36,%37,%38,%39,%40,%41,%42,%43,%44,%45,%46,%47,%48,%49,%50,%51,%52,%53,%54,%55}, %56, %57, p, 1, 1, 0, 1;}"
                 : R8(0), R8(8), R8(16), R8(24), R8(32), R8(40), R8(48)
                 : "l"(da), "l"(db), "r"(sc));
}
__device__ __forceinline__ void wgmma_n128_tn(float* d, desc_t da, desc_t db, int sc) {
    asm volatile("{.reg .pred p; setp.ne.b32 p, %66, 0;\n"
                 "wgmma.mma_async.sync.aligned.m64n128k16.f32.bf16.bf16 {%0,%1,%2,%3,%4,%5,%6,%7,%8,%9,%10,%11,%12,%13,%14,%15,%16,%17,%18,%19,%20,%21,%22,%23,%24,%25,%26,%27,%28,%29,%30,%31,%32,%33,%34,%35,%36,%37,%38,%39,%40,%41,%42,%43,%44,%45,%46,%47,%48,%49,%50,%51,%52,%53,%54,%55,%56,%57,%58,%59,%60,%61,%62,%63}, %64, %65, p, 1, 1, 1, 0;}"
                 : R8(0), R8(8), R8(16), R8(24), R8(32), R8(40), R8(48), R8(56)
                 : "l"(da), "l"(db), "r"(sc));
}
__device__ __forceinline__ void wgmma_n64(float* d, desc_t da, desc_t db, int sc) {
    asm volatile("{.reg .pred p; setp.ne.b32 p, %34, 0;\n"
                 "wgmma.mma_async.sync.aligned.m64n64k16.f32.bf16.bf16 {%0,%1,%2,%3,%4,%5,%6,%7,%8,%9,%10,%11,%12,%13,%14,%15,%16,%17,%18,%19,%20,%21,%22,%23,%24,%25,%26,%27,%28,%29,%30,%31}, %32, %33, p, 1, 1, 0, 1;}"
                 : R8(0), R8(8), R8(16), R8(24)
                 : "l"(da), "l"(db), "r"(sc));
}
__device__ __forceinline__ void wgmma_n40_tt(float* d, desc_t da, desc_t db, int sc) {
    asm volatile("{.reg .pred p; setp.ne.b32 p, %22, 0;\n"
                 "wgmma.mma_async.sync.aligned.m64n40k16.f32.bf16.bf16 {%0,%1,%2,%3,%4,%5,%6,%7,%8,%9,%10,%11,%12,%13,%14,%15,%16,%17,%18,%19}, %20, %21, p, 1, 1, 1, 1;}"
                 : R8(0), R8(8), R4(16)
                 : "l"(da), "l"(db), "r"(sc));
}

__device__ __forceinline__ void wgmma_n8_tt(float* d, desc_t da, desc_t db, int sc) {
    asm volatile("{.reg .pred p; setp.ne.b32 p, %6, 0;\n"
                 "wgmma.mma_async.sync.aligned.m64n8k16.f32.bf16.bf16 {%0,%1,%2,%3}, %4, %5, p, 1, 1, 1, 1;}"
                 : R4(0)
                 : "l"(da), "l"(db), "r"(sc));
}

__device__ __forceinline__ void signal_after(unsigned* cnt, uint32_t ack, uint32_t zero, bool pred) {
    asm volatile("{.reg .pred p; setp.ne.u32 p, %2, 0; @p red.relaxed.gpu.global.add.u32 [%0], %1;}"
                 ::"l"(cnt), "r"((ack & zero) + 1), "r"((uint32_t)pred) : "memory");
}
__device__ __forceinline__ void signal_late(unsigned* cnt, const uint32_t* a, uint32_t zero, bool pred) {
    uint32_t v;
    asm volatile("{.reg .b32 t; lop3.b32 t, %1, %2, %3, 0xfe; or.b32 %0, t, %4;}"
                 : "=r"(v) : "r"(a[0]), "r"(a[1]), "r"(a[2]), "r"(a[3]));
    signal_after(cnt, v, zero, pred);
}
__device__ __forceinline__ void red_f32_if(float* p, float a, bool pred) {
    asm volatile("{.reg .pred p; setp.ne.u32 p, %2, 0; @p red.relaxed.gpu.global.add.f32 [%0], %1;}" ::"l"(p), "f"(a), "r"((uint32_t)pred) : "memory");
}
__device__ __forceinline__ void stg_f2_if(float* p, float a, float b, bool pred) {
    asm volatile("{.reg .pred p; setp.ne.u32 p, %3, 0; @p st.global.v2.f32 [%0], {%1,%2};}" ::"l"(p), "f"(a), "f"(b), "r"((uint32_t)pred) : "memory");
}
__device__ __forceinline__ void stg64(void* p, uint32_t a, uint32_t b) {
    asm volatile("st.global.v2.u32 [%0], {%1,%2};" ::"l"(p), "r"(a), "r"(b) : "memory");
}
__device__ __forceinline__ void mma16816_z(float* c, const uint32_t* a, uint32_t b0, uint32_t b1) {
    asm("mma.sync.aligned.m16n8k16.row.col.f32.bf16.bf16.f32 {%0,%1,%2,%3}, {%4,%5,%6,%7}, {%8,%9}, {%10,%10,%10,%10};"
                 : "=f"(c[0]), "=f"(c[1]), "=f"(c[2]), "=f"(c[3])
                 : "r"(a[0]), "r"(a[1]), "r"(a[2]), "r"(a[3]), "r"(b0), "r"(b1), "f"(0.f));
}
__device__ __forceinline__ uint32_t max2(uint32_t a, uint32_t b) { uint32_t r; asm("max.bf16x2 %0, %1, %2;" : "=r"(r) : "r"(a), "r"(b)); return r; }
__device__ __forceinline__ uint32_t min2(uint32_t a, uint32_t b) { uint32_t r; asm("min.bf16x2 %0, %1, %2;" : "=r"(r) : "r"(a), "r"(b)); return r; }
__device__ __forceinline__ void bar_arrive(int id, int n) { asm volatile("bar.arrive %0, %1;" ::"r"(id), "r"(n) : "memory"); }
__device__ __forceinline__ void mbar_arrive_n_if(uint32_t bar, uint32_t n, bool pred) {
    asm volatile("{.reg .pred p; setp.ne.u32 p, %1, 0; @p mbarrier.arrive.shared::cta.b64 _, [%0], %2;}" ::"r"(bar), "r"((uint32_t)pred), "r"(n) : "memory");
}
__device__ __forceinline__ float4 lds_f4(uint32_t a) {
    float4 v;
    asm volatile("ld.shared.v4.f32 {%0,%1,%2,%3}, [%4];" : "=f"(v.x), "=f"(v.y), "=f"(v.z), "=f"(v.w) : "r"(a) : "memory");
    return v;
}
__device__ __forceinline__ void lds_f4_if(float4& v, uint32_t a, bool pred) {
    asm volatile("{.reg .pred p; setp.ne.u32 p, %5, 0; @p ld.shared.v4.f32 {%0,%1,%2,%3}, [%4];}"
                 : "+f"(v.x), "+f"(v.y), "+f"(v.z), "+f"(v.w) : "r"(a), "r"((uint32_t)pred) : "memory");
}
__device__ __forceinline__ uint4 ld_tagged(const unsigned long long* p) {
    unsigned long long a, b;
    asm volatile("ld.acquire.gpu.global.v2.b64 {%0,%1}, [%2];" : "=l"(a), "=l"(b) : "l"(p) : "memory");
    return make_uint4((unsigned)a, (unsigned)(a >> 32), (unsigned)b, (unsigned)(b >> 32));
}
__device__ __forceinline__ uint4 ld_tagged_rlx(const unsigned long long* p) {
    unsigned long long a, b;
    asm volatile("ld.relaxed.gpu.global.v2.b64 {%0,%1}, [%2];" : "=l"(a), "=l"(b) : "l"(p) : "memory");
    return make_uint4((unsigned)a, (unsigned)(a >> 32), (unsigned)b, (unsigned)(b >> 32));
}
__device__ __forceinline__ void sts32(uint32_t a, uint32_t x) { asm volatile("st.shared.u32 [%0], %1;" ::"r"(a), "r"(x) : "memory"); }
__device__ __forceinline__ void fetch_tagged(const unsigned long long* src, uint32_t dst, unsigned epoch) {
    uint4 v;
    uint32_t it = 0;
    while (true) {
        v = ld_tagged_rlx(src);
        if (!__any_sync(0xffffffffu, v.y != epoch || v.w != epoch)) break;
        __nanosleep(60);
        trap_if_gt(++it, 1u << 22);
    }
    sts64(dst, v.x, v.z);
}
__device__ __forceinline__ void st_tagged_if(unsigned long long* p, float a, float b, unsigned tag, bool pred) {
    const unsigned long long t = (unsigned long long)tag << 32;
    asm volatile("{.reg .pred p; setp.ne.u32 p, %3, 0; @p st.relaxed.gpu.global.v2.b64 [%0], {%1,%2};}"
                 ::"l"(p), "l"(t | __float_as_uint(a)), "l"(t | __float_as_uint(b)), "r"((uint32_t)pred) : "memory");
}

__device__ __forceinline__ void store_tile(uint32_t tile_rows, uint4* gdst, const uint32_t* lo, const uint32_t* hi, int lane, uint32_t* ack) {
    const int r = lane & 15;
#pragma unroll
    for (int b = 0; b < 4; b++)
        stsm4(tile_rows + r * 128 + (((2 * b + (lane >> 4)) ^ (r & 7)) << 4), lo[2 * b], hi[2 * b], lo[2 * b + 1], hi[2 * b + 1]);
    fence_async_smem();
    __syncwarp();
#pragma unroll
    for (int i = 0; i < 4; i++) {
        const uint4 v = lds128(tile_rows + i * 512 + lane * 16);
        stg128(gdst + 32 * i, v.x, v.y, v.z, v.w);
    }
#pragma unroll
    for (int i = 0; i < 4; i++) ack[i] = readback(gdst + 32 * i);
}

__device__ __forceinline__ void feature_maps(const uint32_t* a, const uint32_t* wb, float c0, float c1, uint32_t* plus, uint32_t* minus) {
    uint32_t P[16], mx[4], mn[4];
#pragma unroll
    for (int h = 0; h < 4; h++) {
        float p[8];
        mma16816_z(p, a + 4 * h, wb[4 * h], wb[4 * h + 1]);
        mma16816_z(p + 4, a + 4 * h, wb[4 * h + 2], wb[4 * h + 3]);
        P[4 * h] = pack_bf16(p[0], p[2]); P[4 * h + 1] = pack_bf16(p[1], p[3]);
        P[4 * h + 2] = pack_bf16(p[4], p[6]); P[4 * h + 3] = pack_bf16(p[5], p[7]);
        mx[h] = max2(max2(P[4 * h], P[4 * h + 1]), max2(P[4 * h + 2], P[4 * h + 3]));
        mn[h] = min2(min2(P[4 * h], P[4 * h + 1]), min2(P[4 * h + 2], P[4 * h + 3]));
    }
#pragma unroll
    for (int s = 1; s <= 2; s <<= 1) {
        uint32_t tx[4], tn[4];
#pragma unroll
        for (int h = 0; h < 4; h++) { tx[h] = __shfl_xor_sync(0xffffffffu, mx[h], s); tn[h] = __shfl_xor_sync(0xffffffffu, mn[h], s); }
#pragma unroll
        for (int h = 0; h < 4; h++) { mx[h] = max2(mx[h], tx[h]); mn[h] = min2(mn[h], tn[h]); }
    }
#pragma unroll
    for (int h = 0; h < 4; h++) {
        const float mx0 = bf_lo(mx[h]) * c0, mx1 = bf_hi(mx[h]) * c1, mn0 = bf_lo(mn[h]) * c0, mn1 = bf_hi(mn[h]) * c1;
        float ep[8], em[8];
#pragma unroll
        for (int i = 0; i < 8; i++) {
            const bool r1 = (i & 2);
            const uint32_t w = P[4 * h + (i >> 2) * 2 + (i & 1)];
            const float p = r1 ? bf_hi(w) : bf_lo(w);
            ep[i] = ex2(fmaf(p, r1 ? c1 : c0, r1 ? -mx1 : -mx0));
            em[i] = ex2(fmaf(p, r1 ? -c1 : -c0, r1 ? mn1 : mn0));
        }
        float sp[4], sm[4];
        uint32_t tp[4], tm[4];
#pragma unroll
        for (int i = 0; i < 4; i++) { tp[i] = pack_bf16(ep[2 * i], ep[2 * i + 1]); tm[i] = pack_bf16(em[2 * i], em[2 * i + 1]); }
        mma16816_z(sp, tp, 0x3f803f80u, 0x3f803f80u);
        mma16816_z(sm, tm, 0x3f803f80u, 0x3f803f80u);
        const float r0 = rcp(sp[0] * sm[0]), r1 = rcp(sp[2] * sm[2]);
        const float rs[4] = {r0 * sm[0], r1 * sm[2], r0 * sp[0], r1 * sp[2]};
#pragma unroll
        for (int i = 0; i < 4; i++) {
            plus[4 * h + i] = pack_bf16(ep[2 * i] * rs[i & 1], ep[2 * i + 1] * rs[i & 1]);
            minus[4 * h + i] = pack_bf16(em[2 * i] * rs[2 + (i & 1)], em[2 * i + 1] * rs[2 + (i & 1)]);
        }
    }
}

template <bool SCALE>
__device__ __forceinline__ void ln_frag(const float* acc, uint32_t cs_addr, float rs0, float nm0, float rs1, float nm1, uint32_t* a) {
    const float2 c0 = lds_f2(cs_addr), c1 = lds_f2(cs_addr + 32);
    const float s0 = SCALE ? rs0 : 1.f, s1 = SCALE ? rs1 : 1.f;
    a[0] = pack_bf16(fmaf(nm0, c0.x, acc[0]) * s0, fmaf(nm0, c0.y, acc[1]) * s0);
    a[1] = pack_bf16(fmaf(nm1, c0.x, acc[2]) * s1, fmaf(nm1, c0.y, acc[3]) * s1);
    a[2] = pack_bf16(fmaf(nm0, c1.x, acc[4]) * s0, fmaf(nm0, c1.y, acc[5]) * s0);
    a[3] = pack_bf16(fmaf(nm1, c1.x, acc[6]) * s1, fmaf(nm1, c1.y, acc[7]) * s1);
}

template <int UP>
__device__ __forceinline__ uint32_t hh_pair(const float* ag, float4 cs, float nmean) {
    const float g0 = fmaf(nmean, cs.x, ag[0]), g1 = fmaf(nmean, cs.y, ag[1]);
    const float u0 = fmaf(nmean, cs.z, ag[UP]), u1 = fmaf(nmean, cs.w, ag[UP + 1]);
    return pack_bf16(g0 * u0, g1 * u1);
}
template <int NTP>
__device__ __forceinline__ void hh_stage(const float* acc, const float4* cs, float nm0, float nm1, uint32_t stg, int lane) {
#pragma unroll
    for (int tp = 0; tp < NTP; tp++)
        stsm4(stg + (lane & 15) * 128 + (((2 * tp + (lane >> 4)) ^ (lane & 7)) << 4), hh_pair<32>(acc + 8 * tp, cs[2 * tp], nm0),
              hh_pair<32>(acc + 8 * tp + 2, cs[2 * tp], nm1), hh_pair<32>(acc + 8 * tp + 4, cs[2 * tp + 1], nm0),
              hh_pair<32>(acc + 8 * tp + 6, cs[2 * tp + 1], nm1));
    fence_async_smem();
    __syncwarp();
}

template <int TP0, int TP1>
__device__ __forceinline__ void hh_stage2(const float* acc, const float4* cs, float nm0, float nm1, uint32_t stg, int lane) {
#pragma unroll
    for (int tp = TP0; tp < TP1; tp++)
        stsm4(stg + (lane & 15) * 128 + (((2 * tp + (lane >> 4)) ^ (lane & 7)) << 4), hh_pair<32>(acc + 8 * tp, cs[2 * tp], nm0),
              hh_pair<32>(acc + 8 * tp + 2, cs[2 * tp], nm1), hh_pair<32>(acc + 8 * tp + 4, cs[2 * tp + 1], nm0),
              hh_pair<32>(acc + 8 * tp + 6, cs[2 * tp + 1], nm1));
}
struct Ring {
    int slot; uint32_t phase;
    __device__ __forceinline__ void adv() { if (++slot == NB) { slot = 0; phase ^= 1; } }
    __device__ __forceinline__ void adv5() { slot += slot == 3; adv(); }
};

__global__ void __cluster_dims__(2, 1, 1) __launch_bounds__(NTHREADS, 1) fused_kernel(const __grid_constant__ Params P) {
    extern __shared__ __align__(1024) uint8_t smem_raw[];
    const uint32_t sb = smem_u32(smem_raw);
    const int tid = threadIdx.x, lane = tid & 31;
    if (tid >= 256 && tid < 258) prefetch_tmap(&P.tx + (tid & 1));
    const int warp = __shfl_sync(0xffffffffu, tid >> 5, 0);
    const unsigned role = P.role[blockIdx.x], rank = blockIdx.x & 1;
    const int m = role >> 3, j = role & 7;
    const bool helper = role >= 128;

    TL(0, tid == 0); TLG(0, tid == 0);
    float* const acc_j = g_acc + j * ACC_SIZE;

    if (__builtin_expect(warp >= 8, 1)) {
        asm volatile("setmaxnreg.dec.sync.aligned.u32 72;");
        if (elect_one()) {
            if (warp == 8) {
                if (!helper) {
#pragma unroll
                    for (int i = 0; i < NB; i++) mbar_init(sb + BAR_FULLB + 8 * i, 1);
#pragma unroll
                    for (int i = 0; i < 2; i++) {
                        mbar_expect_tx(sb + BAR_FULLB + 8 * i, SLOT);
                        tma2d(sb + OFF_B + i * SLOT, &P.twq, sb + BAR_FULLB + 8 * i, DM + 64 * j, 64 * i);
                        tma2d(sb + OFF_B + i * SLOT + 8192, &P.twq, sb + BAR_FULLB + 8 * i, 2 * DM + 64 * j, 64 * i);
                    }
                }
            } else if (warp == 9) {
#pragma unroll
                for (int i = 0; i < 8; i++) mbar_init(sb + BAR_FULLA + 8 * i, 1);
                if (!helper) {
#pragma unroll
                    for (int i = 0; i < 2; i++) {
                        mbar_expect_tx(sb + BAR_FULLA + 8 * i, SLOT);
                        tma2d(sb + OFF_A + i * SLOT, &P.tx, sb + BAR_FULLA + 8 * i, 64 * i, 128 * m);
                    }
                }
            } else if (warp == 10) {
#pragma unroll
                for (int i = 0; i < 12; i++) mbar_init(sb + BAR_CS1 + 8 * i, i < 2 || i >= 8 ? 64 : (i < 4 ? 32 : 8));
                trap_if_gt(sb & 1023, 0);
            } else {
#pragma unroll
                for (int i = 0; i < 14; i++) mbar_init(sb + (i < 8 ? BAR_EMPTYA : BAR_EMPTYB - 64) + 8 * i, i < 8 ? 8 : 16);
            }
            asm volatile("fence.mbarrier_init.release.cluster;" ::: "memory");
        }
        __syncwarp();
        asm volatile("barrier.cluster.arrive.relaxed.aligned;" ::: "memory");
        const unsigned epoch = ld_relaxed(&g_epoch);
        bar_sync(0, NTHREADS);
        if (helper) {
            if (elect_one()) {
#pragma unroll 1
                for (int i = warp - 8; i < 72; i += 4) {
                    const uint32_t full = sb + BAR_FULLA + 8 * (i & 7), dst = sb + OFF_A + (i & 7) * SLOT;
                    const int n = i >> 1, jj = 2 * j + (i & 1);
                    const bool qkv = n < 12;
                    const int c0 = qkv ? (n < 8 ? DM + 128 * (n & 4) : 0) + 64 * jj : 176 * jj + 8 * ((n - 12) & ~7);
                    const int r0 = qkv ? 128 * (n & 3) : 64 * ((n - 12) & 7);
                    mbar_wait(sb + BAR_EMPTYA + 8 * (i & 7), ((i >> 3) & 1) ^ 1);
                    mbar_expect_tx(full, SLOT);
                    tma2d(dst, qkv ? &P.twq : &P.twg, full, c0, r0);
                    tma2d(dst + 8192, qkv ? &P.twq : &P.twu, full, c0, qkv ? r0 + 64 : r0);
                }
                prefetch_l2(P.wd + (size_t)(4 * j + warp - 8) * 44032, 88064);
            }
            return;
        }
        if (warp == 8) {
            asm volatile("barrier.cluster.wait.aligned;" ::: "memory");
            if (elect_one()) {
                if (m >= 6)
                    asm volatile("cp.async.bulk.prefetch.tensor.2d.L2.global [%0, {%1, %2}];" ::"l"(&P.twq), "r"(DM + DM * (m & 1) + 64 * j), "r"(64 * (m >> 1)) : "memory");
                if (j >= 3)
                    asm volatile("cp.async.bulk.prefetch.tensor.2d.L2.global [%0, {%1, %2}];" ::"l"(&P.tx), "r"(64 * j), "r"(128 * m) : "memory");
                Ring r{2, 0};
                const uint32_t dst = sb + OFF_B + rank * 8192;
#define B_LOAD(TM, C0, R0)                                                                                  \
        mbar_waitc(sb + BAR_EMPTYB + 8 * r.slot, r.phase ^ 1);                                              \
        mbar_expect_tx(sb + BAR_FULLB + 8 * r.slot, SLOT);                                                  \
        tma2d_mc(dst + r.slot * SLOT, TM, sb + BAR_FULLB + 8 * r.slot, C0, R0);
#pragma unroll 1
                for (int i = 2; i < 8; i++) {
                    if (i >= AHEAD && i < 6) mbar_waitc(sb + BAR_FULLB + 8 * (i - AHEAD), 0);
                    B_LOAD(&P.twq, DM + DM * rank + 64 * j, 64 * i)
                    r.adv();
                }
#pragma unroll 1
                for (int i = 8; i < 20; i++) {
                    if (i < 12) {
                        mbar_waitc(sb + BAR_EMPTYB + 8 * r.slot, r.phase ^ 1);
                        mbar_arrive(sb + BAR_FULLB + 8 * r.slot);
                    } else {
                        const int e = 2 * (i & 3) + rank;
                        B_LOAD(i < 16 ? &P.twq : &P.two, 64 * j, 64 * (i < 16 ? e : KORD(e, j)))
                    }
                    r.adv();
                }
#pragma unroll 1
                for (int i = 0; i < 24; i++) {
                    B_LOAD(&P.twg + rank, 176 * j + 8 * (i & ~7), 64 * (i < 8 ? KORD(i, j) : i & 7))
                    r.adv5();
                }
#pragma unroll 1
                for (int i = 0; i < 12; i++) {
                    B_LOAD(&P.twd, 64 * j, 176 * (2 * (i & 3) + rank) + 64 * (i >> 2))
                    r.adv5();
                }
            }
            return;
        }
        if (warp == 9) {
            if (elect_one()) {
#pragma unroll 1
                for (int i = 2; i < 8; i++) {
                    if (i >= AHEAD + 1) mbar_wait(sb + BAR_FULLA + 8 * (i - AHEAD - 1), 0);
                    mbar_expect_tx(sb + BAR_FULLA + 8 * i, SLOT);
                    tma2d(sb + OFF_A + i * SLOT, &P.tx, sb + BAR_FULLA + 8 * i, 64 * i, 128 * m);
                }
#pragma unroll 1
                for (int i = 2; i < 7; i++) prefetch_tmap(&P.tx + i);
                unsigned nf = 0;
#pragma unroll 1
                for (int r = 1; r < 6; r++) {
                    const int skip = r < 3 ? j : 8;
                    const uint4* src = g_act + ((r - 1) * 128 + m * 8) * 1024;
                    const unsigned* fl = g_flag + (m * 5 + r - 1) * 32;
                    if (r < 4) mbar_wait(sb + BAR_EMPTYA + 8 * (r == 3 ? PF_DELAY : (j ^ 2)), (r - 1) & 1);
                    if (r < 4 || nf != epoch * 8) wait_count(fl, epoch * (r < 3 ? 64 : 8));
                    TL(64 + r, true);
#pragma unroll 1
                    for (int t = 0; t < 8; t++) {
                        if (t == skip) continue;
                        if (t == 6) nf = readback(fl + 32);
                        mbar_wait(sb + BAR_EMPTYA + 8 * t, (r - 1) & 1);
                        mbar_expect_tx(sb + BAR_FULLA + 8 * t, SLOT);
                        asm volatile("cp.async.bulk.shared::cluster.global.mbarrier::complete_tx::bytes [%0], [%1], %2, [%3];"
                                     ::"r"(sb + OFF_A + t * SLOT), "l"(src + t * 1024), "r"(SLOT), "r"(sb + BAR_FULLA + 8 * t) : "memory");
                    }
                }
            }
            return;
        }
        const int a = warp - 10;
        {
            const int row = 16 * j + 8 * a + (lane >> 2);
            const uint32_t ra = sb + OFF_A + row * 128;
            float sh = 0.f, s0 = 0.f, s1 = 0.f, q0 = 0.f, q1 = 0.f;
#pragma unroll 1
            for (int kt = 0; kt < 8; kt++) {
                mbar_wait(sb + BAR_FULLA + 8 * kt, 0);
                if (kt == 0) sh = bf_lo(lds128(ra + ((row & 7) << 4)).x);
#pragma unroll
                for (int i = 0; i < 2; i++) {
                    const uint4 v = lds128(ra + kt * SLOT + (((2 * (lane & 3) + i) ^ (row & 7)) << 4));
                    const uint32_t ww[4] = {v.x, v.y, v.z, v.w};
#pragma unroll
                    for (int e = 0; e < 4; e++) {
                        const float d0 = bf_lo(ww[e]) - sh, d1 = bf_hi(ww[e]) - sh;
                        s0 += d0; q0 = fmaf(d0, d0, q0);
                        s1 += d1; q1 = fmaf(d1, d1, q1);
                    }
                }
            }
            s0 += s1; q0 += q1;
#pragma unroll
            for (int o = 1; o <= 2; o <<= 1) { s0 += __shfl_xor_sync(0xffffffffu, s0, o); q0 += __shfl_xor_sync(0xffffffffu, q0, o); }
            const float md = s0 * (1.f / DM);
            const float rs = rsqrtf(fmaxf(q0 * (1.f / DM) - md * md, 0.f) + 1e-5f);
            st_tagged_if(g_xstat + 2 * (128 * m + row), rs, -(sh + md), epoch, (lane & 3) == 0);
            TL(1, lane == 0 && a == 0);
        }
        const unsigned long long* cs = g_cs + j * 768 + 2 * lane;
        {
            const unsigned long long* xs = g_xstat + 2 * (128 * m + 64 * a + lane);
            uint4 v0, v1, v2;
            uint32_t it = 0;
            do {
                v0 = ld_tagged_rlx(xs); v1 = ld_tagged_rlx(xs + 64); v2 = ld_tagged_rlx(cs);
                trap_if_gt(++it, 1u << 22);
            } while (__any_sync(0xffffffffu, v0.y != epoch || v0.w != epoch || v1.y != epoch || v1.w != epoch || v2.y != epoch || v2.w != epoch));
            sts64(sb + OFF_XST + (64 * a + lane) * 8, v0.x, v0.z);
            sts64(sb + OFF_XST + (64 * a + 32 + lane) * 8, v1.x, v1.z);
            sts64(sb + OFF_CS1 + 256 + 8 * lane, v2.x, v2.z);
            mbar_arrive(sb + BAR_CS1);
            TL(22 + a, lane == 0);
            fetch_tagged(cs + 128 + 128 * a, sb + OFF_CS1 + 512 - 512 * a + 8 * lane, epoch);
            mbar_arrive(sb + BAR_CSV - 8 * a);
            TL(24 + a, lane == 0);
        }
        {
            mbar_wait(sb + BAR_KVW, 0);
            const float* src = acc_j + 4 * (128 * a + lane);
            float4 v[12];
            uint32_t it = 0;
            bool bad;
            while (__any_sync(0xffffffffu, readback(acc_j + 2048 + 128 * (lane & 7) + 127) != 0x41800000u)) trap_if_gt(++it, 1u << 22);
            TL(19, lane == 0 && a == 0);
            do {
                bad = false;
#pragma unroll
                for (int i = 0; i < 12; i++) v[i] = ld_l2_f4(src + 1024 * (i % 3) + 128 * (i / 3));
#pragma unroll
                for (int i = 0; i < 12; i++) bad |= v[i].w != 16.f;
                trap_if_gt(++it, 1u << 22);
            } while (__any_sync(0xffffffffu, bad));
            TL(14, lane == 0 && a == 0);
            mbar_wait(sb + BAR_EMPTYB, 0);
            const uint32_t d0 = sb + OFF_A + (j ^ 1) * SLOT + (64 * a + (lane >> 2)) * 48;
            const uint32_t d = d0 + (lane & 3) * 4, dz = d0 + (lane & 1) * 384 + 32 + (lane & 2) * 4;
#pragma unroll
            for (int u = 0; u < 4; u++) {
                sts32(d + 768 * u, pack_bf16(v[3 * u].x, v[3 * u].y));
                sts32(d + 768 * u + 384, pack_bf16(v[3 * u].z, v[3 * u + 1].z));
                sts32(d + 768 * u + 16, pack_bf16(v[3 * u + 1].x, v[3 * u + 1].y));
                sts32(d + 768 * u + 400, pack_bf16(v[3 * u + 2].x, v[3 * u + 2].y));
                const uint32_t z2 = pack_bf16(v[3 * u + 2].z, v[3 * u + 2].z);
                sts64(dz + 768 * u, z2, z2);
            }
            mbar_arrive(sb + BAR_KVR);
        }
#pragma unroll 1
        for (int c = 0; c < 3; c++) {
            fetch_tagged(cs + 384 + 128 * c + 64 * a, sb + OFF_CS3 + (32 * c + lane) * 16 + 8 * a, epoch);
            mbar_arrive(sb + BAR_CSG + 8 * c);
            TL(45 + c, lane == 0 && a == 0);
        }
        {
            uint32_t it = 0;
            while (__any_sync(0xffffffffu, (int)(readback(g_flag + (m * 5 + 1) * 32) - epoch * 64) < 0)) {
                __nanosleep(200);
                trap_if_gt(++it, 1u << 22);
            }
#pragma unroll 1
            for (int rr = 0; rr < 2; rr++) {
                const int row = 64 * rr + 32 * a + lane;
                const unsigned long long* hs = g_hstat + (1024 * m + row) * 2;
                uint4 v[8];
                bool bad;
                do {
                    bad = false;
#pragma unroll
                    for (int i = 0; i < 8; i++) v[i] = ld_tagged_rlx(hs + 256 * i);
#pragma unroll
                    for (int i = 0; i < 8; i++) bad |= v[i].y != epoch || v[i].w != epoch;
                    trap_if_gt(++it, 1u << 22);
                } while (__any_sync(0xffffffffu, bad));
                float mean = 0.f;
#pragma unroll
                for (int i = 0; i < 8; i++) mean += __uint_as_float(v[i].x);
                mean *= 0.125f;
                float m2 = 0.f, dv = 0.f;
#pragma unroll
                for (int i = 0; i < 8; i++) { const float d = __uint_as_float(v[i].x) - mean; m2 += __uint_as_float(v[i].z); dv = fmaf(d, d, dv); }
                sts_f2(sb + OFF_CS1 + row * 8, -mean, rcp(fmaf(dv, 64.f, m2) * (1.f / DM) + 1e-5f));
            }
        }
        mbar_arrive(sb + BAR_CS3);
#pragma unroll 1
        for (int c = a; c < 3; c += 2) {
            mbar_wait(sb + BAR_STG + 8 * c, 0);
            if (elect_one()) {
                asm volatile("cp.async.bulk.global.shared::cta.bulk_group [%0], [%1], %2;" ::"l"(g_act + ((2 + c) * 128 + role) * 1024), "r"(sb + OFF_B + 4 * SLOT), "r"(SLOT) : "memory");
                asm volatile("cp.async.bulk.commit_group;" ::: "memory");
                asm volatile("cp.async.bulk.wait_group.read 0;" ::: "memory");
                mbar_arrive(sb + BAR_FULLB + 8 * 4);
                asm volatile("cp.async.bulk.wait_group 0;" ::: "memory");
            }
            __syncwarp();
            TL(60 + c, lane == 0);
            uint32_t ack = 0;
            const uint4* rb = g_act + ((2 + c) * 128 + role) * 1024 + lane * 8;
#pragma unroll
            for (int i = 0; i < 4; i++) ack |= readback(rb + 256 * i);
            signal_after(g_flag + (m * 5 + 2 + c) * 32, ack, P.zero, lane == 0);
            TL(54 + c, lane == 0);
        }
        return;
    }
    const unsigned epoch = ld_relaxed(&g_epoch);
    uint32_t wraw[16];
    if (!helper) {
        const uint32_t* wp = reinterpret_cast<const uint32_t*>(P.wphi) + (4 * j) * 128 + (lane & 3) * 16 + (lane >> 2);
#pragma unroll
        for (int i = 0; i < 16; i++)
            asm volatile("ld.global.nc.u32 %0, [%1];" : "=r"(wraw[i]) : "l"(wp + (i >> 2) * 128 + ((i >> 1) & 1) * 64 + (i & 1) * 8));
    }
    asm volatile("barrier.cluster.arrive.relaxed.aligned;" ::: "memory");
    asm volatile("setmaxnreg.inc.sync.aligned.u32 216;");
    bar_sync(0, NTHREADS);
    if (helper) {
        const int w = warp >> 2;
        sts64(sb + OFF_B + 8 * tid, 0x3f803f80u, 0x3f803f80u);
        fence_async_smem();
        uint32_t zack[6];
        {
            float* z = g_acc + 2 * j * ACC_SIZE + 4 * tid;
#pragma unroll
            for (int u = 0; u < 6; u++) stg128(z + 1024 * u, 0, 0, 0, 0);
#pragma unroll
            for (int u = 0; u < 6; u++) zack[u] = readback(z + 1024 * u);
        }
        bar_sync(1, 256);
        TL(70, tid == 0);
        float acc[8];
        int i = w;
#pragma unroll 1
        for (int job = 0; job < 6; job++) {
            const int n = job < 3 ? 4 : 8;
#pragma unroll 1
            for (int t = 0; t < n; t++, i += 2) {
                mbar_waitc(sb + BAR_FULLA + 8 * (i & 7), (i >> 3) & 1);
                const desc_t da = desc_lo(sb + OFF_A) + (i & 7) * (SLOT >> 4);
                wg_fence();
#pragma unroll
                for (int k = 0; k < 8; k++) wgmma_n8_tt(acc + (k & 4), da + 128 * k, desc_lo(sb + OFF_B), (t | (k & 3)) != 0);
                wg_commit();
                wg_wait<0>();
                mbar_arrive_n_if(sb + BAR_EMPTYA + 8 * (i & 7), 2, lane == 0);
            }
            fence_acc<8>(acc);
            TL(71 + job, tid == 0);
            if (job == 1) {
                asm volatile("{.reg .pred p; .reg .b32 t; lop3.b32 t, %0, %1, %2, 0xfe; lop3.b32 t, t, %3, %4, 0xfe; or.b32 t, t, %5; setp.ne.u32 p, t, 0; @p trap;}"
                             ::"r"(zack[0]), "r"(zack[1]), "r"(zack[2]), "r"(zack[3]), "r"(zack[4]), "r"(zack[5]));
                bar_sync(1, 256);
            }
            const int q = lane & 3;
            const float lo = (q & 1) ? acc[2] : acc[0], hi = (q & 1) ? acc[6] : acc[4];
            const float v = job < 3 ? lo + hi : ((q & 2) ? hi : lo);
            unsigned long long* dst = g_cs + ((2 * j + w) * 6 + job) * 128 + (q >> 1) * 64 + 16 * (warp & 3) + 8 * (q & 1) + (lane >> 2);
            asm volatile("st.relaxed.gpu.global.b64 [%0], %1;" ::"l"(dst), "l"(((unsigned long long)epoch << 32) | __float_as_uint(v)) : "memory");
        }
        return;
    }
    {
        const int w = warp >> 2, wv = warp & 3, g = lane >> 2, q = lane & 3;
        const uint32_t sa = sb + OFF_A + w * 8192;
        const desc_t dA = desc_lo(sa), dB = desc_lo(sb + OFF_B);
        unsigned* const flag_m = g_flag + m * 160;
        const bool l0 = lane == 0, l2 = lane < 2;
        const uint32_t eb = mapa(sb + BAR_EMPTYB, lane & 1);
        asm volatile("barrier.cluster.wait.aligned;" ::: "memory");
        Ring rg{0, 0};
        int prev = 0;

        uint32_t wb[16];
        constexpr float L2E = 1.4426950408889634f;
        const int ch = lane >> 4, sw = lane & 7;
        const uint32_t lrow = (lane & 15) * 128;
        uint32_t fp[16], fm[16];
        {
            float acc[64];
#pragma unroll 1
            for (int kt = 0; kt < 8; kt++) {
                mbar_waitc(sb + BAR_FULLA + 8 * kt, 0);
                mbar_waitc(sb + BAR_FULLB + 8 * rg.slot, rg.phase);
                const desc_t da = dA + kt * (SLOT >> 4), db = dB + rg.slot * (SLOT >> 4);
                wg_fence();
#pragma unroll
                for (int k = 0; k < 4; k++) wgmma_n128(acc, da + 2 * k, db + 128 * k, (kt | k) != 0);
                wg_commit();
                wg_wait<1>();
                mbar_arrive_cl_if(eb + 8 * prev, l2 && kt > 0);
                prev = rg.slot; rg.adv();
            }
#pragma unroll
            for (int i = 0; i < 8; i++) {
                wb[(i >> 1) * 4 + (i & 1)] = __byte_perm(wraw[2 * i], wraw[2 * i + 1], 0x5410);
                wb[(i >> 1) * 4 + 2 + (i & 1)] = __byte_perm(wraw[2 * i], wraw[2 * i + 1], 0x7632);
            }
            uint32_t a[16];
#pragma unroll
            for (int i = 2; i < 6; i++) mbar_waitc(sb + BAR_FULLB + 8 * i, 1);
            TL(17, tid == 0);
            mbar_waitc(sb + BAR_CS1, 0);
            const float2 s0 = lds_f2(sb + OFF_XST + (16 * warp + g) * 8), s1 = lds_f2(sb + OFF_XST + (16 * warp + g + 8) * 8);
            wg_wait<0>();
            fence_acc<64>(acc);
            mbar_arrive_cl_if(eb + 8 * prev, l2);
            TL(2, tid == 0);
            const uint32_t st = sb + OFF_B + 2 * SLOT + warp * 2048 + lrow;
#pragma unroll
            for (int hh = 0; hh < 4; hh++)
                ln_frag<false>(acc + 8 * hh, sb + OFF_CS1 + (64 + 16 * hh + 2 * q) * 4, 0.f, s0.y, 0.f, s1.y, a + 4 * hh);
#pragma unroll 1
            for (int it = 0; it < 2; it++) {
                feature_maps(a, wb, s0.x * L2E, s1.x * L2E, fp, fm);
                if (it == 0) {
#pragma unroll
                    for (int hh = 0; hh < 4; hh++) {
                        stsm4(st + (hh >> 1) * SLOT + (((4 * (hh & 1) + ch) ^ sw) << 4), fp[4 * hh], fp[4 * hh + 1], fp[4 * hh + 2], fp[4 * hh + 3]);
                        stsm4(st + (hh >> 1) * SLOT + (((4 * (hh & 1) + 2 + ch) ^ sw) << 4), fm[4 * hh], fm[4 * hh + 1], fm[4 * hh + 2], fm[4 * hh + 3]);
                    }
                    mbar_waitc(sb + BAR_CSV, 0);
#pragma unroll
                    for (int hh = 0; hh < 4; hh++) {
                        ln_frag<true>(acc + 32 + 8 * hh, sb + OFF_CS1 + (128 + 16 * hh + 2 * q) * 4, s0.x, s0.y, s1.x, s1.y, a);
                        stsm4(st + (2 + (hh >> 1)) * SLOT + (((2 * (hh & 1) + ch) ^ sw) << 4), a[0], a[1], a[2], a[3]);
                    }
                    stsm4(st + (2 + ch) * SLOT + ((4 ^ sw) << 4), 0x3f803f80u, 0x3f803f80u, 0x3f803f80u, 0x3f803f80u);
                    fence_async_smem();
                    bar_sync(1, 256);
                    float kvd[20];
                    wg_fence();
#pragma unroll
                    for (int k = 0; k < 8; k++)
                        wgmma_n40_tt(kvd, dB + (2 + w) * (SLOT >> 4) + 128 * k, dB + (4 + w) * (SLOT >> 4) + 128 * k, k != 0);
                    wg_commit();
                    wg_wait<0>();
                    fence_acc<20>(kvd);
                    mbar_arrive_cl_if(eb + 8 * (2 + (lane >> 1)), lane < 8);
                    const bool h1 = wv >= 2;
                    float* kvp = acc_j + 4 * tid;
                    red_f32x4(kvp, h1 ? kvd[8] : kvd[0], h1 ? kvd[9] : kvd[1], h1 ? kvd[10] : kvd[2], 1.f);
                    red_f32x4(kvp + 1024, h1 ? kvd[12] : kvd[4], h1 ? kvd[13] : kvd[5], h1 ? kvd[11] : kvd[3], 1.f);
                    red_f32x4(kvp + 2048, h1 ? kvd[14] : kvd[6], h1 ? kvd[15] : kvd[7], (q & 1) ? kvd[18] : kvd[16], 1.f);
                    mbar_arrive_if(sb + BAR_KVW, l0);
                    TL(3, tid == 0);
                    float accq[32];
#pragma unroll 1
                    for (int b = 0; b < 4; b++) {
                        mbar_waitc(sb + BAR_FULLB + 8 * b, 0);
                        const desc_t da = dA + b * (2 * SLOT >> 4), db = dB + b * (SLOT >> 4);
                        wg_fence();
#pragma unroll
                        for (int k = 0; k < 8; k++) wgmma_n64(accq, da + (k >> 2) * (SLOT >> 4) + (k & 3) * 2, db + 128 * k, (b | k) != 0);
                        wg_commit();
                    }
                    mbar_waitc(sb + BAR_CSQ, 0);
                    wg_wait<0>();
                    fence_acc<32>(accq);
                    mbar_arrive_cl_if(eb + 8 * (lane >> 1), lane < 8);
                    TL(4, tid == 0);
#pragma unroll
                    for (int hh = 0; hh < 4; hh++)
                        ln_frag<false>(accq + 8 * hh, sb + OFF_CS1 + (16 * hh + 2 * q) * 4, 0.f, s0.y, 0.f, s1.y, a + 4 * hh);
                }
            }
        }
        uint32_t res_lo[8], res_hi[8], ack[4];
        const uint32_t own_rows = sb + OFF_A + j * SLOT + warp * 2048;
#pragma unroll
        for (int b = 0; b < 4; b++)
            ldsm4(own_rows + lrow + (((2 * b + ch) ^ sw) << 4), res_lo[2 * b], res_hi[2 * b], res_lo[2 * b + 1], res_hi[2 * b + 1]);
        mbar_arrive_if(sb + BAR_EMPTYA + 8 * lane, lane < 8 && (lane | 1) != (j | 1));
        TL(5, tid == 0);
        mbar_waitc(sb + BAR_KVR, 0);
        TL(6, tid == 0);
        {
            const uint32_t kvs = sb + OFF_A + (j ^ 1) * SLOT;
            uint32_t o_lo[8], o_hi[8];
#pragma unroll
            for (int hh = 0; hh < 4; hh++) {
                uint32_t b[8], zb[4];
                const uint32_t base = kvs + hh * 32 * 48;
                ldsm4t(base + (lane & 15) * 48 + (lane >> 4) * 16, b[0], b[1], b[2], b[3]);
                ldsm4t(base + (16 + (lane & 15)) * 48 + (lane >> 4) * 16, b[4], b[5], b[6], b[7]);
                ldsm4t(base + lane * 48 + 32, zb[0], zb[1], zb[2], zb[3]);
                float n0[4], n1[4], dn[4];
                mma16816_z(n0, fp + 4 * hh, b[0], b[1]); mma16816_z(n1, fp + 4 * hh, b[2], b[3]); mma16816_z(dn, fp + 4 * hh, zb[0], zb[1]);
                mma16816(n0, fm + 4 * hh, b[4], b[5]); mma16816(n1, fm + 4 * hh, b[6], b[7]); mma16816(dn, fm + 4 * hh, zb[2], zb[3]);
                const float i0 = rcp(dn[0] + 1e-6f), i1 = rcp(dn[2] + 1e-6f);
                o_lo[2 * hh] = pack_bf16(n0[0] * i0, n0[1] * i0); o_hi[2 * hh] = pack_bf16(n0[2] * i1, n0[3] * i1);
                o_lo[2 * hh + 1] = pack_bf16(n1[0] * i0, n1[1] * i0); o_hi[2 * hh + 1] = pack_bf16(n1[2] * i1, n1[3] * i1);
            }
            __syncwarp();
            mbar_arrive_if(sb + BAR_EMPTYA + 8 * (j ^ 1), l0);
            rg.slot = 4; rg.phase = 0;
            store_tile(own_rows, g_act + role * 1024 + warp * 128 + lane, o_lo, o_hi, lane, ack);
            TL(7, tid == 0);
        }
        float acch[32];
        {
            float* acc = acch;
#pragma unroll
            for (int t = 0; t < 8; t++) {
                acc[4 * t] = bf_lo(res_lo[t]); acc[4 * t + 1] = bf_hi(res_lo[t]);
                acc[4 * t + 2] = bf_lo(res_hi[t]); acc[4 * t + 3] = bf_hi(res_hi[t]);
            }
            fence_acc<32>(acc);
            int pa = 0;
#pragma unroll 1
            for (int kp = 0; kp < 4; kp++) {
                mbar_waitc(sb + BAR_FULLB + 8 * rg.slot, rg.phase);
#pragma unroll
                for (int hf = 0; hf < 2; hf++) {
                    const int i = 2 * kp + hf, kt = KORD(i, j);
                    mbar_waitc(sb + BAR_FULLA + 8 * kt, i != 0);
                    TL(8, i == 1 && tid == 0);
                    const desc_t da = dA + kt * (SLOT >> 4), db = dB + rg.slot * (SLOT >> 4);
                    wg_fence();
#pragma unroll
                    for (int k = 0; k < 4; k++) wgmma_n64(acc, da + 2 * k, db + (hf * 4 + k) * 128, 1);
                    wg_commit();
                    wg_wait<1>();
                    mbar_arrive_if(sb + BAR_EMPTYA + 8 * pa, l0 && i > 1);
                    if (hf == 0) {
                        mbar_arrive_cl_if(eb + 8 * prev, l2 && i > 0);
                        if (i == 0) { signal_late(flag_m, ack, P.zero, l0); TL(20, tid == 0); }
                    }
                    pa = kt;
                }
                prev = rg.slot; rg.adv();
            }
            wg_wait<0>();
            fence_acc<32>(acc);
            mbar_arrive_if(sb + BAR_EMPTYA + 8 * pa, l0);
            mbar_arrive_cl_if(eb + 8 * prev, l2);
            TL(9, tid == 0);
#pragma unroll
            for (int t = 0; t < 8; t++) {
                res_lo[t] = pack_bf16(acc[4 * t], acc[4 * t + 1]);
                res_hi[t] = pack_bf16(acc[4 * t + 2], acc[4 * t + 3]);
            }
            store_tile(own_rows, g_act + (128 + role) * 1024 + warp * 128 + lane, res_lo, res_hi, lane, ack);
            TL(10, tid == 0);
        }
        float acc0[64], acc1[64], acc2[56], nm0, nm1;
        float4 cs[8];
        uint32_t hr[16];
#define P3_GROUP(MMA, ACC, KT)                                                                              \
        mbar_waitc(sb + BAR_FULLB + 8 * rg.slot, rg.phase);                                                 \
        {                                                                                                   \
            const desc_t da = dA + (KT) * (SLOT >> 4), db = dB + rg.slot * (SLOT >> 4);                     \
            wg_fence();                                                                                     \
            _Pragma("unroll") for (int k = 0; k < 4; k++) MMA(ACC, da + 2 * k, db + 128 * k, (i | k) != 0); \
            wg_commit();                                                                                    \
        }
#define P3_CS(C, NT)    \
        _Pragma("unroll") for (int t = 0; t < (NT); t++) lds_f4_if(cs[t], sb + OFF_CS3 + q * 16 + 512 * (C) + 64 * t, i == t);
#define P3_EPI2(C, ACC)                                                                                     \
        if (i == 0) {                                                                                       \
            fence_acc<64>(ACC);                                                                             \
            if (C) mbar_waitc(sb + BAR_FULLB + 8 * 4, 1);                                                   \
            hh_stage2<0, 2>(ACC, cs, nm0, nm1, stg, lane);                                                  \
            mbar_waitc(sb + BAR_CSG + 8 * (C) + 8, 0);                                                      \
        }                                                                                                   \
        if (i == 1) {                                                                                       \
            hh_stage2<2, 4>(ACC, cs, nm0, nm1, stg, lane);                                                  \
            fence_async_smem();                                                                             \
            __syncwarp();                                                                                   \
            mbar_arrive_if(sb + BAR_STG + 8 * (C), l0);                                                     \
        }
#define P3_EPI(C, ACC, N, NTP)                                                                              \
        fence_acc<N>(ACC);                                                                                  \
        TL(11 + (C), tid == 0);                                                                             \
        hh_stage<NTP>(ACC, cs, nm0, nm1, sb + OFF_B + 4 * SLOT + warp * 2048, lane);                        \
        mbar_arrive_if(sb + BAR_STG + 8 * (C), l0);                                                         \
        TL(50 + (C), tid == 0);
        const uint32_t stg = sb + OFF_B + 4 * SLOT + warp * 2048;
        const uint32_t blk = ((lane & 7) + (lane >> 4) * 8) * 128 + (((2 * wv + ((lane >> 3) & 1)) ^ (lane & 7)) << 4);
#pragma unroll 1
        for (int i = 0; i < 8; i++) {
            const int kt = KORD(i, j);
            mbar_waitc(sb + BAR_FULLA + 8 * kt, 0);
            TL(44, tid == 0 && i == 1);
            P3_GROUP(wgmma_n128, acc0, kt)
            if (i == 7) {
                mbar_waitc(sb + BAR_CS3, 0);
                nm0 = lds_f2(sb + OFF_CS1 + (16 * warp + g) * 8).x; nm1 = lds_f2(sb + OFF_CS1 + (16 * warp + g + 8) * 8).x;
            }
            wg_wait<1>();
            mbar_arrive_cl_if(eb + 8 * prev, l2 && i > 0);
            if (i == 0) {
                signal_late(flag_m + 32, ack, P.zero, l0);
                TL(21, tid == 0);
                {
                    fence_acc<32>(acch);
                    const float* acc = acch;
                    float s0 = 0.f, s1 = 0.f;
#pragma unroll
                    for (int t = 0; t < 8; t++) { s0 += acc[4 * t] + acc[4 * t + 1]; s1 += acc[4 * t + 2] + acc[4 * t + 3]; }
            s0 += __shfl_xor_sync(0xffffffffu, s0, 1); s1 += __shfl_xor_sync(0xffffffffu, s1, 1);
            s0 += __shfl_xor_sync(0xffffffffu, s0, 2); s1 += __shfl_xor_sync(0xffffffffu, s1, 2);
            const float mu0 = s0 * (1.f / 64), mu1 = s1 * (1.f / 64);
            float q0 = 0.f, q1 = 0.f;
#pragma unroll
            for (int t = 0; t < 8; t++) {
                float d;
                d = acc[4 * t] - mu0; q0 = fmaf(d, d, q0);
                d = acc[4 * t + 1] - mu0; q0 = fmaf(d, d, q0);
                d = acc[4 * t + 2] - mu1; q1 = fmaf(d, d, q1);
                d = acc[4 * t + 3] - mu1; q1 = fmaf(d, d, q1);
            }
            q0 += __shfl_xor_sync(0xffffffffu, q0, 1); q1 += __shfl_xor_sync(0xffffffffu, q1, 1);
            q0 += __shfl_xor_sync(0xffffffffu, q0, 2); q1 += __shfl_xor_sync(0xffffffffu, q1, 2);
            st_tagged_if(g_hstat + (role * 128 + 16 * warp + g + 8 * (q & 1)) * 2, q ? mu1 : mu0, q ? q1 : q0, epoch, q < 2);
                }
                bar_sync(2 + w, 128);
#pragma unroll
                for (int tp = 0; tp < 4; tp++) ldsm4t(sa + j * SLOT + blk + tp * 2048, hr[4 * tp], hr[4 * tp + 1], hr[4 * tp + 2], hr[4 * tp + 3]);
                mbar_waitc(sb + BAR_CSG, 0);
#pragma unroll
                for (int t = 0; t < 8; t++) cs[t] = lds_f4(sb + OFF_CS3 + q * 16 + 64 * t);
            }
            prev = rg.slot; rg.adv5();
        }
#pragma unroll 1
        for (int i = 0; i < 8; i++) {
            P3_GROUP(wgmma_n128, acc1, i)
            wg_wait<1>();
            mbar_arrive_cl_if(eb + 8 * prev, l2);
            P3_EPI2(0, acc0)
            P3_CS(1, 8)
            prev = rg.slot; rg.adv5();
        }
#pragma unroll 1
        for (int i = 0; i < 8; i++) {
            P3_GROUP(wgmma_n112, acc2, i)
            wg_wait<1>();
            mbar_arrive_cl_if(eb + 8 * prev, l2);
            mbar_arrive_if(sb + BAR_EMPTYA + 8 * ((i + 7) & 7), l0 && i > 0);
            if (i == 0) { mbar_waitc(sb + BAR_FULLB + 8 * 4, 1); P3_EPI(1, acc1, 64, 4) mbar_waitc(sb + BAR_CSG + 16, 0); }
            P3_CS(2, 6)
            prev = rg.slot; rg.adv5();
        }
        mbar_waitc(sb + BAR_FULLB + 8 * 4, 0);
        wg_wait<0>();
        mbar_arrive_cl_if(eb + 8 * prev, l2);
        mbar_arrive_if(sb + BAR_EMPTYA + 8 * 7, l0);
        P3_EPI(2, acc2, 56, 3)
        {
            float acc[64];
            const desc_t dA0 = desc_lo(sb + OFF_A);
#define KT_P4(I, NK)                                                                                        \
        const int s_ = (2 * (I) + w) & 7;                                                                   \
        mbar_waitc(sb + BAR_FULLB + 8 * rg.slot, rg.phase);                                                 \
        mbar_waitc(sb + BAR_FULLA + 8 * s_, (((I) >> 2) + 1) & 1);                                          \
        const desc_t dh_ = dA0 + s_ * (SLOT >> 4), dw_ = dB + rg.slot * (SLOT >> 4) + w * 512;              \
        wg_fence();                                                                                         \
        _Pragma("unroll") for (int k = 0; k < (NK); k++) wgmma_n128_tn(acc, dw_ + 128 * k, dh_ + 2 * k, ((I) | k) != 0); \
        wg_commit();                                                                                        \
        wg_wait<1>();
#pragma unroll 1
            for (int i = 0; i < 8; i++) {
                KT_P4(i, 4)
                mbar_arrive_n_if(sb + BAR_EMPTYA + 8 * ((s_ + 6) & 7), 2, l0 && i > 0);
                mbar_arrive_cl_if(eb + 8 * prev, l2 && i > 0);
#pragma unroll
                for (int t = 0; t < 8; t++) lds_f4_if(cs[t], sb + OFF_CS1 + (64 * w + 8 * t + 2 * q) * 8, i == t);
                prev = rg.slot; rg.adv5();
            }
#pragma unroll 1
            for (int i = 8; i < 12; i++) {
                KT_P4(i, 3)
                mbar_arrive_n_if(sb + BAR_EMPTYA + 8 * ((s_ + 6) & 7), 2, l0);
                rg.adv5();
            }
            wg_wait<0>();
            fence_acc<64>(acc);
            TL(15, tid == 0);
            const uint32_t xch = sb + OFF_A + 2 * SLOT + (tid & 127) * 16;
            if (w) {
#pragma unroll
                for (int t = 0; t < 8; t++) {
                    sts128(xch + SLOT + t * 2048, __float_as_uint(acc[4 * t]), __float_as_uint(acc[4 * t + 1]),
                           __float_as_uint(acc[4 * t + 2]), __float_as_uint(acc[4 * t + 3]));
                }
#pragma unroll
                for (int t = 0; t < 32; t++) acc[t] = acc[32 + t];
            } else {
#pragma unroll
                for (int t = 0; t < 8; t++)
                    sts128(xch + t * 2048, __float_as_uint(acc[32 + 4 * t]), __float_as_uint(acc[33 + 4 * t]),
                           __float_as_uint(acc[34 + 4 * t]), __float_as_uint(acc[35 + 4 * t]));
            }
            bar_sync(1, 256);
            float4 o[8];
#pragma unroll
            for (int t = 0; t < 8; t++) o[t] = lds_f4(xch + (w ^ 1) * SLOT + t * 2048);
            const uint32_t tile = sb + OFF_A + w * SLOT;
#pragma unroll
            for (int t = 0; t < 8; t++) {
                hr[2 * t] = pack_bf16(fmaf(acc[4 * t] + o[t].x, cs[t].y, bf_lo(hr[2 * t])), fmaf(acc[4 * t + 1] + o[t].y, cs[t].w, bf_hi(hr[2 * t])));
                hr[2 * t + 1] = pack_bf16(fmaf(acc[4 * t + 2] + o[t].z, cs[t].y, bf_lo(hr[2 * t + 1])), fmaf(acc[4 * t + 3] + o[t].w, cs[t].w, bf_hi(hr[2 * t + 1])));
            }
#pragma unroll
            for (int tp = 0; tp < 4; tp++) stsm4t(tile + blk + tp * 2048, hr[4 * tp], hr[4 * tp + 1], hr[4 * tp + 2], hr[4 * tp + 3]);
            fence_async_smem();
            bar_sync(2 + w, 128);
            if ((tid & 127) == 0) {
                tma_store2d(&P.tout, tile, 64 * j, 128 * m + 64 * w);
                asm volatile("cp.async.bulk.wait_group.read 0;" ::: "memory");
            }
            if (tid == 0 && role == 0) g_epoch = epoch + 1;
            TL(16, tid == 0); TLG(1, tid == 0);
        }
    }
}

__global__ void probe_kernel() {}

typedef CUresult (*EncodeFn)(CUtensorMap*, CUtensorMapDataType, cuuint32_t, void*, const cuuint64_t*, const cuuint64_t*,
                             const cuuint32_t*, const cuuint32_t*, CUtensorMapInterleave, CUtensorMapSwizzle,
                             CUtensorMapL2promotion, CUtensorMapFloatOOBfill);

static void make_map2d(EncodeFn enc, CUtensorMap* tm, const void* base, uint64_t cols, uint64_t rows, uint64_t pitch_elems,
                       uint32_t box_rows) {
    cuuint64_t gd[2] = {cols, rows};
    cuuint64_t gs[1] = {pitch_elems * 2};
    cuuint32_t bd[2] = {64, box_rows};
    cuuint32_t es[2] = {1, 1};
    enc(tm, CU_TENSOR_MAP_DATA_TYPE_BFLOAT16, 2, const_cast<void*>(base), gd, gs, bd, es, CU_TENSOR_MAP_INTERLEAVE_NONE,
        CU_TENSOR_MAP_SWIZZLE_128B, CU_TENSOR_MAP_L2_PROMOTION_L2_256B, CU_TENSOR_MAP_FLOAT_OOB_FILL_NONE);
}

}

extern "C" void kernel_launch(void* const* d_in, const int* in_sizes, int n_in, void* d_out, int out_size) {
    using namespace hk;
    (void)in_sizes; (void)n_in; (void)out_size;
    static EncodeFn enc = nullptr;
    static int std_layout = 0;
    if (!enc) {
        void* fn = nullptr;
        cudaDriverEntryPointQueryResult qr;
        cudaGetDriverEntryPoint("cuTensorMapEncodeTiled", &fn, cudaEnableDefault, &qr);
        enc = (EncodeFn)fn;
        cudaFuncSetAttribute(fused_kernel, cudaFuncAttributeMaxDynamicSharedMemorySize, SMEM_BYTES);
        int dev = 0, sms = 0;
        cudaGetDevice(&dev);
        cudaDeviceGetAttribute(&sms, cudaDevAttrMultiProcessorCount, dev);
        cudaFuncSetAttribute(probe_kernel, cudaFuncAttributeNonPortableClusterSizeAllowed, 1);
        cudaFuncSetAttribute(probe_kernel, cudaFuncAttributeMaxDynamicSharedMemorySize, SMEM_BYTES);
        const int sizes[3] = {8, 9, 16}, want[3] = {15, 9, 7};
        bool ok = sms == NCTA;
        for (int i = 0; i < 3 && ok; i++) {
            cudaLaunchConfig_t cfg = {};
            cfg.gridDim = dim3(sizes[i] * 8); cfg.blockDim = dim3(NTHREADS); cfg.dynamicSmemBytes = SMEM_BYTES;
            cudaLaunchAttribute at;
            at.id = cudaLaunchAttributeClusterDimension;
            at.val.clusterDim.x = sizes[i]; at.val.clusterDim.y = 1; at.val.clusterDim.z = 1;
            cfg.attrs = &at; cfg.numAttrs = 1;
            int n = 0;
            ok = cudaOccupancyMaxActiveClusters(&n, probe_kernel, &cfg) == cudaSuccess && n == want[i];
        }
        (void)cudaGetLastError();
        std_layout = ok ? 1 : 0;
    }
    Params P;
    const __nv_bfloat16* x = (const __nv_bfloat16*)d_in[0];
    P.x = x;
    P.wqkv = (const __nv_bfloat16*)d_in[1];
    P.wphi = (const __nv_bfloat16*)d_in[2];
    P.wo = (const __nv_bfloat16*)d_in[3];
    P.wg = (const __nv_bfloat16*)d_in[5];
    P.wu = (const __nv_bfloat16*)d_in[6];
    P.wd = (const __nv_bfloat16*)d_in[7];
    P.out = (__nv_bfloat16*)d_out;
    P.zero = 0;
    for (int i = 0; i < NCTA; i++) {
        const int odd = i & 1;
        int role = i < 4 ? 128 + i : (((i - 4) >> 4) * 2 + odd) * 8 + (((i - 4) >> 1) & 7);
        if (std_layout) {
            const int tpc = i < 8 ? 62 + (i >> 1) : (i - 8) >> 1;
            if (tpc < 32) role = (tpc & 7) ? (2 * ((tpc & 7) - 1) + odd) * 8 + (tpc >> 3) : (14 + odd) * 8 + (tpc >> 3);
            else if (tpc < 60) role = (2 * ((tpc - 32) % 7) + odd) * 8 + 4 + (tpc - 32) / 7;
            else if (tpc < 62) role = 128 + (tpc - 60) * 2 + odd;
            else role = (14 + odd) * 8 + 4 + (tpc - 62);
        }
        P.role[i] = (unsigned char)role;
    }
    make_map2d(enc, &P.tx, x, DM, SEQ, DM, 128);
    make_map2d(enc, &P.twq, P.wqkv, 3 * DM, DM, 3 * DM, 64);
    make_map2d(enc, &P.two, P.wo, DM, DM, DM, 64);
    make_map2d(enc, &P.twg, P.wg, FF, DM, FF, 64);
    make_map2d(enc, &P.twu, P.wu, FF, DM, FF, 64);
    make_map2d(enc, &P.twd, P.wd, DM, FF, DM, 64);
    make_map2d(enc, &P.tout, d_out, DM, SEQ, DM, 64);
    fused_kernel<<<NCTA, NTHREADS, SMEM_BYTES>>>(P);
}
```

```cpp
#include <cuda_runtime.h>
#include <cuda_bf16.h>
#include <cuda.h>
#include <stdint.h>

namespace hk {

constexpr int SEQ = 2048, DM = 512, FF = 1376;
constexpr int NCTA = 132;
constexpr int NTHREADS = 384;
constexpr uint32_t SLOT = 16384;
constexpr uint32_t OFF_A = 0, OFF_B = 8 * SLOT, OFF_MISC = 14 * SLOT;
constexpr uint32_t BAR_FULLA = OFF_MISC + 0, BAR_EMPTYA = OFF_MISC + 64, BAR_FULLB = OFF_MISC + 128,
                   BAR_EMPTYB = OFF_MISC + 176, BAR_CS1 = OFF_MISC + 224, BAR_CS3 = OFF_MISC + 232,
                   BAR_CSQ = OFF_MISC + 240, BAR_CSV = OFF_MISC + 248,
                   BAR_STG = OFF_MISC + 256,
                   BAR_KVW = OFF_MISC + 280, BAR_KVR = OFF_MISC + 288, BAR_CSG = OFF_MISC + 296;
constexpr uint32_t OFF_CS1 = OFF_MISC + 384;
constexpr uint32_t OFF_CS3 = OFF_CS1 + 1024;
constexpr uint32_t OFF_XST = OFF_CS3;
constexpr uint32_t SMEM_BYTES = OFF_CS3 + 1536;
#define KORD(i, j) ((i) == 0 ? (j) : (i) - ((i) <= (j)))
constexpr int NB = 6;
#define PF_DELAY 2
#define KV_POLL 1
constexpr int AHEAD = 3;

constexpr int ACC_SIZE = 3 * 256 * 4;

__device__ __align__(1024) uint4 g_act[5 * 128 * 1024];
__device__ __align__(128) unsigned long long g_hstat[SEQ * 16];
__device__ __align__(128) unsigned long long g_xstat[SEQ * 2];
__device__ __align__(128) float g_acc[8 * ACC_SIZE];
__device__ __align__(128) unsigned long long g_cs[8 * 6 * 128];
__device__ __align__(128) unsigned g_flag[16 * 5 * 32 + 32];
__device__ unsigned g_epoch = 1;

#define TL(i, pred) do {} while (0)
#define TLG(i, pred) do {} while (0)

struct Params {
    CUtensorMap tx, twq, two, twg, twu, twd, tout;
    const __nv_bfloat16 *x, *wqkv, *wphi, *wo, *wg, *wu, *wd;
    __nv_bfloat16* out;
    unsigned zero;
    unsigned char role[NCTA];
};

__device__ __forceinline__ uint32_t smem_u32(const void* p) { return (uint32_t)__cvta_generic_to_shared(p); }
__device__ __forceinline__ void mbar_init(uint32_t bar, uint32_t cnt) {
    asm volatile("mbarrier.init.shared::cta.b64 [%0], %1;" ::"r"(bar), "r"(cnt) : "memory");
}
__device__ __forceinline__ void mbar_expect_tx(uint32_t bar, uint32_t bytes) {
    asm volatile("mbarrier.arrive.expect_tx.shared::cta.b64 _, [%0], %1;" ::"r"(bar), "r"(bytes) : "memory");
}
__device__ __forceinline__ void mbar_arrive(uint32_t bar) {
    asm volatile("mbarrier.arrive.shared::cta.b64 _, [%0];" ::"r"(bar) : "memory");
}
__device__ __forceinline__ void mbar_arrive_if(uint32_t bar, bool pred) {
    asm volatile("{.reg .pred p; setp.ne.u32 p, %1, 0; @p mbarrier.arrive.shared::cta.b64 _, [%0];}" ::"r"(bar), "r"((uint32_t)pred) : "memory");
}
__device__ __forceinline__ bool mbar_try(uint32_t bar, uint32_t parity) {
    uint32_t ok;
    asm volatile("{.reg .pred p; mbarrier.try_wait.parity.shared::cta.b64 p, [%1], %2; selp.u32 %0,1,0,p;}"
                 : "=r"(ok) : "r"(bar), "r"(parity) : "memory");
    return ok;
}
__device__ __forceinline__ bool mbar_test(uint32_t bar, uint32_t parity) {
    uint32_t ok;
    asm volatile("{.reg .pred p; mbarrier.test_wait.parity.shared::cta.b64 p, [%1], %2; selp.u32 %0,1,0,p;}"
                 : "=r"(ok) : "r"(bar), "r"(parity) : "memory");
    return ok;
}
__device__ __forceinline__ void trap_if_gt(uint32_t v, uint32_t lim) {
    asm volatile("{.reg .pred p; setp.gt.u32 p, %0, %1; @p trap;}" ::"r"(v), "r"(lim));
}
__device__ __forceinline__ void mbar_wait(uint32_t bar, uint32_t parity) {
    asm volatile("{\n"
                 ".reg .pred P1, P2;\n"
                 ".reg .u32 c;\n"
                 "mov.u32 c, 0;\n"
                 "LAB_WAIT:\n"
                 "mbarrier.try_wait.parity.shared::cta.b64 P1, [%0], %1;\n"
                 "@P1 bra LAB_DONE;\n"
                 "add.u32 c, c, 1;\n"
                 "setp.gt.u32 P2, c, 4194304;\n"
                 "@P2 trap;\n"
                 "bra LAB_WAIT;\n"
                 "LAB_DONE:\n"
                 "}" ::"r"(bar), "r"(parity) : "memory");
}
__device__ __forceinline__ void mbar_waitc(uint32_t bar, uint32_t parity) {
    asm volatile("{\n"
                 ".reg .pred P1;\n"
                 "LAB_WAIT:\n"
                 "mbarrier.try_wait.parity.shared::cta.b64 P1, [%0], %1;\n"
                 "@!P1 bra LAB_WAIT;\n"
                 "}" ::"r"(bar), "r"(parity) : "memory");
}
__device__ __forceinline__ void tma2d(uint32_t dst, const CUtensorMap* tm, uint32_t bar, int c0, int c1) {
    asm volatile("cp.async.bulk.tensor.2d.shared::cluster.global.mbarrier::complete_tx::bytes [%0], [%1, {%3, %4}], [%2];"
                 ::"r"(dst), "l"(tm), "r"(bar), "r"(c0), "r"(c1) : "memory");
}
__device__ __forceinline__ void tma2d_mc(uint32_t dst, const CUtensorMap* tm, uint32_t bar, int c0, int c1) {
    asm volatile("cp.async.bulk.tensor.2d.shared::cluster.global.mbarrier::complete_tx::bytes.multicast::cluster [%0], [%1, {%3, %4}], [%2], %5;"
                 ::"r"(dst), "l"(tm), "r"(bar), "r"(c0), "r"(c1), "h"((uint16_t)3) : "memory");
}
__device__ __forceinline__ uint32_t mapa(uint32_t addr, uint32_t rank) {
    uint32_t r; asm("mapa.shared::cluster.u32 %0, %1, %2;" : "=r"(r) : "r"(addr), "r"(rank)); return r;
}
__device__ __forceinline__ void mbar_arrive_cl_if(uint32_t cbar, bool pred) {
    asm volatile("{.reg .pred p; setp.ne.u32 p, %1, 0; @p mbarrier.arrive.shared::cluster.b64 _, [%0];}" ::"r"(cbar), "r"((uint32_t)pred) : "memory");
}
__device__ __forceinline__ bool elect_one() {
    uint32_t ok;
    asm volatile("{.reg .pred p; elect.sync _|p, 0xffffffff; selp.u32 %0, 1, 0, p;}" : "=r"(ok));
    return ok;
}
__device__ __forceinline__ void prefetch_tmap(const CUtensorMap* tm) {
    asm volatile("prefetch.tensormap [%0];" ::"l"(tm) : "memory");
}
__device__ __forceinline__ void prefetch_l2(const void* p, uint32_t bytes) {
    asm volatile("cp.async.bulk.prefetch.L2.global [%0], %1;" ::"l"(p), "r"(bytes) : "memory");
}
__device__ __forceinline__ unsigned ld_acquire(const unsigned* p) {
    unsigned v; asm volatile("ld.acquire.gpu.global.u32 %0, [%1];" : "=r"(v) : "l"(p) : "memory"); return v;
}
__device__ __forceinline__ uint4 ld_acquire4(const unsigned* p) {
    uint4 v;
    asm volatile("ld.acquire.gpu.global.v4.u32 {%0,%1,%2,%3}, [%4];" : "=r"(v.x), "=r"(v.y), "=r"(v.z), "=r"(v.w) : "l"(p) : "memory");
    return v;
}
__device__ __forceinline__ unsigned ld_relaxed(const unsigned* p) {
    unsigned v; asm volatile("ld.relaxed.gpu.global.u32 %0, [%1];" : "=r"(v) : "l"(p)); return v;
}
__device__ __forceinline__ void st_relaxed(unsigned* p, unsigned v) {
    asm volatile("st.relaxed.gpu.global.u32 [%0], %1;" ::"l"(p), "r"(v) : "memory");
}
__device__ __forceinline__ void red_relaxed(unsigned* p, unsigned v) {
    asm volatile("red.relaxed.gpu.global.add.u32 [%0], %1;" ::"l"(p), "r"(v) : "memory");
}
__device__ __forceinline__ void fence_gpu() { asm volatile("fence.acq_rel.gpu;" ::: "memory"); }
__device__ __forceinline__ void fence_async_smem() { asm volatile("fence.proxy.async.shared::cta;" ::: "memory"); }
__device__ __forceinline__ void fence_async_global() { asm volatile("fence.proxy.async.global;" ::: "memory"); }
__device__ __forceinline__ uint32_t readback(const void* p) {
    uint32_t v; asm volatile("ld.relaxed.gpu.global.u32 %0, [%1];" : "=r"(v) : "l"(p) : "memory"); return v;
}
__device__ __forceinline__ void wait_count(const unsigned* p, unsigned target) {
    uint32_t it = 0;
    while ((int)(readback(p) - target) < 0) trap_if_gt(++it, 1u << 22);
}
__device__ __forceinline__ void wait_count_warp(const unsigned* p, unsigned target) {
    uint32_t it = 0;
    while (__any_sync(0xffffffffu, (int)(readback(p) - target) < 0)) trap_if_gt(++it, 1u << 22);
}
__device__ __forceinline__ void red_f32(float* p, float a) {
    asm volatile("red.relaxed.gpu.global.add.f32 [%0], %1;" ::"l"(p), "f"(a) : "memory");
}
__device__ __forceinline__ void red_f32x2(float* p, float a, float b) {
    asm volatile("red.relaxed.gpu.global.add.v2.f32 [%0], {%1, %2};" ::"l"(p), "f"(a), "f"(b) : "memory");
}
__device__ __forceinline__ void red_f32x4(float* p, float a, float b, float c, float d) {
    asm volatile("red.relaxed.gpu.global.add.v4.f32 [%0], {%1, %2, %3, %4};" ::"l"(p), "f"(a), "f"(b), "f"(c), "f"(d) : "memory");
}
__device__ __forceinline__ float4 ld_l2_f4(const float* p) {
    float4 v;
    asm volatile("ld.relaxed.gpu.global.v4.f32 {%0,%1,%2,%3}, [%4];" : "=f"(v.x), "=f"(v.y), "=f"(v.z), "=f"(v.w) : "l"(p) : "memory");
    return v;
}
__device__ __forceinline__ float2 ld_l2_f2(const float* p) {
    float2 v;
    asm volatile("ld.relaxed.gpu.global.v2.f32 {%0,%1}, [%2];" : "=f"(v.x), "=f"(v.y) : "l"(p) : "memory");
    return v;
}
__device__ __forceinline__ float ld_l2_f(const float* p) {
    float v;
    asm volatile("ld.relaxed.gpu.global.f32 %0, [%1];" : "=f"(v) : "l"(p) : "memory");
    return v;
}
__device__ __forceinline__ uint4 ldg_nc(const void* p) {
    uint4 v;
    asm volatile("ld.global.nc.L1::no_allocate.v4.u32 {%0,%1,%2,%3}, [%4];" : "=r"(v.x), "=r"(v.y), "=r"(v.z), "=r"(v.w) : "l"(p));
    return v;
}
__device__ __forceinline__ void stg128(void* p, uint32_t a, uint32_t b, uint32_t c, uint32_t d) {
    asm volatile("st.global.v4.u32 [%0], {%1,%2,%3,%4};" ::"l"(p), "r"(a), "r"(b), "r"(c), "r"(d) : "memory");
}
__device__ __forceinline__ uint4 lds128(uint32_t a) {
    uint4 v;
    asm volatile("ld.shared.v4.u32 {%0,%1,%2,%3}, [%4];" : "=r"(v.x), "=r"(v.y), "=r"(v.z), "=r"(v.w) : "r"(a) : "memory");
    return v;
}
__device__ __forceinline__ float2 lds_f2(uint32_t a) {
    float2 v;
    asm volatile("ld.shared.v2.f32 {%0,%1}, [%2];" : "=f"(v.x), "=f"(v.y) : "r"(a) : "memory");
    return v;
}
__device__ __forceinline__ void sts_f2(uint32_t a, float x, float y) {
    asm volatile("st.shared.v2.f32 [%0], {%1,%2};" ::"r"(a), "f"(x), "f"(y) : "memory");
}
__device__ __forceinline__ void sts64(uint32_t a, uint32_t x, uint32_t y) {
    asm volatile("st.shared.v2.u32 [%0], {%1,%2};" ::"r"(a), "r"(x), "r"(y) : "memory");
}
__device__ __forceinline__ void sts128(uint32_t a, uint32_t x, uint32_t y, uint32_t z, uint32_t w) {
    asm volatile("st.shared.v4.u32 [%0], {%1,%2,%3,%4};" ::"r"(a), "r"(x), "r"(y), "r"(z), "r"(w) : "memory");
}
__device__ __forceinline__ void stsm4(uint32_t a, uint32_t r0, uint32_t r1, uint32_t r2, uint32_t r3) {
    asm volatile("stmatrix.sync.aligned.m8n8.x4.shared.b16 [%0], {%1,%2,%3,%4};" ::"r"(a), "r"(r0), "r"(r1), "r"(r2), "r"(r3) : "memory");
}
__device__ __forceinline__ void stsm4t(uint32_t a, uint32_t r0, uint32_t r1, uint32_t r2, uint32_t r3) {
    asm volatile("stmatrix.sync.aligned.m8n8.x4.trans.shared.b16 [%0], {%1,%2,%3,%4};" ::"r"(a), "r"(r0), "r"(r1), "r"(r2), "r"(r3) : "memory");
}
__device__ __forceinline__ void tma_store2d(const CUtensorMap* tm, uint32_t src, int c0, int c1) {
    asm volatile("cp.async.bulk.tensor.2d.global.shared::cta.bulk_group [%0, {%2, %3}], [%1];" ::"l"(tm), "r"(src), "r"(c0), "r"(c1) : "memory");
    asm volatile("cp.async.bulk.commit_group;" ::: "memory");
}
__device__ __forceinline__ void ldsm4(uint32_t a, uint32_t& r0, uint32_t& r1, uint32_t& r2, uint32_t& r3) {
    asm volatile("ldmatrix.sync.aligned.m8n8.x4.shared.b16 {%0,%1,%2,%3}, [%4];" : "=r"(r0), "=r"(r1), "=r"(r2), "=r"(r3) : "r"(a) : "memory");
}
__device__ __forceinline__ void ldsm4t(uint32_t a, uint32_t& r0, uint32_t& r1, uint32_t& r2, uint32_t& r3) {
    asm volatile("ldmatrix.sync.aligned.m8n8.x4.trans.shared.b16 {%0,%1,%2,%3}, [%4];" : "=r"(r0), "=r"(r1), "=r"(r2), "=r"(r3) : "r"(a) : "memory");
}
__device__ __forceinline__ void mma16816(float* c, const uint32_t* a, uint32_t b0, uint32_t b1) {
    asm("mma.sync.aligned.m16n8k16.row.col.f32.bf16.bf16.f32 {%0,%1,%2,%3}, {%4,%5,%6,%7}, {%8,%9}, {%0,%1,%2,%3};"
                 : "+f"(c[0]), "+f"(c[1]), "+f"(c[2]), "+f"(c[3])
                 : "r"(a[0]), "r"(a[1]), "r"(a[2]), "r"(a[3]), "r"(b0), "r"(b1));
}
__device__ __forceinline__ uint32_t pack_bf16(float lo, float hi) {
    uint32_t r; asm("cvt.rn.bf16x2.f32 %0, %1, %2;" : "=r"(r) : "f"(hi), "f"(lo)); return r;
}
__device__ __forceinline__ float bf_lo(uint32_t w) { return __uint_as_float(w << 16); }
__device__ __forceinline__ float bf_hi(uint32_t w) { return __uint_as_float(w & 0xffff0000u); }
__device__ __forceinline__ float ex2(float x) { float r; asm("ex2.approx.ftz.f32 %0, %1;" : "=f"(r) : "f"(x)); return r; }
__device__ __forceinline__ float rcp(float x) { float r; asm("rcp.approx.ftz.f32 %0, %1;" : "=f"(r) : "f"(x)); return r; }
__device__ __forceinline__ void bar_sync(int id, int n) { asm volatile("bar.sync %0, %1;" ::"r"(id), "r"(n) : "memory"); }

typedef unsigned long long desc_t;
__device__ __forceinline__ desc_t desc_lo(uint32_t addr) { return (desc_t)(((addr & 0x3FFFF) >> 4) | (512u << 16)) | (0x40000040ull << 32); }
__device__ __forceinline__ void wg_fence() { asm volatile("wgmma.fence.sync.aligned;" ::: "memory"); }
__device__ __forceinline__ void wg_commit() { asm volatile("wgmma.commit_group.sync.aligned;" ::: "memory"); }
template <int N> __device__ __forceinline__ void wg_wait() { asm volatile("wgmma.wait_group.sync.aligned %0;" ::"n"(N) : "memory"); }
template <int N> __device__ __forceinline__ void fence_acc(float* d) {
#pragma unroll
    for (int i = 0; i < N; i++) asm volatile("" : "+f"(d[i])::"memory");
}
#define R4(o) "+f"(d[o + 0]), "+f"(d[o + 1]), "+f"(d[o + 2]), "+f"(d[o + 3])
#define R8(o) R4(o), R4(o + 4)
__device__ __forceinline__ void wgmma_n128(float* d, desc_t da, desc_t db, int sc) {
    asm volatile("{.reg .pred p; setp.ne.b32 p, %66, 0;\n"
                 "wgmma.mma_async.sync.aligned.m64n128k16.f32.bf16.bf16 {%0,%1,%2,%3,%4,%5,%6,%7,%8,%9,%10,%11,%12,%13,%14,%15,%16,%17,%18,%19,%20,%21,%22,%23,%24,%25,%26,%27,%28,%29,%30,%31,"
                 "%32,%33,%34,%35,%36,%37,%38,%39,%40,%41,%42,%43,%44,%45,%46,%47,%48,%49,%50,%51,%52,%53,%54,%55,%56,%57,%58,%59,%60,%61,%62,%63}, %64, %65, p, 1, 1, 0, 1;}"
                 : R8(0), R8(8), R8(16), R8(24), R8(32), R8(40), R8(48), R8(56)
                 : "l"(da), "l"(db), "r"(sc));
}
__device__ __forceinline__ void wgmma_n112(float* d, desc_t da, desc_t db, int sc) {
    asm volatile("{.reg .pred p; setp.ne.b32 p, %58, 0;\n"
                 "wgmma.mma_async.sync.aligned.m64n112k16.f32.bf16.bf16 {%0,%1,%2,%3,%4,%5,%6,%7,%8,%9,%10,%11,%12,%13,%14,%15,%16,%17,%18,%19,%20,%21,%22,%23,%24,%25,%26,%27,%28,%29,%30,%31,%32,%33,%34,%35,%36,%37,%38,%39,%40,%41,%42,%43,%44,%45,%46,%47,%48,%49,%50,%51,%52,%53,%54,%55}, %56, %57, p, 1, 1, 0, 1;}"
                 : R8(0), R8(8), R8(16), R8(24), R8(32), R8(40), R8(48)
                 : "l"(da), "l"(db), "r"(sc));
}
__device__ __forceinline__ void wgmma_n128_tn(float* d, desc_t da, desc_t db, int sc) {
    asm volatile("{.reg .pred p; setp.ne.b32 p, %66, 0;\n"
                 "wgmma.mma_async.sync.aligned.m64n128k16.f32.bf16.bf16 {%0,%1,%2,%3,%4,%5,%6,%7,%8,%9,%10,%11,%12,%13,%14,%15,%16,%17,%18,%19,%20,%21,%22,%23,%24,%25,%26,%27,%28,%29,%30,%31,%32,%33,%34,%35,%36,%37,%38,%39,%40,%41,%42,%43,%44,%45,%46,%47,%48,%49,%50,%51,%52,%53,%54,%55,%56,%57,%58,%59,%60,%61,%62,%63}, %64, %65, p, 1, 1, 1, 0;}"
                 : R8(0), R8(8), R8(16), R8(24), R8(32), R8(40), R8(48), R8(56)
                 : "l"(da), "l"(db), "r"(sc));
}
__device__ __forceinline__ void wgmma_n64(float* d, desc_t da, desc_t db, int sc) {
    asm volatile("{.reg .pred p; setp.ne.b32 p, %34, 0;\n"
                 "wgmma.mma_async.sync.aligned.m64n64k16.f32.bf16.bf16 {%0,%1,%2,%3,%4,%5,%6,%7,%8,%9,%10,%11,%12,%13,%14,%15,%16,%17,%18,%19,%20,%21,%22,%23,%24,%25,%26,%27,%28,%29,%30,%31}, %32, %33, p, 1, 1, 0, 1;}"
                 : R8(0), R8(8), R8(16), R8(24)
                 : "l"(da), "l"(db), "r"(sc));
}
__device__ __forceinline__ void wgmma_n40_tt(float* d, desc_t da, desc_t db, int sc) {
    asm volatile("{.reg .pred p; setp.ne.b32 p, %22, 0;\n"
                 "wgmma.mma_async.sync.aligned.m64n40k16.f32.bf16.bf16 {%0,%1,%2,%3,%4,%5,%6,%7,%8,%9,%10,%11,%12,%13,%14,%15,%16,%17,%18,%19}, %20, %21, p, 1, 1, 1, 1;}"
                 : R8(0), R8(8), R4(16)
                 : "l"(da), "l"(db), "r"(sc));
}

__device__ __forceinline__ void wgmma_n8_tt(float* d, desc_t da, desc_t db, int sc) {
    asm volatile("{.reg .pred p; setp.ne.b32 p, %6, 0;\n"
                 "wgmma.mma_async.sync.aligned.m64n8k16.f32.bf16.bf16 {%0,%1,%2,%3}, %4, %5, p, 1, 1, 1, 1;}"
                 : R4(0)
                 : "l"(da), "l"(db), "r"(sc));
}

__device__ __forceinline__ void signal_after(unsigned* cnt, uint32_t ack, uint32_t zero, bool pred) {
    asm volatile("{.reg .pred p; setp.ne.u32 p, %2, 0; @p red.relaxed.gpu.global.add.u32 [%0], %1;}"
                 ::"l"(cnt), "r"((ack & zero) + 1), "r"((uint32_t)pred) : "memory");
}
__device__ __forceinline__ void signal_late(unsigned* cnt, const uint32_t* a, uint32_t zero, bool pred) {
    uint32_t v;
    asm volatile("{.reg .b32 t; lop3.b32 t, %1, %2, %3, 0xfe; or.b32 %0, t, %4;}"
                 : "=r"(v) : "r"(a[0]), "r"(a[1]), "r"(a[2]), "r"(a[3]));
    signal_after(cnt, v, zero, pred);
}
__device__ __forceinline__ void red_f32_if(float* p, float a, bool pred) {
    asm volatile("{.reg .pred p; setp.ne.u32 p, %2, 0; @p red.relaxed.gpu.global.add.f32 [%0], %1;}" ::"l"(p), "f"(a), "r"((uint32_t)pred) : "memory");
}
__device__ __forceinline__ void stg_f2_if(float* p, float a, float b, bool pred) {
    asm volatile("{.reg .pred p; setp.ne.u32 p, %3, 0; @p st.global.v2.f32 [%0], {%1,%2};}" ::"l"(p), "f"(a), "f"(b), "r"((uint32_t)pred) : "memory");
}
__device__ __forceinline__ void stg64(void* p, uint32_t a, uint32_t b) {
    asm volatile("st.global.v2.u32 [%0], {%1,%2};" ::"l"(p), "r"(a), "r"(b) : "memory");
}
__device__ __forceinline__ void mma16816_z(float* c, const uint32_t* a, uint32_t b0, uint32_t b1) {
    asm("mma.sync.aligned.m16n8k16.row.col.f32.bf16.bf16.f32 {%0,%1,%2,%3}, {%4,%5,%6,%7}, {%8,%9}, {%10,%10,%10,%10};"
                 : "=f"(c[0]), "=f"(c[1]), "=f"(c[2]), "=f"(c[3])
                 : "r"(a[0]), "r"(a[1]), "r"(a[2]), "r"(a[3]), "r"(b0), "r"(b1), "f"(0.f));
}
__device__ __forceinline__ uint32_t max2(uint32_t a, uint32_t b) { uint32_t r; asm("max.bf16x2 %0, %1, %2;" : "=r"(r) : "r"(a), "r"(b)); return r; }
__device__ __forceinline__ uint32_t min2(uint32_t a, uint32_t b) { uint32_t r; asm("min.bf16x2 %0, %1, %2;" : "=r"(r) : "r"(a), "r"(b)); return r; }
__device__ __forceinline__ void bar_arrive(int id, int n) { asm volatile("bar.arrive %0, %1;" ::"r"(id), "r"(n) : "memory"); }
__device__ __forceinline__ void mbar_arrive_n_if(uint32_t bar, uint32_t n, bool pred) {
    asm volatile("{.reg .pred p; setp.ne.u32 p, %1, 0; @p mbarrier.arrive.shared::cta.b64 _, [%0], %2;}" ::"r"(bar), "r"((uint32_t)pred), "r"(n) : "memory");
}
__device__ __forceinline__ float4 lds_f4(uint32_t a) {
    float4 v;
    asm volatile("ld.shared.v4.f32 {%0,%1,%2,%3}, [%4];" : "=f"(v.x), "=f"(v.y), "=f"(v.z), "=f"(v.w) : "r"(a) : "memory");
    return v;
}
__device__ __forceinline__ void lds_f4_if(float4& v, uint32_t a, bool pred) {
    asm volatile("{.reg .pred p; setp.ne.u32 p, %5, 0; @p ld.shared.v4.f32 {%0,%1,%2,%3}, [%4];}"
                 : "+f"(v.x), "+f"(v.y), "+f"(v.z), "+f"(v.w) : "r"(a), "r"((uint32_t)pred) : "memory");
}
__device__ __forceinline__ uint4 ld_tagged(const unsigned long long* p) {
    unsigned long long a, b;
    asm volatile("ld.acquire.gpu.global.v2.b64 {%0,%1}, [%2];" : "=l"(a), "=l"(b) : "l"(p) : "memory");
    return make_uint4((unsigned)a, (unsigned)(a >> 32), (unsigned)b, (unsigned)(b >> 32));
}
__device__ __forceinline__ uint4 ld_tagged_rlx(const unsigned long long* p) {
    unsigned long long a, b;
    asm volatile("ld.relaxed.gpu.global.v2.b64 {%0,%1}, [%2];" : "=l"(a), "=l"(b) : "l"(p) : "memory");
    return make_uint4((unsigned)a, (unsigned)(a >> 32), (unsigned)b, (unsigned)(b >> 32));
}
__device__ __forceinline__ void sts32(uint32_t a, uint32_t x) { asm volatile("st.shared.u32 [%0], %1;" ::"r"(a), "r"(x) : "memory"); }
__device__ __forceinline__ void fetch_tagged(const unsigned long long* src, uint32_t dst, unsigned epoch) {
    uint4 v;
    uint32_t it = 0;
    while (true) {
        v = ld_tagged_rlx(src);
        if (!__any_sync(0xffffffffu, v.y != epoch || v.w != epoch)) break;
        __nanosleep(60);
        trap_if_gt(++it, 1u << 22);
    }
    sts64(dst, v.x, v.z);
}
__device__ __forceinline__ void st_tagged_if(unsigned long long* p, float a, float b, unsigned tag, bool pred) {
    const unsigned long long t = (unsigned long long)tag << 32;
    asm volatile("{.reg .pred p; setp.ne.u32 p, %3, 0; @p st.relaxed.gpu.global.v2.b64 [%0], {%1,%2};}"
                 ::"l"(p), "l"(t | __float_as_uint(a)), "l"(t | __float_as_uint(b)), "r"((uint32_t)pred) : "memory");
}

__device__ __forceinline__ void store_tile(uint32_t tile_rows, uint4* gdst, const uint32_t* lo, const uint32_t* hi, int lane, uint32_t* ack) {
    const int r = lane & 15;
#pragma unroll
    for (int b = 0; b < 4; b++)
        stsm4(tile_rows + r * 128 + (((2 * b + (lane >> 4)) ^ (r & 7)) << 4), lo[2 * b], hi[2 * b], lo[2 * b + 1], hi[2 * b + 1]);
    fence_async_smem();
    __syncwarp();
#pragma unroll
    for (int i = 0; i < 4; i++) {
        const uint4 v = lds128(tile_rows + i * 512 + lane * 16);
        stg128(gdst + 32 * i, v.x, v.y, v.z, v.w);
    }
#pragma unroll
    for (int i = 0; i < 4; i++) ack[i] = readback(gdst + 32 * i);
}

__device__ __forceinline__ void feature_maps(const uint32_t* a, const uint32_t* wb, float c0, float c1, uint32_t* plus, uint32_t* minus) {
    uint32_t P[16], mx[4], mn[4];
#pragma unroll
    for (int h = 0; h < 4; h++) {
        float p[8];
        mma16816_z(p, a + 4 * h, wb[4 * h], wb[4 * h + 1]);
        mma16816_z(p + 4, a + 4 * h, wb[4 * h + 2], wb[4 * h + 3]);
        P[4 * h] = pack_bf16(p[0], p[2]); P[4 * h + 1] = pack_bf16(p[1], p[3]);
        P[4 * h + 2] = pack_bf16(p[4], p[6]); P[4 * h + 3] = pack_bf16(p[5], p[7]);
        mx[h] = max2(max2(P[4 * h], P[4 * h + 1]), max2(P[4 * h + 2], P[4 * h + 3]));
        mn[h] = min2(min2(P[4 * h], P[4 * h + 1]), min2(P[4 * h + 2], P[4 * h + 3]));
    }
#pragma unroll
    for (int s = 1; s <= 2; s <<= 1) {
        uint32_t tx[4], tn[4];
#pragma unroll
        for (int h = 0; h < 4; h++) { tx[h] = __shfl_xor_sync(0xffffffffu, mx[h], s); tn[h] = __shfl_xor_sync(0xffffffffu, mn[h], s); }
#pragma unroll
        for (int h = 0; h < 4; h++) { mx[h] = max2(mx[h], tx[h]); mn[h] = min2(mn[h], tn[h]); }
    }
#pragma unroll
    for (int h = 0; h < 4; h++) {
        const float mx0 = bf_lo(mx[h]) * c0, mx1 = bf_hi(mx[h]) * c1, mn0 = bf_lo(mn[h]) * c0, mn1 = bf_hi(mn[h]) * c1;
        float ep[8], em[8];
#pragma unroll
        for (int i = 0; i < 8; i++) {
            const bool r1 = (i & 2);
            const uint32_t w = P[4 * h + (i >> 2) * 2 + (i & 1)];
            const float p = r1 ? bf_hi(w) : bf_lo(w);
            ep[i] = ex2(fmaf(p, r1 ? c1 : c0, r1 ? -mx1 : -mx0));
            em[i] = ex2(fmaf(p, r1 ? -c1 : -c0, r1 ? mn1 : mn0));
        }
        float sp[4], sm[4];
        uint32_t tp[4], tm[4];
#pragma unroll
        for (int i = 0; i < 4; i++) { tp[i] = pack_bf16(ep[2 * i], ep[2 * i + 1]); tm[i] = pack_bf16(em[2 * i], em[2 * i + 1]); }
        mma16816_z(sp, tp, 0x3f803f80u, 0x3f803f80u);
        mma16816_z(sm, tm, 0x3f803f80u, 0x3f803f80u);
        const float r0 = rcp(sp[0] * sm[0]), r1 = rcp(sp[2] * sm[2]);
        const float rs[4] = {r0 * sm[0], r1 * sm[2], r0 * sp[0], r1 * sp[2]};
#pragma unroll
        for (int i = 0; i < 4; i++) {
            plus[4 * h + i] = pack_bf16(ep[2 * i] * rs[i & 1], ep[2 * i + 1] * rs[i & 1]);
            minus[4 * h + i] = pack_bf16(em[2 * i] * rs[2 + (i & 1)], em[2 * i + 1] * rs[2 + (i & 1)]);
        }
    }
}

template <bool SCALE>
__device__ __forceinline__ void ln_frag(const float* acc, uint32_t cs_addr, float rs0, float nm0, float rs1, float nm1, uint32_t* a) {
    const float2 c0 = lds_f2(cs_addr), c1 = lds_f2(cs_addr + 32);
    const float s0 = SCALE ? rs0 : 1.f, s1 = SCALE ? rs1 : 1.f;
    a[0] = pack_bf16(fmaf(nm0, c0.x, acc[0]) * s0, fmaf(nm0, c0.y, acc[1]) * s0);
    a[1] = pack_bf16(fmaf(nm1, c0.x, acc[2]) * s1, fmaf(nm1, c0.y, acc[3]) * s1);
    a[2] = pack_bf16(fmaf(nm0, c1.x, acc[4]) * s0, fmaf(nm0, c1.y, acc[5]) * s0);
    a[3] = pack_bf16(fmaf(nm1, c1.x, acc[6]) * s1, fmaf(nm1, c1.y, acc[7]) * s1);
}

template <int UP>
__device__ __forceinline__ uint32_t hh_pair(const float* ag, float4 cs, float nmean) {
    const float g0 = fmaf(nmean, cs.x, ag[0]), g1 = fmaf(nmean, cs.y, ag[1]);
    const float u0 = fmaf(nmean, cs.z, ag[UP]), u1 = fmaf(nmean, cs.w, ag[UP + 1]);
    return pack_bf16(g0 * u0, g1 * u1);
}
template <int NTP>
__device__ __forceinline__ void hh_stage(const float* acc, const float4* cs, float nm0, float nm1, uint32_t stg, int lane) {
#pragma unroll
    for (int tp = 0; tp < NTP; tp++)
        stsm4(stg + (lane & 15) * 128 + (((2 * tp + (lane >> 4)) ^ (lane & 7)) << 4), hh_pair<32>(acc + 8 * tp, cs[2 * tp], nm0),
              hh_pair<32>(acc + 8 * tp + 2, cs[2 * tp], nm1), hh_pair<32>(acc + 8 * tp + 4, cs[2 * tp + 1], nm0),
              hh_pair<32>(acc + 8 * tp + 6, cs[2 * tp + 1], nm1));
    fence_async_smem();
    __syncwarp();
}

template <int TP0, int TP1>
__device__ __forceinline__ void hh_stage2(const float* acc, const float4* cs, float nm0, float nm1, uint32_t stg, int lane) {
#pragma unroll
    for (int tp = TP0; tp < TP1; tp++)
        stsm4(stg + (lane & 15) * 128 + (((2 * tp + (lane >> 4)) ^ (lane & 7)) << 4), hh_pair<32>(acc + 8 * tp, cs[2 * tp], nm0),
              hh_pair<32>(acc + 8 * tp + 2, cs[2 * tp], nm1), hh_pair<32>(acc + 8 * tp + 4, cs[2 * tp + 1], nm0),
              hh_pair<32>(acc + 8 * tp + 6, cs[2 * tp + 1], nm1));
}
struct Ring {
    int slot; uint32_t phase;
    __device__ __forceinline__ void adv() { if (++slot == NB) { slot = 0; phase ^= 1; } }
    __device__ __forceinline__ void adv5() { slot += slot == 3; adv(); }
};

__global__ void __cluster_dims__(2, 1, 1) __launch_bounds__(NTHREADS, 1) fused_kernel(const __grid_constant__ Params P) {
    extern __shared__ __align__(1024) uint8_t smem_raw[];
    const uint32_t sb = smem_u32(smem_raw);
    const int tid = threadIdx.x, lane = tid & 31;
    if (tid >= 256 && tid < 258) prefetch_tmap(&P.tx + (tid & 1));
    const int warp = __shfl_sync(0xffffffffu, tid >> 5, 0);
    const unsigned role = P.role[blockIdx.x], rank = blockIdx.x & 1;
    const int m = role >> 3, j = role & 7;
    const bool helper = role >= 128;

    TL(0, tid == 0); TLG(0, tid == 0);
    float* const acc_j = g_acc + j * ACC_SIZE;

    if (__builtin_expect(warp >= 8, 1)) {
        asm volatile("setmaxnreg.dec.sync.aligned.u32 72;");
        if (elect_one()) {
            if (warp == 8) {
                if (!helper) {
#pragma unroll
                    for (int i = 0; i < NB; i++) mbar_init(sb + BAR_FULLB + 8 * i, 1);
#pragma unroll
                    for (int i = 0; i < 2; i++) {
                        mbar_expect_tx(sb + BAR_FULLB + 8 * i, SLOT);
                        tma2d(sb + OFF_B + i * SLOT, &P.twq, sb + BAR_FULLB + 8 * i, DM + 64 * j, 64 * i);
                        tma2d(sb + OFF_B + i * SLOT + 8192, &P.twq, sb + BAR_FULLB + 8 * i, 2 * DM + 64 * j, 64 * i);
                    }
                }
            } else if (warp == 9) {
#pragma unroll
                for (int i = 0; i < 8; i++) mbar_init(sb + BAR_FULLA + 8 * i, 1);
                if (!helper) {
#pragma unroll
                    for (int i = 0; i < 2; i++) {
                        mbar_expect_tx(sb + BAR_FULLA + 8 * i, SLOT);
                        tma2d(sb + OFF_A + i * SLOT, &P.tx, sb + BAR_FULLA + 8 * i, 64 * i, 128 * m);
                    }
                }
            } else if (warp == 10) {
#pragma unroll
                for (int i = 0; i < 12; i++) mbar_init(sb + BAR_CS1 + 8 * i, i < 2 || i >= 8 ? 64 : (i < 4 ? 32 : 8));
                trap_if_gt(sb & 1023, 0);
            } else {
#pragma unroll
                for (int i = 0; i < 14; i++) mbar_init(sb + (i < 8 ? BAR_EMPTYA : BAR_EMPTYB - 64) + 8 * i, i < 8 ? 8 : 16);
            }
            asm volatile("fence.mbarrier_init.release.cluster;" ::: "memory");
        }
        __syncwarp();
        asm volatile("barrier.cluster.arrive.relaxed.aligned;" ::: "memory");
        const unsigned epoch = ld_relaxed(&g_epoch);
        bar_sync(0, NTHREADS);
        if (helper) {
            if (elect_one()) {
#pragma unroll 1
                for (int i = warp - 8; i < 72; i += 4) {
                    const uint32_t full = sb + BAR_FULLA + 8 * (i & 7), dst = sb + OFF_A + (i & 7) * SLOT;
                    const int n = i >> 1, jj = 2 * j + (i & 1);
                    const bool qkv = n < 12;
                    const int c0 = qkv ? (n < 8 ? DM + 128 * (n & 4) : 0) + 64 * jj : 176 * jj + 8 * ((n - 12) & ~7);
                    const int r0 = qkv ? 128 * (n & 3) : 64 * ((n - 12) & 7);
                    mbar_wait(sb + BAR_EMPTYA + 8 * (i & 7), ((i >> 3) & 1) ^ 1);
                    mbar_expect_tx(full, SLOT);
                    tma2d(dst, qkv ? &P.twq : &P.twg, full, c0, r0);
                    tma2d(dst + 8192, qkv ? &P.twq : &P.twu, full, c0, qkv ? r0 + 64 : r0);
                }
                prefetch_l2(P.wd + (size_t)(4 * j + warp - 8) * 44032, 88064);
            }
            return;
        }
        if (warp == 8) {
            asm volatile("barrier.cluster.wait.aligned;" ::: "memory");
            if (elect_one()) {
                if (m >= 6)
                    asm volatile("cp.async.bulk.prefetch.tensor.2d.L2.global [%0, {%1, %2}];" ::"l"(&P.twq), "r"(DM + DM * (m & 1) + 64 * j), "r"(64 * (m >> 1)) : "memory");
                if (j >= 3)
                    asm volatile("cp.async.bulk.prefetch.tensor.2d.L2.global [%0, {%1, %2}];" ::"l"(&P.tx), "r"(64 * j), "r"(128 * m) : "memory");
                Ring r{2, 0};
                const uint32_t dst = sb + OFF_B + rank * 8192;
#define B_LOAD(TM, C0, R0)                                                                                  \
        mbar_waitc(sb + BAR_EMPTYB + 8 * r.slot, r.phase ^ 1);                                              \
        mbar_expect_tx(sb + BAR_FULLB + 8 * r.slot, SLOT);                                                  \
        tma2d_mc(dst + r.slot * SLOT, TM, sb + BAR_FULLB + 8 * r.slot, C0, R0);
#pragma unroll 1
                for (int i = 2; i < 8; i++) {
                    if (i >= AHEAD && i < 6) mbar_waitc(sb + BAR_FULLB + 8 * (i - AHEAD), 0);
                    B_LOAD(&P.twq, DM + DM * rank + 64 * j, 64 * i)
                    r.adv();
                }
#pragma unroll 1
                for (int i = 8; i < 20; i++) {
                    if (i >= 9 && i < 13) {
                        mbar_waitc(sb + BAR_EMPTYB + 8 * r.slot, r.phase ^ 1);
                        mbar_arrive(sb + BAR_FULLB + 8 * r.slot);
                    } else {
                        const int e = 2 * (i & 3) + rank;
                        B_LOAD(i < 16 ? &P.twq : &P.two, 64 * j, 64 * (i < 16 ? e : KORD(e, j)))
                    }
                    r.adv();
                }
#pragma unroll 1
                for (int i = 0; i < 24; i++) {
                    B_LOAD(&P.twg + rank, 176 * j + 8 * (i & ~7), 64 * (i < 8 ? KORD(i, j) : i & 7))
                    r.adv5();
                }
#pragma unroll 1
                for (int i = 0; i < 12; i++) {
                    B_LOAD(&P.twd, 64 * j, 176 * (2 * (i & 3) + rank) + 64 * (i >> 2))
                    r.adv5();
                }
            }
            return;
        }
        if (warp == 9) {
            if (elect_one()) {
#pragma unroll 1
                for (int i = 2; i < 8; i++) {
                    if (i >= AHEAD + 1) mbar_wait(sb + BAR_FULLA + 8 * (i - AHEAD - 1), 0);
                    mbar_expect_tx(sb + BAR_FULLA + 8 * i, SLOT);
                    tma2d(sb + OFF_A + i * SLOT, &P.tx, sb + BAR_FULLA + 8 * i, 64 * i, 128 * m);
                }
#pragma unroll 1
                for (int i = 2; i < 7; i++) prefetch_tmap(&P.tx + i);
                unsigned nf = 0;
#pragma unroll 1
                for (int r = 1; r < 6; r++) {
                    const int skip = r < 3 ? j : 8;
                    const uint4* src = g_act + ((r - 1) * 128 + m * 8) * 1024;
                    const unsigned* fl = g_flag + (m * 5 + r - 1) * 32;
                    if (r < 4) mbar_wait(sb + BAR_EMPTYA + 8 * (r == 3 ? PF_DELAY : 2 + (j == 2)), (r - 1) & 1);
                    if (r < 4 || nf != epoch * 8) wait_count(fl, epoch * (r < 3 ? 64 : 8));
                    TL(64 + r, true);
#pragma unroll 1
                    for (int t = 0; t < 8; t++) {
                        if (t == skip) continue;
                        if (t == 6) nf = readback(fl + 32);
                        mbar_wait(sb + BAR_EMPTYA + 8 * t, (r - 1) & 1);
                        mbar_expect_tx(sb + BAR_FULLA + 8 * t, SLOT);
                        asm volatile("cp.async.bulk.shared::cluster.global.mbarrier::complete_tx::bytes [%0], [%1], %2, [%3];"
                                     ::"r"(sb + OFF_A + t * SLOT), "l"(src + t * 1024), "r"(SLOT), "r"(sb + BAR_FULLA + 8 * t) : "memory");
                    }
                }
            }
            return;
        }
        const int a = warp - 10;
        {
            const int row = 16 * j + 8 * a + (lane >> 2);
            const uint32_t ra = sb + OFF_A + row * 128;
            float sh = 0.f, s0 = 0.f, s1 = 0.f, q0 = 0.f, q1 = 0.f;
#pragma unroll 1
            for (int kt = 0; kt < 8; kt++) {
                mbar_wait(sb + BAR_FULLA + 8 * kt, 0);
                if (kt == 0) sh = bf_lo(lds128(ra + ((row & 7) << 4)).x);
#pragma unroll
                for (int i = 0; i < 2; i++) {
                    const uint4 v = lds128(ra + kt * SLOT + (((2 * (lane & 3) + i) ^ (row & 7)) << 4));
                    const uint32_t ww[4] = {v.x, v.y, v.z, v.w};
#pragma unroll
                    for (int e = 0; e < 4; e++) {
                        const float d0 = bf_lo(ww[e]) - sh, d1 = bf_hi(ww[e]) - sh;
                        s0 += d0; q0 = fmaf(d0, d0, q0);
                        s1 += d1; q1 = fmaf(d1, d1, q1);
                    }
                }
            }
            s0 += s1; q0 += q1;
#pragma unroll
            for (int o = 1; o <= 2; o <<= 1) { s0 += __shfl_xor_sync(0xffffffffu, s0, o); q0 += __shfl_xor_sync(0xffffffffu, q0, o); }
            const float md = s0 * (1.f / DM);
            const float rs = rsqrtf(fmaxf(q0 * (1.f / DM) - md * md, 0.f) + 1e-5f);
            st_tagged_if(g_xstat + 2 * (128 * m + row), rs, -(sh + md), epoch, (lane & 3) == 0);
            TL(1, lane == 0 && a == 0);
        }
        const unsigned long long* cs = g_cs + j * 768 + 2 * lane;
        {
            const unsigned long long* xs = g_xstat + 2 * (128 * m + 64 * a + lane);
            uint4 v0, v1, v2;
            uint32_t it = 0;
            do {
                v0 = ld_tagged_rlx(xs); v1 = ld_tagged_rlx(xs + 64); v2 = ld_tagged_rlx(cs);
                trap_if_gt(++it, 1u << 22);
            } while (__any_sync(0xffffffffu, v0.y != epoch || v0.w != epoch || v1.y != epoch || v1.w != epoch || v2.y != epoch || v2.w != epoch));
            sts64(sb + OFF_XST + (64 * a + lane) * 8, v0.x, v0.z);
            sts64(sb + OFF_XST + (64 * a + 32 + lane) * 8, v1.x, v1.z);
            sts64(sb + OFF_CS1 + 256 + 8 * lane, v2.x, v2.z);
            mbar_arrive(sb + BAR_CS1);
            TL(22 + a, lane == 0);
            fetch_tagged(cs + 128 + 128 * a, sb + OFF_CS1 + 512 - 512 * a + 8 * lane, epoch);
            mbar_arrive(sb + BAR_CSV - 8 * a);
            TL(24 + a, lane == 0);
        }
        {
            mbar_wait(sb + BAR_KVW, 0);
            const float* src = acc_j + 4 * (128 * a + lane);
            float4 v[12];
            uint32_t it = 0;
            bool bad;
            while (__any_sync(0xffffffffu, readback(acc_j + 2048 + 128 * (lane & 7) + 127) != 0x41800000u)) trap_if_gt(++it, 1u << 22);
            TL(19, lane == 0 && a == 0);
            do {
                bad = false;
#pragma unroll
                for (int i = 0; i < 12; i++) v[i] = ld_l2_f4(src + 1024 * (i % 3) + 128 * (i / 3));
#pragma unroll
                for (int i = 0; i < 12; i++) bad |= v[i].w != 16.f;
                trap_if_gt(++it, 1u << 22);
            } while (__any_sync(0xffffffffu, bad));
            TL(14, lane == 0 && a == 0);
            const uint32_t d0 = sb + OFF_A + (j == 0) * SLOT + (64 * a + (lane >> 2)) * 48;
            const uint32_t d = d0 + (lane & 3) * 4, dz = d0 + (lane & 1) * 384 + 32 + (lane & 2) * 4;
#pragma unroll
            for (int u = 0; u < 4; u++) {
                sts32(d + 768 * u, pack_bf16(v[3 * u].x, v[3 * u].y));
                sts32(d + 768 * u + 384, pack_bf16(v[3 * u].z, v[3 * u + 1].z));
                sts32(d + 768 * u + 16, pack_bf16(v[3 * u + 1].x, v[3 * u + 1].y));
                sts32(d + 768 * u + 400, pack_bf16(v[3 * u + 2].x, v[3 * u + 2].y));
                const uint32_t z2 = pack_bf16(v[3 * u + 2].z, v[3 * u + 2].z);
                sts64(dz + 768 * u, z2, z2);
            }
            mbar_arrive(sb + BAR_KVR);
        }
#pragma unroll 1
        for (int c = 0; c < 3; c++) {
            fetch_tagged(cs + 384 + 128 * c + 64 * a, sb + OFF_CS3 + (32 * c + lane) * 16 + 8 * a, epoch);
            mbar_arrive(sb + BAR_CSG + 8 * c);
            TL(45 + c, lane == 0 && a == 0);
        }
        {
            uint32_t it = 0;
            while (__any_sync(0xffffffffu, (int)(readback(g_flag + (m * 5 + 1) * 32) - epoch * 64) < 0)) {
                __nanosleep(200);
                trap_if_gt(++it, 1u << 22);
            }
#pragma unroll 1
            for (int rr = 0; rr < 2; rr++) {
                const int row = 64 * rr + 32 * a + lane;
                const unsigned long long* hs = g_hstat + (1024 * m + row) * 2;
                uint4 v[8];
                bool bad;
                do {
                    bad = false;
#pragma unroll
                    for (int i = 0; i < 8; i++) v[i] = ld_tagged_rlx(hs + 256 * i);
#pragma unroll
                    for (int i = 0; i < 8; i++) bad |= v[i].y != epoch || v[i].w != epoch;
                    trap_if_gt(++it, 1u << 22);
                } while (__any_sync(0xffffffffu, bad));
                float mean = 0.f;
#pragma unroll
                for (int i = 0; i < 8; i++) mean += __uint_as_float(v[i].x);
                mean *= 0.125f;
                float m2 = 0.f, dv = 0.f;
#pragma unroll
                for (int i = 0; i < 8; i++) { const float d = __uint_as_float(v[i].x) - mean; m2 += __uint_as_float(v[i].z); dv = fmaf(d, d, dv); }
                sts_f2(sb + OFF_CS1 + row * 8, -mean, rcp(fmaf(dv, 64.f, m2) * (1.f / DM) + 1e-5f));
            }
        }
        mbar_arrive(sb + BAR_CS3);
#pragma unroll 1
        for (int c = a; c < 3; c += 2) {
            mbar_wait(sb + BAR_STG + 8 * c, 0);
            if (elect_one()) {
                asm volatile("cp.async.bulk.global.shared::cta.bulk_group [%0], [%1], %2;" ::"l"(g_act + ((2 + c) * 128 + role) * 1024), "r"(sb + OFF_B + 4 * SLOT), "r"(SLOT) : "memory");
                asm volatile("cp.async.bulk.commit_group;" ::: "memory");
                asm volatile("cp.async.bulk.wait_group.read 0;" ::: "memory");
                mbar_arrive(sb + BAR_FULLB + 8 * 4);
                asm volatile("cp.async.bulk.wait_group 0;" ::: "memory");
            }
            __syncwarp();
            TL(60 + c, lane == 0);
            uint32_t ack = 0;
            const uint4* rb = g_act + ((2 + c) * 128 + role) * 1024 + lane * 8;
#pragma unroll
            for (int i = 0; i < 4; i++) ack |= readback(rb + 256 * i);
            signal_after(g_flag + (m * 5 + 2 + c) * 32, ack, P.zero, lane == 0);
            TL(54 + c, lane == 0);
        }
        return;
    }
    const unsigned epoch = ld_relaxed(&g_epoch);
    uint32_t wraw[16];
    if (!helper) {
        const uint32_t* wp = reinterpret_cast<const uint32_t*>(P.wphi) + (4 * j) * 128 + (lane & 3) * 16 + (lane >> 2);
#pragma unroll
        for (int i = 0; i < 16; i++)
            asm volatile("ld.global.nc.u32 %0, [%1];" : "=r"(wraw[i]) : "l"(wp + (i >> 2) * 128 + ((i >> 1) & 1) * 64 + (i & 1) * 8));
    }
    asm volatile("barrier.cluster.arrive.relaxed.aligned;" ::: "memory");
    asm volatile("setmaxnreg.inc.sync.aligned.u32 216;");
    bar_sync(0, NTHREADS);
    if (helper) {
        const int w = warp >> 2;
        sts64(sb + OFF_B + 8 * tid, 0x3f803f80u, 0x3f803f80u);
        fence_async_smem();
        uint32_t zack[6];
        {
            float* z = g_acc + 2 * j * ACC_SIZE + 4 * tid;
#pragma unroll
            for (int u = 0; u < 6; u++) stg128(z + 1024 * u, 0, 0, 0, 0);
#pragma unroll
            for (int u = 0; u < 6; u++) zack[u] = readback(z + 1024 * u);
        }
        bar_sync(1, 256);
        TL(70, tid == 0);
        float acc[8];
        int i = w;
#pragma unroll 1
        for (int job = 0; job < 6; job++) {
            const int n = job < 3 ? 4 : 8;
#pragma unroll 1
            for (int t = 0; t < n; t++, i += 2) {
                mbar_waitc(sb + BAR_FULLA + 8 * (i & 7), (i >> 3) & 1);
                const desc_t da = desc_lo(sb + OFF_A) + (i & 7) * (SLOT >> 4);
                wg_fence();
#pragma unroll
                for (int k = 0; k < 8; k++) wgmma_n8_tt(acc + (k & 4), da + 128 * k, desc_lo(sb + OFF_B), (t | (k & 3)) != 0);
                wg_commit();
                wg_wait<0>();
                mbar_arrive_n_if(sb + BAR_EMPTYA + 8 * (i & 7), 2, lane == 0);
            }
            fence_acc<8>(acc);
            TL(71 + job, tid == 0);
            if (job == 1) {
                asm volatile("{.reg .pred p; .reg .b32 t; lop3.b32 t, %0, %1, %2, 0xfe; lop3.b32 t, t, %3, %4, 0xfe; or.b32 t, t, %5; setp.ne.u32 p, t, 0; @p trap;}"
                             ::"r"(zack[0]), "r"(zack[1]), "r"(zack[2]), "r"(zack[3]), "r"(zack[4]), "r"(zack[5]));
                bar_sync(1, 256);
            }
            const int q = lane & 3;
            const float lo = (q & 1) ? acc[2] : acc[0], hi = (q & 1) ? acc[6] : acc[4];
            const float v = job < 3 ? lo + hi : ((q & 2) ? hi : lo);
            unsigned long long* dst = g_cs + ((2 * j + w) * 6 + job) * 128 + (q >> 1) * 64 + 16 * (warp & 3) + 8 * (q & 1) + (lane >> 2);
            asm volatile("st.relaxed.gpu.global.b64 [%0], %1;" ::"l"(dst), "l"(((unsigned long long)epoch << 32) | __float_as_uint(v)) : "memory");
        }
        return;
    }
    {
        const int w = warp >> 2, wv = warp & 3, g = lane >> 2, q = lane & 3;
        const uint32_t sa = sb + OFF_A + w * 8192;
        const desc_t dA = desc_lo(sa), dB = desc_lo(sb + OFF_B);
        unsigned* const flag_m = g_flag + m * 160;
        const bool l0 = lane == 0, l2 = lane < 2;
        const uint32_t eb = mapa(sb + BAR_EMPTYB, lane & 1);
        asm volatile("barrier.cluster.wait.aligned;" ::: "memory");
        Ring rg{0, 0};
        int prev = 0;

        uint32_t wb[16];
        constexpr float L2E = 1.4426950408889634f;
        const int ch = lane >> 4, sw = lane & 7;
        const uint32_t lrow = (lane & 15) * 128;
        uint32_t fp[16], fm[16];
        {
            float acc[64];
#pragma unroll 1
            for (int kt = 0; kt < 8; kt++) {
                mbar_waitc(sb + BAR_FULLA + 8 * kt, 0);
                mbar_waitc(sb + BAR_FULLB + 8 * rg.slot, rg.phase);
                const desc_t da = dA + kt * (SLOT >> 4), db = dB + rg.slot * (SLOT >> 4);
                wg_fence();
#pragma unroll
                for (int k = 0; k < 4; k++) wgmma_n128(acc, da + 2 * k, db + 128 * k, (kt | k) != 0);
                wg_commit();
                wg_wait<1>();
                mbar_arrive_cl_if(eb + 8 * prev, l2 && kt > 0);
                prev = rg.slot; rg.adv();
            }
#pragma unroll
            for (int i = 0; i < 8; i++) {
                wb[(i >> 1) * 4 + (i & 1)] = __byte_perm(wraw[2 * i], wraw[2 * i + 1], 0x5410);
                wb[(i >> 1) * 4 + 2 + (i & 1)] = __byte_perm(wraw[2 * i], wraw[2 * i + 1], 0x7632);
            }
            uint32_t a[16];
            float accq[32];
            mbar_waitc(sb + BAR_FULLB + 8 * 2, 1);
            wg_fence();
#pragma unroll
            for (int k = 0; k < 8; k++) wgmma_n64(accq, dA + (k >> 2) * (SLOT >> 4) + (k & 3) * 2, dB + 2 * (SLOT >> 4) + 128 * k, k != 0);
            wg_commit();
            wg_wait<1>();
            fence_acc<64>(acc);
            mbar_arrive_cl_if(eb + 8 * prev, l2);
            TL(17, tid == 0);
            mbar_waitc(sb + BAR_CS1, 0);
            const float2 s0 = lds_f2(sb + OFF_XST + (16 * warp + g) * 8), s1 = lds_f2(sb + OFF_XST + (16 * warp + g + 8) * 8);
            wg_wait<0>();
            fence_acc<32>(accq);
            mbar_arrive_cl_if(eb + 8 * 2, l2);
            TL(2, tid == 0);
            const uint32_t st = sb + OFF_B + warp * 2048 + lrow;
#pragma unroll
            for (int hh = 0; hh < 4; hh++)
                ln_frag<false>(acc + 8 * hh, sb + OFF_CS1 + (64 + 16 * hh + 2 * q) * 4, 0.f, s0.y, 0.f, s1.y, a + 4 * hh);
#pragma unroll 1
            for (int it = 0; it < 2; it++) {
                feature_maps(a, wb, s0.x * L2E, s1.x * L2E, fp, fm);
                if (it == 0) {
#pragma unroll
                    for (int i = 3; i < 7; i++) mbar_waitc(sb + BAR_FULLB + 8 * (i % 6), i < 6);
                    mbar_waitc(sb + BAR_CSV, 0);
#pragma unroll
                    for (int hh = 0; hh < 4; hh++) {
                        stsm4(st + (3 + (hh >> 1)) * SLOT + (((4 * (hh & 1) + ch) ^ sw) << 4), fp[4 * hh], fp[4 * hh + 1], fp[4 * hh + 2], fp[4 * hh + 3]);
                        stsm4(st + (3 + (hh >> 1)) * SLOT + (((4 * (hh & 1) + 2 + ch) ^ sw) << 4), fm[4 * hh], fm[4 * hh + 1], fm[4 * hh + 2], fm[4 * hh + 3]);
                        ln_frag<true>(acc + 32 + 8 * hh, sb + OFF_CS1 + (128 + 16 * hh + 2 * q) * 4, s0.x, s0.y, s1.x, s1.y, a);
                        stsm4(st + (hh < 2 ? 5 * SLOT : 0) + (((2 * (hh & 1) + ch) ^ sw) << 4), a[0], a[1], a[2], a[3]);
                    }
                    stsm4(st + ch * 5 * SLOT + ((4 ^ sw) << 4), 0x3f803f80u, 0x3f803f80u, 0x3f803f80u, 0x3f803f80u);
                    fence_async_smem();
                    bar_sync(1, 256);
                    float kvd[20];
                    wg_fence();
#pragma unroll
                    for (int k = 0; k < 8; k++)
                        wgmma_n40_tt(kvd, dB + (3 + w) * (SLOT >> 4) + 128 * k, dB + (w ^ 1) * (5 * SLOT >> 4) + 128 * k, k != 0);
                    wg_commit();
                    wg_wait<0>();
                    fence_acc<20>(kvd);
                    mbar_arrive_cl_if(eb + 8 * ((3 + (lane >> 1)) % 6), lane < 8);
                    const bool h1 = wv >= 2;
                    float* kvp = acc_j + 4 * tid;
                    red_f32x4(kvp, h1 ? kvd[8] : kvd[0], h1 ? kvd[9] : kvd[1], h1 ? kvd[10] : kvd[2], 1.f);
                    red_f32x4(kvp + 1024, h1 ? kvd[12] : kvd[4], h1 ? kvd[13] : kvd[5], h1 ? kvd[11] : kvd[3], 1.f);
                    red_f32x4(kvp + 2048, h1 ? kvd[14] : kvd[6], h1 ? kvd[15] : kvd[7], (q & 1) ? kvd[18] : kvd[16], 1.f);
                    mbar_arrive_if(sb + BAR_KVW, l0);
                    TL(3, tid == 0);
#pragma unroll 1
                    for (int b = 1; b < 4; b++) {
                        mbar_waitc(sb + BAR_FULLB + 8 * b, 0);
                        const desc_t da = dA + b * (2 * SLOT >> 4), db = dB + b * (SLOT >> 4);
                        wg_fence();
#pragma unroll
                        for (int k = 0; k < 8; k++) wgmma_n64(accq, da + (k >> 2) * (SLOT >> 4) + (k & 3) * 2, db + 128 * k, 1);
                        wg_commit();
                    }
                    mbar_waitc(sb + BAR_CSQ, 0);
                    wg_wait<0>();
                    fence_acc<32>(accq);
                    mbar_arrive_cl_if(eb + 8 * (1 + (lane >> 1)), lane < 6);
                    TL(4, tid == 0);
#pragma unroll
                    for (int hh = 0; hh < 4; hh++)
                        ln_frag<false>(accq + 8 * hh, sb + OFF_CS1 + (16 * hh + 2 * q) * 4, 0.f, s0.y, 0.f, s1.y, a + 4 * hh);
                }
            }
        }
        uint32_t res_lo[8], res_hi[8], ack[4];
        const uint32_t own_rows = sb + OFF_A + j * SLOT + warp * 2048;
#pragma unroll
        for (int b = 0; b < 4; b++)
            ldsm4(own_rows + lrow + (((2 * b + ch) ^ sw) << 4), res_lo[2 * b], res_hi[2 * b], res_lo[2 * b + 1], res_hi[2 * b + 1]);
        mbar_arrive_if(sb + BAR_EMPTYA + 8 * lane, lane < 8 && lane != j && lane != (j == 0));
        TL(5, tid == 0);
        mbar_waitc(sb + BAR_KVR, 0);
        TL(6, tid == 0);
        {
            const uint32_t kvs = sb + OFF_A + (j == 0) * SLOT;
            uint32_t o_lo[8], o_hi[8];
#pragma unroll
            for (int hh = 0; hh < 4; hh++) {
                uint32_t b[8], zb[4];
                const uint32_t base = kvs + hh * 32 * 48;
                ldsm4t(base + (lane & 15) * 48 + (lane >> 4) * 16, b[0], b[1], b[2], b[3]);
                ldsm4t(base + (16 + (lane & 15)) * 48 + (lane >> 4) * 16, b[4], b[5], b[6], b[7]);
                ldsm4t(base + lane * 48 + 32, zb[0], zb[1], zb[2], zb[3]);
                float n0[4], n1[4], dn[4];
                mma16816_z(n0, fp + 4 * hh, b[0], b[1]); mma16816_z(n1, fp + 4 * hh, b[2], b[3]); mma16816_z(dn, fp + 4 * hh, zb[0], zb[1]);
                mma16816(n0, fm + 4 * hh, b[4], b[5]); mma16816(n1, fm + 4 * hh, b[6], b[7]); mma16816(dn, fm + 4 * hh, zb[2], zb[3]);
                const float i0 = rcp(dn[0] + 1e-6f), i1 = rcp(dn[2] + 1e-6f);
                o_lo[2 * hh] = pack_bf16(n0[0] * i0, n0[1] * i0); o_hi[2 * hh] = pack_bf16(n0[2] * i1, n0[3] * i1);
                o_lo[2 * hh + 1] = pack_bf16(n1[0] * i0, n1[1] * i0); o_hi[2 * hh + 1] = pack_bf16(n1[2] * i1, n1[3] * i1);
            }
            __syncwarp();
            mbar_arrive_if(sb + BAR_EMPTYA + 8 * (j == 0), l0);
            rg.slot = 4; rg.phase = 0;
            store_tile(own_rows, g_act + role * 1024 + warp * 128 + lane, o_lo, o_hi, lane, ack);
            TL(7, tid == 0);
        }
        float acch[32];
        {
            float* acc = acch;
#pragma unroll
            for (int t = 0; t < 8; t++) {
                acc[4 * t] = bf_lo(res_lo[t]); acc[4 * t + 1] = bf_hi(res_lo[t]);
                acc[4 * t + 2] = bf_lo(res_hi[t]); acc[4 * t + 3] = bf_hi(res_hi[t]);
            }
            fence_acc<32>(acc);
            int pa = 0;
#pragma unroll 1
            for (int kp = 0; kp < 4; kp++) {
                mbar_waitc(sb + BAR_FULLB + 8 * rg.slot, rg.phase);
#pragma unroll
                for (int hf = 0; hf < 2; hf++) {
                    const int i = 2 * kp + hf, kt = KORD(i, j);
                    mbar_waitc(sb + BAR_FULLA + 8 * kt, i != 0);
                    TL(8, i == 1 && tid == 0);
                    const desc_t da = dA + kt * (SLOT >> 4), db = dB + rg.slot * (SLOT >> 4);
                    wg_fence();
#pragma unroll
                    for (int k = 0; k < 4; k++) wgmma_n64(acc, da + 2 * k, db + (hf * 4 + k) * 128, 1);
                    wg_commit();
                    wg_wait<1>();
                    mbar_arrive_if(sb + BAR_EMPTYA + 8 * pa, l0 && i > 1);
                    if (hf == 0) {
                        mbar_arrive_cl_if(eb + 8 * prev, l2 && i > 0);
                        if (i == 0) { signal_late(flag_m, ack, P.zero, l0); TL(20, tid == 0); }
                    }
                    pa = kt;
                }
                prev = rg.slot; rg.adv();
            }
            wg_wait<0>();
            fence_acc<32>(acc);
            mbar_arrive_if(sb + BAR_EMPTYA + 8 * pa, l0);
            mbar_arrive_cl_if(eb + 8 * prev, l2);
            TL(9, tid == 0);
#pragma unroll
            for (int t = 0; t < 8; t++) {
                res_lo[t] = pack_bf16(acc[4 * t], acc[4 * t + 1]);
                res_hi[t] = pack_bf16(acc[4 * t + 2], acc[4 * t + 3]);
            }
            store_tile(own_rows, g_act + (128 + role) * 1024 + warp * 128 + lane, res_lo, res_hi, lane, ack);
            TL(10, tid == 0);
        }
        float acc0[64], acc1[64], acc2[56], nm0, nm1;
        float4 cs[8];
        uint32_t hr[16];
#define P3_GROUP(MMA, ACC, KT)                                                                              \
        mbar_waitc(sb + BAR_FULLB + 8 * rg.slot, rg.phase);                                                 \
        {                                                                                                   \
            const desc_t da = dA + (KT) * (SLOT >> 4), db = dB + rg.slot * (SLOT >> 4);                     \
            wg_fence();                                                                                     \
            _Pragma("unroll") for (int k = 0; k < 4; k++) MMA(ACC, da + 2 * k, db + 128 * k, (i | k) != 0); \
            wg_commit();                                                                                    \
        }
#define P3_CS(C, NT)    \
        _Pragma("unroll") for (int t = 0; t < (NT); t++) lds_f4_if(cs[t], sb + OFF_CS3 + q * 16 + 512 * (C) + 64 * t, i == t);
#define P3_EPI2(C, ACC)                                                                                     \
        if (i == 0) {                                                                                       \
            fence_acc<64>(ACC);                                                                             \
            if (C) mbar_waitc(sb + BAR_FULLB + 8 * 4, 1);                                                   \
            hh_stage2<0, 2>(ACC, cs, nm0, nm1, stg, lane);                                                  \
            mbar_waitc(sb + BAR_CSG + 8 * (C) + 8, 0);                                                      \
        }                                                                                                   \
        if (i == 1) {                                                                                       \
            hh_stage2<2, 4>(ACC, cs, nm0, nm1, stg, lane);                                                  \
            fence_async_smem();                                                                             \
            __syncwarp();                                                                                   \
            mbar_arrive_if(sb + BAR_STG + 8 * (C), l0);                                                     \
        }
#define P3_EPI(C, ACC, N, NTP)                                                                              \
        fence_acc<N>(ACC);                                                                                  \
        TL(11 + (C), tid == 0);                                                                             \
        hh_stage<NTP>(ACC, cs, nm0, nm1, sb + OFF_B + 4 * SLOT + warp * 2048, lane);                        \
        mbar_arrive_if(sb + BAR_STG + 8 * (C), l0);                                                         \
        TL(50 + (C), tid == 0);
        const uint32_t stg = sb + OFF_B + 4 * SLOT + warp * 2048;
        const uint32_t blk = ((lane & 7) + (lane >> 4) * 8) * 128 + (((2 * wv + ((lane >> 3) & 1)) ^ (lane & 7)) << 4);
#pragma unroll 1
        for (int i = 0; i < 8; i++) {
            const int kt = KORD(i, j);
            mbar_waitc(sb + BAR_FULLA + 8 * kt, 0);
            TL(44, tid == 0 && i == 1);
            P3_GROUP(wgmma_n128, acc0, kt)
            if (i == 7) {
                mbar_waitc(sb + BAR_CS3, 0);
                nm0 = lds_f2(sb + OFF_CS1 + (16 * warp + g) * 8).x; nm1 = lds_f2(sb + OFF_CS1 + (16 * warp + g + 8) * 8).x;
            }
            wg_wait<1>();
            mbar_arrive_cl_if(eb + 8 * prev, l2 && i > 0);
            if (i == 0) {
                signal_late(flag_m + 32, ack, P.zero, l0);
                TL(21, tid == 0);
                {
                    fence_acc<32>(acch);
                    const float* acc = acch;
                    float s0 = 0.f, s1 = 0.f;
#pragma unroll
                    for (int t = 0; t < 8; t++) { s0 += acc[4 * t] + acc[4 * t + 1]; s1 += acc[4 * t + 2] + acc[4 * t + 3]; }
            s0 += __shfl_xor_sync(0xffffffffu, s0, 1); s1 += __shfl_xor_sync(0xffffffffu, s1, 1);
            s0 += __shfl_xor_sync(0xffffffffu, s0, 2); s1 += __shfl_xor_sync(0xffffffffu, s1, 2);
            const float mu0 = s0 * (1.f / 64), mu1 = s1 * (1.f / 64);
            float q0 = 0.f, q1 = 0.f;
#pragma unroll
            for (int t = 0; t < 8; t++) {
                float d;
                d = acc[4 * t] - mu0; q0 = fmaf(d, d, q0);
                d = acc[4 * t + 1] - mu0; q0 = fmaf(d, d, q0);
                d = acc[4 * t + 2] - mu1; q1 = fmaf(d, d, q1);
                d = acc[4 * t + 3] - mu1; q1 = fmaf(d, d, q1);
            }
            q0 += __shfl_xor_sync(0xffffffffu, q0, 1); q1 += __shfl_xor_sync(0xffffffffu, q1, 1);
            q0 += __shfl_xor_sync(0xffffffffu, q0, 2); q1 += __shfl_xor_sync(0xffffffffu, q1, 2);
            st_tagged_if(g_hstat + (role * 128 + 16 * warp + g + 8 * (q & 1)) * 2, q ? mu1 : mu0, q ? q1 : q0, epoch, q < 2);
                }
                bar_sync(2 + w, 128);
#pragma unroll
                for (int tp = 0; tp < 4; tp++) ldsm4t(sa + j * SLOT + blk + tp * 2048, hr[4 * tp], hr[4 * tp + 1], hr[4 * tp + 2], hr[4 * tp + 3]);
                mbar_waitc(sb + BAR_CSG, 0);
#pragma unroll
                for (int t = 0; t < 8; t++) cs[t] = lds_f4(sb + OFF_CS3 + q * 16 + 64 * t);
            }
            prev = rg.slot; rg.adv5();
        }
#pragma unroll 1
        for (int i = 0; i < 8; i++) {
            P3_GROUP(wgmma_n128, acc1, i)
            wg_wait<1>();
            mbar_arrive_cl_if(eb + 8 * prev, l2);
            P3_EPI2(0, acc0)
            P3_CS(1, 8)
            prev = rg.slot; rg.adv5();
        }
#pragma unroll 1
        for (int i = 0; i < 8; i++) {
            P3_GROUP(wgmma_n112, acc2, i)
            wg_wait<1>();
            mbar_arrive_cl_if(eb + 8 * prev, l2);
            mbar_arrive_if(sb + BAR_EMPTYA + 8 * ((i + 7) & 7), l0 && i > 0);
            if (i == 0) { mbar_waitc(sb + BAR_FULLB + 8 * 4, 1); P3_EPI(1, acc1, 64, 4) mbar_waitc(sb + BAR_CSG + 16, 0); }
            P3_CS(2, 6)
            prev = rg.slot; rg.adv5();
        }
        mbar_waitc(sb + BAR_FULLB + 8 * 4, 0);
        wg_wait<0>();
        mbar_arrive_cl_if(eb + 8 * prev, l2);
        mbar_arrive_if(sb + BAR_EMPTYA + 8 * 7, l0);
        P3_EPI(2, acc2, 56, 3)
        {
            float acc[64];
            const desc_t dA0 = desc_lo(sb + OFF_A);
#define KT_P4(I, NK)                                                                                        \
        const int s_ = (2 * (I) + w) & 7;                                                                   \
        mbar_waitc(sb + BAR_FULLB + 8 * rg.slot, rg.phase);                                                 \
        mbar_waitc(sb + BAR_FULLA + 8 * s_, (((I) >> 2) + 1) & 1);                                          \
        const desc_t dh_ = dA0 + s_ * (SLOT >> 4), dw_ = dB + rg.slot * (SLOT >> 4) + w * 512;              \
        wg_fence();                                                                                         \
        _Pragma("unroll") for (int k = 0; k < (NK); k++) wgmma_n128_tn(acc, dw_ + 128 * k, dh_ + 2 * k, ((I) | k) != 0); \
        wg_commit();                                                                                        \
        wg_wait<1>();
#pragma unroll 1
            for (int i = 0; i < 8; i++) {
                KT_P4(i, 4)
                mbar_arrive_n_if(sb + BAR_EMPTYA + 8 * ((s_ + 6) & 7), 2, l0 && i > 0);
                mbar_arrive_cl_if(eb + 8 * prev, l2 && i > 0);
#pragma unroll
                for (int t = 0; t < 8; t++) lds_f4_if(cs[t], sb + OFF_CS1 + (64 * w + 8 * t + 2 * q) * 8, i == t);
                prev = rg.slot; rg.adv5();
            }
#pragma unroll 1
            for (int i = 8; i < 12; i++) {
                KT_P4(i, 3)
                mbar_arrive_n_if(sb + BAR_EMPTYA + 8 * ((s_ + 6) & 7), 2, l0);
                rg.adv5();
            }
            wg_wait<0>();
            fence_acc<64>(acc);
            TL(15, tid == 0);
            const uint32_t xch = sb + OFF_A + 2 * SLOT + (tid & 127) * 16;
            if (w) {
#pragma unroll
                for (int t = 0; t < 8; t++) {
                    sts128(xch + SLOT + t * 2048, __float_as_uint(acc[4 * t]), __float_as_uint(acc[4 * t + 1]),
                           __float_as_uint(acc[4 * t + 2]), __float_as_uint(acc[4 * t + 3]));
                }
#pragma unroll
                for (int t = 0; t < 32; t++) acc[t] = acc[32 + t];
            } else {
#pragma unroll
                for (int t = 0; t < 8; t++)
                    sts128(xch + t * 2048, __float_as_uint(acc[32 + 4 * t]), __float_as_uint(acc[33 + 4 * t]),
                           __float_as_uint(acc[34 + 4 * t]), __float_as_uint(acc[35 + 4 * t]));
            }
            bar_sync(1, 256);
            float4 o[8];
#pragma unroll
            for (int t = 0; t < 8; t++) o[t] = lds_f4(xch + (w ^ 1) * SLOT + t * 2048);
            const uint32_t tile = sb + OFF_A + w * SLOT;
#pragma unroll
            for (int t = 0; t < 8; t++) {
                hr[2 * t] = pack_bf16(fmaf(acc[4 * t] + o[t].x, cs[t].y, bf_lo(hr[2 * t])), fmaf(acc[4 * t + 1] + o[t].y, cs[t].w, bf_hi(hr[2 * t])));
                hr[2 * t + 1] = pack_bf16(fmaf(acc[4 * t + 2] + o[t].z, cs[t].y, bf_lo(hr[2 * t + 1])), fmaf(acc[4 * t + 3] + o[t].w, cs[t].w, bf_hi(hr[2 * t + 1])));
            }
#pragma unroll
            for (int tp = 0; tp < 4; tp++) stsm4t(tile + blk + tp * 2048, hr[4 * tp], hr[4 * tp + 1], hr[4 * tp + 2], hr[4 * tp + 3]);
            fence_async_smem();
            bar_sync(2 + w, 128);
            if ((tid & 127) == 0) {
                tma_store2d(&P.tout, tile, 64 * j, 128 * m + 64 * w);
                asm volatile("cp.async.bulk.wait_group.read 0;" ::: "memory");
            }
            if (tid == 0 && role == 0) g_epoch = epoch + 1;
            TL(16, tid == 0); TLG(1, tid == 0);
        }
    }
}

__global__ void probe_kernel() {}

typedef CUresult (*EncodeFn)(CUtensorMap*, CUtensorMapDataType, cuuint32_t, void*, const cuuint64_t*, const cuuint64_t*,
                             const cuuint32_t*, const cuuint32_t*, CUtensorMapInterleave, CUtensorMapSwizzle,
                             CUtensorMapL2promotion, CUtensorMapFloatOOBfill);

static void make_map2d(EncodeFn enc, CUtensorMap* tm, const void* base, uint64_t cols, uint64_t rows, uint64_t pitch_elems,
                       uint32_t box_rows) {
    cuuint64_t gd[2] = {cols, rows};
    cuuint64_t gs[1] = {pitch_elems * 2};
    cuuint32_t bd[2] = {64, box_rows};
    cuuint32_t es[2] = {1, 1};
    enc(tm, CU_TENSOR_MAP_DATA_TYPE_BFLOAT16, 2, const_cast<void*>(base), gd, gs, bd, es, CU_TENSOR_MAP_INTERLEAVE_NONE,
        CU_TENSOR_MAP_SWIZZLE_128B, CU_TENSOR_MAP_L2_PROMOTION_L2_256B, CU_TENSOR_MAP_FLOAT_OOB_FILL_NONE);
}

}

extern "C" void kernel_launch(void* const* d_in, const int* in_sizes, int n_in, void* d_out, int out_size) {
    using namespace hk;
    (void)in_sizes; (void)n_in; (void)out_size;
    static EncodeFn enc = nullptr;
    static int std_layout = 0;
    if (!enc) {
        void* fn = nullptr;
        cudaDriverEntryPointQueryResult qr;
        cudaGetDriverEntryPoint("cuTensorMapEncodeTiled", &fn, cudaEnableDefault, &qr);
        enc = (EncodeFn)fn;
        cudaFuncSetAttribute(fused_kernel, cudaFuncAttributeMaxDynamicSharedMemorySize, SMEM_BYTES);
        int dev = 0, sms = 0;
        cudaGetDevice(&dev);
        cudaDeviceGetAttribute(&sms, cudaDevAttrMultiProcessorCount, dev);
        cudaFuncSetAttribute(probe_kernel, cudaFuncAttributeNonPortableClusterSizeAllowed, 1);
        cudaFuncSetAttribute(probe_kernel, cudaFuncAttributeMaxDynamicSharedMemorySize, SMEM_BYTES);
        const int sizes[3] = {8, 9, 16}, want[3] = {15, 9, 7};
        bool ok = sms == NCTA;
        for (int i = 0; i < 3 && ok; i++) {
            cudaLaunchConfig_t cfg = {};
            cfg.gridDim = dim3(sizes[i] * 8); cfg.blockDim = dim3(NTHREADS); cfg.dynamicSmemBytes = SMEM_BYTES;
            cudaLaunchAttribute at;
            at.id = cudaLaunchAttributeClusterDimension;
            at.val.clusterDim.x = sizes[i]; at.val.clusterDim.y = 1; at.val.clusterDim.z = 1;
            cfg.attrs = &at; cfg.numAttrs = 1;
            int n = 0;
            ok = cudaOccupancyMaxActiveClusters(&n, probe_kernel, &cfg) == cudaSuccess && n == want[i];
        }
        (void)cudaGetLastError();
        std_layout = ok ? 1 : 0;
    }
    Params P;
    const __nv_bfloat16* x = (const __nv_bfloat16*)d_in[0];
    P.x = x;
    P.wqkv = (const __nv_bfloat16*)d_in[1];
    P.wphi = (const __nv_bfloat16*)d_in[2];
    P.wo = (const __nv_bfloat16*)d_in[3];
    P.wg = (const __nv_bfloat16*)d_in[5];
    P.wu = (const __nv_bfloat16*)d_in[6];
    P.wd = (const __nv_bfloat16*)d_in[7];
    P.out = (__nv_bfloat16*)d_out;
    P.zero = 0;
    for (int i = 0; i < NCTA; i++) {
        const int odd = i & 1;
        int role = i < 4 ? 128 + i : (((i - 4) >> 4) * 2 + odd) * 8 + (((i - 4) >> 1) & 7);
        if (std_layout) {
            const int tpc = i < 8 ? 62 + (i >> 1) : (i - 8) >> 1;
            if (tpc < 32) role = (tpc & 7) ? (2 * ((tpc & 7) - 1) + odd) * 8 + (tpc >> 3) : (14 + odd) * 8 + (tpc >> 3);
            else if (tpc < 60) role = (2 * ((tpc - 32) % 7) + odd) * 8 + 4 + (tpc - 32) / 7;
            else if (tpc < 62) role = 128 + (tpc - 60) * 2 + odd;
            else role = (14 + odd) * 8 + 4 + (tpc - 62);
        }
        P.role[i] = (unsigned char)role;
    }
    make_map2d(enc, &P.tx, x, DM, SEQ, DM, 128);
    make_map2d(enc, &P.twq, P.wqkv, 3 * DM, DM, 3 * DM, 64);
    make_map2d(enc, &P.two, P.wo, DM, DM, DM, 64);
    make_map2d(enc, &P.twg, P.wg, FF, DM, FF, 64);
    make_map2d(enc, &P.twu, P.wu, FF, DM, FF, 64);
    make_map2d(enc, &P.twd, P.wd, DM, FF, DM, 64);
    make_map2d(enc, &P.tout, d_out, DM, SEQ, DM, 64);
    fused_kernel<<<NCTA, NTHREADS, SMEM_BYTES>>>(P);
}
```

```cpp
#include <cuda_runtime.h>
#include <cuda_bf16.h>
#include <cuda.h>
#include <stdint.h>

namespace hk {

constexpr int SEQ = 2048, DM = 512, FF = 1376;
constexpr int NCTA = 132;
constexpr int NTHREADS = 384;
constexpr uint32_t SLOT = 16384;
constexpr uint32_t OFF_A = 0, OFF_B = 8 * SLOT, OFF_MISC = 14 * SLOT;
constexpr uint32_t BAR_FULLA = OFF_MISC + 0, BAR_EMPTYA = OFF_MISC + 64, BAR_FULLB = OFF_MISC + 128,
                   BAR_EMPTYB = OFF_MISC + 176, BAR_CS1 = OFF_MISC + 224, BAR_CS3 = OFF_MISC + 232,
                   BAR_CSQ = OFF_MISC + 240, BAR_CSV = OFF_MISC + 248,
                   BAR_STG = OFF_MISC + 256,
                   BAR_KVW = OFF_MISC + 280, BAR_KVR = OFF_MISC + 288, BAR_CSG = OFF_MISC + 296;
constexpr uint32_t OFF_CS1 = OFF_MISC + 384;
constexpr uint32_t OFF_CS3 = OFF_CS1 + 1024;
constexpr uint32_t OFF_XST = OFF_CS3;
constexpr uint32_t SMEM_BYTES = OFF_CS3 + 1536;
#define KORD(i, j) ((i) == 0 ? (j) : (i) - ((i) <= (j)))
constexpr int NB = 6;
#define PF_DELAY 2
#define KV_POLL 1
constexpr int AHEAD = 3;

constexpr int ACC_SIZE = 3 * 256 * 4;

__device__ __align__(1024) uint4 g_act[5 * 128 * 1024];
__device__ __align__(128) unsigned long long g_hstat[SEQ * 16];
__device__ __align__(128) unsigned long long g_xstat[SEQ * 2];
__device__ __align__(128) float g_acc[8 * ACC_SIZE];
__device__ __align__(128) unsigned long long g_cs[8 * 6 * 128];
__device__ __align__(128) unsigned g_flag[16 * 5 * 32 + 32];
__device__ unsigned g_epoch = 1;

#define TL(i, pred) do {} while (0)
#define TLG(i, pred) do {} while (0)

struct Params {
    CUtensorMap tx, twq, two, twg, twu, twd, tout;
    const __nv_bfloat16 *x, *wqkv, *wphi, *wo, *wg, *wu, *wd;
    __nv_bfloat16* out;
    unsigned zero;
    unsigned char role[NCTA];
};

__device__ __forceinline__ uint32_t smem_u32(const void* p) { return (uint32_t)__cvta_generic_to_shared(p); }
__device__ __forceinline__ void mbar_init(uint32_t bar, uint32_t cnt) {
    asm volatile("mbarrier.init.shared::cta.b64 [%0], %1;" ::"r"(bar), "r"(cnt) : "memory");
}
__device__ __forceinline__ void mbar_expect_tx(uint32_t bar, uint32_t bytes) {
    asm volatile("mbarrier.arrive.expect_tx.shared::cta.b64 _, [%0], %1;" ::"r"(bar), "r"(bytes) : "memory");
}
__device__ __forceinline__ void mbar_arrive(uint32_t bar) {
    asm volatile("mbarrier.arrive.shared::cta.b64 _, [%0];" ::"r"(bar) : "memory");
}
__device__ __forceinline__ void mbar_arrive_if(uint32_t bar, bool pred) {
    asm volatile("{.reg .pred p; setp.ne.u32 p, %1, 0; @p mbarrier.arrive.shared::cta.b64 _, [%0];}" ::"r"(bar), "r"((uint32_t)pred) : "memory");
}
__device__ __forceinline__ bool mbar_try(uint32_t bar, uint32_t parity) {
    uint32_t ok;
    asm volatile("{.reg .pred p; mbarrier.try_wait.parity.shared::cta.b64 p, [%1], %2; selp.u32 %0,1,0,p;}"
                 : "=r"(ok) : "r"(bar), "r"(parity) : "memory");
    return ok;
}
__device__ __forceinline__ bool mbar_test(uint32_t bar, uint32_t parity) {
    uint32_t ok;
    asm volatile("{.reg .pred p; mbarrier.test_wait.parity.shared::cta.b64 p, [%1], %2; selp.u32 %0,1,0,p;}"
                 : "=r"(ok) : "r"(bar), "r"(parity) : "memory");
    return ok;
}
__device__ __forceinline__ void trap_if_gt(uint32_t v, uint32_t lim) {
    asm volatile("{.reg .pred p; setp.gt.u32 p, %0, %1; @p trap;}" ::"r"(v), "r"(lim));
}
__device__ __forceinline__ void mbar_wait(uint32_t bar, uint32_t parity) {
    asm volatile("{\n"
                 ".reg .pred P1, P2;\n"
                 ".reg .u32 c;\n"
                 "mov.u32 c, 0;\n"
                 "LAB_WAIT:\n"
                 "mbarrier.try_wait.parity.shared::cta.b64 P1, [%0], %1;\n"
                 "@P1 bra LAB_DONE;\n"
                 "add.u32 c, c, 1;\n"
                 "setp.gt.u32 P2, c, 4194304;\n"
                 "@P2 trap;\n"
                 "bra LAB_WAIT;\n"
                 "LAB_DONE:\n"
                 "}" ::"r"(bar), "r"(parity) : "memory");
}
__device__ __forceinline__ void mbar_waitc(uint32_t bar, uint32_t parity) {
    asm volatile("{\n"
                 ".reg .pred P1;\n"
                 "LAB_WAIT:\n"
                 "mbarrier.try_wait.parity.shared::cta.b64 P1, [%0], %1;\n"
                 "@!P1 bra LAB_WAIT;\n"
                 "}" ::"r"(bar), "r"(parity) : "memory");
}
__device__ __forceinline__ void tma2d(uint32_t dst, const CUtensorMap* tm, uint32_t bar, int c0, int c1) {
    asm volatile("cp.async.bulk.tensor.2d.shared::cluster.global.mbarrier::complete_tx::bytes [%0], [%1, {%3, %4}], [%2];"
                 ::"r"(dst), "l"(tm), "r"(bar), "r"(c0), "r"(c1) : "memory");
}
__device__ __forceinline__ void tma2d_mc(uint32_t dst, const CUtensorMap* tm, uint32_t bar, int c0, int c1) {
    asm volatile("cp.async.bulk.tensor.2d.shared::cluster.global.mbarrier::complete_tx::bytes.multicast::cluster [%0], [%1, {%3, %4}], [%2], %5;"
                 ::"r"(dst), "l"(tm), "r"(bar), "r"(c0), "r"(c1), "h"((uint16_t)3) : "memory");
}
__device__ __forceinline__ uint32_t mapa(uint32_t addr, uint32_t rank) {
    uint32_t r; asm("mapa.shared::cluster.u32 %0, %1, %2;" : "=r"(r) : "r"(addr), "r"(rank)); return r;
}
__device__ __forceinline__ void mbar_arrive_cl_if(uint32_t cbar, bool pred) {
    asm volatile("{.reg .pred p; setp.ne.u32 p, %1, 0; @p mbarrier.arrive.shared::cluster.b64 _, [%0];}" ::"r"(cbar), "r"((uint32_t)pred) : "memory");
}
__device__ __forceinline__ bool elect_one() {
    uint32_t ok;
    asm volatile("{.reg .pred p; elect.sync _|p, 0xffffffff; selp.u32 %0, 1, 0, p;}" : "=r"(ok));
    return ok;
}
__device__ __forceinline__ void prefetch_tmap(const CUtensorMap* tm) {
    asm volatile("prefetch.tensormap [%0];" ::"l"(tm) : "memory");
}
__device__ __forceinline__ void prefetch_l2(const void* p, uint32_t bytes) {
    asm volatile("cp.async.bulk.prefetch.L2.global [%0], %1;" ::"l"(p), "r"(bytes) : "memory");
}
__device__ __forceinline__ unsigned ld_acquire(const unsigned* p) {
    unsigned v; asm volatile("ld.acquire.gpu.global.u32 %0, [%1];" : "=r"(v) : "l"(p) : "memory"); return v;
}
__device__ __forceinline__ uint4 ld_acquire4(const unsigned* p) {
    uint4 v;
    asm volatile("ld.acquire.gpu.global.v4.u32 {%0,%1,%2,%3}, [%4];" : "=r"(v.x), "=r"(v.y), "=r"(v.z), "=r"(v.w) : "l"(p) : "memory");
    return v;
}
__device__ __forceinline__ unsigned ld_relaxed(const unsigned* p) {
    unsigned v; asm volatile("ld.relaxed.gpu.global.u32 %0, [%1];" : "=r"(v) : "l"(p)); return v;
}
__device__ __forceinline__ void st_relaxed(unsigned* p, unsigned v) {
    asm volatile("st.relaxed.gpu.global.u32 [%0], %1;" ::"l"(p), "r"(v) : "memory");
}
__device__ __forceinline__ void red_relaxed(unsigned* p, unsigned v) {
    asm volatile("red.relaxed.gpu.global.add.u32 [%0], %1;" ::"l"(p), "r"(v) : "memory");
}
__device__ __forceinline__ void fence_gpu() { asm volatile("fence.acq_rel.gpu;" ::: "memory"); }
__device__ __forceinline__ void fence_async_smem() { asm volatile("fence.proxy.async.shared::cta;" ::: "memory"); }
__device__ __forceinline__ void fence_async_global() { asm volatile("fence.proxy.async.global;" ::: "memory"); }
__device__ __forceinline__ uint32_t readback(const void* p) {
    uint32_t v; asm volatile("ld.relaxed.gpu.global.u32 %0, [%1];" : "=r"(v) : "l"(p) : "memory"); return v;
}
__device__ __forceinline__ void wait_count(const unsigned* p, unsigned target) {
    uint32_t it = 0;
    while ((int)(readback(p) - target) < 0) trap_if_gt(++it, 1u << 22);
}
__device__ __forceinline__ void wait_count_warp(const unsigned* p, unsigned target) {
    uint32_t it = 0;
    while (__any_sync(0xffffffffu, (int)(readback(p) - target) < 0)) trap_if_gt(++it, 1u << 22);
}
__device__ __forceinline__ void red_f32(float* p, float a) {
    asm volatile("red.relaxed.gpu.global.add.f32 [%0], %1;" ::"l"(p), "f"(a) : "memory");
}
__device__ __forceinline__ void red_f32x2(float* p, float a, float b) {
    asm volatile("red.relaxed.gpu.global.add.v2.f32 [%0], {%1, %2};" ::"l"(p), "f"(a), "f"(b) : "memory");
}
__device__ __forceinline__ void red_f32x4(float* p, float a, float b, float c, float d) {
    asm volatile("red.relaxed.gpu.global.add.v4.f32 [%0], {%1, %2, %3, %4};" ::"l"(p), "f"(a), "f"(b), "f"(c), "f"(d) : "memory");
}
__device__ __forceinline__ float4 ld_l2_f4(const float* p) {
    float4 v;
    asm volatile("ld.relaxed.gpu.global.v4.f32 {%0,%1,%2,%3}, [%4];" : "=f"(v.x), "=f"(v.y), "=f"(v.z), "=f"(v.w) : "l"(p) : "memory");
    return v;
}
__device__ __forceinline__ float2 ld_l2_f2(const float* p) {
    float2 v;
    asm volatile("ld.relaxed.gpu.global.v2.f32 {%0,%1}, [%2];" : "=f"(v.x), "=f"(v.y) : "l"(p) : "memory");
    return v;
}
__device__ __forceinline__ float ld_l2_f(const float* p) {
    float v;
    asm volatile("ld.relaxed.gpu.global.f32 %0, [%1];" : "=f"(v) : "l"(p) : "memory");
    return v;
}
__device__ __forceinline__ uint4 ldg_nc(const void* p) {
    uint4 v;
    asm volatile("ld.global.nc.L1::no_allocate.v4.u32 {%0,%1,%2,%3}, [%4];" : "=r"(v.x), "=r"(v.y), "=r"(v.z), "=r"(v.w) : "l"(p));
    return v;
}
__device__ __forceinline__ void stg128(void* p, uint32_t a, uint32_t b, uint32_t c, uint32_t d) {
    asm volatile("st.global.v4.u32 [%0], {%1,%2,%3,%4};" ::"l"(p), "r"(a), "r"(b), "r"(c), "r"(d) : "memory");
}
__device__ __forceinline__ uint4 lds128(uint32_t a) {
    uint4 v;
    asm volatile("ld.shared.v4.u32 {%0,%1,%2,%3}, [%4];" : "=r"(v.x), "=r"(v.y), "=r"(v.z), "=r"(v.w) : "r"(a) : "memory");
    return v;
}
__device__ __forceinline__ float2 lds_f2(uint32_t a) {
    float2 v;
    asm volatile("ld.shared.v2.f32 {%0,%1}, [%2];" : "=f"(v.x), "=f"(v.y) : "r"(a) : "memory");
    return v;
}
__device__ __forceinline__ void sts_f2(uint32_t a, float x, float y) {
    asm volatile("st.shared.v2.f32 [%0], {%1,%2};" ::"r"(a), "f"(x), "f"(y) : "memory");
}
__device__ __forceinline__ void sts64(uint32_t a, uint32_t x, uint32_t y) {
    asm volatile("st.shared.v2.u32 [%0], {%1,%2};" ::"r"(a), "r"(x), "r"(y) : "memory");
}
__device__ __forceinline__ void sts128(uint32_t a, uint32_t x, uint32_t y, uint32_t z, uint32_t w) {
    asm volatile("st.shared.v4.u32 [%0], {%1,%2,%3,%4};" ::"r"(a), "r"(x), "r"(y), "r"(z), "r"(w) : "memory");
}
__device__ __forceinline__ void stsm4(uint32_t a, uint32_t r0, uint32_t r1, uint32_t r2, uint32_t r3) {
    asm volatile("stmatrix.sync.aligned.m8n8.x4.shared.b16 [%0], {%1,%2,%3,%4};" ::"r"(a), "r"(r0), "r"(r1), "r"(r2), "r"(r3) : "memory");
}
__device__ __forceinline__ void stsm4t(uint32_t a, uint32_t r0, uint32_t r1, uint32_t r2, uint32_t r3) {
    asm volatile("stmatrix.sync.aligned.m8n8.x4.trans.shared.b16 [%0], {%1,%2,%3,%4};" ::"r"(a), "r"(r0), "r"(r1), "r"(r2), "r"(r3) : "memory");
}
__device__ __forceinline__ void tma_store2d(const CUtensorMap* tm, uint32_t src, int c0, int c1) {
    asm volatile("cp.async.bulk.tensor.2d.global.shared::cta.bulk_group [%0, {%2, %3}], [%1];" ::"l"(tm), "r"(src), "r"(c0), "r"(c1) : "memory");
    asm volatile("cp.async.bulk.commit_group;" ::: "memory");
}
__device__ __forceinline__ void ldsm4(uint32_t a, uint32_t& r0, uint32_t& r1, uint32_t& r2, uint32_t& r3) {
    asm volatile("ldmatrix.sync.aligned.m8n8.x4.shared.b16 {%0,%1,%2,%3}, [%4];" : "=r"(r0), "=r"(r1), "=r"(r2), "=r"(r3) : "r"(a) : "memory");
}
__device__ __forceinline__ void ldsm4t(uint32_t a, uint32_t& r0, uint32_t& r1, uint32_t& r2, uint32_t& r3) {
    asm volatile("ldmatrix.sync.aligned.m8n8.x4.trans.shared.b16 {%0,%1,%2,%3}, [%4];" : "=r"(r0), "=r"(r1), "=r"(r2), "=r"(r3) : "r"(a) : "memory");
}
__device__ __forceinline__ void mma16816(float* c, const uint32_t* a, uint32_t b0, uint32_t b1) {
    asm("mma.sync.aligned.m16n8k16.row.col.f32.bf16.bf16.f32 {%0,%1,%2,%3}, {%4,%5,%6,%7}, {%8,%9}, {%0,%1,%2,%3};"
                 : "+f"(c[0]), "+f"(c[1]), "+f"(c[2]), "+f"(c[3])
                 : "r"(a[0]), "r"(a[1]), "r"(a[2]), "r"(a[3]), "r"(b0), "r"(b1));
}
__device__ __forceinline__ uint32_t pack_bf16(float lo, float hi) {
    uint32_t r; asm("cvt.rn.bf16x2.f32 %0, %1, %2;" : "=r"(r) : "f"(hi), "f"(lo)); return r;
}
__device__ __forceinline__ float bf_lo(uint32_t w) { return __uint_as_float(w << 16); }
__device__ __forceinline__ float bf_hi(uint32_t w) { return __uint_as_float(w & 0xffff0000u); }
__device__ __forceinline__ float ex2(float x) { float r; asm("ex2.approx.ftz.f32 %0, %1;" : "=f"(r) : "f"(x)); return r; }
__device__ __forceinline__ float rcp(float x) { float r; asm("rcp.approx.ftz.f32 %0, %1;" : "=f"(r) : "f"(x)); return r; }
__device__ __forceinline__ void bar_sync(int id, int n) { asm volatile("bar.sync %0, %1;" ::"r"(id), "r"(n) : "memory"); }

typedef unsigned long long desc_t;
__device__ __forceinline__ desc_t desc_lo(uint32_t addr) { return (desc_t)(((addr & 0x3FFFF) >> 4) | (512u << 16)) | (0x40000040ull << 32); }
__device__ __forceinline__ void wg_fence() { asm volatile("wgmma.fence.sync.aligned;" ::: "memory"); }
__device__ __forceinline__ void wg_commit() { asm volatile("wgmma.commit_group.sync.aligned;" ::: "memory"); }
template <int N> __device__ __forceinline__ void wg_wait() { asm volatile("wgmma.wait_group.sync.aligned %0;" ::"n"(N) : "memory"); }
template <int N> __device__ __forceinline__ void fence_acc(float* d) {
#pragma unroll
    for (int i = 0; i < N; i++) asm volatile("" : "+f"(d[i])::"memory");
}
#define R4(o) "+f"(d[o + 0]), "+f"(d[o + 1]), "+f"(d[o + 2]), "+f"(d[o + 3])
#define R8(o) R4(o), R4(o + 4)
__device__ __forceinline__ void wgmma_n128(float* d, desc_t da, desc_t db, int sc) {
    asm volatile("{.reg .pred p; setp.ne.b32 p, %66, 0;\n"
                 "wgmma.mma_async.sync.aligned.m64n128k16.f32.bf16.bf16 {%0,%1,%2,%3,%4,%5,%6,%7,%8,%9,%10,%11,%12,%13,%14,%15,%16,%17,%18,%19,%20,%21,%22,%23,%24,%25,%26,%27,%28,%29,%30,%31,"
                 "%32,%33,%34,%35,%36,%37,%38,%39,%40,%41,%42,%43,%44,%45,%46,%47,%48,%49,%50,%51,%52,%53,%54,%55,%56,%57,%58,%59,%60,%61,%62,%63}, %64, %65, p, 1, 1, 0, 1;}"
                 : R8(0), R8(8), R8(16), R8(24), R8(32), R8(40), R8(48), R8(56)
                 : "l"(da), "l"(db), "r"(sc));
}
__device__ __forceinline__ void wgmma_n112(float* d, desc_t da, desc_t db, int sc) {
    asm volatile("{.reg .pred p; setp.ne.b32 p, %58, 0;\n"
                 "wgmma.mma_async.sync.aligned.m64n112k16.f32.bf16.bf16 {%0,%1,%2,%3,%4,%5,%6,%7,%8,%9,%10,%11,%12,%13,%14,%15,%16,%17,%18,%19,%20,%21,%22,%23,%24,%25,%26,%27,%28,%29,%30,%31,%32,%33,%34,%35,%36,%37,%38,%39,%40,%41,%42,%43,%44,%45,%46,%47,%48,%49,%50,%51,%52,%53,%54,%55}, %56, %57, p, 1, 1, 0, 1;}"
                 : R8(0), R8(8), R8(16), R8(24), R8(32), R8(40), R8(48)
                 : "l"(da), "l"(db), "r"(sc));
}
__device__ __forceinline__ void wgmma_n128_tn(float* d, desc_t da, desc_t db, int sc) {
    asm volatile("{.reg .pred p; setp.ne.b32 p, %66, 0;\n"
                 "wgmma.mma_async.sync.aligned.m64n128k16.f32.bf16.bf16 {%0,%1,%2,%3,%4,%5,%6,%7,%8,%9,%10,%11,%12,%13,%14,%15,%16,%17,%18,%19,%20,%21,%22,%23,%24,%25,%26,%27,%28,%29,%30,%31,%32,%33,%34,%35,%36,%37,%38,%39,%40,%41,%42,%43,%44,%45,%46,%47,%48,%49,%50,%51,%52,%53,%54,%55,%56,%57,%58,%59,%60,%61,%62,%63}, %64, %65, p, 1, 1, 1, 0;}"
                 : R8(0), R8(8), R8(16), R8(24), R8(32), R8(40), R8(48), R8(56)
                 : "l"(da), "l"(db), "r"(sc));
}
__device__ __forceinline__ void wgmma_n64(float* d, desc_t da, desc_t db, int sc) {
    asm volatile("{.reg .pred p; setp.ne.b32 p, %34, 0;\n"
                 "wgmma.mma_async.sync.aligned.m64n64k16.f32.bf16.bf16 {%0,%1,%2,%3,%4,%5,%6,%7,%8,%9,%10,%11,%12,%13,%14,%15,%16,%17,%18,%19,%20,%21,%22,%23,%24,%25,%26,%27,%28,%29,%30,%31}, %32, %33, p, 1, 1, 0, 1;}"
                 : R8(0), R8(8), R8(16), R8(24)
                 : "l"(da), "l"(db), "r"(sc));
}
__device__ __forceinline__ void wgmma_n40_tt(float* d, desc_t da, desc_t db, int sc) {
    asm volatile("{.reg .pred p; setp.ne.b32 p, %22, 0;\n"
                 "wgmma.mma_async.sync.aligned.m64n40k16.f32.bf16.bf16 {%0,%1,%2,%3,%4,%5,%6,%7,%8,%9,%10,%11,%12,%13,%14,%15,%16,%17,%18,%19}, %20, %21, p, 1, 1, 1, 1;}"
                 : R8(0), R8(8), R4(16)
                 : "l"(da), "l"(db), "r"(sc));
}

__device__ __forceinline__ void wgmma_n8_tt(float* d, desc_t da, desc_t db, int sc) {
    asm volatile("{.reg .pred p; setp.ne.b32 p, %6, 0;\n"
                 "wgmma.mma_async.sync.aligned.m64n8k16.f32.bf16.bf16 {%0,%1,%2,%3}, %4, %5, p, 1, 1, 1, 1;}"
                 : R4(0)
                 : "l"(da), "l"(db), "r"(sc));
}

__device__ __forceinline__ void signal_after(unsigned* cnt, uint32_t ack, uint32_t zero, bool pred) {
    asm volatile("{.reg .pred p; setp.ne.u32 p, %2, 0; @p red.relaxed.gpu.global.add.u32 [%0], %1;}"
                 ::"l"(cnt), "r"((ack & zero) + 1), "r"((uint32_t)pred) : "memory");
}
__device__ __forceinline__ void signal_late(unsigned* cnt, const uint32_t* a, uint32_t zero, bool pred) {
    uint32_t v;
    asm volatile("{.reg .b32 t; lop3.b32 t, %1, %2, %3, 0xfe; or.b32 %0, t, %4;}"
                 : "=r"(v) : "r"(a[0]), "r"(a[1]), "r"(a[2]), "r"(a[3]));
    signal_after(cnt, v, zero, pred);
}
__device__ __forceinline__ void red_f32_if(float* p, float a, bool pred) {
    asm volatile("{.reg .pred p; setp.ne.u32 p, %2, 0; @p red.relaxed.gpu.global.add.f32 [%0], %1;}" ::"l"(p), "f"(a), "r"((uint32_t)pred) : "memory");
}
__device__ __forceinline__ void stg_f2_if(float* p, float a, float b, bool pred) {
    asm volatile("{.reg .pred p; setp.ne.u32 p, %3, 0; @p st.global.v2.f32 [%0], {%1,%2};}" ::"l"(p), "f"(a), "f"(b), "r"((uint32_t)pred) : "memory");
}
__device__ __forceinline__ void stg64(void* p, uint32_t a, uint32_t b) {
    asm volatile("st.global.v2.u32 [%0], {%1,%2};" ::"l"(p), "r"(a), "r"(b) : "memory");
}
__device__ __forceinline__ void mma16816_z(float* c, const uint32_t* a, uint32_t b0, uint32_t b1) {
    asm("mma.sync.aligned.m16n8k16.row.col.f32.bf16.bf16.f32 {%0,%1,%2,%3}, {%4,%5,%6,%7}, {%8,%9}, {%10,%10,%10,%10};"
                 : "=f"(c[0]), "=f"(c[1]), "=f"(c[2]), "=f"(c[3])
                 : "r"(a[0]), "r"(a[1]), "r"(a[2]), "r"(a[3]), "r"(b0), "r"(b1), "f"(0.f));
}
__device__ __forceinline__ uint32_t max2(uint32_t a, uint32_t b) { uint32_t r; asm("max.bf16x2 %0, %1, %2;" : "=r"(r) : "r"(a), "r"(b)); return r; }
__device__ __forceinline__ uint32_t min2(uint32_t a, uint32_t b) { uint32_t r; asm("min.bf16x2 %0, %1, %2;" : "=r"(r) : "r"(a), "r"(b)); return r; }
__device__ __forceinline__ void bar_arrive(int id, int n) { asm volatile("bar.arrive %0, %1;" ::"r"(id), "r"(n) : "memory"); }
__device__ __forceinline__ void mbar_arrive_n_if(uint32_t bar, uint32_t n, bool pred) {
    asm volatile("{.reg .pred p; setp.ne.u32 p, %1, 0; @p mbarrier.arrive.shared::cta.b64 _, [%0], %2;}" ::"r"(bar), "r"((uint32_t)pred), "r"(n) : "memory");
}
__device__ __forceinline__ float4 lds_f4(uint32_t a) {
    float4 v;
    asm volatile("ld.shared.v4.f32 {%0,%1,%2,%3}, [%4];" : "=f"(v.x), "=f"(v.y), "=f"(v.z), "=f"(v.w) : "r"(a) : "memory");
    return v;
}
__device__ __forceinline__ void lds_f4_if(float4& v, uint32_t a, bool pred) {
    asm volatile("{.reg .pred p; setp.ne.u32 p, %5, 0; @p ld.shared.v4.f32 {%0,%1,%2,%3}, [%4];}"
                 : "+f"(v.x), "+f"(v.y), "+f"(v.z), "+f"(v.w) : "r"(a), "r"((uint32_t)pred) : "memory");
}
__device__ __forceinline__ uint4 ld_tagged(const unsigned long long* p) {
    unsigned long long a, b;
    asm volatile("ld.acquire.gpu.global.v2.b64 {%0,%1}, [%2];" : "=l"(a), "=l"(b) : "l"(p) : "memory");
    return make_uint4((unsigned)a, (unsigned)(a >> 32), (unsigned)b, (unsigned)(b >> 32));
}
__device__ __forceinline__ uint4 ld_tagged_rlx(const unsigned long long* p) {
    unsigned long long a, b;
    asm volatile("ld.relaxed.gpu.global.v2.b64 {%0,%1}, [%2];" : "=l"(a), "=l"(b) : "l"(p) : "memory");
    return make_uint4((unsigned)a, (unsigned)(a >> 32), (unsigned)b, (unsigned)(b >> 32));
}
__device__ __forceinline__ void sts32(uint32_t a, uint32_t x) { asm volatile("st.shared.u32 [%0], %1;" ::"r"(a), "r"(x) : "memory"); }
__device__ __forceinline__ void fetch_tagged(const unsigned long long* src, uint32_t dst, unsigned epoch) {
    uint4 v;
    uint32_t it = 0;
    while (true) {
        v = ld_tagged_rlx(src);
        if (!__any_sync(0xffffffffu, v.y != epoch || v.w != epoch)) break;
        __nanosleep(60);
        trap_if_gt(++it, 1u << 22);
    }
    sts64(dst, v.x, v.z);
}
__device__ __forceinline__ void st_tagged_if(unsigned long long* p, float a, float b, unsigned tag, bool pred) {
    const unsigned long long t = (unsigned long long)tag << 32;
    asm volatile("{.reg .pred p; setp.ne.u32 p, %3, 0; @p st.relaxed.gpu.global.v2.b64 [%0], {%1,%2};}"
                 ::"l"(p), "l"(t | __float_as_uint(a)), "l"(t | __float_as_uint(b)), "r"((uint32_t)pred) : "memory");
}

__device__ __forceinline__ void store_tile(uint32_t tile_rows, uint4* gdst, const uint32_t* lo, const uint32_t* hi, int lane, uint32_t* ack) {
    const int r = lane & 15;
#pragma unroll
    for (int b = 0; b < 4; b++)
        stsm4(tile_rows + r * 128 + (((2 * b + (lane >> 4)) ^ (r & 7)) << 4), lo[2 * b], hi[2 * b], lo[2 * b + 1], hi[2 * b + 1]);
    fence_async_smem();
    __syncwarp();
#pragma unroll
    for (int i = 0; i < 4; i++) {
        const uint4 v = lds128(tile_rows + i * 512 + lane * 16);
        stg128(gdst + 32 * i, v.x, v.y, v.z, v.w);
    }
#pragma unroll
    for (int i = 0; i < 4; i++) ack[i] = readback(gdst + 32 * i);
}

__device__ __forceinline__ void feature_maps(const uint32_t* a, const uint32_t* wb, float c0, float c1, uint32_t* plus, uint32_t* minus) {
    uint32_t P[16], mx[4], mn[4];
#pragma unroll
    for (int h = 0; h < 4; h++) {
        float p[8];
        mma16816_z(p, a + 4 * h, wb[4 * h], wb[4 * h + 1]);
        mma16816_z(p + 4, a + 4 * h, wb[4 * h + 2], wb[4 * h + 3]);
        P[4 * h] = pack_bf16(p[0], p[2]); P[4 * h + 1] = pack_bf16(p[1], p[3]);
        P[4 * h + 2] = pack_bf16(p[4], p[6]); P[4 * h + 3] = pack_bf16(p[5], p[7]);
        mx[h] = max2(max2(P[4 * h], P[4 * h + 1]), max2(P[4 * h + 2], P[4 * h + 3]));
        mn[h] = min2(min2(P[4 * h], P[4 * h + 1]), min2(P[4 * h + 2], P[4 * h + 3]));
    }
#pragma unroll
    for (int s = 1; s <= 2; s <<= 1) {
        uint32_t tx[4], tn[4];
#pragma unroll
        for (int h = 0; h < 4; h++) { tx[h] = __shfl_xor_sync(0xffffffffu, mx[h], s); tn[h] = __shfl_xor_sync(0xffffffffu, mn[h], s); }
#pragma unroll
        for (int h = 0; h < 4; h++) { mx[h] = max2(mx[h], tx[h]); mn[h] = min2(mn[h], tn[h]); }
    }
#pragma unroll
    for (int h = 0; h < 4; h++) {
        const float mx0 = bf_lo(mx[h]) * c0, mx1 = bf_hi(mx[h]) * c1, mn0 = bf_lo(mn[h]) * c0, mn1 = bf_hi(mn[h]) * c1;
        float ep[8], em[8];
#pragma unroll
        for (int i = 0; i < 8; i++) {
            const bool r1 = (i & 2);
            const uint32_t w = P[4 * h + (i >> 2) * 2 + (i & 1)];
            const float p = r1 ? bf_hi(w) : bf_lo(w);
            ep[i] = ex2(fmaf(p, r1 ? c1 : c0, r1 ? -mx1 : -mx0));
            em[i] = ex2(fmaf(p, r1 ? -c1 : -c0, r1 ? mn1 : mn0));
        }
        float sp[4], sm[4];
        uint32_t tp[4], tm[4];
#pragma unroll
        for (int i = 0; i < 4; i++) { tp[i] = pack_bf16(ep[2 * i], ep[2 * i + 1]); tm[i] = pack_bf16(em[2 * i], em[2 * i + 1]); }
        mma16816_z(sp, tp, 0x3f803f80u, 0x3f803f80u);
        mma16816_z(sm, tm, 0x3f803f80u, 0x3f803f80u);
        const float r0 = rcp(sp[0] * sm[0]), r1 = rcp(sp[2] * sm[2]);
        const float rs[4] = {r0 * sm[0], r1 * sm[2], r0 * sp[0], r1 * sp[2]};
#pragma unroll
        for (int i = 0; i < 4; i++) {
            plus[4 * h + i] = pack_bf16(ep[2 * i] * rs[i & 1], ep[2 * i + 1] * rs[i & 1]);
            minus[4 * h + i] = pack_bf16(em[2 * i] * rs[2 + (i & 1)], em[2 * i + 1] * rs[2 + (i & 1)]);
        }
    }
}

template <bool SCALE>
__device__ __forceinline__ void ln_frag(const float* acc, uint32_t cs_addr, float rs0, float nm0, float rs1, float nm1, uint32_t* a) {
    const float2 c0 = lds_f2(cs_addr), c1 = lds_f2(cs_addr + 32);
    const float s0 = SCALE ? rs0 : 1.f, s1 = SCALE ? rs1 : 1.f;
    a[0] = pack_bf16(fmaf(nm0, c0.x, acc[0]) * s0, fmaf(nm0, c0.y, acc[1]) * s0);
    a[1] = pack_bf16(fmaf(nm1, c0.x, acc[2]) * s1, fmaf(nm1, c0.y, acc[3]) * s1);
    a[2] = pack_bf16(fmaf(nm0, c1.x, acc[4]) * s0, fmaf(nm0, c1.y, acc[5]) * s0);
    a[3] = pack_bf16(fmaf(nm1, c1.x, acc[6]) * s1, fmaf(nm1, c1.y, acc[7]) * s1);
}

template <int UP>
__device__ __forceinline__ uint32_t hh_pair(const float* ag, float4 cs, float nmean) {
    const float g0 = fmaf(nmean, cs.x, ag[0]), g1 = fmaf(nmean, cs.y, ag[1]);
    const float u0 = fmaf(nmean, cs.z, ag[UP]), u1 = fmaf(nmean, cs.w, ag[UP + 1]);
    return pack_bf16(g0 * u0, g1 * u1);
}
template <int NTP>
__device__ __forceinline__ void hh_stage(const float* acc, const float4* cs, float nm0, float nm1, uint32_t stg, int lane) {
#pragma unroll
    for (int tp = 0; tp < NTP; tp++)
        stsm4(stg + (lane & 15) * 128 + (((2 * tp + (lane >> 4)) ^ (lane & 7)) << 4), hh_pair<32>(acc + 8 * tp, cs[2 * tp], nm0),
              hh_pair<32>(acc + 8 * tp + 2, cs[2 * tp], nm1), hh_pair<32>(acc + 8 * tp + 4, cs[2 * tp + 1], nm0),
              hh_pair<32>(acc + 8 * tp + 6, cs[2 * tp + 1], nm1));
    fence_async_smem();
    __syncwarp();
}

template <int TP0, int TP1>
__device__ __forceinline__ void hh_stage2(const float* acc, const float4* cs, float nm0, float nm1, uint32_t stg, int lane) {
#pragma unroll
    for (int tp = TP0; tp < TP1; tp++)
        stsm4(stg + (lane & 15) * 128 + (((2 * tp + (lane >> 4)) ^ (lane & 7)) << 4), hh_pair<32>(acc + 8 * tp, cs[2 * tp], nm0),
              hh_pair<32>(acc + 8 * tp + 2, cs[2 * tp], nm1), hh_pair<32>(acc + 8 * tp + 4, cs[2 * tp + 1], nm0),
              hh_pair<32>(acc + 8 * tp + 6, cs[2 * tp + 1], nm1));
}
struct Ring {
    int slot; uint32_t phase;
    __device__ __forceinline__ void adv() { if (++slot == NB) { slot = 0; phase ^= 1; } }
    __device__ __forceinline__ void adv5() { slot += slot == 3; adv(); }
};

__global__ void __cluster_dims__(2, 1, 1) __launch_bounds__(NTHREADS, 1) fused_kernel(const __grid_constant__ Params P) {
    extern __shared__ __align__(1024) uint8_t smem_raw[];
    const uint32_t sb = smem_u32(smem_raw);
    const int tid = threadIdx.x, lane = tid & 31;
    if (tid >= 256 && tid < 258) prefetch_tmap(&P.tx + (tid & 1));
    const int warp = __shfl_sync(0xffffffffu, tid >> 5, 0);
    const unsigned role = P.role[blockIdx.x], rank = blockIdx.x & 1;
    const int m = role >> 3, j = role & 7;
    const bool helper = role >= 128;

    TL(0, tid == 0); TLG(0, tid == 0);
    float* const acc_j = g_acc + j * ACC_SIZE;

    if (__builtin_expect(warp >= 8, 1)) {
        asm volatile("setmaxnreg.dec.sync.aligned.u32 72;");
        if (elect_one()) {
            if (warp == 8) {
                if (!helper) {
#pragma unroll
                    for (int i = 0; i < NB; i++) mbar_init(sb + BAR_FULLB + 8 * i, 1);
#pragma unroll
                    for (int i = 0; i < 2; i++) {
                        mbar_expect_tx(sb + BAR_FULLB + 8 * i, SLOT);
                        tma2d(sb + OFF_B + i * SLOT, &P.twq, sb + BAR_FULLB + 8 * i, DM + 64 * j, 64 * i);
                        tma2d(sb + OFF_B + i * SLOT + 8192, &P.twq, sb + BAR_FULLB + 8 * i, 2 * DM + 64 * j, 64 * i);
                    }
                }
            } else if (warp == 9) {
#pragma unroll
                for (int i = 0; i < 8; i++) mbar_init(sb + BAR_FULLA + 8 * i, 1);
                if (!helper) {
#pragma unroll
                    for (int i = 0; i < 2; i++) {
                        mbar_expect_tx(sb + BAR_FULLA + 8 * i, SLOT);
                        tma2d(sb + OFF_A + i * SLOT, &P.tx, sb + BAR_FULLA + 8 * i, 64 * i, 128 * m);
                    }
                }
            } else if (warp == 10) {
#pragma unroll
                for (int i = 0; i < 12; i++) mbar_init(sb + BAR_CS1 + 8 * i, i < 2 || i >= 8 ? 64 : (i < 4 ? 32 : 8));
                trap_if_gt(sb & 1023, 0);
            } else {
#pragma unroll
                for (int i = 0; i < 14; i++) mbar_init(sb + (i < 8 ? BAR_EMPTYA : BAR_EMPTYB - 64) + 8 * i, i < 8 ? 8 : 16);
            }
            asm volatile("fence.mbarrier_init.release.cluster;" ::: "memory");
        }
        __syncwarp();
        asm volatile("barrier.cluster.arrive.relaxed.aligned;" ::: "memory");
        const unsigned epoch = ld_relaxed(&g_epoch);
        bar_sync(0, NTHREADS);
        if (helper) {
            if (elect_one()) {
#pragma unroll 1
                for (int i = warp - 8; i < 72; i += 4) {
                    const uint32_t full = sb + BAR_FULLA + 8 * (i & 7), dst = sb + OFF_A + (i & 7) * SLOT;
                    const int n = i >> 1, jj = 2 * j + (i & 1);
                    const bool qkv = n < 12;
                    const int c0 = qkv ? (n < 8 ? DM + 128 * (n & 4) : 0) + 64 * jj : 176 * jj + 8 * ((n - 12) & ~7);
                    const int r0 = qkv ? 128 * (n & 3) : 64 * ((n - 12) & 7);
                    mbar_wait(sb + BAR_EMPTYA + 8 * (i & 7), ((i >> 3) & 1) ^ 1);
                    mbar_expect_tx(full, SLOT);
                    tma2d(dst, qkv ? &P.twq : &P.twg, full, c0, r0);
                    tma2d(dst + 8192, qkv ? &P.twq : &P.twu, full, c0, qkv ? r0 + 64 : r0);
                }
                prefetch_l2(P.wd + (size_t)(4 * j + warp - 8) * 44032, 88064);
            }
            return;
        }
        if (warp == 8) {
            asm volatile("barrier.cluster.wait.aligned;" ::: "memory");
            if (elect_one()) {
                if (m >= 6)
                    asm volatile("cp.async.bulk.prefetch.tensor.2d.L2.global [%0, {%1, %2}];" ::"l"(&P.twq), "r"(DM + DM * (m & 1) + 64 * j), "r"(64 * (m >> 1)) : "memory");
                if (j >= 3)
                    asm volatile("cp.async.bulk.prefetch.tensor.2d.L2.global [%0, {%1, %2}];" ::"l"(&P.tx), "r"(64 * j), "r"(128 * m) : "memory");
                Ring r{2, 0};
                const uint32_t dst = sb + OFF_B + rank * 8192;
#define B_LOAD(TM, C0, R0)                                                                                  \
        mbar_waitc(sb + BAR_EMPTYB + 8 * r.slot, r.phase ^ 1);                                              \
        mbar_expect_tx(sb + BAR_FULLB + 8 * r.slot, SLOT);                                                  \
        tma2d_mc(dst + r.slot * SLOT, TM, sb + BAR_FULLB + 8 * r.slot, C0, R0);
#pragma unroll 1
                for (int i = 2; i < 8; i++) {
                    if (i >= AHEAD && i < 6) mbar_waitc(sb + BAR_FULLB + 8 * (i - AHEAD), 0);
                    B_LOAD(&P.twq, DM + DM * rank + 64 * j, 64 * i)
                    r.adv();
                }
#pragma unroll 1
                for (int i = 8; i < 18; i++) {
                    if (i == 9 || i == 10) {
                        mbar_waitc(sb + BAR_EMPTYB + 8 * r.slot, r.phase ^ 1);
                        mbar_arrive(sb + BAR_FULLB + 8 * r.slot);
                    } else {
                        const int e = 2 * (i - 14) + rank, b = (i == 8 ? 0 : i - 10) ^ (i < 12 && j < 2);
                        B_LOAD(i < 14 ? &P.twq : &P.two, 64 * j, 64 * (i < 14 ? 2 * b + rank : KORD(e, j)))
                    }
                    r.adv();
                }
#pragma unroll 1
                for (int i = 0; i < 24; i++) {
                    B_LOAD(&P.twg + rank, 176 * j + 8 * (i & ~7), 64 * (i < 8 ? KORD(i, j) : i & 7))
                    r.adv5();
                }
#pragma unroll 1
                for (int i = 0; i < 12; i++) {
                    B_LOAD(&P.twd, 64 * j, 176 * (2 * (i & 3) + rank) + 64 * (i >> 2))
                    r.adv5();
                }
            }
            return;
        }
        if (warp == 9) {
            if (elect_one()) {
#pragma unroll 1
                for (int i = 2; i < 8; i++) {
                    if (i >= AHEAD + 1) mbar_wait(sb + BAR_FULLA + 8 * (i - AHEAD - 1), 0);
                    mbar_expect_tx(sb + BAR_FULLA + 8 * i, SLOT);
                    tma2d(sb + OFF_A + i * SLOT, &P.tx, sb + BAR_FULLA + 8 * i, 64 * i, 128 * m);
                }
#pragma unroll 1
                for (int i = 2; i < 7; i++) prefetch_tmap(&P.tx + i);
                unsigned nf = 0;
#pragma unroll 1
                for (int r = 1; r < 6; r++) {
                    const int skip = r < 3 ? j : 8;
                    const uint4* src = g_act + ((r - 1) * 128 + m * 8) * 1024;
                    const unsigned* fl = g_flag + (m * 5 + r - 1) * 32;
                    if (r < 4) mbar_wait(sb + BAR_EMPTYA + 8 * (r == 3 ? PF_DELAY : 3 - 2 * (j == 3)), (r - 1) & 1);
                    if (r < 4 || nf != epoch * 8) wait_count(fl, epoch * (r < 3 ? 64 : 8));
                    TL(64 + r, true);
#pragma unroll 1
                    for (int t = 0; t < 8; t++) {
                        if (t == skip) continue;
                        if (t == 6) nf = readback(fl + 32);
                        mbar_wait(sb + BAR_EMPTYA + 8 * t, (r - 1) & 1);
                        mbar_expect_tx(sb + BAR_FULLA + 8 * t, SLOT);
                        asm volatile("cp.async.bulk.shared::cluster.global.mbarrier::complete_tx::bytes [%0], [%1], %2, [%3];"
                                     ::"r"(sb + OFF_A + t * SLOT), "l"(src + t * 1024), "r"(SLOT), "r"(sb + BAR_FULLA + 8 * t) : "memory");
                    }
                }
            }
            return;
        }
        const int a = warp - 10;
        {
            const int row = 16 * j + 8 * a + (lane >> 2);
            const uint32_t ra = sb + OFF_A + row * 128;
            float sh = 0.f, s0 = 0.f, s1 = 0.f, q0 = 0.f, q1 = 0.f;
#pragma unroll 1
            for (int kt = 0; kt < 8; kt++) {
                mbar_wait(sb + BAR_FULLA + 8 * kt, 0);
                if (kt == 0) sh = bf_lo(lds128(ra + ((row & 7) << 4)).x);
#pragma unroll
                for (int i = 0; i < 2; i++) {
                    const uint4 v = lds128(ra + kt * SLOT + (((2 * (lane & 3) + i) ^ (row & 7)) << 4));
                    const uint32_t ww[4] = {v.x, v.y, v.z, v.w};
#pragma unroll
                    for (int e = 0; e < 4; e++) {
                        const float d0 = bf_lo(ww[e]) - sh, d1 = bf_hi(ww[e]) - sh;
                        s0 += d0; q0 = fmaf(d0, d0, q0);
                        s1 += d1; q1 = fmaf(d1, d1, q1);
                    }
                }
            }
            s0 += s1; q0 += q1;
#pragma unroll
            for (int o = 1; o <= 2; o <<= 1) { s0 += __shfl_xor_sync(0xffffffffu, s0, o); q0 += __shfl_xor_sync(0xffffffffu, q0, o); }
            const float md = s0 * (1.f / DM);
            const float rs = rsqrtf(fmaxf(q0 * (1.f / DM) - md * md, 0.f) + 1e-5f);
            st_tagged_if(g_xstat + 2 * (128 * m + row), rs, -(sh + md), epoch, (lane & 3) == 0);
            TL(1, lane == 0 && a == 0);
        }
        const unsigned long long* cs = g_cs + j * 768 + 2 * lane;
        {
            const unsigned long long* xs = g_xstat + 2 * (128 * m + 64 * a + lane);
            uint4 v0, v1, v2;
            uint32_t it = 0;
            do {
                v0 = ld_tagged_rlx(xs); v1 = ld_tagged_rlx(xs + 64); v2 = ld_tagged_rlx(cs);
                trap_if_gt(++it, 1u << 22);
            } while (__any_sync(0xffffffffu, v0.y != epoch || v0.w != epoch || v1.y != epoch || v1.w != epoch || v2.y != epoch || v2.w != epoch));
            sts64(sb + OFF_XST + (64 * a + lane) * 8, v0.x, v0.z);
            sts64(sb + OFF_XST + (64 * a + 32 + lane) * 8, v1.x, v1.z);
            sts64(sb + OFF_CS1 + 256 + 8 * lane, v2.x, v2.z);
            mbar_arrive(sb + BAR_CS1);
            TL(22 + a, lane == 0);
            fetch_tagged(cs + 128 + 128 * a, sb + OFF_CS1 + 512 - 512 * a + 8 * lane, epoch);
            mbar_arrive(sb + BAR_CSV - 8 * a);
            TL(24 + a, lane == 0);
        }
        {
            mbar_wait(sb + BAR_KVW, 0);
            const float* src = acc_j + 4 * (128 * a + lane);
            float4 v[12];
            uint32_t it = 0;
            bool bad;
            while (__any_sync(0xffffffffu, readback(acc_j + 2048 + 128 * (lane & 7) + 127) != 0x41800000u)) trap_if_gt(++it, 1u << 22);
            TL(19, lane == 0 && a == 0);
            do {
                bad = false;
#pragma unroll
                for (int i = 0; i < 12; i++) v[i] = ld_l2_f4(src + 1024 * (i % 3) + 128 * (i / 3));
#pragma unroll
                for (int i = 0; i < 12; i++) bad |= v[i].w != 16.f;
                trap_if_gt(++it, 1u << 22);
            } while (__any_sync(0xffffffffu, bad));
            TL(14, lane == 0 && a == 0);
            const uint32_t d0 = sb + OFF_A + (j < 2 ? 2 * SLOT : 0) + (64 * a + (lane >> 2)) * 48;
            const uint32_t d = d0 + (lane & 3) * 4, dz = d0 + (lane & 1) * 384 + 32 + (lane & 2) * 4;
#pragma unroll
            for (int u = 0; u < 4; u++) {
                sts32(d + 768 * u, pack_bf16(v[3 * u].x, v[3 * u].y));
                sts32(d + 768 * u + 384, pack_bf16(v[3 * u].z, v[3 * u + 1].z));
                sts32(d + 768 * u + 16, pack_bf16(v[3 * u + 1].x, v[3 * u + 1].y));
                sts32(d + 768 * u + 400, pack_bf16(v[3 * u + 2].x, v[3 * u + 2].y));
                const uint32_t z2 = pack_bf16(v[3 * u + 2].z, v[3 * u + 2].z);
                sts64(dz + 768 * u, z2, z2);
            }
            mbar_arrive(sb + BAR_KVR);
        }
#pragma unroll 1
        for (int c = 0; c < 3; c++) {
            fetch_tagged(cs + 384 + 128 * c + 64 * a, sb + OFF_CS3 + (32 * c + lane) * 16 + 8 * a, epoch);
            mbar_arrive(sb + BAR_CSG + 8 * c);
            TL(45 + c, lane == 0 && a == 0);
        }
        {
            uint32_t it = 0;
            while (__any_sync(0xffffffffu, (int)(readback(g_flag + (m * 5 + 1) * 32) - epoch * 64) < 0)) {
                __nanosleep(200);
                trap_if_gt(++it, 1u << 22);
            }
#pragma unroll 1
            for (int rr = 0; rr < 2; rr++) {
                const int row = 64 * rr + 32 * a + lane;
                const unsigned long long* hs = g_hstat + (1024 * m + row) * 2;
                uint4 v[8];
                bool bad;
                do {
                    bad = false;
#pragma unroll
                    for (int i = 0; i < 8; i++) v[i] = ld_tagged_rlx(hs + 256 * i);
#pragma unroll
                    for (int i = 0; i < 8; i++) bad |= v[i].y != epoch || v[i].w != epoch;
                    trap_if_gt(++it, 1u << 22);
                } while (__any_sync(0xffffffffu, bad));
                float mean = 0.f;
#pragma unroll
                for (int i = 0; i < 8; i++) mean += __uint_as_float(v[i].x);
                mean *= 0.125f;
                float m2 = 0.f, dv = 0.f;
#pragma unroll
                for (int i = 0; i < 8; i++) { const float d = __uint_as_float(v[i].x) - mean; m2 += __uint_as_float(v[i].z); dv = fmaf(d, d, dv); }
                sts_f2(sb + OFF_CS1 + row * 8, -mean, rcp(fmaf(dv, 64.f, m2) * (1.f / DM) + 1e-5f));
            }
        }
        mbar_arrive(sb + BAR_CS3);
#pragma unroll 1
        for (int c = a; c < 3; c += 2) {
            mbar_wait(sb + BAR_STG + 8 * c, 0);
            if (elect_one()) {
                asm volatile("cp.async.bulk.global.shared::cta.bulk_group [%0], [%1], %2;" ::"l"(g_act + ((2 + c) * 128 + role) * 1024), "r"(sb + OFF_B + 4 * SLOT), "r"(SLOT) : "memory");
                asm volatile("cp.async.bulk.commit_group;" ::: "memory");
                asm volatile("cp.async.bulk.wait_group.read 0;" ::: "memory");
                mbar_arrive(sb + BAR_FULLB + 8 * 4);
                asm volatile("cp.async.bulk.wait_group 0;" ::: "memory");
            }
            __syncwarp();
            TL(60 + c, lane == 0);
            uint32_t ack = 0;
            const uint4* rb = g_act + ((2 + c) * 128 + role) * 1024 + lane * 8;
#pragma unroll
            for (int i = 0; i < 4; i++) ack |= readback(rb + 256 * i);
            signal_after(g_flag + (m * 5 + 2 + c) * 32, ack, P.zero, lane == 0);
            TL(54 + c, lane == 0);
        }
        return;
    }
    const unsigned epoch = ld_relaxed(&g_epoch);
    uint32_t wraw[16];
    if (!helper) {
        const uint32_t* wp = reinterpret_cast<const uint32_t*>(P.wphi) + (4 * j) * 128 + (lane & 3) * 16 + (lane >> 2);
#pragma unroll
        for (int i = 0; i < 16; i++)
            asm volatile("ld.global.nc.u32 %0, [%1];" : "=r"(wraw[i]) : "l"(wp + (i >> 2) * 128 + ((i >> 1) & 1) * 64 + (i & 1) * 8));
    }
    asm volatile("barrier.cluster.arrive.relaxed.aligned;" ::: "memory");
    asm volatile("setmaxnreg.inc.sync.aligned.u32 216;");
    bar_sync(0, NTHREADS);
    if (helper) {
        const int w = warp >> 2;
        sts64(sb + OFF_B + 8 * tid, 0x3f803f80u, 0x3f803f80u);
        fence_async_smem();
        uint32_t zack[6];
        {
            float* z = g_acc + 2 * j * ACC_SIZE + 4 * tid;
#pragma unroll
            for (int u = 0; u < 6; u++) stg128(z + 1024 * u, 0, 0, 0, 0);
#pragma unroll
            for (int u = 0; u < 6; u++) zack[u] = readback(z + 1024 * u);
        }
        bar_sync(1, 256);
        TL(70, tid == 0);
        float acc[8];
        int i = w;
#pragma unroll 1
        for (int job = 0; job < 6; job++) {
            const int n = job < 3 ? 4 : 8;
#pragma unroll 1
            for (int t = 0; t < n; t++, i += 2) {
                mbar_waitc(sb + BAR_FULLA + 8 * (i & 7), (i >> 3) & 1);
                const desc_t da = desc_lo(sb + OFF_A) + (i & 7) * (SLOT >> 4);
                wg_fence();
#pragma unroll
                for (int k = 0; k < 8; k++) wgmma_n8_tt(acc + (k & 4), da + 128 * k, desc_lo(sb + OFF_B), (t | (k & 3)) != 0);
                wg_commit();
                wg_wait<0>();
                mbar_arrive_n_if(sb + BAR_EMPTYA + 8 * (i & 7), 2, lane == 0);
            }
            fence_acc<8>(acc);
            TL(71 + job, tid == 0);
            if (job == 1) {
                asm volatile("{.reg .pred p; .reg .b32 t; lop3.b32 t, %0, %1, %2, 0xfe; lop3.b32 t, t, %3, %4, 0xfe; or.b32 t, t, %5; setp.ne.u32 p, t, 0; @p trap;}"
                             ::"r"(zack[0]), "r"(zack[1]), "r"(zack[2]), "r"(zack[3]), "r"(zack[4]), "r"(zack[5]));
                bar_sync(1, 256);
            }
            const int q = lane & 3;
            const float lo = (q & 1) ? acc[2] : acc[0], hi = (q & 1) ? acc[6] : acc[4];
            const float v = job < 3 ? lo + hi : ((q & 2) ? hi : lo);
            unsigned long long* dst = g_cs + ((2 * j + w) * 6 + job) * 128 + (q >> 1) * 64 + 16 * (warp & 3) + 8 * (q & 1) + (lane >> 2);
            asm volatile("st.relaxed.gpu.global.b64 [%0], %1;" ::"l"(dst), "l"(((unsigned long long)epoch << 32) | __float_as_uint(v)) : "memory");
        }
        return;
    }
    {
        const int w = warp >> 2, wv = warp & 3, g = lane >> 2, q = lane & 3;
        const uint32_t sa = sb + OFF_A + w * 8192;
        const desc_t dA = desc_lo(sa), dB = desc_lo(sb + OFF_B);
        unsigned* const flag_m = g_flag + m * 160;
        const bool l0 = lane == 0, l2 = lane < 2;
        const uint32_t eb = mapa(sb + BAR_EMPTYB, lane & 1);
        asm volatile("barrier.cluster.wait.aligned;" ::: "memory");
        Ring rg{0, 0};
        int prev = 0;

        uint32_t wb[16];
        constexpr float L2E = 1.4426950408889634f;
        const int ch = lane >> 4, sw = lane & 7;
        const uint32_t lrow = (lane & 15) * 128;
        uint32_t fp[16], fm[16];
        const int vs = j < 2 ? 2 : 0;
        {
            float acc[64];
#pragma unroll 1
            for (int kt = 0; kt < 8; kt++) {
                mbar_waitc(sb + BAR_FULLA + 8 * kt, 0);
                mbar_waitc(sb + BAR_FULLB + 8 * rg.slot, rg.phase);
                const desc_t da = dA + kt * (SLOT >> 4), db = dB + rg.slot * (SLOT >> 4);
                wg_fence();
#pragma unroll
                for (int k = 0; k < 4; k++) wgmma_n128(acc, da + 2 * k, db + 128 * k, (kt | k) != 0);
                wg_commit();
                wg_wait<1>();
                mbar_arrive_cl_if(eb + 8 * prev, l2 && kt > 0);
                prev = rg.slot; rg.adv();
            }
#pragma unroll
            for (int i = 0; i < 8; i++) {
                wb[(i >> 1) * 4 + (i & 1)] = __byte_perm(wraw[2 * i], wraw[2 * i + 1], 0x5410);
                wb[(i >> 1) * 4 + 2 + (i & 1)] = __byte_perm(wraw[2 * i], wraw[2 * i + 1], 0x7632);
            }
            uint32_t a[16];
            float accq[32];
            mbar_waitc(sb + BAR_FULLB + 8 * 2, 1);
            wg_fence();
#pragma unroll
            for (int k = 0; k < 8; k++) wgmma_n64(accq, dA + (vs + (k >> 2)) * (SLOT >> 4) + (k & 3) * 2, dB + 2 * (SLOT >> 4) + 128 * k, k != 0);
            wg_commit();
            wg_wait<1>();
            fence_acc<64>(acc);
            mbar_arrive_cl_if(eb + 8 * prev, l2);
            TL(17, tid == 0);
            mbar_waitc(sb + BAR_CS1, 0);
            const float2 s0 = lds_f2(sb + OFF_XST + (16 * warp + g) * 8), s1 = lds_f2(sb + OFF_XST + (16 * warp + g + 8) * 8);
            wg_wait<0>();
            fence_acc<32>(accq);
            mbar_arrive_cl_if(eb + 8 * 2, l2);
            TL(2, tid == 0);
            const uint32_t st = sb + OFF_B + warp * 2048 + lrow;
#pragma unroll
            for (int hh = 0; hh < 4; hh++)
                ln_frag<false>(acc + 8 * hh, sb + OFF_CS1 + (64 + 16 * hh + 2 * q) * 4, 0.f, s0.y, 0.f, s1.y, a + 4 * hh);
#pragma unroll 1
            for (int it = 0; it < 2; it++) {
                feature_maps(a, wb, s0.x * L2E, s1.x * L2E, fp, fm);
                if (it == 0) {
                    mbar_waitc(sb + BAR_FULLB + 8 * 3, 1); mbar_waitc(sb + BAR_FULLB + 8 * 4, 1);
                    mbar_waitc(sb + BAR_CSV, 0);
                    const uint32_t sv = sb + OFF_A + vs * SLOT + warp * 2048 + lrow;
#pragma unroll
                    for (int hh = 0; hh < 4; hh++) {
                        stsm4(st + (3 + (hh >> 1)) * SLOT + (((4 * (hh & 1) + ch) ^ sw) << 4), fp[4 * hh], fp[4 * hh + 1], fp[4 * hh + 2], fp[4 * hh + 3]);
                        stsm4(st + (3 + (hh >> 1)) * SLOT + (((4 * (hh & 1) + 2 + ch) ^ sw) << 4), fm[4 * hh], fm[4 * hh + 1], fm[4 * hh + 2], fm[4 * hh + 3]);
                        ln_frag<true>(acc + 32 + 8 * hh, sb + OFF_CS1 + (128 + 16 * hh + 2 * q) * 4, s0.x, s0.y, s1.x, s1.y, a);
                        stsm4(sv + (hh >> 1) * SLOT + (((2 * (hh & 1) + ch) ^ sw) << 4), a[0], a[1], a[2], a[3]);
                    }
                    stsm4(sv + ch * SLOT + ((4 ^ sw) << 4), 0x3f803f80u, 0x3f803f80u, 0x3f803f80u, 0x3f803f80u);
                    fence_async_smem();
                    bar_sync(1, 256);
                    float kvd[20];
                    wg_fence();
#pragma unroll
                    for (int k = 0; k < 8; k++)
                        wgmma_n40_tt(kvd, dB + (3 + w) * (SLOT >> 4) + 128 * k, desc_lo(sb + OFF_A) + (vs + w) * (SLOT >> 4) + 128 * k, k != 0);
                    wg_commit();
                    wg_wait<0>();
                    fence_acc<20>(kvd);
                    mbar_arrive_cl_if(eb + 8 * (3 + (lane >> 1)), lane < 4);
                    const bool h1 = wv >= 2;
                    float* kvp = acc_j + 4 * tid;
                    red_f32x4(kvp, h1 ? kvd[8] : kvd[0], h1 ? kvd[9] : kvd[1], h1 ? kvd[10] : kvd[2], 1.f);
                    red_f32x4(kvp + 1024, h1 ? kvd[12] : kvd[4], h1 ? kvd[13] : kvd[5], h1 ? kvd[11] : kvd[3], 1.f);
                    red_f32x4(kvp + 2048, h1 ? kvd[14] : kvd[6], h1 ? kvd[15] : kvd[7], (q & 1) ? kvd[18] : kvd[16], 1.f);
                    mbar_arrive_if(sb + BAR_KVW, l0);
                    TL(3, tid == 0);
#pragma unroll 1
                    for (int b = 1; b < 4; b++) {
                        const int slot = b == 1 ? 5 : b - 2;
                        mbar_waitc(sb + BAR_FULLB + 8 * slot, b == 1);
                        const desc_t da = dA + (b == 1 ? 2 - vs : 2 * b) * (SLOT >> 4), db = dB + slot * (SLOT >> 4);
                        wg_fence();
#pragma unroll
                        for (int k = 0; k < 8; k++) wgmma_n64(accq, da + (k >> 2) * (SLOT >> 4) + (k & 3) * 2, db + 128 * k, 1);
                        wg_commit();
                    }
                    mbar_waitc(sb + BAR_CSQ, 0);
                    wg_wait<0>();
                    fence_acc<32>(accq);
                    mbar_arrive_cl_if(eb + 8 * ((5 + (lane >> 1)) % 6), lane < 6);
                    TL(4, tid == 0);
#pragma unroll
                    for (int hh = 0; hh < 4; hh++)
                        ln_frag<false>(accq + 8 * hh, sb + OFF_CS1 + (16 * hh + 2 * q) * 4, 0.f, s0.y, 0.f, s1.y, a + 4 * hh);
                }
            }
        }
        uint32_t res_lo[8], res_hi[8], ack[4];
        const uint32_t own_rows = sb + OFF_A + j * SLOT + warp * 2048;
#pragma unroll
        for (int b = 0; b < 4; b++)
            ldsm4(own_rows + lrow + (((2 * b + ch) ^ sw) << 4), res_lo[2 * b], res_hi[2 * b], res_lo[2 * b + 1], res_hi[2 * b + 1]);
        mbar_arrive_if(sb + BAR_EMPTYA + 8 * lane, lane < 8 && lane != j && lane != vs);
        TL(5, tid == 0);
        mbar_waitc(sb + BAR_KVR, 0);
        TL(6, tid == 0);
        {
            const uint32_t kvs = sb + OFF_A + vs * SLOT;
            uint32_t o_lo[8], o_hi[8];
#pragma unroll
            for (int hh = 0; hh < 4; hh++) {
                uint32_t b[8], zb[4];
                const uint32_t base = kvs + hh * 32 * 48;
                ldsm4t(base + (lane & 15) * 48 + (lane >> 4) * 16, b[0], b[1], b[2], b[3]);
                ldsm4t(base + (16 + (lane & 15)) * 48 + (lane >> 4) * 16, b[4], b[5], b[6], b[7]);
                ldsm4t(base + lane * 48 + 32, zb[0], zb[1], zb[2], zb[3]);
                float n0[4], n1[4], dn[4];
                mma16816_z(n0, fp + 4 * hh, b[0], b[1]); mma16816_z(n1, fp + 4 * hh, b[2], b[3]); mma16816_z(dn, fp + 4 * hh, zb[0], zb[1]);
                mma16816(n0, fm + 4 * hh, b[4], b[5]); mma16816(n1, fm + 4 * hh, b[6], b[7]); mma16816(dn, fm + 4 * hh, zb[2], zb[3]);
                const float i0 = rcp(dn[0] + 1e-6f), i1 = rcp(dn[2] + 1e-6f);
                o_lo[2 * hh] = pack_bf16(n0[0] * i0, n0[1] * i0); o_hi[2 * hh] = pack_bf16(n0[2] * i1, n0[3] * i1);
                o_lo[2 * hh + 1] = pack_bf16(n1[0] * i0, n1[1] * i0); o_hi[2 * hh + 1] = pack_bf16(n1[2] * i1, n1[3] * i1);
            }
            __syncwarp();
            mbar_arrive_if(sb + BAR_EMPTYA + 8 * vs, l0);
            rg.slot = 2; rg.phase = 0;
            store_tile(own_rows, g_act + role * 1024 + warp * 128 + lane, o_lo, o_hi, lane, ack);
            TL(7, tid == 0);
        }
        float acch[32];
        {
            float* acc = acch;
#pragma unroll
            for (int t = 0; t < 8; t++) {
                acc[4 * t] = bf_lo(res_lo[t]); acc[4 * t + 1] = bf_hi(res_lo[t]);
                acc[4 * t + 2] = bf_lo(res_hi[t]); acc[4 * t + 3] = bf_hi(res_hi[t]);
            }
            fence_acc<32>(acc);
            int pa = 0;
#pragma unroll 1
            for (int kp = 0; kp < 4; kp++) {
                mbar_waitc(sb + BAR_FULLB + 8 * rg.slot, rg.phase);
#pragma unroll
                for (int hf = 0; hf < 2; hf++) {
                    const int i = 2 * kp + hf, kt = KORD(i, j);
                    mbar_waitc(sb + BAR_FULLA + 8 * kt, i != 0);
                    TL(8, i == 1 && tid == 0);
                    const desc_t da = dA + kt * (SLOT >> 4), db = dB + rg.slot * (SLOT >> 4);
                    wg_fence();
#pragma unroll
                    for (int k = 0; k < 4; k++) wgmma_n64(acc, da + 2 * k, db + (hf * 4 + k) * 128, 1);
                    wg_commit();
                    wg_wait<1>();
                    mbar_arrive_if(sb + BAR_EMPTYA + 8 * pa, l0 && i > 1);
                    if (hf == 0) {
                        mbar_arrive_cl_if(eb + 8 * prev, l2 && i > 0);
                        if (i == 0) { signal_late(flag_m, ack, P.zero, l0); TL(20, tid == 0); }
                    }
                    pa = kt;
                }
                prev = rg.slot; rg.adv();
            }
            wg_wait<0>();
            fence_acc<32>(acc);
            mbar_arrive_if(sb + BAR_EMPTYA + 8 * pa, l0);
            mbar_arrive_cl_if(eb + 8 * prev, l2);
            TL(9, tid == 0);
#pragma unroll
            for (int t = 0; t < 8; t++) {
                res_lo[t] = pack_bf16(acc[4 * t], acc[4 * t + 1]);
                res_hi[t] = pack_bf16(acc[4 * t + 2], acc[4 * t + 3]);
            }
            store_tile(own_rows, g_act + (128 + role) * 1024 + warp * 128 + lane, res_lo, res_hi, lane, ack);
            TL(10, tid == 0);
        }
        float acc0[64], acc1[64], acc2[56], nm0, nm1;
        float4 cs[8];
        uint32_t hr[16];
#define P3_GROUP(MMA, ACC, KT)                                                                              \
        mbar_waitc(sb + BAR_FULLB + 8 * rg.slot, rg.phase);                                                 \
        {                                                                                                   \
            const desc_t da = dA + (KT) * (SLOT >> 4), db = dB + rg.slot * (SLOT >> 4);                     \
            wg_fence();                                                                                     \
            _Pragma("unroll") for (int k = 0; k < 4; k++) MMA(ACC, da + 2 * k, db + 128 * k, (i | k) != 0); \
            wg_commit();                                                                                    \
        }
#define P3_CS(C, NT)    \
        _Pragma("unroll") for (int t = 0; t < (NT); t++) lds_f4_if(cs[t], sb + OFF_CS3 + q * 16 + 512 * (C) + 64 * t, i == t);
#define P3_EPI2(C, ACC)                                                                                     \
        if (i == 0) {                                                                                       \
            fence_acc<64>(ACC);                                                                             \
            if (C) mbar_waitc(sb + BAR_FULLB + 8 * 4, 1);                                                   \
            hh_stage2<0, 2>(ACC, cs, nm0, nm1, stg, lane);                                                  \
            mbar_waitc(sb + BAR_CSG + 8 * (C) + 8, 0);                                                      \
        }                                                                                                   \
        if (i == 1) {                                                                                       \
            hh_stage2<2, 4>(ACC, cs, nm0, nm1, stg, lane);                                                  \
            fence_async_smem();                                                                             \
            __syncwarp();                                                                                   \
            mbar_arrive_if(sb + BAR_STG + 8 * (C), l0);                                                     \
        }
#define P3_EPI(C, ACC, N, NTP)                                                                              \
        fence_acc<N>(ACC);                                                                                  \
        TL(11 + (C), tid == 0);                                                                             \
        hh_stage<NTP>(ACC, cs, nm0, nm1, sb + OFF_B + 4 * SLOT + warp * 2048, lane);                        \
        mbar_arrive_if(sb + BAR_STG + 8 * (C), l0);                                                         \
        TL(50 + (C), tid == 0);
        const uint32_t stg = sb + OFF_B + 4 * SLOT + warp * 2048;
        const uint32_t blk = ((lane & 7) + (lane >> 4) * 8) * 128 + (((2 * wv + ((lane >> 3) & 1)) ^ (lane & 7)) << 4);
#pragma unroll 1
        for (int i = 0; i < 8; i++) {
            const int kt = KORD(i, j);
            mbar_waitc(sb + BAR_FULLA + 8 * kt, 0);
            TL(44, tid == 0 && i == 1);
            P3_GROUP(wgmma_n128, acc0, kt)
            if (i == 7) {
                mbar_waitc(sb + BAR_CS3, 0);
                nm0 = lds_f2(sb + OFF_CS1 + (16 * warp + g) * 8).x; nm1 = lds_f2(sb + OFF_CS1 + (16 * warp + g + 8) * 8).x;
            }
            wg_wait<1>();
            mbar_arrive_cl_if(eb + 8 * prev, l2 && i > 0);
            if (i == 0) {
                signal_late(flag_m + 32, ack, P.zero, l0);
                TL(21, tid == 0);
                {
                    fence_acc<32>(acch);
                    const float* acc = acch;
                    float s0 = 0.f, s1 = 0.f;
#pragma unroll
                    for (int t = 0; t < 8; t++) { s0 += acc[4 * t] + acc[4 * t + 1]; s1 += acc[4 * t + 2] + acc[4 * t + 3]; }
            s0 += __shfl_xor_sync(0xffffffffu, s0, 1); s1 += __shfl_xor_sync(0xffffffffu, s1, 1);
            s0 += __shfl_xor_sync(0xffffffffu, s0, 2); s1 += __shfl_xor_sync(0xffffffffu, s1, 2);
            const float mu0 = s0 * (1.f / 64), mu1 = s1 * (1.f / 64);
            float q0 = 0.f, q1 = 0.f;
#pragma unroll
            for (int t = 0; t < 8; t++) {
                float d;
                d = acc[4 * t] - mu0; q0 = fmaf(d, d, q0);
                d = acc[4 * t + 1] - mu0; q0 = fmaf(d, d, q0);
                d = acc[4 * t + 2] - mu1; q1 = fmaf(d, d, q1);
                d = acc[4 * t + 3] - mu1; q1 = fmaf(d, d, q1);
            }
            q0 += __shfl_xor_sync(0xffffffffu, q0, 1); q1 += __shfl_xor_sync(0xffffffffu, q1, 1);
            q0 += __shfl_xor_sync(0xffffffffu, q0, 2); q1 += __shfl_xor_sync(0xffffffffu, q1, 2);
            st_tagged_if(g_hstat + (role * 128 + 16 * warp + g + 8 * (q & 1)) * 2, q ? mu1 : mu0, q ? q1 : q0, epoch, q < 2);
                }
                bar_sync(2 + w, 128);
#pragma unroll
                for (int tp = 0; tp < 4; tp++) ldsm4t(sa + j * SLOT + blk + tp * 2048, hr[4 * tp], hr[4 * tp + 1], hr[4 * tp + 2], hr[4 * tp + 3]);
                mbar_waitc(sb + BAR_CSG, 0);
#pragma unroll
                for (int t = 0; t < 8; t++) cs[t] = lds_f4(sb + OFF_CS3 + q * 16 + 64 * t);
            }
            prev = rg.slot; rg.adv5();
        }
#pragma unroll 1
        for (int i = 0; i < 8; i++) {
            P3_GROUP(wgmma_n128, acc1, i)
            wg_wait<1>();
            mbar_arrive_cl_if(eb + 8 * prev, l2);
            P3_EPI2(0, acc0)
            P3_CS(1, 8)
            prev = rg.slot; rg.adv5();
        }
#pragma unroll 1
        for (int i = 0; i < 8; i++) {
            P3_GROUP(wgmma_n112, acc2, i)
            wg_wait<1>();
            mbar_arrive_cl_if(eb + 8 * prev, l2);
            mbar_arrive_if(sb + BAR_EMPTYA + 8 * ((i + 7) & 7), l0 && i > 0);
            if (i == 0) { mbar_waitc(sb + BAR_FULLB + 8 * 4, 1); P3_EPI(1, acc1, 64, 4) mbar_waitc(sb + BAR_CSG + 16, 0); }
            P3_CS(2, 6)
            prev = rg.slot; rg.adv5();
        }
        mbar_waitc(sb + BAR_FULLB + 8 * 4, 0);
        wg_wait<0>();
        mbar_arrive_cl_if(eb + 8 * prev, l2);
        mbar_arrive_if(sb + BAR_EMPTYA + 8 * 7, l0);
        P3_EPI(2, acc2, 56, 3)
        {
            float acc[64];
            const desc_t dA0 = desc_lo(sb + OFF_A);
#define KT_P4(I, NK)                                                                                        \
        const int s_ = (2 * (I) + w) & 7;                                                                   \
        mbar_waitc(sb + BAR_FULLB + 8 * rg.slot, rg.phase);                                                 \
        mbar_waitc(sb + BAR_FULLA + 8 * s_, (((I) >> 2) + 1) & 1);                                          \
        const desc_t dh_ = dA0 + s_ * (SLOT >> 4), dw_ = dB + rg.slot * (SLOT >> 4) + w * 512;              \
        wg_fence();                                                                                         \
        _Pragma("unroll") for (int k = 0; k < (NK); k++) wgmma_n128_tn(acc, dw_ + 128 * k, dh_ + 2 * k, ((I) | k) != 0); \
        wg_commit();                                                                                        \
        wg_wait<1>();
#pragma unroll 1
            for (int i = 0; i < 8; i++) {
                KT_P4(i, 4)
                mbar_arrive_n_if(sb + BAR_EMPTYA + 8 * ((s_ + 6) & 7), 2, l0 && i > 0);
                mbar_arrive_cl_if(eb + 8 * prev, l2 && i > 0);
#pragma unroll
                for (int t = 0; t < 8; t++) lds_f4_if(cs[t], sb + OFF_CS1 + (64 * w + 8 * t + 2 * q) * 8, i == t);
                prev = rg.slot; rg.adv5();
            }
#pragma unroll 1
            for (int i = 8; i < 12; i++) {
                KT_P4(i, 3)
                mbar_arrive_n_if(sb + BAR_EMPTYA + 8 * ((s_ + 6) & 7), 2, l0);
                rg.adv5();
            }
            wg_wait<0>();
            fence_acc<64>(acc);
            TL(15, tid == 0);
            const uint32_t xch = sb + OFF_A + 2 * SLOT + (tid & 127) * 16;
            if (w) {
#pragma unroll
                for (int t = 0; t < 8; t++) {
                    sts128(xch + SLOT + t * 2048, __float_as_uint(acc[4 * t]), __float_as_uint(acc[4 * t + 1]),
                           __float_as_uint(acc[4 * t + 2]), __float_as_uint(acc[4 * t + 3]));
                }
#pragma unroll
                for (int t = 0; t < 32; t++) acc[t] = acc[32 + t];
            } else {
#pragma unroll
                for (int t = 0; t < 8; t++)
                    sts128(xch + t * 2048, __float_as_uint(acc[32 + 4 * t]), __float_as_uint(acc[33 + 4 * t]),
                           __float_as_uint(acc[34 + 4 * t]), __float_as_uint(acc[35 + 4 * t]));
            }
            bar_sync(1, 256);
            float4 o[8];
#pragma unroll
            for (int t = 0; t < 8; t++) o[t] = lds_f4(xch + (w ^ 1) * SLOT + t * 2048);
            const uint32_t tile = sb + OFF_A + w * SLOT;
#pragma unroll
            for (int t = 0; t < 8; t++) {
                hr[2 * t] = pack_bf16(fmaf(acc[4 * t] + o[t].x, cs[t].y, bf_lo(hr[2 * t])), fmaf(acc[4 * t + 1] + o[t].y, cs[t].w, bf_hi(hr[2 * t])));
                hr[2 * t + 1] = pack_bf16(fmaf(acc[4 * t + 2] + o[t].z, cs[t].y, bf_lo(hr[2 * t + 1])), fmaf(acc[4 * t + 3] + o[t].w, cs[t].w, bf_hi(hr[2 * t + 1])));
            }
#pragma unroll
            for (int tp = 0; tp < 4; tp++) stsm4t(tile + blk + tp * 2048, hr[4 * tp], hr[4 * tp + 1], hr[4 * tp + 2], hr[4 * tp + 3]);
            fence_async_smem();
            bar_sync(2 + w, 128);
            if ((tid & 127) == 0) {
                tma_store2d(&P.tout, tile, 64 * j, 128 * m + 64 * w);
                asm volatile("cp.async.bulk.wait_group.read 0;" ::: "memory");
            }
            if (tid == 0 && role == 0) g_epoch = epoch + 1;
            TL(16, tid == 0); TLG(1, tid == 0);
        }
    }
}

__global__ void probe_kernel() {}

typedef CUresult (*EncodeFn)(CUtensorMap*, CUtensorMapDataType, cuuint32_t, void*, const cuuint64_t*, const cuuint64_t*,
                             const cuuint32_t*, const cuuint32_t*, CUtensorMapInterleave, CUtensorMapSwizzle,
                             CUtensorMapL2promotion, CUtensorMapFloatOOBfill);

static void make_map2d(EncodeFn enc, CUtensorMap* tm, const void* base, uint64_t cols, uint64_t rows, uint64_t pitch_elems,
                       uint32_t box_rows) {
    cuuint64_t gd[2] = {cols, rows};
    cuuint64_t gs[1] = {pitch_elems * 2};
    cuuint32_t bd[2] = {64, box_rows};
    cuuint32_t es[2] = {1, 1};
    enc(tm, CU_TENSOR_MAP_DATA_TYPE_BFLOAT16, 2, const_cast<void*>(base), gd, gs, bd, es, CU_TENSOR_MAP_INTERLEAVE_NONE,
        CU_TENSOR_MAP_SWIZZLE_128B, CU_TENSOR_MAP_L2_PROMOTION_L2_256B, CU_TENSOR_MAP_FLOAT_OOB_FILL_NONE);
}

}

extern "C" void kernel_launch(void* const* d_in, const int* in_sizes, int n_in, void* d_out, int out_size) {
    using namespace hk;
    (void)in_sizes; (void)n_in; (void)out_size;
    static EncodeFn enc = nullptr;
    static int std_layout = 0;
    if (!enc) {
        void* fn = nullptr;
        cudaDriverEntryPointQueryResult qr;
        cudaGetDriverEntryPoint("cuTensorMapEncodeTiled", &fn, cudaEnableDefault, &qr);
        enc = (EncodeFn)fn;
        cudaFuncSetAttribute(fused_kernel, cudaFuncAttributeMaxDynamicSharedMemorySize, SMEM_BYTES);
        int dev = 0, sms = 0;
        cudaGetDevice(&dev);
        cudaDeviceGetAttribute(&sms, cudaDevAttrMultiProcessorCount, dev);
        cudaFuncSetAttribute(probe_kernel, cudaFuncAttributeNonPortableClusterSizeAllowed, 1);
        cudaFuncSetAttribute(probe_kernel, cudaFuncAttributeMaxDynamicSharedMemorySize, SMEM_BYTES);
        const int sizes[3] = {8, 9, 16}, want[3] = {15, 9, 7};
        bool ok = sms == NCTA;
        for (int i = 0; i < 3 && ok; i++) {
            cudaLaunchConfig_t cfg = {};
            cfg.gridDim = dim3(sizes[i] * 8); cfg.blockDim = dim3(NTHREADS); cfg.dynamicSmemBytes = SMEM_BYTES;
            cudaLaunchAttribute at;
            at.id = cudaLaunchAttributeClusterDimension;
            at.val.clusterDim.x = sizes[i]; at.val.clusterDim.y = 1; at.val.clusterDim.z = 1;
            cfg.attrs = &at; cfg.numAttrs = 1;
            int n = 0;
            ok = cudaOccupancyMaxActiveClusters(&n, probe_kernel, &cfg) == cudaSuccess && n == want[i];
        }
        (void)cudaGetLastError();
        std_layout = ok ? 1 : 0;
    }
    Params P;
    const __nv_bfloat16* x = (const __nv_bfloat16*)d_in[0];
    P.x = x;
    P.wqkv = (const __nv_bfloat16*)d_in[1];
    P.wphi = (const __nv_bfloat16*)d_in[2];
    P.wo = (const __nv_bfloat16*)d_in[3];
    P.wg = (const __nv_bfloat16*)d_in[5];
    P.wu = (const __nv_bfloat16*)d_in[6];
    P.wd = (const __nv_bfloat16*)d_in[7];
    P.out = (__nv_bfloat16*)d_out;
    P.zero = 0;
    for (int i = 0; i < NCTA; i++) {
        const int odd = i & 1;
        int role = i < 4 ? 128 + i : (((i - 4) >> 4) * 2 + odd) * 8 + (((i - 4) >> 1) & 7);
        if (std_layout) {
            const int tpc = i < 8 ? 62 + (i >> 1) : (i - 8) >> 1;
            if (tpc < 32) role = (tpc & 7) ? (2 * ((tpc & 7) - 1) + odd) * 8 + (tpc >> 3) : (14 + odd) * 8 + (tpc >> 3);
            else if (tpc < 60) role = (2 * ((tpc - 32) % 7) + odd) * 8 + 4 + (tpc - 32) / 7;
            else if (tpc < 62) role = 128 + (tpc - 60) * 2 + odd;
            else role = (14 + odd) * 8 + 4 + (tpc - 62);
        }
        P.role[i] = (unsigned char)role;
    }
    make_map2d(enc, &P.tx, x, DM, SEQ, DM, 128);
    make_map2d(enc, &P.twq, P.wqkv, 3 * DM, DM, 3 * DM, 64);
    make_map2d(enc, &P.two, P.wo, DM, DM, DM, 64);
    make_map2d(enc, &P.twg, P.wg, FF, DM, FF, 64);
    make_map2d(enc, &P.twu, P.wu, FF, DM, FF, 64);
    make_map2d(enc, &P.twd, P.wd, DM, FF, DM, 64);
    make_map2d(enc, &P.tout, d_out, DM, SEQ, DM, 64);
    fused_kernel<<<NCTA, NTHREADS, SMEM_BYTES>>>(P);
}
```

```cpp
#include <cuda_runtime.h>
#include <cuda_bf16.h>
#include <cuda.h>
#include <stdint.h>

namespace hk {

constexpr int SEQ = 2048, DM = 512, FF = 1376;
constexpr int NCTA = 132;
constexpr int NTHREADS = 384;
constexpr uint32_t SLOT = 16384;
constexpr uint32_t OFF_A = 0, OFF_B = 8 * SLOT, OFF_MISC = 14 * SLOT;
constexpr uint32_t BAR_FULLA = OFF_MISC + 0, BAR_EMPTYA = OFF_MISC + 64, BAR_FULLB = OFF_MISC + 128,
                   BAR_EMPTYB = OFF_MISC + 176, BAR_CS1 = OFF_MISC + 224, BAR_CS3 = OFF_MISC + 232,
                   BAR_CSQ = OFF_MISC + 240, BAR_CSV = OFF_MISC + 248,
                   BAR_STG = OFF_MISC + 256,
                   BAR_KVW = OFF_MISC + 280, BAR_KVR = OFF_MISC + 288, BAR_CSG = OFF_MISC + 296;
constexpr uint32_t OFF_CS1 = OFF_MISC + 384;
constexpr uint32_t OFF_CS3 = OFF_CS1 + 1024;
constexpr uint32_t OFF_XST = OFF_CS3;
constexpr uint32_t SMEM_BYTES = OFF_CS3 + 1536;
#define KORD(i, j) ((i) == 0 ? (j) : (i) - ((i) <= (j)))
constexpr int NB = 6;
#define PF_DELAY 2
#define KV_POLL 1
constexpr int AHEAD = 3;

constexpr int ACC_SIZE = 3 * 256 * 4;

__device__ __align__(1024) uint4 g_act[5 * 128 * 1024];
__device__ __align__(128) unsigned long long g_hstat[SEQ * 16];
__device__ __align__(128) unsigned long long g_xstat[SEQ * 2];
__device__ __align__(128) float g_acc[8 * ACC_SIZE];
__device__ __align__(128) unsigned long long g_cs[8 * 6 * 128];
__device__ __align__(128) unsigned g_flag[16 * 5 * 32 + 32];
__device__ unsigned g_epoch = 1;

#define TL(i, pred) do {} while (0)
#define TLG(i, pred) do {} while (0)

struct Params {
    CUtensorMap tx, twq, two, twg, twu, twd, tout;
    const __nv_bfloat16 *x, *wqkv, *wphi, *wo, *wg, *wu, *wd;
    __nv_bfloat16* out;
    unsigned zero;
};

__device__ __forceinline__ uint32_t smem_u32(const void* p) { return (uint32_t)__cvta_generic_to_shared(p); }
__device__ __forceinline__ void mbar_init(uint32_t bar, uint32_t cnt) {
    asm volatile("mbarrier.init.shared::cta.b64 [%0], %1;" ::"r"(bar), "r"(cnt) : "memory");
}
__device__ __forceinline__ void mbar_expect_tx(uint32_t bar, uint32_t bytes) {
    asm volatile("mbarrier.arrive.expect_tx.shared::cta.b64 _, [%0], %1;" ::"r"(bar), "r"(bytes) : "memory");
}
__device__ __forceinline__ void mbar_arrive(uint32_t bar) {
    asm volatile("mbarrier.arrive.shared::cta.b64 _, [%0];" ::"r"(bar) : "memory");
}
__device__ __forceinline__ void mbar_arrive_if(uint32_t bar, bool pred) {
    asm volatile("{.reg .pred p; setp.ne.u32 p, %1, 0; @p mbarrier.arrive.shared::cta.b64 _, [%0];}" ::"r"(bar), "r"((uint32_t)pred) : "memory");
}
__device__ __forceinline__ bool mbar_try(uint32_t bar, uint32_t parity) {
    uint32_t ok;
    asm volatile("{.reg .pred p; mbarrier.try_wait.parity.shared::cta.b64 p, [%1], %2; selp.u32 %0,1,0,p;}"
                 : "=r"(ok) : "r"(bar), "r"(parity) : "memory");
    return ok;
}
__device__ __forceinline__ bool mbar_test(uint32_t bar, uint32_t parity) {
    uint32_t ok;
    asm volatile("{.reg .pred p; mbarrier.test_wait.parity.shared::cta.b64 p, [%1], %2; selp.u32 %0,1,0,p;}"
                 : "=r"(ok) : "r"(bar), "r"(parity) : "memory");
    return ok;
}
__device__ __forceinline__ void trap_if_gt(uint32_t v, uint32_t lim) {
    asm volatile("{.reg .pred p; setp.gt.u32 p, %0, %1; @p trap;}" ::"r"(v), "r"(lim));
}
__device__ __forceinline__ void mbar_wait(uint32_t bar, uint32_t parity) {
    asm volatile("{\n"
                 ".reg .pred P1, P2;\n"
                 ".reg .u32 c;\n"
                 "mov.u32 c, 0;\n"
                 "LAB_WAIT:\n"
                 "mbarrier.try_wait.parity.shared::cta.b64 P1, [%0], %1;\n"
                 "@P1 bra LAB_DONE;\n"
                 "add.u32 c, c, 1;\n"
                 "setp.gt.u32 P2, c, 4194304;\n"
                 "@P2 trap;\n"
                 "bra LAB_WAIT;\n"
                 "LAB_DONE:\n"
                 "}" ::"r"(bar), "r"(parity) : "memory");
}
__device__ __forceinline__ void mbar_waitc(uint32_t bar, uint32_t parity) {
    asm volatile("{\n"
                 ".reg .pred P1;\n"
                 "LAB_WAIT:\n"
                 "mbarrier.try_wait.parity.shared::cta.b64 P1, [%0], %1;\n"
                 "@!P1 bra LAB_WAIT;\n"
                 "}" ::"r"(bar), "r"(parity) : "memory");
}
__device__ __forceinline__ void tma2d(uint32_t dst, const CUtensorMap* tm, uint32_t bar, int c0, int c1) {
    asm volatile("cp.async.bulk.tensor.2d.shared::cluster.global.mbarrier::complete_tx::bytes [%0], [%1, {%3, %4}], [%2];"
                 ::"r"(dst), "l"(tm), "r"(bar), "r"(c0), "r"(c1) : "memory");
}
__device__ __forceinline__ void tma2d_mc(uint32_t dst, const CUtensorMap* tm, uint32_t bar, int c0, int c1) {
    asm volatile("cp.async.bulk.tensor.2d.shared::cluster.global.mbarrier::complete_tx::bytes.multicast::cluster [%0], [%1, {%3, %4}], [%2], %5;"
                 ::"r"(dst), "l"(tm), "r"(bar), "r"(c0), "r"(c1), "h"((uint16_t)3) : "memory");
}
__device__ __forceinline__ uint32_t mapa(uint32_t addr, uint32_t rank) {
    uint32_t r; asm("mapa.shared::cluster.u32 %0, %1, %2;" : "=r"(r) : "r"(addr), "r"(rank)); return r;
}
__device__ __forceinline__ void mbar_arrive_cl_if(uint32_t cbar, bool pred) {
    asm volatile("{.reg .pred p; setp.ne.u32 p, %1, 0; @p mbarrier.arrive.shared::cluster.b64 _, [%0];}" ::"r"(cbar), "r"((uint32_t)pred) : "memory");
}
__device__ __forceinline__ bool elect_one() {
    uint32_t ok;
    asm volatile("{.reg .pred p; elect.sync _|p, 0xffffffff; selp.u32 %0, 1, 0, p;}" : "=r"(ok));
    return ok;
}
__device__ __forceinline__ void prefetch_tmap(const CUtensorMap* tm) {
    asm volatile("prefetch.tensormap [%0];" ::"l"(tm) : "memory");
}
__device__ __forceinline__ void prefetch_l2(const void* p, uint32_t bytes) {
    asm volatile("cp.async.bulk.prefetch.L2.global [%0], %1;" ::"l"(p), "r"(bytes) : "memory");
}
__device__ __forceinline__ unsigned ld_acquire(const unsigned* p) {
    unsigned v; asm volatile("ld.acquire.gpu.global.u32 %0, [%1];" : "=r"(v) : "l"(p) : "memory"); return v;
}
__device__ __forceinline__ uint4 ld_acquire4(const unsigned* p) {
    uint4 v;
    asm volatile("ld.acquire.gpu.global.v4.u32 {%0,%1,%2,%3}, [%4];" : "=r"(v.x), "=r"(v.y), "=r"(v.z), "=r"(v.w) : "l"(p) : "memory");
    return v;
}
__device__ __forceinline__ unsigned ld_relaxed(const unsigned* p) {
    unsigned v; asm volatile("ld.relaxed.gpu.global.u32 %0, [%1];" : "=r"(v) : "l"(p)); return v;
}
__device__ __forceinline__ void st_relaxed(unsigned* p, unsigned v) {
    asm volatile("st.relaxed.gpu.global.u32 [%0], %1;" ::"l"(p), "r"(v) : "memory");
}
__device__ __forceinline__ void red_relaxed(unsigned* p, unsigned v) {
    asm volatile("red.relaxed.gpu.global.add.u32 [%0], %1;" ::"l"(p), "r"(v) : "memory");
}
__device__ __forceinline__ void fence_gpu() { asm volatile("fence.acq_rel.gpu;" ::: "memory"); }
__device__ __forceinline__ void fence_async_smem() { asm volatile("fence.proxy.async.shared::cta;" ::: "memory"); }
__device__ __forceinline__ void fence_async_global() { asm volatile("fence.proxy.async.global;" ::: "memory"); }
__device__ __forceinline__ uint32_t readback(const void* p) {
    uint32_t v; asm volatile("ld.relaxed.gpu.global.u32 %0, [%1];" : "=r"(v) : "l"(p) : "memory"); return v;
}
__device__ __forceinline__ void wait_count(const unsigned* p, unsigned target) {
    uint32_t it = 0;
    while ((int)(readback(p) - target) < 0) trap_if_gt(++it, 1u << 22);
}
__device__ __forceinline__ void wait_count_warp(const unsigned* p, unsigned target) {
    uint32_t it = 0;
    while (__any_sync(0xffffffffu, (int)(readback(p) - target) < 0)) trap_if_gt(++it, 1u << 22);
}
__device__ __forceinline__ void red_f32(float* p, float a) {
    asm volatile("red.relaxed.gpu.global.add.f32 [%0], %1;" ::"l"(p), "f"(a) : "memory");
}
__device__ __forceinline__ void red_f32x2(float* p, float a, float b) {
    asm volatile("red.relaxed.gpu.global.add.v2.f32 [%0], {%1, %2};" ::"l"(p), "f"(a), "f"(b) : "memory");
}
__device__ __forceinline__ void red_f32x4(float* p, float a, float b, float c, float d) {
    asm volatile("red.relaxed.gpu.global.add.v4.f32 [%0], {%1, %2, %3, %4};" ::"l"(p), "f"(a), "f"(b), "f"(c), "f"(d) : "memory");
}
__device__ __forceinline__ float4 ld_l2_f4(const float* p) {
    float4 v;
    asm volatile("ld.relaxed.gpu.global.v4.f32 {%0,%1,%2,%3}, [%4];" : "=f"(v.x), "=f"(v.y), "=f"(v.z), "=f"(v.w) : "l"(p) : "memory");
    return v;
}
__device__ __forceinline__ float2 ld_l2_f2(const float* p) {
    float2 v;
    asm volatile("ld.relaxed.gpu.global.v2.f32 {%0,%1}, [%2];" : "=f"(v.x), "=f"(v.y) : "l"(p) : "memory");
    return v;
}
__device__ __forceinline__ float ld_l2_f(const float* p) {
    float v;
    asm volatile("ld.relaxed.gpu.global.f32 %0, [%1];" : "=f"(v) : "l"(p) : "memory");
    return v;
}
__device__ __forceinline__ uint4 ldg_nc(const void* p) {
    uint4 v;
    asm volatile("ld.global.nc.L1::no_allocate.v4.u32 {%0,%1,%2,%3}, [%4];" : "=r"(v.x), "=r"(v.y), "=r"(v.z), "=r"(v.w) : "l"(p));
    return v;
}
__device__ __forceinline__ void stg128(void* p, uint32_t a, uint32_t b, uint32_t c, uint32_t d) {
    asm volatile("st.global.v4.u32 [%0], {%1,%2,%3,%4};" ::"l"(p), "r"(a), "r"(b), "r"(c), "r"(d) : "memory");
}
__device__ __forceinline__ uint4 lds128(uint32_t a) {
    uint4 v;
    asm volatile("ld.shared.v4.u32 {%0,%1,%2,%3}, [%4];" : "=r"(v.x), "=r"(v.y), "=r"(v.z), "=r"(v.w) : "r"(a) : "memory");
    return v;
}
__device__ __forceinline__ float2 lds_f2(uint32_t a) {
    float2 v;
    asm volatile("ld.shared.v2.f32 {%0,%1}, [%2];" : "=f"(v.x), "=f"(v.y) : "r"(a) : "memory");
    return v;
}
__device__ __forceinline__ void sts_f2(uint32_t a, float x, float y) {
    asm volatile("st.shared.v2.f32 [%0], {%1,%2};" ::"r"(a), "f"(x), "f"(y) : "memory");
}
__device__ __forceinline__ void sts64(uint32_t a, uint32_t x, uint32_t y) {
    asm volatile("st.shared.v2.u32 [%0], {%1,%2};" ::"r"(a), "r"(x), "r"(y) : "memory");
}
__device__ __forceinline__ void sts128(uint32_t a, uint32_t x, uint32_t y, uint32_t z, uint32_t w) {
    asm volatile("st.shared.v4.u32 [%0], {%1,%2,%3,%4};" ::"r"(a), "r"(x), "r"(y), "r"(z), "r"(w) : "memory");
}
__device__ __forceinline__ void stsm4(uint32_t a, uint32_t r0, uint32_t r1, uint32_t r2, uint32_t r3) {
    asm volatile("stmatrix.sync.aligned.m8n8.x4.shared.b16 [%0], {%1,%2,%3,%4};" ::"r"(a), "r"(r0), "r"(r1), "r"(r2), "r"(r3) : "memory");
}
__device__ __forceinline__ void stsm4t(uint32_t a, uint32_t r0, uint32_t r1, uint32_t r2, uint32_t r3) {
    asm volatile("stmatrix.sync.aligned.m8n8.x4.trans.shared.b16 [%0], {%1,%2,%3,%4};" ::"r"(a), "r"(r0), "r"(r1), "r"(r2), "r"(r3) : "memory");
}
__device__ __forceinline__ void tma_store2d(const CUtensorMap* tm, uint32_t src, int c0, int c1) {
    asm volatile("cp.async.bulk.tensor.2d.global.shared::cta.bulk_group [%0, {%2, %3}], [%1];" ::"l"(tm), "r"(src), "r"(c0), "r"(c1) : "memory");
    asm volatile("cp.async.bulk.commit_group;" ::: "memory");
}
__device__ __forceinline__ void ldsm4(uint32_t a, uint32_t& r0, uint32_t& r1, uint32_t& r2, uint32_t& r3) {
    asm volatile("ldmatrix.sync.aligned.m8n8.x4.shared.b16 {%0,%1,%2,%3}, [%4];" : "=r"(r0), "=r"(r1), "=r"(r2), "=r"(r3) : "r"(a) : "memory");
}
__device__ __forceinline__ void ldsm4t(uint32_t a, uint32_t& r0, uint32_t& r1, uint32_t& r2, uint32_t& r3) {
    asm volatile("ldmatrix.sync.aligned.m8n8.x4.trans.shared.b16 {%0,%1,%2,%3}, [%4];" : "=r"(r0), "=r"(r1), "=r"(r2), "=r"(r3) : "r"(a) : "memory");
}
__device__ __forceinline__ void mma16816(float* c, const uint32_t* a, uint32_t b0, uint32_t b1) {
    asm("mma.sync.aligned.m16n8k16.row.col.f32.bf16.bf16.f32 {%0,%1,%2,%3}, {%4,%5,%6,%7}, {%8,%9}, {%0,%1,%2,%3};"
                 : "+f"(c[0]), "+f"(c[1]), "+f"(c[2]), "+f"(c[3])
                 : "r"(a[0]), "r"(a[1]), "r"(a[2]), "r"(a[3]), "r"(b0), "r"(b1));
}
__device__ __forceinline__ uint32_t pack_bf16(float lo, float hi) {
    uint32_t r; asm("cvt.rn.bf16x2.f32 %0, %1, %2;" : "=r"(r) : "f"(hi), "f"(lo)); return r;
}
__device__ __forceinline__ float bf_lo(uint32_t w) { return __uint_as_float(w << 16); }
__device__ __forceinline__ float bf_hi(uint32_t w) { return __uint_as_float(w & 0xffff0000u); }
__device__ __forceinline__ float ex2(float x) { float r; asm("ex2.approx.ftz.f32 %0, %1;" : "=f"(r) : "f"(x)); return r; }
__device__ __forceinline__ float rcp(float x) { float r; asm("rcp.approx.ftz.f32 %0, %1;" : "=f"(r) : "f"(x)); return r; }
__device__ __forceinline__ void bar_sync(int id, int n) { asm volatile("bar.sync %0, %1;" ::"r"(id), "r"(n) : "memory"); }

typedef unsigned long long desc_t;
__device__ __forceinline__ desc_t desc_lo(uint32_t addr) { return (desc_t)(((addr & 0x3FFFF) >> 4) | (512u << 16)) | (0x40000040ull << 32); }
__device__ __forceinline__ void wg_fence() { asm volatile("wgmma.fence.sync.aligned;" ::: "memory"); }
__device__ __forceinline__ void wg_commit() { asm volatile("wgmma.commit_group.sync.aligned;" ::: "memory"); }
template <int N> __device__ __forceinline__ void wg_wait() { asm volatile("wgmma.wait_group.sync.aligned %0;" ::"n"(N) : "memory"); }
template <int N> __device__ __forceinline__ void fence_acc(float* d) {
#pragma unroll
    for (int i = 0; i < N; i++) asm volatile("" : "+f"(d[i])::"memory");
}
#define R4(o) "+f"(d[o + 0]), "+f"(d[o + 1]), "+f"(d[o + 2]), "+f"(d[o + 3])
#define R8(o) R4(o), R4(o + 4)
__device__ __forceinline__ void wgmma_n128(float* d, desc_t da, desc_t db, int sc) {
    asm volatile("{.reg .pred p; setp.ne.b32 p, %66, 0;\n"
                 "wgmma.mma_async.sync.aligned.m64n128k16.f32.bf16.bf16 {%0,%1,%2,%3,%4,%5,%6,%7,%8,%9,%10,%11,%12,%13,%14,%15,%16,%17,%18,%19,%20,%21,%22,%23,%24,%25,%26,%27,%28,%29,%30,%31,"
                 "%32,%33,%34,%35,%36,%37,%38,%39,%40,%41,%42,%43,%44,%45,%46,%47,%48,%49,%50,%51,%52,%53,%54,%55,%56,%57,%58,%59,%60,%61,%62,%63}, %64, %65, p, 1, 1, 0, 1;}"
                 : R8(0), R8(8), R8(16), R8(24), R8(32), R8(40), R8(48), R8(56)
                 : "l"(da), "l"(db), "r"(sc));
}
__device__ __forceinline__ void wgmma_n112(float* d, desc_t da, desc_t db, int sc) {
    asm volatile("{.reg .pred p; setp.ne.b32 p, %58, 0;\n"
                 "wgmma.mma_async.sync.aligned.m64n112k16.f32.bf16.bf16 {%0,%1,%2,%3,%4,%5,%6,%7,%8,%9,%10,%11,%12,%13,%14,%15,%16,%17,%18,%19,%20,%21,%22,%23,%24,%25,%26,%27,%28,%29,%30,%31,%32,%33,%34,%35,%36,%37,%38,%39,%40,%41,%42,%43,%44,%45,%46,%47,%48,%49,%50,%51,%52,%53,%54,%55}, %56, %57, p, 1, 1, 0, 1;}"
                 : R8(0), R8(8), R8(16), R8(24), R8(32), R8(40), R8(48)
                 : "l"(da), "l"(db), "r"(sc));
}
__device__ __forceinline__ void wgmma_n128_tn(float* d, desc_t da, desc_t db, int sc) {
    asm volatile("{.reg .pred p; setp.ne.b32 p, %66, 0;\n"
                 "wgmma.mma_async.sync.aligned.m64n128k16.f32.bf16.bf16 {%0,%1,%2,%3,%4,%5,%6,%7,%8,%9,%10,%11,%12,%13,%14,%15,%16,%17,%18,%19,%20,%21,%22,%23,%24,%25,%26,%27,%28,%29,%30,%31,%32,%33,%34,%35,%36,%37,%38,%39,%40,%41,%42,%43,%44,%45,%46,%47,%48,%49,%50,%51,%52,%53,%54,%55,%56,%57,%58,%59,%60,%61,%62,%63}, %64, %65, p, 1, 1, 1, 0;}"
                 : R8(0), R8(8), R8(16), R8(24), R8(32), R8(40), R8(48), R8(56)
                 : "l"(da), "l"(db), "r"(sc));
}
__device__ __forceinline__ void wgmma_n64(float* d, desc_t da, desc_t db, int sc) {
    asm volatile("{.reg .pred p; setp.ne.b32 p, %34, 0;\n"
                 "wgmma.mma_async.sync.aligned.m64n64k16.f32.bf16.bf16 {%0,%1,%2,%3,%4,%5,%6,%7,%8,%9,%10,%11,%12,%13,%14,%15,%16,%17,%18,%19,%20,%21,%22,%23,%24,%25,%26,%27,%28,%29,%30,%31}, %32, %33, p, 1, 1, 0, 1;}"
                 : R8(0), R8(8), R8(16), R8(24)
                 : "l"(da), "l"(db), "r"(sc));
}
__device__ __forceinline__ void wgmma_n40_tt(float* d, desc_t da, desc_t db, int sc) {
    asm volatile("{.reg .pred p; setp.ne.b32 p, %22, 0;\n"
                 "wgmma.mma_async.sync.aligned.m64n40k16.f32.bf16.bf16 {%0,%1,%2,%3,%4,%5,%6,%7,%8,%9,%10,%11,%12,%13,%14,%15,%16,%17,%18,%19}, %20, %21, p, 1, 1, 1, 1;}"
                 : R8(0), R8(8), R4(16)
                 : "l"(da), "l"(db), "r"(sc));
}

__device__ __forceinline__ void wgmma_n8_tt(float* d, desc_t da, desc_t db, int sc) {
    asm volatile("{.reg .pred p; setp.ne.b32 p, %6, 0;\n"
                 "wgmma.mma_async.sync.aligned.m64n8k16.f32.bf16.bf16 {%0,%1,%2,%3}, %4, %5, p, 1, 1, 1, 1;}"
                 : R4(0)
                 : "l"(da), "l"(db), "r"(sc));
}

__device__ __forceinline__ void signal_after(unsigned* cnt, uint32_t ack, uint32_t zero, bool pred) {
    asm volatile("{.reg .pred p; setp.ne.u32 p, %2, 0; @p red.relaxed.gpu.global.add.u32 [%0], %1;}"
                 ::"l"(cnt), "r"((ack & zero) + 1), "r"((uint32_t)pred) : "memory");
}
__device__ __forceinline__ void signal_late(unsigned* cnt, const uint32_t* a, uint32_t zero, bool pred) {
    uint32_t v;
    asm volatile("{.reg .b32 t; lop3.b32 t, %1, %2, %3, 0xfe; or.b32 %0, t, %4;}"
                 : "=r"(v) : "r"(a[0]), "r"(a[1]), "r"(a[2]), "r"(a[3]));
    signal_after(cnt, v, zero, pred);
}
__device__ __forceinline__ void red_f32_if(float* p, float a, bool pred) {
    asm volatile("{.reg .pred p; setp.ne.u32 p, %2, 0; @p red.relaxed.gpu.global.add.f32 [%0], %1;}" ::"l"(p), "f"(a), "r"((uint32_t)pred) : "memory");
}
__device__ __forceinline__ void stg_f2_if(float* p, float a, float b, bool pred) {
    asm volatile("{.reg .pred p; setp.ne.u32 p, %3, 0; @p st.global.v2.f32 [%0], {%1,%2};}" ::"l"(p), "f"(a), "f"(b), "r"((uint32_t)pred) : "memory");
}
__device__ __forceinline__ void stg64(void* p, uint32_t a, uint32_t b) {
    asm volatile("st.global.v2.u32 [%0], {%1,%2};" ::"l"(p), "r"(a), "r"(b) : "memory");
}
__device__ __forceinline__ void mma16816_z(float* c, const uint32_t* a, uint32_t b0, uint32_t b1) {
    asm("mma.sync.aligned.m16n8k16.row.col.f32.bf16.bf16.f32 {%0,%1,%2,%3}, {%4,%5,%6,%7}, {%8,%9}, {%10,%10,%10,%10};"
                 : "=f"(c[0]), "=f"(c[1]), "=f"(c[2]), "=f"(c[3])
                 : "r"(a[0]), "r"(a[1]), "r"(a[2]), "r"(a[3]), "r"(b0), "r"(b1), "f"(0.f));
}
__device__ __forceinline__ uint32_t max2(uint32_t a, uint32_t b) { uint32_t r; asm("max.bf16x2 %0, %1, %2;" : "=r"(r) : "r"(a), "r"(b)); return r; }
__device__ __forceinline__ uint32_t min2(uint32_t a, uint32_t b) { uint32_t r; asm("min.bf16x2 %0, %1, %2;" : "=r"(r) : "r"(a), "r"(b)); return r; }
__device__ __forceinline__ void bar_arrive(int id, int n) { asm volatile("bar.arrive %0, %1;" ::"r"(id), "r"(n) : "memory"); }
__device__ __forceinline__ void mbar_arrive_n_if(uint32_t bar, uint32_t n, bool pred) {
    asm volatile("{.reg .pred p; setp.ne.u32 p, %1, 0; @p mbarrier.arrive.shared::cta.b64 _, [%0], %2;}" ::"r"(bar), "r"((uint32_t)pred), "r"(n) : "memory");
}
__device__ __forceinline__ float4 lds_f4(uint32_t a) {
    float4 v;
    asm volatile("ld.shared.v4.f32 {%0,%1,%2,%3}, [%4];" : "=f"(v.x), "=f"(v.y), "=f"(v.z), "=f"(v.w) : "r"(a) : "memory");
    return v;
}
__device__ __forceinline__ void lds_f4_if(float4& v, uint32_t a, bool pred) {
    asm volatile("{.reg .pred p; setp.ne.u32 p, %5, 0; @p ld.shared.v4.f32 {%0,%1,%2,%3}, [%4];}"
                 : "+f"(v.x), "+f"(v.y), "+f"(v.z), "+f"(v.w) : "r"(a), "r"((uint32_t)pred) : "memory");
}
__device__ __forceinline__ uint4 ld_tagged(const unsigned long long* p) {
    unsigned long long a, b;
    asm volatile("ld.acquire.gpu.global.v2.b64 {%0,%1}, [%2];" : "=l"(a), "=l"(b) : "l"(p) : "memory");
    return make_uint4((unsigned)a, (unsigned)(a >> 32), (unsigned)b, (unsigned)(b >> 32));
}
__device__ __forceinline__ uint4 ld_tagged_rlx(const unsigned long long* p) {
    unsigned long long a, b;
    asm volatile("ld.relaxed.gpu.global.v2.b64 {%0,%1}, [%2];" : "=l"(a), "=l"(b) : "l"(p) : "memory");
    return make_uint4((unsigned)a, (unsigned)(a >> 32), (unsigned)b, (unsigned)(b >> 32));
}
__device__ __forceinline__ void sts32(uint32_t a, uint32_t x) { asm volatile("st.shared.u32 [%0], %1;" ::"r"(a), "r"(x) : "memory"); }
__device__ __forceinline__ void fetch_tagged(const unsigned long long* src, uint32_t dst, unsigned epoch) {
    uint4 v;
    uint32_t it = 0;
    while (true) {
        v = ld_tagged_rlx(src);
        if (!__any_sync(0xffffffffu, v.y != epoch || v.w != epoch)) break;
        __nanosleep(60);
        trap_if_gt(++it, 1u << 22);
    }
    sts64(dst, v.x, v.z);
}
__device__ __forceinline__ void st_tagged_if(unsigned long long* p, float a, float b, unsigned tag, bool pred) {
    const unsigned long long t = (unsigned long long)tag << 32;
    asm volatile("{.reg .pred p; setp.ne.u32 p, %3, 0; @p st.relaxed.gpu.global.v2.b64 [%0], {%1,%2};}"
                 ::"l"(p), "l"(t | __float_as_uint(a)), "l"(t | __float_as_uint(b)), "r"((uint32_t)pred) : "memory");
}

__device__ __forceinline__ void store_tile(uint32_t tile_rows, uint4* gdst, const uint32_t* lo, const uint32_t* hi, int lane, uint32_t* ack) {
    const int r = lane & 15;
#pragma unroll
    for (int b = 0; b < 4; b++)
        stsm4(tile_rows + r * 128 + (((2 * b + (lane >> 4)) ^ (r & 7)) << 4), lo[2 * b], hi[2 * b], lo[2 * b + 1], hi[2 * b + 1]);
    fence_async_smem();
    __syncwarp();
#pragma unroll
    for (int i = 0; i < 4; i++) {
        const uint4 v = lds128(tile_rows + i * 512 + lane * 16);
        stg128(gdst + 32 * i, v.x, v.y, v.z, v.w);
    }
#pragma unroll
    for (int i = 0; i < 4; i++) ack[i] = readback(gdst + 32 * i);
}

__device__ __forceinline__ void feature_maps(const uint32_t* a, const uint32_t* wb, float c0, float c1, uint32_t* plus, uint32_t* minus) {
    uint32_t P[16], mx[4], mn[4];
#pragma unroll
    for (int h = 0; h < 4; h++) {
        float p[8];
        mma16816_z(p, a + 4 * h, wb[4 * h], wb[4 * h + 1]);
        mma16816_z(p + 4, a + 4 * h, wb[4 * h + 2], wb[4 * h + 3]);
        P[4 * h] = pack_bf16(p[0], p[2]); P[4 * h + 1] = pack_bf16(p[1], p[3]);
        P[4 * h + 2] = pack_bf16(p[4], p[6]); P[4 * h + 3] = pack_bf16(p[5], p[7]);
        mx[h] = max2(max2(P[4 * h], P[4 * h + 1]), max2(P[4 * h + 2], P[4 * h + 3]));
        mn[h] = min2(min2(P[4 * h], P[4 * h + 1]), min2(P[4 * h + 2], P[4 * h + 3]));
    }
#pragma unroll
    for (int s = 1; s <= 2; s <<= 1) {
        uint32_t tx[4], tn[4];
#pragma unroll
        for (int h = 0; h < 4; h++) { tx[h] = __shfl_xor_sync(0xffffffffu, mx[h], s); tn[h] = __shfl_xor_sync(0xffffffffu, mn[h], s); }
#pragma unroll
        for (int h = 0; h < 4; h++) { mx[h] = max2(mx[h], tx[h]); mn[h] = min2(mn[h], tn[h]); }
    }
#pragma unroll
    for (int h = 0; h < 4; h++) {
        const float mx0 = bf_lo(mx[h]) * c0, mx1 = bf_hi(mx[h]) * c1, mn0 = bf_lo(mn[h]) * c0, mn1 = bf_hi(mn[h]) * c1;
        float ep[8], em[8];
#pragma unroll
        for (int i = 0; i < 8; i++) {
            const bool r1 = (i & 2);
            const uint32_t w = P[4 * h + (i >> 2) * 2 + (i & 1)];
            const float p = r1 ? bf_hi(w) : bf_lo(w);
            ep[i] = ex2(fmaf(p, r1 ? c1 : c0, r1 ? -mx1 : -mx0));
            em[i] = ex2(fmaf(p, r1 ? -c1 : -c0, r1 ? mn1 : mn0));
        }
        float sp[4], sm[4];
        uint32_t tp[4], tm[4];
#pragma unroll
        for (int i = 0; i < 4; i++) { tp[i] = pack_bf16(ep[2 * i], ep[2 * i + 1]); tm[i] = pack_bf16(em[2 * i], em[2 * i + 1]); }
        mma16816_z(sp, tp, 0x3f803f80u, 0x3f803f80u);
        mma16816_z(sm, tm, 0x3f803f80u, 0x3f803f80u);
        const float r0 = rcp(sp[0] * sm[0]), r1 = rcp(sp[2] * sm[2]);
        const float rs[4] = {r0 * sm[0], r1 * sm[2], r0 * sp[0], r1 * sp[2]};
#pragma unroll
        for (int i = 0; i < 4; i++) {
            plus[4 * h + i] = pack_bf16(ep[2 * i] * rs[i & 1], ep[2 * i + 1] * rs[i & 1]);
            minus[4 * h + i] = pack_bf16(em[2 * i] * rs[2 + (i & 1)], em[2 * i + 1] * rs[2 + (i & 1)]);
        }
    }
}

template <bool SCALE>
__device__ __forceinline__ void ln_frag(const float* acc, uint32_t cs_addr, float rs0, float nm0, float rs1, float nm1, uint32_t* a) {
    const float2 c0 = lds_f2(cs_addr), c1 = lds_f2(cs_addr + 32);
    const float s0 = SCALE ? rs0 : 1.f, s1 = SCALE ? rs1 : 1.f;
    a[0] = pack_bf16(fmaf(nm0, c0.x, acc[0]) * s0, fmaf(nm0, c0.y, acc[1]) * s0);
    a[1] = pack_bf16(fmaf(nm1, c0.x, acc[2]) * s1, fmaf(nm1, c0.y, acc[3]) * s1);
    a[2] = pack_bf16(fmaf(nm0, c1.x, acc[4]) * s0, fmaf(nm0, c1.y, acc[5]) * s0);
    a[3] = pack_bf16(fmaf(nm1, c1.x, acc[6]) * s1, fmaf(nm1, c1.y, acc[7]) * s1);
}

template <int UP>
__device__ __forceinline__ uint32_t hh_pair(const float* ag, float4 cs, float nmean) {
    const float g0 = fmaf(nmean, cs.x, ag[0]), g1 = fmaf(nmean, cs.y, ag[1]);
    const float u0 = fmaf(nmean, cs.z, ag[UP]), u1 = fmaf(nmean, cs.w, ag[UP + 1]);
    return pack_bf16(g0 * u0, g1 * u1);
}
template <int NTP>
__device__ __forceinline__ void hh_stage(const float* acc, const float4* cs, float nm0, float nm1, uint32_t stg, int lane) {
#pragma unroll
    for (int tp = 0; tp < NTP; tp++)
        stsm4(stg + (lane & 15) * 128 + (((2 * tp + (lane >> 4)) ^ (lane & 7)) << 4), hh_pair<32>(acc + 8 * tp, cs[2 * tp], nm0),
              hh_pair<32>(acc + 8 * tp + 2, cs[2 * tp], nm1), hh_pair<32>(acc + 8 * tp + 4, cs[2 * tp + 1], nm0),
              hh_pair<32>(acc + 8 * tp + 6, cs[2 * tp + 1], nm1));
    fence_async_smem();
    __syncwarp();
}

template <int TP0, int TP1>
__device__ __forceinline__ void hh_stage2(const float* acc, const float4* cs, float nm0, float nm1, uint32_t stg, int lane) {
#pragma unroll
    for (int tp = TP0; tp < TP1; tp++)
        stsm4(stg + (lane & 15) * 128 + (((2 * tp + (lane >> 4)) ^ (lane & 7)) << 4), hh_pair<32>(acc + 8 * tp, cs[2 * tp], nm0),
              hh_pair<32>(acc + 8 * tp + 2, cs[2 * tp], nm1), hh_pair<32>(acc + 8 * tp + 4, cs[2 * tp + 1], nm0),
              hh_pair<32>(acc + 8 * tp + 6, cs[2 * tp + 1], nm1));
}
struct Ring {
    int slot; uint32_t phase;
    __device__ __forceinline__ void adv() { if (++slot == NB) { slot = 0; phase ^= 1; } }
    __device__ __forceinline__ void adv5() { slot += slot == 3; adv(); }
};

__global__ void __cluster_dims__(2, 1, 1) __launch_bounds__(NTHREADS, 1) fused_kernel(const __grid_constant__ Params P) {
    extern __shared__ __align__(1024) uint8_t smem_raw[];
    const uint32_t sb = smem_u32(smem_raw);
    const int tid = threadIdx.x, lane = tid & 31;
    const int warp = __shfl_sync(0xffffffffu, tid >> 5, 0);
    const unsigned rank = blockIdx.x & 1;
    int m, j;
    {
        const int t = (int)(blockIdx.x >> 1) - 4, u = t - 32, r7 = (u * 37) >> 8;
        const int gp = t < 32 ? (t & 7) - 1 : u - 7 * r7;
        j = t < 0 ? t + 6 : (t < 32 ? t >> 3 : (t < 60 ? 4 + r7 : t - 54));
        m = ((t < 0 || t >= 60 || gp < 0) ? 14 : 2 * gp) + rank;
        if (t < -2) { m = 16; j = blockIdx.x; }
    }
    const unsigned role = m * 8 + j;
    const bool helper = m == 16;

    TL(0, tid == 0); TLG(0, tid == 0);
    float* const acc_j = g_acc + j * ACC_SIZE;
    if ((warp & ~1) == 8 && elect_one()) {
        const uint32_t bar = sb + (warp == 8 ? BAR_FULLB : BAR_FULLA);
#pragma unroll
        for (int i = 0; i < 8; i++) if (i < NB || warp == 9) mbar_init(bar + 8 * i, 1);
        if (!helper) {
#pragma unroll
            for (int i = 0; i < 2; i++) {
                mbar_expect_tx(bar + 8 * i, SLOT);
                if (warp == 8) {
                    tma2d(sb + OFF_B + i * SLOT, &P.twq, bar + 8 * i, DM + 64 * j, 64 * i);
                    tma2d(sb + OFF_B + i * SLOT + 8192, &P.twq, bar + 8 * i, 2 * DM + 64 * j, 64 * i);
                } else {
                    tma2d(sb + OFF_A + i * SLOT, &P.tx, bar + 8 * i, 64 * i, 128 * m);
                }
            }
        }
    }
    __syncwarp();

    if (warp >= 8) {
        asm volatile("setmaxnreg.dec.sync.aligned.u32 72;");
        if (elect_one()) {
            if (warp < 10) {
            } else if (warp == 10) {
#pragma unroll
                for (int i = 0; i < 12; i++) mbar_init(sb + BAR_CS1 + 8 * i, i < 2 || i >= 8 ? 64 : (i < 4 ? 32 : 8));
                trap_if_gt(sb & 1023, 0);
            } else {
#pragma unroll
                for (int i = 0; i < 14; i++) mbar_init(sb + (i < 8 ? BAR_EMPTYA : BAR_EMPTYB - 64) + 8 * i, i < 8 ? 8 : 16);
            }
            asm volatile("fence.mbarrier_init.release.cluster;" ::: "memory");
        }
        __syncwarp();
        asm volatile("barrier.cluster.arrive.relaxed.aligned;" ::: "memory");
        const unsigned epoch = ld_relaxed(&g_epoch);
        bar_sync(0, NTHREADS);
        if (helper) {
            if (elect_one()) {
#pragma unroll 1
                for (int i = warp - 8; i < 72; i += 4) {
                    const uint32_t full = sb + BAR_FULLA + 8 * (i & 7), dst = sb + OFF_A + (i & 7) * SLOT;
                    const int n = i >> 1, jj = 2 * j + (i & 1);
                    const bool qkv = n < 12;
                    const int c0 = qkv ? (n < 8 ? DM + 128 * (n & 4) : 0) + 64 * jj : 176 * jj + 8 * ((n - 12) & ~7);
                    const int r0 = qkv ? 128 * (n & 3) : 64 * ((n - 12) & 7);
                    mbar_wait(sb + BAR_EMPTYA + 8 * (i & 7), ((i >> 3) & 1) ^ 1);
                    mbar_expect_tx(full, SLOT);
                    tma2d(dst, qkv ? &P.twq : &P.twg, full, c0, r0);
                    tma2d(dst + 8192, qkv ? &P.twq : &P.twu, full, c0, qkv ? r0 + 64 : r0);
                }
                prefetch_l2(P.wd + (size_t)(4 * j + warp - 8) * 44032, 88064);
            }
            return;
        }
        if (warp == 8) {
            asm volatile("barrier.cluster.wait.aligned;" ::: "memory");
            if (elect_one()) {
                if (m >= 6)
                    asm volatile("cp.async.bulk.prefetch.tensor.2d.L2.global [%0, {%1, %2}];" ::"l"(&P.twq), "r"(DM + DM * (m & 1) + 64 * j), "r"(64 * (m >> 1)) : "memory");
                if (j >= 3)
                    asm volatile("cp.async.bulk.prefetch.tensor.2d.L2.global [%0, {%1, %2}];" ::"l"(&P.tx), "r"(64 * j), "r"(128 * m) : "memory");
                Ring r{2, 0};
                const uint32_t dst = sb + OFF_B + rank * 8192;
#define B_LOAD(TM, C0, R0)                                                                                  \
        mbar_waitc(sb + BAR_EMPTYB + 8 * r.slot, r.phase ^ 1);                                              \
        mbar_expect_tx(sb + BAR_FULLB + 8 * r.slot, SLOT);                                                  \
        tma2d_mc(dst + r.slot * SLOT, TM, sb + BAR_FULLB + 8 * r.slot, C0, R0);
#pragma unroll 1
                for (int i = 2; i < 8; i++) {
                    if (i >= AHEAD && i < 6) mbar_waitc(sb + BAR_FULLB + 8 * (i - AHEAD), 0);
                    B_LOAD(&P.twq, DM + DM * rank + 64 * j, 64 * i)
                    r.adv();
                }
#pragma unroll 1
                for (int i = 8; i < 18; i++) {
                    if (i == 9 || i == 10) {
                        mbar_waitc(sb + BAR_EMPTYB + 8 * r.slot, r.phase ^ 1);
                        mbar_arrive(sb + BAR_FULLB + 8 * r.slot);
                    } else {
                        const int e = 2 * (i - 14) + rank, b = (i == 8 ? 0 : i - 10) ^ (i < 12 && j < 2);
                        B_LOAD(i < 14 ? &P.twq : &P.two, 64 * j, 64 * (i < 14 ? 2 * b + rank : KORD(e, j)))
                    }
                    r.adv();
                }
#pragma unroll 1
                for (int i = 0; i < 24; i++) {
                    B_LOAD(&P.twg + rank, 176 * j + 8 * (i & ~7), 64 * (i < 8 ? KORD(i, j) : i & 7))
                    r.adv5();
                }
#pragma unroll 1
                for (int i = 0; i < 12; i++) {
                    B_LOAD(&P.twd, 64 * j, 176 * (2 * (i & 3) + rank) + 64 * (i >> 2))
                    r.adv5();
                }
            }
            return;
        }
        if (warp == 9) {
            if (elect_one()) {
#pragma unroll 1
                for (int i = 2; i < 8; i++) {
                    if (i >= AHEAD + 1) mbar_wait(sb + BAR_FULLA + 8 * (i - AHEAD - 1), 0);
                    mbar_expect_tx(sb + BAR_FULLA + 8 * i, SLOT);
                    tma2d(sb + OFF_A + i * SLOT, &P.tx, sb + BAR_FULLA + 8 * i, 64 * i, 128 * m);
                }
#pragma unroll 1
                for (int i = 2; i < 7; i++) prefetch_tmap(&P.tx + i);
                unsigned nf = 0;
#pragma unroll 1
                for (int r = 1; r < 6; r++) {
                    const int skip = r < 3 ? j : 8;
                    const uint4* src = g_act + ((r - 1) * 128 + m * 8) * 1024;
                    const unsigned* fl = g_flag + (m * 5 + r - 1) * 32;
                    if (r < 4) mbar_wait(sb + BAR_EMPTYA + 8 * (r == 3 ? PF_DELAY : 3 - 2 * (j == 3)), (r - 1) & 1);
                    if (r < 4 || nf != epoch * 8) wait_count(fl, epoch * (r < 3 ? 64 : 8));
                    TL(64 + r, true);
#pragma unroll 1
                    for (int t = 0; t < 8; t++) {
                        if (t == skip) continue;
                        if (t == 6) nf = readback(fl + 32);
                        mbar_wait(sb + BAR_EMPTYA + 8 * t, (r - 1) & 1);
                        mbar_expect_tx(sb + BAR_FULLA + 8 * t, SLOT);
                        asm volatile("cp.async.bulk.shared::cluster.global.mbarrier::complete_tx::bytes [%0], [%1], %2, [%3];"
                                     ::"r"(sb + OFF_A + t * SLOT), "l"(src + t * 1024), "r"(SLOT), "r"(sb + BAR_FULLA + 8 * t) : "memory");
                    }
                }
            }
            return;
        }
        const int a = warp - 10;
        {
            const int row = 16 * j + 8 * a + (lane >> 2);
            const uint32_t ra = sb + OFF_A + row * 128;
            float sh = 0.f, s0 = 0.f, s1 = 0.f, q0 = 0.f, q1 = 0.f;
#pragma unroll 1
            for (int kt = 0; kt < 8; kt++) {
                mbar_wait(sb + BAR_FULLA + 8 * kt, 0);
                if (kt == 0) sh = bf_lo(lds128(ra + ((row & 7) << 4)).x);
#pragma unroll
                for (int i = 0; i < 2; i++) {
                    const uint4 v = lds128(ra + kt * SLOT + (((2 * (lane & 3) + i) ^ (row & 7)) << 4));
                    const uint32_t ww[4] = {v.x, v.y, v.z, v.w};
#pragma unroll
                    for (int e = 0; e < 4; e++) {
                        const float d0 = bf_lo(ww[e]) - sh, d1 = bf_hi(ww[e]) - sh;
                        s0 += d0; q0 = fmaf(d0, d0, q0);
                        s1 += d1; q1 = fmaf(d1, d1, q1);
                    }
                }
            }
            s0 += s1; q0 += q1;
#pragma unroll
            for (int o = 1; o <= 2; o <<= 1) { s0 += __shfl_xor_sync(0xffffffffu, s0, o); q0 += __shfl_xor_sync(0xffffffffu, q0, o); }
            const float md = s0 * (1.f / DM);
            const float rs = rsqrtf(fmaxf(q0 * (1.f / DM) - md * md, 0.f) + 1e-5f);
            st_tagged_if(g_xstat + 2 * (128 * m + row), rs, -(sh + md), epoch, (lane & 3) == 0);
            TL(1, lane == 0 && a == 0);
        }
        const unsigned long long* cs = g_cs + j * 768 + 2 * lane;
        {
            const unsigned long long* xs = g_xstat + 2 * (128 * m + 64 * a + lane);
            uint4 v0, v1, v2;
            uint32_t it = 0;
            do {
                v0 = ld_tagged_rlx(xs); v1 = ld_tagged_rlx(xs + 64); v2 = ld_tagged_rlx(cs);
                trap_if_gt(++it, 1u << 22);
            } while (__any_sync(0xffffffffu, v0.y != epoch || v0.w != epoch || v1.y != epoch || v1.w != epoch || v2.y != epoch || v2.w != epoch));
            sts64(sb + OFF_XST + (64 * a + lane) * 8, v0.x, v0.z);
            sts64(sb + OFF_XST + (64 * a + 32 + lane) * 8, v1.x, v1.z);
            sts64(sb + OFF_CS1 + 256 + 8 * lane, v2.x, v2.z);
            mbar_arrive(sb + BAR_CS1);
            TL(22 + a, lane == 0);
            fetch_tagged(cs + 128 + 128 * a, sb + OFF_CS1 + 512 - 512 * a + 8 * lane, epoch);
            mbar_arrive(sb + BAR_CSV - 8 * a);
            TL(24 + a, lane == 0);
        }
        {
            mbar_wait(sb + BAR_KVW, 0);
            const float* src = acc_j + 4 * (128 * a + lane);
            float4 v[12];
            uint32_t it = 0;
            bool bad;
            while (__any_sync(0xffffffffu, readback(acc_j + 2048 + 128 * (lane & 7) + 127) != 0x41800000u)) trap_if_gt(++it, 1u << 22);
            TL(19, lane == 0 && a == 0);
            do {
                bad = false;
#pragma unroll
                for (int i = 0; i < 12; i++) v[i] = ld_l2_f4(src + 1024 * (i % 3) + 128 * (i / 3));
#pragma unroll
                for (int i = 0; i < 12; i++) bad |= v[i].w != 16.f;
                trap_if_gt(++it, 1u << 22);
            } while (__any_sync(0xffffffffu, bad));
            TL(14, lane == 0 && a == 0);
            const uint32_t d0 = sb + OFF_A + (j < 2 ? 2 * SLOT : 0) + (64 * a + (lane >> 2)) * 48;
            const uint32_t d = d0 + (lane & 3) * 4, dz = d0 + (lane & 1) * 384 + 32 + (lane & 2) * 4;
#pragma unroll
            for (int u = 0; u < 4; u++) {
                sts32(d + 768 * u, pack_bf16(v[3 * u].x, v[3 * u].y));
                sts32(d + 768 * u + 384, pack_bf16(v[3 * u].z, v[3 * u + 1].z));
                sts32(d + 768 * u + 16, pack_bf16(v[3 * u + 1].x, v[3 * u + 1].y));
                sts32(d + 768 * u + 400, pack_bf16(v[3 * u + 2].x, v[3 * u + 2].y));
                const uint32_t z2 = pack_bf16(v[3 * u + 2].z, v[3 * u + 2].z);
                sts64(dz + 768 * u, z2, z2);
            }
            mbar_arrive(sb + BAR_KVR);
        }
#pragma unroll 1
        for (int c = 0; c < 3; c++) {
            fetch_tagged(cs + 384 + 128 * c + 64 * a, sb + OFF_CS3 + (32 * c + lane) * 16 + 8 * a, epoch);
            mbar_arrive(sb + BAR_CSG + 8 * c);
            TL(45 + c, lane == 0 && a == 0);
        }
        {
            uint32_t it = 0;
            while (__any_sync(0xffffffffu, (int)(readback(g_flag + (m * 5 + 1) * 32) - epoch * 64) < 0)) {
                __nanosleep(200);
                trap_if_gt(++it, 1u << 22);
            }
#pragma unroll 1
            for (int rr = 0; rr < 2; rr++) {
                const int row = 64 * rr + 32 * a + lane;
                const unsigned long long* hs = g_hstat + (1024 * m + row) * 2;
                uint4 v[8];
                bool bad;
                do {
                    bad = false;
#pragma unroll
                    for (int i = 0; i < 8; i++) v[i] = ld_tagged_rlx(hs + 256 * i);
#pragma unroll
                    for (int i = 0; i < 8; i++) bad |= v[i].y != epoch || v[i].w != epoch;
                    trap_if_gt(++it, 1u << 22);
                } while (__any_sync(0xffffffffu, bad));
                float mean = 0.f;
#pragma unroll
                for (int i = 0; i < 8; i++) mean += __uint_as_float(v[i].x);
                mean *= 0.125f;
                float m2 = 0.f, dv = 0.f;
#pragma unroll
                for (int i = 0; i < 8; i++) { const float d = __uint_as_float(v[i].x) - mean; m2 += __uint_as_float(v[i].z); dv = fmaf(d, d, dv); }
                sts_f2(sb + OFF_CS1 + row * 8, -mean, rcp(fmaf(dv, 64.f, m2) * (1.f / DM) + 1e-5f));
            }
        }
        mbar_arrive(sb + BAR_CS3);
#pragma unroll 1
        for (int c = a; c < 3; c += 2) {
            mbar_wait(sb + BAR_STG + 8 * c, 0);
            if (elect_one()) {
                asm volatile("cp.async.bulk.global.shared::cta.bulk_group [%0], [%1], %2;" ::"l"(g_act + ((2 + c) * 128 + role) * 1024), "r"(sb + OFF_B + 4 * SLOT), "r"(SLOT) : "memory");
                asm volatile("cp.async.bulk.commit_group;" ::: "memory");
                asm volatile("cp.async.bulk.wait_group.read 0;" ::: "memory");
                mbar_arrive(sb + BAR_FULLB + 8 * 4);
                asm volatile("cp.async.bulk.wait_group 0;" ::: "memory");
            }
            __syncwarp();
            TL(60 + c, lane == 0);
            uint32_t ack = 0;
            const uint4* rb = g_act + ((2 + c) * 128 + role) * 1024 + lane * 8;
#pragma unroll
            for (int i = 0; i < 4; i++) ack |= readback(rb + 256 * i);
            signal_after(g_flag + (m * 5 + 2 + c) * 32, ack, P.zero, lane == 0);
            TL(54 + c, lane == 0);
        }
        return;
    }
    const unsigned epoch = ld_relaxed(&g_epoch);
    uint32_t wraw[16];
    if (!helper) {
        const uint32_t* wp = reinterpret_cast<const uint32_t*>(P.wphi) + (4 * j) * 128 + (lane & 3) * 16 + (lane >> 2);
#pragma unroll
        for (int i = 0; i < 16; i++)
            asm volatile("ld.global.nc.u32 %0, [%1];" : "=r"(wraw[i]) : "l"(wp + (i >> 2) * 128 + ((i >> 1) & 1) * 64 + (i & 1) * 8));
    }
    asm volatile("barrier.cluster.arrive.relaxed.aligned;" ::: "memory");
    asm volatile("setmaxnreg.inc.sync.aligned.u32 216;");
    bar_sync(0, NTHREADS);
    if (helper) {
        const int w = warp >> 2;
        sts64(sb + OFF_B + 8 * tid, 0x3f803f80u, 0x3f803f80u);
        fence_async_smem();
        uint32_t zack[6];
        {
            float* z = g_acc + 2 * j * ACC_SIZE + 4 * tid;
#pragma unroll
            for (int u = 0; u < 6; u++) stg128(z + 1024 * u, 0, 0, 0, 0);
#pragma unroll
            for (int u = 0; u < 6; u++) zack[u] = readback(z + 1024 * u);
        }
        bar_sync(1, 256);
        TL(70, tid == 0);
        float acc[8];
        int i = w;
#pragma unroll 1
        for (int job = 0; job < 6; job++) {
            const int n = job < 3 ? 4 : 8;
#pragma unroll 1
            for (int t = 0; t < n; t++, i += 2) {
                mbar_waitc(sb + BAR_FULLA + 8 * (i & 7), (i >> 3) & 1);
                const desc_t da = desc_lo(sb + OFF_A) + (i & 7) * (SLOT >> 4);
                wg_fence();
#pragma unroll
                for (int k = 0; k < 8; k++) wgmma_n8_tt(acc + (k & 4), da + 128 * k, desc_lo(sb + OFF_B), (t | (k & 3)) != 0);
                wg_commit();
                wg_wait<0>();
                mbar_arrive_n_if(sb + BAR_EMPTYA + 8 * (i & 7), 2, lane == 0);
            }
            fence_acc<8>(acc);
            TL(71 + job, tid == 0);
            if (job == 1) {
                asm volatile("{.reg .pred p; .reg .b32 t; lop3.b32 t, %0, %1, %2, 0xfe; lop3.b32 t, t, %3, %4, 0xfe; or.b32 t, t, %5; setp.ne.u32 p, t, 0; @p trap;}"
                             ::"r"(zack[0]), "r"(zack[1]), "r"(zack[2]), "r"(zack[3]), "r"(zack[4]), "r"(zack[5]));
                bar_sync(1, 256);
            }
            const int q = lane & 3;
            const float lo = (q & 1) ? acc[2] : acc[0], hi = (q & 1) ? acc[6] : acc[4];
            const float v = job < 3 ? lo + hi : ((q & 2) ? hi : lo);
            unsigned long long* dst = g_cs + ((2 * j + w) * 6 + job) * 128 + (q >> 1) * 64 + 16 * (warp & 3) + 8 * (q & 1) + (lane >> 2);
            asm volatile("st.relaxed.gpu.global.b64 [%0], %1;" ::"l"(dst), "l"(((unsigned long long)epoch << 32) | __float_as_uint(v)) : "memory");
        }
        return;
    }
    {
        const int w = warp >> 2, wv = warp & 3, g = lane >> 2, q = lane & 3;
        const uint32_t sa = sb + OFF_A + w * 8192;
        const desc_t dA = desc_lo(sa), dB = desc_lo(sb + OFF_B);
        unsigned* const flag_m = g_flag + m * 160;
        const bool l0 = lane == 0, l2 = lane < 2;
        const uint32_t eb = mapa(sb + BAR_EMPTYB, lane & 1);
        asm volatile("barrier.cluster.wait.aligned;" ::: "memory");
        Ring rg{0, 0};
        int prev = 0;

        uint32_t wb[16];
        constexpr float L2E = 1.4426950408889634f;
        const int ch = lane >> 4, sw = lane & 7;
        const uint32_t lrow = (lane & 15) * 128;
        uint32_t fp[16], fm[16];
        const int vs = j < 2 ? 2 : 0;
        {
            float acc[64];
#pragma unroll 1
            for (int kt = 0; kt < 8; kt++) {
                mbar_waitc(sb + BAR_FULLA + 8 * kt, 0);
                mbar_waitc(sb + BAR_FULLB + 8 * rg.slot, rg.phase);
                const desc_t da = dA + kt * (SLOT >> 4), db = dB + rg.slot * (SLOT >> 4);
                wg_fence();
#pragma unroll
                for (int k = 0; k < 4; k++) wgmma_n128(acc, da + 2 * k, db + 128 * k, (kt | k) != 0);
                wg_commit();
                wg_wait<1>();
                mbar_arrive_cl_if(eb + 8 * prev, l2 && kt > 0);
                prev = rg.slot; rg.adv();
            }
#pragma unroll
            for (int i = 0; i < 8; i++) {
                wb[(i >> 1) * 4 + (i & 1)] = __byte_perm(wraw[2 * i], wraw[2 * i + 1], 0x5410);
                wb[(i >> 1) * 4 + 2 + (i & 1)] = __byte_perm(wraw[2 * i], wraw[2 * i + 1], 0x7632);
            }
            uint32_t a[16];
            float accq[32];
            mbar_waitc(sb + BAR_FULLB + 8 * 2, 1);
            wg_fence();
#pragma unroll
            for (int k = 0; k < 8; k++) wgmma_n64(accq, dA + (vs + (k >> 2)) * (SLOT >> 4) + (k & 3) * 2, dB + 2 * (SLOT >> 4) + 128 * k, k != 0);
            wg_commit();
            wg_wait<1>();
            fence_acc<64>(acc);
            mbar_arrive_cl_if(eb + 8 * prev, l2);
            TL(17, tid == 0);
            mbar_waitc(sb + BAR_CS1, 0);
            const float2 s0 = lds_f2(sb + OFF_XST + (16 * warp + g) * 8), s1 = lds_f2(sb + OFF_XST + (16 * warp + g + 8) * 8);
            wg_wait<0>();
            fence_acc<32>(accq);
            mbar_arrive_cl_if(eb + 8 * 2, l2);
            TL(2, tid == 0);
            const uint32_t st = sb + OFF_B + warp * 2048 + lrow;
#pragma unroll
            for (int hh = 0; hh < 4; hh++)
                ln_frag<false>(acc + 8 * hh, sb + OFF_CS1 + (64 + 16 * hh + 2 * q) * 4, 0.f, s0.y, 0.f, s1.y, a + 4 * hh);
#pragma unroll 1
            for (int it = 0; it < 2; it++) {
                feature_maps(a, wb, s0.x * L2E, s1.x * L2E, fp, fm);
                if (it == 0) {
                    mbar_waitc(sb + BAR_FULLB + 8 * 3, 1); mbar_waitc(sb + BAR_FULLB + 8 * 4, 1);
                    mbar_waitc(sb + BAR_CSV, 0);
                    const uint32_t sv = sb + OFF_A + vs * SLOT + warp * 2048 + lrow;
#pragma unroll
                    for (int hh = 0; hh < 4; hh++) {
                        stsm4(st + (3 + (hh >> 1)) * SLOT + (((4 * (hh & 1) + ch) ^ sw) << 4), fp[4 * hh], fp[4 * hh + 1], fp[4 * hh + 2], fp[4 * hh + 3]);
                        stsm4(st + (3 + (hh >> 1)) * SLOT + (((4 * (hh & 1) + 2 + ch) ^ sw) << 4), fm[4 * hh], fm[4 * hh + 1], fm[4 * hh + 2], fm[4 * hh + 3]);
                        ln_frag<true>(acc + 32 + 8 * hh, sb + OFF_CS1 + (128 + 16 * hh + 2 * q) * 4, s0.x, s0.y, s1.x, s1.y, a);
                        stsm4(sv + (hh >> 1) * SLOT + (((2 * (hh & 1) + ch) ^ sw) << 4), a[0], a[1], a[2], a[3]);
                    }
                    stsm4(sv + ch * SLOT + ((4 ^ sw) << 4), 0x3f803f80u, 0x3f803f80u, 0x3f803f80u, 0x3f803f80u);
                    fence_async_smem();
                    bar_sync(1, 256);
                    float kvd[20];
                    wg_fence();
#pragma unroll
                    for (int k = 0; k < 8; k++)
                        wgmma_n40_tt(kvd, dB + (3 + w) * (SLOT >> 4) + 128 * k, desc_lo(sb + OFF_A) + (vs + w) * (SLOT >> 4) + 128 * k, k != 0);
                    wg_commit();
                    wg_wait<0>();
                    fence_acc<20>(kvd);
                    mbar_arrive_cl_if(eb + 8 * (3 + (lane >> 1)), lane < 4);
                    const bool h1 = wv >= 2;
                    float* kvp = acc_j + 4 * tid;
                    red_f32x4(kvp, h1 ? kvd[8] : kvd[0], h1 ? kvd[9] : kvd[1], h1 ? kvd[10] : kvd[2], 1.f);
                    red_f32x4(kvp + 1024, h1 ? kvd[12] : kvd[4], h1 ? kvd[13] : kvd[5], h1 ? kvd[11] : kvd[3], 1.f);
                    red_f32x4(kvp + 2048, h1 ? kvd[14] : kvd[6], h1 ? kvd[15] : kvd[7], (q & 1) ? kvd[18] : kvd[16], 1.f);
                    mbar_arrive_if(sb + BAR_KVW, l0);
                    TL(3, tid == 0);
#pragma unroll 1
                    for (int b = 1; b < 4; b++) {
                        const int slot = b == 1 ? 5 : b - 2;
                        mbar_waitc(sb + BAR_FULLB + 8 * slot, b == 1);
                        const desc_t da = dA + (b == 1 ? 2 - vs : 2 * b) * (SLOT >> 4), db = dB + slot * (SLOT >> 4);
                        wg_fence();
#pragma unroll
                        for (int k = 0; k < 8; k++) wgmma_n64(accq, da + (k >> 2) * (SLOT >> 4) + (k & 3) * 2, db + 128 * k, 1);
                        wg_commit();
                    }
                    mbar_waitc(sb + BAR_CSQ, 0);
                    wg_wait<0>();
                    fence_acc<32>(accq);
                    mbar_arrive_cl_if(eb + 8 * ((5 + (lane >> 1)) % 6), lane < 6);
                    TL(4, tid == 0);
#pragma unroll
                    for (int hh = 0; hh < 4; hh++)
                        ln_frag<false>(accq + 8 * hh, sb + OFF_CS1 + (16 * hh + 2 * q) * 4, 0.f, s0.y, 0.f, s1.y, a + 4 * hh);
                }
            }
        }
        uint32_t res_lo[8], res_hi[8], ack[4];
        const uint32_t own_rows = sb + OFF_A + j * SLOT + warp * 2048;
#pragma unroll
        for (int b = 0; b < 4; b++)
            ldsm4(own_rows + lrow + (((2 * b + ch) ^ sw) << 4), res_lo[2 * b], res_hi[2 * b], res_lo[2 * b + 1], res_hi[2 * b + 1]);
        mbar_arrive_if(sb + BAR_EMPTYA + 8 * lane, lane < 8 && lane != j && lane != vs);
        TL(5, tid == 0);
        mbar_waitc(sb + BAR_KVR, 0);
        TL(6, tid == 0);
        {
            const uint32_t kvs = sb + OFF_A + vs * SLOT;
            uint32_t o_lo[8], o_hi[8];
#pragma unroll
            for (int hh = 0; hh < 4; hh++) {
                uint32_t b[8], zb[4];
                const uint32_t base = kvs + hh * 32 * 48;
                ldsm4t(base + (lane & 15) * 48 + (lane >> 4) * 16, b[0], b[1], b[2], b[3]);
                ldsm4t(base + (16 + (lane & 15)) * 48 + (lane >> 4) * 16, b[4], b[5], b[6], b[7]);
                ldsm4t(base + lane * 48 + 32, zb[0], zb[1], zb[2], zb[3]);
                float n0[4], n1[4], dn[4];
                mma16816_z(n0, fp + 4 * hh, b[0], b[1]); mma16816_z(n1, fp + 4 * hh, b[2], b[3]); mma16816_z(dn, fp + 4 * hh, zb[0], zb[1]);
                mma16816(n0, fm + 4 * hh, b[4], b[5]); mma16816(n1, fm + 4 * hh, b[6], b[7]); mma16816(dn, fm + 4 * hh, zb[2], zb[3]);
                const float i0 = rcp(dn[0] + 1e-6f), i1 = rcp(dn[2] + 1e-6f);
                o_lo[2 * hh] = pack_bf16(n0[0] * i0, n0[1] * i0); o_hi[2 * hh] = pack_bf16(n0[2] * i1, n0[3] * i1);
                o_lo[2 * hh + 1] = pack_bf16(n1[0] * i0, n1[1] * i0); o_hi[2 * hh + 1] = pack_bf16(n1[2] * i1, n1[3] * i1);
            }
            __syncwarp();
            mbar_arrive_if(sb + BAR_EMPTYA + 8 * vs, l0);
            rg.slot = 2; rg.phase = 0;
            store_tile(own_rows, g_act + role * 1024 + warp * 128 + lane, o_lo, o_hi, lane, ack);
            TL(7, tid == 0);
        }
        float acch[32];
        {
            float* acc = acch;
#pragma unroll
            for (int t = 0; t < 8; t++) {
                acc[4 * t] = bf_lo(res_lo[t]); acc[4 * t + 1] = bf_hi(res_lo[t]);
                acc[4 * t + 2] = bf_lo(res_hi[t]); acc[4 * t + 3] = bf_hi(res_hi[t]);
            }
            fence_acc<32>(acc);
            int pa = 0;
#pragma unroll 1
            for (int kp = 0; kp < 4; kp++) {
                mbar_waitc(sb + BAR_FULLB + 8 * rg.slot, rg.phase);
#pragma unroll
                for (int hf = 0; hf < 2; hf++) {
                    const int i = 2 * kp + hf, kt = KORD(i, j);
                    mbar_waitc(sb + BAR_FULLA + 8 * kt, i != 0);
                    TL(8, i == 1 && tid == 0);
                    const desc_t da = dA + kt * (SLOT >> 4), db = dB + rg.slot * (SLOT >> 4);
                    wg_fence();
#pragma unroll
                    for (int k = 0; k < 4; k++) wgmma_n64(acc, da + 2 * k, db + (hf * 4 + k) * 128, 1);
                    wg_commit();
                    wg_wait<1>();
                    mbar_arrive_if(sb + BAR_EMPTYA + 8 * pa, l0 && i > 1);
                    if (hf == 0) {
                        mbar_arrive_cl_if(eb + 8 * prev, l2 && i > 0);
                        if (i == 0) { signal_late(flag_m, ack, P.zero, l0); TL(20, tid == 0); }
                    }
                    pa = kt;
                }
                prev = rg.slot; rg.adv();
            }
            wg_wait<0>();
            fence_acc<32>(acc);
            mbar_arrive_if(sb + BAR_EMPTYA + 8 * pa, l0);
            mbar_arrive_cl_if(eb + 8 * prev, l2);
            TL(9, tid == 0);
#pragma unroll
            for (int t = 0; t < 8; t++) {
                res_lo[t] = pack_bf16(acc[4 * t], acc[4 * t + 1]);
                res_hi[t] = pack_bf16(acc[4 * t + 2], acc[4 * t + 3]);
            }
            store_tile(own_rows, g_act + (128 + role) * 1024 + warp * 128 + lane, res_lo, res_hi, lane, ack);
            TL(10, tid == 0);
        }
        float acc0[64], acc1[64], acc2[56], nm0, nm1;
        float4 cs[8];
        uint32_t hr[16];
#define P3_GROUP(MMA, ACC, KT)                                                                              \
        mbar_waitc(sb + BAR_FULLB + 8 * rg.slot, rg.phase);                                                 \
        {                                                                                                   \
            const desc_t da = dA + (KT) * (SLOT >> 4), db = dB + rg.slot * (SLOT >> 4);                     \
            wg_fence();                                                                                     \
            _Pragma("unroll") for (int k = 0; k < 4; k++) MMA(ACC, da + 2 * k, db + 128 * k, (i | k) != 0); \
            wg_commit();                                                                                    \
        }
#define P3_CS(C, NT)    \
        _Pragma("unroll") for (int t = 0; t < (NT); t++) lds_f4_if(cs[t], sb + OFF_CS3 + q * 16 + 512 * (C) + 64 * t, i == t);
#define P3_EPI2(C, ACC)                                                                                     \
        if (i == 0) {                                                                                       \
            fence_acc<64>(ACC);                                                                             \
            if (C) mbar_waitc(sb + BAR_FULLB + 8 * 4, 1);                                                   \
            hh_stage2<0, 2>(ACC, cs, nm0, nm1, stg, lane);                                                  \
            mbar_waitc(sb + BAR_CSG + 8 * (C) + 8, 0);                                                      \
        }                                                                                                   \
        if (i == 1) {                                                                                       \
            hh_stage2<2, 4>(ACC, cs, nm0, nm1, stg, lane);                                                  \
            fence_async_smem();                                                                             \
            __syncwarp();                                                                                   \
            mbar_arrive_if(sb + BAR_STG + 8 * (C), l0);                                                     \
        }
#define P3_EPI(C, ACC, N, NTP)                                                                              \
        fence_acc<N>(ACC);                                                                                  \
        TL(11 + (C), tid == 0);                                                                             \
        hh_stage<NTP>(ACC, cs, nm0, nm1, sb + OFF_B + 4 * SLOT + warp * 2048, lane);                        \
        mbar_arrive_if(sb + BAR_STG + 8 * (C), l0);                                                         \
        TL(50 + (C), tid == 0);
        const uint32_t stg = sb + OFF_B + 4 * SLOT + warp * 2048;
        const uint32_t blk = ((lane & 7) + (lane >> 4) * 8) * 128 + (((2 * wv + ((lane >> 3) & 1)) ^ (lane & 7)) << 4);
#pragma unroll 1
        for (int i = 0; i < 8; i++) {
            const int kt = KORD(i, j);
            mbar_waitc(sb + BAR_FULLA + 8 * kt, 0);
            TL(44, tid == 0 && i == 1);
            P3_GROUP(wgmma_n128, acc0, kt)
            if (i == 7) {
                mbar_waitc(sb + BAR_CS3, 0);
                nm0 = lds_f2(sb + OFF_CS1 + (16 * warp + g) * 8).x; nm1 = lds_f2(sb + OFF_CS1 + (16 * warp + g + 8) * 8).x;
            }
            wg_wait<1>();
            mbar_arrive_cl_if(eb + 8 * prev, l2 && i > 0);
            if (i == 0) {
                signal_late(flag_m + 32, ack, P.zero, l0);
                TL(21, tid == 0);
                {
                    fence_acc<32>(acch);
                    const float* acc = acch;
                    float s0 = 0.f, s1 = 0.f;
#pragma unroll
                    for (int t = 0; t < 8; t++) { s0 += acc[4 * t] + acc[4 * t + 1]; s1 += acc[4 * t + 2] + acc[4 * t + 3]; }
            s0 += __shfl_xor_sync(0xffffffffu, s0, 1); s1 += __shfl_xor_sync(0xffffffffu, s1, 1);
            s0 += __shfl_xor_sync(0xffffffffu, s0, 2); s1 += __shfl_xor_sync(0xffffffffu, s1, 2);
            const float mu0 = s0 * (1.f / 64), mu1 = s1 * (1.f / 64);
            float q0 = 0.f, q1 = 0.f;
#pragma unroll
            for (int t = 0; t < 8; t++) {
                float d;
                d = acc[4 * t] - mu0; q0 = fmaf(d, d, q0);
                d = acc[4 * t + 1] - mu0; q0 = fmaf(d, d, q0);
                d = acc[4 * t + 2] - mu1; q1 = fmaf(d, d, q1);
                d = acc[4 * t + 3] - mu1; q1 = fmaf(d, d, q1);
            }
            q0 += __shfl_xor_sync(0xffffffffu, q0, 1); q1 += __shfl_xor_sync(0xffffffffu, q1, 1);
            q0 += __shfl_xor_sync(0xffffffffu, q0, 2); q1 += __shfl_xor_sync(0xffffffffu, q1, 2);
            st_tagged_if(g_hstat + (role * 128 + 16 * warp + g + 8 * (q & 1)) * 2, q ? mu1 : mu0, q ? q1 : q0, epoch, q < 2);
                }
                bar_sync(2 + w, 128);
#pragma unroll
                for (int tp = 0; tp < 4; tp++) ldsm4t(sa + j * SLOT + blk + tp * 2048, hr[4 * tp], hr[4 * tp + 1], hr[4 * tp + 2], hr[4 * tp + 3]);
                mbar_waitc(sb + BAR_CSG, 0);
#pragma unroll
                for (int t = 0; t < 8; t++) cs[t] = lds_f4(sb + OFF_CS3 + q * 16 + 64 * t);
            }
            prev = rg.slot; rg.adv5();
        }
#pragma unroll 1
        for (int i = 0; i < 8; i++) {
            P3_GROUP(wgmma_n128, acc1, i)
            wg_wait<1>();
            mbar_arrive_cl_if(eb + 8 * prev, l2);
            P3_EPI2(0, acc0)
            P3_CS(1, 8)
            prev = rg.slot; rg.adv5();
        }
#pragma unroll 1
        for (int i = 0; i < 8; i++) {
            P3_GROUP(wgmma_n112, acc2, i)
            wg_wait<1>();
            mbar_arrive_cl_if(eb + 8 * prev, l2);
            mbar_arrive_if(sb + BAR_EMPTYA + 8 * ((i + 7) & 7), l0 && i > 0);
            if (i == 0) { mbar_waitc(sb + BAR_FULLB + 8 * 4, 1); P3_EPI(1, acc1, 64, 4) mbar_waitc(sb + BAR_CSG + 16, 0); }
            P3_CS(2, 6)
            prev = rg.slot; rg.adv5();
        }
        mbar_waitc(sb + BAR_FULLB + 8 * 4, 0);
        wg_wait<0>();
        mbar_arrive_cl_if(eb + 8 * prev, l2);
        mbar_arrive_if(sb + BAR_EMPTYA + 8 * 7, l0);
        P3_EPI(2, acc2, 56, 3)
        {
            float acc[64];
            const desc_t dA0 = desc_lo(sb + OFF_A);
#define KT_P4(I, NK)                                                                                        \
        const int s_ = (2 * (I) + w) & 7;                                                                   \
        mbar_waitc(sb + BAR_FULLB + 8 * rg.slot, rg.phase);                                                 \
        mbar_waitc(sb + BAR_FULLA + 8 * s_, (((I) >> 2) + 1) & 1);                                          \
        const desc_t dh_ = dA0 + s_ * (SLOT >> 4), dw_ = dB + rg.slot * (SLOT >> 4) + w * 512;              \
        wg_fence();                                                                                         \
        _Pragma("unroll") for (int k = 0; k < (NK); k++) wgmma_n128_tn(acc, dw_ + 128 * k, dh_ + 2 * k, ((I) | k) != 0); \
        wg_commit();                                                                                        \
        wg_wait<1>();
#pragma unroll 1
            for (int i = 0; i < 8; i++) {
                KT_P4(i, 4)
                mbar_arrive_n_if(sb + BAR_EMPTYA + 8 * ((s_ + 6) & 7), 2, l0 && i > 0);
                mbar_arrive_cl_if(eb + 8 * prev, l2 && i > 0);
#pragma unroll
                for (int t = 0; t < 8; t++) lds_f4_if(cs[t], sb + OFF_CS1 + (64 * w + 8 * t + 2 * q) * 8, i == t);
                prev = rg.slot; rg.adv5();
            }
#pragma unroll 1
            for (int i = 8; i < 12; i++) {
                KT_P4(i, 3)
                mbar_arrive_n_if(sb + BAR_EMPTYA + 8 * ((s_ + 6) & 7), 2, l0);
                rg.adv5();
            }
            wg_wait<0>();
            fence_acc<64>(acc);
            TL(15, tid == 0);
            const uint32_t xch = sb + OFF_A + 2 * SLOT + (tid & 127) * 16;
            if (w) {
#pragma unroll
                for (int t = 0; t < 8; t++) {
                    sts128(xch + SLOT + t * 2048, __float_as_uint(acc[4 * t]), __float_as_uint(acc[4 * t + 1]),
                           __float_as_uint(acc[4 * t + 2]), __float_as_uint(acc[4 * t + 3]));
                }
#pragma unroll
                for (int t = 0; t < 32; t++) acc[t] = acc[32 + t];
            } else {
#pragma unroll
                for (int t = 0; t < 8; t++)
                    sts128(xch + t * 2048, __float_as_uint(acc[32 + 4 * t]), __float_as_uint(acc[33 + 4 * t]),
                           __float_as_uint(acc[34 + 4 * t]), __float_as_uint(acc[35 + 4 * t]));
            }
            bar_sync(1, 256);
            float4 o[8];
#pragma unroll
            for (int t = 0; t < 8; t++) o[t] = lds_f4(xch + (w ^ 1) * SLOT + t * 2048);
            const uint32_t tile = sb + OFF_A + w * SLOT;
#pragma unroll
            for (int t = 0; t < 8; t++) {
                hr[2 * t] = pack_bf16(fmaf(acc[4 * t] + o[t].x, cs[t].y, bf_lo(hr[2 * t])), fmaf(acc[4 * t + 1] + o[t].y, cs[t].w, bf_hi(hr[2 * t])));
                hr[2 * t + 1] = pack_bf16(fmaf(acc[4 * t + 2] + o[t].z, cs[t].y, bf_lo(hr[2 * t + 1])), fmaf(acc[4 * t + 3] + o[t].w, cs[t].w, bf_hi(hr[2 * t + 1])));
            }
#pragma unroll
            for (int tp = 0; tp < 4; tp++) stsm4t(tile + blk + tp * 2048, hr[4 * tp], hr[4 * tp + 1], hr[4 * tp + 2], hr[4 * tp + 3]);
            fence_async_smem();
            bar_sync(2 + w, 128);
            if ((tid & 127) == 0) {
                tma_store2d(&P.tout, tile, 64 * j, 128 * m + 64 * w);
                asm volatile("cp.async.bulk.wait_group.read 0;" ::: "memory");
            }
            if (tid == 0 && role == 0) g_epoch = epoch + 1;
            TL(16, tid == 0); TLG(1, tid == 0);
        }
    }
}

typedef CUresult (*EncodeFn)(CUtensorMap*, CUtensorMapDataType, cuuint32_t, void*, const cuuint64_t*, const cuuint64_t*,
                             const cuuint32_t*, const cuuint32_t*, CUtensorMapInterleave, CUtensorMapSwizzle,
                             CUtensorMapL2promotion, CUtensorMapFloatOOBfill);

static void make_map2d(EncodeFn enc, CUtensorMap* tm, const void* base, uint64_t cols, uint64_t rows, uint64_t pitch_elems,
                       uint32_t box_rows) {
    cuuint64_t gd[2] = {cols, rows};
    cuuint64_t gs[1] = {pitch_elems * 2};
    cuuint32_t bd[2] = {64, box_rows};
    cuuint32_t es[2] = {1, 1};
    enc(tm, CU_TENSOR_MAP_DATA_TYPE_BFLOAT16, 2, const_cast<void*>(base), gd, gs, bd, es, CU_TENSOR_MAP_INTERLEAVE_NONE,
        CU_TENSOR_MAP_SWIZZLE_128B, CU_TENSOR_MAP_L2_PROMOTION_L2_256B, CU_TENSOR_MAP_FLOAT_OOB_FILL_NONE);
}

}

extern "C" void kernel_launch(void* const* d_in, const int* in_sizes, int n_in, void* d_out, int out_size) {
    using namespace hk;
    (void)in_sizes; (void)n_in; (void)out_size;
    static EncodeFn enc = nullptr;
    if (!enc) {
        void* fn = nullptr;
        cudaDriverEntryPointQueryResult qr;
        cudaGetDriverEntryPoint("cuTensorMapEncodeTiled", &fn, cudaEnableDefault, &qr);
        enc = (EncodeFn)fn;
        cudaFuncSetAttribute(fused_kernel, cudaFuncAttributeMaxDynamicSharedMemorySize, SMEM_BYTES);
    }
    Params P;
    const __nv_bfloat16* x = (const __nv_bfloat16*)d_in[0];
    P.x = x;
    P.wqkv = (const __nv_bfloat16*)d_in[1];
    P.wphi = (const __nv_bfloat16*)d_in[2];
    P.wo = (const __nv_bfloat16*)d_in[3];
    P.wg = (const __nv_bfloat16*)d_in[5];
    P.wu = (const __nv_bfloat16*)d_in[6];
    P.wd = (const __nv_bfloat16*)d_in[7];
    P.out = (__nv_bfloat16*)d_out;
    P.zero = 0;
    make_map2d(enc, &P.tx, x, DM, SEQ, DM, 128);
    make_map2d(enc, &P.twq, P.wqkv, 3 * DM, DM, 3 * DM, 64);
    make_map2d(enc, &P.two, P.wo, DM, DM, DM, 64);
    make_map2d(enc, &P.twg, P.wg, FF, DM, FF, 64);
    make_map2d(enc, &P.twu, P.wu, FF, DM, FF, 64);
    make_map2d(enc, &P.twd, P.wd, DM, FF, DM, 64);
    make_map2d(enc, &P.tout, d_out, DM, SEQ, DM, 64);
    fused_kernel<<<NCTA, NTHREADS, SMEM_BYTES>>>(P);
}
```

```cpp
#include <cuda_runtime.h>
#include <cuda_bf16.h>
#include <cuda.h>
#include <stdint.h>

namespace hk {

constexpr int SEQ = 2048, DM = 512, FF = 1376;
constexpr int NCTA = 132;
constexpr int NTHREADS = 384;
constexpr uint32_t SLOT = 16384;
constexpr uint32_t OFF_A = 0, OFF_B = 8 * SLOT, OFF_MISC = 14 * SLOT;
constexpr uint32_t BAR_FULLA = OFF_MISC + 0, BAR_EMPTYA = OFF_MISC + 64, BAR_FULLB = OFF_MISC + 128,
                   BAR_EMPTYB = OFF_MISC + 176, BAR_CS1 = OFF_MISC + 224, BAR_CS3 = OFF_MISC + 232,
                   BAR_CSQ = OFF_MISC + 240, BAR_CSV = OFF_MISC + 248,
                   BAR_STG = OFF_MISC + 256,
                   BAR_KVW = OFF_MISC + 280, BAR_KVR = OFF_MISC + 288, BAR_CSG = OFF_MISC + 296;
constexpr uint32_t OFF_CS1 = OFF_MISC + 384;
constexpr uint32_t OFF_CS3 = OFF_CS1 + 1024;
constexpr uint32_t OFF_XST = OFF_CS3;
constexpr uint32_t SMEM_BYTES = OFF_CS3 + 1536;
#define KORD(i, j) ((i) == 0 ? (j) : (i) - ((i) <= (j)))
constexpr int NB = 6;
#define PF_DELAY 2
#define KV_POLL 1
#define NPRE 3
#define AHEAD 3

constexpr int ACC_SIZE = 3 * 256 * 4;

__device__ __align__(1024) uint4 g_act[5 * 128 * 1024];
__device__ __align__(128) unsigned long long g_hstat[SEQ * 16];
__device__ __align__(128) unsigned long long g_xstat[SEQ * 2];
__device__ __align__(128) float g_acc[8 * ACC_SIZE];
__device__ __align__(128) unsigned long long g_cs[8 * 6 * 128];
__device__ __align__(128) unsigned g_flag[16 * 5 * 32 + 32];
__device__ unsigned g_epoch = 1;

#define TL(i, pred) do {} while (0)
#define TLG(i, pred) do {} while (0)

struct Params {
    CUtensorMap tx, twq, two, twg, twu, twd, twd48, tout;
    const __nv_bfloat16 *x, *wqkv, *wphi, *wo, *wg, *wu, *wd;
    __nv_bfloat16* out;
    unsigned zero;
};

__device__ __forceinline__ uint32_t smem_u32(const void* p) { return (uint32_t)__cvta_generic_to_shared(p); }
__device__ __forceinline__ void mbar_init(uint32_t bar, uint32_t cnt) {
    asm volatile("mbarrier.init.shared::cta.b64 [%0], %1;" ::"r"(bar), "r"(cnt) : "memory");
}
__device__ __forceinline__ void mbar_expect_tx(uint32_t bar, uint32_t bytes) {
    asm volatile("mbarrier.arrive.expect_tx.shared::cta.b64 _, [%0], %1;" ::"r"(bar), "r"(bytes) : "memory");
}
__device__ __forceinline__ void mbar_arrive(uint32_t bar) {
    asm volatile("mbarrier.arrive.shared::cta.b64 _, [%0];" ::"r"(bar) : "memory");
}
__device__ __forceinline__ void mbar_arrive_if(uint32_t bar, bool pred) {
    asm volatile("{.reg .pred p; setp.ne.u32 p, %1, 0; @p mbarrier.arrive.shared::cta.b64 _, [%0];}" ::"r"(bar), "r"((uint32_t)pred) : "memory");
}
__device__ __forceinline__ bool mbar_try(uint32_t bar, uint32_t parity) {
    uint32_t ok;
    asm volatile("{.reg .pred p; mbarrier.try_wait.parity.shared::cta.b64 p, [%1], %2; selp.u32 %0,1,0,p;}"
                 : "=r"(ok) : "r"(bar), "r"(parity) : "memory");
    return ok;
}
__device__ __forceinline__ bool mbar_test(uint32_t bar, uint32_t parity) {
    uint32_t ok;
    asm volatile("{.reg .pred p; mbarrier.test_wait.parity.shared::cta.b64 p, [%1], %2; selp.u32 %0,1,0,p;}"
                 : "=r"(ok) : "r"(bar), "r"(parity) : "memory");
    return ok;
}
__device__ __forceinline__ void trap_if_gt(uint32_t v, uint32_t lim) {
    asm volatile("{.reg .pred p; setp.gt.u32 p, %0, %1; @p trap;}" ::"r"(v), "r"(lim));
}
__device__ __forceinline__ void mbar_wait(uint32_t bar, uint32_t parity) {
    asm volatile("{\n"
                 ".reg .pred P1, P2;\n"
                 ".reg .u32 c;\n"
                 "mov.u32 c, 0;\n"
                 "LAB_WAIT:\n"
                 "mbarrier.try_wait.parity.shared::cta.b64 P1, [%0], %1;\n"
                 "@P1 bra LAB_DONE;\n"
                 "add.u32 c, c, 1;\n"
                 "setp.gt.u32 P2, c, 4194304;\n"
                 "@P2 trap;\n"
                 "bra LAB_WAIT;\n"
                 "LAB_DONE:\n"
                 "}" ::"r"(bar), "r"(parity) : "memory");
}
__device__ __forceinline__ void mbar_waitc(uint32_t bar, uint32_t parity) {
    asm volatile("{\n"
                 ".reg .pred P1;\n"
                 "LAB_WAIT:\n"
                 "mbarrier.try_wait.parity.shared::cta.b64 P1, [%0], %1;\n"
                 "@!P1 bra LAB_WAIT;\n"
                 "}" ::"r"(bar), "r"(parity) : "memory");
}
__device__ __forceinline__ void tma2d(uint32_t dst, const CUtensorMap* tm, uint32_t bar, int c0, int c1) {
    asm volatile("cp.async.bulk.tensor.2d.shared::cluster.global.mbarrier::complete_tx::bytes [%0], [%1, {%3, %4}], [%2];"
                 ::"r"(dst), "l"(tm), "r"(bar), "r"(c0), "r"(c1) : "memory");
}
__device__ __forceinline__ void tma2d_mc(uint32_t dst, const CUtensorMap* tm, uint32_t bar, int c0, int c1) {
    asm volatile("cp.async.bulk.tensor.2d.shared::cluster.global.mbarrier::complete_tx::bytes.multicast::cluster [%0], [%1, {%3, %4}], [%2], %5;"
                 ::"r"(dst), "l"(tm), "r"(bar), "r"(c0), "r"(c1), "h"((uint16_t)3) : "memory");
}
__device__ __forceinline__ uint32_t mapa(uint32_t addr, uint32_t rank) {
    uint32_t r; asm("mapa.shared::cluster.u32 %0, %1, %2;" : "=r"(r) : "r"(addr), "r"(rank)); return r;
}
__device__ __forceinline__ void mbar_arrive_cl_if(uint32_t cbar, bool pred) {
    asm volatile("{.reg .pred p; setp.ne.u32 p, %1, 0; @p mbarrier.arrive.shared::cluster.b64 _, [%0];}" ::"r"(cbar), "r"((uint32_t)pred) : "memory");
}
__device__ __forceinline__ bool elect_one() {
    uint32_t ok;
    asm volatile("{.reg .pred p; elect.sync _|p, 0xffffffff; selp.u32 %0, 1, 0, p;}" : "=r"(ok));
    return ok;
}
__device__ __forceinline__ void prefetch_tmap(const CUtensorMap* tm) {
    asm volatile("prefetch.tensormap [%0];" ::"l"(tm) : "memory");
}
__device__ __forceinline__ void prefetch_l2(const void* p, uint32_t bytes) {
    asm volatile("cp.async.bulk.prefetch.L2.global [%0], %1;" ::"l"(p), "r"(bytes) : "memory");
}
__device__ __forceinline__ unsigned ld_acquire(const unsigned* p) {
    unsigned v; asm volatile("ld.acquire.gpu.global.u32 %0, [%1];" : "=r"(v) : "l"(p) : "memory"); return v;
}
__device__ __forceinline__ uint4 ld_acquire4(const unsigned* p) {
    uint4 v;
    asm volatile("ld.acquire.gpu.global.v4.u32 {%0,%1,%2,%3}, [%4];" : "=r"(v.x), "=r"(v.y), "=r"(v.z), "=r"(v.w) : "l"(p) : "memory");
    return v;
}
__device__ __forceinline__ unsigned ld_relaxed(const unsigned* p) {
    unsigned v; asm volatile("ld.relaxed.gpu.global.u32 %0, [%1];" : "=r"(v) : "l"(p)); return v;
}
__device__ __forceinline__ void st_relaxed(unsigned* p, unsigned v) {
    asm volatile("st.relaxed.gpu.global.u32 [%0], %1;" ::"l"(p), "r"(v) : "memory");
}
__device__ __forceinline__ void red_relaxed(unsigned* p, unsigned v) {
    asm volatile("red.relaxed.gpu.global.add.u32 [%0], %1;" ::"l"(p), "r"(v) : "memory");
}
__device__ __forceinline__ void fence_gpu() { asm volatile("fence.acq_rel.gpu;" ::: "memory"); }
__device__ __forceinline__ void fence_async_smem() { asm volatile("fence.proxy.async.shared::cta;" ::: "memory"); }
__device__ __forceinline__ void fence_async_global() { asm volatile("fence.proxy.async.global;" ::: "memory"); }
__device__ __forceinline__ uint32_t readback(const void* p) {
    uint32_t v; asm volatile("ld.relaxed.gpu.global.u32 %0, [%1];" : "=r"(v) : "l"(p) : "memory"); return v;
}
__device__ __forceinline__ void wait_count(const unsigned* p, unsigned target) {
    uint32_t it = 0;
    while ((int)(readback(p) - target) < 0) trap_if_gt(++it, 1u << 22);
}
__device__ __forceinline__ void wait_count_warp(const unsigned* p, unsigned target) {
    uint32_t it = 0;
    while (__any_sync(0xffffffffu, (int)(readback(p) - target) < 0)) trap_if_gt(++it, 1u << 22);
}
__device__ __forceinline__ void red_f32(float* p, float a) {
    asm volatile("red.relaxed.gpu.global.add.f32 [%0], %1;" ::"l"(p), "f"(a) : "memory");
}
__device__ __forceinline__ void red_f32x2(float* p, float a, float b) {
    asm volatile("red.relaxed.gpu.global.add.v2.f32 [%0], {%1, %2};" ::"l"(p), "f"(a), "f"(b) : "memory");
}
__device__ __forceinline__ void red_f32x4(float* p, float a, float b, float c, float d) {
    asm volatile("red.relaxed.gpu.global.add.v4.f32 [%0], {%1, %2, %3, %4};" ::"l"(p), "f"(a), "f"(b), "f"(c), "f"(d) : "memory");
}
__device__ __forceinline__ float4 ld_l2_f4(const float* p) {
    float4 v;
    asm volatile("ld.relaxed.gpu.global.v4.f32 {%0,%1,%2,%3}, [%4];" : "=f"(v.x), "=f"(v.y), "=f"(v.z), "=f"(v.w) : "l"(p) : "memory");
    return v;
}
__device__ __forceinline__ float2 ld_l2_f2(const float* p) {
    float2 v;
    asm volatile("ld.relaxed.gpu.global.v2.f32 {%0,%1}, [%2];" : "=f"(v.x), "=f"(v.y) : "l"(p) : "memory");
    return v;
}
__device__ __forceinline__ float ld_l2_f(const float* p) {
    float v;
    asm volatile("ld.relaxed.gpu.global.f32 %0, [%1];" : "=f"(v) : "l"(p) : "memory");
    return v;
}
__device__ __forceinline__ uint4 ldg_nc(const void* p) {
    uint4 v;
    asm volatile("ld.global.nc.L1::no_allocate.v4.u32 {%0,%1,%2,%3}, [%4];" : "=r"(v.x), "=r"(v.y), "=r"(v.z), "=r"(v.w) : "l"(p));
    return v;
}
__device__ __forceinline__ void stg128(void* p, uint32_t a, uint32_t b, uint32_t c, uint32_t d) {
    asm volatile("st.global.v4.u32 [%0], {%1,%2,%3,%4};" ::"l"(p), "r"(a), "r"(b), "r"(c), "r"(d) : "memory");
}
__device__ __forceinline__ uint4 lds128(uint32_t a) {
    uint4 v;
    asm volatile("ld.shared.v4.u32 {%0,%1,%2,%3}, [%4];" : "=r"(v.x), "=r"(v.y), "=r"(v.z), "=r"(v.w) : "r"(a) : "memory");
    return v;
}
__device__ __forceinline__ float2 lds_f2(uint32_t a) {
    float2 v;
    asm volatile("ld.shared.v2.f32 {%0,%1}, [%2];" : "=f"(v.x), "=f"(v.y) : "r"(a) : "memory");
    return v;
}
__device__ __forceinline__ void sts_f2(uint32_t a, float x, float y) {
    asm volatile("st.shared.v2.f32 [%0], {%1,%2};" ::"r"(a), "f"(x), "f"(y) : "memory");
}
__device__ __forceinline__ void sts64(uint32_t a, uint32_t x, uint32_t y) {
    asm volatile("st.shared.v2.u32 [%0], {%1,%2};" ::"r"(a), "r"(x), "r"(y) : "memory");
}
__device__ __forceinline__ void sts128(uint32_t a, uint32_t x, uint32_t y, uint32_t z, uint32_t w) {
    asm volatile("st.shared.v4.u32 [%0], {%1,%2,%3,%4};" ::"r"(a), "r"(x), "r"(y), "r"(z), "r"(w) : "memory");
}
__device__ __forceinline__ void stsm4(uint32_t a, uint32_t r0, uint32_t r1, uint32_t r2, uint32_t r3) {
    asm volatile("stmatrix.sync.aligned.m8n8.x4.shared.b16 [%0], {%1,%2,%3,%4};" ::"r"(a), "r"(r0), "r"(r1), "r"(r2), "r"(r3) : "memory");
}
__device__ __forceinline__ void stsm4t(uint32_t a, uint32_t r0, uint32_t r1, uint32_t r2, uint32_t r3) {
    asm volatile("stmatrix.sync.aligned.m8n8.x4.trans.shared.b16 [%0], {%1,%2,%3,%4};" ::"r"(a), "r"(r0), "r"(r1), "r"(r2), "r"(r3) : "memory");
}
__device__ __forceinline__ void tma_store2d(const CUtensorMap* tm, uint32_t src, int c0, int c1) {
    asm volatile("cp.async.bulk.tensor.2d.global.shared::cta.bulk_group [%0, {%2, %3}], [%1];" ::"l"(tm), "r"(src), "r"(c0), "r"(c1) : "memory");
    asm volatile("cp.async.bulk.commit_group;" ::: "memory");
}
__device__ __forceinline__ void ldsm4(uint32_t a, uint32_t& r0, uint32_t& r1, uint32_t& r2, uint32_t& r3) {
    asm volatile("ldmatrix.sync.aligned.m8n8.x4.shared.b16 {%0,%1,%2,%3}, [%4];" : "=r"(r0), "=r"(r1), "=r"(r2), "=r"(r3) : "r"(a) : "memory");
}
__device__ __forceinline__ void ldsm4t(uint32_t a, uint32_t& r0, uint32_t& r1, uint32_t& r2, uint32_t& r3) {
    asm volatile("ldmatrix.sync.aligned.m8n8.x4.trans.shared.b16 {%0,%1,%2,%3}, [%4];" : "=r"(r0), "=r"(r1), "=r"(r2), "=r"(r3) : "r"(a) : "memory");
}
__device__ __forceinline__ void mma16816(float* c, const uint32_t* a, uint32_t b0, uint32_t b1) {
    asm("mma.sync.aligned.m16n8k16.row.col.f32.bf16.bf16.f32 {%0,%1,%2,%3}, {%4,%5,%6,%7}, {%8,%9}, {%0,%1,%2,%3};"
                 : "+f"(c[0]), "+f"(c[1]), "+f"(c[2]), "+f"(c[3])
                 : "r"(a[0]), "r"(a[1]), "r"(a[2]), "r"(a[3]), "r"(b0), "r"(b1));
}
__device__ __forceinline__ uint32_t pack_bf16(float lo, float hi) {
    uint32_t r; asm("cvt.rn.bf16x2.f32 %0, %1, %2;" : "=r"(r) : "f"(hi), "f"(lo)); return r;
}
__device__ __forceinline__ float bf_lo(uint32_t w) { return __uint_as_float(w << 16); }
__device__ __forceinline__ float bf_hi(uint32_t w) { return __uint_as_float(w & 0xffff0000u); }
__device__ __forceinline__ float ex2(float x) { float r; asm("ex2.approx.ftz.f32 %0, %1;" : "=f"(r) : "f"(x)); return r; }
__device__ __forceinline__ float rcp(float x) { float r; asm("rcp.approx.ftz.f32 %0, %1;" : "=f"(r) : "f"(x)); return r; }
__device__ __forceinline__ void bar_sync(int id, int n) { asm volatile("bar.sync %0, %1;" ::"r"(id), "r"(n) : "memory"); }

typedef unsigned long long desc_t;
__device__ __forceinline__ desc_t desc_lo(uint32_t addr) { return (desc_t)(((addr & 0x3FFFF) >> 4) | (512u << 16)) | (0x40000040ull << 32); }
__device__ __forceinline__ void wg_fence() { asm volatile("wgmma.fence.sync.aligned;" ::: "memory"); }
__device__ __forceinline__ void wg_commit() { asm volatile("wgmma.commit_group.sync.aligned;" ::: "memory"); }
template <int N> __device__ __forceinline__ void wg_wait() { asm volatile("wgmma.wait_group.sync.aligned %0;" ::"n"(N) : "memory"); }
template <int N> __device__ __forceinline__ void fence_acc(float* d) {
#pragma unroll
    for (int i = 0; i < N; i++) asm volatile("" : "+f"(d[i])::"memory");
}
#define R4(o) "+f"(d[o + 0]), "+f"(d[o + 1]), "+f"(d[o + 2]), "+f"(d[o + 3])
#define R8(o) R4(o), R4(o + 4)
__device__ __forceinline__ void wgmma_n128(float* d, desc_t da, desc_t db, int sc) {
    asm volatile("{.reg .pred p; setp.ne.b32 p, %66, 0;\n"
                 "wgmma.mma_async.sync.aligned.m64n128k16.f32.bf16.bf16 {%0,%1,%2,%3,%4,%5,%6,%7,%8,%9,%10,%11,%12,%13,%14,%15,%16,%17,%18,%19,%20,%21,%22,%23,%24,%25,%26,%27,%28,%29,%30,%31,"
                 "%32,%33,%34,%35,%36,%37,%38,%39,%40,%41,%42,%43,%44,%45,%46,%47,%48,%49,%50,%51,%52,%53,%54,%55,%56,%57,%58,%59,%60,%61,%62,%63}, %64, %65, p, 1, 1, 0, 1;}"
                 : R8(0), R8(8), R8(16), R8(24), R8(32), R8(40), R8(48), R8(56)
                 : "l"(da), "l"(db), "r"(sc));
}
__device__ __forceinline__ void wgmma_n112(float* d, desc_t da, desc_t db, int sc) {
    asm volatile("{.reg .pred p; setp.ne.b32 p, %58, 0;\n"
                 "wgmma.mma_async.sync.aligned.m64n112k16.f32.bf16.bf16 {%0,%1,%2,%3,%4,%5,%6,%7,%8,%9,%10,%11,%12,%13,%14,%15,%16,%17,%18,%19,%20,%21,%22,%23,%24,%25,%26,%27,%28,%29,%30,%31,%32,%33,%34,%35,%36,%37,%38,%39,%40,%41,%42,%43,%44,%45,%46,%47,%48,%49,%50,%51,%52,%53,%54,%55}, %56, %57, p, 1, 1, 0, 1;}"
                 : R8(0), R8(8), R8(16), R8(24), R8(32), R8(40), R8(48)
                 : "l"(da), "l"(db), "r"(sc));
}
__device__ __forceinline__ void wgmma_n128_tn(float* d, desc_t da, desc_t db, int sc) {
    asm volatile("{.reg .pred p; setp.ne.b32 p, %66, 0;\n"
                 "wgmma.mma_async.sync.aligned.m64n128k16.f32.bf16.bf16 {%0,%1,%2,%3,%4,%5,%6,%7,%8,%9,%10,%11,%12,%13,%14,%15,%16,%17,%18,%19,%20,%21,%22,%23,%24,%25,%26,%27,%28,%29,%30,%31,%32,%33,%34,%35,%36,%37,%38,%39,%40,%41,%42,%43,%44,%45,%46,%47,%48,%49,%50,%51,%52,%53,%54,%55,%56,%57,%58,%59,%60,%61,%62,%63}, %64, %65, p, 1, 1, 1, 0;}"
                 : R8(0), R8(8), R8(16), R8(24), R8(32), R8(40), R8(48), R8(56)
                 : "l"(da), "l"(db), "r"(sc));
}
__device__ __forceinline__ void wgmma_n64(float* d, desc_t da, desc_t db, int sc) {
    asm volatile("{.reg .pred p; setp.ne.b32 p, %34, 0;\n"
                 "wgmma.mma_async.sync.aligned.m64n64k16.f32.bf16.bf16 {%0,%1,%2,%3,%4,%5,%6,%7,%8,%9,%10,%11,%12,%13,%14,%15,%16,%17,%18,%19,%20,%21,%22,%23,%24,%25,%26,%27,%28,%29,%30,%31}, %32, %33, p, 1, 1, 0, 1;}"
                 : R8(0), R8(8), R8(16), R8(24)
                 : "l"(da), "l"(db), "r"(sc));
}
__device__ __forceinline__ void wgmma_n40_tt(float* d, desc_t da, desc_t db, int sc) {
    asm volatile("{.reg .pred p; setp.ne.b32 p, %22, 0;\n"
                 "wgmma.mma_async.sync.aligned.m64n40k16.f32.bf16.bf16 {%0,%1,%2,%3,%4,%5,%6,%7,%8,%9,%10,%11,%12,%13,%14,%15,%16,%17,%18,%19}, %20, %21, p, 1, 1, 1, 1;}"
                 : R8(0), R8(8), R4(16)
                 : "l"(da), "l"(db), "r"(sc));
}

__device__ __forceinline__ void wgmma_n8_tt(float* d, desc_t da, desc_t db, int sc) {
    asm volatile("{.reg .pred p; setp.ne.b32 p, %6, 0;\n"
                 "wgmma.mma_async.sync.aligned.m64n8k16.f32.bf16.bf16 {%0,%1,%2,%3}, %4, %5, p, 1, 1, 1, 1;}"
                 : R4(0)
                 : "l"(da), "l"(db), "r"(sc));
}

__device__ __forceinline__ void signal_after(unsigned* cnt, uint32_t ack, uint32_t zero, bool pred) {
    asm volatile("{.reg .pred p; setp.ne.u32 p, %2, 0; @p red.relaxed.gpu.global.add.u32 [%0], %1;}"
                 ::"l"(cnt), "r"((ack & zero) + 1), "r"((uint32_t)pred) : "memory");
}
__device__ __forceinline__ void signal_late(unsigned* cnt, const uint32_t* a, uint32_t zero, bool pred) {
    uint32_t v;
    asm volatile("{.reg .b32 t; lop3.b32 t, %1, %2, %3, 0xfe; or.b32 %0, t, %4;}"
                 : "=r"(v) : "r"(a[0]), "r"(a[1]), "r"(a[2]), "r"(a[3]));
    signal_after(cnt, v, zero, pred);
}
__device__ __forceinline__ void red_f32_if(float* p, float a, bool pred) {
    asm volatile("{.reg .pred p; setp.ne.u32 p, %2, 0; @p red.relaxed.gpu.global.add.f32 [%0], %1;}" ::"l"(p), "f"(a), "r"((uint32_t)pred) : "memory");
}
__device__ __forceinline__ void stg_f2_if(float* p, float a, float b, bool pred) {
    asm volatile("{.reg .pred p; setp.ne.u32 p, %3, 0; @p st.global.v2.f32 [%0], {%1,%2};}" ::"l"(p), "f"(a), "f"(b), "r"((uint32_t)pred) : "memory");
}
__device__ __forceinline__ void stg64(void* p, uint32_t a, uint32_t b) {
    asm volatile("st.global.v2.u32 [%0], {%1,%2};" ::"l"(p), "r"(a), "r"(b) : "memory");
}
__device__ __forceinline__ void mma16816_z(float* c, const uint32_t* a, uint32_t b0, uint32_t b1) {
    asm("mma.sync.aligned.m16n8k16.row.col.f32.bf16.bf16.f32 {%0,%1,%2,%3}, {%4,%5,%6,%7}, {%8,%9}, {%10,%10,%10,%10};"
                 : "=f"(c[0]), "=f"(c[1]), "=f"(c[2]), "=f"(c[3])
                 : "r"(a[0]), "r"(a[1]), "r"(a[2]), "r"(a[3]), "r"(b0), "r"(b1), "f"(0.f));
}
__device__ __forceinline__ uint32_t max2(uint32_t a, uint32_t b) { uint32_t r; asm("max.bf16x2 %0, %1, %2;" : "=r"(r) : "r"(a), "r"(b)); return r; }
__device__ __forceinline__ uint32_t min2(uint32_t a, uint32_t b) { uint32_t r; asm("min.bf16x2 %0, %1, %2;" : "=r"(r) : "r"(a), "r"(b)); return r; }
__device__ __forceinline__ void bar_arrive(int id, int n) { asm volatile("bar.arrive %0, %1;" ::"r"(id), "r"(n) : "memory"); }
__device__ __forceinline__ void mbar_arrive_n_if(uint32_t bar, uint32_t n, bool pred) {
    asm volatile("{.reg .pred p; setp.ne.u32 p, %1, 0; @p mbarrier.arrive.shared::cta.b64 _, [%0], %2;}" ::"r"(bar), "r"((uint32_t)pred), "r"(n) : "memory");
}
__device__ __forceinline__ float4 lds_f4(uint32_t a) {
    float4 v;
    asm volatile("ld.shared.v4.f32 {%0,%1,%2,%3}, [%4];" : "=f"(v.x), "=f"(v.y), "=f"(v.z), "=f"(v.w) : "r"(a) : "memory");
    return v;
}
__device__ __forceinline__ void lds_f4_if(float4& v, uint32_t a, bool pred) {
    asm volatile("{.reg .pred p; setp.ne.u32 p, %5, 0; @p ld.shared.v4.f32 {%0,%1,%2,%3}, [%4];}"
                 : "+f"(v.x), "+f"(v.y), "+f"(v.z), "+f"(v.w) : "r"(a), "r"((uint32_t)pred) : "memory");
}
__device__ __forceinline__ uint4 ld_tagged(const unsigned long long* p) {
    unsigned long long a, b;
    asm volatile("ld.acquire.gpu.global.v2.b64 {%0,%1}, [%2];" : "=l"(a), "=l"(b) : "l"(p) : "memory");
    return make_uint4((unsigned)a, (unsigned)(a >> 32), (unsigned)b, (unsigned)(b >> 32));
}
__device__ __forceinline__ uint4 ld_tagged_rlx(const unsigned long long* p) {
    unsigned long long a, b;
    asm volatile("ld.relaxed.gpu.global.v2.b64 {%0,%1}, [%2];" : "=l"(a), "=l"(b) : "l"(p) : "memory");
    return make_uint4((unsigned)a, (unsigned)(a >> 32), (unsigned)b, (unsigned)(b >> 32));
}
__device__ __forceinline__ void sts32(uint32_t a, uint32_t x) { asm volatile("st.shared.u32 [%0], %1;" ::"r"(a), "r"(x) : "memory"); }
__device__ __forceinline__ void fetch_tagged(const unsigned long long* src, uint32_t dst, unsigned epoch) {
    uint4 v;
    uint32_t it = 0;
    while (true) {
        v = ld_tagged_rlx(src);
        if (!__any_sync(0xffffffffu, v.y != epoch || v.w != epoch)) break;
        __nanosleep(60);
        trap_if_gt(++it, 1u << 22);
    }
    sts64(dst, v.x, v.z);
}
__device__ __forceinline__ void st_tagged_if(unsigned long long* p, float a, float b, unsigned tag, bool pred) {
    const unsigned long long t = (unsigned long long)tag << 32;
    asm volatile("{.reg .pred p; setp.ne.u32 p, %3, 0; @p st.relaxed.gpu.global.v2.b64 [%0], {%1,%2};}"
                 ::"l"(p), "l"(t | __float_as_uint(a)), "l"(t | __float_as_uint(b)), "r"((uint32_t)pred) : "memory");
}

__device__ __forceinline__ void store_tile(uint32_t tile_rows, uint4* gdst, const uint32_t* lo, const uint32_t* hi, int lane, uint32_t* ack) {
    const int r = lane & 15;
#pragma unroll
    for (int b = 0; b < 4; b++)
        stsm4(tile_rows + r * 128 + (((2 * b + (lane >> 4)) ^ (r & 7)) << 4), lo[2 * b], hi[2 * b], lo[2 * b + 1], hi[2 * b + 1]);
    fence_async_smem();
    __syncwarp();
#pragma unroll
    for (int i = 0; i < 4; i++) {
        const uint4 v = lds128(tile_rows + i * 512 + lane * 16);
        stg128(gdst + 32 * i, v.x, v.y, v.z, v.w);
    }
#pragma unroll
    for (int i = 0; i < 4; i++) ack[i] = readback(gdst + 32 * i);
}

__device__ __forceinline__ void feature_maps(const uint32_t* a, const uint32_t* wb, float c0, float c1, uint32_t* plus, uint32_t* minus) {
    uint32_t P[16], mx[4], mn[4];
#pragma unroll
    for (int h = 0; h < 4; h++) {
        float p[8];
        mma16816_z(p, a + 4 * h, wb[4 * h], wb[4 * h + 1]);
        mma16816_z(p + 4, a + 4 * h, wb[4 * h + 2], wb[4 * h + 3]);
        P[4 * h] = pack_bf16(p[0], p[2]); P[4 * h + 1] = pack_bf16(p[1], p[3]);
        P[4 * h + 2] = pack_bf16(p[4], p[6]); P[4 * h + 3] = pack_bf16(p[5], p[7]);
        mx[h] = max2(max2(P[4 * h], P[4 * h + 1]), max2(P[4 * h + 2], P[4 * h + 3]));
        mn[h] = min2(min2(P[4 * h], P[4 * h + 1]), min2(P[4 * h + 2], P[4 * h + 3]));
    }
#pragma unroll
    for (int s = 1; s <= 2; s <<= 1) {
        uint32_t tx[4], tn[4];
#pragma unroll
        for (int h = 0; h < 4; h++) { tx[h] = __shfl_xor_sync(0xffffffffu, mx[h], s); tn[h] = __shfl_xor_sync(0xffffffffu, mn[h], s); }
#pragma unroll
        for (int h = 0; h < 4; h++) { mx[h] = max2(mx[h], tx[h]); mn[h] = min2(mn[h], tn[h]); }
    }
#pragma unroll
    for (int h = 0; h < 4; h++) {
        const float mx0 = bf_lo(mx[h]) * c0, mx1 = bf_hi(mx[h]) * c1, mn0 = bf_lo(mn[h]) * c0, mn1 = bf_hi(mn[h]) * c1;
        float ep[8], em[8];
#pragma unroll
        for (int i = 0; i < 8; i++) {
            const bool r1 = (i & 2);
            const uint32_t w = P[4 * h + (i >> 2) * 2 + (i & 1)];
            const float p = r1 ? bf_hi(w) : bf_lo(w);
            ep[i] = ex2(fmaf(p, r1 ? c1 : c0, r1 ? -mx1 : -mx0));
            em[i] = ex2(fmaf(p, r1 ? -c1 : -c0, r1 ? mn1 : mn0));
        }
        float sp[4], sm[4];
        uint32_t tp[4], tm[4];
#pragma unroll
        for (int i = 0; i < 4; i++) { tp[i] = pack_bf16(ep[2 * i], ep[2 * i + 1]); tm[i] = pack_bf16(em[2 * i], em[2 * i + 1]); }
        mma16816_z(sp, tp, 0x3f803f80u, 0x3f803f80u);
        mma16816_z(sm, tm, 0x3f803f80u, 0x3f803f80u);
        const float r0 = rcp(sp[0] * sm[0]), r1 = rcp(sp[2] * sm[2]);
        const float rs[4] = {r0 * sm[0], r1 * sm[2], r0 * sp[0], r1 * sp[2]};
#pragma unroll
        for (int i = 0; i < 4; i++) {
            plus[4 * h + i] = pack_bf16(ep[2 * i] * rs[i & 1], ep[2 * i + 1] * rs[i & 1]);
            minus[4 * h + i] = pack_bf16(em[2 * i] * rs[2 + (i & 1)], em[2 * i + 1] * rs[2 + (i & 1)]);
        }
    }
}

template <bool SCALE>
__device__ __forceinline__ void ln_frag(const float* acc, uint32_t cs_addr, float rs0, float nm0, float rs1, float nm1, uint32_t* a) {
    const float2 c0 = lds_f2(cs_addr), c1 = lds_f2(cs_addr + 32);
    const float s0 = SCALE ? rs0 : 1.f, s1 = SCALE ? rs1 : 1.f;
    a[0] = pack_bf16(fmaf(nm0, c0.x, acc[0]) * s0, fmaf(nm0, c0.y, acc[1]) * s0);
    a[1] = pack_bf16(fmaf(nm1, c0.x, acc[2]) * s1, fmaf(nm1, c0.y, acc[3]) * s1);
    a[2] = pack_bf16(fmaf(nm0, c1.x, acc[4]) * s0, fmaf(nm0, c1.y, acc[5]) * s0);
    a[3] = pack_bf16(fmaf(nm1, c1.x, acc[6]) * s1, fmaf(nm1, c1.y, acc[7]) * s1);
}

template <int UP>
__device__ __forceinline__ uint32_t hh_pair(const float* ag, float4 cs, float nmean) {
    const float g0 = fmaf(nmean, cs.x, ag[0]), g1 = fmaf(nmean, cs.y, ag[1]);
    const float u0 = fmaf(nmean, cs.z, ag[UP]), u1 = fmaf(nmean, cs.w, ag[UP + 1]);
    return pack_bf16(g0 * u0, g1 * u1);
}
template <int NTP>
__device__ __forceinline__ void hh_stage(const float* acc, const float4* cs, float nm0, float nm1, uint32_t stg, int lane) {
#pragma unroll
    for (int tp = 0; tp < NTP; tp++)
        stsm4(stg + (lane & 15) * 128 + (((2 * tp + (lane >> 4)) ^ (lane & 7)) << 4), hh_pair<32>(acc + 8 * tp, cs[2 * tp], nm0),
              hh_pair<32>(acc + 8 * tp + 2, cs[2 * tp], nm1), hh_pair<32>(acc + 8 * tp + 4, cs[2 * tp + 1], nm0),
              hh_pair<32>(acc + 8 * tp + 6, cs[2 * tp + 1], nm1));
    fence_async_smem();
    __syncwarp();
}

template <int TP0, int TP1>
__device__ __forceinline__ void hh_stage2(const float* acc, const float4* cs, float nm0, float nm1, uint32_t stg, int lane) {
#pragma unroll
    for (int tp = TP0; tp < TP1; tp++)
        stsm4(stg + (lane & 15) * 128 + (((2 * tp + (lane >> 4)) ^ (lane & 7)) << 4), hh_pair<32>(acc + 8 * tp, cs[2 * tp], nm0),
              hh_pair<32>(acc + 8 * tp + 2, cs[2 * tp], nm1), hh_pair<32>(acc + 8 * tp + 4, cs[2 * tp + 1], nm0),
              hh_pair<32>(acc + 8 * tp + 6, cs[2 * tp + 1], nm1));
}
struct Ring {
    int slot; uint32_t phase;
    __device__ __forceinline__ void adv() { if (++slot == NB) { slot = 0; phase ^= 1; } }
    __device__ __forceinline__ void adv5() { slot += slot == 3; adv(); }
};

__global__ void __cluster_dims__(2, 1, 1) __launch_bounds__(NTHREADS, 1) fused_kernel(const __grid_constant__ Params P) {
    extern __shared__ __align__(1024) uint8_t smem_raw[];
    const uint32_t sb = smem_u32(smem_raw);
    const int tid = threadIdx.x, lane = tid & 31;
    const int warp = __shfl_sync(0xffffffffu, tid >> 5, 0);
    const unsigned rank = blockIdx.x & 1;
    int m, j;
    {
        const int t = (int)(blockIdx.x >> 1) - 4, u = t - 32, r7 = (u * 37) >> 8;
        const int gp = t < 32 ? (t & 7) - 1 : u - 7 * r7;
        j = t < 0 ? t + 8 : (t < 32 ? t >> 3 : 4 + r7);
        m = ((t < 0 || gp < 0) ? 14 : 2 * gp) + rank;
        if (t >= 60) { m = 16; j = blockIdx.x - 128; }
    }
    const unsigned role = m * 8 + j;
    const bool helper = m == 16;

    TL(0, tid == 0); TLG(0, tid == 0);
    float* const acc_j = g_acc + j * ACC_SIZE;
    if ((warp & ~1) == 8 && elect_one()) {
        const uint32_t bar = sb + (warp == 8 ? BAR_FULLB : BAR_FULLA);
#pragma unroll
        for (int i = 0; i < 8; i++) if (i < NB || warp == 9) mbar_init(bar + 8 * i, 1);
        if (!helper) {
#pragma unroll 1
            for (int i = 0; i < NPRE; i++) {
                mbar_expect_tx(bar + 8 * i, SLOT);
                if (warp == 8) {
                    tma2d(sb + OFF_B + i * SLOT, &P.twq, bar + 8 * i, DM + 64 * j, 64 * i);
                    tma2d(sb + OFF_B + i * SLOT + 8192, &P.twq, bar + 8 * i, 2 * DM + 64 * j, 64 * i);
                } else {
                    tma2d(sb + OFF_A + i * SLOT, &P.tx, bar + 8 * i, 64 * i, 128 * m);
                }
            }
        }
    }
    __syncwarp();

    if (warp >= 8) {
        asm volatile("setmaxnreg.dec.sync.aligned.u32 72;");
        if (elect_one()) {
            if (warp < 10) {
            } else if (warp == 10) {
#pragma unroll
                for (int i = 0; i < 12; i++) mbar_init(sb + BAR_CS1 + 8 * i, i < 2 || i >= 8 ? 64 : (i < 4 ? 32 : 8));
                trap_if_gt(sb & 1023, 0);
            } else {
#pragma unroll
                for (int i = 0; i < 14; i++) mbar_init(sb + (i < 8 ? BAR_EMPTYA : BAR_EMPTYB - 64) + 8 * i, i < 8 ? 8 : 16);
            }
            asm volatile("fence.mbarrier_init.release.cluster;" ::: "memory");
        }
        __syncwarp();
        asm volatile("barrier.cluster.arrive.relaxed.aligned;" ::: "memory");
        const unsigned epoch = ld_relaxed(&g_epoch);
        bar_sync(0, NTHREADS);
        if (helper) {
            if (elect_one()) {
#pragma unroll 1
                for (int i = warp - 8; i < 72; i += 4) {
                    const uint32_t full = sb + BAR_FULLA + 8 * (i & 7), dst = sb + OFF_A + (i & 7) * SLOT;
                    const int n = i >> 1, jj = 2 * j + (i & 1);
                    const bool qkv = n < 12;
                    const int c0 = qkv ? (n < 8 ? DM + 128 * (n & 4) : 0) + 64 * jj : 176 * jj + 8 * ((n - 12) & ~7);
                    const int r0 = qkv ? 128 * (n & 3) : 64 * ((n - 12) & 7);
                    mbar_wait(sb + BAR_EMPTYA + 8 * (i & 7), ((i >> 3) & 1) ^ 1);
                    mbar_expect_tx(full, SLOT);
                    tma2d(dst, qkv ? &P.twq : &P.twg, full, c0, r0);
                    tma2d(dst + 8192, qkv ? &P.twq : &P.twu, full, c0, qkv ? r0 + 64 : r0);
                }
                prefetch_l2(P.wd + (size_t)(4 * j + warp - 8) * 44032, 88064);
            }
            return;
        }
        if (warp == 8) {
            asm volatile("barrier.cluster.wait.aligned;" ::: "memory");
            if (elect_one()) {
                if (m >= 6)
                    asm volatile("cp.async.bulk.prefetch.tensor.2d.L2.global [%0, {%1, %2}];" ::"l"(&P.twq), "r"(DM + DM * (m & 1) + 64 * j), "r"(64 * (m >> 1)) : "memory");
                if (j >= 3)
                    asm volatile("cp.async.bulk.prefetch.tensor.2d.L2.global [%0, {%1, %2}];" ::"l"(&P.tx), "r"(64 * j), "r"(128 * m) : "memory");
                Ring r{NPRE, 0};
                const uint32_t dst = sb + OFF_B + rank * 8192;
#define B_LOADN(TM, C0, R0, NB_)                                                                                \
        mbar_waitc(sb + BAR_EMPTYB + 8 * r.slot, r.phase ^ 1);                                              \
        mbar_expect_tx(sb + BAR_FULLB + 8 * r.slot, NB_);                                                   \
        tma2d_mc(dst + r.slot * SLOT, TM, sb + BAR_FULLB + 8 * r.slot, C0, R0);
#define B_LOAD(TM, C0, R0) B_LOADN(TM, C0, R0, SLOT)
#pragma unroll 1
                for (int i = NPRE; i < 8; i++) {
                    if (i >= AHEAD && i < 6) mbar_waitc(sb + BAR_FULLB + 8 * (i - AHEAD), 0);
                    B_LOAD(&P.twq, DM + DM * rank + 64 * j, 64 * i)
                    r.adv();
                }
#pragma unroll 1
                for (int i = 8; i < 18; i++) {
                    if (i == 9 || i == 10) {
                        mbar_waitc(sb + BAR_EMPTYB + 8 * r.slot, r.phase ^ 1);
                        mbar_arrive(sb + BAR_FULLB + 8 * r.slot);
                    } else {
                        const int e = 2 * (i - 14) + rank, b = (i == 8 ? 0 : i - 10) ^ (i < 12 && j < 2);
                        B_LOAD(i < 14 ? &P.twq : &P.two, 64 * j, 64 * (i < 14 ? 2 * b + rank : KORD(e, j)))
                    }
                    r.adv();
                }
#pragma unroll 1
                for (int i = 0; i < 24; i++) {
                    B_LOAD(&P.twg + rank, 176 * j + 8 * (i & ~7), 64 * (i < 8 ? KORD(i, j) : i & 7))
                    r.adv5();
                }
#pragma unroll 1
                for (int i = 0; i < 12; i++) {
                    B_LOADN(&P.twd + (i >> 3), 64 * j, 176 * (2 * (i & 3) + rank) + 64 * (i >> 2), i < 8 ? SLOT : 12288)
                    r.adv5();
                }
            }
            return;
        }
        if (warp == 9) {
            if (elect_one()) {
#pragma unroll 1
                for (int i = NPRE; i < 8; i++) {
                    if (i >= AHEAD + 1) mbar_wait(sb + BAR_FULLA + 8 * (i - AHEAD - 1), 0);
                    mbar_expect_tx(sb + BAR_FULLA + 8 * i, SLOT);
                    tma2d(sb + OFF_A + i * SLOT, &P.tx, sb + BAR_FULLA + 8 * i, 64 * i, 128 * m);
                }
#pragma unroll 1
                for (int i = 2; i < 8; i++) prefetch_tmap(&P.tx + i);
                unsigned nf = 0;
#pragma unroll 1
                for (int r = 1; r < 6; r++) {
                    const int skip = r < 3 ? j : 8;
                    const uint32_t bytes = r == 5 ? 12288 : SLOT;
                    const uint4* src = g_act + ((r - 1) * 128 + m * 8) * 1024;
                    const unsigned* fl = g_flag + (m * 5 + r - 1) * 32;
                    if (r < 4) mbar_wait(sb + BAR_EMPTYA + 8 * (r == 3 ? PF_DELAY : 3 - 2 * (j == 3)), (r - 1) & 1);
                    if (r < 4 || nf != epoch * 8) wait_count(fl, epoch * (r < 3 ? 64 : 8));
                    TL(64 + r, true);
#pragma unroll 1
                    for (int t = 0; t < 8; t++) {
                        if (t == skip) continue;
                        if (t == 6) nf = readback(fl + 32);
                        mbar_wait(sb + BAR_EMPTYA + 8 * t, (r - 1) & 1);
                        mbar_expect_tx(sb + BAR_FULLA + 8 * t, bytes);
                        asm volatile("cp.async.bulk.shared::cluster.global.mbarrier::complete_tx::bytes [%0], [%1], %2, [%3];"
                                     ::"r"(sb + OFF_A + t * SLOT), "l"(src + t * 1024), "r"(bytes), "r"(sb + BAR_FULLA + 8 * t) : "memory");
                    }
                }
            }
            return;
        }
        const int a = warp - 10;
        {
            const int row = 16 * j + 8 * a + (lane >> 2);
            const uint32_t ra = sb + OFF_A + row * 128;
            float sh = 0.f, s0 = 0.f, s1 = 0.f, q0 = 0.f, q1 = 0.f;
#pragma unroll 1
            for (int kt = 0; kt < 8; kt++) {
                mbar_wait(sb + BAR_FULLA + 8 * kt, 0);
                if (kt == 0) sh = bf_lo(lds128(ra + ((row & 7) << 4)).x);
#pragma unroll
                for (int i = 0; i < 2; i++) {
                    const uint4 v = lds128(ra + kt * SLOT + (((2 * (lane & 3) + i) ^ (row & 7)) << 4));
                    const uint32_t ww[4] = {v.x, v.y, v.z, v.w};
#pragma unroll
                    for (int e = 0; e < 4; e++) {
                        const float d0 = bf_lo(ww[e]) - sh, d1 = bf_hi(ww[e]) - sh;
                        s0 += d0; q0 = fmaf(d0, d0, q0);
                        s1 += d1; q1 = fmaf(d1, d1, q1);
                    }
                }
            }
            s0 += s1; q0 += q1;
#pragma unroll
            for (int o = 1; o <= 2; o <<= 1) { s0 += __shfl_xor_sync(0xffffffffu, s0, o); q0 += __shfl_xor_sync(0xffffffffu, q0, o); }
            const float md = s0 * (1.f / DM);
            const float rs = rsqrtf(fmaxf(q0 * (1.f / DM) - md * md, 0.f) + 1e-5f);
            st_tagged_if(g_xstat + 2 * (128 * m + row), rs, -(sh + md), epoch, (lane & 3) == 0);
            TL(1, lane == 0 && a == 0);
        }
        const unsigned long long* cs = g_cs + j * 768 + 2 * lane;
        {
            const unsigned long long* xs = g_xstat + 2 * (128 * m + 64 * a + lane);
            uint4 v0, v1, v2;
            uint32_t it = 0;
            do {
                v0 = ld_tagged_rlx(xs); v1 = ld_tagged_rlx(xs + 64); v2 = ld_tagged_rlx(cs);
                trap_if_gt(++it, 1u << 22);
            } while (__any_sync(0xffffffffu, v0.y != epoch || v0.w != epoch || v1.y != epoch || v1.w != epoch || v2.y != epoch || v2.w != epoch));
            sts64(sb + OFF_XST + (64 * a + lane) * 8, v0.x, v0.z);
            sts64(sb + OFF_XST + (64 * a + 32 + lane) * 8, v1.x, v1.z);
            sts64(sb + OFF_CS1 + 256 + 8 * lane, v2.x, v2.z);
            mbar_arrive(sb + BAR_CS1);
            TL(22 + a, lane == 0);
            fetch_tagged(cs + 128 + 128 * a, sb + OFF_CS1 + 512 - 512 * a + 8 * lane, epoch);
            mbar_arrive(sb + BAR_CSV - 8 * a);
            TL(24 + a, lane == 0);
        }
        {
            mbar_wait(sb + BAR_KVW, 0);
            const float* src = acc_j + 4 * (128 * a + lane);
            float4 v[12];
            uint32_t it = 0;
            bool bad;
            while (__any_sync(0xffffffffu, readback(acc_j + 2048 + 128 * (lane & 7) + 127) != 0x41800000u)) trap_if_gt(++it, 1u << 22);
            TL(19, lane == 0 && a == 0);
            do {
                bad = false;
#pragma unroll
                for (int i = 0; i < 12; i++) v[i] = ld_l2_f4(src + 1024 * (i % 3) + 128 * (i / 3));
#pragma unroll
                for (int i = 0; i < 12; i++) bad |= v[i].w != 16.f;
                trap_if_gt(++it, 1u << 22);
            } while (__any_sync(0xffffffffu, bad));
            TL(14, lane == 0 && a == 0);
            const uint32_t d0 = sb + OFF_A + (j < 2 ? 2 * SLOT : 0) + (64 * a + (lane >> 2)) * 48;
            const uint32_t d = d0 + (lane & 3) * 4, dz = d0 + (lane & 1) * 384 + 32 + (lane & 2) * 4;
#pragma unroll
            for (int u = 0; u < 4; u++) {
                sts32(d + 768 * u, pack_bf16(v[3 * u].x, v[3 * u].y));
                sts32(d + 768 * u + 384, pack_bf16(v[3 * u].z, v[3 * u + 1].z));
                sts32(d + 768 * u + 16, pack_bf16(v[3 * u + 1].x, v[3 * u + 1].y));
                sts32(d + 768 * u + 400, pack_bf16(v[3 * u + 2].x, v[3 * u + 2].y));
                const uint32_t z2 = pack_bf16(v[3 * u + 2].z, v[3 * u + 2].z);
                sts64(dz + 768 * u, z2, z2);
            }
            mbar_arrive(sb + BAR_KVR);
        }
#pragma unroll 1
        for (int c = 0; c < 3; c++) {
            fetch_tagged(cs + 384 + 128 * c + 64 * a, sb + OFF_CS3 + (32 * c + lane) * 16 + 8 * a, epoch);
            mbar_arrive(sb + BAR_CSG + 8 * c);
            TL(45 + c, lane == 0 && a == 0);
        }
        {
            uint32_t it = 0;
            while (__any_sync(0xffffffffu, (int)(readback(g_flag + (m * 5 + 1) * 32) - epoch * 64) < 0)) {
                __nanosleep(200);
                trap_if_gt(++it, 1u << 22);
            }
#pragma unroll 1
            for (int rr = 0; rr < 2; rr++) {
                const int row = 64 * rr + 32 * a + lane;
                const unsigned long long* hs = g_hstat + (1024 * m + row) * 2;
                uint4 v[8];
                bool bad;
                do {
                    bad = false;
#pragma unroll
                    for (int i = 0; i < 8; i++) v[i] = ld_tagged_rlx(hs + 256 * i);
#pragma unroll
                    for (int i = 0; i < 8; i++) bad |= v[i].y != epoch || v[i].w != epoch;
                    trap_if_gt(++it, 1u << 22);
                } while (__any_sync(0xffffffffu, bad));
                float mean = 0.f;
#pragma unroll
                for (int i = 0; i < 8; i++) mean += __uint_as_float(v[i].x);
                mean *= 0.125f;
                float m2 = 0.f, dv = 0.f;
#pragma unroll
                for (int i = 0; i < 8; i++) { const float d = __uint_as_float(v[i].x) - mean; m2 += __uint_as_float(v[i].z); dv = fmaf(d, d, dv); }
                sts_f2(sb + OFF_CS1 + row * 8, -mean, rcp(fmaf(dv, 64.f, m2) * (1.f / DM) + 1e-5f));
            }
        }
        mbar_arrive(sb + BAR_CS3);
#pragma unroll 1
        for (int c = a; c < 3; c += 2) {
            mbar_wait(sb + BAR_STG + 8 * c, 0);
            if (elect_one()) {
                asm volatile("cp.async.bulk.global.shared::cta.bulk_group [%0], [%1], %2;" ::"l"(g_act + ((2 + c) * 128 + role) * 1024), "r"(sb + OFF_B + 4 * SLOT), "r"(c == 2 ? 12288 : SLOT) : "memory");
                asm volatile("cp.async.bulk.commit_group;" ::: "memory");
                asm volatile("cp.async.bulk.wait_group.read 0;" ::: "memory");
                mbar_arrive(sb + BAR_FULLB + 8 * 4);
                asm volatile("cp.async.bulk.wait_group 0;" ::: "memory");
            }
            __syncwarp();
            TL(60 + c, lane == 0);
            uint32_t ack = 0;
            const uint4* rb = g_act + ((2 + c) * 128 + role) * 1024 + lane * 8;
#pragma unroll
            for (int i = 0; i < 4; i++) ack |= readback(rb + (i == 3 && c == 2 ? 0 : 256 * i));
            signal_after(g_flag + (m * 5 + 2 + c) * 32, ack, P.zero, lane == 0);
            TL(54 + c, lane == 0);
        }
        return;
    }
    const unsigned epoch = ld_relaxed(&g_epoch);
    uint32_t wraw[16];
    if (!helper) {
        const uint32_t* wp = reinterpret_cast<const uint32_t*>(P.wphi) + (4 * j) * 128 + (lane & 3) * 16 + (lane >> 2);
#pragma unroll
        for (int i = 0; i < 16; i++)
            asm volatile("ld.global.nc.u32 %0, [%1];" : "=r"(wraw[i]) : "l"(wp + (i >> 2) * 128 + ((i >> 1) & 1) * 64 + (i & 1) * 8));
    }
    asm volatile("barrier.cluster.arrive.relaxed.aligned;" ::: "memory");
    asm volatile("setmaxnreg.inc.sync.aligned.u32 216;");
    bar_sync(0, NTHREADS);
    if (helper) {
        const int w = warp >> 2;
        sts64(sb + OFF_B + 8 * tid, 0x3f803f80u, 0x3f803f80u);
        fence_async_smem();
        uint32_t zack[6];
        {
            float* z = g_acc + 2 * j * ACC_SIZE + 4 * tid;
#pragma unroll
            for (int u = 0; u < 6; u++) stg128(z + 1024 * u, 0, 0, 0, 0);
#pragma unroll
            for (int u = 0; u < 6; u++) zack[u] = readback(z + 1024 * u);
        }
        bar_sync(1, 256);
        TL(70, tid == 0);
        float acc[8];
        int i = w;
#pragma unroll 1
        for (int job = 0; job < 6; job++) {
            const int n = job < 3 ? 4 : 8;
#pragma unroll 1
            for (int t = 0; t < n; t++, i += 2) {
                mbar_waitc(sb + BAR_FULLA + 8 * (i & 7), (i >> 3) & 1);
                const desc_t da = desc_lo(sb + OFF_A) + (i & 7) * (SLOT >> 4);
                wg_fence();
#pragma unroll
                for (int k = 0; k < 8; k++) wgmma_n8_tt(acc + (k & 4), da + 128 * k, desc_lo(sb + OFF_B), (t | (k & 3)) != 0);
                wg_commit();
                wg_wait<0>();
                mbar_arrive_n_if(sb + BAR_EMPTYA + 8 * (i & 7), 2, lane == 0);
            }
            fence_acc<8>(acc);
            TL(71 + job, tid == 0);
            if (job == 1) {
                asm volatile("{.reg .pred p; .reg .b32 t; lop3.b32 t, %0, %1, %2, 0xfe; lop3.b32 t, t, %3, %4, 0xfe; or.b32 t, t, %5; setp.ne.u32 p, t, 0; @p trap;}"
                             ::"r"(zack[0]), "r"(zack[1]), "r"(zack[2]), "r"(zack[3]), "r"(zack[4]), "r"(zack[5]));
                bar_sync(1, 256);
            }
            const int q = lane & 3;
            const float lo = (q & 1) ? acc[2] : acc[0], hi = (q & 1) ? acc[6] : acc[4];
            const float v = job < 3 ? lo + hi : ((q & 2) ? hi : lo);
            unsigned long long* dst = g_cs + ((2 * j + w) * 6 + job) * 128 + (q >> 1) * 64 + 16 * (warp & 3) + 8 * (q & 1) + (lane >> 2);
            asm volatile("st.relaxed.gpu.global.b64 [%0], %1;" ::"l"(dst), "l"(((unsigned long long)epoch << 32) | __float_as_uint(v)) : "memory");
        }
        return;
    }
    {
        const int w = warp >> 2, wv = warp & 3, g = lane >> 2, q = lane & 3;
        const uint32_t sa = sb + OFF_A + w * 8192;
        const desc_t dA = desc_lo(sa), dB = desc_lo(sb + OFF_B);
        unsigned* const flag_m = g_flag + m * 160;
        const bool l0 = lane == 0, l2 = lane < 2;
        const uint32_t eb = mapa(sb + BAR_EMPTYB, lane & 1);
        asm volatile("barrier.cluster.wait.aligned;" ::: "memory");
        Ring rg{0, 0};
        int prev = 0;

        uint32_t wb[16];
        constexpr float L2E = 1.4426950408889634f;
        const int ch = lane >> 4, sw = lane & 7;
        const uint32_t lrow = (lane & 15) * 128;
        uint32_t fp[16], fm[16];
        const int vs = j < 2 ? 2 : 0;
        {
            float acc[64];
#pragma unroll 1
            for (int kt = 0; kt < 8; kt++) {
                mbar_waitc(sb + BAR_FULLA + 8 * kt, 0);
                mbar_waitc(sb + BAR_FULLB + 8 * rg.slot, rg.phase);
                const desc_t da = dA + kt * (SLOT >> 4), db = dB + rg.slot * (SLOT >> 4);
                wg_fence();
#pragma unroll
                for (int k = 0; k < 4; k++) wgmma_n128(acc, da + 2 * k, db + 128 * k, (kt | k) != 0);
                wg_commit();
                wg_wait<1>();
                mbar_arrive_cl_if(eb + 8 * prev, l2 && kt > 0);
                prev = rg.slot; rg.adv();
            }
#pragma unroll
            for (int i = 0; i < 8; i++) {
                wb[(i >> 1) * 4 + (i & 1)] = __byte_perm(wraw[2 * i], wraw[2 * i + 1], 0x5410);
                wb[(i >> 1) * 4 + 2 + (i & 1)] = __byte_perm(wraw[2 * i], wraw[2 * i + 1], 0x7632);
            }
            uint32_t a[16];
            float accq[32];
            mbar_waitc(sb + BAR_FULLB + 8 * 2, 1);
            wg_fence();
#pragma unroll
            for (int k = 0; k < 8; k++) wgmma_n64(accq, dA + (vs + (k >> 2)) * (SLOT >> 4) + (k & 3) * 2, dB + 2 * (SLOT >> 4) + 128 * k, k != 0);
            wg_commit();
            wg_wait<1>();
            fence_acc<64>(acc);
            mbar_arrive_cl_if(eb + 8 * prev, l2);
            TL(17, tid == 0);
            mbar_waitc(sb + BAR_CS1, 0);
            const float2 s0 = lds_f2(sb + OFF_XST + (16 * warp + g) * 8), s1 = lds_f2(sb + OFF_XST + (16 * warp + g + 8) * 8);
            wg_wait<0>();
            fence_acc<32>(accq);
            mbar_arrive_cl_if(eb + 8 * 2, l2);
            TL(2, tid == 0);
            const uint32_t st = sb + OFF_B + warp * 2048 + lrow;
#pragma unroll
            for (int hh = 0; hh < 4; hh++)
                ln_frag<false>(acc + 8 * hh, sb + OFF_CS1 + (64 + 16 * hh + 2 * q) * 4, 0.f, s0.y, 0.f, s1.y, a + 4 * hh);
#pragma unroll 1
            for (int it = 0; it < 2; it++) {
                feature_maps(a, wb, s0.x * L2E, s1.x * L2E, fp, fm);
                if (it == 0) {
                    mbar_waitc(sb + BAR_FULLB + 8 * 3, 1); mbar_waitc(sb + BAR_FULLB + 8 * 4, 1);
                    mbar_waitc(sb + BAR_CSV, 0);
                    const uint32_t sv = sb + OFF_A + vs * SLOT + warp * 2048 + lrow;
#pragma unroll
                    for (int hh = 0; hh < 4; hh++) {
                        stsm4(st + (3 + (hh >> 1)) * SLOT + (((4 * (hh & 1) + ch) ^ sw) << 4), fp[4 * hh], fp[4 * hh + 1], fp[4 * hh + 2], fp[4 * hh + 3]);
                        stsm4(st + (3 + (hh >> 1)) * SLOT + (((4 * (hh & 1) + 2 + ch) ^ sw) << 4), fm[4 * hh], fm[4 * hh + 1], fm[4 * hh + 2], fm[4 * hh + 3]);
                        ln_frag<true>(acc + 32 + 8 * hh, sb + OFF_CS1 + (128 + 16 * hh + 2 * q) * 4, s0.x, s0.y, s1.x, s1.y, a);
                        stsm4(sv + (hh >> 1) * SLOT + (((2 * (hh & 1) + ch) ^ sw) << 4), a[0], a[1], a[2], a[3]);
                    }
                    stsm4(sv + ch * SLOT + ((4 ^ sw) << 4), 0x3f803f80u, 0x3f803f80u, 0x3f803f80u, 0x3f803f80u);
                    fence_async_smem();
                    bar_sync(1, 256);
                    float kvd[20];
                    wg_fence();
#pragma unroll
                    for (int k = 0; k < 8; k++)
                        wgmma_n40_tt(kvd, dB + (3 + w) * (SLOT >> 4) + 128 * k, desc_lo(sb + OFF_A) + (vs + w) * (SLOT >> 4) + 128 * k, k != 0);
                    wg_commit();
                    wg_wait<0>();
                    fence_acc<20>(kvd);
                    mbar_arrive_cl_if(eb + 8 * (3 + (lane >> 1)), lane < 4);
                    const bool h1 = wv >= 2;
                    float* kvp = acc_j + 4 * tid;
                    red_f32x4(kvp, h1 ? kvd[8] : kvd[0], h1 ? kvd[9] : kvd[1], h1 ? kvd[10] : kvd[2], 1.f);
                    red_f32x4(kvp + 1024, h1 ? kvd[12] : kvd[4], h1 ? kvd[13] : kvd[5], h1 ? kvd[11] : kvd[3], 1.f);
                    red_f32x4(kvp + 2048, h1 ? kvd[14] : kvd[6], h1 ? kvd[15] : kvd[7], (q & 1) ? kvd[18] : kvd[16], 1.f);
                    mbar_arrive_if(sb + BAR_KVW, l0);
                    TL(3, tid == 0);
#pragma unroll 1
                    for (int b = 1; b < 4; b++) {
                        const int slot = b == 1 ? 5 : b - 2;
                        mbar_waitc(sb + BAR_FULLB + 8 * slot, b == 1);
                        const desc_t da = dA + (b == 1 ? 2 - vs : 2 * b) * (SLOT >> 4), db = dB + slot * (SLOT >> 4);
                        wg_fence();
#pragma unroll
                        for (int k = 0; k < 8; k++) wgmma_n64(accq, da + (k >> 2) * (SLOT >> 4) + (k & 3) * 2, db + 128 * k, 1);
                        wg_commit();
                    }
                    mbar_waitc(sb + BAR_CSQ, 0);
                    wg_wait<0>();
                    fence_acc<32>(accq);
                    mbar_arrive_cl_if(eb + 8 * ((5 + (lane >> 1)) % 6), lane < 6);
                    TL(4, tid == 0);
#pragma unroll
                    for (int hh = 0; hh < 4; hh++)
                        ln_frag<false>(accq + 8 * hh, sb + OFF_CS1 + (16 * hh + 2 * q) * 4, 0.f, s0.y, 0.f, s1.y, a + 4 * hh);
                }
            }
        }
        uint32_t res_lo[8], res_hi[8], ack[4];
        const uint32_t own_rows = sb + OFF_A + j * SLOT + warp * 2048;
#pragma unroll
        for (int b = 0; b < 4; b++)
            ldsm4(own_rows + lrow + (((2 * b + ch) ^ sw) << 4), res_lo[2 * b], res_hi[2 * b], res_lo[2 * b + 1], res_hi[2 * b + 1]);
        mbar_arrive_if(sb + BAR_EMPTYA + 8 * lane, lane < 8 && lane != j && lane != vs);
        TL(5, tid == 0);
        mbar_waitc(sb + BAR_KVR, 0);
        TL(6, tid == 0);
        {
            const uint32_t kvs = sb + OFF_A + vs * SLOT;
            uint32_t o_lo[8], o_hi[8];
#pragma unroll
            for (int hh = 0; hh < 4; hh++) {
                uint32_t b[8], zb[4];
                const uint32_t base = kvs + hh * 32 * 48;
                ldsm4t(base + (lane & 15) * 48 + (lane >> 4) * 16, b[0], b[1], b[2], b[3]);
                ldsm4t(base + (16 + (lane & 15)) * 48 + (lane >> 4) * 16, b[4], b[5], b[6], b[7]);
                ldsm4t(base + lane * 48 + 32, zb[0], zb[1], zb[2], zb[3]);
                float n0[4], n1[4], dn[4];
                mma16816_z(n0, fp + 4 * hh, b[0], b[1]); mma16816_z(n1, fp + 4 * hh, b[2], b[3]); mma16816_z(dn, fp + 4 * hh, zb[0], zb[1]);
                mma16816(n0, fm + 4 * hh, b[4], b[5]); mma16816(n1, fm + 4 * hh, b[6], b[7]); mma16816(dn, fm + 4 * hh, zb[2], zb[3]);
                const float i0 = rcp(dn[0] + 1e-6f), i1 = rcp(dn[2] + 1e-6f);
                o_lo[2 * hh] = pack_bf16(n0[0] * i0, n0[1] * i0); o_hi[2 * hh] = pack_bf16(n0[2] * i1, n0[3] * i1);
                o_lo[2 * hh + 1] = pack_bf16(n1[0] * i0, n1[1] * i0); o_hi[2 * hh + 1] = pack_bf16(n1[2] * i1, n1[3] * i1);
            }
            __syncwarp();
            mbar_arrive_if(sb + BAR_EMPTYA + 8 * vs, l0);
            rg.slot = 2; rg.phase = 0;
            store_tile(own_rows, g_act + role * 1024 + warp * 128 + lane, o_lo, o_hi, lane, ack);
            TL(7, tid == 0);
        }
        float acch[32];
        {
            float* acc = acch;
#pragma unroll
            for (int t = 0; t < 8; t++) {
                acc[4 * t] = bf_lo(res_lo[t]); acc[4 * t + 1] = bf_hi(res_lo[t]);
                acc[4 * t + 2] = bf_lo(res_hi[t]); acc[4 * t + 3] = bf_hi(res_hi[t]);
            }
            fence_acc<32>(acc);
            int pa = 0;
#pragma unroll 1
            for (int kp = 0; kp < 4; kp++) {
                mbar_waitc(sb + BAR_FULLB + 8 * rg.slot, rg.phase);
#pragma unroll
                for (int hf = 0; hf < 2; hf++) {
                    const int i = 2 * kp + hf, kt = KORD(i, j);
                    mbar_waitc(sb + BAR_FULLA + 8 * kt, i != 0);
                    TL(8, i == 1 && tid == 0);
                    const desc_t da = dA + kt * (SLOT >> 4), db = dB + rg.slot * (SLOT >> 4);
                    wg_fence();
#pragma unroll
                    for (int k = 0; k < 4; k++) wgmma_n64(acc, da + 2 * k, db + (hf * 4 + k) * 128, 1);
                    wg_commit();
                    wg_wait<1>();
                    mbar_arrive_if(sb + BAR_EMPTYA + 8 * pa, l0 && i > 1);
                    if (hf == 0) {
                        mbar_arrive_cl_if(eb + 8 * prev, l2 && i > 0);
                        if (i == 0) { signal_late(flag_m, ack, P.zero, l0); TL(20, tid == 0); }
                    }
                    pa = kt;
                }
                prev = rg.slot; rg.adv();
            }
            wg_wait<0>();
            fence_acc<32>(acc);
            mbar_arrive_if(sb + BAR_EMPTYA + 8 * pa, l0);
            mbar_arrive_cl_if(eb + 8 * prev, l2);
            TL(9, tid == 0);
#pragma unroll
            for (int t = 0; t < 8; t++) {
                res_lo[t] = pack_bf16(acc[4 * t], acc[4 * t + 1]);
                res_hi[t] = pack_bf16(acc[4 * t + 2], acc[4 * t + 3]);
            }
            store_tile(own_rows, g_act + (128 + role) * 1024 + warp * 128 + lane, res_lo, res_hi, lane, ack);
            TL(10, tid == 0);
        }
        float acc0[64], acc1[64], acc2[56], nm0, nm1;
        float4 cs[8];
        uint32_t hr[16];
#define P3_GROUP(MMA, ACC, KT)                                                                              \
        mbar_waitc(sb + BAR_FULLB + 8 * rg.slot, rg.phase);                                                 \
        {                                                                                                   \
            const desc_t da = dA + (KT) * (SLOT >> 4), db = dB + rg.slot * (SLOT >> 4);                     \
            wg_fence();                                                                                     \
            _Pragma("unroll") for (int k = 0; k < 4; k++) MMA(ACC, da + 2 * k, db + 128 * k, (i | k) != 0); \
            wg_commit();                                                                                    \
        }
#define P3_CS(C, NT)    \
        _Pragma("unroll") for (int t = 0; t < (NT); t++) lds_f4_if(cs[t], sb + OFF_CS3 + q * 16 + 512 * (C) + 64 * t, i == t);
#define P3_EPI2(C, ACC)                                                                                     \
        if (i == 0) {                                                                                       \
            fence_acc<64>(ACC);                                                                             \
            if (C) mbar_waitc(sb + BAR_FULLB + 8 * 4, 1);                                                   \
            hh_stage2<0, 2>(ACC, cs, nm0, nm1, stg, lane);                                                  \
            mbar_waitc(sb + BAR_CSG + 8 * (C) + 8, 0);                                                      \
        }                                                                                                   \
        if (i == 1) {                                                                                       \
            hh_stage2<2, 4>(ACC, cs, nm0, nm1, stg, lane);                                                  \
            fence_async_smem();                                                                             \
            __syncwarp();                                                                                   \
            mbar_arrive_if(sb + BAR_STG + 8 * (C), l0);                                                     \
        }
#define P3_EPI(C, ACC, N, NTP)                                                                              \
        fence_acc<N>(ACC);                                                                                  \
        TL(11 + (C), tid == 0);                                                                             \
        hh_stage<NTP>(ACC, cs, nm0, nm1, sb + OFF_B + 4 * SLOT + warp * 2048, lane);                        \
        mbar_arrive_if(sb + BAR_STG + 8 * (C), l0);                                                         \
        TL(50 + (C), tid == 0);
        const uint32_t stg = sb + OFF_B + 4 * SLOT + warp * 2048;
        const uint32_t blk = ((lane & 7) + (lane >> 4) * 8) * 128 + (((2 * wv + ((lane >> 3) & 1)) ^ (lane & 7)) << 4);
#pragma unroll 1
        for (int i = 0; i < 8; i++) {
            const int kt = KORD(i, j);
            mbar_waitc(sb + BAR_FULLA + 8 * kt, 0);
            TL(44, tid == 0 && i == 1);
            P3_GROUP(wgmma_n128, acc0, kt)
            if (i == 7) {
                mbar_waitc(sb + BAR_CS3, 0);
                nm0 = lds_f2(sb + OFF_CS1 + (16 * warp + g) * 8).x; nm1 = lds_f2(sb + OFF_CS1 + (16 * warp + g + 8) * 8).x;
            }
            wg_wait<1>();
            mbar_arrive_cl_if(eb + 8 * prev, l2 && i > 0);
            if (i == 0) {
                signal_late(flag_m + 32, ack, P.zero, l0);
                TL(21, tid == 0);
                {
                    fence_acc<32>(acch);
                    const float* acc = acch;
                    float s0 = 0.f, s1 = 0.f;
#pragma unroll
                    for (int t = 0; t < 8; t++) { s0 += acc[4 * t] + acc[4 * t + 1]; s1 += acc[4 * t + 2] + acc[4 * t + 3]; }
            s0 += __shfl_xor_sync(0xffffffffu, s0, 1); s1 += __shfl_xor_sync(0xffffffffu, s1, 1);
            s0 += __shfl_xor_sync(0xffffffffu, s0, 2); s1 += __shfl_xor_sync(0xffffffffu, s1, 2);
            const float mu0 = s0 * (1.f / 64), mu1 = s1 * (1.f / 64);
            float q0 = 0.f, q1 = 0.f;
#pragma unroll
            for (int t = 0; t < 8; t++) {
                float d;
                d = acc[4 * t] - mu0; q0 = fmaf(d, d, q0);
                d = acc[4 * t + 1] - mu0; q0 = fmaf(d, d, q0);
                d = acc[4 * t + 2] - mu1; q1 = fmaf(d, d, q1);
                d = acc[4 * t + 3] - mu1; q1 = fmaf(d, d, q1);
            }
            q0 += __shfl_xor_sync(0xffffffffu, q0, 1); q1 += __shfl_xor_sync(0xffffffffu, q1, 1);
            q0 += __shfl_xor_sync(0xffffffffu, q0, 2); q1 += __shfl_xor_sync(0xffffffffu, q1, 2);
            st_tagged_if(g_hstat + (role * 128 + 16 * warp + g + 8 * (q & 1)) * 2, q ? mu1 : mu0, q ? q1 : q0, epoch, q < 2);
                }
                bar_sync(2 + w, 128);
#pragma unroll
                for (int tp = 0; tp < 4; tp++) ldsm4t(sa + j * SLOT + blk + tp * 2048, hr[4 * tp], hr[4 * tp + 1], hr[4 * tp + 2], hr[4 * tp + 3]);
                mbar_waitc(sb + BAR_CSG, 0);
#pragma unroll
                for (int t = 0; t < 8; t++) cs[t] = lds_f4(sb + OFF_CS3 + q * 16 + 64 * t);
            }
            prev = rg.slot; rg.adv5();
        }
#pragma unroll 1
        for (int i = 0; i < 8; i++) {
            P3_GROUP(wgmma_n128, acc1, i)
            wg_wait<1>();
            mbar_arrive_cl_if(eb + 8 * prev, l2);
            P3_EPI2(0, acc0)
            P3_CS(1, 8)
            prev = rg.slot; rg.adv5();
        }
#pragma unroll 1
        for (int i = 0; i < 8; i++) {
            P3_GROUP(wgmma_n112, acc2, i)
            wg_wait<1>();
            mbar_arrive_cl_if(eb + 8 * prev, l2);
            mbar_arrive_if(sb + BAR_EMPTYA + 8 * ((i + 7) & 7), l0 && i > 0);
            if (i == 0) { mbar_waitc(sb + BAR_FULLB + 8 * 4, 1); P3_EPI(1, acc1, 64, 4) mbar_waitc(sb + BAR_CSG + 16, 0); }
            P3_CS(2, 6)
            prev = rg.slot; rg.adv5();
        }
        mbar_waitc(sb + BAR_FULLB + 8 * 4, 0);
        wg_wait<0>();
        mbar_arrive_cl_if(eb + 8 * prev, l2);
        mbar_arrive_if(sb + BAR_EMPTYA + 8 * 7, l0);
        fence_acc<56>(acc2);
        TL(13, tid == 0);
#pragma unroll
        for (int tp = 0; tp < 3; tp++)
            stsm4(sb + OFF_B + 4 * SLOT + tp * 4096 + warp * 512 + (lane & 15) * 32 + ((ch ^ ((lane >> 2) & 1)) << 4),
                  hh_pair<32>(acc2 + 8 * tp, cs[2 * tp], nm0), hh_pair<32>(acc2 + 8 * tp + 2, cs[2 * tp], nm1),
                  hh_pair<32>(acc2 + 8 * tp + 4, cs[2 * tp + 1], nm0), hh_pair<32>(acc2 + 8 * tp + 6, cs[2 * tp + 1], nm1));
        fence_async_smem();
        __syncwarp();
        mbar_arrive_if(sb + BAR_STG + 16, l0);
        TL(52, tid == 0);
        {
            float acc[64];
            const desc_t dA0 = desc_lo(sb + OFF_A);
#define KT_P4(I, NK, DH, STEP)                                                                                   \
        const int s_ = (2 * (I) + w) & 7;                                                                   \
        mbar_waitc(sb + BAR_FULLB + 8 * rg.slot, rg.phase);                                                 \
        mbar_waitc(sb + BAR_FULLA + 8 * s_, (((I) >> 2) + 1) & 1);                                          \
        const desc_t dh_ = (DH) + s_ * (SLOT >> 4), dw_ = dB + rg.slot * (SLOT >> 4) + w * 512;              \
        wg_fence();                                                                                         \
        _Pragma("unroll") for (int k = 0; k < (NK); k++) wgmma_n128_tn(acc, dw_ + 128 * k, dh_ + (STEP) * k, ((I) | k) != 0); \
        wg_commit();                                                                                        \
        wg_wait<1>();
#pragma unroll 1
            for (int i = 0; i < 8; i++) {
                KT_P4(i, 4, dA0, 2)
                mbar_arrive_n_if(sb + BAR_EMPTYA + 8 * ((s_ + 6) & 7), 2, l0 && i > 0);
                mbar_arrive_cl_if(eb + 8 * prev, l2 && i > 0);
#pragma unroll
                for (int t = 0; t < 8; t++) lds_f4_if(cs[t], sb + OFF_CS1 + (64 * w + 8 * t + 2 * q) * 8, i == t);
                prev = rg.slot; rg.adv5();
            }
#pragma unroll 1
            for (int i = 8; i < 12; i++) {
                KT_P4(i, 3, dA0 + ((0xC0000010ull - 0x40000040ull) << 32), 256)
                mbar_arrive_n_if(sb + BAR_EMPTYA + 8 * ((s_ + 6) & 7), 2, l0);
                rg.adv5();
            }
            wg_wait<0>();
            fence_acc<64>(acc);
            TL(15, tid == 0);
            const uint32_t xch = sb + OFF_A + 2 * SLOT + (tid & 127) * 16;
            if (w) {
#pragma unroll
                for (int t = 0; t < 8; t++) {
                    sts128(xch + SLOT + t * 2048, __float_as_uint(acc[4 * t]), __float_as_uint(acc[4 * t + 1]),
                           __float_as_uint(acc[4 * t + 2]), __float_as_uint(acc[4 * t + 3]));
                }
#pragma unroll
                for (int t = 0; t < 32; t++) acc[t] = acc[32 + t];
            } else {
#pragma unroll
                for (int t = 0; t < 8; t++)
                    sts128(xch + t * 2048, __float_as_uint(acc[32 + 4 * t]), __float_as_uint(acc[33 + 4 * t]),
                           __float_as_uint(acc[34 + 4 * t]), __float_as_uint(acc[35 + 4 * t]));
            }
            bar_sync(1, 256);
            float4 o[8];
#pragma unroll
            for (int t = 0; t < 8; t++) o[t] = lds_f4(xch + (w ^ 1) * SLOT + t * 2048);
            const uint32_t tile = sb + OFF_A + w * SLOT;
#pragma unroll
            for (int t = 0; t < 8; t++) {
                hr[2 * t] = pack_bf16(fmaf(acc[4 * t] + o[t].x, cs[t].y, bf_lo(hr[2 * t])), fmaf(acc[4 * t + 1] + o[t].y, cs[t].w, bf_hi(hr[2 * t])));
                hr[2 * t + 1] = pack_bf16(fmaf(acc[4 * t + 2] + o[t].z, cs[t].y, bf_lo(hr[2 * t + 1])), fmaf(acc[4 * t + 3] + o[t].w, cs[t].w, bf_hi(hr[2 * t + 1])));
            }
#pragma unroll
            for (int tp = 0; tp < 4; tp++) stsm4t(tile + blk + tp * 2048, hr[4 * tp], hr[4 * tp + 1], hr[4 * tp + 2], hr[4 * tp + 3]);
            fence_async_smem();
            bar_sync(2 + w, 128);
            if ((tid & 127) == 0) {
                tma_store2d(&P.tout, tile, 64 * j, 128 * m + 64 * w);
                asm volatile("cp.async.bulk.wait_group.read 0;" ::: "memory");
            }
            if (tid == 0 && role == 0) g_epoch = epoch + 1;
            TL(16, tid == 0); TLG(1, tid == 0);
        }
    }
}

typedef CUresult (*EncodeFn)(CUtensorMap*, CUtensorMapDataType, cuuint32_t, void*, const cuuint64_t*, const cuuint64_t*,
                             const cuuint32_t*, const cuuint32_t*, CUtensorMapInterleave, CUtensorMapSwizzle,
                             CUtensorMapL2promotion, CUtensorMapFloatOOBfill);

static void make_map2d(EncodeFn enc, CUtensorMap* tm, const void* base, uint64_t cols, uint64_t rows, uint64_t pitch_elems,
                       uint32_t box_rows) {
    cuuint64_t gd[2] = {cols, rows};
    cuuint64_t gs[1] = {pitch_elems * 2};
    cuuint32_t bd[2] = {64, box_rows};
    cuuint32_t es[2] = {1, 1};
    enc(tm, CU_TENSOR_MAP_DATA_TYPE_BFLOAT16, 2, const_cast<void*>(base), gd, gs, bd, es, CU_TENSOR_MAP_INTERLEAVE_NONE,
        CU_TENSOR_MAP_SWIZZLE_128B, CU_TENSOR_MAP_L2_PROMOTION_L2_256B, CU_TENSOR_MAP_FLOAT_OOB_FILL_NONE);
}

}

extern "C" void kernel_launch(void* const* d_in, const int* in_sizes, int n_in, void* d_out, int out_size) {
    using namespace hk;
    (void)in_sizes; (void)n_in; (void)out_size;
    static EncodeFn enc = nullptr;
    if (!enc) {
        void* fn = nullptr;
        cudaDriverEntryPointQueryResult qr;
        cudaGetDriverEntryPoint("cuTensorMapEncodeTiled", &fn, cudaEnableDefault, &qr);
        enc = (EncodeFn)fn;
        cudaFuncSetAttribute(fused_kernel, cudaFuncAttributeMaxDynamicSharedMemorySize, SMEM_BYTES);
    }
    Params P;
    const __nv_bfloat16* x = (const __nv_bfloat16*)d_in[0];
    P.x = x;
    P.wqkv = (const __nv_bfloat16*)d_in[1];
    P.wphi = (const __nv_bfloat16*)d_in[2];
    P.wo = (const __nv_bfloat16*)d_in[3];
    P.wg = (const __nv_bfloat16*)d_in[5];
    P.wu = (const __nv_bfloat16*)d_in[6];
    P.wd = (const __nv_bfloat16*)d_in[7];
    P.out = (__nv_bfloat16*)d_out;
    P.zero = 0;
    make_map2d(enc, &P.tx, x, DM, SEQ, DM, 128);
    make_map2d(enc, &P.twq, P.wqkv, 3 * DM, DM, 3 * DM, 64);
    make_map2d(enc, &P.two, P.wo, DM, DM, DM, 64);
    make_map2d(enc, &P.twg, P.wg, FF, DM, FF, 64);
    make_map2d(enc, &P.twu, P.wu, FF, DM, FF, 64);
    make_map2d(enc, &P.twd, P.wd, DM, FF, DM, 64);
    make_map2d(enc, &P.twd48, P.wd, DM, FF, DM, 48);
    make_map2d(enc, &P.tout, d_out, DM, SEQ, DM, 64);
    fused_kernel<<<NCTA, NTHREADS, SMEM_BYTES>>>(P);
}
```

```cpp
#include <cuda_runtime.h>
#include <cuda_bf16.h>
#include <cuda.h>
#include <stdint.h>

namespace hk {

constexpr int SEQ = 2048, DM = 512, FF = 1376;
constexpr int NCTA = 132;
constexpr int NTHREADS = 384;
constexpr uint32_t SLOT = 16384;
constexpr uint32_t OFF_A = 0, OFF_B = 8 * SLOT, OFF_MISC = 14 * SLOT;
constexpr uint32_t BAR_FULLA = OFF_MISC + 0, BAR_EMPTYA = OFF_MISC + 64, BAR_FULLB = OFF_MISC + 128,
                   BAR_EMPTYB = OFF_MISC + 176, BAR_CS1 = OFF_MISC + 224, BAR_CS3 = OFF_MISC + 232,
                   BAR_CSQ = OFF_MISC + 240, BAR_CSV = OFF_MISC + 248,
                   BAR_STG = OFF_MISC + 256,
                   BAR_KVW = OFF_MISC + 280, BAR_KVR = OFF_MISC + 288,
                   BAR_CSG = OFF_MISC + 296;
constexpr uint32_t OFF_CS1 = OFF_MISC + 384;
constexpr uint32_t OFF_CS3 = OFF_CS1 + 1024;
constexpr uint32_t OFF_XST = OFF_CS3;
constexpr uint32_t SMEM_BYTES = OFF_CS3 + 1536;
#define KORD(i, j) ((i) == 0 ? (j) : (i) - ((i) <= (j)))
constexpr int NB = 6;
constexpr int NPRE = 3, AHEAD = 3, AHEADA = 5;
constexpr int PF_DELAY = 2;

constexpr int ACC_SIZE = 3 * 256 * 4;

__device__ __align__(1024) uint4 g_act[5 * 128 * 1024];
__device__ __align__(128) unsigned long long g_hstat[SEQ * 16];
__device__ __align__(128) unsigned long long g_xstat[SEQ * 2];
__device__ __align__(128) float g_acc[8 * ACC_SIZE];
__device__ __align__(128) unsigned long long g_cs[8 * 6 * 128];
__device__ __align__(128) unsigned g_flag[16 * 5 * 32];
__device__ unsigned g_epoch = 1;

#define TL(i, pred) do {} while (0)
#define TLG(i, pred) do {} while (0)

struct Params {
    CUtensorMap tx, twq, two, twg, twu, twd, twd48, tout;
    const __nv_bfloat16 *x, *wqkv, *wphi, *wo, *wg, *wu, *wd;
    __nv_bfloat16* out;
    unsigned zero;
};

__device__ __forceinline__ uint32_t smem_u32(const void* p) { return (uint32_t)__cvta_generic_to_shared(p); }
__device__ __forceinline__ void mbar_init(uint32_t bar, uint32_t cnt) {
    asm volatile("mbarrier.init.shared::cta.b64 [%0], %1;" ::"r"(bar), "r"(cnt) : "memory");
}
__device__ __forceinline__ void mbar_expect_tx(uint32_t bar, uint32_t bytes) {
    asm volatile("mbarrier.arrive.expect_tx.shared::cta.b64 _, [%0], %1;" ::"r"(bar), "r"(bytes) : "memory");
}
__device__ __forceinline__ void mbar_arrive(uint32_t bar) {
    asm volatile("mbarrier.arrive.shared::cta.b64 _, [%0];" ::"r"(bar) : "memory");
}
__device__ __forceinline__ void mbar_arrive_if(uint32_t bar, bool pred) {
    asm volatile("{.reg .pred p; setp.ne.u32 p, %1, 0; @p mbarrier.arrive.shared::cta.b64 _, [%0];}" ::"r"(bar), "r"((uint32_t)pred) : "memory");
}
__device__ __forceinline__ void trap_if_gt(uint32_t v, uint32_t lim) {
    asm volatile("{.reg .pred p; setp.gt.u32 p, %0, %1; @p trap;}" ::"r"(v), "r"(lim));
}
__device__ __forceinline__ void mbar_wait(uint32_t bar, uint32_t parity) {
    asm volatile("{\n"
                 ".reg .pred P1, P2;\n"
                 ".reg .u32 c;\n"
                 "mov.u32 c, 0;\n"
                 "LAB_WAIT:\n"
                 "mbarrier.try_wait.parity.shared::cta.b64 P1, [%0], %1;\n"
                 "@P1 bra LAB_DONE;\n"
                 "add.u32 c, c, 1;\n"
                 "setp.gt.u32 P2, c, 1048576;\n"
                 "@P2 trap;\n"
                 "bra LAB_WAIT;\n"
                 "LAB_DONE:\n"
                 "}" ::"r"(bar), "r"(parity) : "memory");
}
__device__ __forceinline__ void mbar_waitc(uint32_t bar, uint32_t parity) {
    asm volatile("{\n"
                 ".reg .pred P1;\n"
                 "LAB_WAIT:\n"
                 "mbarrier.try_wait.parity.shared::cta.b64 P1, [%0], %1;\n"
                 "@!P1 bra LAB_WAIT;\n"
                 "}" ::"r"(bar), "r"(parity) : "memory");
}
__device__ __forceinline__ void tma2d(uint32_t dst, const CUtensorMap* tm, uint32_t bar, int c0, int c1) {
    asm volatile("cp.async.bulk.tensor.2d.shared::cluster.global.mbarrier::complete_tx::bytes [%0], [%1, {%3, %4}], [%2];"
                 ::"r"(dst), "l"(tm), "r"(bar), "r"(c0), "r"(c1) : "memory");
}
__device__ __forceinline__ void tma2d_mc(uint32_t dst, const CUtensorMap* tm, uint32_t bar, int c0, int c1) {
    asm volatile("cp.async.bulk.tensor.2d.shared::cluster.global.mbarrier::complete_tx::bytes.multicast::cluster [%0], [%1, {%3, %4}], [%2], %5;"
                 ::"r"(dst), "l"(tm), "r"(bar), "r"(c0), "r"(c1), "h"((uint16_t)3) : "memory");
}
__device__ __forceinline__ uint32_t mapa(uint32_t addr, uint32_t rank) {
    uint32_t r; asm("mapa.shared::cluster.u32 %0, %1, %2;" : "=r"(r) : "r"(addr), "r"(rank)); return r;
}
__device__ __forceinline__ void mbar_arrive_cl_if(uint32_t cbar, bool pred) {
    asm volatile("{.reg .pred p; setp.ne.u32 p, %1, 0; @p mbarrier.arrive.shared::cluster.b64 _, [%0];}" ::"r"(cbar), "r"((uint32_t)pred) : "memory");
}
__device__ __forceinline__ bool elect_one() {
    uint32_t ok;
    asm volatile("{.reg .pred p; elect.sync _|p, 0xffffffff; selp.u32 %0, 1, 0, p;}" : "=r"(ok));
    return ok;
}
__device__ __forceinline__ void prefetch_tmap(const CUtensorMap* tm) {
    asm volatile("prefetch.tensormap [%0];" ::"l"(tm) : "memory");
}
__device__ __forceinline__ void prefetch_l2(const void* p, uint32_t bytes) {
    asm volatile("cp.async.bulk.prefetch.L2.global [%0], %1;" ::"l"(p), "r"(bytes) : "memory");
}
__device__ __forceinline__ unsigned ld_relaxed(const unsigned* p) {
    unsigned v; asm volatile("ld.relaxed.gpu.global.u32 %0, [%1];" : "=r"(v) : "l"(p)); return v;
}
__device__ __forceinline__ void fence_async_smem() { asm volatile("fence.proxy.async.shared::cta;" ::: "memory"); }
__device__ __forceinline__ uint32_t readback(const void* p) {
    uint32_t v; asm volatile("ld.relaxed.gpu.global.u32 %0, [%1];" : "=r"(v) : "l"(p) : "memory"); return v;
}
__device__ __forceinline__ void wait_count(const unsigned* p, unsigned target) {
    uint32_t it = 0;
    while ((int)(readback(p) - target) < 0) trap_if_gt(++it, 1u << 22);
}
__device__ __forceinline__ void red_f32x4(float* p, float a, float b, float c, float d) {
    asm volatile("red.relaxed.gpu.global.add.v4.f32 [%0], {%1, %2, %3, %4};" ::"l"(p), "f"(a), "f"(b), "f"(c), "f"(d) : "memory");
}
__device__ __forceinline__ float4 ld_l2_f4(const float* p) {
    float4 v;
    asm volatile("ld.relaxed.gpu.global.v4.f32 {%0,%1,%2,%3}, [%4];" : "=f"(v.x), "=f"(v.y), "=f"(v.z), "=f"(v.w) : "l"(p) : "memory");
    return v;
}
__device__ __forceinline__ void stg128(void* p, uint32_t a, uint32_t b, uint32_t c, uint32_t d) {
    asm volatile("st.global.v4.u32 [%0], {%1,%2,%3,%4};" ::"l"(p), "r"(a), "r"(b), "r"(c), "r"(d) : "memory");
}
__device__ __forceinline__ uint4 lds128(uint32_t a) {
    uint4 v;
    asm volatile("ld.shared.v4.u32 {%0,%1,%2,%3}, [%4];" : "=r"(v.x), "=r"(v.y), "=r"(v.z), "=r"(v.w) : "r"(a) : "memory");
    return v;
}
__device__ __forceinline__ float2 lds_f2(uint32_t a) {
    float2 v;
    asm volatile("ld.shared.v2.f32 {%0,%1}, [%2];" : "=f"(v.x), "=f"(v.y) : "r"(a) : "memory");
    return v;
}
__device__ __forceinline__ void sts_f2(uint32_t a, float x, float y) {
    asm volatile("st.shared.v2.f32 [%0], {%1,%2};" ::"r"(a), "f"(x), "f"(y) : "memory");
}
__device__ __forceinline__ void sts64(uint32_t a, uint32_t x, uint32_t y) {
    asm volatile("st.shared.v2.u32 [%0], {%1,%2};" ::"r"(a), "r"(x), "r"(y) : "memory");
}
__device__ __forceinline__ void sts128(uint32_t a, uint32_t x, uint32_t y, uint32_t z, uint32_t w) {
    asm volatile("st.shared.v4.u32 [%0], {%1,%2,%3,%4};" ::"r"(a), "r"(x), "r"(y), "r"(z), "r"(w) : "memory");
}
__device__ __forceinline__ void stsm4(uint32_t a, uint32_t r0, uint32_t r1, uint32_t r2, uint32_t r3) {
    asm volatile("stmatrix.sync.aligned.m8n8.x4.shared.b16 [%0], {%1,%2,%3,%4};" ::"r"(a), "r"(r0), "r"(r1), "r"(r2), "r"(r3) : "memory");
}
__device__ __forceinline__ void stsm4t(uint32_t a, uint32_t r0, uint32_t r1, uint32_t r2, uint32_t r3) {
    asm volatile("stmatrix.sync.aligned.m8n8.x4.trans.shared.b16 [%0], {%1,%2,%3,%4};" ::"r"(a), "r"(r0), "r"(r1), "r"(r2), "r"(r3) : "memory");
}
__device__ __forceinline__ void tma_store2d(const CUtensorMap* tm, uint32_t src, int c0, int c1) {
    asm volatile("cp.async.bulk.tensor.2d.global.shared::cta.bulk_group [%0, {%2, %3}], [%1];" ::"l"(tm), "r"(src), "r"(c0), "r"(c1) : "memory");
    asm volatile("cp.async.bulk.commit_group;" ::: "memory");
}
__device__ __forceinline__ void ldsm4(uint32_t a, uint32_t& r0, uint32_t& r1, uint32_t& r2, uint32_t& r3) {
    asm volatile("ldmatrix.sync.aligned.m8n8.x4.shared.b16 {%0,%1,%2,%3}, [%4];" : "=r"(r0), "=r"(r1), "=r"(r2), "=r"(r3) : "r"(a) : "memory");
}
__device__ __forceinline__ void ldsm4t(uint32_t a, uint32_t& r0, uint32_t& r1, uint32_t& r2, uint32_t& r3) {
    asm volatile("ldmatrix.sync.aligned.m8n8.x4.trans.shared.b16 {%0,%1,%2,%3}, [%4];" : "=r"(r0), "=r"(r1), "=r"(r2), "=r"(r3) : "r"(a) : "memory");
}
__device__ __forceinline__ void mma16816(float* c, const uint32_t* a, uint32_t b0, uint32_t b1) {
    asm("mma.sync.aligned.m16n8k16.row.col.f32.bf16.bf16.f32 {%0,%1,%2,%3}, {%4,%5,%6,%7}, {%8,%9}, {%0,%1,%2,%3};"
                 : "+f"(c[0]), "+f"(c[1]), "+f"(c[2]), "+f"(c[3])
                 : "r"(a[0]), "r"(a[1]), "r"(a[2]), "r"(a[3]), "r"(b0), "r"(b1));
}
__device__ __forceinline__ uint32_t pack_bf16(float lo, float hi) {
    uint32_t r; asm("cvt.rn.bf16x2.f32 %0, %1, %2;" : "=r"(r) : "f"(hi), "f"(lo)); return r;
}
__device__ __forceinline__ float bf_lo(uint32_t w) { return __uint_as_float(w << 16); }
__device__ __forceinline__ float bf_hi(uint32_t w) { return __uint_as_float(w & 0xffff0000u); }
__device__ __forceinline__ float ex2(float x) { float r; asm("ex2.approx.ftz.f32 %0, %1;" : "=f"(r) : "f"(x)); return r; }
__device__ __forceinline__ float rcp(float x) { float r; asm("rcp.approx.ftz.f32 %0, %1;" : "=f"(r) : "f"(x)); return r; }
__device__ __forceinline__ void bar_sync(int id, int n) { asm volatile("bar.sync %0, %1;" ::"r"(id), "r"(n) : "memory"); }

typedef unsigned long long desc_t;
__device__ __forceinline__ desc_t desc_lo(uint32_t addr) { return (desc_t)(((addr & 0x3FFFF) >> 4) | (512u << 16)) | (0x40000040ull << 32); }
__device__ __forceinline__ void wg_fence() { asm volatile("wgmma.fence.sync.aligned;" ::: "memory"); }
__device__ __forceinline__ void wg_commit() { asm volatile("wgmma.commit_group.sync.aligned;" ::: "memory"); }
template <int N> __device__ __forceinline__ void wg_wait() { asm volatile("wgmma.wait_group.sync.aligned %0;" ::"n"(N) : "memory"); }
template <int N> __device__ __forceinline__ void fence_acc(float* d) {
#pragma unroll
    for (int i = 0; i < N; i++) asm volatile("" : "+f"(d[i])::"memory");
}
#define R4(o) "+f"(d[o + 0]), "+f"(d[o + 1]), "+f"(d[o + 2]), "+f"(d[o + 3])
#define R8(o) R4(o), R4(o + 4)
__device__ __forceinline__ void wgmma_n128(float* d, desc_t da, desc_t db, int sc) {
    asm volatile("{.reg .pred p; setp.ne.b32 p, %66, 0;\n"
                 "wgmma.mma_async.sync.aligned.m64n128k16.f32.bf16.bf16 {%0,%1,%2,%3,%4,%5,%6,%7,%8,%9,%10,%11,%12,%13,%14,%15,%16,%17,%18,%19,%20,%21,%22,%23,%24,%25,%26,%27,%28,%29,%30,%31,"
                 "%32,%33,%34,%35,%36,%37,%38,%39,%40,%41,%42,%43,%44,%45,%46,%47,%48,%49,%50,%51,%52,%53,%54,%55,%56,%57,%58,%59,%60,%61,%62,%63}, %64, %65, p, 1, 1, 0, 1;}"
                 : R8(0), R8(8), R8(16), R8(24), R8(32), R8(40), R8(48), R8(56)
                 : "l"(da), "l"(db), "r"(sc));
}
__device__ __forceinline__ void wgmma_n112(float* d, desc_t da, desc_t db, int sc) {
    asm volatile("{.reg .pred p; setp.ne.b32 p, %58, 0;\n"
                 "wgmma.mma_async.sync.aligned.m64n112k16.f32.bf16.bf16 {%0,%1,%2,%3,%4,%5,%6,%7,%8,%9,%10,%11,%12,%13,%14,%15,%16,%17,%18,%19,%20,%21,%22,%23,%24,%25,%26,%27,%28,%29,%30,%31,%32,%33,%34,%35,%36,%37,%38,%39,%40,%41,%42,%43,%44,%45,%46,%47,%48,%49,%50,%51,%52,%53,%54,%55}, %56, %57, p, 1, 1, 0, 1;}"
                 : R8(0), R8(8), R8(16), R8(24), R8(32), R8(40), R8(48)
                 : "l"(da), "l"(db), "r"(sc));
}
__device__ __forceinline__ void wgmma_n128_tn(float* d, desc_t da, desc_t db, int sc) {
    asm volatile("{.reg .pred p; setp.ne.b32 p, %66, 0;\n"
                 "wgmma.mma_async.sync.aligned.m64n128k16.f32.bf16.bf16 {%0,%1,%2,%3,%4,%5,%6,%7,%8,%9,%10,%11,%12,%13,%14,%15,%16,%17,%18,%19,%20,%21,%22,%23,%24,%25,%26,%27,%28,%29,%30,%31,%32,%33,%34,%35,%36,%37,%38,%39,%40,%41,%42,%43,%44,%45,%46,%47,%48,%49,%50,%51,%52,%53,%54,%55,%56,%57,%58,%59,%60,%61,%62,%63}, %64, %65, p, 1, 1, 1, 0;}"
                 : R8(0), R8(8), R8(16), R8(24), R8(32), R8(40), R8(48), R8(56)
                 : "l"(da), "l"(db), "r"(sc));
}
__device__ __forceinline__ void wgmma_n64(float* d, desc_t da, desc_t db, int sc) {
    asm volatile("{.reg .pred p; setp.ne.b32 p, %34, 0;\n"
                 "wgmma.mma_async.sync.aligned.m64n64k16.f32.bf16.bf16 {%0,%1,%2,%3,%4,%5,%6,%7,%8,%9,%10,%11,%12,%13,%14,%15,%16,%17,%18,%19,%20,%21,%22,%23,%24,%25,%26,%27,%28,%29,%30,%31}, %32, %33, p, 1, 1, 0, 1;}"
                 : R8(0), R8(8), R8(16), R8(24)
                 : "l"(da), "l"(db), "r"(sc));
}
__device__ __forceinline__ void wgmma_n40_tt(float* d, desc_t da, desc_t db, int sc) {
    asm volatile("{.reg .pred p; setp.ne.b32 p, %22, 0;\n"
                 "wgmma.mma_async.sync.aligned.m64n40k16.f32.bf16.bf16 {%0,%1,%2,%3,%4,%5,%6,%7,%8,%9,%10,%11,%12,%13,%14,%15,%16,%17,%18,%19}, %20, %21, p, 1, 1, 1, 1;}"
                 : R8(0), R8(8), R4(16)
                 : "l"(da), "l"(db), "r"(sc));
}

__device__ __forceinline__ void wgmma_n8_tt(float* d, desc_t da, desc_t db, int sc) {
    asm volatile("{.reg .pred p; setp.ne.b32 p, %6, 0;\n"
                 "wgmma.mma_async.sync.aligned.m64n8k16.f32.bf16.bf16 {%0,%1,%2,%3}, %4, %5, p, 1, 1, 1, 1;}"
                 : R4(0)
                 : "l"(da), "l"(db), "r"(sc));
}

__device__ __forceinline__ void signal_after(unsigned* cnt, uint32_t ack, uint32_t zero, bool pred) {
    asm volatile("{.reg .pred p; setp.ne.u32 p, %2, 0; @p red.relaxed.gpu.global.add.u32 [%0], %1;}"
                 ::"l"(cnt), "r"((ack & zero) + 1), "r"((uint32_t)pred) : "memory");
}
__device__ __forceinline__ void signal_late(unsigned* cnt, const uint32_t* a, uint32_t zero, bool pred) {
    uint32_t v;
    asm volatile("{.reg .b32 t; lop3.b32 t, %1, %2, %3, 0xfe; or.b32 %0, t, %4;}"
                 : "=r"(v) : "r"(a[0]), "r"(a[1]), "r"(a[2]), "r"(a[3]));
    signal_after(cnt, v, zero, pred);
}
__device__ __forceinline__ void mma16816_z(float* c, const uint32_t* a, uint32_t b0, uint32_t b1) {
    asm("mma.sync.aligned.m16n8k16.row.col.f32.bf16.bf16.f32 {%0,%1,%2,%3}, {%4,%5,%6,%7}, {%8,%9}, {%10,%10,%10,%10};"
                 : "=f"(c[0]), "=f"(c[1]), "=f"(c[2]), "=f"(c[3])
                 : "r"(a[0]), "r"(a[1]), "r"(a[2]), "r"(a[3]), "r"(b0), "r"(b1), "f"(0.f));
}
__device__ __forceinline__ uint32_t max2(uint32_t a, uint32_t b) { uint32_t r; asm("max.bf16x2 %0, %1, %2;" : "=r"(r) : "r"(a), "r"(b)); return r; }
__device__ __forceinline__ uint32_t min2(uint32_t a, uint32_t b) { uint32_t r; asm("min.bf16x2 %0, %1, %2;" : "=r"(r) : "r"(a), "r"(b)); return r; }
__device__ __forceinline__ void mbar_arrive_n_if(uint32_t bar, uint32_t n, bool pred) {
    asm volatile("{.reg .pred p; setp.ne.u32 p, %1, 0; @p mbarrier.arrive.shared::cta.b64 _, [%0], %2;}" ::"r"(bar), "r"((uint32_t)pred), "r"(n) : "memory");
}
__device__ __forceinline__ float4 lds_f4(uint32_t a) {
    float4 v;
    asm volatile("ld.shared.v4.f32 {%0,%1,%2,%3}, [%4];" : "=f"(v.x), "=f"(v.y), "=f"(v.z), "=f"(v.w) : "r"(a) : "memory");
    return v;
}
__device__ __forceinline__ void lds_f4_if(float4& v, uint32_t a, bool pred) {
    asm volatile("{.reg .pred p; setp.ne.u32 p, %5, 0; @p ld.shared.v4.f32 {%0,%1,%2,%3}, [%4];}"
                 : "+f"(v.x), "+f"(v.y), "+f"(v.z), "+f"(v.w) : "r"(a), "r"((uint32_t)pred) : "memory");
}
__device__ __forceinline__ uint4 ld_tagged_rlx(const unsigned long long* p) {
    unsigned long long a, b;
    asm volatile("ld.relaxed.gpu.global.v2.b64 {%0,%1}, [%2];" : "=l"(a), "=l"(b) : "l"(p) : "memory");
    return make_uint4((unsigned)a, (unsigned)(a >> 32), (unsigned)b, (unsigned)(b >> 32));
}
__device__ __forceinline__ void sts32(uint32_t a, uint32_t x) { asm volatile("st.shared.u32 [%0], %1;" ::"r"(a), "r"(x) : "memory"); }
__device__ __forceinline__ void fetch_tagged(const unsigned long long* src, uint32_t dst, unsigned epoch) {
    uint4 v;
    uint32_t it = 0;
    while (true) {
        v = ld_tagged_rlx(src);
        if (!__any_sync(0xffffffffu, v.y != epoch || v.w != epoch)) break;
        __nanosleep(60);
        trap_if_gt(++it, 1u << 22);
    }
    sts64(dst, v.x, v.z);
}
__device__ __forceinline__ void st_tagged_if(unsigned long long* p, float a, float b, unsigned tag, bool pred) {
    const unsigned long long t = (unsigned long long)tag << 32;
    asm volatile("{.reg .pred p; setp.ne.u32 p, %3, 0; @p st.relaxed.gpu.global.v2.b64 [%0], {%1,%2};}"
                 ::"l"(p), "l"(t | __float_as_uint(a)), "l"(t | __float_as_uint(b)), "r"((uint32_t)pred) : "memory");
}

__device__ __forceinline__ void store_tile(uint32_t tile_rows, uint4* gdst, const uint32_t* lo, const uint32_t* hi, int lane, uint32_t* ack) {
    const int r = lane & 15;
#pragma unroll
    for (int b = 0; b < 4; b++)
        stsm4(tile_rows + r * 128 + (((2 * b + (lane >> 4)) ^ (r & 7)) << 4), lo[2 * b], hi[2 * b], lo[2 * b + 1], hi[2 * b + 1]);
    fence_async_smem();
    __syncwarp();
#pragma unroll
    for (int i = 0; i < 4; i++) {
        const uint4 v = lds128(tile_rows + i * 512 + lane * 16);
        stg128(gdst + 32 * i, v.x, v.y, v.z, v.w);
    }
#pragma unroll
    for (int i = 0; i < 4; i++) ack[i] = readback(gdst + 32 * i);
}

__device__ __forceinline__ void feature_maps(const uint32_t* a, const uint32_t* wb, float c0, float c1, uint32_t* plus, uint32_t* minus) {
    uint32_t P[16], mx[4], mn[4];
#pragma unroll
    for (int h = 0; h < 4; h++) {
        float p[8];
        mma16816_z(p, a + 4 * h, wb[4 * h], wb[4 * h + 1]);
        mma16816_z(p + 4, a + 4 * h, wb[4 * h + 2], wb[4 * h + 3]);
        P[4 * h] = pack_bf16(p[0], p[2]); P[4 * h + 1] = pack_bf16(p[1], p[3]);
        P[4 * h + 2] = pack_bf16(p[4], p[6]); P[4 * h + 3] = pack_bf16(p[5], p[7]);
        mx[h] = max2(max2(P[4 * h], P[4 * h + 1]), max2(P[4 * h + 2], P[4 * h + 3]));
        mn[h] = min2(min2(P[4 * h], P[4 * h + 1]), min2(P[4 * h + 2], P[4 * h + 3]));
    }
#pragma unroll
    for (int s = 1; s <= 2; s <<= 1) {
        uint32_t tx[4], tn[4];
#pragma unroll
        for (int h = 0; h < 4; h++) { tx[h] = __shfl_xor_sync(0xffffffffu, mx[h], s); tn[h] = __shfl_xor_sync(0xffffffffu, mn[h], s); }
#pragma unroll
        for (int h = 0; h < 4; h++) { mx[h] = max2(mx[h], tx[h]); mn[h] = min2(mn[h], tn[h]); }
    }
#pragma unroll
    for (int h = 0; h < 4; h++) {
        const float mx0 = bf_lo(mx[h]) * c0, mx1 = bf_hi(mx[h]) * c1, mn0 = bf_lo(mn[h]) * c0, mn1 = bf_hi(mn[h]) * c1;
        float ep[8], em[8];
#pragma unroll
        for (int i = 0; i < 8; i++) {
            const bool r1 = (i & 2);
            const uint32_t w = P[4 * h + (i >> 2) * 2 + (i & 1)];
            const float p = r1 ? bf_hi(w) : bf_lo(w);
            ep[i] = ex2(fmaf(p, r1 ? c1 : c0, r1 ? -mx1 : -mx0));
            em[i] = ex2(fmaf(p, r1 ? -c1 : -c0, r1 ? mn1 : mn0));
        }
        float sp[4], sm[4];
        uint32_t tp[4], tm[4];
#pragma unroll
        for (int i = 0; i < 4; i++) { tp[i] = pack_bf16(ep[2 * i], ep[2 * i + 1]); tm[i] = pack_bf16(em[2 * i], em[2 * i + 1]); }
        mma16816_z(sp, tp, 0x3f803f80u, 0x3f803f80u);
        mma16816_z(sm, tm, 0x3f803f80u, 0x3f803f80u);
        const float r0 = rcp(sp[0] * sm[0]), r1 = rcp(sp[2] * sm[2]);
        const float rs[4] = {r0 * sm[0], r1 * sm[2], r0 * sp[0], r1 * sp[2]};
#pragma unroll
        for (int i = 0; i < 4; i++) {
            plus[4 * h + i] = pack_bf16(ep[2 * i] * rs[i & 1], ep[2 * i + 1] * rs[i & 1]);
            minus[4 * h + i] = pack_bf16(em[2 * i] * rs[2 + (i & 1)], em[2 * i + 1] * rs[2 + (i & 1)]);
        }
    }
}

template <bool SCALE>
__device__ __forceinline__ void ln_frag(const float* acc, uint32_t cs_addr, float rs0, float nm0, float rs1, float nm1, uint32_t* a) {
    const float2 c0 = lds_f2(cs_addr), c1 = lds_f2(cs_addr + 32);
    const float s0 = SCALE ? rs0 : 1.f, s1 = SCALE ? rs1 : 1.f;
    a[0] = pack_bf16(fmaf(nm0, c0.x, acc[0]) * s0, fmaf(nm0, c0.y, acc[1]) * s0);
    a[1] = pack_bf16(fmaf(nm1, c0.x, acc[2]) * s1, fmaf(nm1, c0.y, acc[3]) * s1);
    a[2] = pack_bf16(fmaf(nm0, c1.x, acc[4]) * s0, fmaf(nm0, c1.y, acc[5]) * s0);
    a[3] = pack_bf16(fmaf(nm1, c1.x, acc[6]) * s1, fmaf(nm1, c1.y, acc[7]) * s1);
}

template <int UP>
__device__ __forceinline__ uint32_t hh_pair(const float* ag, float4 cs, float nmean) {
    const float g0 = fmaf(nmean, cs.x, ag[0]), g1 = fmaf(nmean, cs.y, ag[1]);
    const float u0 = fmaf(nmean, cs.z, ag[UP]), u1 = fmaf(nmean, cs.w, ag[UP + 1]);
    return pack_bf16(g0 * u0, g1 * u1);
}
template <int NTP>
__device__ __forceinline__ void hh_stage(const float* acc, const float4* cs, float nm0, float nm1, uint32_t stg, int lane) {
#pragma unroll
    for (int tp = 0; tp < NTP; tp++)
        stsm4(stg + (lane & 15) * 128 + (((2 * tp + (lane >> 4)) ^ (lane & 7)) << 4), hh_pair<32>(acc + 8 * tp, cs[2 * tp], nm0),
              hh_pair<32>(acc + 8 * tp + 2, cs[2 * tp], nm1), hh_pair<32>(acc + 8 * tp + 4, cs[2 * tp + 1], nm0),
              hh_pair<32>(acc + 8 * tp + 6, cs[2 * tp + 1], nm1));
    fence_async_smem();
    __syncwarp();
}

template <int TP0, int TP1>
__device__ __forceinline__ void hh_stage2(const float* acc, const float4* cs, float nm0, float nm1, uint32_t stg, int lane) {
#pragma unroll
    for (int tp = TP0; tp < TP1; tp++)
        stsm4(stg + (lane & 15) * 128 + (((2 * tp + (lane >> 4)) ^ (lane & 7)) << 4), hh_pair<32>(acc + 8 * tp, cs[2 * tp], nm0),
              hh_pair<32>(acc + 8 * tp + 2, cs[2 * tp], nm1), hh_pair<32>(acc + 8 * tp + 4, cs[2 * tp + 1], nm0),
              hh_pair<32>(acc + 8 * tp + 6, cs[2 * tp + 1], nm1));
}
struct Ring {
    int slot; uint32_t phase;
    __device__ __forceinline__ void adv() { if (++slot == NB) { slot = 0; phase ^= 1; } }
    __device__ __forceinline__ void adv5() { slot += slot == 3; adv(); }
};

__global__ void __cluster_dims__(2, 1, 1) __launch_bounds__(NTHREADS, 1) fused_kernel(const __grid_constant__ Params P) {
    extern __shared__ __align__(1024) uint8_t smem_raw[];
    const uint32_t sb = smem_u32(smem_raw);
    const int tid = threadIdx.x, lane = tid & 31;
    const int warp = __shfl_sync(0xffffffffu, tid >> 5, 0);
    const unsigned rank = blockIdx.x & 1;
    int m, j;
    {
        const int t = (int)(blockIdx.x >> 1) - 4, u = t - 32, r7 = (u * 37) >> 8;
        const int gp = t < 32 ? (t & 7) - 1 : u - 7 * r7;
        j = t < 0 ? t + 8 : (t < 32 ? t >> 3 : 4 + r7);
        m = ((t < 0 || gp < 0) ? 14 : 2 * gp) + rank;
        if (t >= 60) { m = 16; j = blockIdx.x - 128; }
    }
    const unsigned role = m * 8 + j;
    const bool helper = m == 16;

    TL(0, tid == 0); TLG(0, tid == 0);
    float* const acc_j = g_acc + j * ACC_SIZE;
    if ((warp & ~1) == 8 && elect_one()) {
        const uint32_t bar = sb + (warp == 8 ? BAR_FULLB : BAR_FULLA);
#pragma unroll
        for (int i = 0; i < 8; i++) if (i < NB || warp == 9) mbar_init(bar + 8 * i, 1);
        if (!helper) {
#pragma unroll 1
            for (int i = 0; i < NPRE; i++) {
                mbar_expect_tx(bar + 8 * i, SLOT);
                if (warp == 8) {
                    tma2d(sb + OFF_B + i * SLOT, &P.twq, bar + 8 * i, DM + 64 * j, 64 * i);
                    tma2d(sb + OFF_B + i * SLOT + 8192, &P.twq, bar + 8 * i, 2 * DM + 64 * j, 64 * i);
                } else {
                    tma2d(sb + OFF_A + i * SLOT, &P.tx, bar + 8 * i, 64 * i, 128 * m);
                }
            }
        }
    }
    __syncwarp();

    if (warp >= 8) {
        asm volatile("setmaxnreg.dec.sync.aligned.u32 72;");
        if (elect_one()) {
            if (warp < 10) {
            } else if (warp == 10) {
#pragma unroll
                for (int i = 0; i < 12; i++) mbar_init(sb + BAR_CS1 + 8 * i, i < 2 || i >= 8 ? 64 : (i < 4 ? 32 : 8));
                trap_if_gt(sb & 1023, 0);
            } else {
#pragma unroll
                for (int i = 0; i < 14; i++) mbar_init(sb + (i < 8 ? BAR_EMPTYA : BAR_EMPTYB - 64) + 8 * i, i < 8 ? 8 : 16);
            }
            asm volatile("fence.mbarrier_init.release.cluster;" ::: "memory");
        }
        __syncwarp();
        asm volatile("barrier.cluster.arrive.relaxed.aligned;" ::: "memory");
        const unsigned epoch = ld_relaxed(&g_epoch);
        bar_sync(0, NTHREADS);
        if (helper) {
            if (elect_one()) {
#pragma unroll 1
                for (int i = warp - 8; i < 72; i += 4) {
                    const uint32_t full = sb + BAR_FULLA + 8 * (i & 7), dst = sb + OFF_A + (i & 7) * SLOT;
                    const int n = i >> 1, jj = 2 * j + (i & 1);
                    const bool qkv = n < 12;
                    const int c0 = qkv ? (n < 8 ? DM + 128 * (n & 4) : 0) + 64 * jj : 176 * jj + 8 * ((n - 12) & ~7);
                    const int r0 = qkv ? 128 * (n & 3) : 64 * ((n - 12) & 7);
                    mbar_wait(sb + BAR_EMPTYA + 8 * (i & 7), ((i >> 3) & 1) ^ 1);
                    mbar_expect_tx(full, SLOT);
                    tma2d(dst, qkv ? &P.twq : &P.twg, full, c0, r0);
                    tma2d(dst + 8192, qkv ? &P.twq : &P.twu, full, c0, qkv ? r0 + 64 : r0);
                }
                prefetch_l2(P.wd + (size_t)(4 * j + warp - 8) * 44032, 88064);
            }
            return;
        }
        if (warp == 8) {
            asm volatile("barrier.cluster.wait.aligned;" ::: "memory");
            if (elect_one()) {
                if (m >= 6)
                    asm volatile("cp.async.bulk.prefetch.tensor.2d.L2.global [%0, {%1, %2}];" ::"l"(&P.twq), "r"(DM + DM * (m & 1) + 64 * j), "r"(64 * (m >> 1)) : "memory");
                if (j >= 3)
                    asm volatile("cp.async.bulk.prefetch.tensor.2d.L2.global [%0, {%1, %2}];" ::"l"(&P.tx), "r"(64 * j), "r"(128 * m) : "memory");
                Ring r{NPRE, 0};
                const uint32_t dst = sb + OFF_B + rank * 8192;
#define B_LOADN(TM, C0, R0, NB_)                                                                                \
        mbar_waitc(sb + BAR_EMPTYB + 8 * r.slot, r.phase ^ 1);                                              \
        mbar_expect_tx(sb + BAR_FULLB + 8 * r.slot, NB_);                                                   \
        tma2d_mc(dst + r.slot * SLOT, TM, sb + BAR_FULLB + 8 * r.slot, C0, R0);
#define B_LOAD(TM, C0, R0) B_LOADN(TM, C0, R0, SLOT)
#pragma unroll 1
                for (int i = NPRE; i < 8; i++) {
                    if (i >= AHEAD && i < 6) mbar_waitc(sb + BAR_FULLB + 8 * (i - AHEAD), 0);
                    B_LOAD(&P.twq, DM + DM * rank + 64 * j, 64 * i)
                    r.adv();
                }
#pragma unroll 1
                for (int i = 8; i < 18; i++) {
                    if (i == 9 || i == 10) {
                        mbar_waitc(sb + BAR_EMPTYB + 8 * r.slot, r.phase ^ 1);
                        mbar_arrive(sb + BAR_FULLB + 8 * r.slot);
                    } else {
                        const int e = 2 * (i - 14) + rank, b = (i == 8 ? 0 : i - 10) ^ (i < 12 && j < 2);
                        B_LOAD(i < 14 ? &P.twq : &P.two, 64 * j, 64 * (i < 14 ? 2 * b + rank : KORD(e, j)))
                    }
                    r.adv();
                }
#pragma unroll 1
                for (int i = 0; i < 24; i++) {
                    B_LOAD(&P.twg + rank, 176 * j + 8 * (i & ~7), 64 * (i < 8 ? KORD(i, j) : i & 7))
                    r.adv5();
                }
#pragma unroll 1
                for (int i = 0; i < 12; i++) {
                    B_LOADN(&P.twd + (i >> 3), 64 * j, 176 * (2 * (i & 3) + rank) + 64 * (i >> 2), i < 8 ? SLOT : 12288)
                    r.adv5();
                }
            }
            return;
        }
        if (warp == 9) {
            if (elect_one()) {
#pragma unroll 1
                for (int i = NPRE; i < 8; i++) {
                    if (i >= AHEADA) mbar_wait(sb + BAR_FULLA + 8 * (i - AHEADA), 0);
                    mbar_expect_tx(sb + BAR_FULLA + 8 * i, SLOT);
                    tma2d(sb + OFF_A + i * SLOT, &P.tx, sb + BAR_FULLA + 8 * i, 64 * i, 128 * m);
                }
#pragma unroll 1
                for (int i = 2; i < 8; i++) prefetch_tmap(&P.tx + i);
                unsigned nf = 0;
#pragma unroll 1
                for (int r = 1; r < 6; r++) {
                    const int skip = r < 3 ? j : 8;
                    const uint32_t bytes = r == 5 ? 12288 : SLOT;
                    const uint4* src = g_act + ((r - 1) * 128 + m * 8) * 1024;
                    const unsigned* fl = g_flag + (m * 5 + r - 1) * 32;
                    if (r < 4) mbar_wait(sb + BAR_EMPTYA + 8 * (r == 3 ? PF_DELAY : 3 - 2 * (j == 3)), (r - 1) & 1);
                    const unsigned tgt = epoch * (r < 3 ? 64 : 8);
                    if (nf != tgt) wait_count(fl, tgt);
                    TL(64 + r, true);
#pragma unroll 1
                    for (int t = 0; t < 8; t++) {
                        if (t == skip) continue;
                        if (t == 6 && r < 5) nf = readback(fl + 32);
                        mbar_wait(sb + BAR_EMPTYA + 8 * t, (r - 1) & 1);
                        mbar_expect_tx(sb + BAR_FULLA + 8 * t, bytes);
                        asm volatile("cp.async.bulk.shared::cluster.global.mbarrier::complete_tx::bytes [%0], [%1], %2, [%3];"
                                     ::"r"(sb + OFF_A + t * SLOT), "l"(src + t * 1024), "r"(bytes), "r"(sb + BAR_FULLA + 8 * t) : "memory");
                    }
                }
            }
            return;
        }
        const int a = warp - 10;
        {
            const int row = 16 * j + 8 * a + (lane >> 2);
            const uint32_t ra = sb + OFF_A + row * 128;
            float sh = 0.f, s0 = 0.f, s1 = 0.f, q0 = 0.f, q1 = 0.f;
#pragma unroll 1
            for (int kt = 0; kt < 8; kt++) {
                mbar_wait(sb + BAR_FULLA + 8 * kt, 0);
                if (kt == 0) sh = bf_lo(lds128(ra + ((row & 7) << 4)).x);
#pragma unroll
                for (int i = 0; i < 2; i++) {
                    const uint4 v = lds128(ra + kt * SLOT + (((2 * (lane & 3) + i) ^ (row & 7)) << 4));
                    const uint32_t ww[4] = {v.x, v.y, v.z, v.w};
#pragma unroll
                    for (int e = 0; e < 4; e++) {
                        const float d0 = bf_lo(ww[e]) - sh, d1 = bf_hi(ww[e]) - sh;
                        s0 += d0; q0 = fmaf(d0, d0, q0);
                        s1 += d1; q1 = fmaf(d1, d1, q1);
                    }
                }
            }
            s0 += s1; q0 += q1;
#pragma unroll
            for (int o = 1; o <= 2; o <<= 1) { s0 += __shfl_xor_sync(0xffffffffu, s0, o); q0 += __shfl_xor_sync(0xffffffffu, q0, o); }
            const float md = s0 * (1.f / DM);
            const float rs = rsqrtf(fmaxf(q0 * (1.f / DM) - md * md, 0.f) + 1e-5f);
            st_tagged_if(g_xstat + 2 * (128 * m + row), rs, -(sh + md), epoch, (lane & 3) == 0);
            TL(1, lane == 0 && a == 0);
        }
        const unsigned long long* cs = g_cs + j * 768 + 2 * lane;
        {
            const unsigned long long* xs = g_xstat + 2 * (128 * m + 64 * a + lane);
            uint4 v0, v1, v2;
            uint32_t it = 0;
            do {
                v0 = ld_tagged_rlx(xs); v1 = ld_tagged_rlx(xs + 64); v2 = ld_tagged_rlx(cs);
                trap_if_gt(++it, 1u << 22);
            } while (__any_sync(0xffffffffu, v0.y != epoch || v0.w != epoch || v1.y != epoch || v1.w != epoch || v2.y != epoch || v2.w != epoch));
            sts64(sb + OFF_XST + (64 * a + lane) * 8, v0.x, v0.z);
            sts64(sb + OFF_XST + (64 * a + 32 + lane) * 8, v1.x, v1.z);
            sts64(sb + OFF_CS1 + 256 + 8 * lane, v2.x, v2.z);
            mbar_arrive(sb + BAR_CS1);
            TL(22 + a, lane == 0);
            fetch_tagged(cs + 128 + 128 * a, sb + OFF_CS1 + 512 - 512 * a + 8 * lane, epoch);
            mbar_arrive(sb + BAR_CSV - 8 * a);
            TL(24 + a, lane == 0);
        }
        {
            mbar_wait(sb + BAR_KVW, 0);
            const float* src = acc_j + 4 * (128 * a + lane);
            float4 v[12];
            uint32_t it = 0;
            bool bad;
            while (__any_sync(0xffffffffu, readback(acc_j + 2048 + 128 * (lane & 7) + 127) != 0x41800000u)) trap_if_gt(++it, 1u << 22);
            TL(19, lane == 0 && a == 0);
            do {
                bad = false;
#pragma unroll
                for (int i = 0; i < 12; i++) v[i] = ld_l2_f4(src + 1024 * (i % 3) + 128 * (i / 3));
#pragma unroll
                for (int i = 0; i < 12; i++) bad |= v[i].w != 16.f;
                trap_if_gt(++it, 1u << 22);
            } while (__any_sync(0xffffffffu, bad));
            TL(14, lane == 0 && a == 0);
            const uint32_t d0 = sb + OFF_A + (j < 2 ? 2 * SLOT : 0) + (64 * a + (lane >> 2)) * 48;
            const uint32_t d = d0 + (lane & 3) * 4, dz = d0 + (lane & 1) * 384 + 32 + (lane & 2) * 4;
#pragma unroll
            for (int u = 0; u < 4; u++) {
                sts32(d + 768 * u, pack_bf16(v[3 * u].x, v[3 * u].y));
                sts32(d + 768 * u + 384, pack_bf16(v[3 * u].z, v[3 * u + 1].z));
                sts32(d + 768 * u + 16, pack_bf16(v[3 * u + 1].x, v[3 * u + 1].y));
                sts32(d + 768 * u + 400, pack_bf16(v[3 * u + 2].x, v[3 * u + 2].y));
                const uint32_t z2 = pack_bf16(v[3 * u + 2].z, v[3 * u + 2].z);
                sts64(dz + 768 * u, z2, z2);
            }
            mbar_arrive(sb + BAR_KVR);
        }
#pragma unroll 1
        for (int c = 0; c < 3; c++) {
            fetch_tagged(cs + 384 + 128 * c + 64 * a, sb + OFF_CS3 + (32 * c + lane) * 16 + 8 * a, epoch);
            mbar_arrive(sb + BAR_CSG + 8 * c);
            TL(45 + c, lane == 0 && a == 0);
        }
        {
            uint32_t it = 0;
            while (__any_sync(0xffffffffu, (int)(readback(g_flag + (m * 5 + 1) * 32) - epoch * 64) < 0)) {
                __nanosleep(200);
                trap_if_gt(++it, 1u << 22);
            }
#pragma unroll 1
            for (int rr = 0; rr < 2; rr++) {
                const int row = 64 * rr + 32 * a + lane;
                const unsigned long long* hs = g_hstat + (1024 * m + row) * 2;
                uint4 v[8];
                bool bad;
                do {
                    bad = false;
#pragma unroll
                    for (int i = 0; i < 8; i++) v[i] = ld_tagged_rlx(hs + 256 * i);
#pragma unroll
                    for (int i = 0; i < 8; i++) bad |= v[i].y != epoch || v[i].w != epoch;
                    trap_if_gt(++it, 1u << 22);
                } while (__any_sync(0xffffffffu, bad));
                float mean = 0.f;
#pragma unroll
                for (int i = 0; i < 8; i++) mean += __uint_as_float(v[i].x);
                mean *= 0.125f;
                float m2 = 0.f, dv = 0.f;
#pragma unroll
                for (int i = 0; i < 8; i++) { const float d = __uint_as_float(v[i].x) - mean; m2 += __uint_as_float(v[i].z); dv = fmaf(d, d, dv); }
                sts_f2(sb + OFF_CS1 + row * 8, -mean, rcp(fmaf(dv, 64.f, m2) * (1.f / DM) + 1e-5f));
            }
        }
        mbar_arrive(sb + BAR_CS3);
#pragma unroll 1
        for (int c = a; c < 3; c += 2) {
            mbar_wait(sb + BAR_STG + 8 * c, 0);
            if (elect_one()) {
                asm volatile("cp.async.bulk.global.shared::cta.bulk_group [%0], [%1], %2;" ::"l"(g_act + ((2 + c) * 128 + role) * 1024), "r"(sb + OFF_B + 4 * SLOT), "r"(c == 2 ? 12288 : SLOT) : "memory");
                asm volatile("cp.async.bulk.commit_group;" ::: "memory");
                asm volatile("cp.async.bulk.wait_group.read 0;" ::: "memory");
                mbar_arrive(sb + BAR_FULLB + 8 * 4);
                asm volatile("cp.async.bulk.wait_group 0;" ::: "memory");
            }
            __syncwarp();
            TL(60 + c, lane == 0);
            uint32_t ack = 0;
            const uint4* rb = g_act + ((2 + c) * 128 + role) * 1024 + lane * 8;
#pragma unroll
            for (int i = 0; i < 4; i++) ack |= readback(rb + (i == 3 && c == 2 ? 0 : 256 * i));
            signal_after(g_flag + (m * 5 + 2 + c) * 32, ack, P.zero, lane == 0);
            TL(54 + c, lane == 0);
        }
        return;
    }
    const unsigned epoch = ld_relaxed(&g_epoch);
    uint32_t wraw[16];
    if (!helper) {
        const uint32_t* wp = reinterpret_cast<const uint32_t*>(P.wphi) + (4 * j) * 128 + (lane & 3) * 16 + (lane >> 2);
#pragma unroll
        for (int i = 0; i < 16; i++)
            asm volatile("ld.global.nc.u32 %0, [%1];" : "=r"(wraw[i]) : "l"(wp + (i >> 2) * 128 + ((i >> 1) & 1) * 64 + (i & 1) * 8));
    }
    asm volatile("barrier.cluster.arrive.relaxed.aligned;" ::: "memory");
    asm volatile("setmaxnreg.inc.sync.aligned.u32 216;");
    bar_sync(0, NTHREADS);
    if (helper) {
        const int w = warp >> 2;
        sts64(sb + OFF_B + 8 * tid, 0x3f803f80u, 0x3f803f80u);
        fence_async_smem();
        uint32_t zack[6];
        {
            float* z = g_acc + 2 * j * ACC_SIZE + 4 * tid;
#pragma unroll
            for (int u = 0; u < 6; u++) stg128(z + 1024 * u, 0, 0, 0, 0);
#pragma unroll
            for (int u = 0; u < 6; u++) zack[u] = readback(z + 1024 * u);
        }
        bar_sync(1, 256);
        TL(70, tid == 0);
        float acc[8];
        int i = w;
#pragma unroll 1
        for (int job = 0; job < 6; job++) {
            const int n = job < 3 ? 4 : 8;
#pragma unroll 1
            for (int t = 0; t < n; t++, i += 2) {
                mbar_waitc(sb + BAR_FULLA + 8 * (i & 7), (i >> 3) & 1);
                const desc_t da = desc_lo(sb + OFF_A) + (i & 7) * (SLOT >> 4);
                wg_fence();
#pragma unroll
                for (int k = 0; k < 8; k++) wgmma_n8_tt(acc + (k & 4), da + 128 * k, desc_lo(sb + OFF_B), (t | (k & 3)) != 0);
                wg_commit();
                wg_wait<0>();
                mbar_arrive_n_if(sb + BAR_EMPTYA + 8 * (i & 7), 2, lane == 0);
            }
            fence_acc<8>(acc);
            TL(71 + job, tid == 0);
            if (job == 1) {
                asm volatile("{.reg .pred p; .reg .b32 t; lop3.b32 t, %0, %1, %2, 0xfe; lop3.b32 t, t, %3, %4, 0xfe; or.b32 t, t, %5; setp.ne.u32 p, t, 0; @p trap;}"
                             ::"r"(zack[0]), "r"(zack[1]), "r"(zack[2]), "r"(zack[3]), "r"(zack[4]), "r"(zack[5]));
                bar_sync(1, 256);
            }
            const int q = lane & 3;
            const float lo = (q & 1) ? acc[2] : acc[0], hi = (q & 1) ? acc[6] : acc[4];
            const float v = job < 3 ? lo + hi : ((q & 2) ? hi : lo);
            unsigned long long* dst = g_cs + ((2 * j + w) * 6 + job) * 128 + (q >> 1) * 64 + 16 * (warp & 3) + 8 * (q & 1) + (lane >> 2);
            asm volatile("st.relaxed.gpu.global.b64 [%0], %1;" ::"l"(dst), "l"(((unsigned long long)epoch << 32) | __float_as_uint(v)) : "memory");
        }
        return;
    }
    {
        const int w = warp >> 2, wv = warp & 3, g = lane >> 2, q = lane & 3;
        const uint32_t sa = sb + OFF_A + w * 8192;
        const desc_t dA = desc_lo(sa), dB = desc_lo(sb + OFF_B);
        unsigned* const flag_m = g_flag + m * 160;
        const bool l0 = lane == 0, l2 = lane < 2;
        const uint32_t eb = mapa(sb + BAR_EMPTYB, lane & 1);
        asm volatile("barrier.cluster.wait.aligned;" ::: "memory");
        Ring rg{0, 0};
        int prev = 0;

        uint32_t wb[16];
        constexpr float L2E = 1.4426950408889634f;
        const int ch = lane >> 4, sw = lane & 7;
        const uint32_t lrow = (lane & 15) * 128;
        uint32_t fp[16], fm[16];
        const int vs = j < 2 ? 2 : 0;
        {
            float acc[64];
#pragma unroll 1
            for (int kt = 0; kt < 8; kt++) {
                mbar_waitc(sb + BAR_FULLA + 8 * kt, 0);
                mbar_waitc(sb + BAR_FULLB + 8 * rg.slot, rg.phase);
                const desc_t da = dA + kt * (SLOT >> 4), db = dB + rg.slot * (SLOT >> 4);
                wg_fence();
#pragma unroll
                for (int k = 0; k < 4; k++) wgmma_n128(acc, da + 2 * k, db + 128 * k, (kt | k) != 0);
                wg_commit();
                wg_wait<1>();
                mbar_arrive_cl_if(eb + 8 * prev, l2 && kt > 0);
                prev = rg.slot; rg.adv();
            }
#pragma unroll
            for (int i = 0; i < 8; i++) {
                wb[(i >> 1) * 4 + (i & 1)] = __byte_perm(wraw[2 * i], wraw[2 * i + 1], 0x5410);
                wb[(i >> 1) * 4 + 2 + (i & 1)] = __byte_perm(wraw[2 * i], wraw[2 * i + 1], 0x7632);
            }
            uint32_t a[16];
            float accq[32];
            mbar_waitc(sb + BAR_FULLB + 8 * 2, 1);
            wg_fence();
#pragma unroll
            for (int k = 0; k < 8; k++) wgmma_n64(accq, dA + (vs + (k >> 2)) * (SLOT >> 4) + (k & 3) * 2, dB + 2 * (SLOT >> 4) + 128 * k, k != 0);
            wg_commit();
            wg_wait<1>();
            fence_acc<64>(acc);
            mbar_arrive_cl_if(eb + 8 * prev, l2);
            TL(17, tid == 0);
            mbar_waitc(sb + BAR_CS1, 0);
            const float2 s0 = lds_f2(sb + OFF_XST + (16 * warp + g) * 8), s1 = lds_f2(sb + OFF_XST + (16 * warp + g + 8) * 8);
            wg_wait<0>();
            fence_acc<32>(accq);
            mbar_arrive_cl_if(eb + 8 * 2, l2);
            TL(2, tid == 0);
            const uint32_t st = sb + OFF_B + warp * 2048 + lrow;
#pragma unroll
            for (int hh = 0; hh < 4; hh++)
                ln_frag<false>(acc + 8 * hh, sb + OFF_CS1 + (64 + 16 * hh + 2 * q) * 4, 0.f, s0.y, 0.f, s1.y, a + 4 * hh);
#pragma unroll 1
            for (int it = 0; it < 2; it++) {
                feature_maps(a, wb, s0.x * L2E, s1.x * L2E, fp, fm);
                if (it == 0) {
                    mbar_waitc(sb + BAR_FULLB + 8 * 3, 1); mbar_waitc(sb + BAR_FULLB + 8 * 4, 1);
                    mbar_waitc(sb + BAR_CSV, 0);
                    const uint32_t sv = sb + OFF_A + vs * SLOT + warp * 2048 + lrow;
#pragma unroll
                    for (int hh = 0; hh < 4; hh++) {
                        stsm4(st + (3 + (hh >> 1)) * SLOT + (((4 * (hh & 1) + ch) ^ sw) << 4), fp[4 * hh], fp[4 * hh + 1], fp[4 * hh + 2], fp[4 * hh + 3]);
                        stsm4(st + (3 + (hh >> 1)) * SLOT + (((4 * (hh & 1) + 2 + ch) ^ sw) << 4), fm[4 * hh], fm[4 * hh + 1], fm[4 * hh + 2], fm[4 * hh + 3]);
                        ln_frag<true>(acc + 32 + 8 * hh, sb + OFF_CS1 + (128 + 16 * hh + 2 * q) * 4, s0.x, s0.y, s1.x, s1.y, a);
                        stsm4(sv + (hh >> 1) * SLOT + (((2 * (hh & 1) + ch) ^ sw) << 4), a[0], a[1], a[2], a[3]);
                    }
                    stsm4(sv + ch * SLOT + ((4 ^ sw) << 4), 0x3f803f80u, 0x3f803f80u, 0x3f803f80u, 0x3f803f80u);
                    fence_async_smem();
                    bar_sync(1, 256);
                    float kvd[20];
                    wg_fence();
#pragma unroll
                    for (int k = 0; k < 8; k++)
                        wgmma_n40_tt(kvd, dB + (3 + w) * (SLOT >> 4) + 128 * k, desc_lo(sb + OFF_A) + (vs + w) * (SLOT >> 4) + 128 * k, k != 0);
                    wg_commit();
                    wg_wait<0>();
                    fence_acc<20>(kvd);
                    mbar_arrive_cl_if(eb + 8 * (3 + (lane >> 1)), lane < 4);
                    const bool h1 = wv >= 2;
                    float* kvp = acc_j + 4 * tid;
                    red_f32x4(kvp, h1 ? kvd[8] : kvd[0], h1 ? kvd[9] : kvd[1], h1 ? kvd[10] : kvd[2], 1.f);
                    red_f32x4(kvp + 1024, h1 ? kvd[12] : kvd[4], h1 ? kvd[13] : kvd[5], h1 ? kvd[11] : kvd[3], 1.f);
                    red_f32x4(kvp + 2048, h1 ? kvd[14] : kvd[6], h1 ? kvd[15] : kvd[7], (q & 1) ? kvd[18] : kvd[16], 1.f);
                    mbar_arrive_if(sb + BAR_KVW, l0);
                    TL(3, tid == 0);
#pragma unroll 1
                    for (int b = 1; b < 4; b++) {
                        const int slot = b == 1 ? 5 : b - 2;
                        mbar_waitc(sb + BAR_FULLB + 8 * slot, b == 1);
                        const desc_t da = dA + (b == 1 ? 2 - vs : 2 * b) * (SLOT >> 4), db = dB + slot * (SLOT >> 4);
                        wg_fence();
#pragma unroll
                        for (int k = 0; k < 8; k++) wgmma_n64(accq, da + (k >> 2) * (SLOT >> 4) + (k & 3) * 2, db + 128 * k, 1);
                        wg_commit();
                    }
                    mbar_waitc(sb + BAR_CSQ, 0);
                    wg_wait<0>();
                    fence_acc<32>(accq);
                    mbar_arrive_cl_if(eb + 8 * ((5 + (lane >> 1)) % 6), lane < 6);
                    TL(4, tid == 0);
#pragma unroll
                    for (int hh = 0; hh < 4; hh++)
                        ln_frag<false>(accq + 8 * hh, sb + OFF_CS1 + (16 * hh + 2 * q) * 4, 0.f, s0.y, 0.f, s1.y, a + 4 * hh);
                }
            }
        }
        uint32_t res_lo[8], res_hi[8], ack[4];
        const uint32_t own_rows = sb + OFF_A + j * SLOT + warp * 2048;
#pragma unroll
        for (int b = 0; b < 4; b++)
            ldsm4(own_rows + lrow + (((2 * b + ch) ^ sw) << 4), res_lo[2 * b], res_hi[2 * b], res_lo[2 * b + 1], res_hi[2 * b + 1]);
        mbar_arrive_if(sb + BAR_EMPTYA + 8 * lane, lane < 8 && lane != j && lane != vs);
        TL(5, tid == 0);
        mbar_waitc(sb + BAR_KVR, 0);
        TL(6, tid == 0);
        {
            const uint32_t kvs = sb + OFF_A + vs * SLOT;
            uint32_t o_lo[8], o_hi[8];
#pragma unroll
            for (int hh = 0; hh < 4; hh++) {
                uint32_t b[8], zb[4];
                const uint32_t base = kvs + hh * 32 * 48;
                ldsm4t(base + (lane & 15) * 48 + (lane >> 4) * 16, b[0], b[1], b[2], b[3]);
                ldsm4t(base + (16 + (lane & 15)) * 48 + (lane >> 4) * 16, b[4], b[5], b[6], b[7]);
                ldsm4t(base + lane * 48 + 32, zb[0], zb[1], zb[2], zb[3]);
                float n0[4], n1[4], dn[4];
                mma16816_z(n0, fp + 4 * hh, b[0], b[1]); mma16816_z(n1, fp + 4 * hh, b[2], b[3]); mma16816_z(dn, fp + 4 * hh, zb[0], zb[1]);
                mma16816(n0, fm + 4 * hh, b[4], b[5]); mma16816(n1, fm + 4 * hh, b[6], b[7]); mma16816(dn, fm + 4 * hh, zb[2], zb[3]);
                const float i0 = rcp(dn[0] + 1e-6f), i1 = rcp(dn[2] + 1e-6f);
                o_lo[2 * hh] = pack_bf16(n0[0] * i0, n0[1] * i0); o_hi[2 * hh] = pack_bf16(n0[2] * i1, n0[3] * i1);
                o_lo[2 * hh + 1] = pack_bf16(n1[0] * i0, n1[1] * i0); o_hi[2 * hh + 1] = pack_bf16(n1[2] * i1, n1[3] * i1);
            }
            __syncwarp();
            mbar_arrive_if(sb + BAR_EMPTYA + 8 * vs, l0);
            rg.slot = 2; rg.phase = 0;
            store_tile(own_rows, g_act + role * 1024 + warp * 128 + lane, o_lo, o_hi, lane, ack);
            TL(7, tid == 0);
        }
        float acch[32];
        {
            float* acc = acch;
#pragma unroll
            for (int t = 0; t < 8; t++) {
                acc[4 * t] = bf_lo(res_lo[t]); acc[4 * t + 1] = bf_hi(res_lo[t]);
                acc[4 * t + 2] = bf_lo(res_hi[t]); acc[4 * t + 3] = bf_hi(res_hi[t]);
            }
            fence_acc<32>(acc);
            int pa = 0;
#pragma unroll 1
            for (int kp = 0; kp < 4; kp++) {
                mbar_waitc(sb + BAR_FULLB + 8 * rg.slot, rg.phase);
#pragma unroll
                for (int hf = 0; hf < 2; hf++) {
                    const int i = 2 * kp + hf, kt = KORD(i, j);
                    mbar_waitc(sb + BAR_FULLA + 8 * kt, i != 0);
                    TL(8, i == 1 && tid == 0);
                    const desc_t da = dA + kt * (SLOT >> 4), db = dB + rg.slot * (SLOT >> 4);
                    wg_fence();
#pragma unroll
                    for (int k = 0; k < 4; k++) wgmma_n64(acc, da + 2 * k, db + (hf * 4 + k) * 128, 1);
                    wg_commit();
                    wg_wait<1>();
                    mbar_arrive_if(sb + BAR_EMPTYA + 8 * pa, l0 && i > 1);
                    if (hf == 0) {
                        mbar_arrive_cl_if(eb + 8 * prev, l2 && i > 0);
                        if (i == 0) { signal_late(flag_m, ack, P.zero, l0); TL(20, tid == 0); }
                    }
                    pa = kt;
                }
                prev = rg.slot; rg.adv();
            }
            wg_wait<0>();
            fence_acc<32>(acc);
            mbar_arrive_if(sb + BAR_EMPTYA + 8 * pa, l0);
            mbar_arrive_cl_if(eb + 8 * prev, l2);
            TL(9, tid == 0);
#pragma unroll
            for (int t = 0; t < 8; t++) {
                res_lo[t] = pack_bf16(acc[4 * t], acc[4 * t + 1]);
                res_hi[t] = pack_bf16(acc[4 * t + 2], acc[4 * t + 3]);
            }
            store_tile(own_rows, g_act + (128 + role) * 1024 + warp * 128 + lane, res_lo, res_hi, lane, ack);
            TL(10, tid == 0);
        }
        float acc0[64], acc1[64], acc2[56], nm0, nm1;
        float4 cs[8];
        uint32_t hr[16];
#define P3_GROUP(MMA, ACC, KT)                                                                              \
        mbar_waitc(sb + BAR_FULLB + 8 * rg.slot, rg.phase);                                                 \
        {                                                                                                   \
            const desc_t da = dA + (KT) * (SLOT >> 4), db = dB + rg.slot * (SLOT >> 4);                     \
            wg_fence();                                                                                     \
            _Pragma("unroll") for (int k = 0; k < 4; k++) MMA(ACC, da + 2 * k, db + 128 * k, (i | k) != 0); \
            wg_commit();                                                                                    \
        }
#define P3_CS(C, NT)    \
        _Pragma("unroll") for (int t = 0; t < (NT); t++) lds_f4_if(cs[t], sb + OFF_CS3 + q * 16 + 512 * (C) + 64 * t, i == t);
#define P3_EPI2(C, ACC)                                                                                     \
        if (i == 0) {                                                                                       \
            fence_acc<64>(ACC);                                                                             \
            if (C) mbar_waitc(sb + BAR_FULLB + 8 * 4, 1);                                                   \
            hh_stage2<0, 2>(ACC, cs, nm0, nm1, stg, lane);                                                  \
            mbar_waitc(sb + BAR_CSG + 8 * (C) + 8, 0);                                                      \
        }                                                                                                   \
        if (i == 1) {                                                                                       \
            hh_stage2<2, 4>(ACC, cs, nm0, nm1, stg, lane);                                                  \
            fence_async_smem();                                                                             \
            __syncwarp();                                                                                   \
            mbar_arrive_if(sb + BAR_STG + 8 * (C), l0);                                                     \
        }
#define P3_EPI(C, ACC, N, NTP)                                                                              \
        fence_acc<N>(ACC);                                                                                  \
        TL(11 + (C), tid == 0);                                                                             \
        hh_stage<NTP>(ACC, cs, nm0, nm1, sb + OFF_B + 4 * SLOT + warp * 2048, lane);                        \
        mbar_arrive_if(sb + BAR_STG + 8 * (C), l0);                                                         \
        TL(50 + (C), tid == 0);
        const uint32_t stg = sb + OFF_B + 4 * SLOT + warp * 2048;
        const uint32_t blk = ((lane & 7) + (lane >> 4) * 8) * 128 + (((2 * wv + ((lane >> 3) & 1)) ^ (lane & 7)) << 4);
#pragma unroll 1
        for (int i = 0; i < 8; i++) {
            const int kt = KORD(i, j);
            mbar_waitc(sb + BAR_FULLA + 8 * kt, 0);
            TL(44, tid == 0 && i == 1);
            P3_GROUP(wgmma_n128, acc0, kt)
            if (i == 7) {
                mbar_waitc(sb + BAR_CS3, 0);
                nm0 = lds_f2(sb + OFF_CS1 + (16 * warp + g) * 8).x; nm1 = lds_f2(sb + OFF_CS1 + (16 * warp + g + 8) * 8).x;
            }
            wg_wait<1>();
            mbar_arrive_cl_if(eb + 8 * prev, l2 && i > 0);
            if (i == 0) {
                signal_late(flag_m + 32, ack, P.zero, l0);
                TL(21, tid == 0);
                {
                    fence_acc<32>(acch);
                    const float* acc = acch;
                    float s0 = 0.f, s1 = 0.f;
#pragma unroll
                    for (int t = 0; t < 8; t++) { s0 += acc[4 * t] + acc[4 * t + 1]; s1 += acc[4 * t + 2] + acc[4 * t + 3]; }
            s0 += __shfl_xor_sync(0xffffffffu, s0, 1); s1 += __shfl_xor_sync(0xffffffffu, s1, 1);
            s0 += __shfl_xor_sync(0xffffffffu, s0, 2); s1 += __shfl_xor_sync(0xffffffffu, s1, 2);
            const float mu0 = s0 * (1.f / 64), mu1 = s1 * (1.f / 64);
            float q0 = 0.f, q1 = 0.f;
#pragma unroll
            for (int t = 0; t < 8; t++) {
                float d;
                d = acc[4 * t] - mu0; q0 = fmaf(d, d, q0);
                d = acc[4 * t + 1] - mu0; q0 = fmaf(d, d, q0);
                d = acc[4 * t + 2] - mu1; q1 = fmaf(d, d, q1);
                d = acc[4 * t + 3] - mu1; q1 = fmaf(d, d, q1);
            }
            q0 += __shfl_xor_sync(0xffffffffu, q0, 1); q1 += __shfl_xor_sync(0xffffffffu, q1, 1);
            q0 += __shfl_xor_sync(0xffffffffu, q0, 2); q1 += __shfl_xor_sync(0xffffffffu, q1, 2);
            st_tagged_if(g_hstat + (role * 128 + 16 * warp + g + 8 * (q & 1)) * 2, q ? mu1 : mu0, q ? q1 : q0, epoch, q < 2);
                }
                bar_sync(2 + w, 128);
#pragma unroll
                for (int tp = 0; tp < 4; tp++) ldsm4t(sa + j * SLOT + blk + tp * 2048, hr[4 * tp], hr[4 * tp + 1], hr[4 * tp + 2], hr[4 * tp + 3]);
                mbar_waitc(sb + BAR_CSG, 0);
#pragma unroll
                for (int t = 0; t < 8; t++) cs[t] = lds_f4(sb + OFF_CS3 + q * 16 + 64 * t);
            }
            prev = rg.slot; rg.adv5();
        }
#pragma unroll 1
        for (int i = 0; i < 8; i++) {
            P3_GROUP(wgmma_n128, acc1, i)
            wg_wait<1>();
            mbar_arrive_cl_if(eb + 8 * prev, l2);
            P3_EPI2(0, acc0)
            P3_CS(1, 8)
            prev = rg.slot; rg.adv5();
        }
#pragma unroll 1
        for (int i = 0; i < 8; i++) {
            P3_GROUP(wgmma_n112, acc2, i)
            wg_wait<1>();
            mbar_arrive_cl_if(eb + 8 * prev, l2);
            mbar_arrive_if(sb + BAR_EMPTYA + 8 * ((i + 7) & 7), l0 && i > 0);
            if (i == 0) { mbar_waitc(sb + BAR_FULLB + 8 * 4, 1); P3_EPI(1, acc1, 64, 4) mbar_waitc(sb + BAR_CSG + 16, 0); }
            P3_CS(2, 6)
            prev = rg.slot; rg.adv5();
        }
        mbar_waitc(sb + BAR_FULLB + 8 * 4, 0);
        wg_wait<0>();
        mbar_arrive_cl_if(eb + 8 * prev, l2);
        mbar_arrive_if(sb + BAR_EMPTYA + 8 * 7, l0);
        fence_acc<56>(acc2);
        TL(13, tid == 0);
#pragma unroll
        for (int tp = 0; tp < 3; tp++)
            stsm4(sb + OFF_B + 4 * SLOT + tp * 4096 + warp * 512 + (lane & 15) * 32 + ((ch ^ ((lane >> 2) & 1)) << 4),
                  hh_pair<32>(acc2 + 8 * tp, cs[2 * tp], nm0), hh_pair<32>(acc2 + 8 * tp + 2, cs[2 * tp], nm1),
                  hh_pair<32>(acc2 + 8 * tp + 4, cs[2 * tp + 1], nm0), hh_pair<32>(acc2 + 8 * tp + 6, cs[2 * tp + 1], nm1));
        fence_async_smem();
        __syncwarp();
        mbar_arrive_if(sb + BAR_STG + 16, l0);
        TL(52, tid == 0);
        {
            float acc[64];
            const desc_t dA0 = desc_lo(sb + OFF_A);
#define KT_P4(I, NK, DH, STEP)                                                                                   \
        const int s_ = (2 * (I) + w) & 7;                                                                   \
        mbar_waitc(sb + BAR_FULLB + 8 * rg.slot, rg.phase);                                                 \
        mbar_waitc(sb + BAR_FULLA + 8 * s_, (((I) >> 2) + 1) & 1);                                          \
        const desc_t dh_ = (DH) + s_ * (SLOT >> 4), dw_ = dB + rg.slot * (SLOT >> 4) + w * 512;              \
        wg_fence();                                                                                         \
        _Pragma("unroll") for (int k = 0; k < (NK); k++) wgmma_n128_tn(acc, dw_ + 128 * k, dh_ + (STEP) * k, ((I) | k) != 0); \
        wg_commit();
#pragma unroll 1
            for (int i = 0; i < 8; i++) {
                KT_P4(i, 4, dA0, 2)
#pragma unroll
                for (int t = 0; t < 8; t++) lds_f4_if(cs[t], sb + OFF_CS1 + (64 * w + 8 * t + 2 * q) * 8, i == t);
                wg_wait<0>();
                mbar_arrive_n_if(sb + BAR_EMPTYA + 8 * s_, 2, l0);
                mbar_arrive_cl_if(eb + 8 * rg.slot, l2 && i < 7);
                rg.adv5();
            }
#pragma unroll 1
            for (int i = 8; i < 12; i++) {
                KT_P4(i, 3, dA0 + ((0xC0000010ull - 0x40000040ull) << 32), 256)
                wg_wait<1>();
                rg.adv5();
            }
            wg_wait<0>();
            fence_acc<64>(acc);
            TL(15, tid == 0);
            const uint32_t xch = sb + OFF_A + 2 * SLOT + (tid & 127) * 16;
            if (w) {
#pragma unroll
                for (int t = 0; t < 8; t++) {
                    sts128(xch + SLOT + t * 2048, __float_as_uint(acc[4 * t]), __float_as_uint(acc[4 * t + 1]),
                           __float_as_uint(acc[4 * t + 2]), __float_as_uint(acc[4 * t + 3]));
                }
#pragma unroll
                for (int t = 0; t < 32; t++) acc[t] = acc[32 + t];
            } else {
#pragma unroll
                for (int t = 0; t < 8; t++)
                    sts128(xch + t * 2048, __float_as_uint(acc[32 + 4 * t]), __float_as_uint(acc[33 + 4 * t]),
                           __float_as_uint(acc[34 + 4 * t]), __float_as_uint(acc[35 + 4 * t]));
            }
            bar_sync(1, 256);
            float4 o[8];
#pragma unroll
            for (int t = 0; t < 8; t++) o[t] = lds_f4(xch + (w ^ 1) * SLOT + t * 2048);
            const uint32_t tile = sb + OFF_A + w * SLOT;
#pragma unroll
            for (int t = 0; t < 8; t++) {
                hr[2 * t] = pack_bf16(fmaf(acc[4 * t] + o[t].x, cs[t].y, bf_lo(hr[2 * t])), fmaf(acc[4 * t + 1] + o[t].y, cs[t].w, bf_hi(hr[2 * t])));
                hr[2 * t + 1] = pack_bf16(fmaf(acc[4 * t + 2] + o[t].z, cs[t].y, bf_lo(hr[2 * t + 1])), fmaf(acc[4 * t + 3] + o[t].w, cs[t].w, bf_hi(hr[2 * t + 1])));
            }
#pragma unroll
            for (int tp = 0; tp < 4; tp++) stsm4t(tile + blk + tp * 2048, hr[4 * tp], hr[4 * tp + 1], hr[4 * tp + 2], hr[4 * tp + 3]);
            fence_async_smem();
            bar_sync(2 + w, 128);
            if ((tid & 127) == 0) {
                tma_store2d(&P.tout, tile, 64 * j, 128 * m + 64 * w);
                asm volatile("cp.async.bulk.wait_group.read 0;" ::: "memory");
            }
            if (tid == 0 && role == 0) g_epoch = epoch + 1;
            TL(16, tid == 0); TLG(1, tid == 0);
        }
    }
}

typedef CUresult (*EncodeFn)(CUtensorMap*, CUtensorMapDataType, cuuint32_t, void*, const cuuint64_t*, const cuuint64_t*,
                             const cuuint32_t*, const cuuint32_t*, CUtensorMapInterleave, CUtensorMapSwizzle,
                             CUtensorMapL2promotion, CUtensorMapFloatOOBfill);

static void make_map2d(EncodeFn enc, CUtensorMap* tm, const void* base, uint64_t cols, uint64_t rows, uint64_t pitch_elems,
                       uint32_t box_rows) {
    cuuint64_t gd[2] = {cols, rows};
    cuuint64_t gs[1] = {pitch_elems * 2};
    cuuint32_t bd[2] = {64, box_rows};
    cuuint32_t es[2] = {1, 1};
    enc(tm, CU_TENSOR_MAP_DATA_TYPE_BFLOAT16, 2, const_cast<void*>(base), gd, gs, bd, es, CU_TENSOR_MAP_INTERLEAVE_NONE,
        CU_TENSOR_MAP_SWIZZLE_128B, CU_TENSOR_MAP_L2_PROMOTION_L2_256B, CU_TENSOR_MAP_FLOAT_OOB_FILL_NONE);
}

}

extern "C" void kernel_launch(void* const* d_in, const int* in_sizes, int n_in, void* d_out, int out_size) {
    using namespace hk;
    (void)in_sizes; (void)n_in; (void)out_size;
    static EncodeFn enc = nullptr;
    if (!enc) {
        void* fn = nullptr;
        cudaDriverEntryPointQueryResult qr;
        cudaGetDriverEntryPoint("cuTensorMapEncodeTiled", &fn, cudaEnableDefault, &qr);
        enc = (EncodeFn)fn;
        cudaFuncSetAttribute(fused_kernel, cudaFuncAttributeMaxDynamicSharedMemorySize, SMEM_BYTES);
    }
    Params P;
    const __nv_bfloat16* x = (const __nv_bfloat16*)d_in[0];
    P.x = x;
    P.wqkv = (const __nv_bfloat16*)d_in[1];
    P.wphi = (const __nv_bfloat16*)d_in[2];
    P.wo = (const __nv_bfloat16*)d_in[3];
    P.wg = (const __nv_bfloat16*)d_in[5];
    P.wu = (const __nv_bfloat16*)d_in[6];
    P.wd = (const __nv_bfloat16*)d_in[7];
    P.out = (__nv_bfloat16*)d_out;
    P.zero = 0;
    make_map2d(enc, &P.tx, x, DM, SEQ, DM, 128);
    make_map2d(enc, &P.twq, P.wqkv, 3 * DM, DM, 3 * DM, 64);
    make_map2d(enc, &P.two, P.wo, DM, DM, DM, 64);
    make_map2d(enc, &P.twg, P.wg, FF, DM, FF, 64);
    make_map2d(enc, &P.twu, P.wu, FF, DM, FF, 64);
    make_map2d(enc, &P.twd, P.wd, DM, FF, DM, 64);
    make_map2d(enc, &P.twd48, P.wd, DM, FF, DM, 48);
    make_map2d(enc, &P.tout, d_out, DM, SEQ, DM, 64);
    fused_kernel<<<NCTA, NTHREADS, SMEM_BYTES>>>(P);
}
```

```cpp
#include <cuda_runtime.h>
#include <cuda_bf16.h>
#include <cuda.h>
#include <stdint.h>

namespace hk {

constexpr int SEQ = 2048, DM = 512, FF = 1376;
constexpr int NCTA = 132;
constexpr int NTHREADS = 384;
constexpr uint32_t SLOT = 16384;
constexpr uint32_t OFF_A = 0, OFF_B = 8 * SLOT, OFF_MISC = 14 * SLOT;
constexpr uint32_t BAR_FULLA = OFF_MISC + 0, BAR_EMPTYA = OFF_MISC + 64, BAR_FULLB = OFF_MISC + 128,
                   BAR_EMPTYB = OFF_MISC + 176, BAR_CS1 = OFF_MISC + 224, BAR_CS3 = OFF_MISC + 232,
                   BAR_CSQ = OFF_MISC + 240, BAR_CSV = OFF_MISC + 248,
                   BAR_STG = OFF_MISC + 256,
                   BAR_KVW = OFF_MISC + 280, BAR_KVR = OFF_MISC + 288,
                   BAR_CSG = OFF_MISC + 296;
constexpr uint32_t OFF_CS1 = OFF_MISC + 384;
constexpr uint32_t OFF_CS3 = OFF_CS1 + 1024;
constexpr uint32_t OFF_XST = OFF_CS3;
constexpr uint32_t SMEM_BYTES = OFF_CS3 + 1536;
#define KORD(i, j) ((i) == 0 ? (j) : (i) - ((i) <= (j)))
constexpr int NB = 6;
constexpr int NPRE = 3, AHEAD = 3, AHEADA = 5;
constexpr int PF_DELAY = 2;

constexpr int ACC_SIZE = 3 * 256 * 4;

__device__ __align__(1024) uint4 g_act[5 * 128 * 1024];
__device__ __align__(128) unsigned long long g_hstat[SEQ * 16];
__device__ __align__(128) unsigned long long g_xstat[SEQ * 2];
__device__ __align__(128) float g_acc[8 * ACC_SIZE];
__device__ __align__(128) unsigned long long g_cs[8 * 6 * 128];
__device__ __align__(128) unsigned g_flag[16 * 5 * 32];
__device__ unsigned g_epoch = 1;

#define TL(i, pred) do {} while (0)
#define TLG(i, pred) do {} while (0)

struct Params {
    CUtensorMap tx, twq, two, twg, twu, twd, twd48, tout;
    const __nv_bfloat16 *x, *wqkv, *wphi, *wo, *wg, *wu, *wd;
    __nv_bfloat16* out;
    unsigned zero;
};

__device__ __forceinline__ uint32_t smem_u32(const void* p) { return (uint32_t)__cvta_generic_to_shared(p); }
__device__ __forceinline__ void mbar_init(uint32_t bar, uint32_t cnt) {
    asm volatile("mbarrier.init.shared::cta.b64 [%0], %1;" ::"r"(bar), "r"(cnt) : "memory");
}
__device__ __forceinline__ void mbar_expect_tx(uint32_t bar, uint32_t bytes) {
    asm volatile("mbarrier.arrive.expect_tx.shared::cta.b64 _, [%0], %1;" ::"r"(bar), "r"(bytes) : "memory");
}
__device__ __forceinline__ void mbar_arrive(uint32_t bar) {
    asm volatile("mbarrier.arrive.shared::cta.b64 _, [%0];" ::"r"(bar) : "memory");
}
__device__ __forceinline__ void mbar_arrive_if(uint32_t bar, bool pred) {
    asm volatile("{.reg .pred p; setp.ne.u32 p, %1, 0; @p mbarrier.arrive.shared::cta.b64 _, [%0];}" ::"r"(bar), "r"((uint32_t)pred) : "memory");
}
__device__ __forceinline__ void trap_if_gt(uint32_t v, uint32_t lim) {
    asm volatile("{.reg .pred p; setp.gt.u32 p, %0, %1; @p trap;}" ::"r"(v), "r"(lim));
}
__device__ __forceinline__ void mbar_wait(uint32_t bar, uint32_t parity) {
    asm volatile("{\n"
                 ".reg .pred P1, P2;\n"
                 ".reg .u32 c;\n"
                 "mov.u32 c, 0;\n"
                 "LAB_WAIT:\n"
                 "mbarrier.try_wait.parity.shared::cta.b64 P1, [%0], %1;\n"
                 "@P1 bra LAB_DONE;\n"
                 "add.u32 c, c, 1;\n"
                 "setp.gt.u32 P2, c, 1048576;\n"
                 "@P2 trap;\n"
                 "bra LAB_WAIT;\n"
                 "LAB_DONE:\n"
                 "}" ::"r"(bar), "r"(parity) : "memory");
}
__device__ __forceinline__ void mbar_waitc(uint32_t bar, uint32_t parity) {
    asm volatile("{\n"
                 ".reg .pred P1;\n"
                 "LAB_WAIT:\n"
                 "mbarrier.try_wait.parity.shared::cta.b64 P1, [%0], %1;\n"
                 "@!P1 bra LAB_WAIT;\n"
                 "}" ::"r"(bar), "r"(parity) : "memory");
}
__device__ __forceinline__ void tma2d(uint32_t dst, const CUtensorMap* tm, uint32_t bar, int c0, int c1) {
    asm volatile("cp.async.bulk.tensor.2d.shared::cluster.global.mbarrier::complete_tx::bytes [%0], [%1, {%3, %4}], [%2];"
                 ::"r"(dst), "l"(tm), "r"(bar), "r"(c0), "r"(c1) : "memory");
}
__device__ __forceinline__ void tma2d_mc(uint32_t dst, const CUtensorMap* tm, uint32_t bar, int c0, int c1) {
    asm volatile("cp.async.bulk.tensor.2d.shared::cluster.global.mbarrier::complete_tx::bytes.multicast::cluster [%0], [%1, {%3, %4}], [%2], %5;"
                 ::"r"(dst), "l"(tm), "r"(bar), "r"(c0), "r"(c1), "h"((uint16_t)3) : "memory");
}
__device__ __forceinline__ uint32_t mapa(uint32_t addr, uint32_t rank) {
    uint32_t r; asm("mapa.shared::cluster.u32 %0, %1, %2;" : "=r"(r) : "r"(addr), "r"(rank)); return r;
}
__device__ __forceinline__ void mbar_arrive_cl_if(uint32_t cbar, bool pred) {
    asm volatile("{.reg .pred p; setp.ne.u32 p, %1, 0; @p mbarrier.arrive.shared::cluster.b64 _, [%0];}" ::"r"(cbar), "r"((uint32_t)pred) : "memory");
}
__device__ __forceinline__ bool elect_one() {
    uint32_t ok;
    asm volatile("{.reg .pred p; elect.sync _|p, 0xffffffff; selp.u32 %0, 1, 0, p;}" : "=r"(ok));
    return ok;
}
__device__ __forceinline__ void prefetch_tmap(const CUtensorMap* tm) {
    asm volatile("prefetch.tensormap [%0];" ::"l"(tm) : "memory");
}
__device__ __forceinline__ void prefetch_l2(const void* p, uint32_t bytes) {
    asm volatile("cp.async.bulk.prefetch.L2.global [%0], %1;" ::"l"(p), "r"(bytes) : "memory");
}
__device__ __forceinline__ unsigned ld_relaxed(const unsigned* p) {
    unsigned v; asm volatile("ld.relaxed.gpu.global.u32 %0, [%1];" : "=r"(v) : "l"(p)); return v;
}
__device__ __forceinline__ void fence_async_smem() { asm volatile("fence.proxy.async.shared::cta;" ::: "memory"); }
__device__ __forceinline__ uint32_t readback(const void* p) {
    uint32_t v; asm volatile("ld.relaxed.gpu.global.u32 %0, [%1];" : "=r"(v) : "l"(p) : "memory"); return v;
}
__device__ __forceinline__ void wait_count(const unsigned* p, unsigned target) {
    uint32_t it = 0;
    while ((int)(readback(p) - target) < 0) trap_if_gt(++it, 1u << 22);
}
__device__ __forceinline__ void red_f32x4(float* p, float a, float b, float c, float d) {
    asm volatile("red.relaxed.gpu.global.add.v4.f32 [%0], {%1, %2, %3, %4};" ::"l"(p), "f"(a), "f"(b), "f"(c), "f"(d) : "memory");
}
__device__ __forceinline__ float4 ld_l2_f4(const float* p) {
    float4 v;
    asm volatile("ld.relaxed.gpu.global.v4.f32 {%0,%1,%2,%3}, [%4];" : "=f"(v.x), "=f"(v.y), "=f"(v.z), "=f"(v.w) : "l"(p) : "memory");
    return v;
}
__device__ __forceinline__ void stg128(void* p, uint32_t a, uint32_t b, uint32_t c, uint32_t d) {
    asm volatile("st.global.v4.u32 [%0], {%1,%2,%3,%4};" ::"l"(p), "r"(a), "r"(b), "r"(c), "r"(d) : "memory");
}
__device__ __forceinline__ uint4 lds128(uint32_t a) {
    uint4 v;
    asm volatile("ld.shared.v4.u32 {%0,%1,%2,%3}, [%4];" : "=r"(v.x), "=r"(v.y), "=r"(v.z), "=r"(v.w) : "r"(a) : "memory");
    return v;
}
__device__ __forceinline__ float2 lds_f2(uint32_t a) {
    float2 v;
    asm volatile("ld.shared.v2.f32 {%0,%1}, [%2];" : "=f"(v.x), "=f"(v.y) : "r"(a) : "memory");
    return v;
}
__device__ __forceinline__ void sts_f2(uint32_t a, float x, float y) {
    asm volatile("st.shared.v2.f32 [%0], {%1,%2};" ::"r"(a), "f"(x), "f"(y) : "memory");
}
__device__ __forceinline__ void sts64(uint32_t a, uint32_t x, uint32_t y) {
    asm volatile("st.shared.v2.u32 [%0], {%1,%2};" ::"r"(a), "r"(x), "r"(y) : "memory");
}
__device__ __forceinline__ void sts128(uint32_t a, uint32_t x, uint32_t y, uint32_t z, uint32_t w) {
    asm volatile("st.shared.v4.u32 [%0], {%1,%2,%3,%4};" ::"r"(a), "r"(x), "r"(y), "r"(z), "r"(w) : "memory");
}
__device__ __forceinline__ void stsm4(uint32_t a, uint32_t r0, uint32_t r1, uint32_t r2, uint32_t r3) {
    asm volatile("stmatrix.sync.aligned.m8n8.x4.shared.b16 [%0], {%1,%2,%3,%4};" ::"r"(a), "r"(r0), "r"(r1), "r"(r2), "r"(r3) : "memory");
}
__device__ __forceinline__ void stsm4t(uint32_t a, uint32_t r0, uint32_t r1, uint32_t r2, uint32_t r3) {
    asm volatile("stmatrix.sync.aligned.m8n8.x4.trans.shared.b16 [%0], {%1,%2,%3,%4};" ::"r"(a), "r"(r0), "r"(r1), "r"(r2), "r"(r3) : "memory");
}
__device__ __forceinline__ void tma_store2d(const CUtensorMap* tm, uint32_t src, int c0, int c1) {
    asm volatile("cp.async.bulk.tensor.2d.global.shared::cta.bulk_group [%0, {%2, %3}], [%1];" ::"l"(tm), "r"(src), "r"(c0), "r"(c1) : "memory");
    asm volatile("cp.async.bulk.commit_group;" ::: "memory");
}
__device__ __forceinline__ void ldsm4(uint32_t a, uint32_t& r0, uint32_t& r1, uint32_t& r2, uint32_t& r3) {
    asm volatile("ldmatrix.sync.aligned.m8n8.x4.shared.b16 {%0,%1,%2,%3}, [%4];" : "=r"(r0), "=r"(r1), "=r"(r2), "=r"(r3) : "r"(a) : "memory");
}
__device__ __forceinline__ void ldsm4t(uint32_t a, uint32_t& r0, uint32_t& r1, uint32_t& r2, uint32_t& r3) {
    asm volatile("ldmatrix.sync.aligned.m8n8.x4.trans.shared.b16 {%0,%1,%2,%3}, [%4];" : "=r"(r0), "=r"(r1), "=r"(r2), "=r"(r3) : "r"(a) : "memory");
}
__device__ __forceinline__ void mma16816(float* c, const uint32_t* a, uint32_t b0, uint32_t b1) {
    asm("mma.sync.aligned.m16n8k16.row.col.f32.bf16.bf16.f32 {%0,%1,%2,%3}, {%4,%5,%6,%7}, {%8,%9}, {%0,%1,%2,%3};"
                 : "+f"(c[0]), "+f"(c[1]), "+f"(c[2]), "+f"(c[3])
                 : "r"(a[0]), "r"(a[1]), "r"(a[2]), "r"(a[3]), "r"(b0), "r"(b1));
}
__device__ __forceinline__ uint32_t pack_bf16(float lo, float hi) {
    uint32_t r; asm("cvt.rn.bf16x2.f32 %0, %1, %2;" : "=r"(r) : "f"(hi), "f"(lo)); return r;
}
__device__ __forceinline__ float bf_lo(uint32_t w) { return __uint_as_float(w << 16); }
__device__ __forceinline__ float bf_hi(uint32_t w) { return __uint_as_float(w & 0xffff0000u); }
__device__ __forceinline__ float ex2(float x) { float r; asm("ex2.approx.ftz.f32 %0, %1;" : "=f"(r) : "f"(x)); return r; }
__device__ __forceinline__ float rcp(float x) { float r; asm("rcp.approx.ftz.f32 %0, %1;" : "=f"(r) : "f"(x)); return r; }
__device__ __forceinline__ void bar_sync(int id, int n) { asm volatile("bar.sync %0, %1;" ::"r"(id), "r"(n) : "memory"); }

typedef unsigned long long desc_t;
__device__ __forceinline__ desc_t desc_lo(uint32_t addr) { return (desc_t)(((addr & 0x3FFFF) >> 4) | (512u << 16)) | (0x40000040ull << 32); }
__device__ __forceinline__ void wg_fence() { asm volatile("wgmma.fence.sync.aligned;" ::: "memory"); }
__device__ __forceinline__ void wg_commit() { asm volatile("wgmma.commit_group.sync.aligned;" ::: "memory"); }
template <int N> __device__ __forceinline__ void wg_wait() { asm volatile("wgmma.wait_group.sync.aligned %0;" ::"n"(N) : "memory"); }
template <int N> __device__ __forceinline__ void fence_acc(float* d) {
#pragma unroll
    for (int i = 0; i < N; i++) asm volatile("" : "+f"(d[i])::"memory");
}
#define R4(o) "+f"(d[o + 0]), "+f"(d[o + 1]), "+f"(d[o + 2]), "+f"(d[o + 3])
#define R8(o) R4(o), R4(o + 4)
__device__ __forceinline__ void wgmma_n128(float* d, desc_t da, desc_t db, int sc) {
    asm volatile("{.reg .pred p; setp.ne.b32 p, %66, 0;\n"
                 "wgmma.mma_async.sync.aligned.m64n128k16.f32.bf16.bf16 {%0,%1,%2,%3,%4,%5,%6,%7,%8,%9,%10,%11,%12,%13,%14,%15,%16,%17,%18,%19,%20,%21,%22,%23,%24,%25,%26,%27,%28,%29,%30,%31,"
                 "%32,%33,%34,%35,%36,%37,%38,%39,%40,%41,%42,%43,%44,%45,%46,%47,%48,%49,%50,%51,%52,%53,%54,%55,%56,%57,%58,%59,%60,%61,%62,%63}, %64, %65, p, 1, 1, 0, 1;}"
                 : R8(0), R8(8), R8(16), R8(24), R8(32), R8(40), R8(48), R8(56)
                 : "l"(da), "l"(db), "r"(sc));
}
__device__ __forceinline__ void wgmma_n112(float* d, desc_t da, desc_t db, int sc) {
    asm volatile("{.reg .pred p; setp.ne.b32 p, %58, 0;\n"
                 "wgmma.mma_async.sync.aligned.m64n112k16.f32.bf16.bf16 {%0,%1,%2,%3,%4,%5,%6,%7,%8,%9,%10,%11,%12,%13,%14,%15,%16,%17,%18,%19,%20,%21,%22,%23,%24,%25,%26,%27,%28,%29,%30,%31,%32,%33,%34,%35,%36,%37,%38,%39,%40,%41,%42,%43,%44,%45,%46,%47,%48,%49,%50,%51,%52,%53,%54,%55}, %56, %57, p, 1, 1, 0, 1;}"
                 : R8(0), R8(8), R8(16), R8(24), R8(32), R8(40), R8(48)
                 : "l"(da), "l"(db), "r"(sc));
}
__device__ __forceinline__ void wgmma_n128_tn(float* d, desc_t da, desc_t db, int sc) {
    asm volatile("{.reg .pred p; setp.ne.b32 p, %66, 0;\n"
                 "wgmma.mma_async.sync.aligned.m64n128k16.f32.bf16.bf16 {%0,%1,%2,%3,%4,%5,%6,%7,%8,%9,%10,%11,%12,%13,%14,%15,%16,%17,%18,%19,%20,%21,%22,%23,%24,%25,%26,%27,%28,%29,%30,%31,%32,%33,%34,%35,%36,%37,%38,%39,%40,%41,%42,%43,%44,%45,%46,%47,%48,%49,%50,%51,%52,%53,%54,%55,%56,%57,%58,%59,%60,%61,%62,%63}, %64, %65, p, 1, 1, 1, 0;}"
                 : R8(0), R8(8), R8(16), R8(24), R8(32), R8(40), R8(48), R8(56)
                 : "l"(da), "l"(db), "r"(sc));
}
__device__ __forceinline__ void wgmma_n64(float* d, desc_t da, desc_t db, int sc) {
    asm volatile("{.reg .pred p; setp.ne.b32 p, %34, 0;\n"
                 "wgmma.mma_async.sync.aligned.m64n64k16.f32.bf16.bf16 {%0,%1,%2,%3,%4,%5,%6,%7,%8,%9,%10,%11,%12,%13,%14,%15,%16,%17,%18,%19,%20,%21,%22,%23,%24,%25,%26,%27,%28,%29,%30,%31}, %32, %33, p, 1, 1, 0, 1;}"
                 : R8(0), R8(8), R8(16), R8(24)
                 : "l"(da), "l"(db), "r"(sc));
}
__device__ __forceinline__ void wgmma_n40_tt(float* d, desc_t da, desc_t db, int sc) {
    asm volatile("{.reg .pred p; setp.ne.b32 p, %22, 0;\n"
                 "wgmma.mma_async.sync.aligned.m64n40k16.f32.bf16.bf16 {%0,%1,%2,%3,%4,%5,%6,%7,%8,%9,%10,%11,%12,%13,%14,%15,%16,%17,%18,%19}, %20, %21, p, 1, 1, 1, 1;}"
                 : R8(0), R8(8), R4(16)
                 : "l"(da), "l"(db), "r"(sc));
}

__device__ __forceinline__ void wgmma_n8_tt(float* d, desc_t da, desc_t db, int sc) {
    asm volatile("{.reg .pred p; setp.ne.b32 p, %6, 0;\n"
                 "wgmma.mma_async.sync.aligned.m64n8k16.f32.bf16.bf16 {%0,%1,%2,%3}, %4, %5, p, 1, 1, 1, 1;}"
                 : R4(0)
                 : "l"(da), "l"(db), "r"(sc));
}

__device__ __forceinline__ void signal_after(unsigned* cnt, uint32_t ack, uint32_t zero, bool pred) {
    asm volatile("{.reg .pred p; setp.ne.u32 p, %2, 0; @p red.relaxed.gpu.global.add.u32 [%0], %1;}"
                 ::"l"(cnt), "r"((ack & zero) + 1), "r"((uint32_t)pred) : "memory");
}
__device__ __forceinline__ void signal_late(unsigned* cnt, const uint32_t* a, uint32_t zero, bool pred) {
    uint32_t v;
    asm volatile("{.reg .b32 t; lop3.b32 t, %1, %2, %3, 0xfe; or.b32 %0, t, %4;}"
                 : "=r"(v) : "r"(a[0]), "r"(a[1]), "r"(a[2]), "r"(a[3]));
    signal_after(cnt, v, zero, pred);
}
__device__ __forceinline__ void mma16816_z(float* c, const uint32_t* a, uint32_t b0, uint32_t b1) {
    asm("mma.sync.aligned.m16n8k16.row.col.f32.bf16.bf16.f32 {%0,%1,%2,%3}, {%4,%5,%6,%7}, {%8,%9}, {%10,%10,%10,%10};"
                 : "=f"(c[0]), "=f"(c[1]), "=f"(c[2]), "=f"(c[3])
                 : "r"(a[0]), "r"(a[1]), "r"(a[2]), "r"(a[3]), "r"(b0), "r"(b1), "f"(0.f));
}
__device__ __forceinline__ uint32_t max2(uint32_t a, uint32_t b) { uint32_t r; asm("max.bf16x2 %0, %1, %2;" : "=r"(r) : "r"(a), "r"(b)); return r; }
__device__ __forceinline__ uint32_t min2(uint32_t a, uint32_t b) { uint32_t r; asm("min.bf16x2 %0, %1, %2;" : "=r"(r) : "r"(a), "r"(b)); return r; }
__device__ __forceinline__ void mbar_arrive_n_if(uint32_t bar, uint32_t n, bool pred) {
    asm volatile("{.reg .pred p; setp.ne.u32 p, %1, 0; @p mbarrier.arrive.shared::cta.b64 _, [%0], %2;}" ::"r"(bar), "r"((uint32_t)pred), "r"(n) : "memory");
}
__device__ __forceinline__ float4 lds_f4(uint32_t a) {
    float4 v;
    asm volatile("ld.shared.v4.f32 {%0,%1,%2,%3}, [%4];" : "=f"(v.x), "=f"(v.y), "=f"(v.z), "=f"(v.w) : "r"(a) : "memory");
    return v;
}
__device__ __forceinline__ void lds_f4_if(float4& v, uint32_t a, bool pred) {
    asm volatile("{.reg .pred p; setp.ne.u32 p, %5, 0; @p ld.shared.v4.f32 {%0,%1,%2,%3}, [%4];}"
                 : "+f"(v.x), "+f"(v.y), "+f"(v.z), "+f"(v.w) : "r"(a), "r"((uint32_t)pred) : "memory");
}
__device__ __forceinline__ uint4 ld_tagged_rlx(const unsigned long long* p) {
    unsigned long long a, b;
    asm volatile("ld.relaxed.gpu.global.v2.b64 {%0,%1}, [%2];" : "=l"(a), "=l"(b) : "l"(p) : "memory");
    return make_uint4((unsigned)a, (unsigned)(a >> 32), (unsigned)b, (unsigned)(b >> 32));
}
__device__ __forceinline__ void sts32(uint32_t a, uint32_t x) { asm volatile("st.shared.u32 [%0], %1;" ::"r"(a), "r"(x) : "memory"); }
__device__ __forceinline__ void fetch_tagged(const unsigned long long* src, uint32_t dst, unsigned epoch, unsigned ns) {
    uint4 v;
    uint32_t it = 0;
    while (true) {
        v = ld_tagged_rlx(src);
        if (!__any_sync(0xffffffffu, v.y != epoch || v.w != epoch)) break;
        __nanosleep(ns);
        trap_if_gt(++it, 1u << 22);
    }
    sts64(dst, v.x, v.z);
}
__device__ __forceinline__ void st_tagged_if(unsigned long long* p, float a, float b, unsigned tag, bool pred) {
    const unsigned long long t = (unsigned long long)tag << 32;
    asm volatile("{.reg .pred p; setp.ne.u32 p, %3, 0; @p st.relaxed.gpu.global.v2.b64 [%0], {%1,%2};}"
                 ::"l"(p), "l"(t | __float_as_uint(a)), "l"(t | __float_as_uint(b)), "r"((uint32_t)pred) : "memory");
}

__device__ __forceinline__ void store_tile(uint32_t tile_rows, uint4* gdst, const uint32_t* lo, const uint32_t* hi, int lane, uint32_t* ack) {
    const int r = lane & 15;
#pragma unroll
    for (int b = 0; b < 4; b++)
        stsm4(tile_rows + r * 128 + (((2 * b + (lane >> 4)) ^ (r & 7)) << 4), lo[2 * b], hi[2 * b], lo[2 * b + 1], hi[2 * b + 1]);
    fence_async_smem();
    __syncwarp();
#pragma unroll
    for (int i = 0; i < 4; i++) {
        const uint4 v = lds128(tile_rows + i * 512 + lane * 16);
        stg128(gdst + 32 * i, v.x, v.y, v.z, v.w);
    }
#pragma unroll
    for (int i = 0; i < 4; i++) ack[i] = readback(gdst + 32 * i);
}

__device__ __forceinline__ void feature_maps(const uint32_t* a, const uint32_t* wb, float c0, float c1, uint32_t* plus, uint32_t* minus) {
    uint32_t P[16], mx[4], mn[4];
#pragma unroll
    for (int h = 0; h < 4; h++) {
        float p[8];
        mma16816_z(p, a + 4 * h, wb[4 * h], wb[4 * h + 1]);
        mma16816_z(p + 4, a + 4 * h, wb[4 * h + 2], wb[4 * h + 3]);
        P[4 * h] = pack_bf16(p[0], p[2]); P[4 * h + 1] = pack_bf16(p[1], p[3]);
        P[4 * h + 2] = pack_bf16(p[4], p[6]); P[4 * h + 3] = pack_bf16(p[5], p[7]);
        mx[h] = max2(max2(P[4 * h], P[4 * h + 1]), max2(P[4 * h + 2], P[4 * h + 3]));
        mn[h] = min2(min2(P[4 * h], P[4 * h + 1]), min2(P[4 * h + 2], P[4 * h + 3]));
    }
#pragma unroll
    for (int s = 1; s <= 2; s <<= 1) {
        uint32_t tx[4], tn[4];
#pragma unroll
        for (int h = 0; h < 4; h++) { tx[h] = __shfl_xor_sync(0xffffffffu, mx[h], s); tn[h] = __shfl_xor_sync(0xffffffffu, mn[h], s); }
#pragma unroll
        for (int h = 0; h < 4; h++) { mx[h] = max2(mx[h], tx[h]); mn[h] = min2(mn[h], tn[h]); }
    }
#pragma unroll
    for (int h = 0; h < 4; h++) {
        const float mx0 = bf_lo(mx[h]) * c0, mx1 = bf_hi(mx[h]) * c1, mn0 = bf_lo(mn[h]) * c0, mn1 = bf_hi(mn[h]) * c1;
        float ep[8], em[8];
#pragma unroll
        for (int i = 0; i < 8; i++) {
            const bool r1 = (i & 2);
            const uint32_t w = P[4 * h + (i >> 2) * 2 + (i & 1)];
            const float p = r1 ? bf_hi(w) : bf_lo(w);
            ep[i] = ex2(fmaf(p, r1 ? c1 : c0, r1 ? -mx1 : -mx0));
            em[i] = ex2(fmaf(p, r1 ? -c1 : -c0, r1 ? mn1 : mn0));
        }
        float sp[4], sm[4];
        uint32_t tp[4], tm[4];
#pragma unroll
        for (int i = 0; i < 4; i++) { tp[i] = pack_bf16(ep[2 * i], ep[2 * i + 1]); tm[i] = pack_bf16(em[2 * i], em[2 * i + 1]); }
        mma16816_z(sp, tp, 0x3f803f80u, 0x3f803f80u);
        mma16816_z(sm, tm, 0x3f803f80u, 0x3f803f80u);
        const float r0 = rcp(sp[0] * sm[0]), r1 = rcp(sp[2] * sm[2]);
        const float rs[4] = {r0 * sm[0], r1 * sm[2], r0 * sp[0], r1 * sp[2]};
#pragma unroll
        for (int i = 0; i < 4; i++) {
            plus[4 * h + i] = pack_bf16(ep[2 * i] * rs[i & 1], ep[2 * i + 1] * rs[i & 1]);
            minus[4 * h + i] = pack_bf16(em[2 * i] * rs[2 + (i & 1)], em[2 * i + 1] * rs[2 + (i & 1)]);
        }
    }
}

template <bool SCALE>
__device__ __forceinline__ void ln_frag(const float* acc, uint32_t cs_addr, float rs0, float nm0, float rs1, float nm1, uint32_t* a) {
    const float2 c0 = lds_f2(cs_addr), c1 = lds_f2(cs_addr + 32);
    const float s0 = SCALE ? rs0 : 1.f, s1 = SCALE ? rs1 : 1.f;
    a[0] = pack_bf16(fmaf(nm0, c0.x, acc[0]) * s0, fmaf(nm0, c0.y, acc[1]) * s0);
    a[1] = pack_bf16(fmaf(nm1, c0.x, acc[2]) * s1, fmaf(nm1, c0.y, acc[3]) * s1);
    a[2] = pack_bf16(fmaf(nm0, c1.x, acc[4]) * s0, fmaf(nm0, c1.y, acc[5]) * s0);
    a[3] = pack_bf16(fmaf(nm1, c1.x, acc[6]) * s1, fmaf(nm1, c1.y, acc[7]) * s1);
}

template <int UP>
__device__ __forceinline__ uint32_t hh_pair(const float* ag, float4 cs, float nmean) {
    const float g0 = fmaf(nmean, cs.x, ag[0]), g1 = fmaf(nmean, cs.y, ag[1]);
    const float u0 = fmaf(nmean, cs.z, ag[UP]), u1 = fmaf(nmean, cs.w, ag[UP + 1]);
    return pack_bf16(g0 * u0, g1 * u1);
}
template <int NTP>
__device__ __forceinline__ void hh_stage(const float* acc, const float4* cs, float nm0, float nm1, uint32_t stg, int lane) {
#pragma unroll
    for (int tp = 0; tp < NTP; tp++)
        stsm4(stg + (lane & 15) * 128 + (((2 * tp + (lane >> 4)) ^ (lane & 7)) << 4), hh_pair<32>(acc + 8 * tp, cs[2 * tp], nm0),
              hh_pair<32>(acc + 8 * tp + 2, cs[2 * tp], nm1), hh_pair<32>(acc + 8 * tp + 4, cs[2 * tp + 1], nm0),
              hh_pair<32>(acc + 8 * tp + 6, cs[2 * tp + 1], nm1));
    fence_async_smem();
    __syncwarp();
}

template <int TP0, int TP1>
__device__ __forceinline__ void hh_stage2(const float* acc, const float4* cs, float nm0, float nm1, uint32_t stg, int lane) {
#pragma unroll
    for (int tp = TP0; tp < TP1; tp++)
        stsm4(stg + (lane & 15) * 128 + (((2 * tp + (lane >> 4)) ^ (lane & 7)) << 4), hh_pair<32>(acc + 8 * tp, cs[2 * tp], nm0),
              hh_pair<32>(acc + 8 * tp + 2, cs[2 * tp], nm1), hh_pair<32>(acc + 8 * tp + 4, cs[2 * tp + 1], nm0),
              hh_pair<32>(acc + 8 * tp + 6, cs[2 * tp + 1], nm1));
}
__device__ __forceinline__ void centre4(const float* acc, const float2* c, float nm0, float nm1, uint32_t* a) {
#pragma unroll
    for (int t = 0; t < 8; t++) {
        a[2 * t] = pack_bf16(fmaf(nm0, c[t].x, acc[4 * t]), fmaf(nm0, c[t].y, acc[4 * t + 1]));
        a[2 * t + 1] = pack_bf16(fmaf(nm1, c[t].x, acc[4 * t + 2]), fmaf(nm1, c[t].y, acc[4 * t + 3]));
    }
}

struct Ring {
    int slot; uint32_t phase;
    __device__ __forceinline__ void adv() { if (++slot == NB) { slot = 0; phase ^= 1; } }
    __device__ __forceinline__ void adv5() { slot += slot == 3; adv(); }
};

__global__ void __cluster_dims__(2, 1, 1) __launch_bounds__(NTHREADS, 1) fused_kernel(const __grid_constant__ Params P) {
    extern __shared__ __align__(1024) uint8_t smem_raw[];
    const uint32_t sb = smem_u32(smem_raw);
    const int tid = threadIdx.x, lane = tid & 31;
    const int warp = __shfl_sync(0xffffffffu, tid >> 5, 0);
    const unsigned rank = blockIdx.x & 1;
    int m, j;
    {
        const int t = (int)(blockIdx.x >> 1) - 4, u = t - 32, r7 = (u * 37) >> 8;
        const int gp = t < 32 ? (t & 7) - 1 : u - 7 * r7;
        j = t < 0 ? t + 8 : (t < 32 ? t >> 3 : 4 + r7);
        m = ((t < 0 || gp < 0) ? 14 : 2 * gp) + rank;
        if (t >= 60) { m = 16; j = blockIdx.x - 128; }
    }
    const unsigned role = m * 8 + j;
    const bool helper = m == 16;

    TL(0, tid == 0); TLG(0, tid == 0);
    float* const acc_j = g_acc + j * ACC_SIZE;
    if ((warp & ~1) == 8 && elect_one()) {
        const uint32_t bar = sb + (warp == 8 ? BAR_FULLB : BAR_FULLA);
#pragma unroll
        for (int i = 0; i < 8; i++) if (i < NB || warp == 9) mbar_init(bar + 8 * i, 1);
        if (!helper) {
#pragma unroll 1
            for (int i = 0; i < NPRE; i++) {
                mbar_expect_tx(bar + 8 * i, SLOT);
                if (warp == 8) {
                    tma2d(sb + OFF_B + i * SLOT, &P.twq, bar + 8 * i, DM + 64 * j, 64 * i);
                    tma2d(sb + OFF_B + i * SLOT + 8192, &P.twq, bar + 8 * i, 2 * DM + 64 * j, 64 * i);
                } else {
                    tma2d(sb + OFF_A + i * SLOT, &P.tx, bar + 8 * i, 64 * i, 128 * m);
                }
            }
        }
    }
    __syncwarp();

    if (warp >= 8) {
        asm volatile("setmaxnreg.dec.sync.aligned.u32 72;");
        if (elect_one()) {
            if (warp < 10) {
            } else if (warp == 10) {
#pragma unroll
                for (int i = 0; i < 12; i++) mbar_init(sb + BAR_CS1 + 8 * i, i < 2 || i >= 8 ? 64 : (i < 4 ? 32 : 8));
                trap_if_gt(sb & 1023, 0);
            } else {
#pragma unroll
                for (int i = 0; i < 14; i++) mbar_init(sb + (i < 8 ? BAR_EMPTYA : BAR_EMPTYB - 64) + 8 * i, i < 8 ? 8 : 16);
            }
            asm volatile("fence.mbarrier_init.release.cluster;" ::: "memory");
        }
        __syncwarp();
        asm volatile("barrier.cluster.arrive.relaxed.aligned;" ::: "memory");
        const unsigned epoch = ld_relaxed(&g_epoch);
        bar_sync(0, NTHREADS);
        if (helper) {
            if (elect_one()) {
#pragma unroll 1
                for (int i = warp - 8; i < 72; i += 4) {
                    const uint32_t full = sb + BAR_FULLA + 8 * (i & 7), dst = sb + OFF_A + (i & 7) * SLOT;
                    const int n = i >> 1, jj = 2 * j + (i & 1);
                    const bool qkv = n < 12;
                    const int c0 = qkv ? (n < 8 ? DM + 128 * (n & 4) : 0) + 64 * jj : 176 * jj + 8 * ((n - 12) & ~7);
                    const int r0 = qkv ? 128 * (n & 3) : 64 * ((n - 12) & 7);
                    mbar_wait(sb + BAR_EMPTYA + 8 * (i & 7), ((i >> 3) & 1) ^ 1);
                    mbar_expect_tx(full, SLOT);
                    tma2d(dst, qkv ? &P.twq : &P.twg, full, c0, r0);
                    tma2d(dst + 8192, qkv ? &P.twq : &P.twu, full, c0, qkv ? r0 + 64 : r0);
                }
                prefetch_l2(P.wd + (size_t)(4 * j + warp - 8) * 44032, 88064);
            }
            return;
        }
        if (warp == 8) {
            asm volatile("barrier.cluster.wait.aligned;" ::: "memory");
            if (elect_one()) {
                if (m >= 6)
                    asm volatile("cp.async.bulk.prefetch.tensor.2d.L2.global [%0, {%1, %2}];" ::"l"(&P.twq), "r"(DM + DM * (m & 1) + 64 * j), "r"(64 * (m >> 1)) : "memory");
                if (j >= 3)
                    asm volatile("cp.async.bulk.prefetch.tensor.2d.L2.global [%0, {%1, %2}];" ::"l"(&P.tx), "r"(64 * j), "r"(128 * m) : "memory");
                Ring r{NPRE, 0};
                const uint32_t dst = sb + OFF_B + rank * 8192;
#define B_LOADN(TM, C0, R0, NB_)                                                                                \
        mbar_waitc(sb + BAR_EMPTYB + 8 * r.slot, r.phase ^ 1);                                              \
        mbar_expect_tx(sb + BAR_FULLB + 8 * r.slot, NB_);                                                   \
        tma2d_mc(dst + r.slot * SLOT, TM, sb + BAR_FULLB + 8 * r.slot, C0, R0);
#define B_LOAD(TM, C0, R0) B_LOADN(TM, C0, R0, SLOT)
#pragma unroll 1
                for (int i = NPRE; i < 8; i++) {
                    if (i >= AHEAD && i < 6) mbar_waitc(sb + BAR_FULLB + 8 * (i - AHEAD), 0);
                    B_LOAD(&P.twq, DM + DM * rank + 64 * j, 64 * i)
                    r.adv();
                }
#pragma unroll 1
                for (int i = 8; i < 18; i++) {
                    if (i == 9 || i == 10) {
                        mbar_waitc(sb + BAR_EMPTYB + 8 * r.slot, r.phase ^ 1);
                        mbar_arrive(sb + BAR_FULLB + 8 * r.slot);
                    } else {
                        const int e = 2 * (i - 14) + rank, b = (i == 8 ? 0 : i - 10) ^ (i < 12 && j < 2);
                        B_LOAD(i < 14 ? &P.twq : &P.two, 64 * j, 64 * (i < 14 ? 2 * b + rank : KORD(e, j)))
                    }
                    r.adv();
                }
#pragma unroll 1
                for (int i = 0; i < 24; i++) {
                    B_LOAD(&P.twg + rank, 176 * j + 8 * (i & ~7), 64 * (i < 8 ? KORD(i, j) : i & 7))
                    r.adv5();
                }
#pragma unroll 1
                for (int i = 0; i < 12; i++) {
                    B_LOADN(&P.twd + (i >> 3), 64 * j, 176 * (2 * (i & 3) + rank) + 64 * (i >> 2), i < 8 ? SLOT : 12288)
                    r.adv5();
                }
            }
            return;
        }
        if (warp == 9) {
            if (elect_one()) {
#pragma unroll 1
                for (int i = NPRE; i < 8; i++) {
                    if (i >= AHEADA) mbar_wait(sb + BAR_FULLA + 8 * (i - AHEADA), 0);
                    mbar_expect_tx(sb + BAR_FULLA + 8 * i, SLOT);
                    tma2d(sb + OFF_A + i * SLOT, &P.tx, sb + BAR_FULLA + 8 * i, 64 * i, 128 * m);
                }
#pragma unroll 1
                for (int i = 2; i < 8; i++) prefetch_tmap(&P.tx + i);
                unsigned nf = 0;
#pragma unroll 1
                for (int r = 1; r < 6; r++) {
                    const int skip = r < 3 ? j : 8;
                    const uint32_t bytes = r == 5 ? 12288 : SLOT;
                    const uint4* src = g_act + ((r - 1) * 128 + m * 8) * 1024;
                    const unsigned* fl = g_flag + (m * 5 + r - 1) * 32;
                    if (r < 4) mbar_wait(sb + BAR_EMPTYA + 8 * (r == 3 ? PF_DELAY : 3 - 2 * (j == 3)), (r - 1) & 1);
                    const unsigned tgt = epoch * (r < 3 ? 64 : 8);
                    if (nf != tgt) wait_count(fl, tgt);
                    TL(64 + r, true);
#pragma unroll 1
                    for (int t = 0; t < 8; t++) {
                        if (t == skip) continue;
                        if (t == 6 && r < 5) nf = readback(fl + 32);
                        mbar_wait(sb + BAR_EMPTYA + 8 * t, (r - 1) & 1);
                        mbar_expect_tx(sb + BAR_FULLA + 8 * t, bytes);
                        asm volatile("cp.async.bulk.shared::cluster.global.mbarrier::complete_tx::bytes [%0], [%1], %2, [%3];"
                                     ::"r"(sb + OFF_A + t * SLOT), "l"(src + t * 1024), "r"(bytes), "r"(sb + BAR_FULLA + 8 * t) : "memory");
                    }
                }
            }
            return;
        }
        const int a = warp - 10;
        {
            const int row = 16 * j + 8 * a + (lane >> 2);
            const uint32_t ra = sb + OFF_A + row * 128;
            float sh = 0.f, s0 = 0.f, s1 = 0.f, q0 = 0.f, q1 = 0.f;
#pragma unroll 1
            for (int kt = 0; kt < 8; kt++) {
                mbar_wait(sb + BAR_FULLA + 8 * kt, 0);
                if (kt == 0) sh = bf_lo(lds128(ra + ((row & 7) << 4)).x);
#pragma unroll
                for (int i = 0; i < 2; i++) {
                    const uint4 v = lds128(ra + kt * SLOT + (((2 * (lane & 3) + i) ^ (row & 7)) << 4));
                    const uint32_t ww[4] = {v.x, v.y, v.z, v.w};
#pragma unroll
                    for (int e = 0; e < 4; e++) {
                        const float d0 = bf_lo(ww[e]) - sh, d1 = bf_hi(ww[e]) - sh;
                        s0 += d0; q0 = fmaf(d0, d0, q0);
                        s1 += d1; q1 = fmaf(d1, d1, q1);
                    }
                }
            }
            s0 += s1; q0 += q1;
#pragma unroll
            for (int o = 1; o <= 2; o <<= 1) { s0 += __shfl_xor_sync(0xffffffffu, s0, o); q0 += __shfl_xor_sync(0xffffffffu, q0, o); }
            const float md = s0 * (1.f / DM);
            const float rs = rsqrtf(fmaxf(q0 * (1.f / DM) - md * md, 0.f) + 1e-5f);
            st_tagged_if(g_xstat + 2 * (128 * m + row), rs, -(sh + md), epoch, (lane & 3) == 0);
            TL(1, lane == 0 && a == 0);
        }
        const unsigned long long* cs = g_cs + j * 768 + 2 * lane;
        {
            const unsigned long long* xs = g_xstat + 2 * (128 * m + 64 * a + lane);
            uint4 v0, v1, v2;
            uint32_t it = 0;
            __nanosleep(250);
            do {
                v0 = ld_tagged_rlx(xs); v1 = ld_tagged_rlx(xs + 64); v2 = ld_tagged_rlx(cs);
                trap_if_gt(++it, 1u << 22);
            } while (__any_sync(0xffffffffu, v0.y != epoch || v0.w != epoch || v1.y != epoch || v1.w != epoch || v2.y != epoch || v2.w != epoch));
            sts64(sb + OFF_XST + (64 * a + lane) * 8, v0.x, v0.z);
            sts64(sb + OFF_XST + (64 * a + 32 + lane) * 8, v1.x, v1.z);
            sts64(sb + OFF_CS1 + 256 + 8 * lane, v2.x, v2.z);
            mbar_arrive(sb + BAR_CS1);
            TL(22 + a, lane == 0);
            fetch_tagged(cs + 128 + 128 * a, sb + OFF_CS1 + 512 - 512 * a + 8 * lane, epoch, 200);
            mbar_arrive(sb + BAR_CSV - 8 * a);
            TL(24 + a, lane == 0);
        }
        {
            mbar_wait(sb + BAR_KVW, 0);
            const float* src = acc_j + 4 * (128 * a + lane);
            float4 v[12];
            uint32_t it = 0;
            bool bad;
            while (__any_sync(0xffffffffu, readback(acc_j + 2048 + 128 * (lane & 7) + 127) != 0x41800000u)) trap_if_gt(++it, 1u << 22);
            TL(19, lane == 0 && a == 0);
            do {
                bad = false;
#pragma unroll
                for (int i = 0; i < 12; i++) v[i] = ld_l2_f4(src + 1024 * (i % 3) + 128 * (i / 3));
#pragma unroll
                for (int i = 0; i < 12; i++) bad |= v[i].w != 16.f;
                trap_if_gt(++it, 1u << 22);
            } while (__any_sync(0xffffffffu, bad));
            TL(14, lane == 0 && a == 0);
            const uint32_t d0 = sb + OFF_A + (j < 2 ? 2 * SLOT : 0) + (64 * a + (lane >> 2)) * 48;
            const uint32_t d = d0 + (lane & 3) * 4, dz = d0 + (lane & 1) * 384 + 32 + (lane & 2) * 4;
#pragma unroll
            for (int u = 0; u < 4; u++) {
                sts32(d + 768 * u, pack_bf16(v[3 * u].x, v[3 * u].y));
                sts32(d + 768 * u + 384, pack_bf16(v[3 * u].z, v[3 * u + 1].z));
                sts32(d + 768 * u + 16, pack_bf16(v[3 * u + 1].x, v[3 * u + 1].y));
                sts32(d + 768 * u + 400, pack_bf16(v[3 * u + 2].x, v[3 * u + 2].y));
                const uint32_t z2 = pack_bf16(v[3 * u + 2].z, v[3 * u + 2].z);
                sts64(dz + 768 * u, z2, z2);
            }
            mbar_arrive(sb + BAR_KVR);
        }
#pragma unroll 1
        for (int c = 0; c < 3; c++) {
            fetch_tagged(cs + 384 + 128 * c + 64 * a, sb + OFF_CS3 + (32 * c + lane) * 16 + 8 * a, epoch, 1000);
            mbar_arrive(sb + BAR_CSG + 8 * c);
            TL(45 + c, lane == 0 && a == 0);
        }
        {
            uint32_t it = 0;
            while (__any_sync(0xffffffffu, (int)(readback(g_flag + (m * 5 + 1) * 32) - epoch * 64) < 0)) {
                __nanosleep(600);
                trap_if_gt(++it, 1u << 22);
            }
#pragma unroll 1
            for (int rr = 0; rr < 2; rr++) {
                const int row = 64 * rr + 32 * a + lane;
                const unsigned long long* hs = g_hstat + (1024 * m + row) * 2;
                uint4 v[8];
                bool bad;
                do {
                    bad = false;
#pragma unroll
                    for (int i = 0; i < 8; i++) v[i] = ld_tagged_rlx(hs + 256 * i);
#pragma unroll
                    for (int i = 0; i < 8; i++) bad |= v[i].y != epoch || v[i].w != epoch;
                    trap_if_gt(++it, 1u << 22);
                } while (__any_sync(0xffffffffu, bad));
                float mean = 0.f;
#pragma unroll
                for (int i = 0; i < 8; i++) mean += __uint_as_float(v[i].x);
                mean *= 0.125f;
                float m2 = 0.f, dv = 0.f;
#pragma unroll
                for (int i = 0; i < 8; i++) { const float d = __uint_as_float(v[i].x) - mean; m2 += __uint_as_float(v[i].z); dv = fmaf(d, d, dv); }
                sts_f2(sb + OFF_CS1 + row * 8, -mean, rcp(fmaf(dv, 64.f, m2) * (1.f / DM) + 1e-5f));
            }
        }
        mbar_arrive(sb + BAR_CS3);
#pragma unroll 1
        for (int c = a; c < 3; c += 2) {
            mbar_wait(sb + BAR_STG + 8 * c, 0);
            if (elect_one()) {
                asm volatile("cp.async.bulk.global.shared::cta.bulk_group [%0], [%1], %2;" ::"l"(g_act + ((2 + c) * 128 + role) * 1024), "r"(sb + OFF_B + 4 * SLOT), "r"(c == 2 ? 12288 : SLOT) : "memory");
                asm volatile("cp.async.bulk.commit_group;" ::: "memory");
                asm volatile("cp.async.bulk.wait_group.read 0;" ::: "memory");
                mbar_arrive(sb + BAR_FULLB + 8 * 4);
                asm volatile("cp.async.bulk.wait_group 0;" ::: "memory");
            }
            __syncwarp();
            TL(60 + c, lane == 0);
            uint32_t ack = 0;
            const uint4* rb = g_act + ((2 + c) * 128 + role) * 1024 + lane * 8;
#pragma unroll
            for (int i = 0; i < 4; i++) ack |= readback(rb + (i == 3 && c == 2 ? 0 : 256 * i));
            signal_after(g_flag + (m * 5 + 2 + c) * 32, ack, P.zero, lane == 0);
            TL(54 + c, lane == 0);
        }
        return;
    }
    const unsigned epoch = ld_relaxed(&g_epoch);
    uint32_t wraw[16];
    if (!helper) {
        const uint32_t* wp = reinterpret_cast<const uint32_t*>(P.wphi) + (4 * j) * 128 + (lane & 3) * 16 + (lane >> 2);
#pragma unroll
        for (int i = 0; i < 16; i++)
            asm volatile("ld.global.nc.u32 %0, [%1];" : "=r"(wraw[i]) : "l"(wp + (i >> 2) * 128 + ((i >> 1) & 1) * 64 + (i & 1) * 8));
    }
    asm volatile("barrier.cluster.arrive.relaxed.aligned;" ::: "memory");
    asm volatile("setmaxnreg.inc.sync.aligned.u32 216;");
    bar_sync(0, NTHREADS);
    if (helper) {
        const int w = warp >> 2;
        sts64(sb + OFF_B + 8 * tid, 0x3f803f80u, 0x3f803f80u);
        fence_async_smem();
        uint32_t zack[6];
        {
            float* z = g_acc + 2 * j * ACC_SIZE + 4 * tid;
#pragma unroll
            for (int u = 0; u < 6; u++) stg128(z + 1024 * u, 0, 0, 0, 0);
#pragma unroll
            for (int u = 0; u < 6; u++) zack[u] = readback(z + 1024 * u);
        }
        bar_sync(1, 256);
        TL(70, tid == 0);
        float acc[8];
        int i = w;
#pragma unroll 1
        for (int job = 0; job < 6; job++) {
            const int n = job < 3 ? 4 : 8;
#pragma unroll 1
            for (int t = 0; t < n; t++, i += 2) {
                mbar_waitc(sb + BAR_FULLA + 8 * (i & 7), (i >> 3) & 1);
                const desc_t da = desc_lo(sb + OFF_A) + (i & 7) * (SLOT >> 4);
                wg_fence();
#pragma unroll
                for (int k = 0; k < 8; k++) wgmma_n8_tt(acc + (k & 4), da + 128 * k, desc_lo(sb + OFF_B), (t | (k & 3)) != 0);
                wg_commit();
                wg_wait<0>();
                mbar_arrive_n_if(sb + BAR_EMPTYA + 8 * (i & 7), 2, lane == 0);
            }
            fence_acc<8>(acc);
            TL(71 + job, tid == 0);
            if (job == 1) {
                asm volatile("{.reg .pred p; .reg .b32 t; lop3.b32 t, %0, %1, %2, 0xfe; lop3.b32 t, t, %3, %4, 0xfe; or.b32 t, t, %5; setp.ne.u32 p, t, 0; @p trap;}"
                             ::"r"(zack[0]), "r"(zack[1]), "r"(zack[2]), "r"(zack[3]), "r"(zack[4]), "r"(zack[5]));
                bar_sync(1, 256);
            }
            const int q = lane & 3;
            const float lo = (q & 1) ? acc[2] : acc[0], hi = (q & 1) ? acc[6] : acc[4];
            const float v = job < 3 ? lo + hi : ((q & 2) ? hi : lo);
            unsigned long long* dst = g_cs + ((2 * j + w) * 6 + job) * 128 + (q >> 1) * 64 + 16 * (warp & 3) + 8 * (q & 1) + (lane >> 2);
            asm volatile("st.relaxed.gpu.global.b64 [%0], %1;" ::"l"(dst), "l"(((unsigned long long)epoch << 32) | __float_as_uint(v)) : "memory");
        }
        return;
    }
    {
        const int w = warp >> 2, wv = warp & 3, g = lane >> 2, q = lane & 3;
        const uint32_t sa = sb + OFF_A + w * 8192;
        const desc_t dA = desc_lo(sa), dB = desc_lo(sb + OFF_B);
        unsigned* const flag_m = g_flag + m * 160;
        const bool l0 = lane == 0, l2 = lane < 2;
        const uint32_t eb = mapa(sb + BAR_EMPTYB, lane & 1);
        asm volatile("barrier.cluster.wait.aligned;" ::: "memory");
        Ring rg{0, 0};
        int prev = 0;

        uint32_t wb[16];
        constexpr float L2E = 1.4426950408889634f;
        const int ch = lane >> 4, sw = lane & 7;
        const uint32_t lrow = (lane & 15) * 128;
        uint32_t fp[16], fm[16];
        const int vs = j < 2 ? 2 : 0;
        {
            float acc[64];
#pragma unroll 1
            for (int kt = 0; kt < 8; kt++) {
                mbar_waitc(sb + BAR_FULLA + 8 * kt, 0);
                mbar_waitc(sb + BAR_FULLB + 8 * rg.slot, rg.phase);
                const desc_t da = dA + kt * (SLOT >> 4), db = dB + rg.slot * (SLOT >> 4);
                wg_fence();
#pragma unroll
                for (int k = 0; k < 4; k++) wgmma_n128(acc, da + 2 * k, db + 128 * k, (kt | k) != 0);
                wg_commit();
                wg_wait<1>();
                mbar_arrive_cl_if(eb + 8 * prev, l2 && kt > 0);
                prev = rg.slot; rg.adv();
            }
#pragma unroll
            for (int i = 0; i < 8; i++) {
                wb[(i >> 1) * 4 + (i & 1)] = __byte_perm(wraw[2 * i], wraw[2 * i + 1], 0x5410);
                wb[(i >> 1) * 4 + 2 + (i & 1)] = __byte_perm(wraw[2 * i], wraw[2 * i + 1], 0x7632);
            }
            uint32_t a[16];
            float accq[32];
            float2 cq[8];
            mbar_waitc(sb + BAR_CS1, 0);
            const float2 s0 = lds_f2(sb + OFF_XST + (16 * warp + g) * 8), s1 = lds_f2(sb + OFF_XST + (16 * warp + g + 8) * 8);
#pragma unroll
            for (int t = 0; t < 8; t++) cq[t] = lds_f2(sb + OFF_CS1 + (64 + 8 * t + 2 * q) * 4);
            mbar_waitc(sb + BAR_FULLB + 8 * 2, 1);
            wg_fence();
#pragma unroll
            for (int k = 0; k < 8; k++) wgmma_n64(accq, dA + (vs + (k >> 2)) * (SLOT >> 4) + (k & 3) * 2, dB + 2 * (SLOT >> 4) + 128 * k, k != 0);
            wg_commit();
            wg_wait<1>();
            fence_acc<64>(acc);
            mbar_arrive_cl_if(eb + 8 * prev, l2);
            TL(17, tid == 0);
            centre4(acc, cq, s0.y, s1.y, a);
#pragma unroll
            for (int i = 0; i < 16; i++) asm volatile("" : "+r"(a[i]), "+r"(wb[i]));
            wg_wait<0>();
            fence_acc<32>(accq);
            mbar_arrive_cl_if(eb + 8 * 2, l2);
            TL(2, tid == 0);
            const uint32_t st = sb + OFF_B + warp * 2048 + lrow;
#pragma unroll 1
            for (int it = 0; it < 2; it++) {
                feature_maps(a, wb, s0.x * L2E, s1.x * L2E, fp, fm);
                if (it == 0) {
                    mbar_waitc(sb + BAR_FULLB + 8 * 3, 1); mbar_waitc(sb + BAR_FULLB + 8 * 4, 1);
                    mbar_waitc(sb + BAR_CSV, 0);
                    const uint32_t sv = sb + OFF_A + vs * SLOT + warp * 2048 + lrow;
#pragma unroll
                    for (int hh = 0; hh < 4; hh++) {
                        stsm4(st + (3 + (hh >> 1)) * SLOT + (((4 * (hh & 1) + ch) ^ sw) << 4), fp[4 * hh], fp[4 * hh + 1], fp[4 * hh + 2], fp[4 * hh + 3]);
                        stsm4(st + (3 + (hh >> 1)) * SLOT + (((4 * (hh & 1) + 2 + ch) ^ sw) << 4), fm[4 * hh], fm[4 * hh + 1], fm[4 * hh + 2], fm[4 * hh + 3]);
                        ln_frag<true>(acc + 32 + 8 * hh, sb + OFF_CS1 + (128 + 16 * hh + 2 * q) * 4, s0.x, s0.y, s1.x, s1.y, a);
                        stsm4(sv + (hh >> 1) * SLOT + (((2 * (hh & 1) + ch) ^ sw) << 4), a[0], a[1], a[2], a[3]);
                    }
                    stsm4(sv + ch * SLOT + ((4 ^ sw) << 4), 0x3f803f80u, 0x3f803f80u, 0x3f803f80u, 0x3f803f80u);
                    fence_async_smem();
                    bar_sync(1, 256);
                    float kvd[20];
                    wg_fence();
#pragma unroll
                    for (int k = 0; k < 8; k++)
                        wgmma_n40_tt(kvd, dB + (3 + w) * (SLOT >> 4) + 128 * k, desc_lo(sb + OFF_A) + (vs + w) * (SLOT >> 4) + 128 * k, k != 0);
                    wg_commit();
                    wg_wait<0>();
                    fence_acc<20>(kvd);
                    mbar_arrive_cl_if(eb + 8 * (3 + (lane >> 1)), lane < 4);
                    const bool h1 = wv >= 2;
                    float* kvp = acc_j + 4 * tid;
                    red_f32x4(kvp, h1 ? kvd[8] : kvd[0], h1 ? kvd[9] : kvd[1], h1 ? kvd[10] : kvd[2], 1.f);
                    red_f32x4(kvp + 1024, h1 ? kvd[12] : kvd[4], h1 ? kvd[13] : kvd[5], h1 ? kvd[11] : kvd[3], 1.f);
                    red_f32x4(kvp + 2048, h1 ? kvd[14] : kvd[6], h1 ? kvd[15] : kvd[7], (q & 1) ? kvd[18] : kvd[16], 1.f);
                    mbar_arrive_if(sb + BAR_KVW, l0);
                    TL(3, tid == 0);
                    mbar_waitc(sb + BAR_CSQ, 0);
#pragma unroll
                    for (int t = 0; t < 8; t++) cq[t] = lds_f2(sb + OFF_CS1 + (8 * t + 2 * q) * 4);
#pragma unroll 1
                    for (int b = 1; b < 4; b++) {
                        const int slot = b == 1 ? 5 : b - 2;
                        mbar_waitc(sb + BAR_FULLB + 8 * slot, b == 1);
                        const desc_t da = dA + (b == 1 ? 2 - vs : 2 * b) * (SLOT >> 4), db = dB + slot * (SLOT >> 4);
                        wg_fence();
#pragma unroll
                        for (int k = 0; k < 8; k++) wgmma_n64(accq, da + (k >> 2) * (SLOT >> 4) + (k & 3) * 2, db + 128 * k, 1);
                        wg_commit();
                    }
                    wg_wait<0>();
                    fence_acc<32>(accq);
                    mbar_arrive_cl_if(eb + 8 * ((5 + (lane >> 1)) % 6), lane < 6);
                    TL(4, tid == 0);
                    centre4(accq, cq, s0.y, s1.y, a);
                }
            }
        }
        uint32_t res_lo[8], res_hi[8], ack[4];
        const uint32_t own_rows = sb + OFF_A + j * SLOT + warp * 2048;
#pragma unroll
        for (int b = 0; b < 4; b++)
            ldsm4(own_rows + lrow + (((2 * b + ch) ^ sw) << 4), res_lo[2 * b], res_hi[2 * b], res_lo[2 * b + 1], res_hi[2 * b + 1]);
        mbar_arrive_if(sb + BAR_EMPTYA + 8 * lane, lane < 8 && lane != j && lane != vs);
        TL(5, tid == 0);
        mbar_waitc(sb + BAR_KVR, 0);
        TL(6, tid == 0);
        {
            const uint32_t kvs = sb + OFF_A + vs * SLOT;
            uint32_t o_lo[8], o_hi[8];
#pragma unroll
            for (int hh = 0; hh < 4; hh++) {
                uint32_t b[8], zb[4];
                const uint32_t base = kvs + hh * 32 * 48;
                ldsm4t(base + (lane & 15) * 48 + (lane >> 4) * 16, b[0], b[1], b[2], b[3]);
                ldsm4t(base + (16 + (lane & 15)) * 48 + (lane >> 4) * 16, b[4], b[5], b[6], b[7]);
                ldsm4t(base + lane * 48 + 32, zb[0], zb[1], zb[2], zb[3]);
                float n0[4], n1[4], dn[4];
                mma16816_z(n0, fp + 4 * hh, b[0], b[1]); mma16816_z(n1, fp + 4 * hh, b[2], b[3]); mma16816_z(dn, fp + 4 * hh, zb[0], zb[1]);
                mma16816(n0, fm + 4 * hh, b[4], b[5]); mma16816(n1, fm + 4 * hh, b[6], b[7]); mma16816(dn, fm + 4 * hh, zb[2], zb[3]);
                const float i0 = rcp(dn[0] + 1e-6f), i1 = rcp(dn[2] + 1e-6f);
                o_lo[2 * hh] = pack_bf16(n0[0] * i0, n0[1] * i0); o_hi[2 * hh] = pack_bf16(n0[2] * i1, n0[3] * i1);
                o_lo[2 * hh + 1] = pack_bf16(n1[0] * i0, n1[1] * i0); o_hi[2 * hh + 1] = pack_bf16(n1[2] * i1, n1[3] * i1);
            }
            __syncwarp();
            mbar_arrive_if(sb + BAR_EMPTYA + 8 * vs, l0);
            rg.slot = 2; rg.phase = 0;
            store_tile(own_rows, g_act + role * 1024 + warp * 128 + lane, o_lo, o_hi, lane, ack);
            TL(7, tid == 0);
        }
        float acch[32];
        {
            float* acc = acch;
#pragma unroll
            for (int t = 0; t < 8; t++) {
                acc[4 * t] = bf_lo(res_lo[t]); acc[4 * t + 1] = bf_hi(res_lo[t]);
                acc[4 * t + 2] = bf_lo(res_hi[t]); acc[4 * t + 3] = bf_hi(res_hi[t]);
            }
            fence_acc<32>(acc);
            int pa = 0;
#pragma unroll 1
            for (int kp = 0; kp < 4; kp++) {
                mbar_waitc(sb + BAR_FULLB + 8 * rg.slot, rg.phase);
#pragma unroll
                for (int hf = 0; hf < 2; hf++) {
                    const int i = 2 * kp + hf, kt = KORD(i, j);
                    mbar_waitc(sb + BAR_FULLA + 8 * kt, i != 0);
                    TL(8, i == 1 && tid == 0);
                    const desc_t da = dA + kt * (SLOT >> 4), db = dB + rg.slot * (SLOT >> 4);
                    wg_fence();
#pragma unroll
                    for (int k = 0; k < 4; k++) wgmma_n64(acc, da + 2 * k, db + (hf * 4 + k) * 128, 1);
                    wg_commit();
                    wg_wait<1>();
                    mbar_arrive_if(sb + BAR_EMPTYA + 8 * pa, l0 && i > 1);
                    if (hf == 0) {
                        mbar_arrive_cl_if(eb + 8 * prev, l2 && i > 0);
                        if (i == 0) { signal_late(flag_m, ack, P.zero, l0); TL(20, tid == 0); }
                    }
                    pa = kt;
                }
                prev = rg.slot; rg.adv();
            }
            wg_wait<0>();
            fence_acc<32>(acc);
            mbar_arrive_if(sb + BAR_EMPTYA + 8 * pa, l0);
            mbar_arrive_cl_if(eb + 8 * prev, l2);
            TL(9, tid == 0);
#pragma unroll
            for (int t = 0; t < 8; t++) {
                res_lo[t] = pack_bf16(acc[4 * t], acc[4 * t + 1]);
                res_hi[t] = pack_bf16(acc[4 * t + 2], acc[4 * t + 3]);
            }
            store_tile(own_rows, g_act + (128 + role) * 1024 + warp * 128 + lane, res_lo, res_hi, lane, ack);
            TL(10, tid == 0);
        }
        float acc0[64], acc1[64], acc2[56], nm0, nm1;
        float4 cs[8];
        uint32_t hr[16];
#define P3_GROUP(MMA, ACC, KT)                                                                              \
        mbar_waitc(sb + BAR_FULLB + 8 * rg.slot, rg.phase);                                                 \
        {                                                                                                   \
            const desc_t da = dA + (KT) * (SLOT >> 4), db = dB + rg.slot * (SLOT >> 4);                     \
            wg_fence();                                                                                     \
            _Pragma("unroll") for (int k = 0; k < 4; k++) MMA(ACC, da + 2 * k, db + 128 * k, (i | k) != 0); \
            wg_commit();                                                                                    \
        }
#define P3_CS(C, NT)    \
        _Pragma("unroll") for (int t = 0; t < (NT); t++) lds_f4_if(cs[t], sb + OFF_CS3 + q * 16 + 512 * (C) + 64 * t, i == t);
#define P3_EPI2(C, ACC)                                                                                     \
        if (i == 0) {                                                                                       \
            fence_acc<64>(ACC);                                                                             \
            if (C) mbar_waitc(sb + BAR_FULLB + 8 * 4, 1);                                                   \
            hh_stage2<0, 2>(ACC, cs, nm0, nm1, stg, lane);                                                  \
            mbar_waitc(sb + BAR_CSG + 8 * (C) + 8, 0);                                                      \
        }                                                                                                   \
        if (i == 1) {                                                                                       \
            hh_stage2<2, 4>(ACC, cs, nm0, nm1, stg, lane);                                                  \
            fence_async_smem();                                                                             \
            __syncwarp();                                                                                   \
            mbar_arrive_if(sb + BAR_STG + 8 * (C), l0);                                                     \
        }
#define P3_EPI(C, ACC, N, NTP)                                                                              \
        fence_acc<N>(ACC);                                                                                  \
        TL(11 + (C), tid == 0);                                                                             \
        hh_stage<NTP>(ACC, cs, nm0, nm1, sb + OFF_B + 4 * SLOT + warp * 2048, lane);                        \
        mbar_arrive_if(sb + BAR_STG + 8 * (C), l0);                                                         \
        TL(50 + (C), tid == 0);
        const uint32_t stg = sb + OFF_B + 4 * SLOT + warp * 2048;
        const uint32_t blk = ((lane & 7) + (lane >> 4) * 8) * 128 + (((2 * wv + ((lane >> 3) & 1)) ^ (lane & 7)) << 4);
#pragma unroll 1
        for (int i = 0; i < 8; i++) {
            const int kt = KORD(i, j);
            mbar_waitc(sb + BAR_FULLA + 8 * kt, 0);
            TL(44, tid == 0 && i == 1);
            P3_GROUP(wgmma_n128, acc0, kt)
            if (i == 7) {
                mbar_waitc(sb + BAR_CS3, 0);
                nm0 = lds_f2(sb + OFF_CS1 + (16 * warp + g) * 8).x; nm1 = lds_f2(sb + OFF_CS1 + (16 * warp + g + 8) * 8).x;
            }
            wg_wait<1>();
            mbar_arrive_cl_if(eb + 8 * prev, l2 && i > 0);
            if (i == 0) {
                signal_late(flag_m + 32, ack, P.zero, l0);
                TL(21, tid == 0);
                {
                    fence_acc<32>(acch);
                    const float* acc = acch;
                    float s0 = 0.f, s1 = 0.f;
#pragma unroll
                    for (int t = 0; t < 8; t++) { s0 += acc[4 * t] + acc[4 * t + 1]; s1 += acc[4 * t + 2] + acc[4 * t + 3]; }
            s0 += __shfl_xor_sync(0xffffffffu, s0, 1); s1 += __shfl_xor_sync(0xffffffffu, s1, 1);
            s0 += __shfl_xor_sync(0xffffffffu, s0, 2); s1 += __shfl_xor_sync(0xffffffffu, s1, 2);
            const float mu0 = s0 * (1.f / 64), mu1 = s1 * (1.f / 64);
            float q0 = 0.f, q1 = 0.f;
#pragma unroll
            for (int t = 0; t < 8; t++) {
                float d;
                d = acc[4 * t] - mu0; q0 = fmaf(d, d, q0);
                d = acc[4 * t + 1] - mu0; q0 = fmaf(d, d, q0);
                d = acc[4 * t + 2] - mu1; q1 = fmaf(d, d, q1);
                d = acc[4 * t + 3] - mu1; q1 = fmaf(d, d, q1);
            }
            q0 += __shfl_xor_sync(0xffffffffu, q0, 1); q1 += __shfl_xor_sync(0xffffffffu, q1, 1);
            q0 += __shfl_xor_sync(0xffffffffu, q0, 2); q1 += __shfl_xor_sync(0xffffffffu, q1, 2);
            st_tagged_if(g_hstat + (role * 128 + 16 * warp + g + 8 * (q & 1)) * 2, q ? mu1 : mu0, q ? q1 : q0, epoch, q < 2);
                }
                bar_sync(2 + w, 128);
#pragma unroll
                for (int tp = 0; tp < 4; tp++) ldsm4t(sa + j * SLOT + blk + tp * 2048, hr[4 * tp], hr[4 * tp + 1], hr[4 * tp + 2], hr[4 * tp + 3]);
                mbar_waitc(sb + BAR_CSG, 0);
#pragma unroll
                for (int t = 0; t < 8; t++) cs[t] = lds_f4(sb + OFF_CS3 + q * 16 + 64 * t);
            }
            prev = rg.slot; rg.adv5();
        }
#pragma unroll 1
        for (int i = 0; i < 8; i++) {
            P3_GROUP(wgmma_n128, acc1, i)
            wg_wait<1>();
            mbar_arrive_cl_if(eb + 8 * prev, l2);
            P3_EPI2(0, acc0)
            P3_CS(1, 8)
            prev = rg.slot; rg.adv5();
        }
#pragma unroll 1
        for (int i = 0; i < 8; i++) {
            P3_GROUP(wgmma_n112, acc2, i)
            wg_wait<1>();
            mbar_arrive_cl_if(eb + 8 * prev, l2);
            mbar_arrive_if(sb + BAR_EMPTYA + 8 * ((i + 7) & 7), l0 && i > 0);
            if (i == 0) { mbar_waitc(sb + BAR_FULLB + 8 * 4, 1); P3_EPI(1, acc1, 64, 4) mbar_waitc(sb + BAR_CSG + 16, 0); }
            P3_CS(2, 6)
            prev = rg.slot; rg.adv5();
        }
        mbar_waitc(sb + BAR_FULLB + 8 * 4, 0);
        wg_wait<0>();
        mbar_arrive_cl_if(eb + 8 * prev, l2);
        mbar_arrive_if(sb + BAR_EMPTYA + 8 * 7, l0);
        fence_acc<56>(acc2);
        TL(13, tid == 0);
#pragma unroll
        for (int tp = 0; tp < 3; tp++)
            stsm4(sb + OFF_B + 4 * SLOT + tp * 4096 + warp * 512 + (lane & 15) * 32 + ((ch ^ ((lane >> 2) & 1)) << 4),
                  hh_pair<32>(acc2 + 8 * tp, cs[2 * tp], nm0), hh_pair<32>(acc2 + 8 * tp + 2, cs[2 * tp], nm1),
                  hh_pair<32>(acc2 + 8 * tp + 4, cs[2 * tp + 1], nm0), hh_pair<32>(acc2 + 8 * tp + 6, cs[2 * tp + 1], nm1));
        fence_async_smem();
        __syncwarp();
        mbar_arrive_if(sb + BAR_STG + 16, l0);
        TL(52, tid == 0);
        {
            float acc[64];
            const desc_t dA0 = desc_lo(sb + OFF_A);
#define KT_P4(I, NK, DH, STEP)                                                                                   \
        const int s_ = (2 * (I) + w) & 7;                                                                   \
        mbar_waitc(sb + BAR_FULLB + 8 * rg.slot, rg.phase);                                                 \
        mbar_waitc(sb + BAR_FULLA + 8 * s_, (((I) >> 2) + 1) & 1);                                          \
        const desc_t dh_ = (DH) + s_ * (SLOT >> 4), dw_ = dB + rg.slot * (SLOT >> 4) + w * 512;              \
        wg_fence();                                                                                         \
        _Pragma("unroll") for (int k = 0; k < (NK); k++) wgmma_n128_tn(acc, dw_ + 128 * k, dh_ + (STEP) * k, ((I) | k) != 0); \
        wg_commit();
#pragma unroll 1
            for (int i = 0; i < 8; i++) {
                KT_P4(i, 4, dA0, 2)
#pragma unroll
                for (int t = 0; t < 8; t++) lds_f4_if(cs[t], sb + OFF_CS1 + (64 * w + 8 * t + 2 * q) * 8, i == t);
                wg_wait<0>();
                mbar_arrive_n_if(sb + BAR_EMPTYA + 8 * s_, 2, l0);
                mbar_arrive_cl_if(eb + 8 * rg.slot, l2 && i < 7);
                rg.adv5();
            }
#pragma unroll 1
            for (int i = 8; i < 12; i++) {
                KT_P4(i, 3, dA0 + ((0xC0000010ull - 0x40000040ull) << 32), 256)
                wg_wait<1>();
                rg.adv5();
            }
            wg_wait<0>();
            fence_acc<64>(acc);
            TL(15, tid == 0);
            const uint32_t xch = sb + OFF_A + 2 * SLOT + (tid & 127) * 16;
            if (w) {
#pragma unroll
                for (int t = 0; t < 8; t++) {
                    sts128(xch + SLOT + t * 2048, __float_as_uint(acc[4 * t]), __float_as_uint(acc[4 * t + 1]),
                           __float_as_uint(acc[4 * t + 2]), __float_as_uint(acc[4 * t + 3]));
                }
#pragma unroll
                for (int t = 0; t < 32; t++) acc[t] = acc[32 + t];
            } else {
#pragma unroll
                for (int t = 0; t < 8; t++)
                    sts128(xch + t * 2048, __float_as_uint(acc[32 + 4 * t]), __float_as_uint(acc[33 + 4 * t]),
                           __float_as_uint(acc[34 + 4 * t]), __float_as_uint(acc[35 + 4 * t]));
            }
            bar_sync(1, 256);
            float4 o[8];
#pragma unroll
            for (int t = 0; t < 8; t++) o[t] = lds_f4(xch + (w ^ 1) * SLOT + t * 2048);
            const uint32_t tile = sb + OFF_A + w * SLOT;
#pragma unroll
            for (int t = 0; t < 8; t++) {
                hr[2 * t] = pack_bf16(fmaf(acc[4 * t] + o[t].x, cs[t].y, bf_lo(hr[2 * t])), fmaf(acc[4 * t + 1] + o[t].y, cs[t].w, bf_hi(hr[2 * t])));
                hr[2 * t + 1] = pack_bf16(fmaf(acc[4 * t + 2] + o[t].z, cs[t].y, bf_lo(hr[2 * t + 1])), fmaf(acc[4 * t + 3] + o[t].w, cs[t].w, bf_hi(hr[2 * t + 1])));
            }
#pragma unroll
            for (int tp = 0; tp < 4; tp++) stsm4t(tile + blk + tp * 2048, hr[4 * tp], hr[4 * tp + 1], hr[4 * tp + 2], hr[4 * tp + 3]);
            fence_async_smem();
            bar_sync(2 + w, 128);
            if ((tid & 127) == 0) {
                tma_store2d(&P.tout, tile, 64 * j, 128 * m + 64 * w);
                asm volatile("cp.async.bulk.wait_group.read 0;" ::: "memory");
            }
            if (tid == 0 && role == 0) g_epoch = epoch + 1;
            TL(16, tid == 0); TLG(1, tid == 0);
        }
    }
}

typedef CUresult (*EncodeFn)(CUtensorMap*, CUtensorMapDataType, cuuint32_t, void*, const cuuint64_t*, const cuuint64_t*,
                             const cuuint32_t*, const cuuint32_t*, CUtensorMapInterleave, CUtensorMapSwizzle,
                             CUtensorMapL2promotion, CUtensorMapFloatOOBfill);

static void make_map2d(EncodeFn enc, CUtensorMap* tm, const void* base, uint64_t cols, uint64_t rows, uint64_t pitch_elems,
                       uint32_t box_rows) {
    cuuint64_t gd[2] = {cols, rows};
    cuuint64_t gs[1] = {pitch_elems * 2};
    cuuint32_t bd[2] = {64, box_rows};
    cuuint32_t es[2] = {1, 1};
    enc(tm, CU_TENSOR_MAP_DATA_TYPE_BFLOAT16, 2, const_cast<void*>(base), gd, gs, bd, es, CU_TENSOR_MAP_INTERLEAVE_NONE,
        CU_TENSOR_MAP_SWIZZLE_128B, CU_TENSOR_MAP_L2_PROMOTION_L2_256B, CU_TENSOR_MAP_FLOAT_OOB_FILL_NONE);
}

}

extern "C" void kernel_launch(void* const* d_in, const int* in_sizes, int n_in, void* d_out, int out_size) {
    using namespace hk;
    (void)in_sizes; (void)n_in; (void)out_size;
    static EncodeFn enc = nullptr;
    if (!enc) {
        void* fn = nullptr;
        cudaDriverEntryPointQueryResult qr;
        cudaGetDriverEntryPoint("cuTensorMapEncodeTiled", &fn, cudaEnableDefault, &qr);
        enc = (EncodeFn)fn;
        cudaFuncSetAttribute(fused_kernel, cudaFuncAttributeMaxDynamicSharedMemorySize, SMEM_BYTES);
    }
    Params P;
    const __nv_bfloat16* x = (const __nv_bfloat16*)d_in[0];
    P.x = x;
    P.wqkv = (const __nv_bfloat16*)d_in[1];
    P.wphi = (const __nv_bfloat16*)d_in[2];
    P.wo = (const __nv_bfloat16*)d_in[3];
    P.wg = (const __nv_bfloat16*)d_in[5];
    P.wu = (const __nv_bfloat16*)d_in[6];
    P.wd = (const __nv_bfloat16*)d_in[7];
    P.out = (__nv_bfloat16*)d_out;
    P.zero = 0;
    make_map2d(enc, &P.tx, x, DM, SEQ, DM, 128);
    make_map2d(enc, &P.twq, P.wqkv, 3 * DM, DM, 3 * DM, 64);
    make_map2d(enc, &P.two, P.wo, DM, DM, DM, 64);
    make_map2d(enc, &P.twg, P.wg, FF, DM, FF, 64);
    make_map2d(enc, &P.twu, P.wu, FF, DM, FF, 64);
    make_map2d(enc, &P.twd, P.wd, DM, FF, DM, 64);
    make_map2d(enc, &P.twd48, P.wd, DM, FF, DM, 48);
    make_map2d(enc, &P.tout, d_out, DM, SEQ, DM, 64);
    fused_kernel<<<NCTA, NTHREADS, SMEM_BYTES>>>(P);
}
```

```cpp
#include <cuda_runtime.h>
#include <cuda_bf16.h>
#include <cuda.h>
#include <stdint.h>

namespace hk {

constexpr int SEQ = 2048, DM = 512, FF = 1376;
constexpr int NCTA = 132;
constexpr int NTHREADS = 384;
constexpr uint32_t SLOT = 16384;
constexpr uint32_t OFF_A = 0, OFF_B = 8 * SLOT, OFF_MISC = 14 * SLOT;
constexpr uint32_t BAR_FULLA = OFF_MISC + 0, BAR_EMPTYA = OFF_MISC + 64, BAR_FULLB = OFF_MISC + 128,
                   BAR_EMPTYB = OFF_MISC + 176, BAR_CS1 = OFF_MISC + 224, BAR_CS3 = OFF_MISC + 232,
                   BAR_CSQ = OFF_MISC + 240, BAR_CSV = OFF_MISC + 248,
                   BAR_STG = OFF_MISC + 256,
                   BAR_KVW = OFF_MISC + 280, BAR_KVR = OFF_MISC + 288,
                   BAR_CSG = OFF_MISC + 296;
constexpr uint32_t OFF_CS1 = OFF_MISC + 384;
constexpr uint32_t OFF_CS3 = OFF_CS1 + 1024;
constexpr uint32_t OFF_XST = OFF_CS3;
constexpr uint32_t SMEM_BYTES = OFF_CS3 + 1536;
#define KORD(i, j) ((i) == 0 ? (j) : (i) - ((i) <= (j)))
constexpr int NB = 6;
constexpr int NPRE = 3, AHEAD = 3, AHEADA = 5;
constexpr int PF_DELAY = 2;

constexpr int ACC_SIZE = 3 * 256 * 4;

__device__ __align__(1024) uint4 g_act[5 * 128 * 1024];
__device__ __align__(128) unsigned long long g_hstat[SEQ * 16];
__device__ __align__(128) unsigned long long g_xstat[SEQ * 2];
__device__ __align__(128) float g_acc[8 * ACC_SIZE];
__device__ __align__(128) unsigned long long g_cs[8 * 6 * 128];
__device__ __align__(128) unsigned g_flag[16 * 5 * 32];
__device__ unsigned g_epoch = 1;

#define TL(i, pred) do {} while (0)
#define TLG(i, pred) do {} while (0)

struct Params {
    CUtensorMap tx, twq, two, twg, twu, twd, twd48, tout;
    const __nv_bfloat16 *x, *wqkv, *wphi, *wo, *wg, *wu, *wd;
    __nv_bfloat16* out;
    unsigned zero;
};

__device__ __forceinline__ uint32_t smem_u32(const void* p) { return (uint32_t)__cvta_generic_to_shared(p); }
__device__ __forceinline__ void mbar_init(uint32_t bar, uint32_t cnt) {
    asm volatile("mbarrier.init.shared::cta.b64 [%0], %1;" ::"r"(bar), "r"(cnt) : "memory");
}
__device__ __forceinline__ void mbar_expect_tx(uint32_t bar, uint32_t bytes) {
    asm volatile("mbarrier.arrive.expect_tx.shared::cta.b64 _, [%0], %1;" ::"r"(bar), "r"(bytes) : "memory");
}
__device__ __forceinline__ void mbar_arrive(uint32_t bar) {
    asm volatile("mbarrier.arrive.shared::cta.b64 _, [%0];" ::"r"(bar) : "memory");
}
__device__ __forceinline__ void mbar_arrive_if(uint32_t bar, bool pred) {
    asm volatile("{.reg .pred p; setp.ne.u32 p, %1, 0; @p mbarrier.arrive.shared::cta.b64 _, [%0];}" ::"r"(bar), "r"((uint32_t)pred) : "memory");
}
__device__ __forceinline__ void trap_if_gt(uint32_t v, uint32_t lim) {
    asm volatile("{.reg .pred p; setp.gt.u32 p, %0, %1; @p trap;}" ::"r"(v), "r"(lim));
}
__device__ __forceinline__ void mbar_wait(uint32_t bar, uint32_t parity) {
    asm volatile("{\n"
                 ".reg .pred P1, P2;\n"
                 ".reg .u32 c;\n"
                 "mov.u32 c, 0;\n"
                 "LAB_WAIT:\n"
                 "mbarrier.try_wait.parity.shared::cta.b64 P1, [%0], %1;\n"
                 "@P1 bra LAB_DONE;\n"
                 "add.u32 c, c, 1;\n"
                 "setp.gt.u32 P2, c, 1048576;\n"
                 "@P2 trap;\n"
                 "bra LAB_WAIT;\n"
                 "LAB_DONE:\n"
                 "}" ::"r"(bar), "r"(parity) : "memory");
}
__device__ __forceinline__ void mbar_waitc(uint32_t bar, uint32_t parity) {
    asm volatile("{\n"
                 ".reg .pred P1;\n"
                 "LAB_WAIT:\n"
                 "mbarrier.try_wait.parity.shared::cta.b64 P1, [%0], %1;\n"
                 "@!P1 bra LAB_WAIT;\n"
                 "}" ::"r"(bar), "r"(parity) : "memory");
}
__device__ __forceinline__ void tma2d(uint32_t dst, const CUtensorMap* tm, uint32_t bar, int c0, int c1) {
    asm volatile("cp.async.bulk.tensor.2d.shared::cluster.global.mbarrier::complete_tx::bytes [%0], [%1, {%3, %4}], [%2];"
                 ::"r"(dst), "l"(tm), "r"(bar), "r"(c0), "r"(c1) : "memory");
}
__device__ __forceinline__ void tma2d_mc(uint32_t dst, const CUtensorMap* tm, uint32_t bar, int c0, int c1) {
    asm volatile("cp.async.bulk.tensor.2d.shared::cluster.global.mbarrier::complete_tx::bytes.multicast::cluster [%0], [%1, {%3, %4}], [%2], %5;"
                 ::"r"(dst), "l"(tm), "r"(bar), "r"(c0), "r"(c1), "h"((uint16_t)3) : "memory");
}
__device__ __forceinline__ uint32_t mapa(uint32_t addr, uint32_t rank) {
    uint32_t r; asm("mapa.shared::cluster.u32 %0, %1, %2;" : "=r"(r) : "r"(addr), "r"(rank)); return r;
}
__device__ __forceinline__ void mbar_arrive_cl_if(uint32_t cbar, bool pred) {
    asm volatile("{.reg .pred p; setp.ne.u32 p, %1, 0; @p mbarrier.arrive.shared::cluster.b64 _, [%0];}" ::"r"(cbar), "r"((uint32_t)pred) : "memory");
}
__device__ __forceinline__ bool elect_one() {
    uint32_t ok;
    asm volatile("{.reg .pred p; elect.sync _|p, 0xffffffff; selp.u32 %0, 1, 0, p;}" : "=r"(ok));
    return ok;
}
__device__ __forceinline__ void prefetch_tmap(const CUtensorMap* tm) {
    asm volatile("prefetch.tensormap [%0];" ::"l"(tm) : "memory");
}
__device__ __forceinline__ void prefetch_l2(const void* p, uint32_t bytes) {
    asm volatile("cp.async.bulk.prefetch.L2.global [%0], %1;" ::"l"(p), "r"(bytes) : "memory");
}
__device__ __forceinline__ unsigned ld_relaxed(const unsigned* p) {
    unsigned v; asm volatile("ld.relaxed.gpu.global.u32 %0, [%1];" : "=r"(v) : "l"(p)); return v;
}
__device__ __forceinline__ void fence_async_smem() { asm volatile("fence.proxy.async.shared::cta;" ::: "memory"); }
__device__ __forceinline__ uint32_t readback(const void* p) {
    uint32_t v; asm volatile("ld.relaxed.gpu.global.u32 %0, [%1];" : "=r"(v) : "l"(p) : "memory"); return v;
}
__device__ __forceinline__ void wait_count(const unsigned* p, unsigned target) {
    uint32_t it = 0;
    while ((int)(readback(p) - target) < 0) trap_if_gt(++it, 1u << 22);
}
__device__ __forceinline__ void red_f32x4(float* p, float a, float b, float c, float d) {
    asm volatile("red.relaxed.gpu.global.add.v4.f32 [%0], {%1, %2, %3, %4};" ::"l"(p), "f"(a), "f"(b), "f"(c), "f"(d) : "memory");
}
__device__ __forceinline__ float4 ld_l2_f4(const float* p) {
    float4 v;
    asm volatile("ld.relaxed.gpu.global.v4.f32 {%0,%1,%2,%3}, [%4];" : "=f"(v.x), "=f"(v.y), "=f"(v.z), "=f"(v.w) : "l"(p) : "memory");
    return v;
}
__device__ __forceinline__ void stg128(void* p, uint32_t a, uint32_t b, uint32_t c, uint32_t d) {
    asm volatile("st.global.v4.u32 [%0], {%1,%2,%3,%4};" ::"l"(p), "r"(a), "r"(b), "r"(c), "r"(d) : "memory");
}
__device__ __forceinline__ uint4 lds128(uint32_t a) {
    uint4 v;
    asm volatile("ld.shared.v4.u32 {%0,%1,%2,%3}, [%4];" : "=r"(v.x), "=r"(v.y), "=r"(v.z), "=r"(v.w) : "r"(a) : "memory");
    return v;
}
__device__ __forceinline__ float2 lds_f2(uint32_t a) {
    float2 v;
    asm volatile("ld.shared.v2.f32 {%0,%1}, [%2];" : "=f"(v.x), "=f"(v.y) : "r"(a) : "memory");
    return v;
}
__device__ __forceinline__ void sts_f2(uint32_t a, float x, float y) {
    asm volatile("st.shared.v2.f32 [%0], {%1,%2};" ::"r"(a), "f"(x), "f"(y) : "memory");
}
__device__ __forceinline__ void sts64(uint32_t a, uint32_t x, uint32_t y) {
    asm volatile("st.shared.v2.u32 [%0], {%1,%2};" ::"r"(a), "r"(x), "r"(y) : "memory");
}
__device__ __forceinline__ void sts128(uint32_t a, uint32_t x, uint32_t y, uint32_t z, uint32_t w) {
    asm volatile("st.shared.v4.u32 [%0], {%1,%2,%3,%4};" ::"r"(a), "r"(x), "r"(y), "r"(z), "r"(w) : "memory");
}
__device__ __forceinline__ void stsm4(uint32_t a, uint32_t r0, uint32_t r1, uint32_t r2, uint32_t r3) {
    asm volatile("stmatrix.sync.aligned.m8n8.x4.shared.b16 [%0], {%1,%2,%3,%4};" ::"r"(a), "r"(r0), "r"(r1), "r"(r2), "r"(r3) : "memory");
}
__device__ __forceinline__ void stsm4t(uint32_t a, uint32_t r0, uint32_t r1, uint32_t r2, uint32_t r3) {
    asm volatile("stmatrix.sync.aligned.m8n8.x4.trans.shared.b16 [%0], {%1,%2,%3,%4};" ::"r"(a), "r"(r0), "r"(r1), "r"(r2), "r"(r3) : "memory");
}
__device__ __forceinline__ void tma_store2d(const CUtensorMap* tm, uint32_t src, int c0, int c1) {
    asm volatile("cp.async.bulk.tensor.2d.global.shared::cta.bulk_group [%0, {%2, %3}], [%1];" ::"l"(tm), "r"(src), "r"(c0), "r"(c1) : "memory");
    asm volatile("cp.async.bulk.commit_group;" ::: "memory");
}
__device__ __forceinline__ void ldsm4(uint32_t a, uint32_t& r0, uint32_t& r1, uint32_t& r2, uint32_t& r3) {
    asm volatile("ldmatrix.sync.aligned.m8n8.x4.shared.b16 {%0,%1,%2,%3}, [%4];" : "=r"(r0), "=r"(r1), "=r"(r2), "=r"(r3) : "r"(a) : "memory");
}
__device__ __forceinline__ void ldsm4t(uint32_t a, uint32_t& r0, uint32_t& r1, uint32_t& r2, uint32_t& r3) {
    asm volatile("ldmatrix.sync.aligned.m8n8.x4.trans.shared.b16 {%0,%1,%2,%3}, [%4];" : "=r"(r0), "=r"(r1), "=r"(r2), "=r"(r3) : "r"(a) : "memory");
}
__device__ __forceinline__ void mma16816(float* c, const uint32_t* a, uint32_t b0, uint32_t b1) {
    asm("mma.sync.aligned.m16n8k16.row.col.f32.bf16.bf16.f32 {%0,%1,%2,%3}, {%4,%5,%6,%7}, {%8,%9}, {%0,%1,%2,%3};"
                 : "+f"(c[0]), "+f"(c[1]), "+f"(c[2]), "+f"(c[3])
                 : "r"(a[0]), "r"(a[1]), "r"(a[2]), "r"(a[3]), "r"(b0), "r"(b1));
}
__device__ __forceinline__ uint32_t pack_bf16(float lo, float hi) {
    uint32_t r; asm("cvt.rn.bf16x2.f32 %0, %1, %2;" : "=r"(r) : "f"(hi), "f"(lo)); return r;
}
__device__ __forceinline__ float bf_lo(uint32_t w) { return __uint_as_float(w << 16); }
__device__ __forceinline__ float bf_hi(uint32_t w) { return __uint_as_float(w & 0xffff0000u); }
__device__ __forceinline__ float ex2(float x) { float r; asm("ex2.approx.ftz.f32 %0, %1;" : "=f"(r) : "f"(x)); return r; }
__device__ __forceinline__ float rcp(float x) { float r; asm("rcp.approx.ftz.f32 %0, %1;" : "=f"(r) : "f"(x)); return r; }
__device__ __forceinline__ void bar_sync(int id, int n) { asm volatile("bar.sync %0, %1;" ::"r"(id), "r"(n) : "memory"); }

typedef unsigned long long desc_t;
__device__ __forceinline__ desc_t desc_lo(uint32_t addr) { return (desc_t)(((addr & 0x3FFFF) >> 4) | (512u << 16)) | (0x40000040ull << 32); }
__device__ __forceinline__ void wg_fence() { asm volatile("wgmma.fence.sync.aligned;" ::: "memory"); }
__device__ __forceinline__ void wg_commit() { asm volatile("wgmma.commit_group.sync.aligned;" ::: "memory"); }
template <int N> __device__ __forceinline__ void wg_wait() { asm volatile("wgmma.wait_group.sync.aligned %0;" ::"n"(N) : "memory"); }
template <int N> __device__ __forceinline__ void fence_acc(float* d) {
#pragma unroll
    for (int i = 0; i < N; i++) asm volatile("" : "+f"(d[i])::"memory");
}
#define R4(o) "+f"(d[o + 0]), "+f"(d[o + 1]), "+f"(d[o + 2]), "+f"(d[o + 3])
#define R8(o) R4(o), R4(o + 4)
__device__ __forceinline__ void wgmma_n128(float* d, desc_t da, desc_t db, int sc) {
    asm volatile("{.reg .pred p; setp.ne.b32 p, %66, 0;\n"
                 "wgmma.mma_async.sync.aligned.m64n128k16.f32.bf16.bf16 {%0,%1,%2,%3,%4,%5,%6,%7,%8,%9,%10,%11,%12,%13,%14,%15,%16,%17,%18,%19,%20,%21,%22,%23,%24,%25,%26,%27,%28,%29,%30,%31,"
                 "%32,%33,%34,%35,%36,%37,%38,%39,%40,%41,%42,%43,%44,%45,%46,%47,%48,%49,%50,%51,%52,%53,%54,%55,%56,%57,%58,%59,%60,%61,%62,%63}, %64, %65, p, 1, 1, 0, 1;}"
                 : R8(0), R8(8), R8(16), R8(24), R8(32), R8(40), R8(48), R8(56)
                 : "l"(da), "l"(db), "r"(sc));
}
__device__ __forceinline__ void wgmma_n112(float* d, desc_t da, desc_t db, int sc) {
    asm volatile("{.reg .pred p; setp.ne.b32 p, %58, 0;\n"
                 "wgmma.mma_async.sync.aligned.m64n112k16.f32.bf16.bf16 {%0,%1,%2,%3,%4,%5,%6,%7,%8,%9,%10,%11,%12,%13,%14,%15,%16,%17,%18,%19,%20,%21,%22,%23,%24,%25,%26,%27,%28,%29,%30,%31,%32,%33,%34,%35,%36,%37,%38,%39,%40,%41,%42,%43,%44,%45,%46,%47,%48,%49,%50,%51,%52,%53,%54,%55}, %56, %57, p, 1, 1, 0, 1;}"
                 : R8(0), R8(8), R8(16), R8(24), R8(32), R8(40), R8(48)
                 : "l"(da), "l"(db), "r"(sc));
}
__device__ __forceinline__ void wgmma_n128_tn(float* d, desc_t da, desc_t db, int sc) {
    asm volatile("{.reg .pred p; setp.ne.b32 p, %66, 0;\n"
                 "wgmma.mma_async.sync.aligned.m64n128k16.f32.bf16.bf16 {%0,%1,%2,%3,%4,%5,%6,%7,%8,%9,%10,%11,%12,%13,%14,%15,%16,%17,%18,%19,%20,%21,%22,%23,%24,%25,%26,%27,%28,%29,%30,%31,%32,%33,%34,%35,%36,%37,%38,%39,%40,%41,%42,%43,%44,%45,%46,%47,%48,%49,%50,%51,%52,%53,%54,%55,%56,%57,%58,%59,%60,%61,%62,%63}, %64, %65, p, 1, 1, 1, 0;}"
                 : R8(0), R8(8), R8(16), R8(24), R8(32), R8(40), R8(48), R8(56)
                 : "l"(da), "l"(db), "r"(sc));
}
__device__ __forceinline__ void wgmma_n64(float* d, desc_t da, desc_t db, int sc) {
    asm volatile("{.reg .pred p; setp.ne.b32 p, %34, 0;\n"
                 "wgmma.mma_async.sync.aligned.m64n64k16.f32.bf16.bf16 {%0,%1,%2,%3,%4,%5,%6,%7,%8,%9,%10,%11,%12,%13,%14,%15,%16,%17,%18,%19,%20,%21,%22,%23,%24,%25,%26,%27,%28,%29,%30,%31}, %32, %33, p, 1, 1, 0, 1;}"
                 : R8(0), R8(8), R8(16), R8(24)
                 : "l"(da), "l"(db), "r"(sc));
}
__device__ __forceinline__ void wgmma_n40_tt(float* d, desc_t da, desc_t db, int sc) {
    asm volatile("{.reg .pred p; setp.ne.b32 p, %22, 0;\n"
                 "wgmma.mma_async.sync.aligned.m64n40k16.f32.bf16.bf16 {%0,%1,%2,%3,%4,%5,%6,%7,%8,%9,%10,%11,%12,%13,%14,%15,%16,%17,%18,%19}, %20, %21, p, 1, 1, 1, 1;}"
                 : R8(0), R8(8), R4(16)
                 : "l"(da), "l"(db), "r"(sc));
}

__device__ __forceinline__ void wgmma_n8_tt(float* d, desc_t da, desc_t db, int sc) {
    asm volatile("{.reg .pred p; setp.ne.b32 p, %6, 0;\n"
                 "wgmma.mma_async.sync.aligned.m64n8k16.f32.bf16.bf16 {%0,%1,%2,%3}, %4, %5, p, 1, 1, 1, 1;}"
                 : R4(0)
                 : "l"(da), "l"(db), "r"(sc));
}

__device__ __forceinline__ void signal_after(unsigned* cnt, uint32_t ack, uint32_t zero, bool pred) {
    asm volatile("{.reg .pred p; setp.ne.u32 p, %2, 0; @p red.relaxed.gpu.global.add.u32 [%0], %1;}"
                 ::"l"(cnt), "r"((ack & zero) + 1), "r"((uint32_t)pred) : "memory");
}
__device__ __forceinline__ void signal_late(unsigned* cnt, const uint32_t* a, uint32_t zero, bool pred) {
    uint32_t v;
    asm volatile("{.reg .b32 t; lop3.b32 t, %1, %2, %3, 0xfe; or.b32 %0, t, %4;}"
                 : "=r"(v) : "r"(a[0]), "r"(a[1]), "r"(a[2]), "r"(a[3]));
    signal_after(cnt, v, zero, pred);
}
__device__ __forceinline__ void mma16816_z(float* c, const uint32_t* a, uint32_t b0, uint32_t b1) {
    asm("mma.sync.aligned.m16n8k16.row.col.f32.bf16.bf16.f32 {%0,%1,%2,%3}, {%4,%5,%6,%7}, {%8,%9}, {%10,%10,%10,%10};"
                 : "=f"(c[0]), "=f"(c[1]), "=f"(c[2]), "=f"(c[3])
                 : "r"(a[0]), "r"(a[1]), "r"(a[2]), "r"(a[3]), "r"(b0), "r"(b1), "f"(0.f));
}
__device__ __forceinline__ uint32_t max2(uint32_t a, uint32_t b) { uint32_t r; asm("max.bf16x2 %0, %1, %2;" : "=r"(r) : "r"(a), "r"(b)); return r; }
__device__ __forceinline__ uint32_t min2(uint32_t a, uint32_t b) { uint32_t r; asm("min.bf16x2 %0, %1, %2;" : "=r"(r) : "r"(a), "r"(b)); return r; }
__device__ __forceinline__ void mbar_arrive_n_if(uint32_t bar, uint32_t n, bool pred) {
    asm volatile("{.reg .pred p; setp.ne.u32 p, %1, 0; @p mbarrier.arrive.shared::cta.b64 _, [%0], %2;}" ::"r"(bar), "r"((uint32_t)pred), "r"(n) : "memory");
}
__device__ __forceinline__ float4 lds_f4(uint32_t a) {
    float4 v;
    asm volatile("ld.shared.v4.f32 {%0,%1,%2,%3}, [%4];" : "=f"(v.x), "=f"(v.y), "=f"(v.z), "=f"(v.w) : "r"(a) : "memory");
    return v;
}
__device__ __forceinline__ void lds_f4_if(float4& v, uint32_t a, bool pred) {
    asm volatile("{.reg .pred p; setp.ne.u32 p, %5, 0; @p ld.shared.v4.f32 {%0,%1,%2,%3}, [%4];}"
                 : "+f"(v.x), "+f"(v.y), "+f"(v.z), "+f"(v.w) : "r"(a), "r"((uint32_t)pred) : "memory");
}
__device__ __forceinline__ uint4 ld_tagged_rlx(const unsigned long long* p) {
    unsigned long long a, b;
    asm volatile("ld.relaxed.gpu.global.v2.b64 {%0,%1}, [%2];" : "=l"(a), "=l"(b) : "l"(p) : "memory");
    return make_uint4((unsigned)a, (unsigned)(a >> 32), (unsigned)b, (unsigned)(b >> 32));
}
__device__ __forceinline__ void sts32(uint32_t a, uint32_t x) { asm volatile("st.shared.u32 [%0], %1;" ::"r"(a), "r"(x) : "memory"); }
__device__ __forceinline__ void fetch_tagged(const unsigned long long* src, uint32_t dst, unsigned epoch, unsigned ns) {
    uint4 v;
    uint32_t it = 0;
    while (true) {
        v = ld_tagged_rlx(src);
        if (!__any_sync(0xffffffffu, v.y != epoch || v.w != epoch)) break;
        __nanosleep(ns);
        trap_if_gt(++it, 1u << 22);
    }
    sts64(dst, v.x, v.z);
}
__device__ __forceinline__ void st_tagged_if(unsigned long long* p, float a, float b, unsigned tag, bool pred) {
    const unsigned long long t = (unsigned long long)tag << 32;
    asm volatile("{.reg .pred p; setp.ne.u32 p, %3, 0; @p st.relaxed.gpu.global.v2.b64 [%0], {%1,%2};}"
                 ::"l"(p), "l"(t | __float_as_uint(a)), "l"(t | __float_as_uint(b)), "r"((uint32_t)pred) : "memory");
}

__device__ __forceinline__ void store_tile(uint32_t tile_rows, uint4* gdst, const uint32_t* lo, const uint32_t* hi, int lane, uint32_t* ack) {
    const int r = lane & 15;
#pragma unroll
    for (int b = 0; b < 4; b++)
        stsm4(tile_rows + r * 128 + (((2 * b + (lane >> 4)) ^ (r & 7)) << 4), lo[2 * b], hi[2 * b], lo[2 * b + 1], hi[2 * b + 1]);
    fence_async_smem();
    __syncwarp();
#pragma unroll
    for (int i = 0; i < 4; i++) {
        const uint4 v = lds128(tile_rows + i * 512 + lane * 16);
        stg128(gdst + 32 * i, v.x, v.y, v.z, v.w);
    }
#pragma unroll
    for (int i = 0; i < 4; i++) ack[i] = readback(gdst + 32 * i);
}

__device__ __forceinline__ void feature_maps(const uint32_t* a, const uint32_t* wb, float c0, float c1, uint32_t* plus, uint32_t* minus) {
    uint32_t P[16], mx[4], mn[4];
#pragma unroll
    for (int h = 0; h < 4; h++) {
        float p[8];
        mma16816_z(p, a + 4 * h, wb[4 * h], wb[4 * h + 1]);
        mma16816_z(p + 4, a + 4 * h, wb[4 * h + 2], wb[4 * h + 3]);
        P[4 * h] = pack_bf16(p[0], p[2]); P[4 * h + 1] = pack_bf16(p[1], p[3]);
        P[4 * h + 2] = pack_bf16(p[4], p[6]); P[4 * h + 3] = pack_bf16(p[5], p[7]);
        mx[h] = max2(max2(P[4 * h], P[4 * h + 1]), max2(P[4 * h + 2], P[4 * h + 3]));
        mn[h] = min2(min2(P[4 * h], P[4 * h + 1]), min2(P[4 * h + 2], P[4 * h + 3]));
    }
#pragma unroll
    for (int s = 1; s <= 2; s <<= 1) {
        uint32_t tx[4], tn[4];
#pragma unroll
        for (int h = 0; h < 4; h++) { tx[h] = __shfl_xor_sync(0xffffffffu, mx[h], s); tn[h] = __shfl_xor_sync(0xffffffffu, mn[h], s); }
#pragma unroll
        for (int h = 0; h < 4; h++) { mx[h] = max2(mx[h], tx[h]); mn[h] = min2(mn[h], tn[h]); }
    }
#pragma unroll
    for (int h = 0; h < 4; h++) {
        const float mx0 = bf_lo(mx[h]) * c0, mx1 = bf_hi(mx[h]) * c1, mn0 = bf_lo(mn[h]) * c0, mn1 = bf_hi(mn[h]) * c1;
        float ep[8], em[8];
#pragma unroll
        for (int i = 0; i < 8; i++) {
            const bool r1 = (i & 2);
            const uint32_t w = P[4 * h + (i >> 2) * 2 + (i & 1)];
            const float p = r1 ? bf_hi(w) : bf_lo(w);
            ep[i] = ex2(fmaf(p, r1 ? c1 : c0, r1 ? -mx1 : -mx0));
            em[i] = ex2(fmaf(p, r1 ? -c1 : -c0, r1 ? mn1 : mn0));
        }
        float sp[4], sm[4];
        uint32_t tp[4], tm[4];
#pragma unroll
        for (int i = 0; i < 4; i++) { tp[i] = pack_bf16(ep[2 * i], ep[2 * i + 1]); tm[i] = pack_bf16(em[2 * i], em[2 * i + 1]); }
        mma16816_z(sp, tp, 0x3f803f80u, 0x3f803f80u);
        mma16816_z(sm, tm, 0x3f803f80u, 0x3f803f80u);
        const float r0 = rcp(sp[0] * sm[0]), r1 = rcp(sp[2] * sm[2]);
        const float rs[4] = {r0 * sm[0], r1 * sm[2], r0 * sp[0], r1 * sp[2]};
#pragma unroll
        for (int i = 0; i < 4; i++) {
            plus[4 * h + i] = pack_bf16(ep[2 * i] * rs[i & 1], ep[2 * i + 1] * rs[i & 1]);
            minus[4 * h + i] = pack_bf16(em[2 * i] * rs[2 + (i & 1)], em[2 * i + 1] * rs[2 + (i & 1)]);
        }
    }
}

template <bool SCALE>
__device__ __forceinline__ void ln_frag(const float* acc, uint32_t cs_addr, float rs0, float nm0, float rs1, float nm1, uint32_t* a) {
    const float2 c0 = lds_f2(cs_addr), c1 = lds_f2(cs_addr + 32);
    const float s0 = SCALE ? rs0 : 1.f, s1 = SCALE ? rs1 : 1.f;
    a[0] = pack_bf16(fmaf(nm0, c0.x, acc[0]) * s0, fmaf(nm0, c0.y, acc[1]) * s0);
    a[1] = pack_bf16(fmaf(nm1, c0.x, acc[2]) * s1, fmaf(nm1, c0.y, acc[3]) * s1);
    a[2] = pack_bf16(fmaf(nm0, c1.x, acc[4]) * s0, fmaf(nm0, c1.y, acc[5]) * s0);
    a[3] = pack_bf16(fmaf(nm1, c1.x, acc[6]) * s1, fmaf(nm1, c1.y, acc[7]) * s1);
}

template <int UP>
__device__ __forceinline__ uint32_t hh_pair(const float* ag, float4 cs, float nmean) {
    const float g0 = fmaf(nmean, cs.x, ag[0]), g1 = fmaf(nmean, cs.y, ag[1]);
    const float u0 = fmaf(nmean, cs.z, ag[UP]), u1 = fmaf(nmean, cs.w, ag[UP + 1]);
    return pack_bf16(g0 * u0, g1 * u1);
}
template <int NTP>
__device__ __forceinline__ void hh_stage(const float* acc, const float4* cs, float nm0, float nm1, uint32_t stg, int lane) {
#pragma unroll
    for (int tp = 0; tp < NTP; tp++)
        stsm4(stg + (lane & 15) * 128 + (((2 * tp + (lane >> 4)) ^ (lane & 7)) << 4), hh_pair<32>(acc + 8 * tp, cs[2 * tp], nm0),
              hh_pair<32>(acc + 8 * tp + 2, cs[2 * tp], nm1), hh_pair<32>(acc + 8 * tp + 4, cs[2 * tp + 1], nm0),
              hh_pair<32>(acc + 8 * tp + 6, cs[2 * tp + 1], nm1));
    fence_async_smem();
    __syncwarp();
}

template <int TP0, int TP1>
__device__ __forceinline__ void hh_stage2(const float* acc, const float4* cs, float nm0, float nm1, uint32_t stg, int lane) {
#pragma unroll
    for (int tp = TP0; tp < TP1; tp++)
        stsm4(stg + (lane & 15) * 128 + (((2 * tp + (lane >> 4)) ^ (lane & 7)) << 4), hh_pair<32>(acc + 8 * tp, cs[2 * tp], nm0),
              hh_pair<32>(acc + 8 * tp + 2, cs[2 * tp], nm1), hh_pair<32>(acc + 8 * tp + 4, cs[2 * tp + 1], nm0),
              hh_pair<32>(acc + 8 * tp + 6, cs[2 * tp + 1], nm1));
}
__device__ __forceinline__ void centre4(const float* acc, const float2* c, float nm0, float nm1, uint32_t* a) {
#pragma unroll
    for (int t = 0; t < 8; t++) {
        a[2 * t] = pack_bf16(fmaf(nm0, c[t].x, acc[4 * t]), fmaf(nm0, c[t].y, acc[4 * t + 1]));
        a[2 * t + 1] = pack_bf16(fmaf(nm1, c[t].x, acc[4 * t + 2]), fmaf(nm1, c[t].y, acc[4 * t + 3]));
    }
}

struct Ring {
    int slot; uint32_t phase;
    __device__ __forceinline__ void adv() { if (++slot == NB) { slot = 0; phase ^= 1; } }
    __device__ __forceinline__ void adv5() { slot += slot == 3; adv(); }
};

__global__ void __cluster_dims__(2, 1, 1) __launch_bounds__(NTHREADS, 1) fused_kernel(const __grid_constant__ Params P) {
    extern __shared__ __align__(1024) uint8_t smem_raw[];
    const uint32_t sb = smem_u32(smem_raw);
    const int tid = threadIdx.x, lane = tid & 31;
    const int warp = __shfl_sync(0xffffffffu, tid >> 5, 0);
    const unsigned rank = blockIdx.x & 1;
    int m, j;
    {
        const int t = (int)(blockIdx.x >> 1) - 4, u = t - 32, r7 = (u * 37) >> 8;
        const int gp = t < 32 ? (t & 7) - 1 : u - 7 * r7;
        j = t < 0 ? t + 8 : (t < 32 ? t >> 3 : 4 + r7);
        m = ((t < 0 || gp < 0) ? 14 : 2 * gp) + rank;
        if (t >= 60) { m = 16; j = blockIdx.x - 128; }
    }
    const unsigned role = m * 8 + j;
    const bool helper = m == 16;

    TL(0, tid == 0); TLG(0, tid == 0);
    float* const acc_j = g_acc + j * ACC_SIZE;
    if ((warp & ~1) == 8 && elect_one()) {
        const uint32_t bar = sb + (warp == 8 ? BAR_FULLB : BAR_FULLA);
#pragma unroll
        for (int i = 0; i < 8; i++) if (i < NB || warp == 9) mbar_init(bar + 8 * i, 1);
        if (!helper) {
#pragma unroll 1
            for (int i = 0; i < NPRE; i++) {
                mbar_expect_tx(bar + 8 * i, SLOT);
                if (warp == 8) {
                    tma2d(sb + OFF_B + i * SLOT, &P.twq, bar + 8 * i, DM + 64 * j, 64 * i);
                    tma2d(sb + OFF_B + i * SLOT + 8192, &P.twq, bar + 8 * i, 2 * DM + 64 * j, 64 * i);
                } else {
                    tma2d(sb + OFF_A + i * SLOT, &P.tx, bar + 8 * i, 64 * i, 128 * m);
                }
            }
        }
    }
    __syncwarp();

    if (warp >= 8) {
        asm volatile("setmaxnreg.dec.sync.aligned.u32 72;");
        if (elect_one()) {
            if (warp < 10) {
            } else if (warp == 10) {
#pragma unroll
                for (int i = 0; i < 12; i++) mbar_init(sb + BAR_CS1 + 8 * i, i < 2 || i >= 8 ? 64 : (i < 4 ? 32 : 8));
                trap_if_gt(sb & 1023, 0);
            } else {
#pragma unroll
                for (int i = 0; i < 14; i++) mbar_init(sb + (i < 8 ? BAR_EMPTYA : BAR_EMPTYB - 64) + 8 * i, i < 8 ? 8 : 16);
            }
            asm volatile("fence.mbarrier_init.release.cluster;" ::: "memory");
        }
        __syncwarp();
        asm volatile("barrier.cluster.arrive.relaxed.aligned;" ::: "memory");
        const unsigned epoch = ld_relaxed(&g_epoch);
        bar_sync(0, NTHREADS);
        if (helper) {
            if (elect_one()) {
#pragma unroll 1
                for (int i = warp - 8; i < 72; i += 4) {
                    const uint32_t full = sb + BAR_FULLA + 8 * (i & 7), dst = sb + OFF_A + (i & 7) * SLOT;
                    const int n = i >> 1, jj = 2 * j + (i & 1);
                    const bool qkv = n < 12;
                    const int c0 = qkv ? (n < 8 ? DM + 128 * (n & 4) : 0) + 64 * jj : 176 * jj + 8 * ((n - 12) & ~7);
                    const int r0 = qkv ? 128 * (n & 3) : 64 * ((n - 12) & 7);
                    mbar_wait(sb + BAR_EMPTYA + 8 * (i & 7), ((i >> 3) & 1) ^ 1);
                    mbar_expect_tx(full, SLOT);
                    tma2d(dst, qkv ? &P.twq : &P.twg, full, c0, r0);
                    tma2d(dst + 8192, qkv ? &P.twq : &P.twu, full, c0, qkv ? r0 + 64 : r0);
                }
                prefetch_l2(P.wd + (size_t)(4 * j + warp - 8) * 44032, 88064);
            }
            return;
        }
        if (warp == 8) {
            asm volatile("barrier.cluster.wait.aligned;" ::: "memory");
            if (elect_one()) {
                if (m >= 6)
                    asm volatile("cp.async.bulk.prefetch.tensor.2d.L2.global [%0, {%1, %2}];" ::"l"(&P.twq), "r"(DM + DM * (m & 1) + 64 * j), "r"(64 * (m >> 1)) : "memory");
                if (j >= 3)
                    asm volatile("cp.async.bulk.prefetch.tensor.2d.L2.global [%0, {%1, %2}];" ::"l"(&P.tx), "r"(64 * j), "r"(128 * m) : "memory");
                Ring r{NPRE, 0};
                const uint32_t dst = sb + OFF_B + rank * 8192;
#define B_LOADN(TM, C0, R0, NB_)                                                                                \
        mbar_waitc(sb + BAR_EMPTYB + 8 * r.slot, r.phase ^ 1);                                              \
        mbar_expect_tx(sb + BAR_FULLB + 8 * r.slot, NB_);                                                   \
        tma2d_mc(dst + r.slot * SLOT, TM, sb + BAR_FULLB + 8 * r.slot, C0, R0);
#define B_LOAD(TM, C0, R0) B_LOADN(TM, C0, R0, SLOT)
#pragma unroll 1
                for (int i = NPRE; i < 8; i++) {
                    if (i >= AHEAD && i < 6) mbar_waitc(sb + BAR_FULLB + 8 * (i - AHEAD), 0);
                    B_LOAD(&P.twq, DM + DM * rank + 64 * j, 64 * i)
                    r.adv();
                }
#pragma unroll 1
                for (int i = 8; i < 18; i++) {
                    if (i == 9 || i == 10) {
                        mbar_waitc(sb + BAR_EMPTYB + 8 * r.slot, r.phase ^ 1);
                        mbar_arrive(sb + BAR_FULLB + 8 * r.slot);
                    } else {
                        const int e = 2 * (i - 14) + rank, b = (i == 8 ? 0 : i - 10) ^ (i < 12 && j < 2);
                        B_LOAD(i < 14 ? &P.twq : &P.two, 64 * j, 64 * (i < 14 ? 2 * b + rank : KORD(e, j)))
                    }
                    r.adv();
                }
#pragma unroll 1
                for (int i = 0; i < 24; i++) {
                    B_LOAD(&P.twg + rank, 176 * j + 8 * (i & ~7), 64 * (i < 8 ? KORD(i, j) : i & 7))
                    r.adv5();
                }
#pragma unroll 1
                for (int i = 0; i < 12; i++) {
                    B_LOADN(&P.twd + (i >> 3), 64 * j, 176 * (2 * (i & 3) + rank) + 64 * (i >> 2), i < 8 ? SLOT : 12288)
                    r.adv5();
                }
            }
            return;
        }
        if (warp == 9) {
            if (elect_one()) {
#pragma unroll 1
                for (int i = NPRE; i < 8; i++) {
                    if (i >= AHEADA) mbar_wait(sb + BAR_FULLA + 8 * (i - AHEADA), 0);
                    mbar_expect_tx(sb + BAR_FULLA + 8 * i, SLOT);
                    tma2d(sb + OFF_A + i * SLOT, &P.tx, sb + BAR_FULLA + 8 * i, 64 * i, 128 * m);
                }
#pragma unroll 1
                for (int i = 2; i < 8; i++) prefetch_tmap(&P.tx + i);
                unsigned nf = 0;
#pragma unroll 1
                for (int r = 1; r < 6; r++) {
                    const int skip = r < 3 ? j : 8;
                    const uint32_t bytes = r == 5 ? 12288 : SLOT;
                    const uint4* src = g_act + ((r - 1) * 128 + m * 8) * 1024;
                    const unsigned* fl = g_flag + (m * 5 + r - 1) * 32;
                    if (r < 4) mbar_wait(sb + BAR_EMPTYA + 8 * (r == 3 ? PF_DELAY : 3 - 2 * (j == 3)), (r - 1) & 1);
                    const unsigned tgt = epoch * (r < 3 ? 64 : 8);
                    if (nf != tgt) wait_count(fl, tgt);
                    TL(64 + r, true);
#pragma unroll 1
                    for (int t = 0; t < 8; t++) {
                        if (t == skip) continue;
                        if (t == 6 && r < 5) nf = readback(fl + 32);
                        mbar_wait(sb + BAR_EMPTYA + 8 * t, (r - 1) & 1);
                        mbar_expect_tx(sb + BAR_FULLA + 8 * t, bytes);
                        asm volatile("cp.async.bulk.shared::cluster.global.mbarrier::complete_tx::bytes [%0], [%1], %2, [%3];"
                                     ::"r"(sb + OFF_A + t * SLOT), "l"(src + t * 1024), "r"(bytes), "r"(sb + BAR_FULLA + 8 * t) : "memory");
                    }
                }
            }
            return;
        }
        const int a = warp - 10;
        {
            const int row = 16 * j + 8 * a + (lane >> 2);
            const uint32_t ra = sb + OFF_A + row * 128;
            float sh = 0.f, s0 = 0.f, s1 = 0.f, q0 = 0.f, q1 = 0.f;
#pragma unroll 1
            for (int kt = 0; kt < 8; kt++) {
                mbar_wait(sb + BAR_FULLA + 8 * kt, 0);
                if (kt == 0) sh = bf_lo(lds128(ra + ((row & 7) << 4)).x);
#pragma unroll
                for (int i = 0; i < 2; i++) {
                    const uint4 v = lds128(ra + kt * SLOT + (((2 * (lane & 3) + i) ^ (row & 7)) << 4));
                    const uint32_t ww[4] = {v.x, v.y, v.z, v.w};
#pragma unroll
                    for (int e = 0; e < 4; e++) {
                        const float d0 = bf_lo(ww[e]) - sh, d1 = bf_hi(ww[e]) - sh;
                        s0 += d0; q0 = fmaf(d0, d0, q0);
                        s1 += d1; q1 = fmaf(d1, d1, q1);
                    }
                }
            }
            s0 += s1; q0 += q1;
#pragma unroll
            for (int o = 1; o <= 2; o <<= 1) { s0 += __shfl_xor_sync(0xffffffffu, s0, o); q0 += __shfl_xor_sync(0xffffffffu, q0, o); }
            const float md = s0 * (1.f / DM);
            const float rs = rsqrtf(fmaxf(q0 * (1.f / DM) - md * md, 0.f) + 1e-5f);
            st_tagged_if(g_xstat + 2 * (128 * m + row), rs, -(sh + md), epoch, (lane & 3) == 0);
            TL(1, lane == 0 && a == 0);
        }
        const unsigned long long* cs = g_cs + j * 768 + 2 * lane;
        {
            const unsigned long long* xs = g_xstat + 2 * (128 * m + 64 * a + lane);
            uint4 v0, v1, v2;
            uint32_t it = 0;
            __nanosleep(250);
            do {
                v0 = ld_tagged_rlx(xs); v1 = ld_tagged_rlx(xs + 64); v2 = ld_tagged_rlx(cs);
                trap_if_gt(++it, 1u << 22);
            } while (__any_sync(0xffffffffu, v0.y != epoch || v0.w != epoch || v1.y != epoch || v1.w != epoch || v2.y != epoch || v2.w != epoch));
            sts64(sb + OFF_XST + (64 * a + lane) * 8, v0.x, v0.z);
            sts64(sb + OFF_XST + (64 * a + 32 + lane) * 8, v1.x, v1.z);
            sts64(sb + OFF_CS1 + 256 + 8 * lane, v2.x, v2.z);
            mbar_arrive(sb + BAR_CS1);
            TL(22 + a, lane == 0);
            fetch_tagged(cs + 128 + 128 * a, sb + OFF_CS1 + 512 - 512 * a + 8 * lane, epoch, 200);
            mbar_arrive(sb + BAR_CSV - 8 * a);
            TL(24 + a, lane == 0);
        }
        {
            mbar_wait(sb + BAR_KVW, 0);
            const float* src = acc_j + 4 * (128 * a + lane);
            float4 v[12];
            uint32_t it = 0;
            bool bad;
            while (__any_sync(0xffffffffu, readback(acc_j + 2048 + 128 * (lane & 7) + 127) != 0x41800000u)) trap_if_gt(++it, 1u << 22);
            TL(19, lane == 0 && a == 0);
            do {
                bad = false;
#pragma unroll
                for (int i = 0; i < 12; i++) v[i] = ld_l2_f4(src + 1024 * (i % 3) + 128 * (i / 3));
#pragma unroll
                for (int i = 0; i < 12; i++) bad |= v[i].w != 16.f;
                trap_if_gt(++it, 1u << 22);
            } while (__any_sync(0xffffffffu, bad));
            TL(14, lane == 0 && a == 0);
            const uint32_t d0 = sb + OFF_A + (j < 2 ? 2 * SLOT : 0) + (64 * a + (lane >> 2)) * 48;
            const uint32_t d = d0 + (lane & 3) * 4, dz = d0 + (lane & 1) * 384 + 32 + (lane & 2) * 4;
#pragma unroll
            for (int u = 0; u < 4; u++) {
                sts32(d + 768 * u, pack_bf16(v[3 * u].x, v[3 * u].y));
                sts32(d + 768 * u + 384, pack_bf16(v[3 * u].z, v[3 * u + 1].z));
                sts32(d + 768 * u + 16, pack_bf16(v[3 * u + 1].x, v[3 * u + 1].y));
                sts32(d + 768 * u + 400, pack_bf16(v[3 * u + 2].x, v[3 * u + 2].y));
                const uint32_t z2 = pack_bf16(v[3 * u + 2].z, v[3 * u + 2].z);
                sts64(dz + 768 * u, z2, z2);
            }
            mbar_arrive(sb + BAR_KVR);
        }
#pragma unroll 1
        for (int c = 0; c < 3; c++) {
            fetch_tagged(cs + 384 + 128 * c + 64 * a, sb + OFF_CS3 + (32 * c + lane) * 16 + 8 * a, epoch, 1000);
            mbar_arrive(sb + BAR_CSG + 8 * c);
            TL(45 + c, lane == 0 && a == 0);
        }
        {
            uint32_t it = 0;
            while (__any_sync(0xffffffffu, (int)(readback(g_flag + (m * 5 + 1) * 32) - epoch * 64) < 0)) {
                __nanosleep(600);
                trap_if_gt(++it, 1u << 22);
            }
#pragma unroll 1
            for (int rr = 0; rr < 2; rr++) {
                const int row = 64 * rr + 32 * a + lane;
                const unsigned long long* hs = g_hstat + (1024 * m + row) * 2;
                uint4 v[8];
                bool bad;
                do {
                    bad = false;
#pragma unroll
                    for (int i = 0; i < 8; i++) v[i] = ld_tagged_rlx(hs + 256 * i);
#pragma unroll
                    for (int i = 0; i < 8; i++) bad |= v[i].y != epoch || v[i].w != epoch;
                    trap_if_gt(++it, 1u << 22);
                } while (__any_sync(0xffffffffu, bad));
                float mean = 0.f;
#pragma unroll
                for (int i = 0; i < 8; i++) mean += __uint_as_float(v[i].x);
                mean *= 0.125f;
                float m2 = 0.f, dv = 0.f;
#pragma unroll
                for (int i = 0; i < 8; i++) { const float d = __uint_as_float(v[i].x) - mean; m2 += __uint_as_float(v[i].z); dv = fmaf(d, d, dv); }
                sts_f2(sb + OFF_CS1 + row * 8, -mean, rcp(fmaf(dv, 64.f, m2) * (1.f / DM) + 1e-5f));
            }
        }
        mbar_arrive(sb + BAR_CS3);
#pragma unroll 1
        for (int c = a; c < 3; c += 2) {
            mbar_wait(sb + BAR_STG + 8 * c, 0);
            if (elect_one()) {
                asm volatile("cp.async.bulk.global.shared::cta.bulk_group [%0], [%1], %2;" ::"l"(g_act + ((2 + c) * 128 + role) * 1024), "r"(sb + OFF_B + 4 * SLOT), "r"(c == 2 ? 12288 : SLOT) : "memory");
                asm volatile("cp.async.bulk.commit_group;" ::: "memory");
                asm volatile("cp.async.bulk.wait_group.read 0;" ::: "memory");
                mbar_arrive(sb + BAR_FULLB + 8 * 4);
                asm volatile("cp.async.bulk.wait_group 0;" ::: "memory");
            }
            __syncwarp();
            TL(60 + c, lane == 0);
            uint32_t ack = 0;
            const uint4* rb = g_act + ((2 + c) * 128 + role) * 1024 + lane * 8;
#pragma unroll
            for (int i = 0; i < 4; i++) ack |= readback(rb + (i == 3 && c == 2 ? 0 : 256 * i));
            signal_after(g_flag + (m * 5 + 2 + c) * 32, ack, P.zero, lane == 0);
            TL(54 + c, lane == 0);
        }
        return;
    }
    const unsigned epoch = ld_relaxed(&g_epoch);
    uint32_t wraw[16];
    if (!helper) {
        const uint32_t* wp = reinterpret_cast<const uint32_t*>(P.wphi) + (4 * j) * 128 + (lane & 3) * 16 + (lane >> 2);
#pragma unroll
        for (int i = 0; i < 16; i++)
            asm volatile("ld.global.nc.u32 %0, [%1];" : "=r"(wraw[i]) : "l"(wp + (i >> 2) * 128 + ((i >> 1) & 1) * 64 + (i & 1) * 8));
    }
    asm volatile("barrier.cluster.arrive.relaxed.aligned;" ::: "memory");
    asm volatile("setmaxnreg.inc.sync.aligned.u32 216;");
    bar_sync(0, NTHREADS);
    if (helper) {
        const int w = warp >> 2;
        sts64(sb + OFF_B + 8 * tid, 0x3f803f80u, 0x3f803f80u);
        fence_async_smem();
        uint32_t zack[6];
        {
            float* z = g_acc + 2 * j * ACC_SIZE + 4 * tid;
#pragma unroll
            for (int u = 0; u < 6; u++) stg128(z + 1024 * u, 0, 0, 0, 0);
#pragma unroll
            for (int u = 0; u < 6; u++) zack[u] = readback(z + 1024 * u);
        }
        bar_sync(1, 256);
        TL(70, tid == 0);
        float acc[8];
        int i = w;
#pragma unroll 1
        for (int job = 0; job < 6; job++) {
            const int n = job < 3 ? 4 : 8;
#pragma unroll 1
            for (int t = 0; t < n; t++, i += 2) {
                mbar_waitc(sb + BAR_FULLA + 8 * (i & 7), (i >> 3) & 1);
                const desc_t da = desc_lo(sb + OFF_A) + (i & 7) * (SLOT >> 4);
                wg_fence();
#pragma unroll
                for (int k = 0; k < 8; k++) wgmma_n8_tt(acc + (k & 4), da + 128 * k, desc_lo(sb + OFF_B), (t | (k & 3)) != 0);
                wg_commit();
                wg_wait<0>();
                mbar_arrive_n_if(sb + BAR_EMPTYA + 8 * (i & 7), 2, lane == 0);
            }
            fence_acc<8>(acc);
            TL(71 + job, tid == 0);
            if (job == 1) {
                asm volatile("{.reg .pred p; .reg .b32 t; lop3.b32 t, %0, %1, %2, 0xfe; lop3.b32 t, t, %3, %4, 0xfe; or.b32 t, t, %5; setp.ne.u32 p, t, 0; @p trap;}"
                             ::"r"(zack[0]), "r"(zack[1]), "r"(zack[2]), "r"(zack[3]), "r"(zack[4]), "r"(zack[5]));
                bar_sync(1, 256);
            }
            const int q = lane & 3;
            const float lo = (q & 1) ? acc[2] : acc[0], hi = (q & 1) ? acc[6] : acc[4];
            const float v = job < 3 ? lo + hi : ((q & 2) ? hi : lo);
            unsigned long long* dst = g_cs + ((2 * j + w) * 6 + job) * 128 + (q >> 1) * 64 + 16 * (warp & 3) + 8 * (q & 1) + (lane >> 2);
            asm volatile("st.relaxed.gpu.global.b64 [%0], %1;" ::"l"(dst), "l"(((unsigned long long)epoch << 32) | __float_as_uint(v)) : "memory");
        }
        return;
    }
    {
        const int w = warp >> 2, wv = warp & 3, g = lane >> 2, q = lane & 3;
        const uint32_t sa = sb + OFF_A + w * 8192;
        const desc_t dA = desc_lo(sa), dB = desc_lo(sb + OFF_B);
        unsigned* const flag_m = g_flag + m * 160;
        const bool l0 = lane == 0, l2 = lane < 2;
        const uint32_t eb = mapa(sb + BAR_EMPTYB, lane & 1);
        asm volatile("barrier.cluster.wait.aligned;" ::: "memory");
        Ring rg{0, 0};
        int prev = 0;

        uint32_t wb[16];
        constexpr float L2E = 1.4426950408889634f;
        const int ch = lane >> 4, sw = lane & 7;
        const uint32_t lrow = (lane & 15) * 128;
        uint32_t fp[16], fm[16];
        const int vs = j < 2 ? 2 : 0;
        {
            float acc[64];
#pragma unroll 1
            for (int kt = 0; kt < 8; kt++) {
                mbar_waitc(sb + BAR_FULLA + 8 * kt, 0);
                mbar_waitc(sb + BAR_FULLB + 8 * rg.slot, rg.phase);
                const desc_t da = dA + kt * (SLOT >> 4), db = dB + rg.slot * (SLOT >> 4);
                wg_fence();
#pragma unroll
                for (int k = 0; k < 4; k++) wgmma_n128(acc, da + 2 * k, db + 128 * k, (kt | k) != 0);
                wg_commit();
                wg_wait<1>();
                mbar_arrive_cl_if(eb + 8 * prev, l2 && kt > 0);
                prev = rg.slot; rg.adv();
            }
#pragma unroll
            for (int i = 0; i < 8; i++) {
                wb[(i >> 1) * 4 + (i & 1)] = __byte_perm(wraw[2 * i], wraw[2 * i + 1], 0x5410);
                wb[(i >> 1) * 4 + 2 + (i & 1)] = __byte_perm(wraw[2 * i], wraw[2 * i + 1], 0x7632);
            }
            uint32_t a[16];
            float accq[32];
            float2 cq[8];
            mbar_waitc(sb + BAR_CS1, 0);
            const float2 s0 = lds_f2(sb + OFF_XST + (16 * warp + g) * 8), s1 = lds_f2(sb + OFF_XST + (16 * warp + g + 8) * 8);
#pragma unroll
            for (int t = 0; t < 8; t++) cq[t] = lds_f2(sb + OFF_CS1 + (64 + 8 * t + 2 * q) * 4);
            mbar_waitc(sb + BAR_FULLB + 8 * 2, 1);
            wg_fence();
#pragma unroll
            for (int k = 0; k < 8; k++) wgmma_n64(accq, dA + (vs + (k >> 2)) * (SLOT >> 4) + (k & 3) * 2, dB + 2 * (SLOT >> 4) + 128 * k, k != 0);
            wg_commit();
            wg_wait<1>();
            fence_acc<64>(acc);
            mbar_arrive_cl_if(eb + 8 * prev, l2);
            TL(17, tid == 0);
            centre4(acc, cq, s0.y, s1.y, a);
#pragma unroll
            for (int i = 0; i < 16; i++) asm volatile("" : "+r"(a[i]), "+r"(wb[i]));
            wg_wait<0>();
            fence_acc<32>(accq);
            mbar_arrive_cl_if(eb + 8 * 2, l2);
            TL(2, tid == 0);
            const uint32_t st = sb + OFF_B + warp * 2048 + lrow;
#pragma unroll 1
            for (int it = 0; it < 2; it++) {
                feature_maps(a, wb, s0.x * L2E, s1.x * L2E, fp, fm);
                if (it == 0) {
                    mbar_waitc(sb + BAR_FULLB + 8 * 3, 1); mbar_waitc(sb + BAR_FULLB + 8 * 4, 1);
                    mbar_waitc(sb + BAR_CSV, 0);
                    const uint32_t sv = sb + OFF_A + vs * SLOT + warp * 2048 + lrow;
#pragma unroll
                    for (int hh = 0; hh < 4; hh++) {
                        stsm4(st + (3 + (hh >> 1)) * SLOT + (((4 * (hh & 1) + ch) ^ sw) << 4), fp[4 * hh], fp[4 * hh + 1], fp[4 * hh + 2], fp[4 * hh + 3]);
                        stsm4(st + (3 + (hh >> 1)) * SLOT + (((4 * (hh & 1) + 2 + ch) ^ sw) << 4), fm[4 * hh], fm[4 * hh + 1], fm[4 * hh + 2], fm[4 * hh + 3]);
                        ln_frag<true>(acc + 32 + 8 * hh, sb + OFF_CS1 + (128 + 16 * hh + 2 * q) * 4, s0.x, s0.y, s1.x, s1.y, a);
                        stsm4(sv + (hh >> 1) * SLOT + (((2 * (hh & 1) + ch) ^ sw) << 4), a[0], a[1], a[2], a[3]);
                    }
                    stsm4(sv + ch * SLOT + ((4 ^ sw) << 4), 0x3f803f80u, 0x3f803f80u, 0x3f803f80u, 0x3f803f80u);
                    fence_async_smem();
                    mbar_waitc(sb + BAR_FULLB + 8 * 5, 1); mbar_waitc(sb + BAR_FULLB, 0); mbar_waitc(sb + BAR_FULLB + 8, 0);
                    mbar_waitc(sb + BAR_CSQ, 0);
#pragma unroll
                    for (int t = 0; t < 8; t++) cq[t] = lds_f2(sb + OFF_CS1 + (8 * t + 2 * q) * 4);
                    bar_sync(1, 256);
                    float kvd[20];
                    wg_fence();
#pragma unroll
                    for (int k = 0; k < 8; k++)
                        wgmma_n40_tt(kvd, dB + (3 + w) * (SLOT >> 4) + 128 * k, desc_lo(sb + OFF_A) + (vs + w) * (SLOT >> 4) + 128 * k, k != 0);
                    wg_commit();
#pragma unroll
                    for (int k = 0; k < 4; k++) wgmma_n64(accq, dA + (2 - vs) * (SLOT >> 4) + 2 * k, dB + 5 * (SLOT >> 4) + 128 * k, 1);
                    wg_commit();
                    wg_wait<1>();
                    fence_acc<20>(kvd);
                    const bool h1 = wv >= 2;
                    float* kvp = acc_j + 4 * tid;
                    red_f32x4(kvp, h1 ? kvd[8] : kvd[0], h1 ? kvd[9] : kvd[1], h1 ? kvd[10] : kvd[2], 1.f);
                    red_f32x4(kvp + 1024, h1 ? kvd[12] : kvd[4], h1 ? kvd[13] : kvd[5], h1 ? kvd[11] : kvd[3], 1.f);
                    red_f32x4(kvp + 2048, h1 ? kvd[14] : kvd[6], h1 ? kvd[15] : kvd[7], (q & 1) ? kvd[18] : kvd[16], 1.f);
                    TL(3, tid == 0);
#pragma unroll 1
                    for (int b = 1; b < 6; b++) {
                        const desc_t da = dA + (b < 2 ? 3 - vs : 2 + b) * (SLOT >> 4), db = dB + (b < 2 ? 11 : b - 2) * (SLOT >> 5);
                        wg_fence();
#pragma unroll
                        for (int k = 0; k < 4; k++) wgmma_n64(accq, da + 2 * k, db + 128 * k, 1);
                        wg_commit();
                    }
                    mbar_arrive_if(sb + BAR_KVW, l0);
                    mbar_arrive_cl_if(eb + 8 * (3 + (lane >> 1)), lane < 4);
                    wg_wait<0>();
                    fence_acc<32>(accq);
                    mbar_arrive_cl_if(eb + 8 * ((5 + (lane >> 1)) % 6), lane < 6);
                    TL(4, tid == 0);
                    centre4(accq, cq, s0.y, s1.y, a);
                }
            }
        }
        uint32_t res_lo[8], res_hi[8], ack[4];
        const uint32_t own_rows = sb + OFF_A + j * SLOT + warp * 2048;
#pragma unroll
        for (int b = 0; b < 4; b++)
            ldsm4(own_rows + lrow + (((2 * b + ch) ^ sw) << 4), res_lo[2 * b], res_hi[2 * b], res_lo[2 * b + 1], res_hi[2 * b + 1]);
        mbar_arrive_if(sb + BAR_EMPTYA + 8 * lane, lane < 8 && lane != j && lane != vs);
        TL(5, tid == 0);
        mbar_waitc(sb + BAR_KVR, 0);
        TL(6, tid == 0);
        {
            const uint32_t kvs = sb + OFF_A + vs * SLOT;
            uint32_t o_lo[8], o_hi[8];
#pragma unroll
            for (int hh = 0; hh < 4; hh++) {
                uint32_t b[8], zb[4];
                const uint32_t base = kvs + hh * 32 * 48;
                ldsm4t(base + (lane & 15) * 48 + (lane >> 4) * 16, b[0], b[1], b[2], b[3]);
                ldsm4t(base + (16 + (lane & 15)) * 48 + (lane >> 4) * 16, b[4], b[5], b[6], b[7]);
                ldsm4t(base + lane * 48 + 32, zb[0], zb[1], zb[2], zb[3]);
                float n0[4], n1[4], dn[4];
                mma16816_z(n0, fp + 4 * hh, b[0], b[1]); mma16816_z(n1, fp + 4 * hh, b[2], b[3]); mma16816_z(dn, fp + 4 * hh, zb[0], zb[1]);
                mma16816(n0, fm + 4 * hh, b[4], b[5]); mma16816(n1, fm + 4 * hh, b[6], b[7]); mma16816(dn, fm + 4 * hh, zb[2], zb[3]);
                const float i0 = rcp(dn[0] + 1e-6f), i1 = rcp(dn[2] + 1e-6f);
                o_lo[2 * hh] = pack_bf16(n0[0] * i0, n0[1] * i0); o_hi[2 * hh] = pack_bf16(n0[2] * i1, n0[3] * i1);
                o_lo[2 * hh + 1] = pack_bf16(n1[0] * i0, n1[1] * i0); o_hi[2 * hh + 1] = pack_bf16(n1[2] * i1, n1[3] * i1);
            }
            __syncwarp();
            mbar_arrive_if(sb + BAR_EMPTYA + 8 * vs, l0);
            rg.slot = 2; rg.phase = 0;
            store_tile(own_rows, g_act + role * 1024 + warp * 128 + lane, o_lo, o_hi, lane, ack);
            TL(7, tid == 0);
        }
        float acch[32];
        {
            float* acc = acch;
#pragma unroll
            for (int t = 0; t < 8; t++) {
                acc[4 * t] = bf_lo(res_lo[t]); acc[4 * t + 1] = bf_hi(res_lo[t]);
                acc[4 * t + 2] = bf_lo(res_hi[t]); acc[4 * t + 3] = bf_hi(res_hi[t]);
            }
            fence_acc<32>(acc);
            int pa = 0;
#pragma unroll 1
            for (int kp = 0; kp < 4; kp++) {
                mbar_waitc(sb + BAR_FULLB + 8 * rg.slot, rg.phase);
#pragma unroll
                for (int hf = 0; hf < 2; hf++) {
                    const int i = 2 * kp + hf, kt = KORD(i, j);
                    mbar_waitc(sb + BAR_FULLA + 8 * kt, i != 0);
                    TL(8, i == 1 && tid == 0);
                    const desc_t da = dA + kt * (SLOT >> 4), db = dB + rg.slot * (SLOT >> 4);
                    wg_fence();
#pragma unroll
                    for (int k = 0; k < 4; k++) wgmma_n64(acc, da + 2 * k, db + (hf * 4 + k) * 128, 1);
                    wg_commit();
                    wg_wait<1>();
                    mbar_arrive_if(sb + BAR_EMPTYA + 8 * pa, l0 && i > 1);
                    if (hf == 0) {
                        mbar_arrive_cl_if(eb + 8 * prev, l2 && i > 0);
                        if (i == 0) { signal_late(flag_m, ack, P.zero, l0); TL(20, tid == 0); }
                    }
                    pa = kt;
                }
                prev = rg.slot; rg.adv();
            }
            wg_wait<0>();
            fence_acc<32>(acc);
            mbar_arrive_if(sb + BAR_EMPTYA + 8 * pa, l0);
            mbar_arrive_cl_if(eb + 8 * prev, l2);
            TL(9, tid == 0);
#pragma unroll
            for (int t = 0; t < 8; t++) {
                res_lo[t] = pack_bf16(acc[4 * t], acc[4 * t + 1]);
                res_hi[t] = pack_bf16(acc[4 * t + 2], acc[4 * t + 3]);
            }
            store_tile(own_rows, g_act + (128 + role) * 1024 + warp * 128 + lane, res_lo, res_hi, lane, ack);
            TL(10, tid == 0);
        }
        float acc0[64], acc1[64], acc2[56], nm0, nm1;
        float4 cs[8];
        uint32_t hr[16];
#define P3_GROUP(MMA, ACC, KT)                                                                              \
        mbar_waitc(sb + BAR_FULLB + 8 * rg.slot, rg.phase);                                                 \
        {                                                                                                   \
            const desc_t da = dA + (KT) * (SLOT >> 4), db = dB + rg.slot * (SLOT >> 4);                     \
            wg_fence();                                                                                     \
            _Pragma("unroll") for (int k = 0; k < 4; k++) MMA(ACC, da + 2 * k, db + 128 * k, (i | k) != 0); \
            wg_commit();                                                                                    \
        }
#define P3_CS(C, NT)    \
        _Pragma("unroll") for (int t = 0; t < (NT); t++) lds_f4_if(cs[t], sb + OFF_CS3 + q * 16 + 512 * (C) + 64 * t, i == t);
#define P3_EPI2(C, ACC)                                                                                     \
        if (i == 0) {                                                                                       \
            fence_acc<64>(ACC);                                                                             \
            if (C) mbar_waitc(sb + BAR_FULLB + 8 * 4, 1);                                                   \
            hh_stage2<0, 2>(ACC, cs, nm0, nm1, stg, lane);                                                  \
            mbar_waitc(sb + BAR_CSG + 8 * (C) + 8, 0);                                                      \
        }                                                                                                   \
        if (i == 1) {                                                                                       \
            hh_stage2<2, 4>(ACC, cs, nm0, nm1, stg, lane);                                                  \
            fence_async_smem();                                                                             \
            __syncwarp();                                                                                   \
            mbar_arrive_if(sb + BAR_STG + 8 * (C), l0);                                                     \
        }
#define P3_EPI(C, ACC, N, NTP)                                                                              \
        fence_acc<N>(ACC);                                                                                  \
        TL(11 + (C), tid == 0);                                                                             \
        hh_stage<NTP>(ACC, cs, nm0, nm1, sb + OFF_B + 4 * SLOT + warp * 2048, lane);                        \
        mbar_arrive_if(sb + BAR_STG + 8 * (C), l0);                                                         \
        TL(50 + (C), tid == 0);
        const uint32_t stg = sb + OFF_B + 4 * SLOT + warp * 2048;
        const uint32_t blk = ((lane & 7) + (lane >> 4) * 8) * 128 + (((2 * wv + ((lane >> 3) & 1)) ^ (lane & 7)) << 4);
#pragma unroll 1
        for (int i = 0; i < 8; i++) {
            const int kt = KORD(i, j);
            mbar_waitc(sb + BAR_FULLA + 8 * kt, 0);
            TL(44, tid == 0 && i == 1);
            P3_GROUP(wgmma_n128, acc0, kt)
            if (i == 7) {
                mbar_waitc(sb + BAR_CS3, 0);
                nm0 = lds_f2(sb + OFF_CS1 + (16 * warp + g) * 8).x; nm1 = lds_f2(sb + OFF_CS1 + (16 * warp + g + 8) * 8).x;
            }
            wg_wait<1>();
            mbar_arrive_cl_if(eb + 8 * prev, l2 && i > 0);
            if (i == 0) {
                signal_late(flag_m + 32, ack, P.zero, l0);
                TL(21, tid == 0);
                {
                    fence_acc<32>(acch);
                    const float* acc = acch;
                    float s0 = 0.f, s1 = 0.f;
#pragma unroll
                    for (int t = 0; t < 8; t++) { s0 += acc[4 * t] + acc[4 * t + 1]; s1 += acc[4 * t + 2] + acc[4 * t + 3]; }
            s0 += __shfl_xor_sync(0xffffffffu, s0, 1); s1 += __shfl_xor_sync(0xffffffffu, s1, 1);
            s0 += __shfl_xor_sync(0xffffffffu, s0, 2); s1 += __shfl_xor_sync(0xffffffffu, s1, 2);
            const float mu0 = s0 * (1.f / 64), mu1 = s1 * (1.f / 64);
            float q0 = 0.f, q1 = 0.f;
#pragma unroll
            for (int t = 0; t < 8; t++) {
                float d;
                d = acc[4 * t] - mu0; q0 = fmaf(d, d, q0);
                d = acc[4 * t + 1] - mu0; q0 = fmaf(d, d, q0);
                d = acc[4 * t + 2] - mu1; q1 = fmaf(d, d, q1);
                d = acc[4 * t + 3] - mu1; q1 = fmaf(d, d, q1);
            }
            q0 += __shfl_xor_sync(0xffffffffu, q0, 1); q1 += __shfl_xor_sync(0xffffffffu, q1, 1);
            q0 += __shfl_xor_sync(0xffffffffu, q0, 2); q1 += __shfl_xor_sync(0xffffffffu, q1, 2);
            st_tagged_if(g_hstat + (role * 128 + 16 * warp + g + 8 * (q & 1)) * 2, q ? mu1 : mu0, q ? q1 : q0, epoch, q < 2);
                }
                bar_sync(2 + w, 128);
#pragma unroll
                for (int tp = 0; tp < 4; tp++) ldsm4t(sa + j * SLOT + blk + tp * 2048, hr[4 * tp], hr[4 * tp + 1], hr[4 * tp + 2], hr[4 * tp + 3]);
                mbar_waitc(sb + BAR_CSG, 0);
#pragma unroll
                for (int t = 0; t < 8; t++) cs[t] = lds_f4(sb + OFF_CS3 + q * 16 + 64 * t);
            }
            prev = rg.slot; rg.adv5();
        }
#pragma unroll 1
        for (int i = 0; i < 8; i++) {
            P3_GROUP(wgmma_n128, acc1, i)
            wg_wait<1>();
            mbar_arrive_cl_if(eb + 8 * prev, l2);
            P3_EPI2(0, acc0)
            P3_CS(1, 8)
            prev = rg.slot; rg.adv5();
        }
#pragma unroll 1
        for (int i = 0; i < 8; i++) {
            P3_GROUP(wgmma_n112, acc2, i)
            wg_wait<1>();
            mbar_arrive_cl_if(eb + 8 * prev, l2);
            mbar_arrive_if(sb + BAR_EMPTYA + 8 * ((i + 7) & 7), l0 && i > 0);
            if (i == 0) { mbar_waitc(sb + BAR_FULLB + 8 * 4, 1); P3_EPI(1, acc1, 64, 4) mbar_waitc(sb + BAR_CSG + 16, 0); }
            P3_CS(2, 6)
            prev = rg.slot; rg.adv5();
        }
        mbar_waitc(sb + BAR_FULLB + 8 * 4, 0);
        wg_wait<0>();
        mbar_arrive_cl_if(eb + 8 * prev, l2);
        mbar_arrive_if(sb + BAR_EMPTYA + 8 * 7, l0);
        fence_acc<56>(acc2);
        TL(13, tid == 0);
#pragma unroll
        for (int tp = 0; tp < 3; tp++)
            stsm4(sb + OFF_B + 4 * SLOT + tp * 4096 + warp * 512 + (lane & 15) * 32 + ((ch ^ ((lane >> 2) & 1)) << 4),
                  hh_pair<32>(acc2 + 8 * tp, cs[2 * tp], nm0), hh_pair<32>(acc2 + 8 * tp + 2, cs[2 * tp], nm1),
                  hh_pair<32>(acc2 + 8 * tp + 4, cs[2 * tp + 1], nm0), hh_pair<32>(acc2 + 8 * tp + 6, cs[2 * tp + 1], nm1));
        fence_async_smem();
        __syncwarp();
        mbar_arrive_if(sb + BAR_STG + 16, l0);
        TL(52, tid == 0);
        {
            float acc[64];
            const desc_t dA0 = desc_lo(sb + OFF_A);
#define KT_P4(I, NK, DH, STEP)                                                                                   \
        const int s_ = (2 * (I) + w) & 7;                                                                   \
        mbar_waitc(sb + BAR_FULLB + 8 * rg.slot, rg.phase);                                                 \
        mbar_waitc(sb + BAR_FULLA + 8 * s_, (((I) >> 2) + 1) & 1);                                          \
        const desc_t dh_ = (DH) + s_ * (SLOT >> 4), dw_ = dB + rg.slot * (SLOT >> 4) + w * 512;              \
        wg_fence();                                                                                         \
        _Pragma("unroll") for (int k = 0; k < (NK); k++) wgmma_n128_tn(acc, dw_ + 128 * k, dh_ + (STEP) * k, ((I) | k) != 0); \
        wg_commit();
#pragma unroll 1
            for (int i = 0; i < 8; i++) {
                KT_P4(i, 4, dA0, 2)
#pragma unroll
                for (int t = 0; t < 8; t++) lds_f4_if(cs[t], sb + OFF_CS1 + (64 * w + 8 * t + 2 * q) * 8, i == t);
                wg_wait<0>();
                mbar_arrive_n_if(sb + BAR_EMPTYA + 8 * s_, 2, l0);
                mbar_arrive_cl_if(eb + 8 * rg.slot, l2 && i < 7);
                rg.adv5();
            }
#pragma unroll 1
            for (int i = 8; i < 12; i++) {
                KT_P4(i, 3, dA0 + ((0xC0000010ull - 0x40000040ull) << 32), 256)
                wg_wait<1>();
                rg.adv5();
            }
            wg_wait<0>();
            fence_acc<64>(acc);
            TL(15, tid == 0);
            const uint32_t xch = sb + OFF_A + 2 * SLOT + (tid & 127) * 16;
            if (w) {
#pragma unroll
                for (int t = 0; t < 8; t++) {
                    sts128(xch + SLOT + t * 2048, __float_as_uint(acc[4 * t]), __float_as_uint(acc[4 * t + 1]),
                           __float_as_uint(acc[4 * t + 2]), __float_as_uint(acc[4 * t + 3]));
                }
#pragma unroll
                for (int t = 0; t < 32; t++) acc[t] = acc[32 + t];
            } else {
#pragma unroll
                for (int t = 0; t < 8; t++)
                    sts128(xch + t * 2048, __float_as_uint(acc[32 + 4 * t]), __float_as_uint(acc[33 + 4 * t]),
                           __float_as_uint(acc[34 + 4 * t]), __float_as_uint(acc[35 + 4 * t]));
            }
            bar_sync(1, 256);
            float4 o[8];
#pragma unroll
            for (int t = 0; t < 8; t++) o[t] = lds_f4(xch + (w ^ 1) * SLOT + t * 2048);
            const uint32_t tile = sb + OFF_A + w * SLOT;
#pragma unroll
            for (int t = 0; t < 8; t++) {
                hr[2 * t] = pack_bf16(fmaf(acc[4 * t] + o[t].x, cs[t].y, bf_lo(hr[2 * t])), fmaf(acc[4 * t + 1] + o[t].y, cs[t].w, bf_hi(hr[2 * t])));
                hr[2 * t + 1] = pack_bf16(fmaf(acc[4 * t + 2] + o[t].z, cs[t].y, bf_lo(hr[2 * t + 1])), fmaf(acc[4 * t + 3] + o[t].w, cs[t].w, bf_hi(hr[2 * t + 1])));
            }
#pragma unroll
            for (int tp = 0; tp < 4; tp++) stsm4t(tile + blk + tp * 2048, hr[4 * tp], hr[4 * tp + 1], hr[4 * tp + 2], hr[4 * tp + 3]);
            fence_async_smem();
            bar_sync(2 + w, 128);
            if ((tid & 127) == 0) {
                tma_store2d(&P.tout, tile, 64 * j, 128 * m + 64 * w);
                asm volatile("cp.async.bulk.wait_group.read 0;" ::: "memory");
            }
            if (tid == 0 && role == 0) g_epoch = epoch + 1;
            TL(16, tid == 0); TLG(1, tid == 0);
        }
    }
}

typedef CUresult (*EncodeFn)(CUtensorMap*, CUtensorMapDataType, cuuint32_t, void*, const cuuint64_t*, const cuuint64_t*,
                             const cuuint32_t*, const cuuint32_t*, CUtensorMapInterleave, CUtensorMapSwizzle,
                             CUtensorMapL2promotion, CUtensorMapFloatOOBfill);

static void make_map2d(EncodeFn enc, CUtensorMap* tm, const void* base, uint64_t cols, uint64_t rows, uint64_t pitch_elems,
                       uint32_t box_rows) {
    cuuint64_t gd[2] = {cols, rows};
    cuuint64_t gs[1] = {pitch_elems * 2};
    cuuint32_t bd[2] = {64, box_rows};
    cuuint32_t es[2] = {1, 1};
    enc(tm, CU_TENSOR_MAP_DATA_TYPE_BFLOAT16, 2, const_cast<void*>(base), gd, gs, bd, es, CU_TENSOR_MAP_INTERLEAVE_NONE,
        CU_TENSOR_MAP_SWIZZLE_128B, CU_TENSOR_MAP_L2_PROMOTION_L2_256B, CU_TENSOR_MAP_FLOAT_OOB_FILL_NONE);
}

}

extern "C" void kernel_launch(void* const* d_in, const int* in_sizes, int n_in, void* d_out, int out_size) {
    using namespace hk;
    (void)in_sizes; (void)n_in; (void)out_size;
    static EncodeFn enc = nullptr;
    if (!enc) {
        void* fn = nullptr;
        cudaDriverEntryPointQueryResult qr;
        cudaGetDriverEntryPoint("cuTensorMapEncodeTiled", &fn, cudaEnableDefault, &qr);
        enc = (EncodeFn)fn;
        cudaFuncSetAttribute(fused_kernel, cudaFuncAttributeMaxDynamicSharedMemorySize, SMEM_BYTES);
    }
    Params P;
    const __nv_bfloat16* x = (const __nv_bfloat16*)d_in[0];
    P.x = x;
    P.wqkv = (const __nv_bfloat16*)d_in[1];
    P.wphi = (const __nv_bfloat16*)d_in[2];
    P.wo = (const __nv_bfloat16*)d_in[3];
    P.wg = (const __nv_bfloat16*)d_in[5];
    P.wu = (const __nv_bfloat16*)d_in[6];
    P.wd = (const __nv_bfloat16*)d_in[7];
    P.out = (__nv_bfloat16*)d_out;
    P.zero = 0;
    make_map2d(enc, &P.tx, x, DM, SEQ, DM, 128);
    make_map2d(enc, &P.twq, P.wqkv, 3 * DM, DM, 3 * DM, 64);
    make_map2d(enc, &P.two, P.wo, DM, DM, DM, 64);
    make_map2d(enc, &P.twg, P.wg, FF, DM, FF, 64);
    make_map2d(enc, &P.twu, P.wu, FF, DM, FF, 64);
    make_map2d(enc, &P.twd, P.wd, DM, FF, DM, 64);
    make_map2d(enc, &P.twd48, P.wd, DM, FF, DM, 48);
    make_map2d(enc, &P.tout, d_out, DM, SEQ, DM, 64);
    fused_kernel<<<NCTA, NTHREADS, SMEM_BYTES>>>(P);
}
```

```cpp
#include <cuda_runtime.h>
#include <cuda_bf16.h>
#include <cuda.h>
#include <stdint.h>

namespace hk {

constexpr int SEQ = 2048, DM = 512, FF = 1376;
constexpr int NCTA = 132;
constexpr int NTHREADS = 384;
constexpr uint32_t SLOT = 16384;
constexpr uint32_t OFF_A = 0, OFF_B = 8 * SLOT, OFF_MISC = 14 * SLOT;
constexpr uint32_t BAR_FULLA = OFF_MISC + 0, BAR_EMPTYA = OFF_MISC + 64, BAR_FULLB = OFF_MISC + 128,
                   BAR_EMPTYB = OFF_MISC + 176, BAR_CS1 = OFF_MISC + 224, BAR_CS3 = OFF_MISC + 232,
                   BAR_CSQ = OFF_MISC + 240, BAR_CSV = OFF_MISC + 248,
                   BAR_STG = OFF_MISC + 256,
                   BAR_KVW = OFF_MISC + 280, BAR_KVR = OFF_MISC + 288,
                   BAR_CSG = OFF_MISC + 296,
                   BAR_FULLH = OFF_MISC + 320;
constexpr uint32_t OFF_CS1 = OFF_MISC + 384;
constexpr uint32_t OFF_CS3 = OFF_CS1 + 1024;
constexpr uint32_t OFF_XST = OFF_CS3;
constexpr uint32_t SMEM_BYTES = OFF_CS3 + 1536;
#define KORD(i, j) ((i) == 0 ? (j) : (i) - ((i) <= (j)))
constexpr int NB = 6;
constexpr int NPRE = 3, AHEAD = 3, AHEADA = 5;
constexpr int PF_DELAY = 2;

constexpr int ACC_SIZE = 3 * 256 * 4;

__device__ __align__(1024) uint4 g_act[5 * 128 * 1024];
__device__ __align__(128) unsigned long long g_hstat[SEQ * 16];
__device__ __align__(128) unsigned long long g_xstat[SEQ * 2];
__device__ __align__(128) float g_acc[8 * ACC_SIZE];
__device__ __align__(128) unsigned long long g_cs[8 * 6 * 128];
__device__ __align__(128) unsigned g_flag[16 * 7 * 32];
__device__ unsigned g_epoch = 1;

#define TL(i, pred) do {} while (0)
#define TLG(i, pred) do {} while (0)

struct Params {
    CUtensorMap tx, twq, two, twg, twu, twd, twd48, tout;
    const __nv_bfloat16 *x, *wqkv, *wphi, *wo, *wg, *wu, *wd;
    __nv_bfloat16* out;
    unsigned zero;
};

__device__ __forceinline__ uint32_t smem_u32(const void* p) { return (uint32_t)__cvta_generic_to_shared(p); }
__device__ __forceinline__ void mbar_init(uint32_t bar, uint32_t cnt) {
    asm volatile("mbarrier.init.shared::cta.b64 [%0], %1;" ::"r"(bar), "r"(cnt) : "memory");
}
__device__ __forceinline__ void mbar_expect_tx(uint32_t bar, uint32_t bytes) {
    asm volatile("mbarrier.arrive.expect_tx.shared::cta.b64 _, [%0], %1;" ::"r"(bar), "r"(bytes) : "memory");
}
__device__ __forceinline__ void mbar_arrive(uint32_t bar) {
    asm volatile("mbarrier.arrive.shared::cta.b64 _, [%0];" ::"r"(bar) : "memory");
}
__device__ __forceinline__ void mbar_arrive_if(uint32_t bar, bool pred) {
    asm volatile("{.reg .pred p; setp.ne.u32 p, %1, 0; @p mbarrier.arrive.shared::cta.b64 _, [%0];}" ::"r"(bar), "r"((uint32_t)pred) : "memory");
}
__device__ __forceinline__ void trap_if_gt(uint32_t v, uint32_t lim) {
    asm volatile("{.reg .pred p; setp.gt.u32 p, %0, %1; @p trap;}" ::"r"(v), "r"(lim));
}
__device__ __forceinline__ void mbar_wait(uint32_t bar, uint32_t parity) {
    asm volatile("{\n"
                 ".reg .pred P1, P2;\n"
                 ".reg .u32 c;\n"
                 "mov.u32 c, 0;\n"
                 "LAB_WAIT:\n"
                 "mbarrier.try_wait.parity.shared::cta.b64 P1, [%0], %1;\n"
                 "@P1 bra LAB_DONE;\n"
                 "add.u32 c, c, 1;\n"
                 "setp.gt.u32 P2, c, 1048576;\n"
                 "@P2 trap;\n"
                 "bra LAB_WAIT;\n"
                 "LAB_DONE:\n"
                 "}" ::"r"(bar), "r"(parity) : "memory");
}
__device__ __forceinline__ void mbar_waitc(uint32_t bar, uint32_t parity) {
    asm volatile("{\n"
                 ".reg .pred P1;\n"
                 "LAB_WAIT:\n"
                 "mbarrier.try_wait.parity.shared::cta.b64 P1, [%0], %1;\n"
                 "@!P1 bra LAB_WAIT;\n"
                 "}" ::"r"(bar), "r"(parity) : "memory");
}
__device__ __forceinline__ void tma2d(uint32_t dst, const CUtensorMap* tm, uint32_t bar, int c0, int c1) {
    asm volatile("cp.async.bulk.tensor.2d.shared::cluster.global.mbarrier::complete_tx::bytes [%0], [%1, {%3, %4}], [%2];"
                 ::"r"(dst), "l"(tm), "r"(bar), "r"(c0), "r"(c1) : "memory");
}
__device__ __forceinline__ void tma2d_mc(uint32_t dst, const CUtensorMap* tm, uint32_t bar, int c0, int c1) {
    asm volatile("cp.async.bulk.tensor.2d.shared::cluster.global.mbarrier::complete_tx::bytes.multicast::cluster [%0], [%1, {%3, %4}], [%2], %5;"
                 ::"r"(dst), "l"(tm), "r"(bar), "r"(c0), "r"(c1), "h"((uint16_t)3) : "memory");
}
__device__ __forceinline__ uint32_t mapa(uint32_t addr, uint32_t rank) {
    uint32_t r; asm("mapa.shared::cluster.u32 %0, %1, %2;" : "=r"(r) : "r"(addr), "r"(rank)); return r;
}
__device__ __forceinline__ void mbar_arrive_cl_if(uint32_t cbar, bool pred) {
    asm volatile("{.reg .pred p; setp.ne.u32 p, %1, 0; @p mbarrier.arrive.shared::cluster.b64 _, [%0];}" ::"r"(cbar), "r"((uint32_t)pred) : "memory");
}
__device__ __forceinline__ bool elect_one() {
    uint32_t ok;
    asm volatile("{.reg .pred p; elect.sync _|p, 0xffffffff; selp.u32 %0, 1, 0, p;}" : "=r"(ok));
    return ok;
}
__device__ __forceinline__ void prefetch_tmap(const CUtensorMap* tm) {
    asm volatile("prefetch.tensormap [%0];" ::"l"(tm) : "memory");
}
__device__ __forceinline__ void prefetch_l2(const void* p, uint32_t bytes) {
    asm volatile("cp.async.bulk.prefetch.L2.global [%0], %1;" ::"l"(p), "r"(bytes) : "memory");
}
__device__ __forceinline__ unsigned ld_relaxed(const unsigned* p) {
    unsigned v; asm volatile("ld.relaxed.gpu.global.u32 %0, [%1];" : "=r"(v) : "l"(p)); return v;
}
__device__ __forceinline__ void fence_async_smem() { asm volatile("fence.proxy.async.shared::cta;" ::: "memory"); }
__device__ __forceinline__ uint32_t readback(const void* p) {
    uint32_t v; asm volatile("ld.relaxed.gpu.global.u32 %0, [%1];" : "=r"(v) : "l"(p) : "memory"); return v;
}
__device__ __forceinline__ void wait_count(const unsigned* p, unsigned target) {
    uint32_t it = 0;
    while ((int)(readback(p) - target) < 0) trap_if_gt(++it, 1u << 22);
}
__device__ __forceinline__ void red_f32x4(float* p, float a, float b, float c, float d) {
    asm volatile("red.relaxed.gpu.global.add.v4.f32 [%0], {%1, %2, %3, %4};" ::"l"(p), "f"(a), "f"(b), "f"(c), "f"(d) : "memory");
}
__device__ __forceinline__ float4 ld_l2_f4(const float* p) {
    float4 v;
    asm volatile("ld.relaxed.gpu.global.v4.f32 {%0,%1,%2,%3}, [%4];" : "=f"(v.x), "=f"(v.y), "=f"(v.z), "=f"(v.w) : "l"(p) : "memory");
    return v;
}
__device__ __forceinline__ void stg128(void* p, uint32_t a, uint32_t b, uint32_t c, uint32_t d) {
    asm volatile("st.global.v4.u32 [%0], {%1,%2,%3,%4};" ::"l"(p), "r"(a), "r"(b), "r"(c), "r"(d) : "memory");
}
__device__ __forceinline__ uint4 lds128(uint32_t a) {
    uint4 v;
    asm volatile("ld.shared.v4.u32 {%0,%1,%2,%3}, [%4];" : "=r"(v.x), "=r"(v.y), "=r"(v.z), "=r"(v.w) : "r"(a) : "memory");
    return v;
}
__device__ __forceinline__ float2 lds_f2(uint32_t a) {
    float2 v;
    asm volatile("ld.shared.v2.f32 {%0,%1}, [%2];" : "=f"(v.x), "=f"(v.y) : "r"(a) : "memory");
    return v;
}
__device__ __forceinline__ void sts_f2(uint32_t a, float x, float y) {
    asm volatile("st.shared.v2.f32 [%0], {%1,%2};" ::"r"(a), "f"(x), "f"(y) : "memory");
}
__device__ __forceinline__ void sts64(uint32_t a, uint32_t x, uint32_t y) {
    asm volatile("st.shared.v2.u32 [%0], {%1,%2};" ::"r"(a), "r"(x), "r"(y) : "memory");
}
__device__ __forceinline__ void sts128(uint32_t a, uint32_t x, uint32_t y, uint32_t z, uint32_t w) {
    asm volatile("st.shared.v4.u32 [%0], {%1,%2,%3,%4};" ::"r"(a), "r"(x), "r"(y), "r"(z), "r"(w) : "memory");
}
__device__ __forceinline__ void stsm4(uint32_t a, uint32_t r0, uint32_t r1, uint32_t r2, uint32_t r3) {
    asm volatile("stmatrix.sync.aligned.m8n8.x4.shared.b16 [%0], {%1,%2,%3,%4};" ::"r"(a), "r"(r0), "r"(r1), "r"(r2), "r"(r3) : "memory");
}
__device__ __forceinline__ void stsm4t(uint32_t a, uint32_t r0, uint32_t r1, uint32_t r2, uint32_t r3) {
    asm volatile("stmatrix.sync.aligned.m8n8.x4.trans.shared.b16 [%0], {%1,%2,%3,%4};" ::"r"(a), "r"(r0), "r"(r1), "r"(r2), "r"(r3) : "memory");
}
__device__ __forceinline__ void tma_store2d(const CUtensorMap* tm, uint32_t src, int c0, int c1) {
    asm volatile("cp.async.bulk.tensor.2d.global.shared::cta.bulk_group [%0, {%2, %3}], [%1];" ::"l"(tm), "r"(src), "r"(c0), "r"(c1) : "memory");
    asm volatile("cp.async.bulk.commit_group;" ::: "memory");
}
__device__ __forceinline__ void ldsm4(uint32_t a, uint32_t& r0, uint32_t& r1, uint32_t& r2, uint32_t& r3) {
    asm volatile("ldmatrix.sync.aligned.m8n8.x4.shared.b16 {%0,%1,%2,%3}, [%4];" : "=r"(r0), "=r"(r1), "=r"(r2), "=r"(r3) : "r"(a) : "memory");
}
__device__ __forceinline__ void ldsm4t(uint32_t a, uint32_t& r0, uint32_t& r1, uint32_t& r2, uint32_t& r3) {
    asm volatile("ldmatrix.sync.aligned.m8n8.x4.trans.shared.b16 {%0,%1,%2,%3}, [%4];" : "=r"(r0), "=r"(r1), "=r"(r2), "=r"(r3) : "r"(a) : "memory");
}
__device__ __forceinline__ void mma16816(float* c, const uint32_t* a, uint32_t b0, uint32_t b1) {
    asm("mma.sync.aligned.m16n8k16.row.col.f32.bf16.bf16.f32 {%0,%1,%2,%3}, {%4,%5,%6,%7}, {%8,%9}, {%0,%1,%2,%3};"
                 : "+f"(c[0]), "+f"(c[1]), "+f"(c[2]), "+f"(c[3])
                 : "r"(a[0]), "r"(a[1]), "r"(a[2]), "r"(a[3]), "r"(b0), "r"(b1));
}
__device__ __forceinline__ uint32_t pack_bf16(float lo, float hi) {
    uint32_t r; asm("cvt.rn.bf16x2.f32 %0, %1, %2;" : "=r"(r) : "f"(hi), "f"(lo)); return r;
}
__device__ __forceinline__ float bf_lo(uint32_t w) { return __uint_as_float(w << 16); }
__device__ __forceinline__ float bf_hi(uint32_t w) { return __uint_as_float(w & 0xffff0000u); }
__device__ __forceinline__ float ex2(float x) { float r; asm("ex2.approx.ftz.f32 %0, %1;" : "=f"(r) : "f"(x)); return r; }
__device__ __forceinline__ float rcp(float x) { float r; asm("rcp.approx.ftz.f32 %0, %1;" : "=f"(r) : "f"(x)); return r; }
__device__ __forceinline__ void bar_sync(int id, int n) { asm volatile("bar.sync %0, %1;" ::"r"(id), "r"(n) : "memory"); }

typedef unsigned long long desc_t;
__device__ __forceinline__ desc_t desc_lo(uint32_t addr) { return (desc_t)(((addr & 0x3FFFF) >> 4) | (512u << 16)) | (0x40000040ull << 32); }
__device__ __forceinline__ void wg_fence() { asm volatile("wgmma.fence.sync.aligned;" ::: "memory"); }
__device__ __forceinline__ void wg_commit() { asm volatile("wgmma.commit_group.sync.aligned;" ::: "memory"); }
template <int N> __device__ __forceinline__ void wg_wait() { asm volatile("wgmma.wait_group.sync.aligned %0;" ::"n"(N) : "memory"); }
template <int N> __device__ __forceinline__ void fence_acc(float* d) {
#pragma unroll
    for (int i = 0; i < N; i++) asm volatile("" : "+f"(d[i])::"memory");
}
#define R4(o) "+f"(d[o + 0]), "+f"(d[o + 1]), "+f"(d[o + 2]), "+f"(d[o + 3])
#define R8(o) R4(o), R4(o + 4)
__device__ __forceinline__ void wgmma_n128(float* d, desc_t da, desc_t db, int sc) {
    asm volatile("{.reg .pred p; setp.ne.b32 p, %66, 0;\n"
                 "wgmma.mma_async.sync.aligned.m64n128k16.f32.bf16.bf16 {%0,%1,%2,%3,%4,%5,%6,%7,%8,%9,%10,%11,%12,%13,%14,%15,%16,%17,%18,%19,%20,%21,%22,%23,%24,%25,%26,%27,%28,%29,%30,%31,"
                 "%32,%33,%34,%35,%36,%37,%38,%39,%40,%41,%42,%43,%44,%45,%46,%47,%48,%49,%50,%51,%52,%53,%54,%55,%56,%57,%58,%59,%60,%61,%62,%63}, %64, %65, p, 1, 1, 0, 1;}"
                 : R8(0), R8(8), R8(16), R8(24), R8(32), R8(40), R8(48), R8(56)
                 : "l"(da), "l"(db), "r"(sc));
}
__device__ __forceinline__ void wgmma_n112(float* d, desc_t da, desc_t db, int sc) {
    asm volatile("{.reg .pred p; setp.ne.b32 p, %58, 0;\n"
                 "wgmma.mma_async.sync.aligned.m64n112k16.f32.bf16.bf16 {%0,%1,%2,%3,%4,%5,%6,%7,%8,%9,%10,%11,%12,%13,%14,%15,%16,%17,%18,%19,%20,%21,%22,%23,%24,%25,%26,%27,%28,%29,%30,%31,%32,%33,%34,%35,%36,%37,%38,%39,%40,%41,%42,%43,%44,%45,%46,%47,%48,%49,%50,%51,%52,%53,%54,%55}, %56, %57, p, 1, 1, 0, 1;}"
                 : R8(0), R8(8), R8(16), R8(24), R8(32), R8(40), R8(48)
                 : "l"(da), "l"(db), "r"(sc));
}
__device__ __forceinline__ void wgmma_n128_tn(float* d, desc_t da, desc_t db, int sc) {
    asm volatile("{.reg .pred p; setp.ne.b32 p, %66, 0;\n"
                 "wgmma.mma_async.sync.aligned.m64n128k16.f32.bf16.bf16 {%0,%1,%2,%3,%4,%5,%6,%7,%8,%9,%10,%11,%12,%13,%14,%15,%16,%17,%18,%19,%20,%21,%22,%23,%24,%25,%26,%27,%28,%29,%30,%31,%32,%33,%34,%35,%36,%37,%38,%39,%40,%41,%42,%43,%44,%45,%46,%47,%48,%49,%50,%51,%52,%53,%54,%55,%56,%57,%58,%59,%60,%61,%62,%63}, %64, %65, p, 1, 1, 1, 0;}"
                 : R8(0), R8(8), R8(16), R8(24), R8(32), R8(40), R8(48), R8(56)
                 : "l"(da), "l"(db), "r"(sc));
}
__device__ __forceinline__ void wgmma_n64(float* d, desc_t da, desc_t db, int sc) {
    asm volatile("{.reg .pred p; setp.ne.b32 p, %34, 0;\n"
                 "wgmma.mma_async.sync.aligned.m64n64k16.f32.bf16.bf16 {%0,%1,%2,%3,%4,%5,%6,%7,%8,%9,%10,%11,%12,%13,%14,%15,%16,%17,%18,%19,%20,%21,%22,%23,%24,%25,%26,%27,%28,%29,%30,%31}, %32, %33, p, 1, 1, 0, 1;}"
                 : R8(0), R8(8), R8(16), R8(24)
                 : "l"(da), "l"(db), "r"(sc));
}
__device__ __forceinline__ void wgmma_n40_tt(float* d, desc_t da, desc_t db, int sc) {
    asm volatile("{.reg .pred p; setp.ne.b32 p, %22, 0;\n"
                 "wgmma.mma_async.sync.aligned.m64n40k16.f32.bf16.bf16 {%0,%1,%2,%3,%4,%5,%6,%7,%8,%9,%10,%11,%12,%13,%14,%15,%16,%17,%18,%19}, %20, %21, p, 1, 1, 1, 1;}"
                 : R8(0), R8(8), R4(16)
                 : "l"(da), "l"(db), "r"(sc));
}

__device__ __forceinline__ void wgmma_n8_tt(float* d, desc_t da, desc_t db, int sc) {
    asm volatile("{.reg .pred p; setp.ne.b32 p, %6, 0;\n"
                 "wgmma.mma_async.sync.aligned.m64n8k16.f32.bf16.bf16 {%0,%1,%2,%3}, %4, %5, p, 1, 1, 1, 1;}"
                 : R4(0)
                 : "l"(da), "l"(db), "r"(sc));
}

__device__ __forceinline__ void signal_after(unsigned* cnt, uint32_t ack, uint32_t zero, bool pred) {
    asm volatile("{.reg .pred p; setp.ne.u32 p, %2, 0; @p red.relaxed.gpu.global.add.u32 [%0], %1;}"
                 ::"l"(cnt), "r"((ack & zero) + 1), "r"((uint32_t)pred) : "memory");
}
__device__ __forceinline__ void signal_late(unsigned* cnt, const uint32_t* a, uint32_t zero, bool pred) {
    uint32_t v;
    asm volatile("{.reg .b32 t; lop3.b32 t, %1, %2, %3, 0xfe; or.b32 %0, t, %4;}"
                 : "=r"(v) : "r"(a[0]), "r"(a[1]), "r"(a[2]), "r"(a[3]));
    signal_after(cnt, v, zero, pred);
}
__device__ __forceinline__ void mma16816_z(float* c, const uint32_t* a, uint32_t b0, uint32_t b1) {
    asm("mma.sync.aligned.m16n8k16.row.col.f32.bf16.bf16.f32 {%0,%1,%2,%3}, {%4,%5,%6,%7}, {%8,%9}, {%10,%10,%10,%10};"
                 : "=f"(c[0]), "=f"(c[1]), "=f"(c[2]), "=f"(c[3])
                 : "r"(a[0]), "r"(a[1]), "r"(a[2]), "r"(a[3]), "r"(b0), "r"(b1), "f"(0.f));
}
__device__ __forceinline__ uint32_t max2(uint32_t a, uint32_t b) { uint32_t r; asm("max.bf16x2 %0, %1, %2;" : "=r"(r) : "r"(a), "r"(b)); return r; }
__device__ __forceinline__ uint32_t min2(uint32_t a, uint32_t b) { uint32_t r; asm("min.bf16x2 %0, %1, %2;" : "=r"(r) : "r"(a), "r"(b)); return r; }
__device__ __forceinline__ void mbar_arrive_n_if(uint32_t bar, uint32_t n, bool pred) {
    asm volatile("{.reg .pred p; setp.ne.u32 p, %1, 0; @p mbarrier.arrive.shared::cta.b64 _, [%0], %2;}" ::"r"(bar), "r"((uint32_t)pred), "r"(n) : "memory");
}
__device__ __forceinline__ float4 lds_f4(uint32_t a) {
    float4 v;
    asm volatile("ld.shared.v4.f32 {%0,%1,%2,%3}, [%4];" : "=f"(v.x), "=f"(v.y), "=f"(v.z), "=f"(v.w) : "r"(a) : "memory");
    return v;
}
__device__ __forceinline__ void lds_f4_if(float4& v, uint32_t a, bool pred) {
    asm volatile("{.reg .pred p; setp.ne.u32 p, %5, 0; @p ld.shared.v4.f32 {%0,%1,%2,%3}, [%4];}"
                 : "+f"(v.x), "+f"(v.y), "+f"(v.z), "+f"(v.w) : "r"(a), "r"((uint32_t)pred) : "memory");
}
__device__ __forceinline__ uint4 ld_tagged_rlx(const unsigned long long* p) {
    unsigned long long a, b;
    asm volatile("ld.relaxed.gpu.global.v2.b64 {%0,%1}, [%2];" : "=l"(a), "=l"(b) : "l"(p) : "memory");
    return make_uint4((unsigned)a, (unsigned)(a >> 32), (unsigned)b, (unsigned)(b >> 32));
}
__device__ __forceinline__ void sts32(uint32_t a, uint32_t x) { asm volatile("st.shared.u32 [%0], %1;" ::"r"(a), "r"(x) : "memory"); }
__device__ __forceinline__ void fetch_tagged(const unsigned long long* src, uint32_t dst, unsigned epoch, unsigned ns) {
    uint4 v;
    uint32_t it = 0;
    while (true) {
        v = ld_tagged_rlx(src);
        if (!__any_sync(0xffffffffu, v.y != epoch || v.w != epoch)) break;
        __nanosleep(ns);
        trap_if_gt(++it, 1u << 22);
    }
    sts64(dst, v.x, v.z);
}
__device__ __forceinline__ void st_tagged_if(unsigned long long* p, float a, float b, unsigned tag, bool pred) {
    const unsigned long long t = (unsigned long long)tag << 32;
    asm volatile("{.reg .pred p; setp.ne.u32 p, %3, 0; @p st.relaxed.gpu.global.v2.b64 [%0], {%1,%2};}"
                 ::"l"(p), "l"(t | __float_as_uint(a)), "l"(t | __float_as_uint(b)), "r"((uint32_t)pred) : "memory");
}

__device__ __forceinline__ void store_tile(uint32_t tile_rows, uint4* gdst, const uint32_t* lo, const uint32_t* hi, int lane, uint32_t* ack) {
    const int r = lane & 15;
#pragma unroll
    for (int b = 0; b < 4; b++)
        stsm4(tile_rows + r * 128 + (((2 * b + (lane >> 4)) ^ (r & 7)) << 4), lo[2 * b], hi[2 * b], lo[2 * b + 1], hi[2 * b + 1]);
    fence_async_smem();
    __syncwarp();
#pragma unroll
    for (int i = 0; i < 4; i++) {
        const uint4 v = lds128(tile_rows + i * 512 + lane * 16);
        stg128(gdst + 32 * i, v.x, v.y, v.z, v.w);
    }
#pragma unroll
    for (int i = 0; i < 4; i++) ack[i] = readback(gdst + 32 * i);
}

__device__ __forceinline__ void feature_maps(const uint32_t* a, const uint32_t* wb, float c0, float c1, uint32_t* plus, uint32_t* minus) {
    uint32_t P[16], mx[4], mn[4];
#pragma unroll
    for (int h = 0; h < 4; h++) {
        float p[8];
        mma16816_z(p, a + 4 * h, wb[4 * h], wb[4 * h + 1]);
        mma16816_z(p + 4, a + 4 * h, wb[4 * h + 2], wb[4 * h + 3]);
        P[4 * h] = pack_bf16(p[0], p[2]); P[4 * h + 1] = pack_bf16(p[1], p[3]);
        P[4 * h + 2] = pack_bf16(p[4], p[6]); P[4 * h + 3] = pack_bf16(p[5], p[7]);
        mx[h] = max2(max2(P[4 * h], P[4 * h + 1]), max2(P[4 * h + 2], P[4 * h + 3]));
        mn[h] = min2(min2(P[4 * h], P[4 * h + 1]), min2(P[4 * h + 2], P[4 * h + 3]));
    }
#pragma unroll
    for (int s = 1; s <= 2; s <<= 1) {
        uint32_t tx[4], tn[4];
#pragma unroll
        for (int h = 0; h < 4; h++) { tx[h] = __shfl_xor_sync(0xffffffffu, mx[h], s); tn[h] = __shfl_xor_sync(0xffffffffu, mn[h], s); }
#pragma unroll
        for (int h = 0; h < 4; h++) { mx[h] = max2(mx[h], tx[h]); mn[h] = min2(mn[h], tn[h]); }
    }
#pragma unroll
    for (int h = 0; h < 4; h++) {
        const float mx0 = bf_lo(mx[h]) * c0, mx1 = bf_hi(mx[h]) * c1, mn0 = bf_lo(mn[h]) * c0, mn1 = bf_hi(mn[h]) * c1;
        float ep[8], em[8];
#pragma unroll
        for (int i = 0; i < 8; i++) {
            const bool r1 = (i & 2);
            const uint32_t w = P[4 * h + (i >> 2) * 2 + (i & 1)];
            const float p = r1 ? bf_hi(w) : bf_lo(w);
            ep[i] = ex2(fmaf(p, r1 ? c1 : c0, r1 ? -mx1 : -mx0));
            em[i] = ex2(fmaf(p, r1 ? -c1 : -c0, r1 ? mn1 : mn0));
        }
        float sp[4], sm[4];
        uint32_t tp[4], tm[4];
#pragma unroll
        for (int i = 0; i < 4; i++) { tp[i] = pack_bf16(ep[2 * i], ep[2 * i + 1]); tm[i] = pack_bf16(em[2 * i], em[2 * i + 1]); }
        mma16816_z(sp, tp, 0x3f803f80u, 0x3f803f80u);
        mma16816_z(sm, tm, 0x3f803f80u, 0x3f803f80u);
        const float r0 = rcp(sp[0] * sm[0]), r1 = rcp(sp[2] * sm[2]);
        const float rs[4] = {r0 * sm[0], r1 * sm[2], r0 * sp[0], r1 * sp[2]};
#pragma unroll
        for (int i = 0; i < 4; i++) {
            plus[4 * h + i] = pack_bf16(ep[2 * i] * rs[i & 1], ep[2 * i + 1] * rs[i & 1]);
            minus[4 * h + i] = pack_bf16(em[2 * i] * rs[2 + (i & 1)], em[2 * i + 1] * rs[2 + (i & 1)]);
        }
    }
}

template <bool SCALE>
__device__ __forceinline__ void ln_frag(const float* acc, uint32_t cs_addr, float rs0, float nm0, float rs1, float nm1, uint32_t* a) {
    const float2 c0 = lds_f2(cs_addr), c1 = lds_f2(cs_addr + 32);
    const float s0 = SCALE ? rs0 : 1.f, s1 = SCALE ? rs1 : 1.f;
    a[0] = pack_bf16(fmaf(nm0, c0.x, acc[0]) * s0, fmaf(nm0, c0.y, acc[1]) * s0);
    a[1] = pack_bf16(fmaf(nm1, c0.x, acc[2]) * s1, fmaf(nm1, c0.y, acc[3]) * s1);
    a[2] = pack_bf16(fmaf(nm0, c1.x, acc[4]) * s0, fmaf(nm0, c1.y, acc[5]) * s0);
    a[3] = pack_bf16(fmaf(nm1, c1.x, acc[6]) * s1, fmaf(nm1, c1.y, acc[7]) * s1);
}

template <int UP>
__device__ __forceinline__ uint32_t hh_pair(const float* ag, float4 cs, float nmean) {
    const float g0 = fmaf(nmean, cs.x, ag[0]), g1 = fmaf(nmean, cs.y, ag[1]);
    const float u0 = fmaf(nmean, cs.z, ag[UP]), u1 = fmaf(nmean, cs.w, ag[UP + 1]);
    return pack_bf16(g0 * u0, g1 * u1);
}
template <int NTP>
__device__ __forceinline__ void hh_stage(const float* acc, const float4* cs, float nm0, float nm1, uint32_t stg, int lane) {
#pragma unroll
    for (int tp = 0; tp < NTP; tp++)
        stsm4(stg + (lane & 15) * 128 + (((2 * tp + (lane >> 4)) ^ (lane & 7)) << 4), hh_pair<32>(acc + 8 * tp, cs[2 * tp], nm0),
              hh_pair<32>(acc + 8 * tp + 2, cs[2 * tp], nm1), hh_pair<32>(acc + 8 * tp + 4, cs[2 * tp + 1], nm0),
              hh_pair<32>(acc + 8 * tp + 6, cs[2 * tp + 1], nm1));
    fence_async_smem();
    __syncwarp();
}

template <int TP0, int TP1>
__device__ __forceinline__ void hh_stage2(const float* acc, const float4* cs, float nm0, float nm1, uint32_t stg, int lane) {
#pragma unroll
    for (int tp = TP0; tp < TP1; tp++)
        stsm4(stg + (lane & 15) * 128 + (((2 * tp + (lane >> 4)) ^ (lane & 7)) << 4), hh_pair<32>(acc + 8 * tp, cs[2 * tp], nm0),
              hh_pair<32>(acc + 8 * tp + 2, cs[2 * tp], nm1), hh_pair<32>(acc + 8 * tp + 4, cs[2 * tp + 1], nm0),
              hh_pair<32>(acc + 8 * tp + 6, cs[2 * tp + 1], nm1));
}
struct Ring {
    int slot; uint32_t phase;
    __device__ __forceinline__ void adv() { if (++slot == NB) { slot = 0; phase ^= 1; } }
    __device__ __forceinline__ void adv5() { slot += slot == 3; adv(); }
};

__global__ void __cluster_dims__(2, 1, 1) __launch_bounds__(NTHREADS, 1) fused_kernel(const __grid_constant__ Params P) {
    extern __shared__ __align__(1024) uint8_t smem_raw[];
    const uint32_t sb = smem_u32(smem_raw);
    const int tid = threadIdx.x, lane = tid & 31;
    const int warp = __shfl_sync(0xffffffffu, tid >> 5, 0);
    const unsigned rank = blockIdx.x & 1;
    int m, j;
    {
        const int t = (int)(blockIdx.x >> 1) - 4, u = t - 32, r7 = (u * 37) >> 8;
        const int gp = t < 32 ? (t & 7) - 1 : u - 7 * r7;
        j = t < 0 ? t + 8 : (t < 32 ? t >> 3 : 4 + r7);
        m = ((t < 0 || gp < 0) ? 14 : 2 * gp) + rank;
        if (t >= 60) { m = 16; j = blockIdx.x - 128; }
    }
    const unsigned role = m * 8 + j;
    const bool helper = m == 16;

    TL(0, tid == 0); TLG(0, tid == 0);
    float* const acc_j = g_acc + j * ACC_SIZE;
    if ((warp & ~1) == 8 && elect_one()) {
        const uint32_t bar = sb + (warp == 8 ? BAR_FULLB : BAR_FULLA);
#pragma unroll
        for (int i = 0; i < 8; i++) if (i < NB || warp == 9) mbar_init(bar + 8 * i, 1);
        if (!helper) {
#pragma unroll 1
            for (int i = 0; i < NPRE; i++) {
                mbar_expect_tx(bar + 8 * i, SLOT);
                if (warp == 8) {
                    tma2d(sb + OFF_B + i * SLOT, &P.twq, bar + 8 * i, DM + 64 * j, 64 * i);
                    tma2d(sb + OFF_B + i * SLOT + 8192, &P.twq, bar + 8 * i, 2 * DM + 64 * j, 64 * i);
                } else {
                    tma2d(sb + OFF_A + i * SLOT, &P.tx, bar + 8 * i, 64 * i, 128 * m);
                }
            }
        }
    }
    __syncwarp();

    if (warp >= 8) {
        asm volatile("setmaxnreg.dec.sync.aligned.u32 72;");
        if (elect_one()) {
            if (warp < 10) {
            } else if (warp == 10) {
#pragma unroll
                for (int i = 0; i < 20; i++) mbar_init(sb + BAR_CS1 + 8 * i, i >= 12 ? 1 : (i < 2 || i >= 8 ? 64 : (i < 4 ? 32 : 8)));
                trap_if_gt(sb & 1023, 0);
            } else {
#pragma unroll
                for (int i = 0; i < 14; i++) mbar_init(sb + (i < 8 ? BAR_EMPTYA : BAR_EMPTYB - 64) + 8 * i, i < 8 ? 8 : 16);
            }
            asm volatile("fence.mbarrier_init.release.cluster;" ::: "memory");
        }
        __syncwarp();
        asm volatile("barrier.cluster.arrive.relaxed.aligned;" ::: "memory");
        const unsigned epoch = ld_relaxed(&g_epoch);
        bar_sync(0, NTHREADS);
        if (helper) {
            if (elect_one()) {
#pragma unroll 1
                for (int i = warp - 8; i < 72; i += 4) {
                    const uint32_t full = sb + BAR_FULLA + 8 * (i & 7), dst = sb + OFF_A + (i & 7) * SLOT;
                    const int n = i >> 1, jj = 2 * j + (i & 1);
                    const bool qkv = n < 12;
                    const int c0 = qkv ? (n < 8 ? DM + 128 * (n & 4) : 0) + 64 * jj : 176 * jj + 8 * ((n - 12) & ~7);
                    const int r0 = qkv ? 128 * (n & 3) : 64 * ((n - 12) & 7);
                    mbar_wait(sb + BAR_EMPTYA + 8 * (i & 7), ((i >> 3) & 1) ^ 1);
                    mbar_expect_tx(full, SLOT);
                    tma2d(dst, qkv ? &P.twq : &P.twg, full, c0, r0);
                    tma2d(dst + 8192, qkv ? &P.twq : &P.twu, full, c0, qkv ? r0 + 64 : r0);
                }
                prefetch_l2(P.wd + (size_t)(4 * j + warp - 8) * 44032, 88064);
            }
            return;
        }
        if (warp == 8) {
            asm volatile("barrier.cluster.wait.aligned;" ::: "memory");
            if (elect_one()) {
                if (m >= 6)
                    asm volatile("cp.async.bulk.prefetch.tensor.2d.L2.global [%0, {%1, %2}];" ::"l"(&P.twq), "r"(DM + DM * (m & 1) + 64 * j), "r"(64 * (m >> 1)) : "memory");
                if (j >= 3)
                    asm volatile("cp.async.bulk.prefetch.tensor.2d.L2.global [%0, {%1, %2}];" ::"l"(&P.tx), "r"(64 * j), "r"(128 * m) : "memory");
                Ring r{NPRE, 0};
                const uint32_t dst = sb + OFF_B + rank * 8192;
#define B_LOADN(TM, C0, R0, NB_)                                                                                \
        mbar_waitc(sb + BAR_EMPTYB + 8 * r.slot, r.phase ^ 1);                                              \
        mbar_expect_tx(sb + BAR_FULLB + 8 * r.slot, NB_);                                                   \
        tma2d_mc(dst + r.slot * SLOT, TM, sb + BAR_FULLB + 8 * r.slot, C0, R0);
#define B_LOAD(TM, C0, R0) B_LOADN(TM, C0, R0, SLOT)
#pragma unroll 1
                for (int i = NPRE; i < 8; i++) {
                    if (i >= AHEAD && i < 6) mbar_waitc(sb + BAR_FULLB + 8 * (i - AHEAD), 0);
                    B_LOAD(&P.twq, DM + DM * rank + 64 * j, 64 * i)
                    r.adv();
                }
#pragma unroll 1
                for (int i = 8; i < 18; i++) {
                    if (i == 9 || i == 10) {
                        mbar_waitc(sb + BAR_EMPTYB + 8 * r.slot, r.phase ^ 1);
                        mbar_arrive(sb + BAR_FULLB + 8 * r.slot);
                    } else {
                        const int e = 2 * (i - 14) + rank, b = (i == 8 ? 0 : i - 10) ^ (i < 12 && j < 2);
                        B_LOAD(i < 14 ? &P.twq : &P.two, 64 * j, 64 * (i < 14 ? 2 * b + rank : KORD(e, j)))
                    }
                    r.adv();
                }
#pragma unroll 1
                for (int i = 0; i < 24; i++) {
                    B_LOAD(&P.twg + rank, 176 * j + 8 * (i & ~7), 64 * (i < 8 ? KORD(i, j) : i & 7))
                    r.adv5();
                }
#pragma unroll 1
                for (int i = 0; i < 12; i++) {
                    B_LOADN(&P.twd + (i >> 3), 64 * j, 176 * (2 * (i & 3) + rank) + 64 * (i >> 2), i < 8 ? SLOT : 12288)
                    r.adv5();
                }
            }
            return;
        }
        if (warp == 9) {
            if (elect_one()) {
#pragma unroll 1
                for (int i = NPRE; i < 8; i++) {
                    if (i >= AHEADA) mbar_wait(sb + BAR_FULLA + 8 * (i - AHEADA), 0);
                    mbar_expect_tx(sb + BAR_FULLA + 8 * i, SLOT);
                    tma2d(sb + OFF_A + i * SLOT, &P.tx, sb + BAR_FULLA + 8 * i, 64 * i, 128 * m);
                }
#pragma unroll 1
                for (int i = 2; i < 8; i++) prefetch_tmap(&P.tx + i);
                mbar_wait(sb + BAR_KVR, 0);
#pragma unroll 1
                for (int r = 0; r < 4; r++) {
                    const uint4* src = g_act + ((r >> 1) * 128 + m * 8) * 1024 + (r & 1) * 512;
                    const uint32_t bar = sb + ((r & 1) ? BAR_FULLH : BAR_FULLA), dst = sb + OFF_A + (r & 1) * 8192;
                    wait_count(g_flag + (m * 7 + r) * 32, epoch * 32);
                    if (r == 1) mbar_wait(sb + BAR_KVW, 1);
                    TL(64 + r, true);
#pragma unroll 1
                    for (int t = 0; t < 8; t++) {
                        if (t == j) continue;
                        mbar_expect_tx(bar + 8 * t, 8192);
                        asm volatile("cp.async.bulk.shared::cluster.global.mbarrier::complete_tx::bytes [%0], [%1], %2, [%3];"
                                     ::"r"(dst + t * SLOT), "l"(src + t * 1024), "r"(8192), "r"(bar + 8 * t) : "memory");
                    }
                }
                unsigned nf = 0;
                mbar_wait(sb + BAR_EMPTYA + 8 * PF_DELAY, 0);
#pragma unroll 1
                for (int c = 0; c < 3; c++) {
                    const uint32_t bytes = c == 2 ? 12288 : SLOT;
                    const uint4* src = g_act + ((2 + c) * 128 + m * 8) * 1024;
                    const unsigned* fl = g_flag + (m * 7 + 4 + c) * 32;
                    if (nf != epoch * 8) wait_count(fl, epoch * 8);
                    TL(68 + c, true);
#pragma unroll 1
                    for (int t = 0; t < 8; t++) {
                        if (t == 6 && c < 2) nf = readback(fl + 32);
                        mbar_wait(sb + BAR_EMPTYA + 8 * t, c & 1);
                        mbar_expect_tx(sb + BAR_FULLA + 8 * t, bytes);
                        asm volatile("cp.async.bulk.shared::cluster.global.mbarrier::complete_tx::bytes [%0], [%1], %2, [%3];"
                                     ::"r"(sb + OFF_A + t * SLOT), "l"(src + t * 1024), "r"(bytes), "r"(sb + BAR_FULLA + 8 * t) : "memory");
                    }
                }
            }
            return;
        }
        const int a = warp - 10;
        {
            const int row = 16 * j + 8 * a + (lane >> 2);
            const uint32_t ra = sb + OFF_A + row * 128;
            float sh = 0.f, s0 = 0.f, s1 = 0.f, q0 = 0.f, q1 = 0.f;
#pragma unroll 1
            for (int kt = 0; kt < 8; kt++) {
                mbar_wait(sb + BAR_FULLA + 8 * kt, 0);
                if (kt == 0) sh = bf_lo(lds128(ra + ((row & 7) << 4)).x);
#pragma unroll
                for (int i = 0; i < 2; i++) {
                    const uint4 v = lds128(ra + kt * SLOT + (((2 * (lane & 3) + i) ^ (row & 7)) << 4));
                    const uint32_t ww[4] = {v.x, v.y, v.z, v.w};
#pragma unroll
                    for (int e = 0; e < 4; e++) {
                        const float d0 = bf_lo(ww[e]) - sh, d1 = bf_hi(ww[e]) - sh;
                        s0 += d0; q0 = fmaf(d0, d0, q0);
                        s1 += d1; q1 = fmaf(d1, d1, q1);
                    }
                }
            }
            s0 += s1; q0 += q1;
#pragma unroll
            for (int o = 1; o <= 2; o <<= 1) { s0 += __shfl_xor_sync(0xffffffffu, s0, o); q0 += __shfl_xor_sync(0xffffffffu, q0, o); }
            const float md = s0 * (1.f / DM);
            const float rs = rsqrtf(fmaxf(q0 * (1.f / DM) - md * md, 0.f) + 1e-5f);
            st_tagged_if(g_xstat + 2 * (128 * m + row), rs, -(sh + md), epoch, (lane & 3) == 0);
            TL(1, lane == 0 && a == 0);
        }
        const unsigned long long* cs = g_cs + j * 768 + 2 * lane;
        {
            const unsigned long long* xs = g_xstat + 2 * (128 * m + 64 * a + lane);
            uint4 v0, v1, v2;
            uint32_t it = 0;
            __nanosleep(250);
            do {
                v0 = ld_tagged_rlx(xs); v1 = ld_tagged_rlx(xs + 64); v2 = ld_tagged_rlx(cs);
                trap_if_gt(++it, 1u << 22);
            } while (__any_sync(0xffffffffu, v0.y != epoch || v0.w != epoch || v1.y != epoch || v1.w != epoch || v2.y != epoch || v2.w != epoch));
            sts64(sb + OFF_XST + (64 * a + lane) * 8, v0.x, v0.z);
            sts64(sb + OFF_XST + (64 * a + 32 + lane) * 8, v1.x, v1.z);
            sts64(sb + OFF_CS1 + 256 + 8 * lane, v2.x, v2.z);
            mbar_arrive(sb + BAR_CS1);
            TL(22 + a, lane == 0);
            fetch_tagged(cs + 128 + 128 * a, sb + OFF_CS1 + 512 - 512 * a + 8 * lane, epoch, 200);
            mbar_arrive(sb + BAR_CSV - 8 * a);
            TL(24 + a, lane == 0);
        }
        {
            mbar_wait(sb + BAR_KVW, 0);
            const float* src = acc_j + 4 * (128 * a + lane);
            float4 v[12];
            uint32_t it = 0;
            bool bad;
            while (__any_sync(0xffffffffu, readback(acc_j + 2048 + 128 * (lane & 7) + 127) != 0x41800000u)) trap_if_gt(++it, 1u << 22);
            TL(19, lane == 0 && a == 0);
            do {
                bad = false;
#pragma unroll
                for (int i = 0; i < 12; i++) v[i] = ld_l2_f4(src + 1024 * (i % 3) + 128 * (i / 3));
#pragma unroll
                for (int i = 0; i < 12; i++) bad |= v[i].w != 16.f;
                trap_if_gt(++it, 1u << 22);
            } while (__any_sync(0xffffffffu, bad));
            TL(14, lane == 0 && a == 0);
            const uint32_t d0 = sb + OFF_A + (j < 2 ? 2 * SLOT : 0) + 8192 + (64 * a + (lane >> 2)) * 48;
            const uint32_t d = d0 + (lane & 3) * 4, dz = d0 + (lane & 1) * 384 + 32 + (lane & 2) * 4;
#pragma unroll
            for (int u = 0; u < 4; u++) {
                sts32(d + 768 * u, pack_bf16(v[3 * u].x, v[3 * u].y));
                sts32(d + 768 * u + 384, pack_bf16(v[3 * u].z, v[3 * u + 1].z));
                sts32(d + 768 * u + 16, pack_bf16(v[3 * u + 1].x, v[3 * u + 1].y));
                sts32(d + 768 * u + 400, pack_bf16(v[3 * u + 2].x, v[3 * u + 2].y));
                const uint32_t z2 = pack_bf16(v[3 * u + 2].z, v[3 * u + 2].z);
                sts64(dz + 768 * u, z2, z2);
            }
            mbar_arrive(sb + BAR_KVR);
        }
#pragma unroll 1
        for (int c = 0; c < 3; c++) {
            fetch_tagged(cs + 384 + 128 * c + 64 * a, sb + OFF_CS3 + (32 * c + lane) * 16 + 8 * a, epoch, 1000);
            mbar_arrive(sb + BAR_CSG + 8 * c);
        }
        {
            uint32_t it = 0;
            while (__any_sync(0xffffffffu, (int)(readback(g_flag + (m * 7 + 2 + (lane & 1)) * 32) - epoch * 32) < 0)) {
                __nanosleep(600);
                trap_if_gt(++it, 1u << 22);
            }
#pragma unroll 1
            for (int rr = 0; rr < 2; rr++) {
                const int row = 64 * rr + 32 * a + lane;
                const unsigned long long* hs = g_hstat + (1024 * m + row) * 2;
                uint4 v[8];
                bool bad;
                do {
                    bad = false;
#pragma unroll
                    for (int i = 0; i < 8; i++) v[i] = ld_tagged_rlx(hs + 256 * i);
#pragma unroll
                    for (int i = 0; i < 8; i++) bad |= v[i].y != epoch || v[i].w != epoch;
                    trap_if_gt(++it, 1u << 22);
                } while (__any_sync(0xffffffffu, bad));
                float mean = 0.f;
#pragma unroll
                for (int i = 0; i < 8; i++) mean += __uint_as_float(v[i].x);
                mean *= 0.125f;
                float m2 = 0.f, dv = 0.f;
#pragma unroll
                for (int i = 0; i < 8; i++) { const float d = __uint_as_float(v[i].x) - mean; m2 += __uint_as_float(v[i].z); dv = fmaf(d, d, dv); }
                sts_f2(sb + OFF_CS1 + row * 8, -mean, rcp(fmaf(dv, 64.f, m2) * (1.f / DM) + 1e-5f));
            }
        }
        mbar_arrive(sb + BAR_CS3);
#pragma unroll 1
        for (int c = a; c < 3; c += 2) {
            mbar_wait(sb + BAR_STG + 8 * c, 0);
            if (elect_one()) {
                asm volatile("cp.async.bulk.global.shared::cta.bulk_group [%0], [%1], %2;" ::"l"(g_act + ((2 + c) * 128 + role) * 1024), "r"(sb + OFF_B + 4 * SLOT), "r"(c == 2 ? 12288 : SLOT) : "memory");
                asm volatile("cp.async.bulk.commit_group;" ::: "memory");
                asm volatile("cp.async.bulk.wait_group.read 0;" ::: "memory");
                mbar_arrive(sb + BAR_FULLB + 8 * 4);
                asm volatile("cp.async.bulk.wait_group 0;" ::: "memory");
            }
            __syncwarp();
            TL(60 + c, lane == 0);
            uint32_t ack = 0;
            const uint4* rb = g_act + ((2 + c) * 128 + role) * 1024 + lane * 8;
#pragma unroll
            for (int i = 0; i < 4; i++) ack |= readback(rb + (i == 3 && c == 2 ? 0 : 256 * i));
            signal_after(g_flag + (m * 7 + 4 + c) * 32, ack, P.zero, lane == 0);
            TL(54 + c, lane == 0);
        }
        return;
    }
    const unsigned epoch = ld_relaxed(&g_epoch);
    uint32_t wraw[16];
    if (!helper) {
        const uint32_t* wp = reinterpret_cast<const uint32_t*>(P.wphi) + (4 * j) * 128 + (lane & 3) * 16 + (lane >> 2);
#pragma unroll
        for (int i = 0; i < 16; i++)
            asm volatile("ld.global.nc.u32 %0, [%1];" : "=r"(wraw[i]) : "l"(wp + (i >> 2) * 128 + ((i >> 1) & 1) * 64 + (i & 1) * 8));
    }
    asm volatile("barrier.cluster.arrive.relaxed.aligned;" ::: "memory");
    asm volatile("setmaxnreg.inc.sync.aligned.u32 216;");
    bar_sync(0, NTHREADS);
    if (helper) {
        const int w = warp >> 2;
        sts64(sb + OFF_B + 8 * tid, 0x3f803f80u, 0x3f803f80u);
        fence_async_smem();
        uint32_t zack[6];
        {
            float* z = g_acc + 2 * j * ACC_SIZE + 4 * tid;
#pragma unroll
            for (int u = 0; u < 6; u++) stg128(z + 1024 * u, 0, 0, 0, 0);
#pragma unroll
            for (int u = 0; u < 6; u++) zack[u] = readback(z + 1024 * u);
        }
        bar_sync(1, 256);
        float acc[8];
        int i = w;
#pragma unroll 1
        for (int job = 0; job < 6; job++) {
            const int n = job < 3 ? 4 : 8;
#pragma unroll 1
            for (int t = 0; t < n; t++, i += 2) {
                mbar_waitc(sb + BAR_FULLA + 8 * (i & 7), (i >> 3) & 1);
                const desc_t da = desc_lo(sb + OFF_A) + (i & 7) * (SLOT >> 4);
                wg_fence();
#pragma unroll
                for (int k = 0; k < 8; k++) wgmma_n8_tt(acc + (k & 4), da + 128 * k, desc_lo(sb + OFF_B), (t | (k & 3)) != 0);
                wg_commit();
                wg_wait<0>();
                mbar_arrive_n_if(sb + BAR_EMPTYA + 8 * (i & 7), 2, lane == 0);
            }
            fence_acc<8>(acc);
            if (job == 1) {
                asm volatile("{.reg .pred p; .reg .b32 t; lop3.b32 t, %0, %1, %2, 0xfe; lop3.b32 t, t, %3, %4, 0xfe; or.b32 t, t, %5; setp.ne.u32 p, t, 0; @p trap;}"
                             ::"r"(zack[0]), "r"(zack[1]), "r"(zack[2]), "r"(zack[3]), "r"(zack[4]), "r"(zack[5]));
                bar_sync(1, 256);
            }
            const int q = lane & 3;
            const float lo = (q & 1) ? acc[2] : acc[0], hi = (q & 1) ? acc[6] : acc[4];
            const float v = job < 3 ? lo + hi : ((q & 2) ? hi : lo);
            unsigned long long* dst = g_cs + ((2 * j + w) * 6 + job) * 128 + (q >> 1) * 64 + 16 * (warp & 3) + 8 * (q & 1) + (lane >> 2);
            asm volatile("st.relaxed.gpu.global.b64 [%0], %1;" ::"l"(dst), "l"(((unsigned long long)epoch << 32) | __float_as_uint(v)) : "memory");
        }
        return;
    }
    {
        const int w = warp >> 2, wv = warp & 3, g = lane >> 2, q = lane & 3;
        const uint32_t sa = sb + OFF_A + w * 8192;
        const desc_t dA = desc_lo(sa), dB = desc_lo(sb + OFF_B);
        unsigned* const flag_m = g_flag + (m * 7 + w) * 32;
        const uint32_t fullh = sb + (w ? BAR_FULLH : BAR_FULLA);
        const bool l0 = lane == 0, l2 = lane < 2;
        const uint32_t eb = mapa(sb + BAR_EMPTYB, lane & 1);
        asm volatile("barrier.cluster.wait.aligned;" ::: "memory");
        Ring rg{0, 0};
        int prev = 0;

        uint32_t wb[16];
        constexpr float L2E = 1.4426950408889634f;
        const int ch = lane >> 4, sw = lane & 7;
        const uint32_t lrow = (lane & 15) * 128;
        uint32_t fp[16], fm[16];
        const int vs = j < 2 ? 2 : 0;
        {
            float acc[64];
#pragma unroll 1
            for (int kt = 0; kt < 8; kt++) {
                mbar_waitc(sb + BAR_FULLA + 8 * kt, 0);
                mbar_waitc(sb + BAR_FULLB + 8 * rg.slot, rg.phase);
                const desc_t da = dA + kt * (SLOT >> 4), db = dB + rg.slot * (SLOT >> 4);
                wg_fence();
#pragma unroll
                for (int k = 0; k < 4; k++) wgmma_n128(acc, da + 2 * k, db + 128 * k, (kt | k) != 0);
                wg_commit();
                wg_wait<1>();
                mbar_arrive_cl_if(eb + 8 * prev, l2 && kt > 0);
                prev = rg.slot; rg.adv();
            }
#pragma unroll
            for (int i = 0; i < 8; i++) {
                wb[(i >> 1) * 4 + (i & 1)] = __byte_perm(wraw[2 * i], wraw[2 * i + 1], 0x5410);
                wb[(i >> 1) * 4 + 2 + (i & 1)] = __byte_perm(wraw[2 * i], wraw[2 * i + 1], 0x7632);
            }
            uint32_t a[16];
            float accq[32];
            mbar_waitc(sb + BAR_FULLB + 8 * 2, 1);
            wg_fence();
#pragma unroll
            for (int k = 0; k < 8; k++) wgmma_n64(accq, dA + (vs + (k >> 2)) * (SLOT >> 4) + (k & 3) * 2, dB + 2 * (SLOT >> 4) + 128 * k, k != 0);
            wg_commit();
            wg_wait<1>();
            fence_acc<64>(acc);
            mbar_arrive_cl_if(eb + 8 * prev, l2);
            TL(17, tid == 0);
            mbar_waitc(sb + BAR_CS1, 0);
            const float2 s0 = lds_f2(sb + OFF_XST + (16 * warp + g) * 8), s1 = lds_f2(sb + OFF_XST + (16 * warp + g + 8) * 8);
            wg_wait<0>();
            fence_acc<32>(accq);
            mbar_arrive_cl_if(eb + 8 * 2, l2);
            TL(2, tid == 0);
            const uint32_t st = sb + OFF_B + warp * 2048 + lrow;
#pragma unroll
            for (int hh = 0; hh < 4; hh++)
                ln_frag<false>(acc + 8 * hh, sb + OFF_CS1 + (64 + 16 * hh + 2 * q) * 4, 0.f, s0.y, 0.f, s1.y, a + 4 * hh);
#pragma unroll 1
            for (int it = 0; it < 2; it++) {
                feature_maps(a, wb, s0.x * L2E, s1.x * L2E, fp, fm);
                if (it == 0) {
                    mbar_waitc(sb + BAR_FULLB + 8 * 3, 1); mbar_waitc(sb + BAR_FULLB + 8 * 4, 1);
                    mbar_waitc(sb + BAR_CSV, 0);
                    const uint32_t sv = sb + OFF_A + vs * SLOT + warp * 2048 + lrow;
#pragma unroll
                    for (int hh = 0; hh < 4; hh++) {
                        stsm4(st + (3 + (hh >> 1)) * SLOT + (((4 * (hh & 1) + ch) ^ sw) << 4), fp[4 * hh], fp[4 * hh + 1], fp[4 * hh + 2], fp[4 * hh + 3]);
                        stsm4(st + (3 + (hh >> 1)) * SLOT + (((4 * (hh & 1) + 2 + ch) ^ sw) << 4), fm[4 * hh], fm[4 * hh + 1], fm[4 * hh + 2], fm[4 * hh + 3]);
                        ln_frag<true>(acc + 32 + 8 * hh, sb + OFF_CS1 + (128 + 16 * hh + 2 * q) * 4, s0.x, s0.y, s1.x, s1.y, a);
                        stsm4(sv + (hh >> 1) * SLOT + (((2 * (hh & 1) + ch) ^ sw) << 4), a[0], a[1], a[2], a[3]);
                    }
                    stsm4(sv + ch * SLOT + ((4 ^ sw) << 4), 0x3f803f80u, 0x3f803f80u, 0x3f803f80u, 0x3f803f80u);
                    fence_async_smem();
                    bar_sync(1, 256);
                    float kvd[20];
                    wg_fence();
#pragma unroll
                    for (int k = 0; k < 8; k++)
                        wgmma_n40_tt(kvd, dB + (3 + w) * (SLOT >> 4) + 128 * k, desc_lo(sb + OFF_A) + (vs + w) * (SLOT >> 4) + 128 * k, k != 0);
                    wg_commit();
                    wg_wait<0>();
                    fence_acc<20>(kvd);
                    mbar_arrive_cl_if(eb + 8 * (3 + (lane >> 1)), lane < 4);
                    const bool h1 = wv >= 2;
                    float* kvp = acc_j + 4 * tid;
                    red_f32x4(kvp, h1 ? kvd[8] : kvd[0], h1 ? kvd[9] : kvd[1], h1 ? kvd[10] : kvd[2], 1.f);
                    red_f32x4(kvp + 1024, h1 ? kvd[12] : kvd[4], h1 ? kvd[13] : kvd[5], h1 ? kvd[11] : kvd[3], 1.f);
                    red_f32x4(kvp + 2048, h1 ? kvd[14] : kvd[6], h1 ? kvd[15] : kvd[7], (q & 1) ? kvd[18] : kvd[16], 1.f);
                    mbar_arrive_if(sb + BAR_KVW, l0);
                    TL(3, tid == 0);
                    if (w) bar_sync(5, 256);
#pragma unroll 1
                    for (int b = 1; b < 4; b++) {
                        const int slot = b == 1 ? 5 : b - 2;
                        mbar_waitc(sb + BAR_FULLB + 8 * slot, b == 1);
                        const desc_t da = dA + (b == 1 ? 2 - vs : 2 * b) * (SLOT >> 4), db = dB + slot * (SLOT >> 4);
                        wg_fence();
#pragma unroll
                        for (int k = 0; k < 8; k++) wgmma_n64(accq, da + (k >> 2) * (SLOT >> 4) + (k & 3) * 2, db + 128 * k, 1);
                        wg_commit();
                    }
                    if (!w) asm volatile("bar.arrive 5, 256;" ::: "memory");
                    mbar_waitc(sb + BAR_CSQ, 0);
                    wg_wait<0>();
                    fence_acc<32>(accq);
                    mbar_arrive_cl_if(eb + 8 * ((5 + (lane >> 1)) % 6), lane < 6);
                    TL(4, tid == 0);
#pragma unroll
                    for (int hh = 0; hh < 4; hh++)
                        ln_frag<false>(accq + 8 * hh, sb + OFF_CS1 + (16 * hh + 2 * q) * 4, 0.f, s0.y, 0.f, s1.y, a + 4 * hh);
                }
            }
        }
        uint32_t res_lo[8], res_hi[8], ack[4];
        const uint32_t own_rows = sb + OFF_A + j * SLOT + warp * 2048;
#pragma unroll
        for (int b = 0; b < 4; b++)
            ldsm4(own_rows + lrow + (((2 * b + ch) ^ sw) << 4), res_lo[2 * b], res_hi[2 * b], res_lo[2 * b + 1], res_hi[2 * b + 1]);
        TL(5, tid == 0); TL(26, tid == 128);
        mbar_waitc(sb + BAR_KVR, 0);
        TL(6, tid == 0);
        {
            const uint32_t kvs = sb + OFF_A + vs * SLOT + 8192;
            uint32_t o_lo[8], o_hi[8];
#pragma unroll
            for (int hh = 0; hh < 4; hh++) {
                uint32_t b[8], zb[4];
                const uint32_t base = kvs + hh * 32 * 48;
                ldsm4t(base + (lane & 15) * 48 + (lane >> 4) * 16, b[0], b[1], b[2], b[3]);
                ldsm4t(base + (16 + (lane & 15)) * 48 + (lane >> 4) * 16, b[4], b[5], b[6], b[7]);
                ldsm4t(base + lane * 48 + 32, zb[0], zb[1], zb[2], zb[3]);
                float n0[4], n1[4], dn[4];
                mma16816_z(n0, fp + 4 * hh, b[0], b[1]); mma16816_z(n1, fp + 4 * hh, b[2], b[3]); mma16816_z(dn, fp + 4 * hh, zb[0], zb[1]);
                mma16816(n0, fm + 4 * hh, b[4], b[5]); mma16816(n1, fm + 4 * hh, b[6], b[7]); mma16816(dn, fm + 4 * hh, zb[2], zb[3]);
                const float i0 = rcp(dn[0] + 1e-6f), i1 = rcp(dn[2] + 1e-6f);
                o_lo[2 * hh] = pack_bf16(n0[0] * i0, n0[1] * i0); o_hi[2 * hh] = pack_bf16(n0[2] * i1, n0[3] * i1);
                o_lo[2 * hh + 1] = pack_bf16(n1[0] * i0, n1[1] * i0); o_hi[2 * hh + 1] = pack_bf16(n1[2] * i1, n1[3] * i1);
            }
            __syncwarp();
            mbar_arrive_if(sb + BAR_KVW, l0);
            rg.slot = 2; rg.phase = 0;
            store_tile(own_rows, g_act + role * 1024 + warp * 128 + lane, o_lo, o_hi, lane, ack);
            TL(7, tid == 0); TL(27, tid == 128);
        }
        float acch[32];
        {
            float* acc = acch;
#pragma unroll
            for (int t = 0; t < 8; t++) {
                acc[4 * t] = bf_lo(res_lo[t]); acc[4 * t + 1] = bf_hi(res_lo[t]);
                acc[4 * t + 2] = bf_lo(res_hi[t]); acc[4 * t + 3] = bf_hi(res_hi[t]);
            }
            fence_acc<32>(acc);
#pragma unroll 1
            for (int kp = 0; kp < 4; kp++) {
                mbar_waitc(sb + BAR_FULLB + 8 * rg.slot, rg.phase);
#pragma unroll
                for (int hf = 0; hf < 2; hf++) {
                    const int i = 2 * kp + hf, kt = KORD(i, j);
                    mbar_waitc(fullh + 8 * kt, (i != 0) ^ w);
                    TL(8, i == 1 && tid == 0);
                    const desc_t da = dA + kt * (SLOT >> 4), db = dB + rg.slot * (SLOT >> 4);
                    wg_fence();
#pragma unroll
                    for (int k = 0; k < 4; k++) wgmma_n64(acc, da + 2 * k, db + (hf * 4 + k) * 128, 1);
                    wg_commit();
                    wg_wait<1>();
                    if (hf == 0) {
                        mbar_arrive_cl_if(eb + 8 * prev, l2 && i > 0);
                        if (i == 0) { signal_late(flag_m, ack, P.zero, l0); TL(20, tid == 0); }
                    }
                }
                prev = rg.slot; rg.adv();
            }
            wg_wait<0>();
            fence_acc<32>(acc);
            mbar_arrive_cl_if(eb + 8 * prev, l2);
            TL(9, tid == 0); TL(29, tid == 128);
#pragma unroll
            for (int t = 0; t < 8; t++) {
                res_lo[t] = pack_bf16(acc[4 * t], acc[4 * t + 1]);
                res_hi[t] = pack_bf16(acc[4 * t + 2], acc[4 * t + 3]);
            }
            store_tile(own_rows, g_act + (128 + role) * 1024 + warp * 128 + lane, res_lo, res_hi, lane, ack);
            TL(10, tid == 0);
        }
        float acc0[64], acc1[64], acc2[56], nm0, nm1;
        float4 cs[8];
        uint32_t hr[16];
#define P3_GROUP(MMA, ACC, KT)                                                                              \
        mbar_waitc(sb + BAR_FULLB + 8 * rg.slot, rg.phase);                                                 \
        {                                                                                                   \
            const desc_t da = dA + (KT) * (SLOT >> 4), db = dB + rg.slot * (SLOT >> 4);                     \
            wg_fence();                                                                                     \
            _Pragma("unroll") for (int k = 0; k < 4; k++) MMA(ACC, da + 2 * k, db + 128 * k, (i | k) != 0); \
            wg_commit();                                                                                    \
        }
#define P3_CS(C, NT)    \
        _Pragma("unroll") for (int t = 0; t < (NT); t++) lds_f4_if(cs[t], sb + OFF_CS3 + q * 16 + 512 * (C) + 64 * t, i == t);
#define P3_EPI2(C, ACC)                                                                                     \
        if (i == 0) {                                                                                       \
            fence_acc<64>(ACC);                                                                             \
            if (C) mbar_waitc(sb + BAR_FULLB + 8 * 4, 1);                                                   \
            hh_stage2<0, 2>(ACC, cs, nm0, nm1, stg, lane);                                                  \
            mbar_waitc(sb + BAR_CSG + 8 * (C) + 8, 0);                                                      \
        }                                                                                                   \
        if (i == 1) {                                                                                       \
            hh_stage2<2, 4>(ACC, cs, nm0, nm1, stg, lane);                                                  \
            fence_async_smem();                                                                             \
            __syncwarp();                                                                                   \
            mbar_arrive_if(sb + BAR_STG + 8 * (C), l0);                                                     \
        }
#define P3_EPI(C, ACC, N, NTP)                                                                              \
        fence_acc<N>(ACC);                                                                                  \
        TL(11 + (C), tid == 0);                                                                             \
        hh_stage<NTP>(ACC, cs, nm0, nm1, sb + OFF_B + 4 * SLOT + warp * 2048, lane);                        \
        mbar_arrive_if(sb + BAR_STG + 8 * (C), l0);                                                         \
        TL(50 + (C), tid == 0);
        const uint32_t stg = sb + OFF_B + 4 * SLOT + warp * 2048;
        const uint32_t blk = ((lane & 7) + (lane >> 4) * 8) * 128 + (((2 * wv + ((lane >> 3) & 1)) ^ (lane & 7)) << 4);
#pragma unroll 1
        for (int i = 0; i < 8; i++) {
            const int kt = KORD(i, j);
            mbar_waitc(fullh + 8 * kt, w);
            TL(44 + w, (tid & 127) == 0 && i == 1);
            P3_GROUP(wgmma_n128, acc0, kt)
            if (i == 7) {
                mbar_waitc(sb + BAR_CS3, 0);
                nm0 = lds_f2(sb + OFF_CS1 + (16 * warp + g) * 8).x; nm1 = lds_f2(sb + OFF_CS1 + (16 * warp + g + 8) * 8).x;
            }
            wg_wait<1>();
            mbar_arrive_cl_if(eb + 8 * prev, l2 && i > 0);
            if (i == 0) {
                signal_late(flag_m + 64, ack, P.zero, l0);
                TL(21, tid == 0);
                {
                    fence_acc<32>(acch);
                    const float* acc = acch;
                    float s0 = 0.f, s1 = 0.f;
#pragma unroll
                    for (int t = 0; t < 8; t++) { s0 += acc[4 * t] + acc[4 * t + 1]; s1 += acc[4 * t + 2] + acc[4 * t + 3]; }
            s0 += __shfl_xor_sync(0xffffffffu, s0, 1); s1 += __shfl_xor_sync(0xffffffffu, s1, 1);
            s0 += __shfl_xor_sync(0xffffffffu, s0, 2); s1 += __shfl_xor_sync(0xffffffffu, s1, 2);
            const float mu0 = s0 * (1.f / 64), mu1 = s1 * (1.f / 64);
            float q0 = 0.f, q1 = 0.f;
#pragma unroll
            for (int t = 0; t < 8; t++) {
                float d;
                d = acc[4 * t] - mu0; q0 = fmaf(d, d, q0);
                d = acc[4 * t + 1] - mu0; q0 = fmaf(d, d, q0);
                d = acc[4 * t + 2] - mu1; q1 = fmaf(d, d, q1);
                d = acc[4 * t + 3] - mu1; q1 = fmaf(d, d, q1);
            }
            q0 += __shfl_xor_sync(0xffffffffu, q0, 1); q1 += __shfl_xor_sync(0xffffffffu, q1, 1);
            q0 += __shfl_xor_sync(0xffffffffu, q0, 2); q1 += __shfl_xor_sync(0xffffffffu, q1, 2);
            st_tagged_if(g_hstat + (role * 128 + 16 * warp + g + 8 * (q & 1)) * 2, q ? mu1 : mu0, q ? q1 : q0, epoch, q < 2);
                }
                bar_sync(2 + w, 128);
#pragma unroll
                for (int tp = 0; tp < 4; tp++) ldsm4t(sa + j * SLOT + blk + tp * 2048, hr[4 * tp], hr[4 * tp + 1], hr[4 * tp + 2], hr[4 * tp + 3]);
                mbar_waitc(sb + BAR_CSG, 0);
#pragma unroll
                for (int t = 0; t < 8; t++) cs[t] = lds_f4(sb + OFF_CS3 + q * 16 + 64 * t);
            }
            prev = rg.slot; rg.adv5();
        }
#pragma unroll 1
        for (int i = 0; i < 8; i++) {
            P3_GROUP(wgmma_n128, acc1, i)
            wg_wait<1>();
            mbar_arrive_cl_if(eb + 8 * prev, l2);
            P3_EPI2(0, acc0)
            P3_CS(1, 8)
            prev = rg.slot; rg.adv5();
        }
#pragma unroll 1
        for (int i = 0; i < 8; i++) {
            P3_GROUP(wgmma_n112, acc2, i)
            wg_wait<1>();
            mbar_arrive_cl_if(eb + 8 * prev, l2);
            mbar_arrive_if(sb + BAR_EMPTYA + 8 * ((i + 7) & 7), l0 && i > 0);
            if (i == 0) { mbar_waitc(sb + BAR_FULLB + 8 * 4, 1); P3_EPI(1, acc1, 64, 4) mbar_waitc(sb + BAR_CSG + 16, 0); }
            P3_CS(2, 6)
            prev = rg.slot; rg.adv5();
        }
        mbar_waitc(sb + BAR_FULLB + 8 * 4, 0);
        wg_wait<0>();
        mbar_arrive_cl_if(eb + 8 * prev, l2);
        mbar_arrive_if(sb + BAR_EMPTYA + 8 * 7, l0);
        fence_acc<56>(acc2);
        TL(13, tid == 0);
#pragma unroll
        for (int tp = 0; tp < 3; tp++)
            stsm4(sb + OFF_B + 4 * SLOT + tp * 4096 + warp * 512 + (lane & 15) * 32 + ((ch ^ ((lane >> 2) & 1)) << 4),
                  hh_pair<32>(acc2 + 8 * tp, cs[2 * tp], nm0), hh_pair<32>(acc2 + 8 * tp + 2, cs[2 * tp], nm1),
                  hh_pair<32>(acc2 + 8 * tp + 4, cs[2 * tp + 1], nm0), hh_pair<32>(acc2 + 8 * tp + 6, cs[2 * tp + 1], nm1));
        fence_async_smem();
        __syncwarp();
        mbar_arrive_if(sb + BAR_STG + 16, l0);
        TL(52, tid == 0);
        {
            float acc[64];
            const desc_t dA0 = desc_lo(sb + OFF_A);
#define KT_P4(I, NK, DH, STEP)                                                                                   \
        const int s_ = (2 * (I) + w) & 7;                                                                   \
        mbar_waitc(sb + BAR_FULLB + 8 * rg.slot, rg.phase);                                                 \
        mbar_waitc(sb + BAR_FULLA + 8 * s_, (((I) >> 2) + 1) & 1);                                          \
        const desc_t dh_ = (DH) + s_ * (SLOT >> 4), dw_ = dB + rg.slot * (SLOT >> 4) + w * 512;              \
        wg_fence();                                                                                         \
        _Pragma("unroll") for (int k = 0; k < (NK); k++) wgmma_n128_tn(acc, dw_ + 128 * k, dh_ + (STEP) * k, ((I) | k) != 0); \
        wg_commit();
#pragma unroll 1
            for (int i = 0; i < 8; i++) {
                KT_P4(i, 4, dA0, 2)
#pragma unroll
                for (int t = 0; t < 8; t++) lds_f4_if(cs[t], sb + OFF_CS1 + (64 * w + 8 * t + 2 * q) * 8, i == t);
                wg_wait<0>();
                mbar_arrive_n_if(sb + BAR_EMPTYA + 8 * s_, 2, l0);
                mbar_arrive_cl_if(eb + 8 * rg.slot, l2 && i < 7);
                rg.adv5();
            }
#pragma unroll 1
            for (int i = 8; i < 12; i++) {
                KT_P4(i, 3, dA0 + ((0xC0000010ull - 0x40000040ull) << 32), 256)
                wg_wait<1>();
                rg.adv5();
            }
            wg_wait<0>();
            fence_acc<64>(acc);
            TL(15, tid == 0);
            const uint32_t xch = sb + OFF_A + 2 * SLOT + (tid & 127) * 16;
            if (w) {
#pragma unroll
                for (int t = 0; t < 8; t++) {
                    sts128(xch + SLOT + t * 2048, __float_as_uint(acc[4 * t]), __float_as_uint(acc[4 * t + 1]),
                           __float_as_uint(acc[4 * t + 2]), __float_as_uint(acc[4 * t + 3]));
                }
#pragma unroll
                for (int t = 0; t < 32; t++) acc[t] = acc[32 + t];
            } else {
#pragma unroll
                for (int t = 0; t < 8; t++)
                    sts128(xch + t * 2048, __float_as_uint(acc[32 + 4 * t]), __float_as_uint(acc[33 + 4 * t]),
                           __float_as_uint(acc[34 + 4 * t]), __float_as_uint(acc[35 + 4 * t]));
            }
            bar_sync(1, 256);
            float4 o[8];
#pragma unroll
            for (int t = 0; t < 8; t++) o[t] = lds_f4(xch + (w ^ 1) * SLOT + t * 2048);
            const uint32_t tile = sb + OFF_A + w * SLOT;
#pragma unroll
            for (int t = 0; t < 8; t++) {
                hr[2 * t] = pack_bf16(fmaf(acc[4 * t] + o[t].x, cs[t].y, bf_lo(hr[2 * t])), fmaf(acc[4 * t + 1] + o[t].y, cs[t].w, bf_hi(hr[2 * t])));
                hr[2 * t + 1] = pack_bf16(fmaf(acc[4 * t + 2] + o[t].z, cs[t].y, bf_lo(hr[2 * t + 1])), fmaf(acc[4 * t + 3] + o[t].w, cs[t].w, bf_hi(hr[2 * t + 1])));
            }
#pragma unroll
            for (int tp = 0; tp < 4; tp++) stsm4t(tile + blk + tp * 2048, hr[4 * tp], hr[4 * tp + 1], hr[4 * tp + 2], hr[4 * tp + 3]);
            fence_async_smem();
            bar_sync(2 + w, 128);
            if ((tid & 127) == 0) {
                tma_store2d(&P.tout, tile, 64 * j, 128 * m + 64 * w);
                asm volatile("cp.async.bulk.wait_group.read 0;" ::: "memory");
            }
            if (tid == 0 && role == 0) g_epoch = epoch + 1;
            TL(16, tid == 0); TLG(1, tid == 0);
        }
    }
}

typedef CUresult (*EncodeFn)(CUtensorMap*, CUtensorMapDataType, cuuint32_t, void*, const cuuint64_t*, const cuuint64_t*,
                             const cuuint32_t*, const cuuint32_t*, CUtensorMapInterleave, CUtensorMapSwizzle,
                             CUtensorMapL2promotion, CUtensorMapFloatOOBfill);

static void make_map2d(EncodeFn enc, CUtensorMap* tm, const void* base, uint64_t cols, uint64_t rows, uint64_t pitch_elems,
                       uint32_t box_rows) {
    cuuint64_t gd[2] = {cols, rows};
    cuuint64_t gs[1] = {pitch_elems * 2};
    cuuint32_t bd[2] = {64, box_rows};
    cuuint32_t es[2] = {1, 1};
    enc(tm, CU_TENSOR_MAP_DATA_TYPE_BFLOAT16, 2, const_cast<void*>(base), gd, gs, bd, es, CU_TENSOR_MAP_INTERLEAVE_NONE,
        CU_TENSOR_MAP_SWIZZLE_128B, CU_TENSOR_MAP_L2_PROMOTION_L2_256B, CU_TENSOR_MAP_FLOAT_OOB_FILL_NONE);
}

}

extern "C" void kernel_launch(void* const* d_in, const int* in_sizes, int n_in, void* d_out, int out_size) {
    using namespace hk;
    (void)in_sizes; (void)n_in; (void)out_size;
    static EncodeFn enc = nullptr;
    if (!enc) {
        void* fn = nullptr;
        cudaDriverEntryPointQueryResult qr;
        cudaGetDriverEntryPoint("cuTensorMapEncodeTiled", &fn, cudaEnableDefault, &qr);
        enc = (EncodeFn)fn;
        cudaFuncSetAttribute(fused_kernel, cudaFuncAttributeMaxDynamicSharedMemorySize, SMEM_BYTES);
    }
    Params P;
    const __nv_bfloat16* x = (const __nv_bfloat16*)d_in[0];
    P.x = x;
    P.wqkv = (const __nv_bfloat16*)d_in[1];
    P.wphi = (const __nv_bfloat16*)d_in[2];
    P.wo = (const __nv_bfloat16*)d_in[3];
    P.wg = (const __nv_bfloat16*)d_in[5];
    P.wu = (const __nv_bfloat16*)d_in[6];
    P.wd = (const __nv_bfloat16*)d_in[7];
    P.out = (__nv_bfloat16*)d_out;
    P.zero = 0;
    make_map2d(enc, &P.tx, x, DM, SEQ, DM, 128);
    make_map2d(enc, &P.twq, P.wqkv, 3 * DM, DM, 3 * DM, 64);
    make_map2d(enc, &P.two, P.wo, DM, DM, DM, 64);
    make_map2d(enc, &P.twg, P.wg, FF, DM, FF, 64);
    make_map2d(enc, &P.twu, P.wu, FF, DM, FF, 64);
    make_map2d(enc, &P.twd, P.wd, DM, FF, DM, 64);
    make_map2d(enc, &P.twd48, P.wd, DM, FF, DM, 48);
    make_map2d(enc, &P.tout, d_out, DM, SEQ, DM, 64);
    fused_kernel<<<NCTA, NTHREADS, SMEM_BYTES>>>(P);
}
```

```cpp
#include <cuda_runtime.h>
#include <cuda_bf16.h>
#include <cuda.h>
#include <stdint.h>

namespace hk {

constexpr int SEQ = 2048, DM = 512, FF = 1376;
constexpr int NCTA = 132;
constexpr int NTHREADS = 384;
constexpr uint32_t SLOT = 16384;
constexpr uint32_t OFF_A = 0, OFF_B = 8 * SLOT, OFF_MISC = 14 * SLOT;
constexpr uint32_t BAR_FULLA = OFF_MISC + 0, BAR_EMPTYA = OFF_MISC + 64, BAR_FULLB = OFF_MISC + 128,
                   BAR_EMPTYB = OFF_MISC + 176, BAR_CS1 = OFF_MISC + 224, BAR_CS3 = OFF_MISC + 232,
                   BAR_CSQ = OFF_MISC + 240, BAR_CSV = OFF_MISC + 248,
                   BAR_STG = OFF_MISC + 256,
                   BAR_KVW = OFF_MISC + 280, BAR_KVR = OFF_MISC + 288,
                   BAR_CSG = OFF_MISC + 296,
                   BAR_FULLH = OFF_MISC + 320;
constexpr uint32_t OFF_CS1 = OFF_MISC + 384;
constexpr uint32_t OFF_CS3 = OFF_CS1 + 1024;
constexpr uint32_t OFF_XST = OFF_CS3;
constexpr uint32_t SMEM_BYTES = OFF_CS3 + 1536;
#define KORD(i, j) ((i) == 0 ? (j) : (i) - ((i) <= (j)))
constexpr int NB = 6;
constexpr int NPRE = 3, AHEAD = 3, AHEADA = 5;
constexpr int PF_DELAY = 2;

constexpr int ACC_SIZE = 3 * 256 * 4;

__device__ __align__(1024) uint4 g_act[5 * 128 * 1024];
__device__ __align__(128) unsigned long long g_hstat[SEQ * 16];
__device__ __align__(128) unsigned long long g_xstat[SEQ * 2];
__device__ __align__(128) float g_acc[8 * ACC_SIZE];
__device__ __align__(128) unsigned long long g_cs[8 * 6 * 128];
__device__ __align__(128) unsigned g_flag[16 * 7 * 32];
__device__ unsigned g_epoch = 1;

#define TL(i, pred) do {} while (0)
#define TLG(i, pred) do {} while (0)

struct Params {
    CUtensorMap tx, twq, two, twg, twu, twd, twd48, tout;
    const __nv_bfloat16 *x, *wqkv, *wphi, *wo, *wg, *wu, *wd;
    __nv_bfloat16* out;
    unsigned zero;
};

__device__ __forceinline__ uint32_t smem_u32(const void* p) { return (uint32_t)__cvta_generic_to_shared(p); }
__device__ __forceinline__ void mbar_init(uint32_t bar, uint32_t cnt) {
    asm volatile("mbarrier.init.shared::cta.b64 [%0], %1;" ::"r"(bar), "r"(cnt) : "memory");
}
__device__ __forceinline__ void mbar_expect_tx(uint32_t bar, uint32_t bytes) {
    asm volatile("mbarrier.arrive.expect_tx.shared::cta.b64 _, [%0], %1;" ::"r"(bar), "r"(bytes) : "memory");
}
__device__ __forceinline__ void mbar_arrive(uint32_t bar) {
    asm volatile("mbarrier.arrive.shared::cta.b64 _, [%0];" ::"r"(bar) : "memory");
}
__device__ __forceinline__ void mbar_arrive_if(uint32_t bar, bool pred) {
    asm volatile("{.reg .pred p; setp.ne.u32 p, %1, 0; @p mbarrier.arrive.shared::cta.b64 _, [%0];}" ::"r"(bar), "r"((uint32_t)pred) : "memory");
}
__device__ __forceinline__ void trap_if_gt(uint32_t v, uint32_t lim) {
    asm volatile("{.reg .pred p; setp.gt.u32 p, %0, %1; @p trap;}" ::"r"(v), "r"(lim));
}
__device__ __forceinline__ void mbar_wait(uint32_t bar, uint32_t parity) {
    asm volatile("{\n"
                 ".reg .pred P1, P2;\n"
                 ".reg .u32 c;\n"
                 "mov.u32 c, 0;\n"
                 "LAB_WAIT:\n"
                 "mbarrier.try_wait.parity.shared::cta.b64 P1, [%0], %1;\n"
                 "@P1 bra LAB_DONE;\n"
                 "add.u32 c, c, 1;\n"
                 "setp.gt.u32 P2, c, 1048576;\n"
                 "@P2 trap;\n"
                 "bra LAB_WAIT;\n"
                 "LAB_DONE:\n"
                 "}" ::"r"(bar), "r"(parity) : "memory");
}
__device__ __forceinline__ void mbar_waitc(uint32_t bar, uint32_t parity) {
    asm volatile("{\n"
                 ".reg .pred P1;\n"
                 "LAB_WAIT:\n"
                 "mbarrier.try_wait.parity.shared::cta.b64 P1, [%0], %1;\n"
                 "@!P1 bra LAB_WAIT;\n"
                 "}" ::"r"(bar), "r"(parity) : "memory");
}
__device__ __forceinline__ void tma2d(uint32_t dst, const CUtensorMap* tm, uint32_t bar, int c0, int c1) {
    asm volatile("cp.async.bulk.tensor.2d.shared::cluster.global.mbarrier::complete_tx::bytes [%0], [%1, {%3, %4}], [%2];"
                 ::"r"(dst), "l"(tm), "r"(bar), "r"(c0), "r"(c1) : "memory");
}
__device__ __forceinline__ void tma2d_mc(uint32_t dst, const CUtensorMap* tm, uint32_t bar, int c0, int c1) {
    asm volatile("cp.async.bulk.tensor.2d.shared::cluster.global.mbarrier::complete_tx::bytes.multicast::cluster [%0], [%1, {%3, %4}], [%2], %5;"
                 ::"r"(dst), "l"(tm), "r"(bar), "r"(c0), "r"(c1), "h"((uint16_t)3) : "memory");
}
__device__ __forceinline__ uint32_t mapa(uint32_t addr, uint32_t rank) {
    uint32_t r; asm("mapa.shared::cluster.u32 %0, %1, %2;" : "=r"(r) : "r"(addr), "r"(rank)); return r;
}
__device__ __forceinline__ void mbar_arrive_cl_if(uint32_t cbar, bool pred) {
    asm volatile("{.reg .pred p; setp.ne.u32 p, %1, 0; @p mbarrier.arrive.shared::cluster.b64 _, [%0];}" ::"r"(cbar), "r"((uint32_t)pred) : "memory");
}
__device__ __forceinline__ bool elect_one() {
    uint32_t ok;
    asm volatile("{.reg .pred p; elect.sync _|p, 0xffffffff; selp.u32 %0, 1, 0, p;}" : "=r"(ok));
    return ok;
}
__device__ __forceinline__ void prefetch_tmap(const CUtensorMap* tm) {
    asm volatile("prefetch.tensormap [%0];" ::"l"(tm) : "memory");
}
__device__ __forceinline__ void prefetch_l2(const void* p, uint32_t bytes) {
    asm volatile("cp.async.bulk.prefetch.L2.global [%0], %1;" ::"l"(p), "r"(bytes) : "memory");
}
__device__ __forceinline__ unsigned ld_relaxed(const unsigned* p) {
    unsigned v; asm volatile("ld.relaxed.gpu.global.u32 %0, [%1];" : "=r"(v) : "l"(p)); return v;
}
__device__ __forceinline__ void fence_async_smem() { asm volatile("fence.proxy.async.shared::cta;" ::: "memory"); }
__device__ __forceinline__ uint32_t readback(const void* p) {
    uint32_t v; asm volatile("ld.relaxed.gpu.global.u32 %0, [%1];" : "=r"(v) : "l"(p) : "memory"); return v;
}
__device__ __forceinline__ void wait_count(const unsigned* p, unsigned target) {
    uint32_t it = 0;
    while ((int)(readback(p) - target) < 0) trap_if_gt(++it, 1u << 22);
}
__device__ __forceinline__ void red_f32x4(float* p, float a, float b, float c, float d) {
    asm volatile("red.relaxed.gpu.global.add.v4.f32 [%0], {%1, %2, %3, %4};" ::"l"(p), "f"(a), "f"(b), "f"(c), "f"(d) : "memory");
}
__device__ __forceinline__ float4 ld_l2_f4(const float* p) {
    float4 v;
    asm volatile("ld.relaxed.gpu.global.v4.f32 {%0,%1,%2,%3}, [%4];" : "=f"(v.x), "=f"(v.y), "=f"(v.z), "=f"(v.w) : "l"(p) : "memory");
    return v;
}
__device__ __forceinline__ void stg128(void* p, uint32_t a, uint32_t b, uint32_t c, uint32_t d) {
    asm volatile("st.global.v4.u32 [%0], {%1,%2,%3,%4};" ::"l"(p), "r"(a), "r"(b), "r"(c), "r"(d) : "memory");
}
__device__ __forceinline__ uint4 lds128(uint32_t a) {
    uint4 v;
    asm volatile("ld.shared.v4.u32 {%0,%1,%2,%3}, [%4];" : "=r"(v.x), "=r"(v.y), "=r"(v.z), "=r"(v.w) : "r"(a) : "memory");
    return v;
}
__device__ __forceinline__ float2 lds_f2(uint32_t a) {
    float2 v;
    asm volatile("ld.shared.v2.f32 {%0,%1}, [%2];" : "=f"(v.x), "=f"(v.y) : "r"(a) : "memory");
    return v;
}
__device__ __forceinline__ void sts_f2(uint32_t a, float x, float y) {
    asm volatile("st.shared.v2.f32 [%0], {%1,%2};" ::"r"(a), "f"(x), "f"(y) : "memory");
}
__device__ __forceinline__ void sts64(uint32_t a, uint32_t x, uint32_t y) {
    asm volatile("st.shared.v2.u32 [%0], {%1,%2};" ::"r"(a), "r"(x), "r"(y) : "memory");
}
__device__ __forceinline__ void sts128(uint32_t a, uint32_t x, uint32_t y, uint32_t z, uint32_t w) {
    asm volatile("st.shared.v4.u32 [%0], {%1,%2,%3,%4};" ::"r"(a), "r"(x), "r"(y), "r"(z), "r"(w) : "memory");
}
__device__ __forceinline__ void stsm4(uint32_t a, uint32_t r0, uint32_t r1, uint32_t r2, uint32_t r3) {
    asm volatile("stmatrix.sync.aligned.m8n8.x4.shared.b16 [%0], {%1,%2,%3,%4};" ::"r"(a), "r"(r0), "r"(r1), "r"(r2), "r"(r3) : "memory");
}
__device__ __forceinline__ void stsm4t(uint32_t a, uint32_t r0, uint32_t r1, uint32_t r2, uint32_t r3) {
    asm volatile("stmatrix.sync.aligned.m8n8.x4.trans.shared.b16 [%0], {%1,%2,%3,%4};" ::"r"(a), "r"(r0), "r"(r1), "r"(r2), "r"(r3) : "memory");
}
__device__ __forceinline__ void tma_store2d(const CUtensorMap* tm, uint32_t src, int c0, int c1) {
    asm volatile("cp.async.bulk.tensor.2d.global.shared::cta.bulk_group [%0, {%2, %3}], [%1];" ::"l"(tm), "r"(src), "r"(c0), "r"(c1) : "memory");
    asm volatile("cp.async.bulk.commit_group;" ::: "memory");
}
__device__ __forceinline__ void ldsm4(uint32_t a, uint32_t& r0, uint32_t& r1, uint32_t& r2, uint32_t& r3) {
    asm volatile("ldmatrix.sync.aligned.m8n8.x4.shared.b16 {%0,%1,%2,%3}, [%4];" : "=r"(r0), "=r"(r1), "=r"(r2), "=r"(r3) : "r"(a) : "memory");
}
__device__ __forceinline__ void ldsm4t(uint32_t a, uint32_t& r0, uint32_t& r1, uint32_t& r2, uint32_t& r3) {
    asm volatile("ldmatrix.sync.aligned.m8n8.x4.trans.shared.b16 {%0,%1,%2,%3}, [%4];" : "=r"(r0), "=r"(r1), "=r"(r2), "=r"(r3) : "r"(a) : "memory");
}
__device__ __forceinline__ void mma16816(float* c, const uint32_t* a, uint32_t b0, uint32_t b1) {
    asm("mma.sync.aligned.m16n8k16.row.col.f32.bf16.bf16.f32 {%0,%1,%2,%3}, {%4,%5,%6,%7}, {%8,%9}, {%0,%1,%2,%3};"
                 : "+f"(c[0]), "+f"(c[1]), "+f"(c[2]), "+f"(c[3])
                 : "r"(a[0]), "r"(a[1]), "r"(a[2]), "r"(a[3]), "r"(b0), "r"(b1));
}
__device__ __forceinline__ uint32_t pack_bf16(float lo, float hi) {
    uint32_t r; asm("cvt.rn.bf16x2.f32 %0, %1, %2;" : "=r"(r) : "f"(hi), "f"(lo)); return r;
}
__device__ __forceinline__ float bf_lo(uint32_t w) { return __uint_as_float(w << 16); }
__device__ __forceinline__ float bf_hi(uint32_t w) { return __uint_as_float(w & 0xffff0000u); }
__device__ __forceinline__ float ex2(float x) { float r; asm("ex2.approx.ftz.f32 %0, %1;" : "=f"(r) : "f"(x)); return r; }
__device__ __forceinline__ float rcp(float x) { float r; asm("rcp.approx.ftz.f32 %0, %1;" : "=f"(r) : "f"(x)); return r; }
__device__ __forceinline__ void bar_sync(int id, int n) { asm volatile("bar.sync %0, %1;" ::"r"(id), "r"(n) : "memory"); }

typedef unsigned long long desc_t;
__device__ __forceinline__ desc_t desc_lo(uint32_t addr) { return (desc_t)(((addr & 0x3FFFF) >> 4) | (512u << 16)) | (0x40000040ull << 32); }
__device__ __forceinline__ void wg_fence() { asm volatile("wgmma.fence.sync.aligned;" ::: "memory"); }
__device__ __forceinline__ void wg_commit() { asm volatile("wgmma.commit_group.sync.aligned;" ::: "memory"); }
template <int N> __device__ __forceinline__ void wg_wait() { asm volatile("wgmma.wait_group.sync.aligned %0;" ::"n"(N) : "memory"); }
template <int N> __device__ __forceinline__ void fence_acc(float* d) {
#pragma unroll
    for (int i = 0; i < N; i++) asm volatile("" : "+f"(d[i])::"memory");
}
#define R4(o) "+f"(d[o + 0]), "+f"(d[o + 1]), "+f"(d[o + 2]), "+f"(d[o + 3])
#define R8(o) R4(o), R4(o + 4)
__device__ __forceinline__ void wgmma_n128(float* d, desc_t da, desc_t db, int sc) {
    asm volatile("{.reg .pred p; setp.ne.b32 p, %66, 0;\n"
                 "wgmma.mma_async.sync.aligned.m64n128k16.f32.bf16.bf16 {%0,%1,%2,%3,%4,%5,%6,%7,%8,%9,%10,%11,%12,%13,%14,%15,%16,%17,%18,%19,%20,%21,%22,%23,%24,%25,%26,%27,%28,%29,%30,%31,"
                 "%32,%33,%34,%35,%36,%37,%38,%39,%40,%41,%42,%43,%44,%45,%46,%47,%48,%49,%50,%51,%52,%53,%54,%55,%56,%57,%58,%59,%60,%61,%62,%63}, %64, %65, p, 1, 1, 0, 1;}"
                 : R8(0), R8(8), R8(16), R8(24), R8(32), R8(40), R8(48), R8(56)
                 : "l"(da), "l"(db), "r"(sc));
}
__device__ __forceinline__ void wgmma_n112(float* d, desc_t da, desc_t db, int sc) {
    asm volatile("{.reg .pred p; setp.ne.b32 p, %58, 0;\n"
                 "wgmma.mma_async.sync.aligned.m64n112k16.f32.bf16.bf16 {%0,%1,%2,%3,%4,%5,%6,%7,%8,%9,%10,%11,%12,%13,%14,%15,%16,%17,%18,%19,%20,%21,%22,%23,%24,%25,%26,%27,%28,%29,%30,%31,%32,%33,%34,%35,%36,%37,%38,%39,%40,%41,%42,%43,%44,%45,%46,%47,%48,%49,%50,%51,%52,%53,%54,%55}, %56, %57, p, 1, 1, 0, 1;}"
                 : R8(0), R8(8), R8(16), R8(24), R8(32), R8(40), R8(48)
                 : "l"(da), "l"(db), "r"(sc));
}
__device__ __forceinline__ void wgmma_n128_tn(float* d, desc_t da, desc_t db, int sc) {
    asm volatile("{.reg .pred p; setp.ne.b32 p, %66, 0;\n"
                 "wgmma.mma_async.sync.aligned.m64n128k16.f32.bf16.bf16 {%0,%1,%2,%3,%4,%5,%6,%7,%8,%9,%10,%11,%12,%13,%14,%15,%16,%17,%18,%19,%20,%21,%22,%23,%24,%25,%26,%27,%28,%29,%30,%31,%32,%33,%34,%35,%36,%37,%38,%39,%40,%41,%42,%43,%44,%45,%46,%47,%48,%49,%50,%51,%52,%53,%54,%55,%56,%57,%58,%59,%60,%61,%62,%63}, %64, %65, p, 1, 1, 1, 0;}"
                 : R8(0), R8(8), R8(16), R8(24), R8(32), R8(40), R8(48), R8(56)
                 : "l"(da), "l"(db), "r"(sc));
}
__device__ __forceinline__ void wgmma_n64(float* d, desc_t da, desc_t db, int sc) {
    asm volatile("{.reg .pred p; setp.ne.b32 p, %34, 0;\n"
                 "wgmma.mma_async.sync.aligned.m64n64k16.f32.bf16.bf16 {%0,%1,%2,%3,%4,%5,%6,%7,%8,%9,%10,%11,%12,%13,%14,%15,%16,%17,%18,%19,%20,%21,%22,%23,%24,%25,%26,%27,%28,%29,%30,%31}, %32, %33, p, 1, 1, 0, 1;}"
                 : R8(0), R8(8), R8(16), R8(24)
                 : "l"(da), "l"(db), "r"(sc));
}
__device__ __forceinline__ void wgmma_n40_tt(float* d, desc_t da, desc_t db, int sc) {
    asm volatile("{.reg .pred p; setp.ne.b32 p, %22, 0;\n"
                 "wgmma.mma_async.sync.aligned.m64n40k16.f32.bf16.bf16 {%0,%1,%2,%3,%4,%5,%6,%7,%8,%9,%10,%11,%12,%13,%14,%15,%16,%17,%18,%19}, %20, %21, p, 1, 1, 1, 1;}"
                 : R8(0), R8(8), R4(16)
                 : "l"(da), "l"(db), "r"(sc));
}

__device__ __forceinline__ void wgmma_n8_tt(float* d, desc_t da, desc_t db, int sc) {
    asm volatile("{.reg .pred p; setp.ne.b32 p, %6, 0;\n"
                 "wgmma.mma_async.sync.aligned.m64n8k16.f32.bf16.bf16 {%0,%1,%2,%3}, %4, %5, p, 1, 1, 1, 1;}"
                 : R4(0)
                 : "l"(da), "l"(db), "r"(sc));
}

__device__ __forceinline__ void signal_after(unsigned* cnt, uint32_t ack, uint32_t zero, bool pred) {
    asm volatile("{.reg .pred p; setp.ne.u32 p, %2, 0; @p red.relaxed.gpu.global.add.u32 [%0], %1;}"
                 ::"l"(cnt), "r"((ack & zero) + 1), "r"((uint32_t)pred) : "memory");
}
__device__ __forceinline__ void signal_late(unsigned* cnt, const uint32_t* a, uint32_t zero, bool pred) {
    uint32_t v;
    asm volatile("{.reg .b32 t; lop3.b32 t, %1, %2, %3, 0xfe; or.b32 %0, t, %4;}"
                 : "=r"(v) : "r"(a[0]), "r"(a[1]), "r"(a[2]), "r"(a[3]));
    signal_after(cnt, v, zero, pred);
}
__device__ __forceinline__ void mma16816_z(float* c, const uint32_t* a, uint32_t b0, uint32_t b1) {
    asm("mma.sync.aligned.m16n8k16.row.col.f32.bf16.bf16.f32 {%0,%1,%2,%3}, {%4,%5,%6,%7}, {%8,%9}, {%10,%10,%10,%10};"
                 : "=f"(c[0]), "=f"(c[1]), "=f"(c[2]), "=f"(c[3])
                 : "r"(a[0]), "r"(a[1]), "r"(a[2]), "r"(a[3]), "r"(b0), "r"(b1), "f"(0.f));
}
__device__ __forceinline__ uint32_t max2(uint32_t a, uint32_t b) { uint32_t r; asm("max.bf16x2 %0, %1, %2;" : "=r"(r) : "r"(a), "r"(b)); return r; }
__device__ __forceinline__ uint32_t min2(uint32_t a, uint32_t b) { uint32_t r; asm("min.bf16x2 %0, %1, %2;" : "=r"(r) : "r"(a), "r"(b)); return r; }
__device__ __forceinline__ void mbar_arrive_n_if(uint32_t bar, uint32_t n, bool pred) {
    asm volatile("{.reg .pred p; setp.ne.u32 p, %1, 0; @p mbarrier.arrive.shared::cta.b64 _, [%0], %2;}" ::"r"(bar), "r"((uint32_t)pred), "r"(n) : "memory");
}
__device__ __forceinline__ float4 lds_f4(uint32_t a) {
    float4 v;
    asm volatile("ld.shared.v4.f32 {%0,%1,%2,%3}, [%4];" : "=f"(v.x), "=f"(v.y), "=f"(v.z), "=f"(v.w) : "r"(a) : "memory");
    return v;
}
__device__ __forceinline__ void lds_f4_if(float4& v, uint32_t a, bool pred) {
    asm volatile("{.reg .pred p; setp.ne.u32 p, %5, 0; @p ld.shared.v4.f32 {%0,%1,%2,%3}, [%4];}"
                 : "+f"(v.x), "+f"(v.y), "+f"(v.z), "+f"(v.w) : "r"(a), "r"((uint32_t)pred) : "memory");
}
__device__ __forceinline__ uint4 ld_tagged_rlx(const unsigned long long* p) {
    unsigned long long a, b;
    asm volatile("ld.relaxed.gpu.global.v2.b64 {%0,%1}, [%2];" : "=l"(a), "=l"(b) : "l"(p) : "memory");
    return make_uint4((unsigned)a, (unsigned)(a >> 32), (unsigned)b, (unsigned)(b >> 32));
}
__device__ __forceinline__ void sts32(uint32_t a, uint32_t x) { asm volatile("st.shared.u32 [%0], %1;" ::"r"(a), "r"(x) : "memory"); }
__device__ __forceinline__ void fetch_tagged(const unsigned long long* src, uint32_t dst, unsigned epoch, unsigned ns) {
    uint4 v;
    uint32_t it = 0;
    while (true) {
        v = ld_tagged_rlx(src);
        if (!__any_sync(0xffffffffu, v.y != epoch || v.w != epoch)) break;
        __nanosleep(ns);
        trap_if_gt(++it, 1u << 22);
    }
    sts64(dst, v.x, v.z);
}
__device__ __forceinline__ void st_tagged_if(unsigned long long* p, float a, float b, unsigned tag, bool pred) {
    const unsigned long long t = (unsigned long long)tag << 32;
    asm volatile("{.reg .pred p; setp.ne.u32 p, %3, 0; @p st.relaxed.gpu.global.v2.b64 [%0], {%1,%2};}"
                 ::"l"(p), "l"(t | __float_as_uint(a)), "l"(t | __float_as_uint(b)), "r"((uint32_t)pred) : "memory");
}

__device__ __forceinline__ void store_tile(uint32_t tile_rows, uint4* gdst, const uint32_t* lo, const uint32_t* hi, int lane, uint32_t* ack) {
    const int r = lane & 15;
#pragma unroll
    for (int b = 0; b < 4; b++)
        stsm4(tile_rows + r * 128 + (((2 * b + (lane >> 4)) ^ (r & 7)) << 4), lo[2 * b], hi[2 * b], lo[2 * b + 1], hi[2 * b + 1]);
    fence_async_smem();
    __syncwarp();
#pragma unroll
    for (int i = 0; i < 4; i++) {
        const uint4 v = lds128(tile_rows + i * 512 + lane * 16);
        stg128(gdst + 32 * i, v.x, v.y, v.z, v.w);
    }
#pragma unroll
    for (int i = 0; i < 4; i++) ack[i] = readback(gdst + 32 * i);
}

__device__ __forceinline__ void feature_maps(const uint32_t* a, const uint32_t* wb, float c0, float c1, uint32_t* plus, uint32_t* minus) {
    uint32_t P[16], mx[4], mn[4];
#pragma unroll
    for (int h = 0; h < 4; h++) {
        float p[8];
        mma16816_z(p, a + 4 * h, wb[4 * h], wb[4 * h + 1]);
        mma16816_z(p + 4, a + 4 * h, wb[4 * h + 2], wb[4 * h + 3]);
        P[4 * h] = pack_bf16(p[0], p[2]); P[4 * h + 1] = pack_bf16(p[1], p[3]);
        P[4 * h + 2] = pack_bf16(p[4], p[6]); P[4 * h + 3] = pack_bf16(p[5], p[7]);
        mx[h] = max2(max2(P[4 * h], P[4 * h + 1]), max2(P[4 * h + 2], P[4 * h + 3]));
        mn[h] = min2(min2(P[4 * h], P[4 * h + 1]), min2(P[4 * h + 2], P[4 * h + 3]));
    }
#pragma unroll
    for (int s = 1; s <= 2; s <<= 1) {
        uint32_t tx[4], tn[4];
#pragma unroll
        for (int h = 0; h < 4; h++) { tx[h] = __shfl_xor_sync(0xffffffffu, mx[h], s); tn[h] = __shfl_xor_sync(0xffffffffu, mn[h], s); }
#pragma unroll
        for (int h = 0; h < 4; h++) { mx[h] = max2(mx[h], tx[h]); mn[h] = min2(mn[h], tn[h]); }
    }
#pragma unroll
    for (int h = 0; h < 4; h++) {
        const float mx0 = bf_lo(mx[h]) * c0, mx1 = bf_hi(mx[h]) * c1, mn0 = bf_lo(mn[h]) * c0, mn1 = bf_hi(mn[h]) * c1;
        float ep[8], em[8];
#pragma unroll
        for (int i = 0; i < 8; i++) {
            const bool r1 = (i & 2);
            const uint32_t w = P[4 * h + (i >> 2) * 2 + (i & 1)];
            const float p = r1 ? bf_hi(w) : bf_lo(w);
            ep[i] = ex2(fmaf(p, r1 ? c1 : c0, r1 ? -mx1 : -mx0));
            em[i] = ex2(fmaf(p, r1 ? -c1 : -c0, r1 ? mn1 : mn0));
        }
        float sp[4], sm[4];
        uint32_t tp[4], tm[4];
#pragma unroll
        for (int i = 0; i < 4; i++) { tp[i] = pack_bf16(ep[2 * i], ep[2 * i + 1]); tm[i] = pack_bf16(em[2 * i], em[2 * i + 1]); }
        mma16816_z(sp, tp, 0x3f803f80u, 0x3f803f80u);
        mma16816_z(sm, tm, 0x3f803f80u, 0x3f803f80u);
        const float r0 = rcp(sp[0] * sm[0]), r1 = rcp(sp[2] * sm[2]);
        const float rs[4] = {r0 * sm[0], r1 * sm[2], r0 * sp[0], r1 * sp[2]};
#pragma unroll
        for (int i = 0; i < 4; i++) {
            plus[4 * h + i] = pack_bf16(ep[2 * i] * rs[i & 1], ep[2 * i + 1] * rs[i & 1]);
            minus[4 * h + i] = pack_bf16(em[2 * i] * rs[2 + (i & 1)], em[2 * i + 1] * rs[2 + (i & 1)]);
        }
    }
}

template <bool SCALE>
__device__ __forceinline__ void ln_frag(const float* acc, uint32_t cs_addr, float rs0, float nm0, float rs1, float nm1, uint32_t* a) {
    const float2 c0 = lds_f2(cs_addr), c1 = lds_f2(cs_addr + 32);
    const float s0 = SCALE ? rs0 : 1.f, s1 = SCALE ? rs1 : 1.f;
    a[0] = pack_bf16(fmaf(nm0, c0.x, acc[0]) * s0, fmaf(nm0, c0.y, acc[1]) * s0);
    a[1] = pack_bf16(fmaf(nm1, c0.x, acc[2]) * s1, fmaf(nm1, c0.y, acc[3]) * s1);
    a[2] = pack_bf16(fmaf(nm0, c1.x, acc[4]) * s0, fmaf(nm0, c1.y, acc[5]) * s0);
    a[3] = pack_bf16(fmaf(nm1, c1.x, acc[6]) * s1, fmaf(nm1, c1.y, acc[7]) * s1);
}

template <int UP>
__device__ __forceinline__ uint32_t hh_pair(const float* ag, float4 cs, float nmean) {
    const float g0 = fmaf(nmean, cs.x, ag[0]), g1 = fmaf(nmean, cs.y, ag[1]);
    const float u0 = fmaf(nmean, cs.z, ag[UP]), u1 = fmaf(nmean, cs.w, ag[UP + 1]);
    return pack_bf16(g0 * u0, g1 * u1);
}
template <int NTP>
__device__ __forceinline__ void hh_stage(const float* acc, const float4* cs, float nm0, float nm1, uint32_t stg, int lane) {
#pragma unroll
    for (int tp = 0; tp < NTP; tp++)
        stsm4(stg + (lane & 15) * 128 + (((2 * tp + (lane >> 4)) ^ (lane & 7)) << 4), hh_pair<32>(acc + 8 * tp, cs[2 * tp], nm0),
              hh_pair<32>(acc + 8 * tp + 2, cs[2 * tp], nm1), hh_pair<32>(acc + 8 * tp + 4, cs[2 * tp + 1], nm0),
              hh_pair<32>(acc + 8 * tp + 6, cs[2 * tp + 1], nm1));
    fence_async_smem();
    __syncwarp();
}

template <int TP0, int TP1>
__device__ __forceinline__ void hh_stage2(const float* acc, const float4* cs, float nm0, float nm1, uint32_t stg, int lane) {
#pragma unroll
    for (int tp = TP0; tp < TP1; tp++)
        stsm4(stg + (lane & 15) * 128 + (((2 * tp + (lane >> 4)) ^ (lane & 7)) << 4), hh_pair<32>(acc + 8 * tp, cs[2 * tp], nm0),
              hh_pair<32>(acc + 8 * tp + 2, cs[2 * tp], nm1), hh_pair<32>(acc + 8 * tp + 4, cs[2 * tp + 1], nm0),
              hh_pair<32>(acc + 8 * tp + 6, cs[2 * tp + 1], nm1));
}
struct Ring {
    int slot; uint32_t phase;
    __device__ __forceinline__ void adv() { if (++slot == NB) { slot = 0; phase ^= 1; } }
    __device__ __forceinline__ void adv5() { slot += slot == 3; adv(); }
};

__global__ void __cluster_dims__(2, 1, 1) __launch_bounds__(NTHREADS, 1) fused_kernel(const __grid_constant__ Params P) {
    extern __shared__ __align__(1024) uint8_t smem_raw[];
    const uint32_t sb = smem_u32(smem_raw);
    const int tid = threadIdx.x, lane = tid & 31;
    const int warp = __shfl_sync(0xffffffffu, tid >> 5, 0);
    const unsigned rank = blockIdx.x & 1;
    int m, j;
    {
        const int t = (int)(blockIdx.x >> 1) - 4, u = t - 32, r7 = (u * 37) >> 8;
        const int gp = t < 32 ? (t & 7) - 1 : u - 7 * r7;
        j = t < 0 ? t + 8 : (t < 32 ? t >> 3 : 4 + r7);
        m = ((t < 0 || gp < 0) ? 14 : 2 * gp) + rank;
        if (t >= 60) { m = 16; j = blockIdx.x - 128; }
    }
    const unsigned role = m * 8 + j;
    const bool helper = m == 16;

    TL(0, tid == 0); TLG(0, tid == 0);
    float* const acc_j = g_acc + j * ACC_SIZE;
    if ((warp & ~1) == 8 && elect_one()) {
        const uint32_t bar = sb + (warp == 8 ? BAR_FULLB : BAR_FULLA);
#pragma unroll
        for (int i = 0; i < 8; i++) if (i < NB || warp == 9) mbar_init(bar + 8 * i, 1);
        if (!helper) {
#pragma unroll 1
            for (int i = 0; i < NPRE; i++) {
                mbar_expect_tx(bar + 8 * i, SLOT);
                if (warp == 8) {
                    tma2d(sb + OFF_B + i * SLOT, &P.twq, bar + 8 * i, DM + 64 * j, 64 * i);
                    tma2d(sb + OFF_B + i * SLOT + 8192, &P.twq, bar + 8 * i, 2 * DM + 64 * j, 64 * i);
                } else {
                    tma2d(sb + OFF_A + i * SLOT, &P.tx, bar + 8 * i, 64 * i, 128 * m);
                }
            }
        }
    }
    __syncwarp();

    if (warp >= 8) {
        asm volatile("setmaxnreg.dec.sync.aligned.u32 72;");
        if (elect_one()) {
            if (warp < 10) {
            } else if (warp == 10) {
#pragma unroll
                for (int i = 0; i < 20; i++) mbar_init(sb + BAR_CS1 + 8 * i, i >= 12 ? 1 : (i < 2 || i >= 8 ? 64 : (i < 4 ? 32 : 8)));
                trap_if_gt(sb & 1023, 0);
            } else {
#pragma unroll
                for (int i = 0; i < 14; i++) mbar_init(sb + (i < 8 ? BAR_EMPTYA : BAR_EMPTYB - 64) + 8 * i, i < 8 ? 8 : 16);
            }
            asm volatile("fence.mbarrier_init.release.cluster;" ::: "memory");
        }
        __syncwarp();
        asm volatile("barrier.cluster.arrive.relaxed.aligned;" ::: "memory");
        const unsigned epoch = ld_relaxed(&g_epoch);
        bar_sync(0, NTHREADS);
        if (helper) {
            if (elect_one()) {
#pragma unroll 1
                for (int i = warp - 8; i < 72; i += 4) {
                    const uint32_t full = sb + BAR_FULLA + 8 * (i & 7), dst = sb + OFF_A + (i & 7) * SLOT;
                    const int n = i >> 1, jj = 2 * j + (i & 1);
                    const bool qkv = n < 12;
                    const int c0 = qkv ? (n < 8 ? DM + 128 * (n & 4) : 0) + 64 * jj : 176 * jj + 8 * ((n - 12) & ~7);
                    const int r0 = qkv ? 128 * (n & 3) : 64 * ((n - 12) & 7);
                    mbar_wait(sb + BAR_EMPTYA + 8 * (i & 7), ((i >> 3) & 1) ^ 1);
                    mbar_expect_tx(full, SLOT);
                    tma2d(dst, qkv ? &P.twq : &P.twg, full, c0, r0);
                    tma2d(dst + 8192, qkv ? &P.twq : &P.twu, full, c0, qkv ? r0 + 64 : r0);
                }
                prefetch_l2(P.wd + (size_t)(4 * j + warp - 8) * 44032, 88064);
            }
            return;
        }
        if (warp == 8) {
            asm volatile("barrier.cluster.wait.aligned;" ::: "memory");
            if (elect_one()) {
                if (m >= 6)
                    asm volatile("cp.async.bulk.prefetch.tensor.2d.L2.global [%0, {%1, %2}];" ::"l"(&P.twq), "r"(DM + DM * (m & 1) + 64 * j), "r"(64 * (m >> 1)) : "memory");
                if (j >= 3)
                    asm volatile("cp.async.bulk.prefetch.tensor.2d.L2.global [%0, {%1, %2}];" ::"l"(&P.tx), "r"(64 * j), "r"(128 * m) : "memory");
                Ring r{NPRE, 0};
                const uint32_t dst = sb + OFF_B + rank * 8192;
#define B_LOADN(TM, C0, R0, NB_)                                                                                \
        mbar_waitc(sb + BAR_EMPTYB + 8 * r.slot, r.phase ^ 1);                                              \
        mbar_expect_tx(sb + BAR_FULLB + 8 * r.slot, NB_);                                                   \
        tma2d_mc(dst + r.slot * SLOT, TM, sb + BAR_FULLB + 8 * r.slot, C0, R0);
#define B_LOAD(TM, C0, R0) B_LOADN(TM, C0, R0, SLOT)
#pragma unroll 1
                for (int i = NPRE; i < 8; i++) {
                    if (i >= AHEAD && i < 6) mbar_waitc(sb + BAR_FULLB + 8 * (i - AHEAD), 0);
                    B_LOAD(&P.twq, DM + DM * rank + 64 * j, 64 * i)
                    r.adv();
                }
#pragma unroll 1
                for (int i = 8; i < 18; i++) {
                    if (i == 9 || i == 10) {
                        mbar_waitc(sb + BAR_EMPTYB + 8 * r.slot, r.phase ^ 1);
                        mbar_arrive(sb + BAR_FULLB + 8 * r.slot);
                    } else {
                        const int e = 2 * (i - 14) + rank, b = (i == 8 ? 0 : i - 10) ^ (i < 12 && j < 2);
                        B_LOAD(i < 14 ? &P.twq : &P.two, 64 * j, 64 * (i < 14 ? 2 * b + rank : KORD(e, j)))
                    }
                    r.adv();
                }
#pragma unroll 1
                for (int i = 0; i < 24; i++) {
                    B_LOAD(&P.twg + rank, 176 * j + 8 * (i & ~7), 64 * (i < 8 ? KORD(i, j) : i & 7))
                    r.adv5();
                }
#pragma unroll 1
                for (int i = 0; i < 12; i++) {
                    B_LOADN(&P.twd + (i >> 3), 64 * j, 176 * (2 * (i & 3) + rank) + 64 * (i >> 2), i < 8 ? SLOT : 12288)
                    r.adv5();
                }
            }
            return;
        }
        if (warp == 9) {
            if (elect_one()) {
#pragma unroll 1
                for (int i = NPRE; i < 8; i++) {
                    if (i >= AHEADA) mbar_wait(sb + BAR_FULLA + 8 * (i - AHEADA), 0);
                    mbar_expect_tx(sb + BAR_FULLA + 8 * i, SLOT);
                    tma2d(sb + OFF_A + i * SLOT, &P.tx, sb + BAR_FULLA + 8 * i, 64 * i, 128 * m);
                }
#pragma unroll 1
                for (int i = 2; i < 8; i++) prefetch_tmap(&P.tx + i);
                mbar_wait(sb + BAR_KVR, 0);
                unsigned nf = 0;
#pragma unroll 1
                for (int r = 0; r < 4; r++) {
                    const uint4* src = g_act + ((r >> 1) * 128 + m * 8) * 1024 + (r & 1) * 512;
                    const uint32_t bar = sb + ((r & 1) ? BAR_FULLH : BAR_FULLA), dst = sb + OFF_A + (r & 1) * 8192;
                    if (!(r & 1)) {
#pragma unroll 1
                        for (int t = 0; t < 8; t++) {
                            if (t == j) continue;
                            if (r) { mbar_wait(sb + BAR_FULLA + 8 * t, 1); mbar_wait(sb + BAR_FULLH + 8 * t, 0); }
                            mbar_expect_tx(sb + BAR_FULLA + 8 * t, 8192);
                            mbar_expect_tx(sb + BAR_FULLH + 8 * t, 8192);
                        }
                    }
                    if (nf != epoch * 32) wait_count(g_flag + (m * 7 + r) * 32, epoch * 32);
                    nf = (r & 1) ? 0 : readback(g_flag + (m * 7 + r + 1) * 32);
                    if (r == 1) mbar_wait(sb + BAR_KVW, 1);
                    TL(64 + r, true);
#pragma unroll
                    for (int i = 1; i < 8; i++) {
                        const int t = KORD(i, j);
                        asm volatile("cp.async.bulk.shared::cluster.global.mbarrier::complete_tx::bytes [%0], [%1], %2, [%3];"
                                     ::"r"(dst + t * SLOT), "l"(src + t * 1024), "r"(8192), "r"(bar + 8 * t) : "memory");
                    }
                }
                mbar_wait(sb + BAR_EMPTYA + 8 * PF_DELAY, 0);
#pragma unroll 1
                for (int c = 0; c < 3; c++) {
                    const uint32_t bytes = c == 2 ? 12288 : SLOT;
                    const uint4* src = g_act + ((2 + c) * 128 + m * 8) * 1024;
                    const unsigned* fl = g_flag + (m * 7 + 4 + c) * 32;
                    if (nf != epoch * 8) wait_count(fl, epoch * 8);
                    TL(68 + c, true);
#pragma unroll 1
                    for (int t = 0; t < 8; t++) {
                        if (t == 6 && c < 2) nf = readback(fl + 32);
                        mbar_wait(sb + BAR_EMPTYA + 8 * t, c & 1);
                        mbar_expect_tx(sb + BAR_FULLA + 8 * t, bytes);
                        asm volatile("cp.async.bulk.shared::cluster.global.mbarrier::complete_tx::bytes [%0], [%1], %2, [%3];"
                                     ::"r"(sb + OFF_A + t * SLOT), "l"(src + t * 1024), "r"(bytes), "r"(sb + BAR_FULLA + 8 * t) : "memory");
                    }
                }
            }
            return;
        }
        const int a = warp - 10;
        {
            const int row = 16 * j + 8 * a + (lane >> 2);
            const uint32_t ra = sb + OFF_A + row * 128;
            float sh = 0.f, s0 = 0.f, s1 = 0.f, q0 = 0.f, q1 = 0.f;
#pragma unroll 1
            for (int kt = 0; kt < 8; kt++) {
                mbar_wait(sb + BAR_FULLA + 8 * kt, 0);
                if (kt == 0) sh = bf_lo(lds128(ra + ((row & 7) << 4)).x);
#pragma unroll
                for (int i = 0; i < 2; i++) {
                    const uint4 v = lds128(ra + kt * SLOT + (((2 * (lane & 3) + i) ^ (row & 7)) << 4));
                    const uint32_t ww[4] = {v.x, v.y, v.z, v.w};
#pragma unroll
                    for (int e = 0; e < 4; e++) {
                        const float d0 = bf_lo(ww[e]) - sh, d1 = bf_hi(ww[e]) - sh;
                        s0 += d0; q0 = fmaf(d0, d0, q0);
                        s1 += d1; q1 = fmaf(d1, d1, q1);
                    }
                }
            }
            s0 += s1; q0 += q1;
#pragma unroll
            for (int o = 1; o <= 2; o <<= 1) { s0 += __shfl_xor_sync(0xffffffffu, s0, o); q0 += __shfl_xor_sync(0xffffffffu, q0, o); }
            const float md = s0 * (1.f / DM);
            const float rs = rsqrtf(fmaxf(q0 * (1.f / DM) - md * md, 0.f) + 1e-5f);
            st_tagged_if(g_xstat + 2 * (128 * m + row), rs, -(sh + md), epoch, (lane & 3) == 0);
            TL(1, lane == 0 && a == 0);
        }
        const unsigned long long* cs = g_cs + j * 768 + 2 * lane;
        {
            const unsigned long long* xs = g_xstat + 2 * (128 * m + 64 * a + lane);
            uint4 v0, v1, v2;
            uint32_t it = 0;
            __nanosleep(250);
            do {
                v0 = ld_tagged_rlx(xs); v1 = ld_tagged_rlx(xs + 64); v2 = ld_tagged_rlx(cs);
                trap_if_gt(++it, 1u << 22);
            } while (__any_sync(0xffffffffu, v0.y != epoch || v0.w != epoch || v1.y != epoch || v1.w != epoch || v2.y != epoch || v2.w != epoch));
            sts64(sb + OFF_XST + (64 * a + lane) * 8, v0.x, v0.z);
            sts64(sb + OFF_XST + (64 * a + 32 + lane) * 8, v1.x, v1.z);
            sts64(sb + OFF_CS1 + 256 + 8 * lane, v2.x, v2.z);
            mbar_arrive(sb + BAR_CS1);
            TL(22 + a, lane == 0);
            fetch_tagged(cs + 128 + 128 * a, sb + OFF_CS1 + 512 - 512 * a + 8 * lane, epoch, 200);
            mbar_arrive(sb + BAR_CSV - 8 * a);
            TL(24 + a, lane == 0);
        }
        {
            mbar_wait(sb + BAR_KVW, 0);
            const float* src = acc_j + 4 * (128 * a + lane);
            float4 v[12];
            uint32_t it = 0;
            bool bad;
            while (__any_sync(0xffffffffu, readback(acc_j + 2048 + 128 * (lane & 7) + 127) != 0x41800000u)) trap_if_gt(++it, 1u << 22);
            TL(19, lane == 0 && a == 0);
            do {
                bad = false;
#pragma unroll
                for (int i = 0; i < 12; i++) v[i] = ld_l2_f4(src + 1024 * (i % 3) + 128 * (i / 3));
#pragma unroll
                for (int i = 0; i < 12; i++) bad |= v[i].w != 16.f;
                trap_if_gt(++it, 1u << 22);
            } while (__any_sync(0xffffffffu, bad));
            TL(14, lane == 0 && a == 0);
            const uint32_t d0 = sb + OFF_A + (j < 2 ? 2 * SLOT : 0) + 8192 + (64 * a + (lane >> 2)) * 48;
            const uint32_t d = d0 + (lane & 3) * 4, dz = d0 + (lane & 1) * 384 + 32 + (lane & 2) * 4;
#pragma unroll
            for (int u = 0; u < 4; u++) {
                sts32(d + 768 * u, pack_bf16(v[3 * u].x, v[3 * u].y));
                sts32(d + 768 * u + 384, pack_bf16(v[3 * u].z, v[3 * u + 1].z));
                sts32(d + 768 * u + 16, pack_bf16(v[3 * u + 1].x, v[3 * u + 1].y));
                sts32(d + 768 * u + 400, pack_bf16(v[3 * u + 2].x, v[3 * u + 2].y));
                const uint32_t z2 = pack_bf16(v[3 * u + 2].z, v[3 * u + 2].z);
                sts64(dz + 768 * u, z2, z2);
            }
            mbar_arrive(sb + BAR_KVR);
        }
#pragma unroll 1
        for (int c = 0; c < 3; c++) {
            fetch_tagged(cs + 384 + 128 * c + 64 * a, sb + OFF_CS3 + (32 * c + lane) * 16 + 8 * a, epoch, 1000);
            mbar_arrive(sb + BAR_CSG + 8 * c);
        }
        {
            uint32_t it = 0;
            while (__any_sync(0xffffffffu, (int)(readback(g_flag + (m * 7 + 2 + (lane & 1)) * 32) - epoch * 32) < 0)) {
                __nanosleep(600);
                trap_if_gt(++it, 1u << 22);
            }
#pragma unroll 1
            for (int rr = 0; rr < 2; rr++) {
                const int row = 64 * rr + 32 * a + lane;
                const unsigned long long* hs = g_hstat + (1024 * m + row) * 2;
                uint4 v[8];
                bool bad;
                do {
                    bad = false;
#pragma unroll
                    for (int i = 0; i < 8; i++) v[i] = ld_tagged_rlx(hs + 256 * i);
#pragma unroll
                    for (int i = 0; i < 8; i++) bad |= v[i].y != epoch || v[i].w != epoch;
                    trap_if_gt(++it, 1u << 22);
                } while (__any_sync(0xffffffffu, bad));
                float mean = 0.f;
#pragma unroll
                for (int i = 0; i < 8; i++) mean += __uint_as_float(v[i].x);
                mean *= 0.125f;
                float m2 = 0.f, dv = 0.f;
#pragma unroll
                for (int i = 0; i < 8; i++) { const float d = __uint_as_float(v[i].x) - mean; m2 += __uint_as_float(v[i].z); dv = fmaf(d, d, dv); }
                sts_f2(sb + OFF_CS1 + row * 8, -mean, rcp(fmaf(dv, 64.f, m2) * (1.f / DM) + 1e-5f));
            }
        }
        mbar_arrive(sb + BAR_CS3);
#pragma unroll 1
        for (int c = a; c < 3; c += 2) {
            mbar_wait(sb + BAR_STG + 8 * c, 0);
            if (elect_one()) {
                asm volatile("cp.async.bulk.global.shared::cta.bulk_group [%0], [%1], %2;" ::"l"(g_act + ((2 + c) * 128 + role) * 1024), "r"(sb + OFF_B + 4 * SLOT), "r"(c == 2 ? 12288 : SLOT) : "memory");
                asm volatile("cp.async.bulk.commit_group;" ::: "memory");
                asm volatile("cp.async.bulk.wait_group.read 0;" ::: "memory");
                mbar_arrive(sb + BAR_FULLB + 8 * 4);
                asm volatile("cp.async.bulk.wait_group 0;" ::: "memory");
            }
            __syncwarp();
            TL(60 + c, lane == 0);
            uint32_t ack = 0;
            const uint4* rb = g_act + ((2 + c) * 128 + role) * 1024 + lane * 8;
#pragma unroll
            for (int i = 0; i < 4; i++) ack |= readback(rb + (i == 3 && c == 2 ? 0 : 256 * i));
            signal_after(g_flag + (m * 7 + 4 + c) * 32, ack, P.zero, lane == 0);
            TL(54 + c, lane == 0);
        }
        return;
    }
    const unsigned epoch = ld_relaxed(&g_epoch);
    uint32_t wraw[16];
    if (!helper) {
        const uint32_t* wp = reinterpret_cast<const uint32_t*>(P.wphi) + (4 * j) * 128 + (lane & 3) * 16 + (lane >> 2);
#pragma unroll
        for (int i = 0; i < 16; i++)
            asm volatile("ld.global.nc.u32 %0, [%1];" : "=r"(wraw[i]) : "l"(wp + (i >> 2) * 128 + ((i >> 1) & 1) * 64 + (i & 1) * 8));
    }
    asm volatile("barrier.cluster.arrive.relaxed.aligned;" ::: "memory");
    asm volatile("setmaxnreg.inc.sync.aligned.u32 216;");
    bar_sync(0, NTHREADS);
    if (helper) {
        const int w = warp >> 2;
        sts64(sb + OFF_B + 8 * tid, 0x3f803f80u, 0x3f803f80u);
        fence_async_smem();
        uint32_t zack[6];
        {
            float* z = g_acc + 2 * j * ACC_SIZE + 4 * tid;
#pragma unroll
            for (int u = 0; u < 6; u++) stg128(z + 1024 * u, 0, 0, 0, 0);
#pragma unroll
            for (int u = 0; u < 6; u++) zack[u] = readback(z + 1024 * u);
        }
        bar_sync(1, 256);
        float acc[8];
        int i = w;
#pragma unroll 1
        for (int job = 0; job < 6; job++) {
            const int n = job < 3 ? 4 : 8;
#pragma unroll 1
            for (int t = 0; t < n; t++, i += 2) {
                mbar_waitc(sb + BAR_FULLA + 8 * (i & 7), (i >> 3) & 1);
                const desc_t da = desc_lo(sb + OFF_A) + (i & 7) * (SLOT >> 4);
                wg_fence();
#pragma unroll
                for (int k = 0; k < 8; k++) wgmma_n8_tt(acc + (k & 4), da + 128 * k, desc_lo(sb + OFF_B), (t | (k & 3)) != 0);
                wg_commit();
                wg_wait<0>();
                mbar_arrive_n_if(sb + BAR_EMPTYA + 8 * (i & 7), 2, lane == 0);
            }
            fence_acc<8>(acc);
            if (job == 1) {
                asm volatile("{.reg .pred p; .reg .b32 t; lop3.b32 t, %0, %1, %2, 0xfe; lop3.b32 t, t, %3, %4, 0xfe; or.b32 t, t, %5; setp.ne.u32 p, t, 0; @p trap;}"
                             ::"r"(zack[0]), "r"(zack[1]), "r"(zack[2]), "r"(zack[3]), "r"(zack[4]), "r"(zack[5]));
                bar_sync(1, 256);
            }
            const int q = lane & 3;
            const float lo = (q & 1) ? acc[2] : acc[0], hi = (q & 1) ? acc[6] : acc[4];
            const float v = job < 3 ? lo + hi : ((q & 2) ? hi : lo);
            unsigned long long* dst = g_cs + ((2 * j + w) * 6 + job) * 128 + (q >> 1) * 64 + 16 * (warp & 3) + 8 * (q & 1) + (lane >> 2);
            asm volatile("st.relaxed.gpu.global.b64 [%0], %1;" ::"l"(dst), "l"(((unsigned long long)epoch << 32) | __float_as_uint(v)) : "memory");
        }
        return;
    }
    {
        const int w = warp >> 2, wv = warp & 3, g = lane >> 2, q = lane & 3;
        const uint32_t sa = sb + OFF_A + w * 8192;
        const desc_t dA = desc_lo(sa), dB = desc_lo(sb + OFF_B);
        unsigned* const flag_m = g_flag + (m * 7 + w) * 32;
        const uint32_t fullh = sb + (w ? BAR_FULLH : BAR_FULLA);
        const bool l0 = lane == 0, l2 = lane < 2;
        const uint32_t eb = mapa(sb + BAR_EMPTYB, lane & 1);
        asm volatile("barrier.cluster.wait.aligned;" ::: "memory");
        Ring rg{0, 0};
        int prev = 0;

        uint32_t wb[16];
        constexpr float L2E = 1.4426950408889634f;
        const int ch = lane >> 4, sw = lane & 7;
        const uint32_t lrow = (lane & 15) * 128;
        uint32_t fp[16], fm[16];
        const int vs = j < 2 ? 2 : 0;
        {
            float acc[64];
#pragma unroll 1
            for (int kt = 0; kt < 8; kt++) {
                mbar_waitc(sb + BAR_FULLA + 8 * kt, 0);
                mbar_waitc(sb + BAR_FULLB + 8 * rg.slot, rg.phase);
                const desc_t da = dA + kt * (SLOT >> 4), db = dB + rg.slot * (SLOT >> 4);
                wg_fence();
#pragma unroll
                for (int k = 0; k < 4; k++) wgmma_n128(acc, da + 2 * k, db + 128 * k, (kt | k) != 0);
                wg_commit();
                wg_wait<1>();
                mbar_arrive_cl_if(eb + 8 * prev, l2 && kt > 0);
                prev = rg.slot; rg.adv();
            }
#pragma unroll
            for (int i = 0; i < 8; i++) {
                wb[(i >> 1) * 4 + (i & 1)] = __byte_perm(wraw[2 * i], wraw[2 * i + 1], 0x5410);
                wb[(i >> 1) * 4 + 2 + (i & 1)] = __byte_perm(wraw[2 * i], wraw[2 * i + 1], 0x7632);
            }
            uint32_t a[16];
            float accq[32];
            mbar_waitc(sb + BAR_FULLB + 8 * 2, 1);
            wg_fence();
#pragma unroll
            for (int k = 0; k < 8; k++) wgmma_n64(accq, dA + (vs + (k >> 2)) * (SLOT >> 4) + (k & 3) * 2, dB + 2 * (SLOT >> 4) + 128 * k, k != 0);
            wg_commit();
            wg_wait<1>();
            fence_acc<64>(acc);
            mbar_arrive_cl_if(eb + 8 * prev, l2);
            TL(17, tid == 0);
            mbar_waitc(sb + BAR_CS1, 0);
            const float2 s0 = lds_f2(sb + OFF_XST + (16 * warp + g) * 8), s1 = lds_f2(sb + OFF_XST + (16 * warp + g + 8) * 8);
            wg_wait<0>();
            fence_acc<32>(accq);
            mbar_arrive_cl_if(eb + 8 * 2, l2);
            TL(2, tid == 0);
            const uint32_t st = sb + OFF_B + warp * 2048 + lrow;
#pragma unroll
            for (int hh = 0; hh < 4; hh++)
                ln_frag<false>(acc + 8 * hh, sb + OFF_CS1 + (64 + 16 * hh + 2 * q) * 4, 0.f, s0.y, 0.f, s1.y, a + 4 * hh);
#pragma unroll 1
            for (int it = 0; it < 2; it++) {
                feature_maps(a, wb, s0.x * L2E, s1.x * L2E, fp, fm);
                if (it == 0) {
                    mbar_waitc(sb + BAR_FULLB + 8 * 3, 1); mbar_waitc(sb + BAR_FULLB + 8 * 4, 1);
                    mbar_waitc(sb + BAR_CSV, 0);
                    const uint32_t sv = sb + OFF_A + vs * SLOT + warp * 2048 + lrow;
#pragma unroll
                    for (int hh = 0; hh < 4; hh++) {
                        stsm4(st + (3 + (hh >> 1)) * SLOT + (((4 * (hh & 1) + ch) ^ sw) << 4), fp[4 * hh], fp[4 * hh + 1], fp[4 * hh + 2], fp[4 * hh + 3]);
                        stsm4(st + (3 + (hh >> 1)) * SLOT + (((4 * (hh & 1) + 2 + ch) ^ sw) << 4), fm[4 * hh], fm[4 * hh + 1], fm[4 * hh + 2], fm[4 * hh + 3]);
                        ln_frag<true>(acc + 32 + 8 * hh, sb + OFF_CS1 + (128 + 16 * hh + 2 * q) * 4, s0.x, s0.y, s1.x, s1.y, a);
                        stsm4(sv + (hh >> 1) * SLOT + (((2 * (hh & 1) + ch) ^ sw) << 4), a[0], a[1], a[2], a[3]);
                    }
                    stsm4(sv + ch * SLOT + ((4 ^ sw) << 4), 0x3f803f80u, 0x3f803f80u, 0x3f803f80u, 0x3f803f80u);
                    fence_async_smem();
                    bar_sync(1, 256);
                    float kvd[20];
                    wg_fence();
#pragma unroll
                    for (int k = 0; k < 8; k++)
                        wgmma_n40_tt(kvd, dB + (3 + w) * (SLOT >> 4) + 128 * k, desc_lo(sb + OFF_A) + (vs + w) * (SLOT >> 4) + 128 * k, k != 0);
                    wg_commit();
                    wg_wait<0>();
                    fence_acc<20>(kvd);
                    mbar_arrive_cl_if(eb + 8 * (3 + (lane >> 1)), lane < 4);
                    const bool h1 = wv >= 2;
                    float* kvp = acc_j + 4 * tid;
                    red_f32x4(kvp, h1 ? kvd[8] : kvd[0], h1 ? kvd[9] : kvd[1], h1 ? kvd[10] : kvd[2], 1.f);
                    red_f32x4(kvp + 1024, h1 ? kvd[12] : kvd[4], h1 ? kvd[13] : kvd[5], h1 ? kvd[11] : kvd[3], 1.f);
                    red_f32x4(kvp + 2048, h1 ? kvd[14] : kvd[6], h1 ? kvd[15] : kvd[7], (q & 1) ? kvd[18] : kvd[16], 1.f);
                    mbar_arrive_if(sb + BAR_KVW, l0);
                    TL(3, tid == 0);
#pragma unroll 1
                    for (int b = 1; b < 4; b++) {
                        const int slot = b == 1 ? 5 : b - 2;
                        mbar_waitc(sb + BAR_FULLB + 8 * slot, b == 1);
                        const desc_t da = dA + (b == 1 ? 2 - vs : 2 * b) * (SLOT >> 4), db = dB + slot * (SLOT >> 4);
                        wg_fence();
#pragma unroll
                        for (int k = 0; k < 8; k++) wgmma_n64(accq, da + (k >> 2) * (SLOT >> 4) + (k & 3) * 2, db + 128 * k, 1);
                        wg_commit();
                    }
                    mbar_waitc(sb + BAR_CSQ, 0);
                    wg_wait<0>();
                    fence_acc<32>(accq);
                    mbar_arrive_cl_if(eb + 8 * ((5 + (lane >> 1)) % 6), lane < 6);
                    TL(4, tid == 0);
#pragma unroll
                    for (int hh = 0; hh < 4; hh++)
                        ln_frag<false>(accq + 8 * hh, sb + OFF_CS1 + (16 * hh + 2 * q) * 4, 0.f, s0.y, 0.f, s1.y, a + 4 * hh);
                }
            }
        }
        uint32_t res_lo[8], res_hi[8], ack[4];
        const uint32_t own_rows = sb + OFF_A + j * SLOT + warp * 2048;
#pragma unroll
        for (int b = 0; b < 4; b++)
            ldsm4(own_rows + lrow + (((2 * b + ch) ^ sw) << 4), res_lo[2 * b], res_hi[2 * b], res_lo[2 * b + 1], res_hi[2 * b + 1]);
        TL(5, tid == 0); TL(26, tid == 128);
        mbar_waitc(sb + BAR_KVR, 0);
        TL(6, tid == 0);
        {
            const uint32_t kvs = sb + OFF_A + vs * SLOT + 8192;
            uint32_t o_lo[8], o_hi[8];
#pragma unroll
            for (int hh = 0; hh < 4; hh++) {
                uint32_t b[8], zb[4];
                const uint32_t base = kvs + hh * 32 * 48;
                ldsm4t(base + (lane & 15) * 48 + (lane >> 4) * 16, b[0], b[1], b[2], b[3]);
                ldsm4t(base + (16 + (lane & 15)) * 48 + (lane >> 4) * 16, b[4], b[5], b[6], b[7]);
                ldsm4t(base + lane * 48 + 32, zb[0], zb[1], zb[2], zb[3]);
                float n0[4], n1[4], dn[4];
                mma16816_z(n0, fp + 4 * hh, b[0], b[1]); mma16816_z(n1, fp + 4 * hh, b[2], b[3]); mma16816_z(dn, fp + 4 * hh, zb[0], zb[1]);
                mma16816(n0, fm + 4 * hh, b[4], b[5]); mma16816(n1, fm + 4 * hh, b[6], b[7]); mma16816(dn, fm + 4 * hh, zb[2], zb[3]);
                const float i0 = rcp(dn[0] + 1e-6f), i1 = rcp(dn[2] + 1e-6f);
                o_lo[2 * hh] = pack_bf16(n0[0] * i0, n0[1] * i0); o_hi[2 * hh] = pack_bf16(n0[2] * i1, n0[3] * i1);
                o_lo[2 * hh + 1] = pack_bf16(n1[0] * i0, n1[1] * i0); o_hi[2 * hh + 1] = pack_bf16(n1[2] * i1, n1[3] * i1);
            }
            __syncwarp();
            mbar_arrive_if(sb + BAR_KVW, l0);
            store_tile(own_rows, g_act + role * 1024 + warp * 128 + lane, o_lo, o_hi, lane, ack);
            TL(7, tid == 0); TL(27, tid == 128);
        }
        float acch[32];
        {
            float* acc = acch;
#pragma unroll
            for (int t = 0; t < 8; t++) {
                acc[4 * t] = bf_lo(res_lo[t]); acc[4 * t + 1] = bf_hi(res_lo[t]);
                acc[4 * t + 2] = bf_lo(res_hi[t]); acc[4 * t + 3] = bf_hi(res_hi[t]);
            }
            fence_acc<32>(acc);
#pragma unroll
            for (int i = 2; i < 6; i++) mbar_waitc(sb + BAR_FULLB + 8 * i, 0);
#pragma unroll 1
            for (int i = 0; i < 8; i++) {
                const int kt = KORD(i, j);
                mbar_waitc(fullh + 8 * kt, (i != 0) ^ w);
                TL(8, i == 1 && tid == 0);
                const desc_t da = dA + kt * (SLOT >> 4), db = dB + (4 + i) * (SLOT >> 5);
                wg_fence();
#pragma unroll
                for (int k = 0; k < 4; k++) wgmma_n64(acc, da + 2 * k, db + 128 * k, 1);
                wg_commit();
                if (i == 0) { signal_late(flag_m, ack, P.zero, l0); TL(20, tid == 0); }
            }
            wg_wait<0>();
            fence_acc<32>(acc);
            mbar_arrive_cl_if(eb + 8 * (2 + (lane >> 1)), lane < 8);
            rg.slot = 0; rg.phase = 1;
            TL(9, tid == 0); TL(29, tid == 128);
#pragma unroll
            for (int t = 0; t < 8; t++) {
                res_lo[t] = pack_bf16(acc[4 * t], acc[4 * t + 1]);
                res_hi[t] = pack_bf16(acc[4 * t + 2], acc[4 * t + 3]);
            }
            store_tile(own_rows, g_act + (128 + role) * 1024 + warp * 128 + lane, res_lo, res_hi, lane, ack);
            TL(10, tid == 0);
        }
        float acc0[64], acc1[64], acc2[56], nm0, nm1;
        float4 cs[8];
        uint32_t hr[16];
#define P3_GROUP(MMA, ACC, KT)                                                                              \
        mbar_waitc(sb + BAR_FULLB + 8 * rg.slot, rg.phase);                                                 \
        {                                                                                                   \
            const desc_t da = dA + (KT) * (SLOT >> 4), db = dB + rg.slot * (SLOT >> 4);                     \
            wg_fence();                                                                                     \
            _Pragma("unroll") for (int k = 0; k < 4; k++) MMA(ACC, da + 2 * k, db + 128 * k, (i | k) != 0); \
            wg_commit();                                                                                    \
        }
#define P3_CS(C, NT)    \
        _Pragma("unroll") for (int t = 0; t < (NT); t++) lds_f4_if(cs[t], sb + OFF_CS3 + q * 16 + 512 * (C) + 64 * t, i == t);
#define P3_EPI2(C, ACC)                                                                                     \
        if (i == 0) {                                                                                       \
            fence_acc<64>(ACC);                                                                             \
            if (C) mbar_waitc(sb + BAR_FULLB + 8 * 4, 1);                                                   \
            hh_stage2<0, 2>(ACC, cs, nm0, nm1, stg, lane);                                                  \
            mbar_waitc(sb + BAR_CSG + 8 * (C) + 8, 0);                                                      \
        }                                                                                                   \
        if (i == 1) {                                                                                       \
            hh_stage2<2, 4>(ACC, cs, nm0, nm1, stg, lane);                                                  \
            fence_async_smem();                                                                             \
            __syncwarp();                                                                                   \
            mbar_arrive_if(sb + BAR_STG + 8 * (C), l0);                                                     \
        }
#define P3_EPI(C, ACC, N, NTP)                                                                              \
        fence_acc<N>(ACC);                                                                                  \
        TL(11 + (C), tid == 0);                                                                             \
        hh_stage<NTP>(ACC, cs, nm0, nm1, sb + OFF_B + 4 * SLOT + warp * 2048, lane);                        \
        mbar_arrive_if(sb + BAR_STG + 8 * (C), l0);                                                         \
        TL(50 + (C), tid == 0);
        const uint32_t stg = sb + OFF_B + 4 * SLOT + warp * 2048;
        const uint32_t blk = ((lane & 7) + (lane >> 4) * 8) * 128 + (((2 * wv + ((lane >> 3) & 1)) ^ (lane & 7)) << 4);
#pragma unroll 1
        for (int i = 0; i < 8; i++) {
            const int kt = KORD(i, j);
            mbar_waitc(fullh + 8 * kt, w);
            TL(44 + w, (tid & 127) == 0 && i == 1);
            P3_GROUP(wgmma_n128, acc0, kt)
            if (i == 7) {
                mbar_waitc(sb + BAR_CS3, 0);
                nm0 = lds_f2(sb + OFF_CS1 + (16 * warp + g) * 8).x; nm1 = lds_f2(sb + OFF_CS1 + (16 * warp + g + 8) * 8).x;
            }
            wg_wait<1>();
            mbar_arrive_cl_if(eb + 8 * prev, l2 && i > 0);
            if (i == 0) {
                signal_late(flag_m + 64, ack, P.zero, l0);
                TL(21, tid == 0);
                {
                    fence_acc<32>(acch);
                    const float* acc = acch;
                    float s0 = 0.f, s1 = 0.f;
#pragma unroll
                    for (int t = 0; t < 8; t++) { s0 += acc[4 * t] + acc[4 * t + 1]; s1 += acc[4 * t + 2] + acc[4 * t + 3]; }
            s0 += __shfl_xor_sync(0xffffffffu, s0, 1); s1 += __shfl_xor_sync(0xffffffffu, s1, 1);
            s0 += __shfl_xor_sync(0xffffffffu, s0, 2); s1 += __shfl_xor_sync(0xffffffffu, s1, 2);
            const float mu0 = s0 * (1.f / 64), mu1 = s1 * (1.f / 64);
            float q0 = 0.f, q1 = 0.f;
#pragma unroll
            for (int t = 0; t < 8; t++) {
                float d;
                d = acc[4 * t] - mu0; q0 = fmaf(d, d, q0);
                d = acc[4 * t + 1] - mu0; q0 = fmaf(d, d, q0);
                d = acc[4 * t + 2] - mu1; q1 = fmaf(d, d, q1);
                d = acc[4 * t + 3] - mu1; q1 = fmaf(d, d, q1);
            }
            q0 += __shfl_xor_sync(0xffffffffu, q0, 1); q1 += __shfl_xor_sync(0xffffffffu, q1, 1);
            q0 += __shfl_xor_sync(0xffffffffu, q0, 2); q1 += __shfl_xor_sync(0xffffffffu, q1, 2);
            st_tagged_if(g_hstat + (role * 128 + 16 * warp + g + 8 * (q & 1)) * 2, q ? mu1 : mu0, q ? q1 : q0, epoch, q < 2);
                }
                bar_sync(2 + w, 128);
#pragma unroll
                for (int tp = 0; tp < 4; tp++) ldsm4t(sa + j * SLOT + blk + tp * 2048, hr[4 * tp], hr[4 * tp + 1], hr[4 * tp + 2], hr[4 * tp + 3]);
                mbar_waitc(sb + BAR_CSG, 0);
#pragma unroll
                for (int t = 0; t < 8; t++) cs[t] = lds_f4(sb + OFF_CS3 + q * 16 + 64 * t);
            }
            prev = rg.slot; rg.adv5();
        }
#pragma unroll 1
        for (int i = 0; i < 8; i++) {
            P3_GROUP(wgmma_n128, acc1, i)
            wg_wait<1>();
            mbar_arrive_cl_if(eb + 8 * prev, l2);
            P3_EPI2(0, acc0)
            P3_CS(1, 8)
            prev = rg.slot; rg.adv5();
        }
#pragma unroll 1
        for (int i = 0; i < 8; i++) {
            P3_GROUP(wgmma_n112, acc2, i)
            wg_wait<1>();
            mbar_arrive_cl_if(eb + 8 * prev, l2);
            mbar_arrive_if(sb + BAR_EMPTYA + 8 * ((i + 7) & 7), l0 && i > 0);
            if (i == 0) { mbar_waitc(sb + BAR_FULLB + 8 * 4, 1); P3_EPI(1, acc1, 64, 4) mbar_waitc(sb + BAR_CSG + 16, 0); }
            P3_CS(2, 6)
            prev = rg.slot; rg.adv5();
        }
        mbar_waitc(sb + BAR_FULLB + 8 * 4, 0);
        wg_wait<0>();
        mbar_arrive_cl_if(eb + 8 * prev, l2);
        mbar_arrive_if(sb + BAR_EMPTYA + 8 * 7, l0);
        fence_acc<56>(acc2);
        TL(13, tid == 0);
#pragma unroll
        for (int tp = 0; tp < 3; tp++)
            stsm4(sb + OFF_B + 4 * SLOT + tp * 4096 + warp * 512 + (lane & 15) * 32 + ((ch ^ ((lane >> 2) & 1)) << 4),
                  hh_pair<32>(acc2 + 8 * tp, cs[2 * tp], nm0), hh_pair<32>(acc2 + 8 * tp + 2, cs[2 * tp], nm1),
                  hh_pair<32>(acc2 + 8 * tp + 4, cs[2 * tp + 1], nm0), hh_pair<32>(acc2 + 8 * tp + 6, cs[2 * tp + 1], nm1));
        fence_async_smem();
        __syncwarp();
        mbar_arrive_if(sb + BAR_STG + 16, l0);
        TL(52, tid == 0);
        {
            float acc[64];
            const desc_t dA0 = desc_lo(sb + OFF_A);
#define KT_P4(I, NK, DH, STEP)                                                                                   \
        const int s_ = (2 * (I) + w) & 7;                                                                   \
        mbar_waitc(sb + BAR_FULLB + 8 * rg.slot, rg.phase);                                                 \
        mbar_waitc(sb + BAR_FULLA + 8 * s_, (((I) >> 2) + 1) & 1);                                          \
        const desc_t dh_ = (DH) + s_ * (SLOT >> 4), dw_ = dB + rg.slot * (SLOT >> 4) + w * 512;              \
        wg_fence();                                                                                         \
        _Pragma("unroll") for (int k = 0; k < (NK); k++) wgmma_n128_tn(acc, dw_ + 128 * k, dh_ + (STEP) * k, ((I) | k) != 0); \
        wg_commit();
#pragma unroll 1
            for (int i = 0; i < 8; i++) {
                KT_P4(i, 4, dA0, 2)
#pragma unroll
                for (int t = 0; t < 8; t++) lds_f4_if(cs[t], sb + OFF_CS1 + (64 * w + 8 * t + 2 * q) * 8, i == t);
                wg_wait<0>();
                mbar_arrive_n_if(sb + BAR_EMPTYA + 8 * s_, 2, l0);
                mbar_arrive_cl_if(eb + 8 * rg.slot, l2 && i < 7);
                rg.adv5();
            }
#pragma unroll 1
            for (int i = 8; i < 12; i++) {
                KT_P4(i, 3, dA0 + ((0xC0000010ull - 0x40000040ull) << 32), 256)
                wg_wait<1>();
                rg.adv5();
            }
            wg_wait<0>();
            fence_acc<64>(acc);
            TL(15, tid == 0);
            const uint32_t xch = sb + OFF_A + 2 * SLOT + (tid & 127) * 16;
            if (w) {
#pragma unroll
                for (int t = 0; t < 8; t++) {
                    sts128(xch + SLOT + t * 2048, __float_as_uint(acc[4 * t]), __float_as_uint(acc[4 * t + 1]),
                           __float_as_uint(acc[4 * t + 2]), __float_as_uint(acc[4 * t + 3]));
                }
#pragma unroll
                for (int t = 0; t < 32; t++) acc[t] = acc[32 + t];
            } else {
#pragma unroll
                for (int t = 0; t < 8; t++)
                    sts128(xch + t * 2048, __float_as_uint(acc[32 + 4 * t]), __float_as_uint(acc[33 + 4 * t]),
                           __float_as_uint(acc[34 + 4 * t]), __float_as_uint(acc[35 + 4 * t]));
            }
            bar_sync(1, 256);
            float4 o[8];
#pragma unroll
            for (int t = 0; t < 8; t++) o[t] = lds_f4(xch + (w ^ 1) * SLOT + t * 2048);
            const uint32_t tile = sb + OFF_A + w * SLOT;
#pragma unroll
            for (int t = 0; t < 8; t++) {
                hr[2 * t] = pack_bf16(fmaf(acc[4 * t] + o[t].x, cs[t].y, bf_lo(hr[2 * t])), fmaf(acc[4 * t + 1] + o[t].y, cs[t].w, bf_hi(hr[2 * t])));
                hr[2 * t + 1] = pack_bf16(fmaf(acc[4 * t + 2] + o[t].z, cs[t].y, bf_lo(hr[2 * t + 1])), fmaf(acc[4 * t + 3] + o[t].w, cs[t].w, bf_hi(hr[2 * t + 1])));
            }
#pragma unroll
            for (int tp = 0; tp < 4; tp++) stsm4t(tile + blk + tp * 2048, hr[4 * tp], hr[4 * tp + 1], hr[4 * tp + 2], hr[4 * tp + 3]);
            fence_async_smem();
            bar_sync(2 + w, 128);
            if ((tid & 127) == 0) {
                tma_store2d(&P.tout, tile, 64 * j, 128 * m + 64 * w);
                asm volatile("cp.async.bulk.wait_group.read 0;" ::: "memory");
            }
            if (tid == 0 && role == 0) g_epoch = epoch + 1;
            TL(16, tid == 0); TLG(1, tid == 0);
        }
    }
}

typedef CUresult (*EncodeFn)(CUtensorMap*, CUtensorMapDataType, cuuint32_t, void*, const cuuint64_t*, const cuuint64_t*,
                             const cuuint32_t*, const cuuint32_t*, CUtensorMapInterleave, CUtensorMapSwizzle,
                             CUtensorMapL2promotion, CUtensorMapFloatOOBfill);

static void make_map2d(EncodeFn enc, CUtensorMap* tm, const void* base, uint64_t cols, uint64_t rows, uint64_t pitch_elems,
                       uint32_t box_rows) {
    cuuint64_t gd[2] = {cols, rows};
    cuuint64_t gs[1] = {pitch_elems * 2};
    cuuint32_t bd[2] = {64, box_rows};
    cuuint32_t es[2] = {1, 1};
    enc(tm, CU_TENSOR_MAP_DATA_TYPE_BFLOAT16, 2, const_cast<void*>(base), gd, gs, bd, es, CU_TENSOR_MAP_INTERLEAVE_NONE,
        CU_TENSOR_MAP_SWIZZLE_128B, CU_TENSOR_MAP_L2_PROMOTION_L2_256B, CU_TENSOR_MAP_FLOAT_OOB_FILL_NONE);
}

}

extern "C" void kernel_launch(void* const* d_in, const int* in_sizes, int n_in, void* d_out, int out_size) {
    using namespace hk;
    (void)in_sizes; (void)n_in; (void)out_size;
    static EncodeFn enc = nullptr;
    if (!enc) {
        void* fn = nullptr;
        cudaDriverEntryPointQueryResult qr;
        cudaGetDriverEntryPoint("cuTensorMapEncodeTiled", &fn, cudaEnableDefault, &qr);
        enc = (EncodeFn)fn;
        cudaFuncSetAttribute(fused_kernel, cudaFuncAttributeMaxDynamicSharedMemorySize, SMEM_BYTES);
    }
    Params P;
    const __nv_bfloat16* x = (const __nv_bfloat16*)d_in[0];
    P.x = x;
    P.wqkv = (const __nv_bfloat16*)d_in[1];
    P.wphi = (const __nv_bfloat16*)d_in[2];
    P.wo = (const __nv_bfloat16*)d_in[3];
    P.wg = (const __nv_bfloat16*)d_in[5];
    P.wu = (const __nv_bfloat16*)d_in[6];
    P.wd = (const __nv_bfloat16*)d_in[7];
    P.out = (__nv_bfloat16*)d_out;
    P.zero = 0;
    make_map2d(enc, &P.tx, x, DM, SEQ, DM, 128);
    make_map2d(enc, &P.twq, P.wqkv, 3 * DM, DM, 3 * DM, 64);
    make_map2d(enc, &P.two, P.wo, DM, DM, DM, 64);
    make_map2d(enc, &P.twg, P.wg, FF, DM, FF, 64);
    make_map2d(enc, &P.twu, P.wu, FF, DM, FF, 64);
    make_map2d(enc, &P.twd, P.wd, DM, FF, DM, 64);
    make_map2d(enc, &P.twd48, P.wd, DM, FF, DM, 48);
    make_map2d(enc, &P.tout, d_out, DM, SEQ, DM, 64);
    fused_kernel<<<NCTA, NTHREADS, SMEM_BYTES>>>(P);
}
```

```cpp
#include <cuda_runtime.h>
#include <cuda_bf16.h>
#include <cuda.h>
#include <stdint.h>

namespace hk {

constexpr int SEQ = 2048, DM = 512, FF = 1376;
constexpr int NCTA = 132;
constexpr int NTHREADS = 384;
constexpr uint32_t SLOT = 16384;
constexpr uint32_t OFF_A = 0, OFF_B = 8 * SLOT, OFF_MISC = 14 * SLOT;
constexpr uint32_t BAR_FULLA = OFF_MISC + 0, BAR_EMPTYA = OFF_MISC + 64, BAR_FULLB = OFF_MISC + 128,
                   BAR_EMPTYB = OFF_MISC + 176, BAR_CS1 = OFF_MISC + 224, BAR_CS3 = OFF_MISC + 232,
                   BAR_CSQ = OFF_MISC + 240, BAR_CSV = OFF_MISC + 248,
                   BAR_STG = OFF_MISC + 256,
                   BAR_KVW = OFF_MISC + 280, BAR_KVR = OFF_MISC + 288,
                   BAR_CSG = OFF_MISC + 296,
                   BAR_FULLH = OFF_MISC + 320;
constexpr uint32_t OFF_CS1 = OFF_MISC + 384;
constexpr uint32_t OFF_CS3 = OFF_CS1 + 1024;
constexpr uint32_t OFF_XST = OFF_CS3;
constexpr uint32_t SMEM_BYTES = OFF_CS3 + 1536;
#define KORD(i, j) ((i) == 0 ? (j) : (i) - ((i) <= (j)))
constexpr int NB = 6;
constexpr int NPRE = 3, AHEAD = 3, AHEADA = 5;
constexpr int PF_DELAY = 2;

constexpr int ACC_SIZE = 3 * 256 * 4;

__device__ __align__(1024) uint4 g_act[5 * 128 * 1024];
__device__ __align__(128) unsigned long long g_hstat[SEQ * 16];
__device__ __align__(128) unsigned long long g_xstat[SEQ * 2];
__device__ __align__(128) float g_acc[8 * ACC_SIZE];
__device__ __align__(128) unsigned long long g_cs[8 * 6 * 128];
__device__ __align__(128) unsigned g_flag[16 * 7 * 32];
__device__ unsigned g_epoch = 1;

#define TL(i, pred) do {} while (0)
#define TLG(i, pred) do {} while (0)

struct Params {
    CUtensorMap tx, twq, two, twg, twu, twd, twd48, tout;
    const __nv_bfloat16 *x, *wqkv, *wphi, *wo, *wg, *wu, *wd;
    __nv_bfloat16* out;
    unsigned zero;
};

__device__ __forceinline__ uint32_t smem_u32(const void* p) { return (uint32_t)__cvta_generic_to_shared(p); }
__device__ __forceinline__ void mbar_init(uint32_t bar, uint32_t cnt) {
    asm volatile("mbarrier.init.shared::cta.b64 [%0], %1;" ::"r"(bar), "r"(cnt) : "memory");
}
__device__ __forceinline__ void mbar_expect_tx(uint32_t bar, uint32_t bytes) {
    asm volatile("mbarrier.arrive.expect_tx.shared::cta.b64 _, [%0], %1;" ::"r"(bar), "r"(bytes) : "memory");
}
__device__ __forceinline__ void mbar_arrive(uint32_t bar) {
    asm volatile("mbarrier.arrive.shared::cta.b64 _, [%0];" ::"r"(bar) : "memory");
}
__device__ __forceinline__ void mbar_arrive_if(uint32_t bar, bool pred) {
    asm volatile("{.reg .pred p; setp.ne.u32 p, %1, 0; @p mbarrier.arrive.shared::cta.b64 _, [%0];}" ::"r"(bar), "r"((uint32_t)pred) : "memory");
}
__device__ __forceinline__ void trap_if_gt(uint32_t v, uint32_t lim) {
    asm volatile("{.reg .pred p; setp.gt.u32 p, %0, %1; @p trap;}" ::"r"(v), "r"(lim));
}
__device__ __forceinline__ void mbar_wait(uint32_t bar, uint32_t parity) {
    asm volatile("{\n"
                 ".reg .pred P1, P2;\n"
                 ".reg .u32 c;\n"
                 "mov.u32 c, 0;\n"
                 "LAB_WAIT:\n"
                 "mbarrier.try_wait.parity.shared::cta.b64 P1, [%0], %1;\n"
                 "@P1 bra LAB_DONE;\n"
                 "add.u32 c, c, 1;\n"
                 "setp.gt.u32 P2, c, 1048576;\n"
                 "@P2 trap;\n"
                 "bra LAB_WAIT;\n"
                 "LAB_DONE:\n"
                 "}" ::"r"(bar), "r"(parity) : "memory");
}
__device__ __forceinline__ void mbar_waitc(uint32_t bar, uint32_t parity) {
    asm volatile("{\n"
                 ".reg .pred P1;\n"
                 "LAB_WAIT:\n"
                 "mbarrier.try_wait.parity.shared::cta.b64 P1, [%0], %1;\n"
                 "@!P1 bra LAB_WAIT;\n"
                 "}" ::"r"(bar), "r"(parity) : "memory");
}
__device__ __forceinline__ void tma2d(uint32_t dst, const CUtensorMap* tm, uint32_t bar, int c0, int c1) {
    asm volatile("cp.async.bulk.tensor.2d.shared::cluster.global.mbarrier::complete_tx::bytes [%0], [%1, {%3, %4}], [%2];"
                 ::"r"(dst), "l"(tm), "r"(bar), "r"(c0), "r"(c1) : "memory");
}
__device__ __forceinline__ void tma2d_mc(uint32_t dst, const CUtensorMap* tm, uint32_t bar, int c0, int c1) {
    asm volatile("cp.async.bulk.tensor.2d.shared::cluster.global.mbarrier::complete_tx::bytes.multicast::cluster [%0], [%1, {%3, %4}], [%2], %5;"
                 ::"r"(dst), "l"(tm), "r"(bar), "r"(c0), "r"(c1), "h"((uint16_t)3) : "memory");
}
__device__ __forceinline__ uint32_t mapa(uint32_t addr, uint32_t rank) {
    uint32_t r; asm("mapa.shared::cluster.u32 %0, %1, %2;" : "=r"(r) : "r"(addr), "r"(rank)); return r;
}
__device__ __forceinline__ void mbar_arrive_cl_if(uint32_t cbar, bool pred) {
    asm volatile("{.reg .pred p; setp.ne.u32 p, %1, 0; @p mbarrier.arrive.shared::cluster.b64 _, [%0];}" ::"r"(cbar), "r"((uint32_t)pred) : "memory");
}
__device__ __forceinline__ bool elect_one() {
    uint32_t ok;
    asm volatile("{.reg .pred p; elect.sync _|p, 0xffffffff; selp.u32 %0, 1, 0, p;}" : "=r"(ok));
    return ok;
}
__device__ __forceinline__ void prefetch_tmap(const CUtensorMap* tm) {
    asm volatile("prefetch.tensormap [%0];" ::"l"(tm) : "memory");
}
__device__ __forceinline__ void prefetch_l2(const void* p, uint32_t bytes) {
    asm volatile("cp.async.bulk.prefetch.L2.global [%0], %1;" ::"l"(p), "r"(bytes) : "memory");
}
__device__ __forceinline__ unsigned ld_relaxed(const unsigned* p) {
    unsigned v; asm volatile("ld.relaxed.gpu.global.u32 %0, [%1];" : "=r"(v) : "l"(p)); return v;
}
__device__ __forceinline__ void fence_async_smem() { asm volatile("fence.proxy.async.shared::cta;" ::: "memory"); }
__device__ __forceinline__ uint32_t readback(const void* p) {
    uint32_t v; asm volatile("ld.relaxed.gpu.global.u32 %0, [%1];" : "=r"(v) : "l"(p) : "memory"); return v;
}
__device__ __forceinline__ void wait_count(const unsigned* p, unsigned target) {
    uint32_t it = 0;
    while ((int)(readback(p) - target) < 0) trap_if_gt(++it, 1u << 22);
}
__device__ __forceinline__ void red_f32x4(float* p, float a, float b, float c, float d) {
    asm volatile("red.relaxed.gpu.global.add.v4.f32 [%0], {%1, %2, %3, %4};" ::"l"(p), "f"(a), "f"(b), "f"(c), "f"(d) : "memory");
}
__device__ __forceinline__ float4 ld_l2_f4(const float* p) {
    float4 v;
    asm volatile("ld.relaxed.gpu.global.v4.f32 {%0,%1,%2,%3}, [%4];" : "=f"(v.x), "=f"(v.y), "=f"(v.z), "=f"(v.w) : "l"(p) : "memory");
    return v;
}
__device__ __forceinline__ void stg128(void* p, uint32_t a, uint32_t b, uint32_t c, uint32_t d) {
    asm volatile("st.global.v4.u32 [%0], {%1,%2,%3,%4};" ::"l"(p), "r"(a), "r"(b), "r"(c), "r"(d) : "memory");
}
__device__ __forceinline__ uint4 lds128(uint32_t a) {
    uint4 v;
    asm volatile("ld.shared.v4.u32 {%0,%1,%2,%3}, [%4];" : "=r"(v.x), "=r"(v.y), "=r"(v.z), "=r"(v.w) : "r"(a) : "memory");
    return v;
}
__device__ __forceinline__ float2 lds_f2(uint32_t a) {
    float2 v;
    asm volatile("ld.shared.v2.f32 {%0,%1}, [%2];" : "=f"(v.x), "=f"(v.y) : "r"(a) : "memory");
    return v;
}
__device__ __forceinline__ void sts_f2(uint32_t a, float x, float y) {
    asm volatile("st.shared.v2.f32 [%0], {%1,%2};" ::"r"(a), "f"(x), "f"(y) : "memory");
}
__device__ __forceinline__ void sts64(uint32_t a, uint32_t x, uint32_t y) {
    asm volatile("st.shared.v2.u32 [%0], {%1,%2};" ::"r"(a), "r"(x), "r"(y) : "memory");
}
__device__ __forceinline__ void sts128(uint32_t a, uint32_t x, uint32_t y, uint32_t z, uint32_t w) {
    asm volatile("st.shared.v4.u32 [%0], {%1,%2,%3,%4};" ::"r"(a), "r"(x), "r"(y), "r"(z), "r"(w) : "memory");
}
__device__ __forceinline__ void stsm4(uint32_t a, uint32_t r0, uint32_t r1, uint32_t r2, uint32_t r3) {
    asm volatile("stmatrix.sync.aligned.m8n8.x4.shared.b16 [%0], {%1,%2,%3,%4};" ::"r"(a), "r"(r0), "r"(r1), "r"(r2), "r"(r3) : "memory");
}
__device__ __forceinline__ void stsm4t(uint32_t a, uint32_t r0, uint32_t r1, uint32_t r2, uint32_t r3) {
    asm volatile("stmatrix.sync.aligned.m8n8.x4.trans.shared.b16 [%0], {%1,%2,%3,%4};" ::"r"(a), "r"(r0), "r"(r1), "r"(r2), "r"(r3) : "memory");
}
__device__ __forceinline__ void tma_store2d(const CUtensorMap* tm, uint32_t src, int c0, int c1) {
    asm volatile("cp.async.bulk.tensor.2d.global.shared::cta.bulk_group [%0, {%2, %3}], [%1];" ::"l"(tm), "r"(src), "r"(c0), "r"(c1) : "memory");
    asm volatile("cp.async.bulk.commit_group;" ::: "memory");
}
__device__ __forceinline__ void ldsm4(uint32_t a, uint32_t& r0, uint32_t& r1, uint32_t& r2, uint32_t& r3) {
    asm volatile("ldmatrix.sync.aligned.m8n8.x4.shared.b16 {%0,%1,%2,%3}, [%4];" : "=r"(r0), "=r"(r1), "=r"(r2), "=r"(r3) : "r"(a) : "memory");
}
__device__ __forceinline__ void ldsm4t(uint32_t a, uint32_t& r0, uint32_t& r1, uint32_t& r2, uint32_t& r3) {
    asm volatile("ldmatrix.sync.aligned.m8n8.x4.trans.shared.b16 {%0,%1,%2,%3}, [%4];" : "=r"(r0), "=r"(r1), "=r"(r2), "=r"(r3) : "r"(a) : "memory");
}
__device__ __forceinline__ void mma16816(float* c, const uint32_t* a, uint32_t b0, uint32_t b1) {
    asm("mma.sync.aligned.m16n8k16.row.col.f32.bf16.bf16.f32 {%0,%1,%2,%3}, {%4,%5,%6,%7}, {%8,%9}, {%0,%1,%2,%3};"
                 : "+f"(c[0]), "+f"(c[1]), "+f"(c[2]), "+f"(c[3])
                 : "r"(a[0]), "r"(a[1]), "r"(a[2]), "r"(a[3]), "r"(b0), "r"(b1));
}
__device__ __forceinline__ uint32_t pack_bf16(float lo, float hi) {
    uint32_t r; asm("cvt.rn.bf16x2.f32 %0, %1, %2;" : "=r"(r) : "f"(hi), "f"(lo)); return r;
}
__device__ __forceinline__ float bf_lo(uint32_t w) { return __uint_as_float(w << 16); }
__device__ __forceinline__ float bf_hi(uint32_t w) { return __uint_as_float(w & 0xffff0000u); }
__device__ __forceinline__ float ex2(float x) { float r; asm("ex2.approx.ftz.f32 %0, %1;" : "=f"(r) : "f"(x)); return r; }
__device__ __forceinline__ float rcp(float x) { float r; asm("rcp.approx.ftz.f32 %0, %1;" : "=f"(r) : "f"(x)); return r; }
__device__ __forceinline__ void bar_sync(int id, int n) { asm volatile("bar.sync %0, %1;" ::"r"(id), "r"(n) : "memory"); }

typedef unsigned long long desc_t;
__device__ __forceinline__ desc_t desc_lo(uint32_t addr) { return (desc_t)(((addr & 0x3FFFF) >> 4) | (512u << 16)) | (0x40000040ull << 32); }
__device__ __forceinline__ void wg_fence() { asm volatile("wgmma.fence.sync.aligned;" ::: "memory"); }
__device__ __forceinline__ void wg_commit() { asm volatile("wgmma.commit_group.sync.aligned;" ::: "memory"); }
template <int N> __device__ __forceinline__ void wg_wait() { asm volatile("wgmma.wait_group.sync.aligned %0;" ::"n"(N) : "memory"); }
template <int N> __device__ __forceinline__ void fence_acc(float* d) {
#pragma unroll
    for (int i = 0; i < N; i++) asm volatile("" : "+f"(d[i])::"memory");
}
#define R4(o) "+f"(d[o + 0]), "+f"(d[o + 1]), "+f"(d[o + 2]), "+f"(d[o + 3])
#define R8(o) R4(o), R4(o + 4)
__device__ __forceinline__ void wgmma_n128(float* d, desc_t da, desc_t db, int sc) {
    asm volatile("{.reg .pred p; setp.ne.b32 p, %66, 0;\n"
                 "wgmma.mma_async.sync.aligned.m64n128k16.f32.bf16.bf16 {%0,%1,%2,%3,%4,%5,%6,%7,%8,%9,%10,%11,%12,%13,%14,%15,%16,%17,%18,%19,%20,%21,%22,%23,%24,%25,%26,%27,%28,%29,%30,%31,"
                 "%32,%33,%34,%35,%36,%37,%38,%39,%40,%41,%42,%43,%44,%45,%46,%47,%48,%49,%50,%51,%52,%53,%54,%55,%56,%57,%58,%59,%60,%61,%62,%63}, %64, %65, p, 1, 1, 0, 1;}"
                 : R8(0), R8(8), R8(16), R8(24), R8(32), R8(40), R8(48), R8(56)
                 : "l"(da), "l"(db), "r"(sc));
}
__device__ __forceinline__ void wgmma_n112(float* d, desc_t da, desc_t db, int sc) {
    asm volatile("{.reg .pred p; setp.ne.b32 p, %58, 0;\n"
                 "wgmma.mma_async.sync.aligned.m64n112k16.f32.bf16.bf16 {%0,%1,%2,%3,%4,%5,%6,%7,%8,%9,%10,%11,%12,%13,%14,%15,%16,%17,%18,%19,%20,%21,%22,%23,%24,%25,%26,%27,%28,%29,%30,%31,%32,%33,%34,%35,%36,%37,%38,%39,%40,%41,%42,%43,%44,%45,%46,%47,%48,%49,%50,%51,%52,%53,%54,%55}, %56, %57, p, 1, 1, 0, 1;}"
                 : R8(0), R8(8), R8(16), R8(24), R8(32), R8(40), R8(48)
                 : "l"(da), "l"(db), "r"(sc));
}
__device__ __forceinline__ void wgmma_n128_tn(float* d, desc_t da, desc_t db, int sc) {
    asm volatile("{.reg .pred p; setp.ne.b32 p, %66, 0;\n"
                 "wgmma.mma_async.sync.aligned.m64n128k16.f32.bf16.bf16 {%0,%1,%2,%3,%4,%5,%6,%7,%8,%9,%10,%11,%12,%13,%14,%15,%16,%17,%18,%19,%20,%21,%22,%23,%24,%25,%26,%27,%28,%29,%30,%31,%32,%33,%34,%35,%36,%37,%38,%39,%40,%41,%42,%43,%44,%45,%46,%47,%48,%49,%50,%51,%52,%53,%54,%55,%56,%57,%58,%59,%60,%61,%62,%63}, %64, %65, p, 1, 1, 1, 0;}"
                 : R8(0), R8(8), R8(16), R8(24), R8(32), R8(40), R8(48), R8(56)
                 : "l"(da), "l"(db), "r"(sc));
}
__device__ __forceinline__ void wgmma_n64(float* d, desc_t da, desc_t db, int sc) {
    asm volatile("{.reg .pred p; setp.ne.b32 p, %34, 0;\n"
                 "wgmma.mma_async.sync.aligned.m64n64k16.f32.bf16.bf16 {%0,%1,%2,%3,%4,%5,%6,%7,%8,%9,%10,%11,%12,%13,%14,%15,%16,%17,%18,%19,%20,%21,%22,%23,%24,%25,%26,%27,%28,%29,%30,%31}, %32, %33, p, 1, 1, 0, 1;}"
                 : R8(0), R8(8), R8(16), R8(24)
                 : "l"(da), "l"(db), "r"(sc));
}
__device__ __forceinline__ void wgmma_n40_tt(float* d, desc_t da, desc_t db, int sc) {
    asm volatile("{.reg .pred p; setp.ne.b32 p, %22, 0;\n"
                 "wgmma.mma_async.sync.aligned.m64n40k16.f32.bf16.bf16 {%0,%1,%2,%3,%4,%5,%6,%7,%8,%9,%10,%11,%12,%13,%14,%15,%16,%17,%18,%19}, %20, %21, p, 1, 1, 1, 1;}"
                 : R8(0), R8(8), R4(16)
                 : "l"(da), "l"(db), "r"(sc));
}

__device__ __forceinline__ void wgmma_n8_tt(float* d, desc_t da, desc_t db, int sc) {
    asm volatile("{.reg .pred p; setp.ne.b32 p, %6, 0;\n"
                 "wgmma.mma_async.sync.aligned.m64n8k16.f32.bf16.bf16 {%0,%1,%2,%3}, %4, %5, p, 1, 1, 1, 1;}"
                 : R4(0)
                 : "l"(da), "l"(db), "r"(sc));
}

__device__ __forceinline__ void signal_after(unsigned* cnt, uint32_t ack, uint32_t zero, bool pred) {
    asm volatile("{.reg .pred p; setp.ne.u32 p, %2, 0; @p red.relaxed.gpu.global.add.u32 [%0], %1;}"
                 ::"l"(cnt), "r"((ack & zero) + 1), "r"((uint32_t)pred) : "memory");
}
__device__ __forceinline__ void signal_late(unsigned* cnt, const uint32_t* a, uint32_t zero, bool pred) {
    uint32_t v;
    asm volatile("{.reg .b32 t; lop3.b32 t, %1, %2, %3, 0xfe; or.b32 %0, t, %4;}"
                 : "=r"(v) : "r"(a[0]), "r"(a[1]), "r"(a[2]), "r"(a[3]));
    signal_after(cnt, v, zero, pred);
}
__device__ __forceinline__ void mma16816_z(float* c, const uint32_t* a, uint32_t b0, uint32_t b1) {
    asm("mma.sync.aligned.m16n8k16.row.col.f32.bf16.bf16.f32 {%0,%1,%2,%3}, {%4,%5,%6,%7}, {%8,%9}, {%10,%10,%10,%10};"
                 : "=f"(c[0]), "=f"(c[1]), "=f"(c[2]), "=f"(c[3])
                 : "r"(a[0]), "r"(a[1]), "r"(a[2]), "r"(a[3]), "r"(b0), "r"(b1), "f"(0.f));
}
__device__ __forceinline__ uint32_t max2(uint32_t a, uint32_t b) { uint32_t r; asm("max.bf16x2 %0, %1, %2;" : "=r"(r) : "r"(a), "r"(b)); return r; }
__device__ __forceinline__ uint32_t min2(uint32_t a, uint32_t b) { uint32_t r; asm("min.bf16x2 %0, %1, %2;" : "=r"(r) : "r"(a), "r"(b)); return r; }
__device__ __forceinline__ void mbar_arrive_n_if(uint32_t bar, uint32_t n, bool pred) {
    asm volatile("{.reg .pred p; setp.ne.u32 p, %1, 0; @p mbarrier.arrive.shared::cta.b64 _, [%0], %2;}" ::"r"(bar), "r"((uint32_t)pred), "r"(n) : "memory");
}
__device__ __forceinline__ float4 lds_f4(uint32_t a) {
    float4 v;
    asm volatile("ld.shared.v4.f32 {%0,%1,%2,%3}, [%4];" : "=f"(v.x), "=f"(v.y), "=f"(v.z), "=f"(v.w) : "r"(a) : "memory");
    return v;
}
__device__ __forceinline__ void lds_f4_if(float4& v, uint32_t a, bool pred) {
    asm volatile("{.reg .pred p; setp.ne.u32 p, %5, 0; @p ld.shared.v4.f32 {%0,%1,%2,%3}, [%4];}"
                 : "+f"(v.x), "+f"(v.y), "+f"(v.z), "+f"(v.w) : "r"(a), "r"((uint32_t)pred) : "memory");
}
__device__ __forceinline__ uint4 ld_tagged_rlx(const unsigned long long* p) {
    unsigned long long a, b;
    asm volatile("ld.relaxed.gpu.global.v2.b64 {%0,%1}, [%2];" : "=l"(a), "=l"(b) : "l"(p) : "memory");
    return make_uint4((unsigned)a, (unsigned)(a >> 32), (unsigned)b, (unsigned)(b >> 32));
}
__device__ __forceinline__ void sts32(uint32_t a, uint32_t x) { asm volatile("st.shared.u32 [%0], %1;" ::"r"(a), "r"(x) : "memory"); }
__device__ __forceinline__ void fetch_tagged(const unsigned long long* src, uint32_t dst, unsigned epoch, unsigned ns) {
    uint4 v;
    uint32_t it = 0;
    while (true) {
        v = ld_tagged_rlx(src);
        if (!__any_sync(0xffffffffu, v.y != epoch || v.w != epoch)) break;
        __nanosleep(ns);
        trap_if_gt(++it, 1u << 22);
    }
    sts64(dst, v.x, v.z);
}
__device__ __forceinline__ void st_tagged_if(unsigned long long* p, float a, float b, unsigned tag, bool pred) {
    const unsigned long long t = (unsigned long long)tag << 32;
    asm volatile("{.reg .pred p; setp.ne.u32 p, %3, 0; @p st.relaxed.gpu.global.v2.b64 [%0], {%1,%2};}"
                 ::"l"(p), "l"(t | __float_as_uint(a)), "l"(t | __float_as_uint(b)), "r"((uint32_t)pred) : "memory");
}

__device__ __forceinline__ void store_tile(uint32_t tile_rows, uint4* gdst, const uint32_t* lo, const uint32_t* hi, int lane, uint32_t* ack) {
    const int r = lane & 15;
#pragma unroll
    for (int b = 0; b < 4; b++)
        stsm4(tile_rows + r * 128 + (((2 * b + (lane >> 4)) ^ (r & 7)) << 4), lo[2 * b], hi[2 * b], lo[2 * b + 1], hi[2 * b + 1]);
    fence_async_smem();
    __syncwarp();
#pragma unroll
    for (int i = 0; i < 4; i++) {
        const uint4 v = lds128(tile_rows + i * 512 + lane * 16);
        stg128(gdst + 32 * i, v.x, v.y, v.z, v.w);
    }
#pragma unroll
    for (int i = 0; i < 4; i++) ack[i] = readback(gdst + 32 * i);
}

__device__ __forceinline__ void feature_maps(const uint32_t* a, const uint32_t* wb, float c0, float c1, uint32_t* plus, uint32_t* minus) {
    uint32_t P[16], mx[4], mn[4];
#pragma unroll
    for (int h = 0; h < 4; h++) {
        float p[8];
        mma16816_z(p, a + 4 * h, wb[4 * h], wb[4 * h + 1]);
        mma16816_z(p + 4, a + 4 * h, wb[4 * h + 2], wb[4 * h + 3]);
        P[4 * h] = pack_bf16(p[0], p[2]); P[4 * h + 1] = pack_bf16(p[1], p[3]);
        P[4 * h + 2] = pack_bf16(p[4], p[6]); P[4 * h + 3] = pack_bf16(p[5], p[7]);
        mx[h] = max2(max2(P[4 * h], P[4 * h + 1]), max2(P[4 * h + 2], P[4 * h + 3]));
        mn[h] = min2(min2(P[4 * h], P[4 * h + 1]), min2(P[4 * h + 2], P[4 * h + 3]));
    }
#pragma unroll
    for (int s = 1; s <= 2; s <<= 1) {
        uint32_t tx[4], tn[4];
#pragma unroll
        for (int h = 0; h < 4; h++) { tx[h] = __shfl_xor_sync(0xffffffffu, mx[h], s); tn[h] = __shfl_xor_sync(0xffffffffu, mn[h], s); }
#pragma unroll
        for (int h = 0; h < 4; h++) { mx[h] = max2(mx[h], tx[h]); mn[h] = min2(mn[h], tn[h]); }
    }
#pragma unroll
    for (int h = 0; h < 4; h++) {
        const float mx0 = bf_lo(mx[h]) * c0, mx1 = bf_hi(mx[h]) * c1, mn0 = bf_lo(mn[h]) * c0, mn1 = bf_hi(mn[h]) * c1;
        float ep[8], em[8];
#pragma unroll
        for (int i = 0; i < 8; i++) {
            const bool r1 = (i & 2);
            const uint32_t w = P[4 * h + (i >> 2) * 2 + (i & 1)];
            const float p = r1 ? bf_hi(w) : bf_lo(w);
            ep[i] = ex2(fmaf(p, r1 ? c1 : c0, r1 ? -mx1 : -mx0));
            em[i] = ex2(fmaf(p, r1 ? -c1 : -c0, r1 ? mn1 : mn0));
        }
        float sp[4], sm[4];
        uint32_t tp[4], tm[4];
#pragma unroll
        for (int i = 0; i < 4; i++) { tp[i] = pack_bf16(ep[2 * i], ep[2 * i + 1]); tm[i] = pack_bf16(em[2 * i], em[2 * i + 1]); }
        mma16816_z(sp, tp, 0x3f803f80u, 0x3f803f80u);
        mma16816_z(sm, tm, 0x3f803f80u, 0x3f803f80u);
        const float r0 = rcp(sp[0] * sm[0]), r1 = rcp(sp[2] * sm[2]);
        const float rs[4] = {r0 * sm[0], r1 * sm[2], r0 * sp[0], r1 * sp[2]};
#pragma unroll
        for (int i = 0; i < 4; i++) {
            plus[4 * h + i] = pack_bf16(ep[2 * i] * rs[i & 1], ep[2 * i + 1] * rs[i & 1]);
            minus[4 * h + i] = pack_bf16(em[2 * i] * rs[2 + (i & 1)], em[2 * i + 1] * rs[2 + (i & 1)]);
        }
    }
}

template <bool SCALE>
__device__ __forceinline__ void ln_frag(const float* acc, uint32_t cs_addr, float rs0, float nm0, float rs1, float nm1, uint32_t* a) {
    const float2 c0 = lds_f2(cs_addr), c1 = lds_f2(cs_addr + 32);
    const float s0 = SCALE ? rs0 : 1.f, s1 = SCALE ? rs1 : 1.f;
    a[0] = pack_bf16(fmaf(nm0, c0.x, acc[0]) * s0, fmaf(nm0, c0.y, acc[1]) * s0);
    a[1] = pack_bf16(fmaf(nm1, c0.x, acc[2]) * s1, fmaf(nm1, c0.y, acc[3]) * s1);
    a[2] = pack_bf16(fmaf(nm0, c1.x, acc[4]) * s0, fmaf(nm0, c1.y, acc[5]) * s0);
    a[3] = pack_bf16(fmaf(nm1, c1.x, acc[6]) * s1, fmaf(nm1, c1.y, acc[7]) * s1);
}

template <int UP>
__device__ __forceinline__ uint32_t hh_pair(const float* ag, float4 cs, float nmean) {
    const float g0 = fmaf(nmean, cs.x, ag[0]), g1 = fmaf(nmean, cs.y, ag[1]);
    const float u0 = fmaf(nmean, cs.z, ag[UP]), u1 = fmaf(nmean, cs.w, ag[UP + 1]);
    return pack_bf16(g0 * u0, g1 * u1);
}
template <int TP0, int TP1>
__device__ __forceinline__ void hh_stage2(const float* acc, const float4* cs, float nm0, float nm1, uint32_t stg, int lane) {
#pragma unroll
    for (int tp = TP0; tp < TP1; tp++)
        stsm4(stg + (lane & 15) * 128 + (((2 * tp + (lane >> 4)) ^ (lane & 7)) << 4), hh_pair<32>(acc + 8 * tp, cs[2 * tp], nm0),
              hh_pair<32>(acc + 8 * tp + 2, cs[2 * tp], nm1), hh_pair<32>(acc + 8 * tp + 4, cs[2 * tp + 1], nm0),
              hh_pair<32>(acc + 8 * tp + 6, cs[2 * tp + 1], nm1));
}
struct Ring {
    int slot; uint32_t phase;
    __device__ __forceinline__ void adv() { if (++slot == NB) { slot = 0; phase ^= 1; } }
    __device__ __forceinline__ void adv5() { slot += slot == 3; adv(); }
};

__global__ void __cluster_dims__(2, 1, 1) __launch_bounds__(NTHREADS, 1) fused_kernel(const __grid_constant__ Params P) {
    extern __shared__ __align__(1024) uint8_t smem_raw[];
    const uint32_t sb = smem_u32(smem_raw);
    const int tid = threadIdx.x, lane = tid & 31;
    const int warp = __shfl_sync(0xffffffffu, tid >> 5, 0);
    const unsigned rank = blockIdx.x & 1;
    int m, j;
    {
        const int t = (int)(blockIdx.x >> 1) - 4, u = t - 32, r7 = (u * 37) >> 8;
        const int gp = t < 32 ? (t & 7) - 1 : u - 7 * r7;
        j = t < 0 ? t + 8 : (t < 32 ? t >> 3 : 4 + r7);
        m = ((t < 0 || gp < 0) ? 14 : 2 * gp) + rank;
        if (t >= 60) { m = 16; j = blockIdx.x - 128; }
    }
    const unsigned role = m * 8 + j;
    const bool helper = m == 16;

    TL(0, tid == 0); TLG(0, tid == 0);
    float* const acc_j = g_acc + j * ACC_SIZE;
    if ((warp & ~1) == 8 && elect_one()) {
        const uint32_t bar = sb + (warp == 8 ? BAR_FULLB : BAR_FULLA);
#pragma unroll
        for (int i = 0; i < 8; i++) if (i < NB || warp == 9) mbar_init(bar + 8 * i, 1);
        if (!helper) {
#pragma unroll 1
            for (int i = 0; i < NPRE; i++) {
                mbar_expect_tx(bar + 8 * i, SLOT);
                if (warp == 8) {
                    tma2d(sb + OFF_B + i * SLOT, &P.twq, bar + 8 * i, DM + 64 * j, 64 * i);
                    tma2d(sb + OFF_B + i * SLOT + 8192, &P.twq, bar + 8 * i, 2 * DM + 64 * j, 64 * i);
                } else {
                    tma2d(sb + OFF_A + i * SLOT, &P.tx, bar + 8 * i, 64 * i, 128 * m);
                }
            }
        }
    }
    __syncwarp();

    if (warp >= 8) {
        asm volatile("setmaxnreg.dec.sync.aligned.u32 72;");
        if (elect_one()) {
            if (warp < 10) {
            } else if (warp == 10) {
#pragma unroll
                for (int i = 0; i < 20; i++) mbar_init(sb + BAR_CS1 + 8 * i, i >= 12 ? 1 : (i < 2 || i >= 8 ? 64 : (i < 4 ? 32 : 8)));
                trap_if_gt(sb & 1023, 0);
            } else {
#pragma unroll
                for (int i = 0; i < 14; i++) mbar_init(sb + (i < 8 ? BAR_EMPTYA : BAR_EMPTYB - 64) + 8 * i, i < 8 ? 8 : 16);
            }
            asm volatile("fence.mbarrier_init.release.cluster;" ::: "memory");
        }
        __syncwarp();
        asm volatile("barrier.cluster.arrive.relaxed.aligned;" ::: "memory");
        const unsigned epoch = ld_relaxed(&g_epoch);
        bar_sync(0, NTHREADS);
        if (helper) {
            if (elect_one()) {
#pragma unroll 1
                for (int i = warp - 8; i < 72; i += 4) {
                    const uint32_t full = sb + BAR_FULLA + 8 * (i & 7), dst = sb + OFF_A + (i & 7) * SLOT;
                    const int n = i >> 1, jj = 2 * j + (i & 1);
                    const bool qkv = n < 12;
                    const int c0 = qkv ? (n < 8 ? DM + 128 * (n & 4) : 0) + 64 * jj : 176 * jj + 8 * ((n - 12) & ~7);
                    const int r0 = qkv ? 128 * (n & 3) : 64 * ((n - 12) & 7);
                    mbar_wait(sb + BAR_EMPTYA + 8 * (i & 7), ((i >> 3) & 1) ^ 1);
                    mbar_expect_tx(full, SLOT);
                    tma2d(dst, qkv ? &P.twq : &P.twg, full, c0, r0);
                    tma2d(dst + 8192, qkv ? &P.twq : &P.twu, full, c0, qkv ? r0 + 64 : r0);
                }
                prefetch_l2(P.wd + (size_t)(4 * j + warp - 8) * 44032, 88064);
            }
            return;
        }
        if (warp == 8) {
            asm volatile("barrier.cluster.wait.aligned;" ::: "memory");
            if (elect_one()) {
                if (m >= 6)
                    asm volatile("cp.async.bulk.prefetch.tensor.2d.L2.global [%0, {%1, %2}];" ::"l"(&P.twq), "r"(DM + DM * (m & 1) + 64 * j), "r"(64 * (m >> 1)) : "memory");
                if (j >= 3)
                    asm volatile("cp.async.bulk.prefetch.tensor.2d.L2.global [%0, {%1, %2}];" ::"l"(&P.tx), "r"(64 * j), "r"(128 * m) : "memory");
                Ring r{NPRE, 0};
                const uint32_t dst = sb + OFF_B + rank * 8192;
#define B_LOADN(TM, C0, R0, NB_)                                                                                \
        mbar_waitc(sb + BAR_EMPTYB + 8 * r.slot, r.phase ^ 1);                                              \
        mbar_expect_tx(sb + BAR_FULLB + 8 * r.slot, NB_);                                                   \
        tma2d_mc(dst + r.slot * SLOT, TM, sb + BAR_FULLB + 8 * r.slot, C0, R0);
#define B_LOAD(TM, C0, R0) B_LOADN(TM, C0, R0, SLOT)
#pragma unroll 1
                for (int i = NPRE; i < 8; i++) {
                    if (i >= AHEAD && i < 6) mbar_waitc(sb + BAR_FULLB + 8 * (i - AHEAD), 0);
                    B_LOAD(&P.twq, DM + DM * rank + 64 * j, 64 * i)
                    r.adv();
                }
#pragma unroll 1
                for (int i = 8; i < 18; i++) {
                    if (i == 9 || i == 10) {
                        mbar_waitc(sb + BAR_EMPTYB + 8 * r.slot, r.phase ^ 1);
                        mbar_arrive(sb + BAR_FULLB + 8 * r.slot);
                    } else {
                        const int e = 2 * (i - 14) + rank, b = (i == 8 ? 0 : i - 10) ^ (i < 12 && j < 2);
                        B_LOAD(i < 14 ? &P.twq : &P.two, 64 * j, 64 * (i < 14 ? 2 * b + rank : KORD(e, j)))
                    }
                    r.adv();
                }
#pragma unroll 1
                for (int i = 0; i < 24; i++) {
                    const int c = i < 2 ? i : (i < 9 ? 0 : (i < 16 ? 1 : 2)), u = i < 2 ? 0 : i - 1 - 7 * c;
                    B_LOAD(&P.twg + rank, 176 * j + 64 * c, 64 * (i < 16 ? KORD(u, j) : i & 7))
                    r.adv5();
                }
#pragma unroll 1
                for (int i = 0; i < 12; i++) {
                    B_LOADN(&P.twd + (i >> 3), 64 * j, 176 * (2 * (i & 3) + rank) + 64 * (i >> 2), i < 8 ? SLOT : 12288)
                    r.adv5();
                }
            }
            return;
        }
        if (warp == 9) {
            if (elect_one()) {
#pragma unroll 1
                for (int i = NPRE; i < 8; i++) {
                    if (i >= AHEADA) mbar_wait(sb + BAR_FULLA + 8 * (i - AHEADA), 0);
                    mbar_expect_tx(sb + BAR_FULLA + 8 * i, SLOT);
                    tma2d(sb + OFF_A + i * SLOT, &P.tx, sb + BAR_FULLA + 8 * i, 64 * i, 128 * m);
                }
#pragma unroll 1
                for (int i = 2; i < 8; i++) prefetch_tmap(&P.tx + i);
                mbar_wait(sb + BAR_KVR, 0);
                unsigned nf = 0;
#pragma unroll 1
                for (int r = 0; r < 4; r++) {
                    const uint4* src = g_act + ((r >> 1) * 128 + m * 8) * 1024 + (r & 1) * 512;
                    const uint32_t bar = sb + ((r & 1) ? BAR_FULLH : BAR_FULLA), dst = sb + OFF_A + (r & 1) * 8192;
                    if (!(r & 1)) {
#pragma unroll 1
                        for (int t = 0; t < 8; t++) {
                            if (t == j) continue;
                            if (r) { mbar_wait(sb + BAR_FULLA + 8 * t, 1); mbar_wait(sb + BAR_FULLH + 8 * t, 0); }
                            mbar_expect_tx(sb + BAR_FULLA + 8 * t, 8192);
                            mbar_expect_tx(sb + BAR_FULLH + 8 * t, 8192);
                        }
                    }
                    if (nf != epoch * 32) wait_count(g_flag + (m * 7 + r) * 32, epoch * 32);
                    nf = (r & 1) ? 0 : readback(g_flag + (m * 7 + r + 1) * 32);
                    if (r == 1) mbar_wait(sb + BAR_KVW, 1);
                    TL(64 + r, true);
#pragma unroll
                    for (int i = 1; i < 8; i++) {
                        const int t = KORD(i, j);
                        asm volatile("cp.async.bulk.shared::cluster.global.mbarrier::complete_tx::bytes [%0], [%1], %2, [%3];"
                                     ::"r"(dst + t * SLOT), "l"(src + t * 1024), "r"(8192), "r"(bar + 8 * t) : "memory");
                    }
                }
                mbar_wait(sb + BAR_EMPTYA + 8 * PF_DELAY, 0);
#pragma unroll 1
                for (int c = 0; c < 3; c++) {
                    const uint32_t bytes = c == 2 ? 12288 : SLOT;
                    const uint4* src = g_act + ((2 + c) * 128 + m * 8) * 1024;
                    const unsigned* fl = g_flag + (m * 7 + 4 + c) * 32;
                    if (nf != epoch * 8) wait_count(fl, epoch * 8);
                    TL(68 + c, true);
#pragma unroll 1
                    for (int t = 0; t < 8; t++) {
                        if (t == 6 && c < 2) nf = readback(fl + 32);
                        mbar_wait(sb + BAR_EMPTYA + 8 * t, c & 1);
                        mbar_expect_tx(sb + BAR_FULLA + 8 * t, bytes);
                        asm volatile("cp.async.bulk.shared::cluster.global.mbarrier::complete_tx::bytes [%0], [%1], %2, [%3];"
                                     ::"r"(sb + OFF_A + t * SLOT), "l"(src + t * 1024), "r"(bytes), "r"(sb + BAR_FULLA + 8 * t) : "memory");
                    }
                }
            }
            return;
        }
        const int a = warp - 10;
        {
            const int row = 16 * j + 8 * a + (lane >> 2);
            const uint32_t ra = sb + OFF_A + row * 128;
            float sh = 0.f, s0 = 0.f, s1 = 0.f, q0 = 0.f, q1 = 0.f;
#pragma unroll 1
            for (int kt = 0; kt < 8; kt++) {
                mbar_wait(sb + BAR_FULLA + 8 * kt, 0);
                if (kt == 0) sh = bf_lo(lds128(ra + ((row & 7) << 4)).x);
#pragma unroll
                for (int i = 0; i < 2; i++) {
                    const uint4 v = lds128(ra + kt * SLOT + (((2 * (lane & 3) + i) ^ (row & 7)) << 4));
                    const uint32_t ww[4] = {v.x, v.y, v.z, v.w};
#pragma unroll
                    for (int e = 0; e < 4; e++) {
                        const float d0 = bf_lo(ww[e]) - sh, d1 = bf_hi(ww[e]) - sh;
                        s0 += d0; q0 = fmaf(d0, d0, q0);
                        s1 += d1; q1 = fmaf(d1, d1, q1);
                    }
                }
            }
            s0 += s1; q0 += q1;
#pragma unroll
            for (int o = 1; o <= 2; o <<= 1) { s0 += __shfl_xor_sync(0xffffffffu, s0, o); q0 += __shfl_xor_sync(0xffffffffu, q0, o); }
            const float md = s0 * (1.f / DM);
            const float rs = rsqrtf(fmaxf(q0 * (1.f / DM) - md * md, 0.f) + 1e-5f);
            st_tagged_if(g_xstat + 2 * (128 * m + row), rs, -(sh + md), epoch, (lane & 3) == 0);
            TL(1, lane == 0 && a == 0);
        }
        const unsigned long long* cs = g_cs + j * 768 + 2 * lane;
        {
            const unsigned long long* xs = g_xstat + 2 * (128 * m + 64 * a + lane);
            uint4 v0, v1, v2;
            uint32_t it = 0;
            __nanosleep(250);
            do {
                v0 = ld_tagged_rlx(xs); v1 = ld_tagged_rlx(xs + 64); v2 = ld_tagged_rlx(cs);
                trap_if_gt(++it, 1u << 22);
            } while (__any_sync(0xffffffffu, v0.y != epoch || v0.w != epoch || v1.y != epoch || v1.w != epoch || v2.y != epoch || v2.w != epoch));
            sts64(sb + OFF_XST + (64 * a + lane) * 8, v0.x, v0.z);
            sts64(sb + OFF_XST + (64 * a + 32 + lane) * 8, v1.x, v1.z);
            sts64(sb + OFF_CS1 + 256 + 8 * lane, v2.x, v2.z);
            mbar_arrive(sb + BAR_CS1);
            TL(22 + a, lane == 0);
            fetch_tagged(cs + 128 + 128 * a, sb + OFF_CS1 + 512 - 512 * a + 8 * lane, epoch, 200);
            mbar_arrive(sb + BAR_CSV - 8 * a);
            TL(24 + a, lane == 0);
        }
        {
            mbar_wait(sb + BAR_KVW, 0);
            const float* src = acc_j + 4 * (128 * a + lane);
            float4 v[12];
            uint32_t it = 0;
            bool bad;
            while (__any_sync(0xffffffffu, readback(acc_j + 2048 + 128 * (lane & 7) + 127) != 0x41800000u)) trap_if_gt(++it, 1u << 22);
            TL(19, lane == 0 && a == 0);
            do {
                bad = false;
#pragma unroll
                for (int i = 0; i < 12; i++) v[i] = ld_l2_f4(src + 1024 * (i % 3) + 128 * (i / 3));
#pragma unroll
                for (int i = 0; i < 12; i++) bad |= v[i].w != 16.f;
                trap_if_gt(++it, 1u << 22);
            } while (__any_sync(0xffffffffu, bad));
            TL(14, lane == 0 && a == 0);
            const uint32_t d0 = sb + OFF_A + (j < 2 ? 2 * SLOT : 0) + 8192 + (64 * a + (lane >> 2)) * 48;
            const uint32_t d = d0 + (lane & 3) * 4, dz = d0 + (lane & 1) * 384 + 32 + (lane & 2) * 4;
#pragma unroll
            for (int u = 0; u < 4; u++) {
                sts32(d + 768 * u, pack_bf16(v[3 * u].x, v[3 * u].y));
                sts32(d + 768 * u + 384, pack_bf16(v[3 * u].z, v[3 * u + 1].z));
                sts32(d + 768 * u + 16, pack_bf16(v[3 * u + 1].x, v[3 * u + 1].y));
                sts32(d + 768 * u + 400, pack_bf16(v[3 * u + 2].x, v[3 * u + 2].y));
                const uint32_t z2 = pack_bf16(v[3 * u + 2].z, v[3 * u + 2].z);
                sts64(dz + 768 * u, z2, z2);
            }
            mbar_arrive(sb + BAR_KVR);
        }
#pragma unroll 1
        for (int c = 0; c < 3; c++) {
            fetch_tagged(cs + 384 + 128 * c + 64 * a, sb + OFF_CS3 + (32 * c + lane) * 16 + 8 * a, epoch, 1000);
            mbar_arrive(sb + BAR_CSG + 8 * c);
        }
        {
            uint32_t it = 0;
            while (__any_sync(0xffffffffu, (int)(readback(g_flag + (m * 7 + 2 + (lane & 1)) * 32) - epoch * 32) < 0)) {
                __nanosleep(600);
                trap_if_gt(++it, 1u << 22);
            }
#pragma unroll 1
            for (int rr = 0; rr < 2; rr++) {
                const int row = 64 * rr + 32 * a + lane;
                const unsigned long long* hs = g_hstat + (1024 * m + row) * 2;
                uint4 v[8];
                bool bad;
                do {
                    bad = false;
#pragma unroll
                    for (int i = 0; i < 8; i++) v[i] = ld_tagged_rlx(hs + 256 * i);
#pragma unroll
                    for (int i = 0; i < 8; i++) bad |= v[i].y != epoch || v[i].w != epoch;
                    trap_if_gt(++it, 1u << 22);
                } while (__any_sync(0xffffffffu, bad));
                float mean = 0.f;
#pragma unroll
                for (int i = 0; i < 8; i++) mean += __uint_as_float(v[i].x);
                mean *= 0.125f;
                float m2 = 0.f, dv = 0.f;
#pragma unroll
                for (int i = 0; i < 8; i++) { const float d = __uint_as_float(v[i].x) - mean; m2 += __uint_as_float(v[i].z); dv = fmaf(d, d, dv); }
                sts_f2(sb + OFF_CS1 + row * 8, -mean, rcp(fmaf(dv, 64.f, m2) * (1.f / DM) + 1e-5f));
            }
        }
        mbar_arrive(sb + BAR_CS3);
#pragma unroll 1
        for (int c = a; c < 3; c += 2) {
            mbar_wait(sb + BAR_STG + 8 * c, 0);
            if (elect_one()) {
                asm volatile("cp.async.bulk.global.shared::cta.bulk_group [%0], [%1], %2;" ::"l"(g_act + ((2 + c) * 128 + role) * 1024), "r"(sb + OFF_B + 4 * SLOT), "r"(c == 2 ? 12288 : SLOT) : "memory");
                asm volatile("cp.async.bulk.commit_group;" ::: "memory");
                asm volatile("cp.async.bulk.wait_group.read 0;" ::: "memory");
                mbar_arrive(sb + BAR_FULLB + 8 * 4);
                asm volatile("cp.async.bulk.wait_group 0;" ::: "memory");
            }
            __syncwarp();
            TL(60 + c, lane == 0);
            uint32_t ack = 0;
            const uint4* rb = g_act + ((2 + c) * 128 + role) * 1024 + lane * 8;
#pragma unroll
            for (int i = 0; i < 4; i++) ack |= readback(rb + (i == 3 && c == 2 ? 0 : 256 * i));
            signal_after(g_flag + (m * 7 + 4 + c) * 32, ack, P.zero, lane == 0);
            TL(54 + c, lane == 0);
        }
        return;
    }
    const unsigned epoch = ld_relaxed(&g_epoch);
    uint32_t wraw[16];
    if (!helper) {
        const uint32_t* wp = reinterpret_cast<const uint32_t*>(P.wphi) + (4 * j) * 128 + (lane & 3) * 16 + (lane >> 2);
#pragma unroll
        for (int i = 0; i < 16; i++)
            asm volatile("ld.global.nc.u32 %0, [%1];" : "=r"(wraw[i]) : "l"(wp + (i >> 2) * 128 + ((i >> 1) & 1) * 64 + (i & 1) * 8));
    }
    asm volatile("barrier.cluster.arrive.relaxed.aligned;" ::: "memory");
    asm volatile("setmaxnreg.inc.sync.aligned.u32 216;");
    bar_sync(0, NTHREADS);
    if (helper) {
        const int w = warp >> 2;
        sts64(sb + OFF_B + 8 * tid, 0x3f803f80u, 0x3f803f80u);
        fence_async_smem();
        uint32_t zack[6];
        {
            float* z = g_acc + 2 * j * ACC_SIZE + 4 * tid;
#pragma unroll
            for (int u = 0; u < 6; u++) stg128(z + 1024 * u, 0, 0, 0, 0);
#pragma unroll
            for (int u = 0; u < 6; u++) zack[u] = readback(z + 1024 * u);
        }
        bar_sync(1, 256);
        float acc[8];
        int i = w;
#pragma unroll 1
        for (int job = 0; job < 6; job++) {
            const int n = job < 3 ? 4 : 8;
#pragma unroll 1
            for (int t = 0; t < n; t++, i += 2) {
                mbar_waitc(sb + BAR_FULLA + 8 * (i & 7), (i >> 3) & 1);
                const desc_t da = desc_lo(sb + OFF_A) + (i & 7) * (SLOT >> 4);
                wg_fence();
#pragma unroll
                for (int k = 0; k < 8; k++) wgmma_n8_tt(acc + (k & 4), da + 128 * k, desc_lo(sb + OFF_B), (t | (k & 3)) != 0);
                wg_commit();
                wg_wait<0>();
                mbar_arrive_n_if(sb + BAR_EMPTYA + 8 * (i & 7), 2, lane == 0);
            }
            fence_acc<8>(acc);
            if (job == 1) {
                asm volatile("{.reg .pred p; .reg .b32 t; lop3.b32 t, %0, %1, %2, 0xfe; lop3.b32 t, t, %3, %4, 0xfe; or.b32 t, t, %5; setp.ne.u32 p, t, 0; @p trap;}"
                             ::"r"(zack[0]), "r"(zack[1]), "r"(zack[2]), "r"(zack[3]), "r"(zack[4]), "r"(zack[5]));
                bar_sync(1, 256);
            }
            const int q = lane & 3;
            const float lo = (q & 1) ? acc[2] : acc[0], hi = (q & 1) ? acc[6] : acc[4];
            const float v = job < 3 ? lo + hi : ((q & 2) ? hi : lo);
            unsigned long long* dst = g_cs + ((2 * j + w) * 6 + job) * 128 + (q >> 1) * 64 + 16 * (warp & 3) + 8 * (q & 1) + (lane >> 2);
            asm volatile("st.relaxed.gpu.global.b64 [%0], %1;" ::"l"(dst), "l"(((unsigned long long)epoch << 32) | __float_as_uint(v)) : "memory");
        }
        return;
    }
    {
        const int w = warp >> 2, wv = warp & 3, g = lane >> 2, q = lane & 3;
        const uint32_t sa = sb + OFF_A + w * 8192;
        const desc_t dA = desc_lo(sa), dB = desc_lo(sb + OFF_B);
        unsigned* const flag_m = g_flag + (m * 7 + w) * 32;
        const uint32_t fullh = sb + (w ? BAR_FULLH : BAR_FULLA);
        const bool l0 = lane == 0, l2 = lane < 2;
        const uint32_t eb = mapa(sb + BAR_EMPTYB, lane & 1);
        asm volatile("barrier.cluster.wait.aligned;" ::: "memory");
        Ring rg{0, 0};
        int prev = 0;

        uint32_t wb[16];
        constexpr float L2E = 1.4426950408889634f;
        const int ch = lane >> 4, sw = lane & 7;
        const uint32_t lrow = (lane & 15) * 128;
        uint32_t fp[16], fm[16];
        const int vs = j < 2 ? 2 : 0;
        {
            float acc[64];
#pragma unroll 1
            for (int kt = 0; kt < 8; kt++) {
                mbar_waitc(sb + BAR_FULLA + 8 * kt, 0);
                mbar_waitc(sb + BAR_FULLB + 8 * rg.slot, rg.phase);
                const desc_t da = dA + kt * (SLOT >> 4), db = dB + rg.slot * (SLOT >> 4);
                wg_fence();
#pragma unroll
                for (int k = 0; k < 4; k++) wgmma_n128(acc, da + 2 * k, db + 128 * k, (kt | k) != 0);
                wg_commit();
                wg_wait<1>();
                mbar_arrive_cl_if(eb + 8 * prev, l2 && kt > 0);
                prev = rg.slot; rg.adv();
            }
#pragma unroll
            for (int i = 0; i < 8; i++) {
                wb[(i >> 1) * 4 + (i & 1)] = __byte_perm(wraw[2 * i], wraw[2 * i + 1], 0x5410);
                wb[(i >> 1) * 4 + 2 + (i & 1)] = __byte_perm(wraw[2 * i], wraw[2 * i + 1], 0x7632);
            }
            uint32_t a[16];
            float accq[32];
            mbar_waitc(sb + BAR_FULLB + 8 * 2, 1);
            wg_fence();
#pragma unroll
            for (int k = 0; k < 8; k++) wgmma_n64(accq, dA + (vs + (k >> 2)) * (SLOT >> 4) + (k & 3) * 2, dB + 2 * (SLOT >> 4) + 128 * k, k != 0);
            wg_commit();
            wg_wait<1>();
            fence_acc<64>(acc);
            mbar_arrive_cl_if(eb + 8 * prev, l2);
            TL(17, tid == 0);
            mbar_waitc(sb + BAR_CS1, 0);
            const float2 s0 = lds_f2(sb + OFF_XST + (16 * warp + g) * 8), s1 = lds_f2(sb + OFF_XST + (16 * warp + g + 8) * 8);
            wg_wait<0>();
            fence_acc<32>(accq);
            mbar_arrive_cl_if(eb + 8 * 2, l2);
            TL(2, tid == 0);
            const uint32_t st = sb + OFF_B + warp * 2048 + lrow;
#pragma unroll
            for (int hh = 0; hh < 4; hh++)
                ln_frag<false>(acc + 8 * hh, sb + OFF_CS1 + (64 + 16 * hh + 2 * q) * 4, 0.f, s0.y, 0.f, s1.y, a + 4 * hh);
#pragma unroll 1
            for (int it = 0; it < 2; it++) {
                feature_maps(a, wb, s0.x * L2E, s1.x * L2E, fp, fm);
                if (it == 0) {
                    mbar_waitc(sb + BAR_FULLB + 8 * 3, 1); mbar_waitc(sb + BAR_FULLB + 8 * 4, 1);
                    mbar_waitc(sb + BAR_CSV, 0);
                    const uint32_t sv = sb + OFF_A + vs * SLOT + warp * 2048 + lrow;
#pragma unroll
                    for (int hh = 0; hh < 4; hh++) {
                        stsm4(st + (3 + (hh >> 1)) * SLOT + (((4 * (hh & 1) + ch) ^ sw) << 4), fp[4 * hh], fp[4 * hh + 1], fp[4 * hh + 2], fp[4 * hh + 3]);
                        stsm4(st + (3 + (hh >> 1)) * SLOT + (((4 * (hh & 1) + 2 + ch) ^ sw) << 4), fm[4 * hh], fm[4 * hh + 1], fm[4 * hh + 2], fm[4 * hh + 3]);
                        ln_frag<true>(acc + 32 + 8 * hh, sb + OFF_CS1 + (128 + 16 * hh + 2 * q) * 4, s0.x, s0.y, s1.x, s1.y, a);
                        stsm4(sv + (hh >> 1) * SLOT + (((2 * (hh & 1) + ch) ^ sw) << 4), a[0], a[1], a[2], a[3]);
                    }
                    stsm4(sv + ch * SLOT + ((4 ^ sw) << 4), 0x3f803f80u, 0x3f803f80u, 0x3f803f80u, 0x3f803f80u);
                    fence_async_smem();
                    bar_sync(1, 256);
                    float kvd[20];
                    wg_fence();
#pragma unroll
                    for (int k = 0; k < 8; k++)
                        wgmma_n40_tt(kvd, dB + (3 + w) * (SLOT >> 4) + 128 * k, desc_lo(sb + OFF_A) + (vs + w) * (SLOT >> 4) + 128 * k, k != 0);
                    wg_commit();
                    wg_wait<0>();
                    fence_acc<20>(kvd);
                    mbar_arrive_cl_if(eb + 8 * (3 + (lane >> 1)), lane < 4);
                    const bool h1 = wv >= 2;
                    float* kvp = acc_j + 4 * tid;
                    red_f32x4(kvp, h1 ? kvd[8] : kvd[0], h1 ? kvd[9] : kvd[1], h1 ? kvd[10] : kvd[2], 1.f);
                    red_f32x4(kvp + 1024, h1 ? kvd[12] : kvd[4], h1 ? kvd[13] : kvd[5], h1 ? kvd[11] : kvd[3], 1.f);
                    red_f32x4(kvp + 2048, h1 ? kvd[14] : kvd[6], h1 ? kvd[15] : kvd[7], (q & 1) ? kvd[18] : kvd[16], 1.f);
                    mbar_arrive_if(sb + BAR_KVW, l0);
                    TL(3, tid == 0);
#pragma unroll 1
                    for (int b = 1; b < 4; b++) {
                        const int slot = b == 1 ? 5 : b - 2;
                        mbar_waitc(sb + BAR_FULLB + 8 * slot, b == 1);
                        const desc_t da = dA + (b == 1 ? 2 - vs : 2 * b) * (SLOT >> 4), db = dB + slot * (SLOT >> 4);
                        wg_fence();
#pragma unroll
                        for (int k = 0; k < 8; k++) wgmma_n64(accq, da + (k >> 2) * (SLOT >> 4) + (k & 3) * 2, db + 128 * k, 1);
                        wg_commit();
                    }
                    mbar_waitc(sb + BAR_CSQ, 0);
                    wg_wait<0>();
                    fence_acc<32>(accq);
                    mbar_arrive_cl_if(eb + 8 * ((5 + (lane >> 1)) % 6), lane < 6);
                    TL(4, tid == 0);
#pragma unroll
                    for (int hh = 0; hh < 4; hh++)
                        ln_frag<false>(accq + 8 * hh, sb + OFF_CS1 + (16 * hh + 2 * q) * 4, 0.f, s0.y, 0.f, s1.y, a + 4 * hh);
                }
            }
        }
        uint32_t res_lo[8], res_hi[8], ack[4];
        const uint32_t own_rows = sb + OFF_A + j * SLOT + warp * 2048;
#pragma unroll
        for (int b = 0; b < 4; b++)
            ldsm4(own_rows + lrow + (((2 * b + ch) ^ sw) << 4), res_lo[2 * b], res_hi[2 * b], res_lo[2 * b + 1], res_hi[2 * b + 1]);
        TL(5, tid == 0); TL(26, tid == 128);
        mbar_waitc(sb + BAR_KVR, 0);
        TL(6, tid == 0);
        {
            const uint32_t kvs = sb + OFF_A + vs * SLOT + 8192;
            uint32_t o_lo[8], o_hi[8];
#pragma unroll
            for (int hh = 0; hh < 4; hh++) {
                uint32_t b[8], zb[4];
                const uint32_t base = kvs + hh * 32 * 48;
                ldsm4t(base + (lane & 15) * 48 + (lane >> 4) * 16, b[0], b[1], b[2], b[3]);
                ldsm4t(base + (16 + (lane & 15)) * 48 + (lane >> 4) * 16, b[4], b[5], b[6], b[7]);
                ldsm4t(base + lane * 48 + 32, zb[0], zb[1], zb[2], zb[3]);
                float n0[4], n1[4], dn[4];
                mma16816_z(n0, fp + 4 * hh, b[0], b[1]); mma16816_z(n1, fp + 4 * hh, b[2], b[3]); mma16816_z(dn, fp + 4 * hh, zb[0], zb[1]);
                mma16816(n0, fm + 4 * hh, b[4], b[5]); mma16816(n1, fm + 4 * hh, b[6], b[7]); mma16816(dn, fm + 4 * hh, zb[2], zb[3]);
                const float i0 = rcp(dn[0] + 1e-6f), i1 = rcp(dn[2] + 1e-6f);
                o_lo[2 * hh] = pack_bf16(n0[0] * i0, n0[1] * i0); o_hi[2 * hh] = pack_bf16(n0[2] * i1, n0[3] * i1);
                o_lo[2 * hh + 1] = pack_bf16(n1[0] * i0, n1[1] * i0); o_hi[2 * hh + 1] = pack_bf16(n1[2] * i1, n1[3] * i1);
            }
            __syncwarp();
            mbar_arrive_if(sb + BAR_KVW, l0);
            store_tile(own_rows, g_act + role * 1024 + warp * 128 + lane, o_lo, o_hi, lane, ack);
            TL(7, tid == 0); TL(27, tid == 128);
        }
        float acch[32];
        {
            float* acc = acch;
#pragma unroll
            for (int t = 0; t < 8; t++) {
                acc[4 * t] = bf_lo(res_lo[t]); acc[4 * t + 1] = bf_hi(res_lo[t]);
                acc[4 * t + 2] = bf_lo(res_hi[t]); acc[4 * t + 3] = bf_hi(res_hi[t]);
            }
            fence_acc<32>(acc);
#pragma unroll
            for (int i = 2; i < 6; i++) mbar_waitc(sb + BAR_FULLB + 8 * i, 0);
#pragma unroll 1
            for (int i = 0; i < 8; i++) {
                const int kt = KORD(i, j);
                mbar_waitc(fullh + 8 * kt, (i != 0) ^ w);
                TL(8, i == 1 && tid == 0);
                const desc_t da = dA + kt * (SLOT >> 4), db = dB + (4 + i) * (SLOT >> 5);
                wg_fence();
#pragma unroll
                for (int k = 0; k < 4; k++) wgmma_n64(acc, da + 2 * k, db + 128 * k, 1);
                wg_commit();
                if (i == 0) { signal_late(flag_m, ack, P.zero, l0); TL(20, tid == 0); }
            }
            wg_wait<0>();
            fence_acc<32>(acc);
            mbar_arrive_cl_if(eb + 8 * (2 + (lane >> 1)), lane < 8);
            rg.slot = 0; rg.phase = 1;
            TL(9, tid == 0); TL(29, tid == 128);
#pragma unroll
            for (int t = 0; t < 8; t++) {
                res_lo[t] = pack_bf16(acc[4 * t], acc[4 * t + 1]);
                res_hi[t] = pack_bf16(acc[4 * t + 2], acc[4 * t + 3]);
            }
            store_tile(own_rows, g_act + (128 + role) * 1024 + warp * 128 + lane, res_lo, res_hi, lane, ack);
            TL(10, tid == 0);
        }
        float acc0[64], acc1[64], acc2[56], nm0, nm1;
        float4 cs[8];
        uint32_t hr[16];
#define P3_GROUP(MMA, ACC, KT)                                                                              \
        mbar_waitc(sb + BAR_FULLB + 8 * rg.slot, rg.phase);                                                 \
        {                                                                                                   \
            const desc_t da = dA + (KT) * (SLOT >> 4), db = dB + rg.slot * (SLOT >> 4);                     \
            wg_fence();                                                                                     \
            _Pragma("unroll") for (int k = 0; k < 4; k++) MMA(ACC, da + 2 * k, db + 128 * k, (i | k) != 0); \
            wg_commit();                                                                                    \
        }
#define P3_CS(C, NT, I0)    \
        _Pragma("unroll") for (int t = 0; t < (NT); t++) lds_f4_if(cs[t], sb + OFF_CS3 + q * 16 + 512 * (C) + 64 * t, i == min(t + (I0), 7));
        const uint32_t stg = sb + OFF_B + 4 * SLOT + warp * 2048;
        const uint32_t blk = ((lane & 7) + (lane >> 4) * 8) * 128 + (((2 * wv + ((lane >> 3) & 1)) ^ (lane & 7)) << 4);
        {
            mbar_waitc(sb + BAR_FULLB, 1); mbar_waitc(sb + BAR_FULLB + 8, 1);
            const desc_t da = dA + j * (SLOT >> 4);
            wg_fence();
#pragma unroll
            for (int k = 0; k < 4; k++) wgmma_n128(acc0, da + 2 * k, dB + 128 * k, k != 0);
            wg_commit();
            signal_late(flag_m + 64, ack, P.zero, l0);
            TL(21, tid == 0);
            wg_fence();
#pragma unroll
            for (int k = 0; k < 4; k++) wgmma_n128(acc1, da + 2 * k, dB + (SLOT >> 4) + 128 * k, k != 0);
            wg_commit();
            const float* acc = acch;
            float s0 = 0.f, s1 = 0.f;
#pragma unroll
            for (int t = 0; t < 8; t++) { s0 += acc[4 * t] + acc[4 * t + 1]; s1 += acc[4 * t + 2] + acc[4 * t + 3]; }
            s0 += __shfl_xor_sync(0xffffffffu, s0, 1); s1 += __shfl_xor_sync(0xffffffffu, s1, 1);
            s0 += __shfl_xor_sync(0xffffffffu, s0, 2); s1 += __shfl_xor_sync(0xffffffffu, s1, 2);
            const float mu0 = s0 * (1.f / 64), mu1 = s1 * (1.f / 64);
            float q0 = 0.f, q1 = 0.f;
#pragma unroll
            for (int t = 0; t < 8; t++) {
                float d;
                d = acc[4 * t] - mu0; q0 = fmaf(d, d, q0);
                d = acc[4 * t + 1] - mu0; q0 = fmaf(d, d, q0);
                d = acc[4 * t + 2] - mu1; q1 = fmaf(d, d, q1);
                d = acc[4 * t + 3] - mu1; q1 = fmaf(d, d, q1);
            }
            q0 += __shfl_xor_sync(0xffffffffu, q0, 1); q1 += __shfl_xor_sync(0xffffffffu, q1, 1);
            q0 += __shfl_xor_sync(0xffffffffu, q0, 2); q1 += __shfl_xor_sync(0xffffffffu, q1, 2);
            st_tagged_if(g_hstat + (role * 128 + 16 * warp + g + 8 * (q & 1)) * 2, q ? mu1 : mu0, q ? q1 : q0, epoch, q < 2);
            wg_wait<0>();
            mbar_arrive_cl_if(eb + 8 * (lane >> 1), lane < 4);
            bar_sync(2 + w, 128);
#pragma unroll
            for (int tp = 0; tp < 4; tp++) ldsm4t(sa + j * SLOT + blk + tp * 2048, hr[4 * tp], hr[4 * tp + 1], hr[4 * tp + 2], hr[4 * tp + 3]);
            mbar_waitc(sb + BAR_CSG, 0);
#pragma unroll
            for (int t = 0; t < 8; t++) cs[t] = lds_f4(sb + OFF_CS3 + q * 16 + 64 * t);
            rg.slot = 2;
        }
#pragma unroll 1
        for (int i = 1; i < 8; i++) {
            const int kt = KORD(i, j);
            mbar_waitc(fullh + 8 * kt, w);
            TL(44 + w, (tid & 127) == 0 && i == 1);
            P3_GROUP(wgmma_n128, acc0, kt)
            if (i == 7) {
                mbar_waitc(sb + BAR_CS3, 0);
                nm0 = lds_f2(sb + OFF_CS1 + (16 * warp + g) * 8).x; nm1 = lds_f2(sb + OFF_CS1 + (16 * warp + g + 8) * 8).x;
            }
            wg_wait<1>();
            mbar_arrive_cl_if(eb + 8 * prev, l2 && i > 1);
            prev = rg.slot; rg.adv5();
        }
#pragma unroll 1
        for (int i = 1; i < 8; i++) {
            P3_GROUP(wgmma_n128, acc1, KORD(i, j))
            wg_wait<1>();
            mbar_arrive_cl_if(eb + 8 * prev, l2);
            if (i == 1) {
                fence_acc<64>(acc0);
                hh_stage2<0, 2>(acc0, cs, nm0, nm1, stg, lane);
                mbar_waitc(sb + BAR_CSG + 8, 0);
            }
            if (i == 2) {
                hh_stage2<2, 4>(acc0, cs, nm0, nm1, stg, lane);
                fence_async_smem();
                __syncwarp();
                mbar_arrive_if(sb + BAR_STG, l0);
            }
            P3_CS(1, 8, 1)
            prev = rg.slot; rg.adv5();
        }
#pragma unroll 1
        for (int i = 0; i < 8; i++) {
            P3_GROUP(wgmma_n112, acc2, i)
            wg_wait<1>();
            mbar_arrive_cl_if(eb + 8 * prev, l2);
            mbar_arrive_if(sb + BAR_EMPTYA + 8 * ((i + 7) & 7), l0 && i > 0);
            if (i == 0) {
                mbar_waitc(sb + BAR_FULLB + 8 * 4, 1);
                fence_acc<64>(acc1);
                TL(12, tid == 0);
                hh_stage2<0, 4>(acc1, cs, nm0, nm1, stg, lane);
                fence_async_smem();
                __syncwarp();
                mbar_arrive_if(sb + BAR_STG + 8, l0);
                mbar_waitc(sb + BAR_CSG + 16, 0);
            }
            P3_CS(2, 6, 0)
            prev = rg.slot; rg.adv5();
        }
        mbar_waitc(sb + BAR_FULLB + 8 * 4, 0);
        wg_wait<0>();
        mbar_arrive_cl_if(eb + 8 * prev, l2);
        mbar_arrive_if(sb + BAR_EMPTYA + 8 * 7, l0);
        fence_acc<56>(acc2);
        TL(13, tid == 0);
#pragma unroll
        for (int tp = 0; tp < 3; tp++)
            stsm4(sb + OFF_B + 4 * SLOT + tp * 4096 + warp * 512 + (lane & 15) * 32 + ((ch ^ ((lane >> 2) & 1)) << 4),
                  hh_pair<32>(acc2 + 8 * tp, cs[2 * tp], nm0), hh_pair<32>(acc2 + 8 * tp + 2, cs[2 * tp], nm1),
                  hh_pair<32>(acc2 + 8 * tp + 4, cs[2 * tp + 1], nm0), hh_pair<32>(acc2 + 8 * tp + 6, cs[2 * tp + 1], nm1));
        fence_async_smem();
        __syncwarp();
        mbar_arrive_if(sb + BAR_STG + 16, l0);
        TL(52, tid == 0);
        {
            float acc[64];
            const desc_t dA0 = desc_lo(sb + OFF_A);
#define KT_P4(I, NK, DH, STEP)                                                                                   \
        const int s_ = (2 * (I) + w) & 7;                                                                   \
        mbar_waitc(sb + BAR_FULLB + 8 * rg.slot, rg.phase);                                                 \
        mbar_waitc(sb + BAR_FULLA + 8 * s_, (((I) >> 2) + 1) & 1);                                          \
        const desc_t dh_ = (DH) + s_ * (SLOT >> 4), dw_ = dB + rg.slot * (SLOT >> 4) + w * 512;              \
        wg_fence();                                                                                         \
        _Pragma("unroll") for (int k = 0; k < (NK); k++) wgmma_n128_tn(acc, dw_ + 128 * k, dh_ + (STEP) * k, ((I) | k) != 0); \
        wg_commit();
#pragma unroll 1
            for (int i = 0; i < 8; i++) {
                KT_P4(i, 4, dA0, 2)
#pragma unroll
                for (int t = 0; t < 8; t++) lds_f4_if(cs[t], sb + OFF_CS1 + (64 * w + 8 * t + 2 * q) * 8, i == t);
                wg_wait<0>();
                mbar_arrive_n_if(sb + BAR_EMPTYA + 8 * s_, 2, l0);
                mbar_arrive_cl_if(eb + 8 * rg.slot, l2 && i < 7);
                rg.adv5();
            }
#pragma unroll 1
            for (int i = 8; i < 12; i++) {
                KT_P4(i, 3, dA0 + ((0xC0000010ull - 0x40000040ull) << 32), 256)
                wg_wait<1>();
                rg.adv5();
            }
            wg_wait<0>();
            fence_acc<64>(acc);
            TL(15, tid == 0);
            const uint32_t xch = sb + OFF_A + 2 * SLOT + (tid & 127) * 16;
            if (w) {
#pragma unroll
                for (int t = 0; t < 8; t++) {
                    sts128(xch + SLOT + t * 2048, __float_as_uint(acc[4 * t]), __float_as_uint(acc[4 * t + 1]),
                           __float_as_uint(acc[4 * t + 2]), __float_as_uint(acc[4 * t + 3]));
                }
#pragma unroll
                for (int t = 0; t < 32; t++) acc[t] = acc[32 + t];
            } else {
#pragma unroll
                for (int t = 0; t < 8; t++)
                    sts128(xch + t * 2048, __float_as_uint(acc[32 + 4 * t]), __float_as_uint(acc[33 + 4 * t]),
                           __float_as_uint(acc[34 + 4 * t]), __float_as_uint(acc[35 + 4 * t]));
            }
            bar_sync(1, 256);
            float4 o[8];
#pragma unroll
            for (int t = 0; t < 8; t++) o[t] = lds_f4(xch + (w ^ 1) * SLOT + t * 2048);
            const uint32_t tile = sb + OFF_A + w * SLOT;
#pragma unroll
            for (int t = 0; t < 8; t++) {
                hr[2 * t] = pack_bf16(fmaf(acc[4 * t] + o[t].x, cs[t].y, bf_lo(hr[2 * t])), fmaf(acc[4 * t + 1] + o[t].y, cs[t].w, bf_hi(hr[2 * t])));
                hr[2 * t + 1] = pack_bf16(fmaf(acc[4 * t + 2] + o[t].z, cs[t].y, bf_lo(hr[2 * t + 1])), fmaf(acc[4 * t + 3] + o[t].w, cs[t].w, bf_hi(hr[2 * t + 1])));
            }
#pragma unroll
            for (int tp = 0; tp < 4; tp++) stsm4t(tile + blk + tp * 2048, hr[4 * tp], hr[4 * tp + 1], hr[4 * tp + 2], hr[4 * tp + 3]);
            fence_async_smem();
            bar_sync(2 + w, 128);
            if ((tid & 127) == 0) {
                tma_store2d(&P.tout, tile, 64 * j, 128 * m + 64 * w);
                asm volatile("cp.async.bulk.wait_group.read 0;" ::: "memory");
            }
            if (tid == 0 && role == 0) g_epoch = epoch + 1;
            TL(16, tid == 0); TLG(1, tid == 0);
        }
    }
}

typedef CUresult (*EncodeFn)(CUtensorMap*, CUtensorMapDataType, cuuint32_t, void*, const cuuint64_t*, const cuuint64_t*,
                             const cuuint32_t*, const cuuint32_t*, CUtensorMapInterleave, CUtensorMapSwizzle,
                             CUtensorMapL2promotion, CUtensorMapFloatOOBfill);

static void make_map2d(EncodeFn enc, CUtensorMap* tm, const void* base, uint64_t cols, uint64_t rows, uint64_t pitch_elems,
                       uint32_t box_rows) {
    cuuint64_t gd[2] = {cols, rows};
    cuuint64_t gs[1] = {pitch_elems * 2};
    cuuint32_t bd[2] = {64, box_rows};
    cuuint32_t es[2] = {1, 1};
    enc(tm, CU_TENSOR_MAP_DATA_TYPE_BFLOAT16, 2, const_cast<void*>(base), gd, gs, bd, es, CU_TENSOR_MAP_INTERLEAVE_NONE,
        CU_TENSOR_MAP_SWIZZLE_128B, CU_TENSOR_MAP_L2_PROMOTION_L2_256B, CU_TENSOR_MAP_FLOAT_OOB_FILL_NONE);
}

}

extern "C" void kernel_launch(void* const* d_in, const int* in_sizes, int n_in, void* d_out, int out_size) {
    using namespace hk;
    (void)in_sizes; (void)n_in; (void)out_size;
    static EncodeFn enc = nullptr;
    if (!enc) {
        void* fn = nullptr;
        cudaDriverEntryPointQueryResult qr;
        cudaGetDriverEntryPoint("cuTensorMapEncodeTiled", &fn, cudaEnableDefault, &qr);
        enc = (EncodeFn)fn;
        cudaFuncSetAttribute(fused_kernel, cudaFuncAttributeMaxDynamicSharedMemorySize, SMEM_BYTES);
    }
    Params P;
    const __nv_bfloat16* x = (const __nv_bfloat16*)d_in[0];
    P.x = x;
    P.wqkv = (const __nv_bfloat16*)d_in[1];
    P.wphi = (const __nv_bfloat16*)d_in[2];
    P.wo = (const __nv_bfloat16*)d_in[3];
    P.wg = (const __nv_bfloat16*)d_in[5];
    P.wu = (const __nv_bfloat16*)d_in[6];
    P.wd = (const __nv_bfloat16*)d_in[7];
    P.out = (__nv_bfloat16*)d_out;
    P.zero = 0;
    make_map2d(enc, &P.tx, x, DM, SEQ, DM, 128);
    make_map2d(enc, &P.twq, P.wqkv, 3 * DM, DM, 3 * DM, 64);
    make_map2d(enc, &P.two, P.wo, DM, DM, DM, 64);
    make_map2d(enc, &P.twg, P.wg, FF, DM, FF, 64);
    make_map2d(enc, &P.twu, P.wu, FF, DM, FF, 64);
    make_map2d(enc, &P.twd, P.wd, DM, FF, DM, 64);
    make_map2d(enc, &P.twd48, P.wd, DM, FF, DM, 48);
    make_map2d(enc, &P.tout, d_out, DM, SEQ, DM, 64);
    fused_kernel<<<NCTA, NTHREADS, SMEM_BYTES>>>(P);
}
```

```cpp
#include <cuda_runtime.h>
#include <cuda_bf16.h>
#include <cuda.h>
#include <stdint.h>

namespace hk {

constexpr int SEQ = 2048, DM = 512, FF = 1376;
constexpr int NCTA = 132;
constexpr int NTHREADS = 384;
constexpr uint32_t SLOT = 16384;
constexpr uint32_t OFF_A = 0, OFF_B = 8 * SLOT, OFF_MISC = 14 * SLOT;
constexpr uint32_t BAR_FULLA = OFF_MISC + 0, BAR_EMPTYA = OFF_MISC + 64, BAR_FULLB = OFF_MISC + 128,
                   BAR_EMPTYB = OFF_MISC + 176, BAR_CS1 = OFF_MISC + 224, BAR_CS3 = OFF_MISC + 232,
                   BAR_CSQ = OFF_MISC + 240, BAR_CSV = OFF_MISC + 248,
                   BAR_STG = OFF_MISC + 256,
                   BAR_KVW = OFF_MISC + 280, BAR_KVR = OFF_MISC + 288,
                   BAR_CSG = OFF_MISC + 296,
                   BAR_FULLH = OFF_MISC + 320;
constexpr uint32_t OFF_CS1 = OFF_MISC + 384;
constexpr uint32_t OFF_CS3 = OFF_CS1 + 1024;
constexpr uint32_t OFF_XST = OFF_CS3;
constexpr uint32_t SMEM_BYTES = OFF_CS3 + 1536;
#define KORD(i, j) ((i) == 0 ? (j) : (i) - ((i) <= (j)))
constexpr int NB = 6;
constexpr int NPRE = 3, AHEAD = 3, AHEADA = 5;
constexpr int PF_DELAY = 2;

constexpr int ACC_SIZE = 3 * 256 * 4;

__device__ __align__(1024) uint4 g_act[5 * 128 * 1024];
__device__ __align__(128) unsigned long long g_hstat[SEQ * 16];
__device__ __align__(128) unsigned long long g_xstat[SEQ * 2];
__device__ __align__(128) float g_acc[8 * ACC_SIZE];
__device__ __align__(128) unsigned long long g_cs[8 * 6 * 128];
__device__ __align__(128) unsigned g_flag[16 * 7 * 32];
__device__ unsigned g_epoch = 1;

#define TL(i, pred) do {} while (0)
#define TLG(i, pred) do {} while (0)

struct Params {
    CUtensorMap tx, twq, two, twg, twu, twd, twd48, tout;
    const __nv_bfloat16 *x, *wqkv, *wphi, *wo, *wg, *wu, *wd;
    __nv_bfloat16* out;
    unsigned zero;
};

__device__ __forceinline__ uint32_t smem_u32(const void* p) { return (uint32_t)__cvta_generic_to_shared(p); }
__device__ __forceinline__ void mbar_init(uint32_t bar, uint32_t cnt) {
    asm volatile("mbarrier.init.shared::cta.b64 [%0], %1;" ::"r"(bar), "r"(cnt) : "memory");
}
__device__ __forceinline__ void mbar_expect_tx(uint32_t bar, uint32_t bytes) {
    asm volatile("mbarrier.arrive.expect_tx.shared::cta.b64 _, [%0], %1;" ::"r"(bar), "r"(bytes) : "memory");
}
__device__ __forceinline__ void mbar_arrive(uint32_t bar) {
    asm volatile("mbarrier.arrive.shared::cta.b64 _, [%0];" ::"r"(bar) : "memory");
}
__device__ __forceinline__ void mbar_arrive_if(uint32_t bar, bool pred) {
    asm volatile("{.reg .pred p; setp.ne.u32 p, %1, 0; @p mbarrier.arrive.shared::cta.b64 _, [%0];}" ::"r"(bar), "r"((uint32_t)pred) : "memory");
}
__device__ __forceinline__ void trap_if_gt(uint32_t v, uint32_t lim) {
    asm volatile("{.reg .pred p; setp.gt.u32 p, %0, %1; @p trap;}" ::"r"(v), "r"(lim));
}
__device__ __forceinline__ void mbar_wait(uint32_t bar, uint32_t parity) {
    asm volatile("{\n"
                 ".reg .pred P1, P2;\n"
                 ".reg .u32 c;\n"
                 "mov.u32 c, 0;\n"
                 "LAB_WAIT:\n"
                 "mbarrier.try_wait.parity.shared::cta.b64 P1, [%0], %1;\n"
                 "@P1 bra LAB_DONE;\n"
                 "add.u32 c, c, 1;\n"
                 "setp.gt.u32 P2, c, 1048576;\n"
                 "@P2 trap;\n"
                 "bra LAB_WAIT;\n"
                 "LAB_DONE:\n"
                 "}" ::"r"(bar), "r"(parity) : "memory");
}
__device__ __forceinline__ void mbar_waitc(uint32_t bar, uint32_t parity) {
    asm volatile("{\n"
                 ".reg .pred P1;\n"
                 "LAB_WAIT:\n"
                 "mbarrier.try_wait.parity.shared::cta.b64 P1, [%0], %1;\n"
                 "@!P1 bra LAB_WAIT;\n"
                 "}" ::"r"(bar), "r"(parity) : "memory");
}
__device__ __forceinline__ void tma2d(uint32_t dst, const CUtensorMap* tm, uint32_t bar, int c0, int c1) {
    asm volatile("cp.async.bulk.tensor.2d.shared::cluster.global.mbarrier::complete_tx::bytes [%0], [%1, {%3, %4}], [%2];"
                 ::"r"(dst), "l"(tm), "r"(bar), "r"(c0), "r"(c1) : "memory");
}
__device__ __forceinline__ void tma2d_mc(uint32_t dst, const CUtensorMap* tm, uint32_t bar, int c0, int c1) {
    asm volatile("cp.async.bulk.tensor.2d.shared::cluster.global.mbarrier::complete_tx::bytes.multicast::cluster [%0], [%1, {%3, %4}], [%2], %5;"
                 ::"r"(dst), "l"(tm), "r"(bar), "r"(c0), "r"(c1), "h"((uint16_t)3) : "memory");
}
__device__ __forceinline__ uint32_t mapa(uint32_t addr, uint32_t rank) {
    uint32_t r; asm("mapa.shared::cluster.u32 %0, %1, %2;" : "=r"(r) : "r"(addr), "r"(rank)); return r;
}
__device__ __forceinline__ void mbar_arrive_cl_if(uint32_t cbar, bool pred) {
    asm volatile("{.reg .pred p; setp.ne.u32 p, %1, 0; @p mbarrier.arrive.shared::cluster.b64 _, [%0];}" ::"r"(cbar), "r"((uint32_t)pred) : "memory");
}
__device__ __forceinline__ bool elect_one() {
    uint32_t ok;
    asm volatile("{.reg .pred p; elect.sync _|p, 0xffffffff; selp.u32 %0, 1, 0, p;}" : "=r"(ok));
    return ok;
}
__device__ __forceinline__ void prefetch_tmap(const CUtensorMap* tm) {
    asm volatile("prefetch.tensormap [%0];" ::"l"(tm) : "memory");
}
__device__ __forceinline__ void prefetch_l2(const void* p, uint32_t bytes) {
    asm volatile("cp.async.bulk.prefetch.L2.global [%0], %1;" ::"l"(p), "r"(bytes) : "memory");
}
__device__ __forceinline__ unsigned ld_relaxed(const unsigned* p) {
    unsigned v; asm volatile("ld.relaxed.gpu.global.u32 %0, [%1];" : "=r"(v) : "l"(p)); return v;
}
__device__ __forceinline__ void fence_async_smem() { asm volatile("fence.proxy.async.shared::cta;" ::: "memory"); }
__device__ __forceinline__ uint32_t readback(const void* p) {
    uint32_t v; asm volatile("ld.relaxed.gpu.global.u32 %0, [%1];" : "=r"(v) : "l"(p) : "memory"); return v;
}
__device__ __forceinline__ void wait_count(const unsigned* p, unsigned target) {
    uint32_t it = 0;
    while ((int)(readback(p) - target) < 0) trap_if_gt(++it, 1u << 22);
}
__device__ __forceinline__ void red_f32x4(float* p, float a, float b, float c, float d) {
    asm volatile("red.relaxed.gpu.global.add.v4.f32 [%0], {%1, %2, %3, %4};" ::"l"(p), "f"(a), "f"(b), "f"(c), "f"(d) : "memory");
}
__device__ __forceinline__ float4 ld_l2_f4(const float* p) {
    float4 v;
    asm volatile("ld.relaxed.gpu.global.v4.f32 {%0,%1,%2,%3}, [%4];" : "=f"(v.x), "=f"(v.y), "=f"(v.z), "=f"(v.w) : "l"(p) : "memory");
    return v;
}
__device__ __forceinline__ void stg128(void* p, uint32_t a, uint32_t b, uint32_t c, uint32_t d) {
    asm volatile("st.global.v4.u32 [%0], {%1,%2,%3,%4};" ::"l"(p), "r"(a), "r"(b), "r"(c), "r"(d) : "memory");
}
__device__ __forceinline__ uint4 lds128(uint32_t a) {
    uint4 v;
    asm volatile("ld.shared.v4.u32 {%0,%1,%2,%3}, [%4];" : "=r"(v.x), "=r"(v.y), "=r"(v.z), "=r"(v.w) : "r"(a) : "memory");
    return v;
}
__device__ __forceinline__ float2 lds_f2(uint32_t a) {
    float2 v;
    asm volatile("ld.shared.v2.f32 {%0,%1}, [%2];" : "=f"(v.x), "=f"(v.y) : "r"(a) : "memory");
    return v;
}
__device__ __forceinline__ void sts_f2(uint32_t a, float x, float y) {
    asm volatile("st.shared.v2.f32 [%0], {%1,%2};" ::"r"(a), "f"(x), "f"(y) : "memory");
}
__device__ __forceinline__ void sts64(uint32_t a, uint32_t x, uint32_t y) {
    asm volatile("st.shared.v2.u32 [%0], {%1,%2};" ::"r"(a), "r"(x), "r"(y) : "memory");
}
__device__ __forceinline__ void sts128(uint32_t a, uint32_t x, uint32_t y, uint32_t z, uint32_t w) {
    asm volatile("st.shared.v4.u32 [%0], {%1,%2,%3,%4};" ::"r"(a), "r"(x), "r"(y), "r"(z), "r"(w) : "memory");
}
__device__ __forceinline__ void stsm4(uint32_t a, uint32_t r0, uint32_t r1, uint32_t r2, uint32_t r3) {
    asm volatile("stmatrix.sync.aligned.m8n8.x4.shared.b16 [%0], {%1,%2,%3,%4};" ::"r"(a), "r"(r0), "r"(r1), "r"(r2), "r"(r3) : "memory");
}
__device__ __forceinline__ void stsm4t(uint32_t a, uint32_t r0, uint32_t r1, uint32_t r2, uint32_t r3) {
    asm volatile("stmatrix.sync.aligned.m8n8.x4.trans.shared.b16 [%0], {%1,%2,%3,%4};" ::"r"(a), "r"(r0), "r"(r1), "r"(r2), "r"(r3) : "memory");
}
__device__ __forceinline__ void tma_store2d(const CUtensorMap* tm, uint32_t src, int c0, int c1) {
    asm volatile("cp.async.bulk.tensor.2d.global.shared::cta.bulk_group [%0, {%2, %3}], [%1];" ::"l"(tm), "r"(src), "r"(c0), "r"(c1) : "memory");
    asm volatile("cp.async.bulk.commit_group;" ::: "memory");
}
__device__ __forceinline__ void ldsm4(uint32_t a, uint32_t& r0, uint32_t& r1, uint32_t& r2, uint32_t& r3) {
    asm volatile("ldmatrix.sync.aligned.m8n8.x4.shared.b16 {%0,%1,%2,%3}, [%4];" : "=r"(r0), "=r"(r1), "=r"(r2), "=r"(r3) : "r"(a) : "memory");
}
__device__ __forceinline__ void ldsm4t(uint32_t a, uint32_t& r0, uint32_t& r1, uint32_t& r2, uint32_t& r3) {
    asm volatile("ldmatrix.sync.aligned.m8n8.x4.trans.shared.b16 {%0,%1,%2,%3}, [%4];" : "=r"(r0), "=r"(r1), "=r"(r2), "=r"(r3) : "r"(a) : "memory");
}
__device__ __forceinline__ void mma16816(float* c, const uint32_t* a, uint32_t b0, uint32_t b1) {
    asm("mma.sync.aligned.m16n8k16.row.col.f32.bf16.bf16.f32 {%0,%1,%2,%3}, {%4,%5,%6,%7}, {%8,%9}, {%0,%1,%2,%3};"
                 : "+f"(c[0]), "+f"(c[1]), "+f"(c[2]), "+f"(c[3])
                 : "r"(a[0]), "r"(a[1]), "r"(a[2]), "r"(a[3]), "r"(b0), "r"(b1));
}
__device__ __forceinline__ uint32_t pack_bf16(float lo, float hi) {
    uint32_t r; asm("cvt.rn.bf16x2.f32 %0, %1, %2;" : "=r"(r) : "f"(hi), "f"(lo)); return r;
}
__device__ __forceinline__ float bf_lo(uint32_t w) { return __uint_as_float(w << 16); }
__device__ __forceinline__ float bf_hi(uint32_t w) { return __uint_as_float(w & 0xffff0000u); }
__device__ __forceinline__ float ex2(float x) { float r; asm("ex2.approx.ftz.f32 %0, %1;" : "=f"(r) : "f"(x)); return r; }
__device__ __forceinline__ float rcp(float x) { float r; asm("rcp.approx.ftz.f32 %0, %1;" : "=f"(r) : "f"(x)); return r; }
__device__ __forceinline__ void bar_sync(int id, int n) { asm volatile("bar.sync %0, %1;" ::"r"(id), "r"(n) : "memory"); }

typedef unsigned long long desc_t;
__device__ __forceinline__ desc_t desc_lo(uint32_t addr) { return (desc_t)(((addr & 0x3FFFF) >> 4) | (512u << 16)) | (0x40000040ull << 32); }
__device__ __forceinline__ void wg_fence() { asm volatile("wgmma.fence.sync.aligned;" ::: "memory"); }
__device__ __forceinline__ void wg_commit() { asm volatile("wgmma.commit_group.sync.aligned;" ::: "memory"); }
template <int N> __device__ __forceinline__ void wg_wait() { asm volatile("wgmma.wait_group.sync.aligned %0;" ::"n"(N) : "memory"); }
template <int N> __device__ __forceinline__ void fence_acc(float* d) {
#pragma unroll
    for (int i = 0; i < N; i++) asm volatile("" : "+f"(d[i])::"memory");
}
#define R4(o) "+f"(d[o + 0]), "+f"(d[o + 1]), "+f"(d[o + 2]), "+f"(d[o + 3])
#define R8(o) R4(o), R4(o + 4)
__device__ __forceinline__ void wgmma_n128(float* d, desc_t da, desc_t db, int sc) {
    asm volatile("{.reg .pred p; setp.ne.b32 p, %66, 0;\n"
                 "wgmma.mma_async.sync.aligned.m64n128k16.f32.bf16.bf16 {%0,%1,%2,%3,%4,%5,%6,%7,%8,%9,%10,%11,%12,%13,%14,%15,%16,%17,%18,%19,%20,%21,%22,%23,%24,%25,%26,%27,%28,%29,%30,%31,"
                 "%32,%33,%34,%35,%36,%37,%38,%39,%40,%41,%42,%43,%44,%45,%46,%47,%48,%49,%50,%51,%52,%53,%54,%55,%56,%57,%58,%59,%60,%61,%62,%63}, %64, %65, p, 1, 1, 0, 1;}"
                 : R8(0), R8(8), R8(16), R8(24), R8(32), R8(40), R8(48), R8(56)
                 : "l"(da), "l"(db), "r"(sc));
}
__device__ __forceinline__ void wgmma_n112(float* d, desc_t da, desc_t db, int sc) {
    asm volatile("{.reg .pred p; setp.ne.b32 p, %58, 0;\n"
                 "wgmma.mma_async.sync.aligned.m64n112k16.f32.bf16.bf16 {%0,%1,%2,%3,%4,%5,%6,%7,%8,%9,%10,%11,%12,%13,%14,%15,%16,%17,%18,%19,%20,%21,%22,%23,%24,%25,%26,%27,%28,%29,%30,%31,%32,%33,%34,%35,%36,%37,%38,%39,%40,%41,%42,%43,%44,%45,%46,%47,%48,%49,%50,%51,%52,%53,%54,%55}, %56, %57, p, 1, 1, 0, 1;}"
                 : R8(0), R8(8), R8(16), R8(24), R8(32), R8(40), R8(48)
                 : "l"(da), "l"(db), "r"(sc));
}
__device__ __forceinline__ void wgmma_n128_tn(float* d, desc_t da, desc_t db, int sc) {
    asm volatile("{.reg .pred p; setp.ne.b32 p, %66, 0;\n"
                 "wgmma.mma_async.sync.aligned.m64n128k16.f32.bf16.bf16 {%0,%1,%2,%3,%4,%5,%6,%7,%8,%9,%10,%11,%12,%13,%14,%15,%16,%17,%18,%19,%20,%21,%22,%23,%24,%25,%26,%27,%28,%29,%30,%31,%32,%33,%34,%35,%36,%37,%38,%39,%40,%41,%42,%43,%44,%45,%46,%47,%48,%49,%50,%51,%52,%53,%54,%55,%56,%57,%58,%59,%60,%61,%62,%63}, %64, %65, p, 1, 1, 1, 0;}"
                 : R8(0), R8(8), R8(16), R8(24), R8(32), R8(40), R8(48), R8(56)
                 : "l"(da), "l"(db), "r"(sc));
}
__device__ __forceinline__ void wgmma_n64(float* d, desc_t da, desc_t db, int sc) {
    asm volatile("{.reg .pred p; setp.ne.b32 p, %34, 0;\n"
                 "wgmma.mma_async.sync.aligned.m64n64k16.f32.bf16.bf16 {%0,%1,%2,%3,%4,%5,%6,%7,%8,%9,%10,%11,%12,%13,%14,%15,%16,%17,%18,%19,%20,%21,%22,%23,%24,%25,%26,%27,%28,%29,%30,%31}, %32, %33, p, 1, 1, 0, 1;}"
                 : R8(0), R8(8), R8(16), R8(24)
                 : "l"(da), "l"(db), "r"(sc));
}
__device__ __forceinline__ void wgmma_n40_tt(float* d, desc_t da, desc_t db, int sc) {
    asm volatile("{.reg .pred p; setp.ne.b32 p, %22, 0;\n"
                 "wgmma.mma_async.sync.aligned.m64n40k16.f32.bf16.bf16 {%0,%1,%2,%3,%4,%5,%6,%7,%8,%9,%10,%11,%12,%13,%14,%15,%16,%17,%18,%19}, %20, %21, p, 1, 1, 1, 1;}"
                 : R8(0), R8(8), R4(16)
                 : "l"(da), "l"(db), "r"(sc));
}

__device__ __forceinline__ void wgmma_n8_tt(float* d, desc_t da, desc_t db, int sc) {
    asm volatile("{.reg .pred p; setp.ne.b32 p, %6, 0;\n"
                 "wgmma.mma_async.sync.aligned.m64n8k16.f32.bf16.bf16 {%0,%1,%2,%3}, %4, %5, p, 1, 1, 1, 1;}"
                 : R4(0)
                 : "l"(da), "l"(db), "r"(sc));
}

__device__ __forceinline__ void signal_after(unsigned* cnt, uint32_t ack, uint32_t zero, bool pred) {
    asm volatile("{.reg .pred p; setp.ne.u32 p, %2, 0; @p red.relaxed.gpu.global.add.u32 [%0], %1;}"
                 ::"l"(cnt), "r"((ack & zero) + 1), "r"((uint32_t)pred) : "memory");
}
__device__ __forceinline__ void signal_late(unsigned* cnt, const uint32_t* a, uint32_t zero, bool pred) {
    uint32_t v;
    asm volatile("{.reg .b32 t; lop3.b32 t, %1, %2, %3, 0xfe; or.b32 %0, t, %4;}"
                 : "=r"(v) : "r"(a[0]), "r"(a[1]), "r"(a[2]), "r"(a[3]));
    signal_after(cnt, v, zero, pred);
}
__device__ __forceinline__ void mma16816_z(float* c, const uint32_t* a, uint32_t b0, uint32_t b1) {
    asm("mma.sync.aligned.m16n8k16.row.col.f32.bf16.bf16.f32 {%0,%1,%2,%3}, {%4,%5,%6,%7}, {%8,%9}, {%10,%10,%10,%10};"
                 : "=f"(c[0]), "=f"(c[1]), "=f"(c[2]), "=f"(c[3])
                 : "r"(a[0]), "r"(a[1]), "r"(a[2]), "r"(a[3]), "r"(b0), "r"(b1), "f"(0.f));
}
__device__ __forceinline__ uint32_t max2(uint32_t a, uint32_t b) { uint32_t r; asm("max.bf16x2 %0, %1, %2;" : "=r"(r) : "r"(a), "r"(b)); return r; }
__device__ __forceinline__ uint32_t min2(uint32_t a, uint32_t b) { uint32_t r; asm("min.bf16x2 %0, %1, %2;" : "=r"(r) : "r"(a), "r"(b)); return r; }
__device__ __forceinline__ void mbar_arrive_n_if(uint32_t bar, uint32_t n, bool pred) {
    asm volatile("{.reg .pred p; setp.ne.u32 p, %1, 0; @p mbarrier.arrive.shared::cta.b64 _, [%0], %2;}" ::"r"(bar), "r"((uint32_t)pred), "r"(n) : "memory");
}
__device__ __forceinline__ float4 lds_f4(uint32_t a) {
    float4 v;
    asm volatile("ld.shared.v4.f32 {%0,%1,%2,%3}, [%4];" : "=f"(v.x), "=f"(v.y), "=f"(v.z), "=f"(v.w) : "r"(a) : "memory");
    return v;
}
__device__ __forceinline__ void lds_f4_if(float4& v, uint32_t a, bool pred) {
    asm volatile("{.reg .pred p; setp.ne.u32 p, %5, 0; @p ld.shared.v4.f32 {%0,%1,%2,%3}, [%4];}"
                 : "+f"(v.x), "+f"(v.y), "+f"(v.z), "+f"(v.w) : "r"(a), "r"((uint32_t)pred) : "memory");
}
__device__ __forceinline__ uint4 ld_tagged_rlx(const unsigned long long* p) {
    unsigned long long a, b;
    asm volatile("ld.relaxed.gpu.global.v2.b64 {%0,%1}, [%2];" : "=l"(a), "=l"(b) : "l"(p) : "memory");
    return make_uint4((unsigned)a, (unsigned)(a >> 32), (unsigned)b, (unsigned)(b >> 32));
}
__device__ __forceinline__ void sts32(uint32_t a, uint32_t x) { asm volatile("st.shared.u32 [%0], %1;" ::"r"(a), "r"(x) : "memory"); }
__device__ __forceinline__ void fetch_tagged(const unsigned long long* src, uint32_t dst, unsigned epoch, unsigned ns) {
    uint4 v;
    uint32_t it = 0;
    while (true) {
        v = ld_tagged_rlx(src);
        if (!__any_sync(0xffffffffu, v.y != epoch || v.w != epoch)) break;
        __nanosleep(ns);
        trap_if_gt(++it, 1u << 22);
    }
    sts64(dst, v.x, v.z);
}
__device__ __forceinline__ void st_tagged_if(unsigned long long* p, float a, float b, unsigned tag, bool pred) {
    const unsigned long long t = (unsigned long long)tag << 32;
    asm volatile("{.reg .pred p; setp.ne.u32 p, %3, 0; @p st.relaxed.gpu.global.v2.b64 [%0], {%1,%2};}"
                 ::"l"(p), "l"(t | __float_as_uint(a)), "l"(t | __float_as_uint(b)), "r"((uint32_t)pred) : "memory");
}

__device__ __forceinline__ void store_tile(uint32_t tile_rows, uint4* gdst, const uint32_t* lo, const uint32_t* hi, int lane, uint32_t* ack) {
    const int r = lane & 15;
#pragma unroll
    for (int b = 0; b < 4; b++)
        stsm4(tile_rows + r * 128 + (((2 * b + (lane >> 4)) ^ (r & 7)) << 4), lo[2 * b], hi[2 * b], lo[2 * b + 1], hi[2 * b + 1]);
    fence_async_smem();
    __syncwarp();
#pragma unroll
    for (int i = 0; i < 4; i++) {
        const uint4 v = lds128(tile_rows + i * 512 + lane * 16);
        stg128(gdst + 32 * i, v.x, v.y, v.z, v.w);
    }
#pragma unroll
    for (int i = 0; i < 4; i++) ack[i] = readback(gdst + 32 * i);
}

__device__ __forceinline__ void feature_maps(const uint32_t* a, const uint32_t* wb, float c0, float c1, uint32_t* plus, uint32_t* minus) {
    uint32_t P[16], mx[4], mn[4];
#pragma unroll
    for (int h = 0; h < 4; h++) {
        float p[8];
        mma16816_z(p, a + 4 * h, wb[4 * h], wb[4 * h + 1]);
        mma16816_z(p + 4, a + 4 * h, wb[4 * h + 2], wb[4 * h + 3]);
        P[4 * h] = pack_bf16(p[0], p[2]); P[4 * h + 1] = pack_bf16(p[1], p[3]);
        P[4 * h + 2] = pack_bf16(p[4], p[6]); P[4 * h + 3] = pack_bf16(p[5], p[7]);
        mx[h] = max2(max2(P[4 * h], P[4 * h + 1]), max2(P[4 * h + 2], P[4 * h + 3]));
        mn[h] = min2(min2(P[4 * h], P[4 * h + 1]), min2(P[4 * h + 2], P[4 * h + 3]));
    }
#pragma unroll
    for (int s = 1; s <= 2; s <<= 1) {
        uint32_t tx[4], tn[4];
#pragma unroll
        for (int h = 0; h < 4; h++) { tx[h] = __shfl_xor_sync(0xffffffffu, mx[h], s); tn[h] = __shfl_xor_sync(0xffffffffu, mn[h], s); }
#pragma unroll
        for (int h = 0; h < 4; h++) { mx[h] = max2(mx[h], tx[h]); mn[h] = min2(mn[h], tn[h]); }
    }
#pragma unroll
    for (int h = 0; h < 4; h++) {
        const float mx0 = bf_lo(mx[h]) * c0, mx1 = bf_hi(mx[h]) * c1, mn0 = bf_lo(mn[h]) * c0, mn1 = bf_hi(mn[h]) * c1;
        float ep[8], em[8];
#pragma unroll
        for (int i = 0; i < 8; i++) {
            const bool r1 = (i & 2);
            const uint32_t w = P[4 * h + (i >> 2) * 2 + (i & 1)];
            const float p = r1 ? bf_hi(w) : bf_lo(w);
            ep[i] = ex2(fmaf(p, r1 ? c1 : c0, r1 ? -mx1 : -mx0));
            em[i] = ex2(fmaf(p, r1 ? -c1 : -c0, r1 ? mn1 : mn0));
        }
        float sp[4], sm[4];
        uint32_t tp[4], tm[4];
#pragma unroll
        for (int i = 0; i < 4; i++) { tp[i] = pack_bf16(ep[2 * i], ep[2 * i + 1]); tm[i] = pack_bf16(em[2 * i], em[2 * i + 1]); }
        mma16816_z(sp, tp, 0x3f803f80u, 0x3f803f80u);
        mma16816_z(sm, tm, 0x3f803f80u, 0x3f803f80u);
        const float r0 = rcp(sp[0] * sm[0]), r1 = rcp(sp[2] * sm[2]);
        const float rs[4] = {r0 * sm[0], r1 * sm[2], r0 * sp[0], r1 * sp[2]};
#pragma unroll
        for (int i = 0; i < 4; i++) {
            plus[4 * h + i] = pack_bf16(ep[2 * i] * rs[i & 1], ep[2 * i + 1] * rs[i & 1]);
            minus[4 * h + i] = pack_bf16(em[2 * i] * rs[2 + (i & 1)], em[2 * i + 1] * rs[2 + (i & 1)]);
        }
    }
}

template <bool SCALE>
__device__ __forceinline__ void ln_frag(const float* acc, uint32_t cs_addr, float rs0, float nm0, float rs1, float nm1, uint32_t* a) {
    const float2 c0 = lds_f2(cs_addr), c1 = lds_f2(cs_addr + 32);
    const float s0 = SCALE ? rs0 : 1.f, s1 = SCALE ? rs1 : 1.f;
    a[0] = pack_bf16(fmaf(nm0, c0.x, acc[0]) * s0, fmaf(nm0, c0.y, acc[1]) * s0);
    a[1] = pack_bf16(fmaf(nm1, c0.x, acc[2]) * s1, fmaf(nm1, c0.y, acc[3]) * s1);
    a[2] = pack_bf16(fmaf(nm0, c1.x, acc[4]) * s0, fmaf(nm0, c1.y, acc[5]) * s0);
    a[3] = pack_bf16(fmaf(nm1, c1.x, acc[6]) * s1, fmaf(nm1, c1.y, acc[7]) * s1);
}

template <int UP>
__device__ __forceinline__ uint32_t hh_pair(const float* ag, float4 cs, float nmean) {
    const float g0 = fmaf(nmean, cs.x, ag[0]), g1 = fmaf(nmean, cs.y, ag[1]);
    const float u0 = fmaf(nmean, cs.z, ag[UP]), u1 = fmaf(nmean, cs.w, ag[UP + 1]);
    return pack_bf16(g0 * u0, g1 * u1);
}
template <int TP0, int TP1>
__device__ __forceinline__ void hh_stage(const float* acc, const float4* cs, float nm0, float nm1, uint32_t stg, int lane) {
#pragma unroll
    for (int tp = TP0; tp < TP1; tp++)
        stsm4(stg + (lane & 15) * 128 + (((2 * tp + (lane >> 4)) ^ (lane & 7)) << 4), hh_pair<32>(acc + 8 * tp, cs[2 * tp], nm0),
              hh_pair<32>(acc + 8 * tp + 2, cs[2 * tp], nm1), hh_pair<32>(acc + 8 * tp + 4, cs[2 * tp + 1], nm0),
              hh_pair<32>(acc + 8 * tp + 6, cs[2 * tp + 1], nm1));
}
struct Ring {
    int slot; uint32_t phase;
    __device__ __forceinline__ void adv() { if (++slot == NB) { slot = 0; phase ^= 1; } }
    __device__ __forceinline__ void adv5() { slot += slot == 3; adv(); }
};

__global__ void __cluster_dims__(2, 1, 1) __launch_bounds__(NTHREADS, 1) fused_kernel(const __grid_constant__ Params P) {
    extern __shared__ __align__(1024) uint8_t smem_raw[];
    const uint32_t sb = smem_u32(smem_raw);
    const int tid = threadIdx.x, lane = tid & 31;
    const int warp = __shfl_sync(0xffffffffu, tid >> 5, 0);
    const unsigned rank = blockIdx.x & 1;
    int m, j;
    {
        const int t = (int)(blockIdx.x >> 1) - 4, u = t - 32, r7 = (u * 37) >> 8;
        const int gp = t < 32 ? (t & 7) - 1 : u - 7 * r7;
        j = t < 0 ? t + 8 : (t < 32 ? t >> 3 : 4 + r7);
        m = ((t < 0 || gp < 0) ? 14 : 2 * gp) + rank;
        if (t >= 60) { m = 16; j = blockIdx.x - 128; }
    }
    const unsigned role = m * 8 + j;
    const bool helper = m == 16;

    TL(0, tid == 0); TLG(0, tid == 0);
    float* const acc_j = g_acc + j * ACC_SIZE;
    if ((warp & ~1) == 8 && elect_one()) {
        const uint32_t bar = sb + (warp == 8 ? BAR_FULLB : BAR_FULLA);
#pragma unroll
        for (int i = 0; i < 8; i++) if (i < NB || warp == 9) mbar_init(bar + 8 * i, 1);
        if (!helper) {
#pragma unroll 1
            for (int i = 0; i < NPRE; i++) {
                mbar_expect_tx(bar + 8 * i, SLOT);
                if (warp == 8) {
                    tma2d(sb + OFF_B + i * SLOT, &P.twq, bar + 8 * i, DM + 64 * j, 64 * i);
                    tma2d(sb + OFF_B + i * SLOT + 8192, &P.twq, bar + 8 * i, 2 * DM + 64 * j, 64 * i);
                } else {
                    tma2d(sb + OFF_A + i * SLOT, &P.tx, bar + 8 * i, 64 * i, 128 * m);
                }
            }
        }
    }
    __syncwarp();

    if (warp >= 8) {
        asm volatile("setmaxnreg.dec.sync.aligned.u32 72;");
        if (elect_one()) {
            if (warp < 10) {
            } else if (warp == 10) {
#pragma unroll
                for (int i = 0; i < 20; i++) mbar_init(sb + BAR_CS1 + 8 * i, i >= 12 ? 1 : (i < 2 || i >= 8 ? 64 : (i < 4 ? 32 : 8)));
                trap_if_gt(sb & 1023, 0);
            } else {
#pragma unroll
                for (int i = 0; i < 14; i++) mbar_init(sb + (i < 8 ? BAR_EMPTYA : BAR_EMPTYB - 64) + 8 * i, i < 8 ? 8 : 16);
            }
            asm volatile("fence.mbarrier_init.release.cluster;" ::: "memory");
        }
        __syncwarp();
        asm volatile("barrier.cluster.arrive.relaxed.aligned;" ::: "memory");
        const unsigned epoch = ld_relaxed(&g_epoch);
        bar_sync(0, NTHREADS);
        if (helper) {
            if (elect_one()) {
#pragma unroll 1
                for (int i = warp - 8; i < 72; i += 4) {
                    const uint32_t full = sb + BAR_FULLA + 8 * (i & 7), dst = sb + OFF_A + (i & 7) * SLOT;
                    const int n = i >> 1, jj = 2 * j + (i & 1);
                    const bool qkv = n < 12;
                    const int c0 = qkv ? (n < 8 ? DM + 128 * (n & 4) : 0) + 64 * jj : 176 * jj + 8 * ((n - 12) & ~7);
                    const int r0 = qkv ? 128 * (n & 3) : 64 * ((n - 12) & 7);
                    mbar_wait(sb + BAR_EMPTYA + 8 * (i & 7), ((i >> 3) & 1) ^ 1);
                    mbar_expect_tx(full, SLOT);
                    tma2d(dst, qkv ? &P.twq : &P.twg, full, c0, r0);
                    tma2d(dst + 8192, qkv ? &P.twq : &P.twu, full, c0, qkv ? r0 + 64 : r0);
                }
                prefetch_l2(P.wd + (size_t)(4 * j + warp - 8) * 44032, 88064);
            }
            return;
        }
        if (warp == 8) {
            asm volatile("barrier.cluster.wait.aligned;" ::: "memory");
            if (elect_one()) {
                if (m >= 6)
                    asm volatile("cp.async.bulk.prefetch.tensor.2d.L2.global [%0, {%1, %2}];" ::"l"(&P.twq), "r"(DM + DM * (m & 1) + 64 * j), "r"(64 * (m >> 1)) : "memory");
                if (j >= 3)
                    asm volatile("cp.async.bulk.prefetch.tensor.2d.L2.global [%0, {%1, %2}];" ::"l"(&P.tx), "r"(64 * j), "r"(128 * m) : "memory");
                Ring r{NPRE, 0};
                const uint32_t dst = sb + OFF_B + rank * 8192;
#define B_LOADN(TM, C0, R0, NB_)                                                                                \
        mbar_waitc(sb + BAR_EMPTYB + 8 * r.slot, r.phase ^ 1);                                              \
        mbar_expect_tx(sb + BAR_FULLB + 8 * r.slot, NB_);                                                   \
        tma2d_mc(dst + r.slot * SLOT, TM, sb + BAR_FULLB + 8 * r.slot, C0, R0);
#define B_LOAD(TM, C0, R0) B_LOADN(TM, C0, R0, SLOT)
#pragma unroll 1
                for (int i = NPRE; i < 8; i++) {
                    if (i >= AHEAD && i < 6) mbar_waitc(sb + BAR_FULLB + 8 * (i - AHEAD), 0);
                    B_LOAD(&P.twq, DM + DM * rank + 64 * j, 64 * i)
                    r.adv();
                }
#pragma unroll 1
                for (int i = 8; i < 18; i++) {
                    if (i == 9 || i == 10) {
                        mbar_waitc(sb + BAR_EMPTYB + 8 * r.slot, r.phase ^ 1);
                        mbar_arrive(sb + BAR_FULLB + 8 * r.slot);
                    } else {
                        const int e = 2 * (i - 14) + rank, b = (i == 8 ? 0 : i - 10) ^ (i < 12 && j < 2);
                        B_LOAD(i < 14 ? &P.twq : &P.two, 64 * j, 64 * (i < 14 ? 2 * b + rank : KORD(e, j)))
                    }
                    r.adv();
                }
#pragma unroll 1
                for (int i = 0; i < 24; i++) {
                    B_LOAD(&P.twg + rank, 176 * j + 8 * (i & ~7), 64 * (i < 8 ? KORD(i, j) : i & 7))
                    r.adv5();
                }
#pragma unroll 1
                for (int i = 0; i < 12; i++) {
                    B_LOADN(&P.twd + (i >> 3), 64 * j, 176 * (2 * (i & 3) + rank) + 64 * (i >> 2), i < 8 ? SLOT : 12288)
                    r.adv5();
                }
            }
            return;
        }
        if (warp == 9) {
            if (elect_one()) {
#pragma unroll 1
                for (int i = NPRE; i < 8; i++) {
                    if (i >= AHEADA) mbar_wait(sb + BAR_FULLA + 8 * (i - AHEADA), 0);
                    mbar_expect_tx(sb + BAR_FULLA + 8 * i, SLOT);
                    tma2d(sb + OFF_A + i * SLOT, &P.tx, sb + BAR_FULLA + 8 * i, 64 * i, 128 * m);
                }
#pragma unroll 1
                for (int i = 2; i < 8; i++) prefetch_tmap(&P.tx + i);
                mbar_wait(sb + BAR_KVR, 0);
                unsigned nf = 0;
#pragma unroll 1
                for (int r = 0; r < 4; r++) {
                    const uint4* src = g_act + ((r >> 1) * 128 + m * 8) * 1024 + (r & 1) * 512;
                    const uint32_t bar = sb + ((r & 1) ? BAR_FULLH : BAR_FULLA), dst = sb + OFF_A + (r & 1) * 8192;
                    if (!(r & 1)) {
#pragma unroll 1
                        for (int t = 0; t < 8; t++) {
                            if (t == j) continue;
                            if (r) { mbar_wait(sb + BAR_FULLA + 8 * t, 1); mbar_wait(sb + BAR_FULLH + 8 * t, 0); }
                            mbar_expect_tx(sb + BAR_FULLA + 8 * t, 8192);
                            mbar_expect_tx(sb + BAR_FULLH + 8 * t, 8192);
                        }
                    }
                    if (nf != epoch * 32) wait_count(g_flag + (m * 7 + r) * 32, epoch * 32);
                    nf = (r & 1) ? 0 : readback(g_flag + (m * 7 + r + 1) * 32);
                    if (r == 1) mbar_wait(sb + BAR_KVW, 1);
                    TL(64 + r, true);
#pragma unroll
                    for (int i = 1; i < 8; i++) {
                        const int t = KORD(i, j);
                        asm volatile("cp.async.bulk.shared::cluster.global.mbarrier::complete_tx::bytes [%0], [%1], %2, [%3];"
                                     ::"r"(dst + t * SLOT), "l"(src + t * 1024), "r"(8192), "r"(bar + 8 * t) : "memory");
                    }
                }
                mbar_wait(sb + BAR_EMPTYA + 8 * PF_DELAY, 0);
#pragma unroll 1
                for (int c = 0; c < 3; c++) {
                    const uint32_t bytes = c == 2 ? 12288 : SLOT;
                    const uint4* src = g_act + ((2 + c) * 128 + m * 8) * 1024;
                    const unsigned* fl = g_flag + (m * 7 + 4 + c) * 32;
                    if (nf != epoch * 8) wait_count(fl, epoch * 8);
                    TL(68 + c, true);
#pragma unroll 1
                    for (int t = 0; t < 8; t++) {
                        if (t == 6 && c < 2) nf = readback(fl + 32);
                        mbar_wait(sb + BAR_EMPTYA + 8 * t, c & 1);
                        mbar_expect_tx(sb + BAR_FULLA + 8 * t, bytes);
                        asm volatile("cp.async.bulk.shared::cluster.global.mbarrier::complete_tx::bytes [%0], [%1], %2, [%3];"
                                     ::"r"(sb + OFF_A + t * SLOT), "l"(src + t * 1024), "r"(bytes), "r"(sb + BAR_FULLA + 8 * t) : "memory");
                    }
                }
            }
            return;
        }
        const int a = warp - 10;
        {
            const int row = 16 * j + 8 * a + (lane >> 2);
            const uint32_t ra = sb + OFF_A + row * 128;
            float sh = 0.f, s0 = 0.f, s1 = 0.f, q0 = 0.f, q1 = 0.f;
#pragma unroll 1
            for (int kt = 0; kt < 8; kt++) {
                mbar_wait(sb + BAR_FULLA + 8 * kt, 0);
                if (kt == 0) sh = bf_lo(lds128(ra + ((row & 7) << 4)).x);
#pragma unroll
                for (int i = 0; i < 2; i++) {
                    const uint4 v = lds128(ra + kt * SLOT + (((2 * (lane & 3) + i) ^ (row & 7)) << 4));
                    const uint32_t ww[4] = {v.x, v.y, v.z, v.w};
#pragma unroll
                    for (int e = 0; e < 4; e++) {
                        const float d0 = bf_lo(ww[e]) - sh, d1 = bf_hi(ww[e]) - sh;
                        s0 += d0; q0 = fmaf(d0, d0, q0);
                        s1 += d1; q1 = fmaf(d1, d1, q1);
                    }
                }
            }
            s0 += s1; q0 += q1;
#pragma unroll
            for (int o = 1; o <= 2; o <<= 1) { s0 += __shfl_xor_sync(0xffffffffu, s0, o); q0 += __shfl_xor_sync(0xffffffffu, q0, o); }
            const float md = s0 * (1.f / DM);
            const float rs = rsqrtf(fmaxf(q0 * (1.f / DM) - md * md, 0.f) + 1e-5f);
            st_tagged_if(g_xstat + 2 * (128 * m + row), rs, -(sh + md), epoch, (lane & 3) == 0);
            TL(1, lane == 0 && a == 0);
        }
        const unsigned long long* cs = g_cs + j * 768 + 2 * lane;
        {
            const unsigned long long* xs = g_xstat + 2 * (128 * m + 64 * a + lane);
            uint4 v0, v1, v2;
            uint32_t it = 0;
            __nanosleep(250);
            do {
                v0 = ld_tagged_rlx(xs); v1 = ld_tagged_rlx(xs + 64); v2 = ld_tagged_rlx(cs);
                trap_if_gt(++it, 1u << 22);
            } while (__any_sync(0xffffffffu, v0.y != epoch || v0.w != epoch || v1.y != epoch || v1.w != epoch || v2.y != epoch || v2.w != epoch));
            sts64(sb + OFF_XST + (64 * a + lane) * 8, v0.x, v0.z);
            sts64(sb + OFF_XST + (64 * a + 32 + lane) * 8, v1.x, v1.z);
            sts64(sb + OFF_CS1 + 256 + 8 * lane, v2.x, v2.z);
            mbar_arrive(sb + BAR_CS1);
            TL(22 + a, lane == 0);
            fetch_tagged(cs + 128 + 128 * a, sb + OFF_CS1 + 512 - 512 * a + 8 * lane, epoch, 200);
            mbar_arrive(sb + BAR_CSV - 8 * a);
            TL(24 + a, lane == 0);
        }
        {
            mbar_wait(sb + BAR_KVW, 0);
            const float* src = acc_j + 4 * (128 * a + lane);
            float4 v[12];
            uint32_t it = 0;
            bool bad;
            while (__any_sync(0xffffffffu, readback(acc_j + 2048 + 128 * (lane & 7) + 127) != 0x41800000u)) trap_if_gt(++it, 1u << 22);
            TL(19, lane == 0 && a == 0);
            do {
                bad = false;
#pragma unroll
                for (int i = 0; i < 12; i++) v[i] = ld_l2_f4(src + 1024 * (i % 3) + 128 * (i / 3));
#pragma unroll
                for (int i = 0; i < 12; i++) bad |= v[i].w != 16.f;
                trap_if_gt(++it, 1u << 22);
            } while (__any_sync(0xffffffffu, bad));
            TL(14, lane == 0 && a == 0);
            const uint32_t d0 = sb + OFF_A + (j < 2 ? 2 * SLOT : 0) + 8192 + (64 * a + (lane >> 2)) * 48;
            const uint32_t d = d0 + (lane & 3) * 4, dz = d0 + (lane & 1) * 384 + 32 + (lane & 2) * 4;
#pragma unroll
            for (int u = 0; u < 4; u++) {
                sts32(d + 768 * u, pack_bf16(v[3 * u].x, v[3 * u].y));
                sts32(d + 768 * u + 384, pack_bf16(v[3 * u].z, v[3 * u + 1].z));
                sts32(d + 768 * u + 16, pack_bf16(v[3 * u + 1].x, v[3 * u + 1].y));
                sts32(d + 768 * u + 400, pack_bf16(v[3 * u + 2].x, v[3 * u + 2].y));
                const uint32_t z2 = pack_bf16(v[3 * u + 2].z, v[3 * u + 2].z);
                sts64(dz + 768 * u, z2, z2);
            }
            mbar_arrive(sb + BAR_KVR);
        }
#pragma unroll 1
        for (int c = 0; c < 3; c++) {
            fetch_tagged(cs + 384 + 128 * c + 64 * a, sb + OFF_CS3 + (32 * c + lane) * 16 + 8 * a, epoch, 1000);
            mbar_arrive(sb + BAR_CSG + 8 * c);
        }
        {
            uint32_t it = 0;
            while (__any_sync(0xffffffffu, (int)(readback(g_flag + (m * 7 + 2 + (lane & 1)) * 32) - epoch * 32) < 0)) {
                __nanosleep(600);
                trap_if_gt(++it, 1u << 22);
            }
#pragma unroll 1
            for (int rr = 0; rr < 2; rr++) {
                const int row = 64 * rr + 32 * a + lane;
                const unsigned long long* hs = g_hstat + (1024 * m + row) * 2;
                uint4 v[8];
                bool bad;
                do {
                    bad = false;
#pragma unroll
                    for (int i = 0; i < 8; i++) v[i] = ld_tagged_rlx(hs + 256 * i);
#pragma unroll
                    for (int i = 0; i < 8; i++) bad |= v[i].y != epoch || v[i].w != epoch;
                    trap_if_gt(++it, 1u << 22);
                } while (__any_sync(0xffffffffu, bad));
                float mean = 0.f;
#pragma unroll
                for (int i = 0; i < 8; i++) mean += __uint_as_float(v[i].x);
                mean *= 0.125f;
                float m2 = 0.f, dv = 0.f;
#pragma unroll
                for (int i = 0; i < 8; i++) { const float d = __uint_as_float(v[i].x) - mean; m2 += __uint_as_float(v[i].z); dv = fmaf(d, d, dv); }
                sts_f2(sb + OFF_CS1 + row * 8, -mean, rcp(fmaf(dv, 64.f, m2) * (1.f / DM) + 1e-5f));
            }
        }
        mbar_arrive(sb + BAR_CS3);
#pragma unroll 1
        for (int c = a; c < 3; c += 2) {
            mbar_wait(sb + BAR_STG + 8 * c, 0);
            if (elect_one()) {
                asm volatile("cp.async.bulk.global.shared::cta.bulk_group [%0], [%1], %2;" ::"l"(g_act + ((2 + c) * 128 + role) * 1024), "r"(sb + OFF_B + 4 * SLOT), "r"(c == 2 ? 12288 : SLOT) : "memory");
                asm volatile("cp.async.bulk.commit_group;" ::: "memory");
                asm volatile("cp.async.bulk.wait_group.read 0;" ::: "memory");
                mbar_arrive(sb + BAR_FULLB + 8 * 4);
                asm volatile("cp.async.bulk.wait_group 0;" ::: "memory");
            }
            __syncwarp();
            TL(60 + c, lane == 0);
            uint32_t ack = 0;
            const uint4* rb = g_act + ((2 + c) * 128 + role) * 1024 + lane * 8;
#pragma unroll
            for (int i = 0; i < 4; i++) ack |= readback(rb + (i == 3 && c == 2 ? 0 : 256 * i));
            signal_after(g_flag + (m * 7 + 4 + c) * 32, ack, P.zero, lane == 0);
            TL(54 + c, lane == 0);
        }
        return;
    }
    const unsigned epoch = ld_relaxed(&g_epoch);
    uint32_t wraw[16];
    if (!helper) {
        const uint32_t* wp = reinterpret_cast<const uint32_t*>(P.wphi) + (4 * j) * 128 + (lane & 3) * 16 + (lane >> 2);
#pragma unroll
        for (int i = 0; i < 16; i++)
            asm volatile("ld.global.nc.u32 %0, [%1];" : "=r"(wraw[i]) : "l"(wp + (i >> 2) * 128 + ((i >> 1) & 1) * 64 + (i & 1) * 8));
    }
    asm volatile("barrier.cluster.arrive.relaxed.aligned;" ::: "memory");
    asm volatile("setmaxnreg.inc.sync.aligned.u32 216;");
    bar_sync(0, NTHREADS);
    if (helper) {
        const int w = warp >> 2;
        sts64(sb + OFF_B + 8 * tid, 0x3f803f80u, 0x3f803f80u);
        fence_async_smem();
        uint32_t zack[6];
        {
            float* z = g_acc + 2 * j * ACC_SIZE + 4 * tid;
#pragma unroll
            for (int u = 0; u < 6; u++) stg128(z + 1024 * u, 0, 0, 0, 0);
#pragma unroll
            for (int u = 0; u < 6; u++) zack[u] = readback(z + 1024 * u);
        }
        bar_sync(1, 256);
        float acc[8];
        int i = w;
#pragma unroll 1
        for (int job = 0; job < 6; job++) {
            const int n = job < 3 ? 4 : 8;
#pragma unroll 1
            for (int t = 0; t < n; t++, i += 2) {
                mbar_waitc(sb + BAR_FULLA + 8 * (i & 7), (i >> 3) & 1);
                const desc_t da = desc_lo(sb + OFF_A) + (i & 7) * (SLOT >> 4);
                wg_fence();
#pragma unroll
                for (int k = 0; k < 8; k++) wgmma_n8_tt(acc + (k & 4), da + 128 * k, desc_lo(sb + OFF_B), (t | (k & 3)) != 0);
                wg_commit();
                wg_wait<0>();
                mbar_arrive_n_if(sb + BAR_EMPTYA + 8 * (i & 7), 2, lane == 0);
            }
            fence_acc<8>(acc);
            if (job == 1) {
                asm volatile("{.reg .pred p; .reg .b32 t; lop3.b32 t, %0, %1, %2, 0xfe; lop3.b32 t, t, %3, %4, 0xfe; or.b32 t, t, %5; setp.ne.u32 p, t, 0; @p trap;}"
                             ::"r"(zack[0]), "r"(zack[1]), "r"(zack[2]), "r"(zack[3]), "r"(zack[4]), "r"(zack[5]));
                bar_sync(1, 256);
            }
            const int q = lane & 3;
            const float lo = (q & 1) ? acc[2] : acc[0], hi = (q & 1) ? acc[6] : acc[4];
            const float v = job < 3 ? lo + hi : ((q & 2) ? hi : lo);
            unsigned long long* dst = g_cs + ((2 * j + w) * 6 + job) * 128 + (q >> 1) * 64 + 16 * (warp & 3) + 8 * (q & 1) + (lane >> 2);
            asm volatile("st.relaxed.gpu.global.b64 [%0], %1;" ::"l"(dst), "l"(((unsigned long long)epoch << 32) | __float_as_uint(v)) : "memory");
        }
        return;
    }
    {
        const int w = warp >> 2, wv = warp & 3, g = lane >> 2, q = lane & 3;
        const uint32_t sa = sb + OFF_A + w * 8192;
        const desc_t dA = desc_lo(sa), dB = desc_lo(sb + OFF_B);
        unsigned* const flag_m = g_flag + (m * 7 + w) * 32;
        const uint32_t fullh = sb + (w ? BAR_FULLH : BAR_FULLA);
        const bool l0 = lane == 0, l2 = lane < 2;
        const uint32_t eb = mapa(sb + BAR_EMPTYB, lane & 1);
        asm volatile("barrier.cluster.wait.aligned;" ::: "memory");
        Ring rg{0, 0};
        int prev = 0;

        uint32_t wb[16];
        constexpr float L2E = 1.4426950408889634f;
        const int ch = lane >> 4, sw = lane & 7;
        const uint32_t lrow = (lane & 15) * 128;
        uint32_t fp[16], fm[16];
        const int vs = j < 2 ? 2 : 0;
        {
            float acc[64];
#pragma unroll 1
            for (int kt = 0; kt < 8; kt++) {
                mbar_waitc(sb + BAR_FULLA + 8 * kt, 0);
                mbar_waitc(sb + BAR_FULLB + 8 * rg.slot, rg.phase);
                const desc_t da = dA + kt * (SLOT >> 4), db = dB + rg.slot * (SLOT >> 4);
                wg_fence();
#pragma unroll
                for (int k = 0; k < 4; k++) wgmma_n128(acc, da + 2 * k, db + 128 * k, (kt | k) != 0);
                wg_commit();
                wg_wait<1>();
                mbar_arrive_cl_if(eb + 8 * prev, l2 && kt > 0);
                prev = rg.slot; rg.adv();
            }
#pragma unroll
            for (int i = 0; i < 8; i++) {
                wb[(i >> 1) * 4 + (i & 1)] = __byte_perm(wraw[2 * i], wraw[2 * i + 1], 0x5410);
                wb[(i >> 1) * 4 + 2 + (i & 1)] = __byte_perm(wraw[2 * i], wraw[2 * i + 1], 0x7632);
            }
            uint32_t a[16];
            float accq[32];
            mbar_waitc(sb + BAR_FULLB + 8 * 2, 1);
            wg_fence();
#pragma unroll
            for (int k = 0; k < 8; k++) wgmma_n64(accq, dA + (vs + (k >> 2)) * (SLOT >> 4) + (k & 3) * 2, dB + 2 * (SLOT >> 4) + 128 * k, k != 0);
            wg_commit();
            wg_wait<1>();
            fence_acc<64>(acc);
            mbar_arrive_cl_if(eb + 8 * prev, l2);
            TL(17, tid == 0);
            mbar_waitc(sb + BAR_CS1, 0);
            const float2 s0 = lds_f2(sb + OFF_XST + (16 * warp + g) * 8), s1 = lds_f2(sb + OFF_XST + (16 * warp + g + 8) * 8);
            wg_wait<0>();
            fence_acc<32>(accq);
            mbar_arrive_cl_if(eb + 8 * 2, l2);
            TL(2, tid == 0);
            const uint32_t st = sb + OFF_B + warp * 2048 + lrow;
#pragma unroll
            for (int hh = 0; hh < 4; hh++)
                ln_frag<false>(acc + 8 * hh, sb + OFF_CS1 + (64 + 16 * hh + 2 * q) * 4, 0.f, s0.y, 0.f, s1.y, a + 4 * hh);
#pragma unroll 1
            for (int it = 0; it < 2; it++) {
                feature_maps(a, wb, s0.x * L2E, s1.x * L2E, fp, fm);
                if (it == 0) {
                    mbar_waitc(sb + BAR_FULLB + 8 * 3, 1); mbar_waitc(sb + BAR_FULLB + 8 * 4, 1);
                    mbar_waitc(sb + BAR_CSV, 0);
                    const uint32_t sv = sb + OFF_A + vs * SLOT + warp * 2048 + lrow;
#pragma unroll
                    for (int hh = 0; hh < 4; hh++) {
                        stsm4(st + (3 + (hh >> 1)) * SLOT + (((4 * (hh & 1) + ch) ^ sw) << 4), fp[4 * hh], fp[4 * hh + 1], fp[4 * hh + 2], fp[4 * hh + 3]);
                        stsm4(st + (3 + (hh >> 1)) * SLOT + (((4 * (hh & 1) + 2 + ch) ^ sw) << 4), fm[4 * hh], fm[4 * hh + 1], fm[4 * hh + 2], fm[4 * hh + 3]);
                        ln_frag<true>(acc + 32 + 8 * hh, sb + OFF_CS1 + (128 + 16 * hh + 2 * q) * 4, s0.x, s0.y, s1.x, s1.y, a);
                        stsm4(sv + (hh >> 1) * SLOT + (((2 * (hh & 1) + ch) ^ sw) << 4), a[0], a[1], a[2], a[3]);
                    }
                    stsm4(sv + ch * SLOT + ((4 ^ sw) << 4), 0x3f803f80u, 0x3f803f80u, 0x3f803f80u, 0x3f803f80u);
                    fence_async_smem();
                    bar_sync(1, 256);
                    float kvd[20];
                    wg_fence();
#pragma unroll
                    for (int k = 0; k < 8; k++)
                        wgmma_n40_tt(kvd, dB + (3 + w) * (SLOT >> 4) + 128 * k, desc_lo(sb + OFF_A) + (vs + w) * (SLOT >> 4) + 128 * k, k != 0);
                    wg_commit();
                    wg_wait<0>();
                    fence_acc<20>(kvd);
                    mbar_arrive_cl_if(eb + 8 * (3 + (lane >> 1)), lane < 4);
                    const bool h1 = wv >= 2;
                    float* kvp = acc_j + 4 * tid;
                    red_f32x4(kvp, h1 ? kvd[8] : kvd[0], h1 ? kvd[9] : kvd[1], h1 ? kvd[10] : kvd[2], 1.f);
                    red_f32x4(kvp + 1024, h1 ? kvd[12] : kvd[4], h1 ? kvd[13] : kvd[5], h1 ? kvd[11] : kvd[3], 1.f);
                    red_f32x4(kvp + 2048, h1 ? kvd[14] : kvd[6], h1 ? kvd[15] : kvd[7], (q & 1) ? kvd[18] : kvd[16], 1.f);
                    mbar_arrive_if(sb + BAR_KVW, l0);
                    TL(3, tid == 0);
#pragma unroll 1
                    for (int b = 1; b < 4; b++) {
                        const int slot = b == 1 ? 5 : b - 2;
                        mbar_waitc(sb + BAR_FULLB + 8 * slot, b == 1);
                        const desc_t da = dA + (b == 1 ? 2 - vs : 2 * b) * (SLOT >> 4), db = dB + slot * (SLOT >> 4);
                        wg_fence();
#pragma unroll
                        for (int k = 0; k < 8; k++) wgmma_n64(accq, da + (k >> 2) * (SLOT >> 4) + (k & 3) * 2, db + 128 * k, 1);
                        wg_commit();
                    }
                    mbar_waitc(sb + BAR_CSQ, 0);
                    wg_wait<0>();
                    fence_acc<32>(accq);
                    mbar_arrive_cl_if(eb + 8 * ((5 + (lane >> 1)) % 6), lane < 6);
                    TL(4, tid == 0);
#pragma unroll
                    for (int hh = 0; hh < 4; hh++)
                        ln_frag<false>(accq + 8 * hh, sb + OFF_CS1 + (16 * hh + 2 * q) * 4, 0.f, s0.y, 0.f, s1.y, a + 4 * hh);
                }
            }
        }
        uint32_t res_lo[8], res_hi[8], ack[4];
        const uint32_t own_rows = sb + OFF_A + j * SLOT + warp * 2048;
#pragma unroll
        for (int b = 0; b < 4; b++)
            ldsm4(own_rows + lrow + (((2 * b + ch) ^ sw) << 4), res_lo[2 * b], res_hi[2 * b], res_lo[2 * b + 1], res_hi[2 * b + 1]);
        TL(5, tid == 0); TL(26, tid == 128);
        mbar_waitc(sb + BAR_KVR, 0);
        TL(6, tid == 0);
        {
            const uint32_t kvs = sb + OFF_A + vs * SLOT + 8192;
            uint32_t o_lo[8], o_hi[8];
#pragma unroll
            for (int hh = 0; hh < 4; hh++) {
                uint32_t b[8], zb[4];
                const uint32_t base = kvs + hh * 32 * 48;
                ldsm4t(base + (lane & 15) * 48 + (lane >> 4) * 16, b[0], b[1], b[2], b[3]);
                ldsm4t(base + (16 + (lane & 15)) * 48 + (lane >> 4) * 16, b[4], b[5], b[6], b[7]);
                ldsm4t(base + lane * 48 + 32, zb[0], zb[1], zb[2], zb[3]);
                float n0[4], n1[4], dn[4];
                mma16816_z(n0, fp + 4 * hh, b[0], b[1]); mma16816_z(n1, fp + 4 * hh, b[2], b[3]); mma16816_z(dn, fp + 4 * hh, zb[0], zb[1]);
                mma16816(n0, fm + 4 * hh, b[4], b[5]); mma16816(n1, fm + 4 * hh, b[6], b[7]); mma16816(dn, fm + 4 * hh, zb[2], zb[3]);
                const float i0 = rcp(dn[0] + 1e-6f), i1 = rcp(dn[2] + 1e-6f);
                o_lo[2 * hh] = pack_bf16(n0[0] * i0, n0[1] * i0); o_hi[2 * hh] = pack_bf16(n0[2] * i1, n0[3] * i1);
                o_lo[2 * hh + 1] = pack_bf16(n1[0] * i0, n1[1] * i0); o_hi[2 * hh + 1] = pack_bf16(n1[2] * i1, n1[3] * i1);
            }
            __syncwarp();
            mbar_arrive_if(sb + BAR_KVW, l0);
            store_tile(own_rows, g_act + role * 1024 + warp * 128 + lane, o_lo, o_hi, lane, ack);
            TL(7, tid == 0); TL(27, tid == 128);
        }
        float acch[32];
        {
            float* acc = acch;
#pragma unroll
            for (int t = 0; t < 8; t++) {
                acc[4 * t] = bf_lo(res_lo[t]); acc[4 * t + 1] = bf_hi(res_lo[t]);
                acc[4 * t + 2] = bf_lo(res_hi[t]); acc[4 * t + 3] = bf_hi(res_hi[t]);
            }
            fence_acc<32>(acc);
#pragma unroll
            for (int i = 2; i < 6; i++) mbar_waitc(sb + BAR_FULLB + 8 * i, 0);
#pragma unroll 1
            for (int i = 0; i < 8; i++) {
                const int kt = KORD(i, j);
                mbar_waitc(fullh + 8 * kt, (i != 0) ^ w);
                TL(8, i == 1 && tid == 0);
                const desc_t da = dA + kt * (SLOT >> 4), db = dB + (4 + i) * (SLOT >> 5);
                wg_fence();
#pragma unroll
                for (int k = 0; k < 4; k++) wgmma_n64(acc, da + 2 * k, db + 128 * k, 1);
                wg_commit();
                if (i == 0) { signal_late(flag_m, ack, P.zero, l0); TL(20, tid == 0); }
                wg_wait<1>();
                mbar_arrive_cl_if(eb + 8 * (1 + (i >> 1)), l2 && (i == 2 || i == 4));
            }
            wg_wait<0>();
            fence_acc<32>(acc);
            mbar_arrive_cl_if(eb + 8 * 5, l2);
            rg.slot = 0; rg.phase = 1;
            TL(9, tid == 0); TL(29, tid == 128);
#pragma unroll
            for (int t = 0; t < 8; t++) {
                res_lo[t] = pack_bf16(acc[4 * t], acc[4 * t + 1]);
                res_hi[t] = pack_bf16(acc[4 * t + 2], acc[4 * t + 3]);
            }
            store_tile(own_rows, g_act + (128 + role) * 1024 + warp * 128 + lane, res_lo, res_hi, lane, ack);
            TL(10, tid == 0);
        }
        float acc0[64], acc1[64], acc2[56], nm0, nm1;
        float4 cs[8];
        uint32_t hr[16];
#define P3_GROUP(MMA, ACC, KT)                                                                              \
        mbar_waitc(sb + BAR_FULLB + 8 * rg.slot, rg.phase);                                                 \
        {                                                                                                   \
            const desc_t da = dA + (KT) * (SLOT >> 4), db = dB + rg.slot * (SLOT >> 4);                     \
            wg_fence();                                                                                     \
            _Pragma("unroll") for (int k = 0; k < 4; k++) MMA(ACC, da + 2 * k, db + 128 * k, (i | k) != 0); \
            wg_commit();                                                                                    \
        }
#define P3_CS(C, NT)    \
        _Pragma("unroll") for (int t = 0; t < (NT); t++) lds_f4_if(cs[t], sb + OFF_CS3 + q * 16 + 512 * (C) + 64 * t, i == t);
        const uint32_t stg = sb + OFF_B + 4 * SLOT + warp * 2048;
        const uint32_t blk = ((lane & 7) + (lane >> 4) * 8) * 128 + (((2 * wv + ((lane >> 3) & 1)) ^ (lane & 7)) << 4);
#pragma unroll 1
        for (int i = 0; i < 8; i++) {
            const int kt = KORD(i, j);
            mbar_waitc(fullh + 8 * kt, w);
            TL(44 + w, (tid & 127) == 0 && i == 1);
            P3_GROUP(wgmma_n128, acc0, kt)
            if (i == 7) {
                mbar_waitc(sb + BAR_CS3, 0);
                nm0 = lds_f2(sb + OFF_CS1 + (16 * warp + g) * 8).x; nm1 = lds_f2(sb + OFF_CS1 + (16 * warp + g + 8) * 8).x;
            }
            wg_wait<1>();
            mbar_arrive_cl_if(eb + 8 * prev, l2 && i > 0);
            if (i == 0) {
                signal_late(flag_m + 64, ack, P.zero, l0);
                TL(21, tid == 0);
                {
                    fence_acc<32>(acch);
                    const float* acc = acch;
                    float s0 = 0.f, s1 = 0.f;
#pragma unroll
                    for (int t = 0; t < 8; t++) { s0 += acc[4 * t] + acc[4 * t + 1]; s1 += acc[4 * t + 2] + acc[4 * t + 3]; }
                    s0 += __shfl_xor_sync(0xffffffffu, s0, 1); s1 += __shfl_xor_sync(0xffffffffu, s1, 1);
                    s0 += __shfl_xor_sync(0xffffffffu, s0, 2); s1 += __shfl_xor_sync(0xffffffffu, s1, 2);
                    const float mu0 = s0 * (1.f / 64), mu1 = s1 * (1.f / 64);
                    float q0 = 0.f, q1 = 0.f;
#pragma unroll
                    for (int t = 0; t < 8; t++) {
                        float d;
                        d = acc[4 * t] - mu0; q0 = fmaf(d, d, q0);
                        d = acc[4 * t + 1] - mu0; q0 = fmaf(d, d, q0);
                        d = acc[4 * t + 2] - mu1; q1 = fmaf(d, d, q1);
                        d = acc[4 * t + 3] - mu1; q1 = fmaf(d, d, q1);
                    }
                    q0 += __shfl_xor_sync(0xffffffffu, q0, 1); q1 += __shfl_xor_sync(0xffffffffu, q1, 1);
                    q0 += __shfl_xor_sync(0xffffffffu, q0, 2); q1 += __shfl_xor_sync(0xffffffffu, q1, 2);
                    st_tagged_if(g_hstat + (role * 128 + 16 * warp + g + 8 * (q & 1)) * 2, q ? mu1 : mu0, q ? q1 : q0, epoch, q < 2);
                }
                bar_sync(2 + w, 128);
#pragma unroll
                for (int tp = 0; tp < 4; tp++) ldsm4t(sa + j * SLOT + blk + tp * 2048, hr[4 * tp], hr[4 * tp + 1], hr[4 * tp + 2], hr[4 * tp + 3]);
                mbar_waitc(sb + BAR_CSG, 0);
#pragma unroll
                for (int t = 0; t < 8; t++) cs[t] = lds_f4(sb + OFF_CS3 + q * 16 + 64 * t);
            }
            prev = rg.slot; rg.adv5();
        }
#pragma unroll 1
        for (int i = 0; i < 8; i++) {
            P3_GROUP(wgmma_n128, acc1, i)
            wg_wait<1>();
            mbar_arrive_cl_if(eb + 8 * prev, l2);
            if (i == 0) {
                fence_acc<64>(acc0);
                hh_stage<0, 2>(acc0, cs, nm0, nm1, stg, lane);
                mbar_waitc(sb + BAR_CSG + 8, 0);
            }
            if (i == 1) {
                hh_stage<2, 4>(acc0, cs, nm0, nm1, stg, lane);
                fence_async_smem();
                __syncwarp();
                mbar_arrive_if(sb + BAR_STG, l0);
            }
            P3_CS(1, 8)
            prev = rg.slot; rg.adv5();
        }
#pragma unroll 1
        for (int i = 0; i < 8; i++) {
            P3_GROUP(wgmma_n112, acc2, i)
            wg_wait<1>();
            mbar_arrive_cl_if(eb + 8 * prev, l2);
            mbar_arrive_if(sb + BAR_EMPTYA + 8 * ((i + 7) & 7), l0 && i > 0);
            if (i == 0) {
                mbar_waitc(sb + BAR_FULLB + 8 * 4, 1);
                fence_acc<64>(acc1);
                TL(12, tid == 0);
                hh_stage<0, 4>(acc1, cs, nm0, nm1, stg, lane);
                fence_async_smem();
                __syncwarp();
                mbar_arrive_if(sb + BAR_STG + 8, l0);
                mbar_waitc(sb + BAR_CSG + 16, 0);
            }
            P3_CS(2, 6)
            prev = rg.slot; rg.adv5();
        }
        mbar_waitc(sb + BAR_FULLB + 8 * 4, 0);
        wg_wait<0>();
        mbar_arrive_cl_if(eb + 8 * prev, l2);
        mbar_arrive_if(sb + BAR_EMPTYA + 8 * 7, l0);
        fence_acc<56>(acc2);
        TL(13, tid == 0);
#pragma unroll
        for (int tp = 0; tp < 3; tp++)
            stsm4(sb + OFF_B + 4 * SLOT + tp * 4096 + warp * 512 + (lane & 15) * 32 + ((ch ^ ((lane >> 2) & 1)) << 4),
                  hh_pair<32>(acc2 + 8 * tp, cs[2 * tp], nm0), hh_pair<32>(acc2 + 8 * tp + 2, cs[2 * tp], nm1),
                  hh_pair<32>(acc2 + 8 * tp + 4, cs[2 * tp + 1], nm0), hh_pair<32>(acc2 + 8 * tp + 6, cs[2 * tp + 1], nm1));
        fence_async_smem();
        __syncwarp();
        mbar_arrive_if(sb + BAR_STG + 16, l0);
        TL(52, tid == 0);
        {
            float acc[64];
            const desc_t dA0 = desc_lo(sb + OFF_A);
#define KT_P4(I, NK, DH, STEP)                                                                                   \
        const int s_ = (2 * (I) + w) & 7;                                                                   \
        mbar_waitc(sb + BAR_FULLB + 8 * rg.slot, rg.phase);                                                 \
        mbar_waitc(sb + BAR_FULLA + 8 * s_, (((I) >> 2) + 1) & 1);                                          \
        const desc_t dh_ = (DH) + s_ * (SLOT >> 4), dw_ = dB + rg.slot * (SLOT >> 4) + w * 512;              \
        wg_fence();                                                                                         \
        _Pragma("unroll") for (int k = 0; k < (NK); k++) wgmma_n128_tn(acc, dw_ + 128 * k, dh_ + (STEP) * k, ((I) | k) != 0); \
        wg_commit();
#pragma unroll 1
            for (int i = 0; i < 8; i++) {
                KT_P4(i, 4, dA0, 2)
#pragma unroll
                for (int t = 0; t < 8; t++) lds_f4_if(cs[t], sb + OFF_CS1 + (64 * w + 8 * t + 2 * q) * 8, i == t);
                wg_wait<0>();
                mbar_arrive_n_if(sb + BAR_EMPTYA + 8 * s_, 2, l0);
                mbar_arrive_cl_if(eb + 8 * rg.slot, l2 && i < 7);
                rg.adv5();
            }
#pragma unroll 1
            for (int i = 8; i < 12; i++) {
                KT_P4(i, 3, dA0 + ((0xC0000010ull - 0x40000040ull) << 32), 256)
                wg_wait<1>();
                rg.adv5();
            }
            wg_wait<0>();
            fence_acc<64>(acc);
            TL(15, tid == 0);
            const uint32_t xch = sb + OFF_A + 2 * SLOT + (tid & 127) * 16;
            if (w) {
#pragma unroll
                for (int t = 0; t < 8; t++) {
                    sts128(xch + SLOT + t * 2048, __float_as_uint(acc[4 * t]), __float_as_uint(acc[4 * t + 1]),
                           __float_as_uint(acc[4 * t + 2]), __float_as_uint(acc[4 * t + 3]));
                }
#pragma unroll
                for (int t = 0; t < 32; t++) acc[t] = acc[32 + t];
            } else {
#pragma unroll
                for (int t = 0; t < 8; t++)
                    sts128(xch + t * 2048, __float_as_uint(acc[32 + 4 * t]), __float_as_uint(acc[33 + 4 * t]),
                           __float_as_uint(acc[34 + 4 * t]), __float_as_uint(acc[35 + 4 * t]));
            }
            bar_sync(1, 256);
            float4 o[8];
#pragma unroll
            for (int t = 0; t < 8; t++) o[t] = lds_f4(xch + (w ^ 1) * SLOT + t * 2048);
            const uint32_t tile = sb + OFF_A + w * SLOT;
#pragma unroll
            for (int t = 0; t < 8; t++) {
                hr[2 * t] = pack_bf16(fmaf(acc[4 * t] + o[t].x, cs[t].y, bf_lo(hr[2 * t])), fmaf(acc[4 * t + 1] + o[t].y, cs[t].w, bf_hi(hr[2 * t])));
                hr[2 * t + 1] = pack_bf16(fmaf(acc[4 * t + 2] + o[t].z, cs[t].y, bf_lo(hr[2 * t + 1])), fmaf(acc[4 * t + 3] + o[t].w, cs[t].w, bf_hi(hr[2 * t + 1])));
            }
#pragma unroll
            for (int tp = 0; tp < 4; tp++) stsm4t(tile + blk + tp * 2048, hr[4 * tp], hr[4 * tp + 1], hr[4 * tp + 2], hr[4 * tp + 3]);
            fence_async_smem();
            bar_sync(2 + w, 128);
            if ((tid & 127) == 0) {
                tma_store2d(&P.tout, tile, 64 * j, 128 * m + 64 * w);
                asm volatile("cp.async.bulk.wait_group.read 0;" ::: "memory");
            }
            if (tid == 0 && role == 0) g_epoch = epoch + 1;
            TL(16, tid == 0); TLG(1, tid == 0);
        }
    }
}

typedef CUresult (*EncodeFn)(CUtensorMap*, CUtensorMapDataType, cuuint32_t, void*, const cuuint64_t*, const cuuint64_t*,
                             const cuuint32_t*, const cuuint32_t*, CUtensorMapInterleave, CUtensorMapSwizzle,
                             CUtensorMapL2promotion, CUtensorMapFloatOOBfill);

static void make_map2d(EncodeFn enc, CUtensorMap* tm, const void* base, uint64_t cols, uint64_t rows, uint64_t pitch_elems,
                       uint32_t box_rows) {
    cuuint64_t gd[2] = {cols, rows};
    cuuint64_t gs[1] = {pitch_elems * 2};
    cuuint32_t bd[2] = {64, box_rows};
    cuuint32_t es[2] = {1, 1};
    enc(tm, CU_TENSOR_MAP_DATA_TYPE_BFLOAT16, 2, const_cast<void*>(base), gd, gs, bd, es, CU_TENSOR_MAP_INTERLEAVE_NONE,
        CU_TENSOR_MAP_SWIZZLE_128B, CU_TENSOR_MAP_L2_PROMOTION_L2_256B, CU_TENSOR_MAP_FLOAT_OOB_FILL_NONE);
}

}

extern "C" void kernel_launch(void* const* d_in, const int* in_sizes, int n_in, void* d_out, int out_size) {
    using namespace hk;
    (void)in_sizes; (void)n_in; (void)out_size;
    static EncodeFn enc = nullptr;
    if (!enc) {
        void* fn = nullptr;
        cudaDriverEntryPointQueryResult qr;
        cudaGetDriverEntryPoint("cuTensorMapEncodeTiled", &fn, cudaEnableDefault, &qr);
        enc = (EncodeFn)fn;
        cudaFuncSetAttribute(fused_kernel, cudaFuncAttributeMaxDynamicSharedMemorySize, SMEM_BYTES);
    }
    Params P;
    const __nv_bfloat16* x = (const __nv_bfloat16*)d_in[0];
    P.x = x;
    P.wqkv = (const __nv_bfloat16*)d_in[1];
    P.wphi = (const __nv_bfloat16*)d_in[2];
    P.wo = (const __nv_bfloat16*)d_in[3];
    P.wg = (const __nv_bfloat16*)d_in[5];
    P.wu = (const __nv_bfloat16*)d_in[6];
    P.wd = (const __nv_bfloat16*)d_in[7];
    P.out = (__nv_bfloat16*)d_out;
    P.zero = 0;
    make_map2d(enc, &P.tx, x, DM, SEQ, DM, 128);
    make_map2d(enc, &P.twq, P.wqkv, 3 * DM, DM, 3 * DM, 64);
    make_map2d(enc, &P.two, P.wo, DM, DM, DM, 64);
    make_map2d(enc, &P.twg, P.wg, FF, DM, FF, 64);
    make_map2d(enc, &P.twu, P.wu, FF, DM, FF, 64);
    make_map2d(enc, &P.twd, P.wd, DM, FF, DM, 64);
    make_map2d(enc, &P.twd48, P.wd, DM, FF, DM, 48);
    make_map2d(enc, &P.tout, d_out, DM, SEQ, DM, 64);
    fused_kernel<<<NCTA, NTHREADS, SMEM_BYTES>>>(P);
}
```
